```python
import torch

def _softmax(x, axis=-1):
    return torch.softmax(x, dim=axis)

def _gelu(x):
    return torch.nn.functional.gelu(x, approximate='tanh')

def _silu(x):
    return torch.nn.functional.silu(x)

def _sigmoid(x):
    return torch.sigmoid(x)

def _layernorm(x, axis=-1, eps=1e-05):
    m = x.mean(dim=axis, keepdim=True)
    v = x.var(dim=axis, keepdim=True, unbiased=False)
    return (x - m) / torch.sqrt(v + eps)

def _scatter_add(tgt, idx, src, axis=0):
    return tgt.clone().index_add_(axis, idx, src)

def _segment_sum(src, seg, n):
    out = torch.zeros((n,) + src.shape[1:], dtype=src.dtype)
    return out.index_add_(0, seg, src)

def _pad(x, pw):
    flat = tuple((v for pair in reversed(pw) for v in pair))
    return torch.nn.functional.pad(x, flat)
kernel_name = 'adaLN_cond__sliding_local_dilated__glu_gated_swiglu__prompt'

def setup_inputs():

    _w = lambda a: (lambda t: t.to(torch.bfloat16) if t.is_floating_point() else t)(torch.as_tensor(a))

    def _A_setup():
        B, S, D = (1, 2048, 1024)
        return {'x': _w((lambda *s: torch.randn(*s, dtype=torch.bfloat16) * 0.05)(B, S, D)), 'wqkv': _w((lambda *s: torch.randn(*s, dtype=torch.bfloat16) * 0.05)(D, 3 * D)), 'wo': _w((lambda *s: torch.randn(*s, dtype=torch.bfloat16) * 0.05)(D, D))}
    _A_in = _A_setup()

    def _B_setup():
        B, S, D, F = (1, 2048, 1024, 3584)
        return {'x': _w((lambda *s: torch.randn(*s, dtype=torch.bfloat16) * 0.05)(B, S, D)), 'w1': _w((lambda *s: torch.randn(*s, dtype=torch.bfloat16) * 0.8)(D, F) * (2.0 / D) ** 0.5), 'w3': _w((lambda *s: torch.randn(*s, dtype=torch.bfloat16) * 0.8)(D, F) * (2.0 / D) ** 0.5), 'w2': _w((lambda *s: torch.randn(*s, dtype=torch.bfloat16) * 0.8)(F, D) * (2.0 / F) ** 0.5)}
    _B_in = _B_setup()
    return {'A_x': _A_in['x'], 'A_wqkv': _A_in['wqkv'], 'A_wo': _A_in['wo'], 'B_x': _B_in['x'], 'B_w1': _B_in['w1'], 'B_w3': _B_in['w3'], 'B_w2': _B_in['w2'], 'c': _w((lambda *s: torch.randn(*s, dtype=torch.bfloat16) * 0.1)(1, 1024) * 8.0), 'w_mod': _w((lambda *s: torch.randn(*s, dtype=torch.bfloat16) * 0.1)(1024, 6 * 1024) * 1024 ** (-0.5) * 8.0)}

def reference(A_x, A_wqkv, A_wo, B_x, B_w1, B_w3, B_w2, c, w_mod):

    def _A_ref(x, wqkv, wo):
        B, S, D = x.shape
        H = 32
        Dh = D // H
        W, dil = (8, 2)
        qkv = (lambda x, *d: x.permute(*d))((x @ wqkv).reshape(B, S, 3, H, Dh), 2, 0, 3, 1, 4)
        q, k, v = (qkv[0], qkv[1], qkv[2])
        scale = Dh ** (-0.5)
        pos = torch.arange(S)
        off = torch.arange(W) * dil
        idx = pos[:, None] - off[None, :]
        mask = idx >= 0
        idx_c = torch.where(mask, idx, 0).reshape(-1)
        kg = k[:, :, idx_c, :].reshape(B, H, S, W, Dh)
        vg = v[:, :, idx_c, :].reshape(B, H, S, W, Dh)
        logits = torch.einsum('bhsd,bhswd->bhsw', q, kg) * scale
        logits = torch.where(mask[None, None, :, :], logits, -1000000000.0)
        attn = _softmax(logits, axis=-1)
        o = torch.einsum('bhsw,bhswd->bhsd', attn, vg)
        return (lambda x, *d: x.permute(*d))(o, 0, 2, 1, 3).reshape(B, S, D) @ wo

    def _B_ref(x, w1, w3, w2):
        gate = torch.einsum('bsd,df->bsf', x, w1)
        up = torch.einsum('bsd,df->bsf', x, w3)
        h = _silu(gate) * up
        out = torch.einsum('bsf,fd->bsd', h, w2)
        return out
    x = A_x
    mod = (_silu(c) @ w_mod).reshape(c.shape[0], 6, 1, -1)
    sa, ca, ga, sb, cb, gb = (mod[:, 0].clone(), mod[:, 1].clone(), mod[:, 2].clone(), mod[:, 3].clone(), mod[:, 4].clone(), mod[:, 5].clone())
    h = _layernorm(x, axis=-1) * (1 + ca) + sa
    x = x + ga * _A_ref(h, A_wqkv, A_wo)
    h = _layernorm(x, axis=-1) * (1 + cb) + sb
    x = x + gb * _B_ref(h, B_w1, B_w3, B_w2)
    return x
```

```cpp
#include <cuda_runtime.h>
#include <cuda_bf16.h>
#include <cuda.h>
#include <stdint.h>

typedef __nv_bfloat16 bf16;

namespace {

constexpr int S_ = 2048, D_ = 1024, F_ = 3584;
constexpr int BLK = 16384;
constexpr int HALF = 8192;
constexpr int RING = 196608;
constexpr int STG = RING;
constexpr int MISC = RING + 2 * BLK;
constexpr int SMEM_BYTES = MISC + 3072;
constexpr int B_FULL4 = 0, B_EMPTY4 = 32, B_FULL6 = 64, B_EMPTY6 = 112, B_RDY = 160, B_FREE = 176, B_X = 192, B_MOD = 208;
constexpr int MODV = 256;
constexpr int RED_OFF = 40960;
constexpr int U_H1 = 0, U_O = 8, U_H2 = 24, U_HH = 32;

struct Maps { CUtensorMap x, out, wqkv, wo, w1, w3, w1s, w3s, w2; };

__device__ uint4 g_h[16 * 16 * 1024];
__device__ uint4 g_o[16 * 16 * 1024];
__device__ uint4 g_hh[16 * 56 * 1024];
__device__ uint4 g_x1[128 * 8 * 256];
__device__ uint2 g_modp[8 * 6 * 4 * 128];
__device__ uint4 g_stat[2 * 16 * 8 * 128];
__device__ uint4 g_halo[16 * 8 * 2 * 2 * 256];
__device__ uint32_t g_flag[16 * 2 * 64];
__device__ uint32_t g_epoch[128];
#define TR(i)

__device__ __forceinline__ uint32_t smem_u32(const void* p) { return (uint32_t)__cvta_generic_to_shared(p); }
__device__ __forceinline__ void mbar_init(uint32_t bar, uint32_t cnt) { asm volatile("mbarrier.init.shared::cta.b64 [%0], %1;" :: "r"(bar), "r"(cnt) : "memory"); }
__device__ __forceinline__ void mbar_expect_tx(uint32_t bar, uint32_t bytes) { asm volatile("mbarrier.arrive.expect_tx.shared::cta.b64 _, [%0], %1;" :: "r"(bar), "r"(bytes) : "memory"); }
__device__ __forceinline__ void mbar_arrive(uint32_t bar) { asm volatile("mbarrier.arrive.shared::cta.b64 _, [%0];" :: "r"(bar) : "memory"); }
__device__ __forceinline__ void mbar_arrive_cl(uint32_t cl_addr) { asm volatile("mbarrier.arrive.shared::cluster.b64 _, [%0];" :: "r"(cl_addr) : "memory"); }
__device__ __forceinline__ uint32_t mapa(uint32_t addr, uint32_t cta) { uint32_t r; asm("mapa.shared::cluster.u32 %0, %1, %2;" : "=r"(r) : "r"(addr), "r"(cta)); return r; }
__device__ __forceinline__ bool mbar_try(uint32_t bar, uint32_t parity) {
  uint32_t ok;
  asm volatile("{\n.reg .pred p;\nmbarrier.try_wait.parity.shared::cta.b64 p, [%1], %2;\nselp.u32 %0, 1, 0, p;\n}" : "=r"(ok) : "r"(bar), "r"(parity) : "memory");
  return ok;
}
__device__ __forceinline__ void mbar_wait(uint32_t bar, uint32_t parity) {
  uint32_t n = 0;
  while (!mbar_try(bar, parity)) { if (++n > (1u << 22)) __trap(); }
}
__device__ __forceinline__ void tma_3d(uint32_t dst, const CUtensorMap* m, uint32_t bar, int c0, int c1, int c2) {
  asm volatile("cp.async.bulk.tensor.3d.shared::cluster.global.mbarrier::complete_tx::bytes [%0], [%1, {%3, %4, %5}], [%2];" :: "r"(dst), "l"(m), "r"(bar), "r"(c0), "r"(c1), "r"(c2) : "memory");
}
__device__ __forceinline__ void tma_store_3d(const CUtensorMap* m, uint32_t src, int c0, int c1, int c2) {
  asm volatile("cp.async.bulk.tensor.3d.global.shared::cta.bulk_group [%0, {%2, %3, %4}], [%1];" :: "l"(m), "r"(src), "r"(c0), "r"(c1), "r"(c2) : "memory");
}
__device__ __forceinline__ void bulk_ld(uint32_t dst, const void* src, uint32_t bytes, uint32_t bar) {
  asm volatile("cp.async.bulk.shared::cluster.global.mbarrier::complete_tx::bytes [%0], [%1], %2, [%3];" :: "r"(dst), "l"(src), "r"(bytes), "r"(bar) : "memory");
}
__device__ __forceinline__ void bulk_ld_mc(uint32_t dst, const void* src, uint32_t bytes, uint32_t bar) {
  asm volatile("cp.async.bulk.shared::cluster.global.mbarrier::complete_tx::bytes.multicast::cluster [%0], [%1], %2, [%3], %4;" :: "r"(dst), "l"(src), "r"(bytes), "r"(bar), "h"((uint16_t)3) : "memory");
}
__device__ __forceinline__ void bulk_st(void* dst, uint32_t src, uint32_t bytes) {
  asm volatile("cp.async.bulk.global.shared::cta.bulk_group [%0], [%1], %2;" :: "l"(dst), "r"(src), "r"(bytes) : "memory");
}
__device__ __forceinline__ void bulk_commit() { asm volatile("cp.async.bulk.commit_group;" ::: "memory"); }
__device__ __forceinline__ void bulk_wait_read() { asm volatile("cp.async.bulk.wait_group.read 0;" ::: "memory"); }
__device__ __forceinline__ void bulk_wait_all() { asm volatile("cp.async.bulk.wait_group 0;" ::: "memory"); }
__device__ __forceinline__ void fence_async() { asm volatile("fence.proxy.async;" ::: "memory"); }
__device__ __forceinline__ void fence_async_smem() { asm volatile("fence.proxy.async.shared::cta;" ::: "memory"); }
__device__ __forceinline__ void wg_arrive() { asm volatile("wgmma.fence.sync.aligned;" ::: "memory"); }
__device__ __forceinline__ void wg_commit() { asm volatile("wgmma.commit_group.sync.aligned;" ::: "memory"); }
template <int N> __device__ __forceinline__ void wg_wait() { asm volatile("wgmma.wait_group.sync.aligned %0;" :: "n"(N) : "memory"); }
__device__ __forceinline__ void cl_arrive() { asm volatile("barrier.cluster.arrive.release.aligned;" ::: "memory"); }
__device__ __forceinline__ void cl_arrive_relaxed() { asm volatile("barrier.cluster.arrive.relaxed.aligned;" ::: "memory"); }
__device__ __forceinline__ void cl_wait() { asm volatile("barrier.cluster.wait.acquire.aligned;" ::: "memory"); }
__device__ __forceinline__ void named_bar(int id, int n) { asm volatile("bar.sync %0, %1;" :: "r"(id), "r"(n) : "memory"); }
__device__ __forceinline__ uint32_t pack2(float lo, float hi) { uint32_t r; asm("cvt.rn.bf16x2.f32 %0, %1, %2;" : "=r"(r) : "f"(hi), "f"(lo)); return r; }
__device__ __forceinline__ float bf_lo(uint32_t w) { return __uint_as_float(w << 16); }
__device__ __forceinline__ float bf_hi(uint32_t w) { return __uint_as_float(w & 0xffff0000u); }
__device__ __forceinline__ float bf_round(float v) { return __bfloat162float(__float2bfloat16_rn(v)); }
__device__ __forceinline__ void stsm4(uint32_t addr, uint32_t a, uint32_t b, uint32_t c, uint32_t d) {
  asm volatile("stmatrix.sync.aligned.m8n8.x4.shared.b16 [%0], {%1, %2, %3, %4};" :: "r"(addr), "r"(a), "r"(b), "r"(c), "r"(d) : "memory");
}
__device__ __forceinline__ void ldsm4(uint32_t addr, uint32_t& a, uint32_t& b, uint32_t& c, uint32_t& d) {
  asm volatile("ldmatrix.sync.aligned.m8n8.x4.shared.b16 {%0, %1, %2, %3}, [%4];" : "=r"(a), "=r"(b), "=r"(c), "=r"(d) : "r"(addr) : "memory");
}
__device__ __forceinline__ uint32_t movm(uint32_t a) { uint32_t r; asm volatile("movmatrix.sync.aligned.m8n8.trans.b16 %0, %1;" : "=r"(r) : "r"(a)); return r; }
__device__ __forceinline__ void mma16(float (&d)[4], uint32_t a0, uint32_t a1, uint32_t a2, uint32_t a3, uint32_t b0, uint32_t b1) {
  asm volatile("mma.sync.aligned.m16n8k16.row.col.f32.bf16.bf16.f32 {%0,%1,%2,%3}, {%4,%5,%6,%7}, {%8,%9}, {%0,%1,%2,%3};"
               : "+f"(d[0]), "+f"(d[1]), "+f"(d[2]), "+f"(d[3]) : "r"(a0), "r"(a1), "r"(a2), "r"(a3), "r"(b0), "r"(b1));
}
__device__ __forceinline__ void mma8(float (&d)[4], uint32_t a0, uint32_t a1, uint32_t b0) {
  asm volatile("mma.sync.aligned.m16n8k8.row.col.f32.bf16.bf16.f32 {%0,%1,%2,%3}, {%4,%5}, {%6}, {%0,%1,%2,%3};"
               : "+f"(d[0]), "+f"(d[1]), "+f"(d[2]), "+f"(d[3]) : "r"(a0), "r"(a1), "r"(b0));
}
__device__ __forceinline__ uint4 lds128(uint32_t a) { uint4 v; asm volatile("ld.shared.v4.u32 {%0,%1,%2,%3}, [%4];" : "=r"(v.x), "=r"(v.y), "=r"(v.z), "=r"(v.w) : "r"(a) : "memory"); return v; }
__device__ __forceinline__ void sts128(uint32_t a, uint32_t x, uint32_t y, uint32_t z, uint32_t w) { asm volatile("st.shared.v4.u32 [%0], {%1,%2,%3,%4};" :: "r"(a), "r"(x), "r"(y), "r"(z), "r"(w) : "memory"); }
__device__ __forceinline__ float lds32f(uint32_t a) { float v; asm volatile("ld.shared.f32 %0, [%1];" : "=f"(v) : "r"(a) : "memory"); return v; }
__device__ __forceinline__ void sts16(uint32_t a, bf16 v) { asm volatile("st.shared.b16 [%0], %1;" :: "r"(a), "h"(__bfloat16_as_ushort(v)) : "memory"); }
__device__ __forceinline__ uint4 ldg_nc(const void* p) { uint4 v; asm volatile("ld.global.nc.L1::no_allocate.v4.u32 {%0,%1,%2,%3}, [%4];" : "=r"(v.x), "=r"(v.y), "=r"(v.z), "=r"(v.w) : "l"(p)); return v; }
__device__ __forceinline__ uint4 ld_rlx4(const uint4* p) {
  unsigned long long a, b; asm volatile("ld.relaxed.gpu.global.v2.b64 {%0,%1}, [%2];" : "=l"(a), "=l"(b) : "l"(p) : "memory");
  return make_uint4((uint32_t)a, (uint32_t)(a >> 32), (uint32_t)b, (uint32_t)(b >> 32));
}
__device__ __forceinline__ uint2 ld_rlx2(const uint2* p) { unsigned long long a; asm volatile("ld.relaxed.gpu.global.b64 %0, [%1];" : "=l"(a) : "l"(p) : "memory"); return make_uint2((uint32_t)a, (uint32_t)(a >> 32)); }
__device__ __forceinline__ void st_rlx4(uint4* p, uint32_t x, uint32_t y, uint32_t z, uint32_t w) {
  asm volatile("st.relaxed.gpu.global.v2.b64 [%0], {%1,%2};" :: "l"(p), "l"((unsigned long long)x | ((unsigned long long)y << 32)), "l"((unsigned long long)z | ((unsigned long long)w << 32)) : "memory");
}
__device__ __forceinline__ void st_rlx2(uint2* p, uint32_t x, uint32_t y) { asm volatile("st.relaxed.gpu.global.b64 [%0], %1;" :: "l"(p), "l"((unsigned long long)x | ((unsigned long long)y << 32)) : "memory"); }
__device__ __forceinline__ void st_release(uint32_t* p, uint32_t v) { asm volatile("st.release.gpu.global.u32 [%0], %1;" :: "l"(p), "r"(v) : "memory"); }
__device__ __forceinline__ uint32_t ld_acquire(const uint32_t* p) { uint32_t v; asm volatile("ld.acquire.gpu.global.u32 %0, [%1];" : "=r"(v) : "l"(p) : "memory"); return v; }
__device__ __forceinline__ float ex2(float x) { float r; asm("ex2.approx.ftz.f32 %0, %1;" : "=f"(r) : "f"(x)); return r; }
__device__ __forceinline__ float tanh_fast(float x) { float r; asm("tanh.approx.f32 %0, %1;" : "=f"(r) : "f"(x)); return r; }
#define SPIN_GUARD(n) if (++(n) > (1u << 24)) __trap()

__device__ __forceinline__ void wgmma_n128(float (&d)[64], uint64_t da, uint64_t db) {
  asm volatile("wgmma.mma_async.sync.aligned.m64n128k16.f32.bf16.bf16 "
    "{%0, %1, %2, %3, %4, %5, %6, %7, %8, %9, %10, %11, %12, %13, %14, %15, %16, %17, %18, %19, %20, %21, %22, %23, %24, %25, %26, %27, %28, %29, %30, %31, %32, %33, %34, %35, %36, %37, %38, %39, %40, %41, %42, %43, %44, %45, %46, %47, %48, %49, %50, %51, %52, %53, %54, %55, %56, %57, %58, %59, %60, %61, %62, %63}, "
    "%64, %65, 1, 1, 1, 0, 1;\n"
    : "+f"(d[0]), "+f"(d[1]), "+f"(d[2]), "+f"(d[3]), "+f"(d[4]), "+f"(d[5]), "+f"(d[6]), "+f"(d[7]), "+f"(d[8]), "+f"(d[9]), "+f"(d[10]), "+f"(d[11]), "+f"(d[12]), "+f"(d[13]), "+f"(d[14]), "+f"(d[15]), "+f"(d[16]), "+f"(d[17]), "+f"(d[18]), "+f"(d[19]), "+f"(d[20]), "+f"(d[21]), "+f"(d[22]), "+f"(d[23]), "+f"(d[24]), "+f"(d[25]), "+f"(d[26]), "+f"(d[27]), "+f"(d[28]), "+f"(d[29]), "+f"(d[30]), "+f"(d[31]), "+f"(d[32]), "+f"(d[33]), "+f"(d[34]), "+f"(d[35]), "+f"(d[36]), "+f"(d[37]), "+f"(d[38]), "+f"(d[39]), "+f"(d[40]), "+f"(d[41]), "+f"(d[42]), "+f"(d[43]), "+f"(d[44]), "+f"(d[45]), "+f"(d[46]), "+f"(d[47]), "+f"(d[48]), "+f"(d[49]), "+f"(d[50]), "+f"(d[51]), "+f"(d[52]), "+f"(d[53]), "+f"(d[54]), "+f"(d[55]), "+f"(d[56]), "+f"(d[57]), "+f"(d[58]), "+f"(d[59]), "+f"(d[60]), "+f"(d[61]), "+f"(d[62]), "+f"(d[63])
    : "l"(da), "l"(db));
}
__device__ __forceinline__ void wgmma_n128_first(float (&d)[64], uint64_t da, uint64_t db) {
  asm volatile("wgmma.mma_async.sync.aligned.m64n128k16.f32.bf16.bf16 "
    "{%0, %1, %2, %3, %4, %5, %6, %7, %8, %9, %10, %11, %12, %13, %14, %15, %16, %17, %18, %19, %20, %21, %22, %23, %24, %25, %26, %27, %28, %29, %30, %31, %32, %33, %34, %35, %36, %37, %38, %39, %40, %41, %42, %43, %44, %45, %46, %47, %48, %49, %50, %51, %52, %53, %54, %55, %56, %57, %58, %59, %60, %61, %62, %63}, "
    "%64, %65, 0, 1, 1, 0, 1;\n"
    : "=f"(d[0]), "=f"(d[1]), "=f"(d[2]), "=f"(d[3]), "=f"(d[4]), "=f"(d[5]), "=f"(d[6]), "=f"(d[7]), "=f"(d[8]), "=f"(d[9]), "=f"(d[10]), "=f"(d[11]), "=f"(d[12]), "=f"(d[13]), "=f"(d[14]), "=f"(d[15]), "=f"(d[16]), "=f"(d[17]), "=f"(d[18]), "=f"(d[19]), "=f"(d[20]), "=f"(d[21]), "=f"(d[22]), "=f"(d[23]), "=f"(d[24]), "=f"(d[25]), "=f"(d[26]), "=f"(d[27]), "=f"(d[28]), "=f"(d[29]), "=f"(d[30]), "=f"(d[31]), "=f"(d[32]), "=f"(d[33]), "=f"(d[34]), "=f"(d[35]), "=f"(d[36]), "=f"(d[37]), "=f"(d[38]), "=f"(d[39]), "=f"(d[40]), "=f"(d[41]), "=f"(d[42]), "=f"(d[43]), "=f"(d[44]), "=f"(d[45]), "=f"(d[46]), "=f"(d[47]), "=f"(d[48]), "=f"(d[49]), "=f"(d[50]), "=f"(d[51]), "=f"(d[52]), "=f"(d[53]), "=f"(d[54]), "=f"(d[55]), "=f"(d[56]), "=f"(d[57]), "=f"(d[58]), "=f"(d[59]), "=f"(d[60]), "=f"(d[61]), "=f"(d[62]), "=f"(d[63])
    : "l"(da), "l"(db));
}
__device__ __forceinline__ void wgmma_n192(float (&d)[96], uint64_t da, uint64_t db) {
  asm volatile("wgmma.mma_async.sync.aligned.m64n192k16.f32.bf16.bf16 "
    "{%0, %1, %2, %3, %4, %5, %6, %7, %8, %9, %10, %11, %12, %13, %14, %15, %16, %17, %18, %19, %20, %21, %22, %23, %24, %25, %26, %27, %28, %29, %30, %31, %32, %33, %34, %35, %36, %37, %38, %39, %40, %41, %42, %43, %44, %45, %46, %47, %48, %49, %50, %51, %52, %53, %54, %55, %56, %57, %58, %59, %60, %61, %62, %63, %64, %65, %66, %67, %68, %69, %70, %71, %72, %73, %74, %75, %76, %77, %78, %79, %80, %81, %82, %83, %84, %85, %86, %87, %88, %89, %90, %91, %92, %93, %94, %95}, "
    "%96, %97, 1, 1, 1, 0, 1;\n"
    : "+f"(d[0]), "+f"(d[1]), "+f"(d[2]), "+f"(d[3]), "+f"(d[4]), "+f"(d[5]), "+f"(d[6]), "+f"(d[7]), "+f"(d[8]), "+f"(d[9]), "+f"(d[10]), "+f"(d[11]), "+f"(d[12]), "+f"(d[13]), "+f"(d[14]), "+f"(d[15]), "+f"(d[16]), "+f"(d[17]), "+f"(d[18]), "+f"(d[19]), "+f"(d[20]), "+f"(d[21]), "+f"(d[22]), "+f"(d[23]), "+f"(d[24]), "+f"(d[25]), "+f"(d[26]), "+f"(d[27]), "+f"(d[28]), "+f"(d[29]), "+f"(d[30]), "+f"(d[31]), "+f"(d[32]), "+f"(d[33]), "+f"(d[34]), "+f"(d[35]), "+f"(d[36]), "+f"(d[37]), "+f"(d[38]), "+f"(d[39]), "+f"(d[40]), "+f"(d[41]), "+f"(d[42]), "+f"(d[43]), "+f"(d[44]), "+f"(d[45]), "+f"(d[46]), "+f"(d[47]), "+f"(d[48]), "+f"(d[49]), "+f"(d[50]), "+f"(d[51]), "+f"(d[52]), "+f"(d[53]), "+f"(d[54]), "+f"(d[55]), "+f"(d[56]), "+f"(d[57]), "+f"(d[58]), "+f"(d[59]), "+f"(d[60]), "+f"(d[61]), "+f"(d[62]), "+f"(d[63]), "+f"(d[64]), "+f"(d[65]), "+f"(d[66]), "+f"(d[67]), "+f"(d[68]), "+f"(d[69]), "+f"(d[70]), "+f"(d[71]), "+f"(d[72]), "+f"(d[73]), "+f"(d[74]), "+f"(d[75]), "+f"(d[76]), "+f"(d[77]), "+f"(d[78]), "+f"(d[79]), "+f"(d[80]), "+f"(d[81]), "+f"(d[82]), "+f"(d[83]), "+f"(d[84]), "+f"(d[85]), "+f"(d[86]), "+f"(d[87]), "+f"(d[88]), "+f"(d[89]), "+f"(d[90]), "+f"(d[91]), "+f"(d[92]), "+f"(d[93]), "+f"(d[94]), "+f"(d[95])
    : "l"(da), "l"(db));
}
__device__ __forceinline__ void wgmma_n192_first(float (&d)[96], uint64_t da, uint64_t db) {
  asm volatile("wgmma.mma_async.sync.aligned.m64n192k16.f32.bf16.bf16 "
    "{%0, %1, %2, %3, %4, %5, %6, %7, %8, %9, %10, %11, %12, %13, %14, %15, %16, %17, %18, %19, %20, %21, %22, %23, %24, %25, %26, %27, %28, %29, %30, %31, %32, %33, %34, %35, %36, %37, %38, %39, %40, %41, %42, %43, %44, %45, %46, %47, %48, %49, %50, %51, %52, %53, %54, %55, %56, %57, %58, %59, %60, %61, %62, %63, %64, %65, %66, %67, %68, %69, %70, %71, %72, %73, %74, %75, %76, %77, %78, %79, %80, %81, %82, %83, %84, %85, %86, %87, %88, %89, %90, %91, %92, %93, %94, %95}, "
    "%96, %97, 0, 1, 1, 0, 1;\n"
    : "=f"(d[0]), "=f"(d[1]), "=f"(d[2]), "=f"(d[3]), "=f"(d[4]), "=f"(d[5]), "=f"(d[6]), "=f"(d[7]), "=f"(d[8]), "=f"(d[9]), "=f"(d[10]), "=f"(d[11]), "=f"(d[12]), "=f"(d[13]), "=f"(d[14]), "=f"(d[15]), "=f"(d[16]), "=f"(d[17]), "=f"(d[18]), "=f"(d[19]), "=f"(d[20]), "=f"(d[21]), "=f"(d[22]), "=f"(d[23]), "=f"(d[24]), "=f"(d[25]), "=f"(d[26]), "=f"(d[27]), "=f"(d[28]), "=f"(d[29]), "=f"(d[30]), "=f"(d[31]), "=f"(d[32]), "=f"(d[33]), "=f"(d[34]), "=f"(d[35]), "=f"(d[36]), "=f"(d[37]), "=f"(d[38]), "=f"(d[39]), "=f"(d[40]), "=f"(d[41]), "=f"(d[42]), "=f"(d[43]), "=f"(d[44]), "=f"(d[45]), "=f"(d[46]), "=f"(d[47]), "=f"(d[48]), "=f"(d[49]), "=f"(d[50]), "=f"(d[51]), "=f"(d[52]), "=f"(d[53]), "=f"(d[54]), "=f"(d[55]), "=f"(d[56]), "=f"(d[57]), "=f"(d[58]), "=f"(d[59]), "=f"(d[60]), "=f"(d[61]), "=f"(d[62]), "=f"(d[63]), "=f"(d[64]), "=f"(d[65]), "=f"(d[66]), "=f"(d[67]), "=f"(d[68]), "=f"(d[69]), "=f"(d[70]), "=f"(d[71]), "=f"(d[72]), "=f"(d[73]), "=f"(d[74]), "=f"(d[75]), "=f"(d[76]), "=f"(d[77]), "=f"(d[78]), "=f"(d[79]), "=f"(d[80]), "=f"(d[81]), "=f"(d[82]), "=f"(d[83]), "=f"(d[84]), "=f"(d[85]), "=f"(d[86]), "=f"(d[87]), "=f"(d[88]), "=f"(d[89]), "=f"(d[90]), "=f"(d[91]), "=f"(d[92]), "=f"(d[93]), "=f"(d[94]), "=f"(d[95])
    : "l"(da), "l"(db));
}
__device__ __forceinline__ void wgmma_n256(float (&d)[128], uint64_t da, uint64_t db) {
  asm volatile("wgmma.mma_async.sync.aligned.m64n256k16.f32.bf16.bf16 "
    "{%0, %1, %2, %3, %4, %5, %6, %7, %8, %9, %10, %11, %12, %13, %14, %15, %16, %17, %18, %19, %20, %21, %22, %23, %24, %25, %26, %27, %28, %29, %30, %31, %32, %33, %34, %35, %36, %37, %38, %39, %40, %41, %42, %43, %44, %45, %46, %47, %48, %49, %50, %51, %52, %53, %54, %55, %56, %57, %58, %59, %60, %61, %62, %63, %64, %65, %66, %67, %68, %69, %70, %71, %72, %73, %74, %75, %76, %77, %78, %79, %80, %81, %82, %83, %84, %85, %86, %87, %88, %89, %90, %91, %92, %93, %94, %95, %96, %97, %98, %99, %100, %101, %102, %103, %104, %105, %106, %107, %108, %109, %110, %111, %112, %113, %114, %115, %116, %117, %118, %119, %120, %121, %122, %123, %124, %125, %126, %127}, "
    "%128, %129, 1, 1, 1, 0, 1;\n"
    : "+f"(d[0]), "+f"(d[1]), "+f"(d[2]), "+f"(d[3]), "+f"(d[4]), "+f"(d[5]), "+f"(d[6]), "+f"(d[7]), "+f"(d[8]), "+f"(d[9]), "+f"(d[10]), "+f"(d[11]), "+f"(d[12]), "+f"(d[13]), "+f"(d[14]), "+f"(d[15]), "+f"(d[16]), "+f"(d[17]), "+f"(d[18]), "+f"(d[19]), "+f"(d[20]), "+f"(d[21]), "+f"(d[22]), "+f"(d[23]), "+f"(d[24]), "+f"(d[25]), "+f"(d[26]), "+f"(d[27]), "+f"(d[28]), "+f"(d[29]), "+f"(d[30]), "+f"(d[31]), "+f"(d[32]), "+f"(d[33]), "+f"(d[34]), "+f"(d[35]), "+f"(d[36]), "+f"(d[37]), "+f"(d[38]), "+f"(d[39]), "+f"(d[40]), "+f"(d[41]), "+f"(d[42]), "+f"(d[43]), "+f"(d[44]), "+f"(d[45]), "+f"(d[46]), "+f"(d[47]), "+f"(d[48]), "+f"(d[49]), "+f"(d[50]), "+f"(d[51]), "+f"(d[52]), "+f"(d[53]), "+f"(d[54]), "+f"(d[55]), "+f"(d[56]), "+f"(d[57]), "+f"(d[58]), "+f"(d[59]), "+f"(d[60]), "+f"(d[61]), "+f"(d[62]), "+f"(d[63]), "+f"(d[64]), "+f"(d[65]), "+f"(d[66]), "+f"(d[67]), "+f"(d[68]), "+f"(d[69]), "+f"(d[70]), "+f"(d[71]), "+f"(d[72]), "+f"(d[73]), "+f"(d[74]), "+f"(d[75]), "+f"(d[76]), "+f"(d[77]), "+f"(d[78]), "+f"(d[79]), "+f"(d[80]), "+f"(d[81]), "+f"(d[82]), "+f"(d[83]), "+f"(d[84]), "+f"(d[85]), "+f"(d[86]), "+f"(d[87]), "+f"(d[88]), "+f"(d[89]), "+f"(d[90]), "+f"(d[91]), "+f"(d[92]), "+f"(d[93]), "+f"(d[94]), "+f"(d[95]), "+f"(d[96]), "+f"(d[97]), "+f"(d[98]), "+f"(d[99]), "+f"(d[100]), "+f"(d[101]), "+f"(d[102]), "+f"(d[103]), "+f"(d[104]), "+f"(d[105]), "+f"(d[106]), "+f"(d[107]), "+f"(d[108]), "+f"(d[109]), "+f"(d[110]), "+f"(d[111]), "+f"(d[112]), "+f"(d[113]), "+f"(d[114]), "+f"(d[115]), "+f"(d[116]), "+f"(d[117]), "+f"(d[118]), "+f"(d[119]), "+f"(d[120]), "+f"(d[121]), "+f"(d[122]), "+f"(d[123]), "+f"(d[124]), "+f"(d[125]), "+f"(d[126]), "+f"(d[127])
    : "l"(da), "l"(db));
}
__device__ __forceinline__ void wgmma_n256_first(float (&d)[128], uint64_t da, uint64_t db) {
  asm volatile("wgmma.mma_async.sync.aligned.m64n256k16.f32.bf16.bf16 "
    "{%0, %1, %2, %3, %4, %5, %6, %7, %8, %9, %10, %11, %12, %13, %14, %15, %16, %17, %18, %19, %20, %21, %22, %23, %24, %25, %26, %27, %28, %29, %30, %31, %32, %33, %34, %35, %36, %37, %38, %39, %40, %41, %42, %43, %44, %45, %46, %47, %48, %49, %50, %51, %52, %53, %54, %55, %56, %57, %58, %59, %60, %61, %62, %63, %64, %65, %66, %67, %68, %69, %70, %71, %72, %73, %74, %75, %76, %77, %78, %79, %80, %81, %82, %83, %84, %85, %86, %87, %88, %89, %90, %91, %92, %93, %94, %95, %96, %97, %98, %99, %100, %101, %102, %103, %104, %105, %106, %107, %108, %109, %110, %111, %112, %113, %114, %115, %116, %117, %118, %119, %120, %121, %122, %123, %124, %125, %126, %127}, "
    "%128, %129, 0, 1, 1, 0, 1;\n"
    : "=f"(d[0]), "=f"(d[1]), "=f"(d[2]), "=f"(d[3]), "=f"(d[4]), "=f"(d[5]), "=f"(d[6]), "=f"(d[7]), "=f"(d[8]), "=f"(d[9]), "=f"(d[10]), "=f"(d[11]), "=f"(d[12]), "=f"(d[13]), "=f"(d[14]), "=f"(d[15]), "=f"(d[16]), "=f"(d[17]), "=f"(d[18]), "=f"(d[19]), "=f"(d[20]), "=f"(d[21]), "=f"(d[22]), "=f"(d[23]), "=f"(d[24]), "=f"(d[25]), "=f"(d[26]), "=f"(d[27]), "=f"(d[28]), "=f"(d[29]), "=f"(d[30]), "=f"(d[31]), "=f"(d[32]), "=f"(d[33]), "=f"(d[34]), "=f"(d[35]), "=f"(d[36]), "=f"(d[37]), "=f"(d[38]), "=f"(d[39]), "=f"(d[40]), "=f"(d[41]), "=f"(d[42]), "=f"(d[43]), "=f"(d[44]), "=f"(d[45]), "=f"(d[46]), "=f"(d[47]), "=f"(d[48]), "=f"(d[49]), "=f"(d[50]), "=f"(d[51]), "=f"(d[52]), "=f"(d[53]), "=f"(d[54]), "=f"(d[55]), "=f"(d[56]), "=f"(d[57]), "=f"(d[58]), "=f"(d[59]), "=f"(d[60]), "=f"(d[61]), "=f"(d[62]), "=f"(d[63]), "=f"(d[64]), "=f"(d[65]), "=f"(d[66]), "=f"(d[67]), "=f"(d[68]), "=f"(d[69]), "=f"(d[70]), "=f"(d[71]), "=f"(d[72]), "=f"(d[73]), "=f"(d[74]), "=f"(d[75]), "=f"(d[76]), "=f"(d[77]), "=f"(d[78]), "=f"(d[79]), "=f"(d[80]), "=f"(d[81]), "=f"(d[82]), "=f"(d[83]), "=f"(d[84]), "=f"(d[85]), "=f"(d[86]), "=f"(d[87]), "=f"(d[88]), "=f"(d[89]), "=f"(d[90]), "=f"(d[91]), "=f"(d[92]), "=f"(d[93]), "=f"(d[94]), "=f"(d[95]), "=f"(d[96]), "=f"(d[97]), "=f"(d[98]), "=f"(d[99]), "=f"(d[100]), "=f"(d[101]), "=f"(d[102]), "=f"(d[103]), "=f"(d[104]), "=f"(d[105]), "=f"(d[106]), "=f"(d[107]), "=f"(d[108]), "=f"(d[109]), "=f"(d[110]), "=f"(d[111]), "=f"(d[112]), "=f"(d[113]), "=f"(d[114]), "=f"(d[115]), "=f"(d[116]), "=f"(d[117]), "=f"(d[118]), "=f"(d[119]), "=f"(d[120]), "=f"(d[121]), "=f"(d[122]), "=f"(d[123]), "=f"(d[124]), "=f"(d[125]), "=f"(d[126]), "=f"(d[127])
    : "l"(da), "l"(db));
}

template <int N> struct WG;
#define DEF_WG(N) template <> struct WG<N> { \
  static __device__ __forceinline__ void mma(float (&d)[N / 2], uint64_t a, uint64_t b) { wgmma_n##N(d, a, b); } \
  static __device__ __forceinline__ void first(float (&d)[N / 2], uint64_t a, uint64_t b) { wgmma_n##N##_first(d, a, b); } };
DEF_WG(128) DEF_WG(192) DEF_WG(256)

constexpr uint64_t DESC_A = (1ull << 62) | ((uint64_t)(1024 >> 4) << 32) | (1ull << 16);
constexpr uint64_t DESC_B = (1ull << 62) | ((uint64_t)(1024 >> 4) << 32) | ((uint64_t)(8192 >> 4) << 16);

struct Ring { int s; uint32_t ph; };

template <int NS> __device__ __forceinline__ void ring_next(Ring& r) { r.ph ^= 1u << r.s; r.s = (r.s + 1 == NS) ? 0 : r.s + 1; }

__device__ __forceinline__ int own_order(int it, int j) { return it < 2 ? 2 * j + it : it < 14 ? ((j >> 1) * 4 + 2 + it) & 15 : 2 * (j ^ 1) + it - 14; }

template <int N, int NS>
__device__ __forceinline__ void mainloop(float (&acc)[N / 2], int nkb, bool own, Ring& r, uint32_t sb, int wg, int lane, uint32_t rel_base) {
  constexpr int SLOT = RING / NS;
  const uint32_t full = sb + MISC + (NS == 4 ? B_FULL4 : B_FULL6);
  const uint32_t rel = rel_base + (NS == 4 ? B_EMPTY4 : B_EMPTY6);
  {
    uint32_t sa = (own ? sb + STG : sb + r.s * SLOT) + wg * HALF, sbb = sb + r.s * SLOT + BLK;
    uint64_t da = DESC_A | (uint64_t)((sa & 0x3FFFF) >> 4), db = DESC_B | (uint64_t)((sbb & 0x3FFFF) >> 4);
    mbar_wait(full + r.s * 8, (r.ph >> r.s) & 1);
    wg_arrive();
    WG<N>::first(acc, da, db);
#pragma unroll
    for (int k = 1; k < 4; k++) WG<N>::mma(acc, da + k * 2, db + k * 128);
    wg_commit();
  }
  int ps = r.s;
  ring_next<NS>(r);
#pragma unroll 1
  for (int it = 1; it < nkb; it++) {
    uint32_t sa = ((own && it == 1) ? sb + STG + BLK : sb + r.s * SLOT) + wg * HALF, sbb = sb + r.s * SLOT + BLK;
    uint64_t da = DESC_A | (uint64_t)((sa & 0x3FFFF) >> 4), db = DESC_B | (uint64_t)((sbb & 0x3FFFF) >> 4);
    mbar_wait(full + r.s * 8, (r.ph >> r.s) & 1);
    wg_arrive();
#pragma unroll
    for (int k = 0; k < 4; k++) WG<N>::mma(acc, da + k * 2, db + k * 128);
    wg_commit();
    wg_wait<1>();
    if (lane < 2) mbar_arrive_cl(rel + ps * 8);
    ps = r.s;
    ring_next<NS>(r);
  }
  wg_wait<0>();
  if (lane < 2) mbar_arrive_cl(rel + ps * 8);
}

__device__ __forceinline__ void ln_publish(const float (&v)[64], uint4* st, int j, int row0, int lane, uint32_t ep) {
  float s0 = 0, s1 = 0;
#pragma unroll
  for (int i = 0; i < 16; i++) { s0 += v[4 * i] + v[4 * i + 1]; s1 += v[4 * i + 2] + v[4 * i + 3]; }
  s0 += __shfl_xor_sync(~0u, s0, 1); s1 += __shfl_xor_sync(~0u, s1, 1);
  s0 += __shfl_xor_sync(~0u, s0, 2); s1 += __shfl_xor_sync(~0u, s1, 2);
  s0 *= (1.f / 128); s1 *= (1.f / 128);
  float q0 = 0, q1 = 0, q2 = 0, q3 = 0;
#pragma unroll
  for (int i = 0; i < 16; i++) {
    float a = v[4 * i] - s0, b = v[4 * i + 1] - s0, c = v[4 * i + 2] - s1, d = v[4 * i + 3] - s1;
    q0 = fmaf(a, a, q0); q1 = fmaf(b, b, q1); q2 = fmaf(c, c, q2); q3 = fmaf(d, d, q3);
  }
  q0 += q1; q2 += q3;
  q0 += __shfl_xor_sync(~0u, q0, 1); q2 += __shfl_xor_sync(~0u, q2, 1);
  q0 += __shfl_xor_sync(~0u, q0, 2); q2 += __shfl_xor_sync(~0u, q2, 2);
  int c = lane & 3;
  if (c < 2) st_rlx4(st + j * 128 + row0 + c * 8, __float_as_uint(c ? s1 : s0), ep, __float_as_uint(c ? q2 : q0), ep);
}
__device__ __forceinline__ void ln_gather(const uint4* st, int row0, int lane, uint32_t ep, float& mu0, float& r0, float& mu1, float& r1) {
  const uint4* p = st + (lane & 3) * 256 + row0;
  uint4 a, b, c, d; uint32_t n = 0;
  while (true) {
    a = ld_rlx4(p); b = ld_rlx4(p + 128); c = ld_rlx4(p + 8); d = ld_rlx4(p + 136);
    if (a.y == ep && a.w == ep && b.y == ep && b.w == ep && c.y == ep && c.w == ep && d.y == ep && d.w == ep) break;
    SPIN_GUARD(n);
  }
  __syncwarp();
  float ma = __uint_as_float(a.x), mb = __uint_as_float(b.x), mc = __uint_as_float(c.x), md = __uint_as_float(d.x);
  mu0 = ma + mb; mu1 = mc + md;
  mu0 += __shfl_xor_sync(~0u, mu0, 1); mu1 += __shfl_xor_sync(~0u, mu1, 1);
  mu0 += __shfl_xor_sync(~0u, mu0, 2); mu1 += __shfl_xor_sync(~0u, mu1, 2);
  mu0 *= 0.125f; mu1 *= 0.125f;
  ma -= mu0; mb -= mu0; mc -= mu1; md -= mu1;
  float q0 = __uint_as_float(a.z) + __uint_as_float(b.z) + 128.f * (ma * ma + mb * mb);
  float q1 = __uint_as_float(c.z) + __uint_as_float(d.z) + 128.f * (mc * mc + md * md);
  q0 += __shfl_xor_sync(~0u, q0, 1); q1 += __shfl_xor_sync(~0u, q1, 1);
  q0 += __shfl_xor_sync(~0u, q0, 2); q1 += __shfl_xor_sync(~0u, q1, 2);
  r0 = rsqrtf(q0 * (1.f / 1024) + 1e-5f); r1 = rsqrtf(q1 * (1.f / 1024) + 1e-5f);
}
__device__ __forceinline__ void load_vec(uint32_t (&w)[16], uint32_t sb, int sec, int lane) {
#pragma unroll
  for (int q = 0; q < 4; q++) { uint4 t = lds128(sb + MISC + MODV + sec * 256 + (lane & 3) * 64 + q * 16); w[4 * q] = t.x; w[4 * q + 1] = t.y; w[4 * q + 2] = t.z; w[4 * q + 3] = t.w; }
}
__device__ __forceinline__ void ln_apply(const float (&v)[64], float mu0, float r0, float mu1, float r1, uint32_t sb, int sec_shift, int sec_scale, uint32_t stg_row, int lane) {
  uint32_t sc[16], sh[16];
  load_vec(sc, sb, sec_scale, lane); load_vec(sh, sb, sec_shift, lane);
  const float n0 = -mu0 * r0, n1 = -mu1 * r1;
#pragma unroll
  for (int i = 0; i < 16; i += 2) {
    uint32_t w[4];
#pragma unroll
    for (int u = 0; u < 2; u++) {
      int q = i + u;
      float c0 = bf_lo(sc[q]), c1 = bf_hi(sc[q]), s0 = bf_lo(sh[q]), s1 = bf_hi(sh[q]);
      w[2 * u] = pack2(fmaf(fmaf(v[4 * q], r0, n0), c0, s0), fmaf(fmaf(v[4 * q + 1], r0, n0), c1, s1));
      w[2 * u + 1] = pack2(fmaf(fmaf(v[4 * q + 2], r1, n1), c0, s0), fmaf(fmaf(v[4 * q + 3], r1, n1), c1, s1));
    }
    stsm4(stg_row + (i >> 3) * BLK + ((((i & 7) + (lane >> 4)) ^ (lane & 7)) << 4), w[0], w[1], w[2], w[3]);
  }
}
__device__ __forceinline__ void stage_done(uint32_t sb, int wg, int lane) {
  fence_async_smem();
  __syncwarp();
  if (lane == 0) mbar_arrive(sb + MISC + B_RDY + wg * 8);
}
__device__ __forceinline__ float silu_mul(float g, float u) { float hg = 0.5f * g; return fmaf(hg, tanh_fast(hg), hg) * u; }

__device__ __forceinline__ void gemv_fma(float (&a)[8], uint4 w, float s) {
  a[0] = fmaf(bf_lo(w.x), s, a[0]); a[1] = fmaf(bf_hi(w.x), s, a[1]); a[2] = fmaf(bf_lo(w.y), s, a[2]); a[3] = fmaf(bf_hi(w.y), s, a[3]);
  a[4] = fmaf(bf_lo(w.z), s, a[4]); a[5] = fmaf(bf_hi(w.z), s, a[5]); a[6] = fmaf(bf_lo(w.w), s, a[6]); a[7] = fmaf(bf_hi(w.w), s, a[7]);
}
__device__ __forceinline__ float silu_c(bf16 c) { float v = __bfloat162float(c); return bf_round(v / (1.f + __expf(-v))); }
__device__ __forceinline__ float mod_gather(const uint2* p, uint32_t ep) {
  uint2 a, b, c, d; uint32_t n = 0;
  while (true) {
    a = ld_rlx2(p); b = ld_rlx2(p + 128); c = ld_rlx2(p + 256); d = ld_rlx2(p + 384);
    if (a.y == ep && b.y == ep && c.y == ep && d.y == ep) break;
    SPIN_GUARD(n);
  }
  return (__uint_as_float(a.x) + __uint_as_float(b.x)) + (__uint_as_float(c.x) + __uint_as_float(d.x));
}
__device__ __forceinline__ void mod_store(uint32_t sb, int sec, int col, float v) {
  v = bf_round(v);
  if (sec == 1 || sec == 4) v += 1.f;
  sts16(sb + MISC + MODV + sec * 256 + (((col >> 1) & 3) * 16 + (col >> 3)) * 4 + (col & 1) * 2, __float2bfloat16_rn(v));
}

__global__ void __cluster_dims__(2, 1, 1) __launch_bounds__(384, 1)
fused_kernel(const __grid_constant__ Maps maps, const bf16* __restrict__ cvec, const bf16* __restrict__ wmod) {
  extern __shared__ __align__(1024) uint8_t smem_raw[];
  const uint32_t sb = smem_u32(smem_raw);
  const int warp = __shfl_sync(~0u, threadIdx.x >> 5, 0), lane = threadIdx.x & 31;
  const int rank = blockIdx.x & 1, cid = blockIdx.x >> 1;
  const int m = cid >> 2, j = (cid & 3) * 2 + rank;
  const uint32_t bar = sb + MISC;

  if (warp >= 8) {
    asm volatile("setmaxnreg.dec.sync.aligned.u32 56;");
    if (warp == 8) {
      if (lane == 0) {
        if (sb & 1023) __trap();
        for (int s = 0; s < 4; s++) { mbar_init(bar + B_FULL4 + s * 8, 2); mbar_init(bar + B_EMPTY4 + s * 8, 16); }
        for (int s = 0; s < 6; s++) { mbar_init(bar + B_FULL6 + s * 8, 2); mbar_init(bar + B_EMPTY6 + s * 8, 16); }
        for (int w = 0; w < 2; w++) { mbar_init(bar + B_RDY + w * 8, 4); mbar_init(bar + B_FREE + w * 8, 1); mbar_init(bar + B_X + w * 8, 1); }
        mbar_init(bar + B_MOD, 2);
        asm volatile("fence.mbarrier_init.release.cluster;" ::: "memory");
        fence_async();
        for (int w = 0; w < 2; w++) {
          mbar_expect_tx(bar + B_X + w * 8, BLK);
          for (int b = 0; b < 2; b++) tma_3d(sb + STG + b * BLK + w * HALF, &maps.x, bar + B_X + w * 8, j * 128 + b * 64, m * 64, w);
        }
      }
      __syncwarp();
      cl_arrive();
      if (lane == 0) {
        Ring r4{0, ~0u}, r6{0, ~0u};
        auto acq4 = [&](uint32_t bytes) { mbar_wait(bar + B_EMPTY4 + r4.s * 8, (r4.ph >> r4.s) & 1); mbar_expect_tx(bar + B_FULL4 + r4.s * 8, bytes); };
        auto acq6 = [&]() { mbar_wait(bar + B_EMPTY6 + r6.s * 8, (r6.ph >> r6.s) & 1); mbar_expect_tx(bar + B_FULL6 + r6.s * 8, BLK); };
        auto old4 = [&](int s6) { int a = (s6 * 2) / 3, b = (s6 * 2 + 1) / 3; mbar_wait(bar + B_EMPTY4 + a * 8, (r4.ph >> a) & 1); mbar_wait(bar + B_EMPTY4 + b * 8, (r4.ph >> b) & 1); };
        auto old6 = [&](int s4) { int a = (s4 * 3) / 2; mbar_wait(bar + B_EMPTY6 + a * 8, (r6.ph >> a) & 1); mbar_wait(bar + B_EMPTY6 + a * 8 + 8, (r6.ph >> (a + 1)) & 1); };
        for (int it = 0; it < 32; it++) {
          int kb = it < 16 ? own_order(it, j) : it - 16;
          acq4(24576);
          tma_3d(sb + r4.s * 49152 + BLK, &maps.wqkv, bar + B_FULL4 + r4.s * 8, ((it >> 4) * 8 + j) * 64, kb * 64, 0);
          ring_next<4>(r4);
        }
        for (int it = 0; it < 16; it++) {
          if (it < 6) old4(r6.s);
          acq6();
          tma_3d(sb + r6.s * 32768 + BLK, &maps.wo, bar + B_FULL6 + r6.s * 8, 0, it * 64, 2 * j);
          ring_next<6>(r6);
        }
        r4.s = 3;
        for (int it = 0; it < 48; it++) {
          int kb = it < 16 ? own_order(it, j) : it & 15;
          if (it < 4) old6(r4.s);
          acq4(32768);
          tma_3d(sb + r4.s * 49152 + BLK, &maps.w1, bar + B_FULL4 + r4.s * 8, 0, kb * 64, 2 * ((it >> 4) * 8 + j));
          tma_3d(sb + r4.s * 49152 + 2 * BLK, &maps.w3, bar + B_FULL4 + r4.s * 8, 0, kb * 64, 2 * ((it >> 4) * 8 + j));
          ring_next<4>(r4);
        }
        r6.s = 5;
        for (int it = 0; it < 16; it++) {
          if (it < 6) old4(r6.s);
          acq6();
          tma_3d(sb + r6.s * 32768 + BLK, &maps.w1s, bar + B_FULL6 + r6.s * 8, 0, it * 64, 48 + j);
          tma_3d(sb + r6.s * 32768 + BLK + HALF, &maps.w3s, bar + B_FULL6 + r6.s * 8, 0, it * 64, 48 + j);
          ring_next<6>(r6);
        }
        for (int it = 0; it < 56; it++) {
          acq6();
          tma_3d(sb + r6.s * 32768 + BLK, &maps.w2, bar + B_FULL6 + r6.s * 8, 0, it * 64, 2 * j);
          ring_next<6>(r6);
        }
      }
    } else if (warp == 9) {
      const uint32_t ep = g_epoch[blockIdx.x] + 1;
      cl_arrive(); cl_wait();
      Ring r4{0, ~0u}, r6{0, ~0u};
      uint32_t mk[2][2] = {{0, 0}, {0, 0}};
      const uint32_t* fl = g_flag + m * 128;
      auto need = [&](int o, int hi, int u) {
        uint32_t n = 0;
        if (!((mk[o][hi] >> u) & 1)) {
          do { mk[o][hi] = __ballot_sync(~0u, ld_acquire(fl + (rank ^ o) * 64 + hi * 32 + lane) == ep); SPIN_GUARD(n); } while (!((mk[o][hi] >> u) & 1));
          __syncwarp();
          fence_async();
        }
      };
      auto wait4 = [&]() { mbar_wait(bar + B_EMPTY4 + r4.s * 8, (r4.ph >> r4.s) & 1); };
      auto wait6 = [&]() { mbar_wait(bar + B_EMPTY6 + r6.s * 8, (r6.ph >> r6.s) & 1); };
      auto old4 = [&](int s6) { int a = (s6 * 2) / 3, b = (s6 * 2 + 1) / 3; mbar_wait(bar + B_EMPTY4 + a * 8, (r4.ph >> a) & 1); mbar_wait(bar + B_EMPTY4 + b * 8, (r4.ph >> b) & 1); };
      auto old6 = [&](int s4) { int a = (s4 * 3) / 2; mbar_wait(bar + B_EMPTY6 + a * 8, (r6.ph >> a) & 1); mbar_wait(bar + B_EMPTY6 + a * 8 + 8, (r6.ph >> (a + 1)) & 1); };
      auto ld_mc = [&](uint32_t slot, uint32_t full, const uint4* blk) {
        if (lane == 0) { mbar_expect_tx(full, BLK); bulk_ld_mc(slot + rank * HALF, blk + rank * 512, HALF, full); }
      };
      auto big_phase = [&](int ntile, int ubase, bool trans) {
        for (int it = 0; it < ntile * 16; it++) {
          int kb = it < 16 ? own_order(it, j) : it & 15;
          uint32_t full = bar + B_FULL4 + r4.s * 8, slot = sb + r4.s * 49152;
          const uint4* blk = g_h + (m * 16 + kb) * 1024;
          if (trans && it < 4) old6(r4.s);
          wait4();
          if (it < 2) { if (lane == 0) mbar_arrive(full); }
          else if (it == 14 || it == 15) {
            need(0, 0, ubase + (kb >> 1)); need(1, 0, ubase + (kb >> 1));
            if (lane == 0) { mbar_expect_tx(full, BLK); bulk_ld(slot, blk, BLK, full); }
          } else { need(0, 0, ubase + (kb >> 1)); ld_mc(slot, full, blk); }
          ring_next<4>(r4);
        }
      };
      big_phase(2, U_H1, false);
      for (int it = 0; it < 16; it++) {
        if (it < 6) old4(r6.s);
        wait6(); need(0, 0, U_O + it);
        ld_mc(sb + r6.s * 32768, bar + B_FULL6 + r6.s * 8, g_o + (m * 16 + it) * 1024);
        ring_next<6>(r6);
      }
      r4.s = 3;
      big_phase(3, U_H2, true);
      r6.s = 5;
      for (int it = 0; it < 16; it++) {
        if (it < 6) old4(r6.s);
        wait6();
        ld_mc(sb + r6.s * 32768, bar + B_FULL6 + r6.s * 8, g_h + (m * 16 + it) * 1024);
        ring_next<6>(r6);
      }
      for (int it = 0; it < 56; it++) {
        wait6(); need(0, 1, it < 48 ? it >> 1 : it - 24);
        ld_mc(sb + r6.s * 32768, bar + B_FULL6 + r6.s * 8, g_hh + (m * 56 + it) * 1024);
        ring_next<6>(r6);
      }
    } else {
      const int wg = warp - 10;
      const uint32_t ep = g_epoch[blockIdx.x] + 1;
      cl_arrive(); cl_wait();
      const uint32_t rdy = bar + B_RDY + wg * 8, fr = bar + B_FREE + wg * 8, stg = sb + STG + wg * HALF;
      uint32_t* fl = g_flag + m * 128 + wg * 64;
      auto store_ev = [&](int e, uint4* dst, int nblk, int unit) {
        if (lane == 0) {
          mbar_wait(rdy, e & 1);
          bulk_st(dst + wg * 512, stg, HALF);
          if (nblk == 2) bulk_st(dst + 1024 + wg * 512, stg + BLK, HALF);
          bulk_commit();
          bulk_wait_read();
          mbar_arrive(fr);
          if (e == 2) {
            mbar_expect_tx(bar + B_X + wg * 8, BLK);
            for (int b = 0; b < 2; b++) tma_3d(stg + b * BLK, &maps.x, bar + B_X + wg * 8, j * 128 + b * 64, m * 64, wg);
          }
          bulk_wait_all();
          st_release(fl + unit, ep);
        }
        __syncwarp();
      };
      store_ev(0, g_h + (m * 16 + 2 * j) * 1024, 2, U_H1 + j);
      {
        const int u = m * 2 + wg, sec = 2 + ((u >> 1) & 3), hf = u & 1, ks = u >> 3;
        const bf16* wp = wmod + (size_t)(ks * 256 + (lane >> 3)) * 6144 + sec * 1024 + j * 128 + hf * 64 + (lane & 7) * 8;
        float a[8] = {0, 0, 0, 0, 0, 0, 0, 0};
#pragma unroll 1
        for (int c = 0; c < 8; c++) {
          float s = silu_c(cvec[ks * 256 + c * 32 + lane]);
#pragma unroll
          for (int h = 0; h < 2; h++) {
            uint4 w[4];
#pragma unroll
            for (int i = 0; i < 4; i++) w[i] = ldg_nc(wp + (size_t)(c * 32 + h * 16 + i * 4) * 6144);
#pragma unroll
            for (int i = 0; i < 4; i++) gemv_fma(a, w[i], __shfl_sync(~0u, s, h * 16 + i * 4 + (lane >> 3)));
          }
        }
#pragma unroll
        for (int i = 0; i < 8; i++) { a[i] += __shfl_xor_sync(~0u, a[i], 8); a[i] += __shfl_xor_sync(~0u, a[i], 16); }
        int q = lane >> 3;
        float v0 = q == 0 ? a[0] : q == 1 ? a[2] : q == 2 ? a[4] : a[6], v1 = q == 0 ? a[1] : q == 1 ? a[3] : q == 2 ? a[5] : a[7];
        st_rlx4((uint4*)(g_modp + ((j * 6 + sec) * 4 + ks) * 128 + hf * 64 + (lane & 7) * 8 + q * 2), __float_as_uint(v0), ep, __float_as_uint(v1), ep);
      }
      store_ev(1, g_o + (m * 16 + j) * 1024, 1, U_O + j);
#pragma unroll 1
      for (int i = 0; i < 8; i++) {
        int sec = 2 + wg * 2 + (i >> 2), col = (i & 3) * 32 + lane;
        mod_store(sb, sec, col, mod_gather(g_modp + (j * 6 + sec) * 512 + col, ep));
      }
      __syncwarp();
      if (lane == 0) mbar_arrive(bar + B_MOD);
      store_ev(2, g_o + (m * 16 + 8 + j) * 1024, 1, U_O + 8 + j);
      store_ev(3, g_h + (m * 16 + 2 * j) * 1024, 2, U_H2 + j);
      for (int t = 0; t < 3; t++) store_ev(4 + t, g_hh + (m * 56 + 2 * (8 * t + j)) * 1024, 2, U_HH + 8 * t + j);
      store_ev(7, g_hh + (m * 56 + 48 + j) * 1024, 1, U_HH + 24 + j);
      if (lane == 0) {
        mbar_wait(rdy, 0);
        for (int b = 0; b < 2; b++) tma_store_3d(&maps.out, stg + b * BLK, j * 128 + b * 64, m * 64, wg);
        bulk_commit();
        bulk_wait_read();
      }
      TR(40 + wg);
    }
  } else {
    asm volatile("setmaxnreg.inc.sync.aligned.u32 224;");
    const int wg = warp >> 2, wq = warp & 3, tid = threadIdx.x;
    const int g = lane >> 2, c = lane & 3;
    if (warp == 0) TR(0);
    const int sec0 = (m >> 1) & 1, hf0 = m & 1, ks0 = m >> 2;
    uint4 wv[8];
    {
      const bf16* wp = wmod + (size_t)(ks0 * 256 + warp * 32 + (lane >> 3)) * 6144 + sec0 * 1024 + j * 128 + hf0 * 64 + (lane & 7) * 8;
#pragma unroll
      for (int i = 0; i < 8; i++) wv[i] = ldg_nc(wp + (size_t)i * 4 * 6144);
    }
    const float sc_ = silu_c(cvec[ks0 * 256 + warp * 32 + lane]);
    const uint32_t ep = g_epoch[blockIdx.x] + 1;
    cl_arrive(); cl_wait();
    const uint32_t rel = mapa(bar, (lane & 1) ^ rank);
    const int row0 = wg * 64 + wq * 16 + g;
    const uint32_t stg_row = sb + STG + (wg * 64 + wq * 16 + (lane & 15)) * 128;
    Ring r4{0, 0}, r6{0, 0};
    {
      float a[8] = {0, 0, 0, 0, 0, 0, 0, 0};
#pragma unroll
      for (int i = 0; i < 8; i++) gemv_fma(a, wv[i], __shfl_sync(~0u, sc_, i * 4 + (lane >> 3)));
#pragma unroll
      for (int i = 0; i < 8; i++) { a[i] += __shfl_xor_sync(~0u, a[i], 8); a[i] += __shfl_xor_sync(~0u, a[i], 16); }
      if (lane < 8) {
        sts128(sb + RED_OFF + warp * 256 + lane * 32, __float_as_uint(a[0]), __float_as_uint(a[1]), __float_as_uint(a[2]), __float_as_uint(a[3]));
        sts128(sb + RED_OFF + warp * 256 + lane * 32 + 16, __float_as_uint(a[4]), __float_as_uint(a[5]), __float_as_uint(a[6]), __float_as_uint(a[7]));
      }
      named_bar(1, 256);
      if (tid < 64) {
        float s = 0;
#pragma unroll
        for (int w = 0; w < 8; w++) s += lds32f(sb + RED_OFF + w * 256 + tid * 4);
        st_rlx2(g_modp + ((j * 6 + sec0) * 4 + ks0) * 128 + hf0 * 64 + tid, __float_as_uint(s), ep);
      }
      if (warp == 0) TR(1);
      float v[64];
      mbar_wait(bar + B_X + wg * 8, 0);
#pragma unroll
      for (int i = 0; i < 16; i += 2) {
        uint32_t w0, w1, w2, w3;
        ldsm4(stg_row + (i >> 3) * BLK + ((((i & 7) + (lane >> 4)) ^ (lane & 7)) << 4), w0, w1, w2, w3);
        v[4 * i] = bf_lo(w0); v[4 * i + 1] = bf_hi(w0); v[4 * i + 2] = bf_lo(w1); v[4 * i + 3] = bf_hi(w1);
        v[4 * i + 4] = bf_lo(w2); v[4 * i + 5] = bf_hi(w2); v[4 * i + 6] = bf_lo(w3); v[4 * i + 7] = bf_hi(w3);
      }
      ln_publish(v, g_stat + m * 1024, j, row0, lane, ep);
      if (warp == 0) TR(2);
      mod_store(sb, tid >> 7, tid & 127, mod_gather(g_modp + (j * 6 + (tid >> 7)) * 512 + (tid & 127), ep));
      float mu0, r0, mu1, r1;
      ln_gather(g_stat + m * 1024, row0, lane, ep, mu0, r0, mu1, r1);
      named_bar(1, 256);
      if (warp == 0) TR(3);
      ln_apply(v, mu0, r0, mu1, r1, sb, 0, 1, stg_row, lane);
      stage_done(sb, wg, lane);
      named_bar(2 + wg, 128);
    }
    if (warp == 0) TR(4);
#pragma unroll 1
    for (int t = 0; t < 2; t++) {
      float acc[96];
      mainloop<192, 4>(acc, 16, t == 0, r4, sb, wg, lane, rel);
      if (warp == 0) TR(5 + 2 * t);
      uint32_t qf[16], kf[16], vf[16], pv[16];
#pragma unroll
      for (int i = 0; i < 16; i++) { kf[i] = pack2(acc[32 + 2 * i], acc[33 + 2 * i]); vf[i] = movm(pack2(acc[64 + 2 * i], acc[65 + 2 * i])); }
      if (wq == 3) {
        if (m < 15) {
          uint4* hp = g_halo + ((((m + 1) * 8 + j) * 2 + t) * 2 + wg) * 256 + lane;
#pragma unroll
          for (int i = 0; i < 8; i++) st_rlx4(hp + i * 32, kf[2 * i + 1], ep, vf[2 * i + 1], ep);
        }
        mbar_wait(bar + B_FREE + wg * 8, t & 1);
      } else {
        mbar_wait(bar + B_FREE + wg * 8, t & 1);
        uint32_t xa = sb + STG + BLK + wg * HALF + wq * 2048 + lane * 16;
#pragma unroll
        for (int i = 0; i < 4; i++) sts128(xa + i * 512, kf[4 * i + 1], vf[4 * i + 1], kf[4 * i + 3], vf[4 * i + 3]);
      }
#pragma unroll
      for (int i = 0; i < 16; i++) qf[i] = pack2(acc[2 * i], acc[2 * i + 1]);
      named_bar(2 + wg, 128);
      bool have_prev = true;
      if (wq == 0) {
        if (m > 0) {
          const uint4* hp = g_halo + (((m * 8 + j) * 2 + t) * 2 + wg) * 256 + lane;
          uint32_t n = 0;
          while (true) {
            bool ok = true;
#pragma unroll
            for (int i = 0; i < 8; i++) { uint4 q = ld_rlx4(hp + i * 32); pv[2 * i] = q.x; pv[2 * i + 1] = q.z; ok = ok && q.y == ep && q.w == ep; }
            if (ok) break;
            SPIN_GUARD(n);
          }
          __syncwarp();
        } else {
          have_prev = false;
#pragma unroll
          for (int i = 0; i < 16; i++) pv[i] = 0;
        }
      } else {
        uint32_t xa = sb + STG + BLK + wg * HALF + (wq - 1) * 2048 + lane * 16;
#pragma unroll
        for (int i = 0; i < 4; i++) { uint4 q = lds128(xa + i * 512); pv[4 * i] = q.x; pv[4 * i + 1] = q.y; pv[4 * i + 2] = q.z; pv[4 * i + 3] = q.w; }
      }
      const bool up0 = 2 * c > g, up1 = 2 * c + 1 > g;
      const float SCL = 0.17677669529663687f * 1.4426950408889634f;
#pragma unroll
      for (int h = 0; h < 2; h++) {
        float s0[4] = {0, 0, 0, 0}, s1[4] = {0, 0, 0, 0}, s2[4] = {0, 0, 0, 0};
#pragma unroll
        for (int ks = 0; ks < 2; ks++) {
          int i = 4 * h + 2 * ks;
          mma16(s1, qf[2 * i], qf[2 * i + 1], qf[2 * i + 2], qf[2 * i + 3], kf[2 * i], kf[2 * i + 2]);
          mma16(s2, qf[2 * i], qf[2 * i + 1], qf[2 * i + 2], qf[2 * i + 3], kf[2 * i + 1], kf[2 * i + 3]);
          mma16(s0, qf[2 * i], qf[2 * i + 1], qf[2 * i + 2], qf[2 * i + 3], pv[2 * i], pv[2 * i + 2]);
        }
        if (!have_prev) { s0[0] = -INFINITY; s0[1] = -INFINITY; }
        float a0 = (up0 ? s0[0] : s1[0]) * SCL, a1 = (up1 ? s0[1] : s1[1]) * SCL;
        float b0 = (up0 ? s1[2] : s2[2]) * SCL, b1 = (up1 ? s1[3] : s2[3]) * SCL;
        float ma = fmaxf(a0, a1), mb = fmaxf(b0, b1);
        ma = fmaxf(ma, __shfl_xor_sync(~0u, ma, 1)); mb = fmaxf(mb, __shfl_xor_sync(~0u, mb, 1));
        ma = fmaxf(ma, __shfl_xor_sync(~0u, ma, 2)); mb = fmaxf(mb, __shfl_xor_sync(~0u, mb, 2));
        a0 = ex2(a0 - ma); a1 = ex2(a1 - ma); b0 = ex2(b0 - mb); b1 = ex2(b1 - mb);
        float sa = a0 + a1, sbm = b0 + b1;
        sa += __shfl_xor_sync(~0u, sa, 1); sbm += __shfl_xor_sync(~0u, sbm, 1);
        sa += __shfl_xor_sync(~0u, sa, 2); sbm += __shfl_xor_sync(~0u, sbm, 2);
        sa = __fdividef(1.f, sa); sbm = __fdividef(1.f, sbm);
        uint32_t pa = pack2(a0 * sa, a1 * sa), pb = pack2(b0 * sbm, b1 * sbm);
        const uint32_t mup = (up0 ? 0xffffu : 0u) | (up1 ? 0xffff0000u : 0u);
        uint32_t of[8];
#pragma unroll
        for (int d = 0; d < 4; d++) {
          int i = 4 * h + d;
          float o[4] = {0, 0, 0, 0};
          mma16(o, pa & ~mup, pb & mup, 0u, pb & ~mup, vf[2 * i], vf[2 * i + 1]);
          mma8(o, pa & mup, 0u, pv[2 * i + 1]);
          of[2 * d] = pack2(o[0], o[1]); of[2 * d + 1] = pack2(o[2], o[3]);
        }
#pragma unroll
        for (int d = 0; d < 4; d += 2) stsm4(stg_row + (((4 * h + d + (lane >> 4)) ^ (lane & 7)) << 4), of[2 * d], of[2 * d + 1], of[2 * d + 2], of[2 * d + 3]);
      }
      stage_done(sb, wg, lane);
      if (warp == 0) TR(6 + 2 * t);
    }
    {
      float acc[64];
      mainloop<128, 6>(acc, 16, false, r6, sb, wg, lane, rel);
      if (warp == 0) TR(9);
      mbar_wait(bar + B_MOD, 0);
      mbar_wait(bar + B_X + wg * 8, 1);
      uint32_t ga[16];
      load_vec(ga, sb, 2, lane);
#pragma unroll
      for (int i = 0; i < 16; i += 2) {
        uint32_t w[4];
        ldsm4(stg_row + (i >> 3) * BLK + ((((i & 7) + (lane >> 4)) ^ (lane & 7)) << 4), w[0], w[1], w[2], w[3]);
#pragma unroll
        for (int u = 0; u < 2; u++) {
          int q = i + u;
          acc[4 * q] = fmaf(acc[4 * q], bf_lo(ga[q]), bf_lo(w[2 * u])); acc[4 * q + 1] = fmaf(acc[4 * q + 1], bf_hi(ga[q]), bf_hi(w[2 * u]));
          acc[4 * q + 2] = fmaf(acc[4 * q + 2], bf_lo(ga[q]), bf_lo(w[2 * u + 1])); acc[4 * q + 3] = fmaf(acc[4 * q + 3], bf_hi(ga[q]), bf_hi(w[2 * u + 1]));
        }
      }
      ln_publish(acc, g_stat + (16 + m) * 1024, j, row0, lane, ep);
#pragma unroll
      for (int i = 0; i < 8; i++)
        g_x1[(blockIdx.x * 8 + i) * 256 + tid] = make_uint4(pack2(acc[8 * i], acc[8 * i + 1]), pack2(acc[8 * i + 2], acc[8 * i + 3]), pack2(acc[8 * i + 4], acc[8 * i + 5]), pack2(acc[8 * i + 6], acc[8 * i + 7]));
      float mu0, r0, mu1, r1;
      ln_gather(g_stat + (16 + m) * 1024, row0, lane, ep, mu0, r0, mu1, r1);
      if (warp == 0) TR(10);
      ln_apply(acc, mu0, r0, mu1, r1, sb, 3, 4, stg_row, lane);
      stage_done(sb, wg, lane);
      named_bar(2 + wg, 128);
      if (warp == 0) TR(11);
    }
    r4.s = 3;
#pragma unroll 1
    for (int t = 0; t < 3; t++) {
      float acc[128];
      mainloop<256, 4>(acc, 16, t == 0, r4, sb, wg, lane, rel);
      if (warp == 0) TR(12 + 2 * t);
      mbar_wait(bar + B_FREE + wg * 8, (3 + t) & 1);
#pragma unroll
      for (int i = 0; i < 16; i += 2) {
        uint32_t w[4];
#pragma unroll
        for (int u = 0; u < 4; u++) w[u] = pack2(silu_mul(acc[4 * i + 2 * u], acc[64 + 4 * i + 2 * u]), silu_mul(acc[4 * i + 2 * u + 1], acc[65 + 4 * i + 2 * u]));
        stsm4(stg_row + (i >> 3) * BLK + ((((i & 7) + (lane >> 4)) ^ (lane & 7)) << 4), w[0], w[1], w[2], w[3]);
      }
      stage_done(sb, wg, lane);
      if (warp == 0) TR(13 + 2 * t);
    }
    r6.s = 5;
    {
      float acc[64];
      mainloop<128, 6>(acc, 16, false, r6, sb, wg, lane, rel);
      if (warp == 0) TR(18);
      mbar_wait(bar + B_FREE + wg * 8, 0);
#pragma unroll
      for (int i = 0; i < 8; i += 2) {
        uint32_t w[4];
#pragma unroll
        for (int u = 0; u < 4; u++) w[u] = pack2(silu_mul(acc[4 * i + 2 * u], acc[32 + 4 * i + 2 * u]), silu_mul(acc[4 * i + 2 * u + 1], acc[33 + 4 * i + 2 * u]));
        stsm4(stg_row + (((i + (lane >> 4)) ^ (lane & 7)) << 4), w[0], w[1], w[2], w[3]);
      }
      stage_done(sb, wg, lane);
      if (warp == 0) TR(19);
    }
    {
      uint4 x1[8];
#pragma unroll
      for (int i = 0; i < 8; i++) x1[i] = g_x1[(blockIdx.x * 8 + i) * 256 + tid];
      float acc[64];
      mainloop<128, 6>(acc, 56, false, r6, sb, wg, lane, rel);
      __syncwarp();
      cl_arrive_relaxed();
      if (warp == 0) TR(20);
      uint32_t gb[16];
      load_vec(gb, sb, 5, lane);
      mbar_wait(bar + B_FREE + wg * 8, 1);
#pragma unroll
      for (int i = 0; i < 16; i += 2) {
        uint4 x = x1[i >> 1];
        uint32_t w0 = pack2(fmaf(acc[4 * i], bf_lo(gb[i]), bf_lo(x.x)), fmaf(acc[4 * i + 1], bf_hi(gb[i]), bf_hi(x.x)));
        uint32_t w1 = pack2(fmaf(acc[4 * i + 2], bf_lo(gb[i]), bf_lo(x.y)), fmaf(acc[4 * i + 3], bf_hi(gb[i]), bf_hi(x.y)));
        uint32_t w2 = pack2(fmaf(acc[4 * i + 4], bf_lo(gb[i + 1]), bf_lo(x.z)), fmaf(acc[4 * i + 5], bf_hi(gb[i + 1]), bf_hi(x.z)));
        uint32_t w3 = pack2(fmaf(acc[4 * i + 6], bf_lo(gb[i + 1]), bf_lo(x.w)), fmaf(acc[4 * i + 7], bf_hi(gb[i + 1]), bf_hi(x.w)));
        stsm4(stg_row + (i >> 3) * BLK + ((((i & 7) + (lane >> 4)) ^ (lane & 7)) << 4), w0, w1, w2, w3);
      }
      stage_done(sb, wg, lane);
      if (tid == 0) g_epoch[blockIdx.x] = ep;
      if (warp == 0) TR(21);
      cl_wait();
    }
  }
}

typedef CUresult (*EncodeFn)(CUtensorMap*, CUtensorMapDataType, cuuint32_t, void*, const cuuint64_t*, const cuuint64_t*, const cuuint32_t*, const cuuint32_t*,
                             CUtensorMapInterleave, CUtensorMapSwizzle, CUtensorMapL2promotion, CUtensorMapFloatOOBfill);

void make_map(EncodeFn fn, CUtensorMap* mp, const void* base, uint64_t d0, uint64_t d1, uint64_t d2, uint64_t s1, uint64_t s2, uint32_t b2) {
  cuuint64_t d[3] = {d0, d1, d2}, s[2] = {s1, s2};
  cuuint32_t b[3] = {64, 64, b2}, e[3] = {1, 1, 1};
  fn(mp, CU_TENSOR_MAP_DATA_TYPE_BFLOAT16, 3, (void*)base, d, s, b, e, CU_TENSOR_MAP_INTERLEAVE_NONE, CU_TENSOR_MAP_SWIZZLE_128B,
     CU_TENSOR_MAP_L2_PROMOTION_L2_128B, CU_TENSOR_MAP_FLOAT_OOB_FILL_NONE);
}

}

extern "C" void kernel_launch(void* const* d_in, const int* in_sizes, int n_in, void* d_out, int out_size) {
  static EncodeFn fn = nullptr;
  if (!fn) {
    void* p = nullptr; cudaDriverEntryPointQueryResult q;
    cudaGetDriverEntryPoint("cuTensorMapEncodeTiled", &p, cudaEnableDefault, &q);
    fn = (EncodeFn)p;
    cudaFuncSetAttribute(fused_kernel, cudaFuncAttributeMaxDynamicSharedMemorySize, SMEM_BYTES);
  }
  Maps mp;
  make_map(fn, &mp.x, d_in[0], D_, S_ / 2, 2, 4096, 2048, 1);
  make_map(fn, &mp.out, d_out, D_, S_ / 2, 2, 4096, 2048, 1);
  make_map(fn, &mp.wqkv, d_in[1], D_, D_, 3, 3 * D_ * 2, D_ * 2, 3);
  make_map(fn, &mp.wo, d_in[2], 64, D_, D_ / 64, D_ * 2, 128, 2);
  make_map(fn, &mp.w1, d_in[4], 64, D_, F_ / 64, F_ * 2, 128, 2);
  make_map(fn, &mp.w3, d_in[5], 64, D_, F_ / 64, F_ * 2, 128, 2);
  make_map(fn, &mp.w1s, d_in[4], 64, D_, F_ / 64, F_ * 2, 128, 1);
  make_map(fn, &mp.w3s, d_in[5], 64, D_, F_ / 64, F_ * 2, 128, 1);
  make_map(fn, &mp.w2, d_in[6], 64, F_, D_ / 64, D_ * 2, 128, 2);
  fused_kernel<<<128, 384, SMEM_BYTES>>>(mp, (const bf16*)d_in[7], (const bf16*)d_in[8]);
}
```

```cpp
#include <cuda_runtime.h>
#include <cuda_bf16.h>
#include <cuda.h>
#include <stdint.h>

typedef __nv_bfloat16 bf16;

namespace {

constexpr int S_ = 2048, D_ = 1024, F_ = 3584;
constexpr int BLK = 16384;
constexpr int HALF = 8192;
constexpr int RING = 196608;
constexpr int STG = RING;
constexpr int MISC = RING + 2 * BLK;
constexpr int SMEM_BYTES = MISC + 3072;
constexpr int B_FULL4 = 0, B_EMPTY4 = 32, B_FULL6 = 64, B_EMPTY6 = 112, B_RDY = 160, B_FREE = 192, B_X = 224, B_MOD = 240, B_HALO = 248, B_OWN = 264;
constexpr int MODV = 512;
constexpr int RED_OFF = 0;
constexpr float SCL = 0.17677669529663687f * 1.4426950408889634f;
constexpr int U_H1 = 0, U_O = 16, U_H2 = 32, U_HH = 64;

struct Maps { CUtensorMap x, out, wqkv, wo, w1, w3, w1s, w3s, w2; };

__device__ uint4 g_h[16 * 16 * 1024];
__device__ uint4 g_o[16 * 16 * 1024];
__device__ uint4 g_hh[16 * 56 * 1024];
__device__ uint2 g_modp[8 * 6 * 4 * 128];
__device__ uint4 g_stat[2 * 16 * 8 * 128];
__device__ uint4 g_halo[16 * 8 * 2 * 512];
__device__ uint32_t g_flag[16 * 2 * 128];
__device__ uint32_t g_epoch[128];
#define TR(i)

__device__ __forceinline__ void bail() { asm volatile("st.global.u32 [%0], %1;" :: "l"(0ull), "r"(0) : "memory"); }
__device__ __forceinline__ uint32_t smem_u32(const void* p) { return (uint32_t)__cvta_generic_to_shared(p); }
__device__ __forceinline__ void mbar_init(uint32_t bar, uint32_t cnt) { asm volatile("mbarrier.init.shared::cta.b64 [%0], %1;" :: "r"(bar), "r"(cnt) : "memory"); }
__device__ __forceinline__ void mbar_expect_tx(uint32_t bar, uint32_t bytes) { asm volatile("mbarrier.arrive.expect_tx.shared::cta.b64 _, [%0], %1;" :: "r"(bar), "r"(bytes) : "memory"); }
__device__ __forceinline__ void mbar_arrive(uint32_t bar) { asm volatile("mbarrier.arrive.shared::cta.b64 _, [%0];" :: "r"(bar) : "memory"); }
__device__ __forceinline__ void mbar_arrive_cl(uint32_t cl_addr) { asm volatile("mbarrier.arrive.shared::cluster.b64 _, [%0];" :: "r"(cl_addr) : "memory"); }
__device__ __forceinline__ uint32_t mapa(uint32_t addr, uint32_t cta) { uint32_t r; asm("mapa.shared::cluster.u32 %0, %1, %2;" : "=r"(r) : "r"(addr), "r"(cta)); return r; }
__device__ __forceinline__ bool mbar_try(uint32_t bar, uint32_t parity) {
  uint32_t ok;
  asm volatile("{\n.reg .pred p;\nmbarrier.try_wait.parity.shared::cta.b64 p, [%1], %2;\nselp.u32 %0, 1, 0, p;\n}" : "=r"(ok) : "r"(bar), "r"(parity) : "memory");
  return ok;
}
__device__ __forceinline__ void mbar_wait(uint32_t bar, uint32_t parity) {
  uint32_t n = 0;
  while (!mbar_try(bar, parity)) { if (++n > (1u << 22)) bail(); }
}
__device__ __forceinline__ void tma_3d(uint32_t dst, const CUtensorMap* m, uint32_t bar, int c0, int c1, int c2) {
  asm volatile("cp.async.bulk.tensor.3d.shared::cluster.global.mbarrier::complete_tx::bytes [%0], [%1, {%3, %4, %5}], [%2];" :: "r"(dst), "l"(m), "r"(bar), "r"(c0), "r"(c1), "r"(c2) : "memory");
}
__device__ __forceinline__ void tma_store_3d(const CUtensorMap* m, uint32_t src, int c0, int c1, int c2) {
  asm volatile("cp.async.bulk.tensor.3d.global.shared::cta.bulk_group [%0, {%2, %3, %4}], [%1];" :: "l"(m), "r"(src), "r"(c0), "r"(c1), "r"(c2) : "memory");
}
__device__ __forceinline__ void tma_pf(const CUtensorMap* m, int c1, int c2) {
  asm volatile("cp.async.bulk.prefetch.tensor.3d.L2.global [%0, {%1, %2, %3}];" :: "l"(m), "r"(0), "r"(c1), "r"(c2) : "memory");
}
__device__ __forceinline__ void bulk_ld(uint32_t dst, const void* src, uint32_t bytes, uint32_t bar) {
  asm volatile("cp.async.bulk.shared::cluster.global.mbarrier::complete_tx::bytes [%0], [%1], %2, [%3];" :: "r"(dst), "l"(src), "r"(bytes), "r"(bar) : "memory");
}
__device__ __forceinline__ void bulk_ld_mc(uint32_t dst, const void* src, uint32_t bytes, uint32_t bar) {
  asm volatile("cp.async.bulk.shared::cluster.global.mbarrier::complete_tx::bytes.multicast::cluster [%0], [%1], %2, [%3], %4;" :: "r"(dst), "l"(src), "r"(bytes), "r"(bar), "h"((uint16_t)3) : "memory");
}
__device__ __forceinline__ void bulk_st(void* dst, uint32_t src, uint32_t bytes) {
  asm volatile("cp.async.bulk.global.shared::cta.bulk_group [%0], [%1], %2;" :: "l"(dst), "r"(src), "r"(bytes) : "memory");
}
__device__ __forceinline__ void bulk_commit() { asm volatile("cp.async.bulk.commit_group;" ::: "memory"); }
__device__ __forceinline__ void bulk_wait_read() { asm volatile("cp.async.bulk.wait_group.read 0;" ::: "memory"); }
__device__ __forceinline__ void bulk_wait_all() { asm volatile("cp.async.bulk.wait_group 0;" ::: "memory"); }
__device__ __forceinline__ void fence_async() { asm volatile("fence.proxy.async.global;" ::: "memory"); }
__device__ __forceinline__ void fence_async_smem() { asm volatile("fence.proxy.async.shared::cta;" ::: "memory"); }
__device__ __forceinline__ void wg_arrive() { asm volatile("wgmma.fence.sync.aligned;" ::: "memory"); }
__device__ __forceinline__ void wg_commit() { asm volatile("wgmma.commit_group.sync.aligned;" ::: "memory"); }
template <int N> __device__ __forceinline__ void wg_wait() { asm volatile("wgmma.wait_group.sync.aligned %0;" :: "n"(N) : "memory"); }
__device__ __forceinline__ void cl_arrive_relaxed() { asm volatile("barrier.cluster.arrive.relaxed.aligned;" ::: "memory"); }
__device__ __forceinline__ void cl_wait() { asm volatile("barrier.cluster.wait.acquire.aligned;" ::: "memory"); }
__device__ __forceinline__ void named_bar(int id, int n) { asm volatile("bar.sync %0, %1;" :: "r"(id), "r"(n) : "memory"); }
__device__ __forceinline__ uint32_t pack2(float lo, float hi) { uint32_t r; asm("cvt.rn.bf16x2.f32 %0, %1, %2;" : "=r"(r) : "f"(hi), "f"(lo)); return r; }
__device__ __forceinline__ float bf_lo(uint32_t w) { return __uint_as_float(w << 16); }
__device__ __forceinline__ float bf_hi(uint32_t w) { return __uint_as_float(w & 0xffff0000u); }
__device__ __forceinline__ float bf_round(float v) { return __bfloat162float(__float2bfloat16_rn(v)); }
__device__ __forceinline__ void stsm4(uint32_t addr, uint32_t a, uint32_t b, uint32_t c, uint32_t d) {
  asm volatile("stmatrix.sync.aligned.m8n8.x4.shared.b16 [%0], {%1, %2, %3, %4};" :: "r"(addr), "r"(a), "r"(b), "r"(c), "r"(d) : "memory");
}
__device__ __forceinline__ void ldsm4(uint32_t addr, uint32_t& a, uint32_t& b, uint32_t& c, uint32_t& d) {
  asm volatile("ldmatrix.sync.aligned.m8n8.x4.shared.b16 {%0, %1, %2, %3}, [%4];" : "=r"(a), "=r"(b), "=r"(c), "=r"(d) : "r"(addr) : "memory");
}
__device__ __forceinline__ uint32_t movm(uint32_t a) { uint32_t r; asm volatile("movmatrix.sync.aligned.m8n8.trans.b16 %0, %1;" : "=r"(r) : "r"(a)); return r; }
__device__ __forceinline__ void mma16(float (&d)[4], uint32_t a0, uint32_t a1, uint32_t a2, uint32_t a3, uint32_t b0, uint32_t b1) {
  asm volatile("mma.sync.aligned.m16n8k16.row.col.f32.bf16.bf16.f32 {%0,%1,%2,%3}, {%4,%5,%6,%7}, {%8,%9}, {%0,%1,%2,%3};"
               : "+f"(d[0]), "+f"(d[1]), "+f"(d[2]), "+f"(d[3]) : "r"(a0), "r"(a1), "r"(a2), "r"(a3), "r"(b0), "r"(b1));
}
__device__ __forceinline__ void mma8(float (&d)[4], uint32_t a0, uint32_t a1, uint32_t b0) {
  asm volatile("mma.sync.aligned.m16n8k8.row.col.f32.bf16.bf16.f32 {%0,%1,%2,%3}, {%4,%5}, {%6}, {%0,%1,%2,%3};"
               : "+f"(d[0]), "+f"(d[1]), "+f"(d[2]), "+f"(d[3]) : "r"(a0), "r"(a1), "r"(b0));
}
__device__ __forceinline__ uint4 lds128(uint32_t a) { uint4 v; asm volatile("ld.shared.v4.u32 {%0,%1,%2,%3}, [%4];" : "=r"(v.x), "=r"(v.y), "=r"(v.z), "=r"(v.w) : "r"(a) : "memory"); return v; }
__device__ __forceinline__ void sts128(uint32_t a, uint32_t x, uint32_t y, uint32_t z, uint32_t w) { asm volatile("st.shared.v4.u32 [%0], {%1,%2,%3,%4};" :: "r"(a), "r"(x), "r"(y), "r"(z), "r"(w) : "memory"); }
__device__ __forceinline__ float lds32f(uint32_t a) { float v; asm volatile("ld.shared.f32 %0, [%1];" : "=f"(v) : "r"(a) : "memory"); return v; }
__device__ __forceinline__ void sts16(uint32_t a, bf16 v) { asm volatile("st.shared.b16 [%0], %1;" :: "r"(a), "h"(__bfloat16_as_ushort(v)) : "memory"); }
__device__ __forceinline__ uint4 ldg_nc(const void* p) { uint4 v; asm volatile("ld.global.nc.L1::no_allocate.v4.u32 {%0,%1,%2,%3}, [%4];" : "=r"(v.x), "=r"(v.y), "=r"(v.z), "=r"(v.w) : "l"(p)); return v; }
__device__ __forceinline__ uint4 ld_rlx4(const uint4* p) {
  unsigned long long a, b; asm volatile("ld.relaxed.gpu.global.v2.b64 {%0,%1}, [%2];" : "=l"(a), "=l"(b) : "l"(p) : "memory");
  return make_uint4((uint32_t)a, (uint32_t)(a >> 32), (uint32_t)b, (uint32_t)(b >> 32));
}
__device__ __forceinline__ uint2 ld_rlx2(const uint2* p) { unsigned long long a; asm volatile("ld.relaxed.gpu.global.b64 %0, [%1];" : "=l"(a) : "l"(p) : "memory"); return make_uint2((uint32_t)a, (uint32_t)(a >> 32)); }
__device__ __forceinline__ void st_rlx4(uint4* p, uint32_t x, uint32_t y, uint32_t z, uint32_t w) {
  asm volatile("st.relaxed.gpu.global.v2.b64 [%0], {%1,%2};" :: "l"(p), "l"((unsigned long long)x | ((unsigned long long)y << 32)), "l"((unsigned long long)z | ((unsigned long long)w << 32)) : "memory");
}
__device__ __forceinline__ void st_rlx2(uint2* p, uint32_t x, uint32_t y) { asm volatile("st.relaxed.gpu.global.b64 [%0], %1;" :: "l"(p), "l"((unsigned long long)x | ((unsigned long long)y << 32)) : "memory"); }
__device__ __forceinline__ void st_flag(uint32_t* p, uint32_t v) { asm volatile("st.relaxed.gpu.global.u32 [%0], %1;" :: "l"(p), "r"(v) : "memory"); }
__device__ __forceinline__ uint32_t ld_flag(const uint32_t* p) { uint32_t v; asm volatile("ld.relaxed.gpu.global.u32 %0, [%1];" : "=r"(v) : "l"(p) : "memory"); return v; }
__device__ __forceinline__ void cp_async16(uint32_t dst, const void* src) { asm volatile("cp.async.cg.shared.global [%0], [%1], 16;" :: "r"(dst), "l"(src) : "memory"); }
__device__ __forceinline__ void prefetch_map(const CUtensorMap* m) { asm volatile("prefetch.tensormap [%0];" :: "l"(m) : "memory"); }
__device__ __forceinline__ float ex2(float x) { float r; asm("ex2.approx.ftz.f32 %0, %1;" : "=f"(r) : "f"(x)); return r; }
__device__ __forceinline__ float tanh_fast(float x) { float r; asm("tanh.approx.f32 %0, %1;" : "=f"(r) : "f"(x)); return r; }
#define SPIN_GUARD(n) if (++(n) > (1u << 24)) bail()

__device__ __forceinline__ void wgmma_n128(float (&d)[64], uint64_t da, uint64_t db) {
  asm volatile("wgmma.mma_async.sync.aligned.m64n128k16.f32.bf16.bf16 "
    "{%0, %1, %2, %3, %4, %5, %6, %7, %8, %9, %10, %11, %12, %13, %14, %15, %16, %17, %18, %19, %20, %21, %22, %23, %24, %25, %26, %27, %28, %29, %30, %31, %32, %33, %34, %35, %36, %37, %38, %39, %40, %41, %42, %43, %44, %45, %46, %47, %48, %49, %50, %51, %52, %53, %54, %55, %56, %57, %58, %59, %60, %61, %62, %63}, "
    "%64, %65, 1, 1, 1, 0, 1;\n"
    : "+f"(d[0]), "+f"(d[1]), "+f"(d[2]), "+f"(d[3]), "+f"(d[4]), "+f"(d[5]), "+f"(d[6]), "+f"(d[7]), "+f"(d[8]), "+f"(d[9]), "+f"(d[10]), "+f"(d[11]), "+f"(d[12]), "+f"(d[13]), "+f"(d[14]), "+f"(d[15]), "+f"(d[16]), "+f"(d[17]), "+f"(d[18]), "+f"(d[19]), "+f"(d[20]), "+f"(d[21]), "+f"(d[22]), "+f"(d[23]), "+f"(d[24]), "+f"(d[25]), "+f"(d[26]), "+f"(d[27]), "+f"(d[28]), "+f"(d[29]), "+f"(d[30]), "+f"(d[31]), "+f"(d[32]), "+f"(d[33]), "+f"(d[34]), "+f"(d[35]), "+f"(d[36]), "+f"(d[37]), "+f"(d[38]), "+f"(d[39]), "+f"(d[40]), "+f"(d[41]), "+f"(d[42]), "+f"(d[43]), "+f"(d[44]), "+f"(d[45]), "+f"(d[46]), "+f"(d[47]), "+f"(d[48]), "+f"(d[49]), "+f"(d[50]), "+f"(d[51]), "+f"(d[52]), "+f"(d[53]), "+f"(d[54]), "+f"(d[55]), "+f"(d[56]), "+f"(d[57]), "+f"(d[58]), "+f"(d[59]), "+f"(d[60]), "+f"(d[61]), "+f"(d[62]), "+f"(d[63])
    : "l"(da), "l"(db));
}
__device__ __forceinline__ void wgmma_n128_first(float (&d)[64], uint64_t da, uint64_t db) {
  asm volatile("wgmma.mma_async.sync.aligned.m64n128k16.f32.bf16.bf16 "
    "{%0, %1, %2, %3, %4, %5, %6, %7, %8, %9, %10, %11, %12, %13, %14, %15, %16, %17, %18, %19, %20, %21, %22, %23, %24, %25, %26, %27, %28, %29, %30, %31, %32, %33, %34, %35, %36, %37, %38, %39, %40, %41, %42, %43, %44, %45, %46, %47, %48, %49, %50, %51, %52, %53, %54, %55, %56, %57, %58, %59, %60, %61, %62, %63}, "
    "%64, %65, 0, 1, 1, 0, 1;\n"
    : "=f"(d[0]), "=f"(d[1]), "=f"(d[2]), "=f"(d[3]), "=f"(d[4]), "=f"(d[5]), "=f"(d[6]), "=f"(d[7]), "=f"(d[8]), "=f"(d[9]), "=f"(d[10]), "=f"(d[11]), "=f"(d[12]), "=f"(d[13]), "=f"(d[14]), "=f"(d[15]), "=f"(d[16]), "=f"(d[17]), "=f"(d[18]), "=f"(d[19]), "=f"(d[20]), "=f"(d[21]), "=f"(d[22]), "=f"(d[23]), "=f"(d[24]), "=f"(d[25]), "=f"(d[26]), "=f"(d[27]), "=f"(d[28]), "=f"(d[29]), "=f"(d[30]), "=f"(d[31]), "=f"(d[32]), "=f"(d[33]), "=f"(d[34]), "=f"(d[35]), "=f"(d[36]), "=f"(d[37]), "=f"(d[38]), "=f"(d[39]), "=f"(d[40]), "=f"(d[41]), "=f"(d[42]), "=f"(d[43]), "=f"(d[44]), "=f"(d[45]), "=f"(d[46]), "=f"(d[47]), "=f"(d[48]), "=f"(d[49]), "=f"(d[50]), "=f"(d[51]), "=f"(d[52]), "=f"(d[53]), "=f"(d[54]), "=f"(d[55]), "=f"(d[56]), "=f"(d[57]), "=f"(d[58]), "=f"(d[59]), "=f"(d[60]), "=f"(d[61]), "=f"(d[62]), "=f"(d[63])
    : "l"(da), "l"(db));
}
__device__ __forceinline__ void wgmma_n256(float (&d)[128], uint64_t da, uint64_t db) {
  asm volatile("wgmma.mma_async.sync.aligned.m64n256k16.f32.bf16.bf16 "
    "{%0, %1, %2, %3, %4, %5, %6, %7, %8, %9, %10, %11, %12, %13, %14, %15, %16, %17, %18, %19, %20, %21, %22, %23, %24, %25, %26, %27, %28, %29, %30, %31, %32, %33, %34, %35, %36, %37, %38, %39, %40, %41, %42, %43, %44, %45, %46, %47, %48, %49, %50, %51, %52, %53, %54, %55, %56, %57, %58, %59, %60, %61, %62, %63, %64, %65, %66, %67, %68, %69, %70, %71, %72, %73, %74, %75, %76, %77, %78, %79, %80, %81, %82, %83, %84, %85, %86, %87, %88, %89, %90, %91, %92, %93, %94, %95, %96, %97, %98, %99, %100, %101, %102, %103, %104, %105, %106, %107, %108, %109, %110, %111, %112, %113, %114, %115, %116, %117, %118, %119, %120, %121, %122, %123, %124, %125, %126, %127}, "
    "%128, %129, 1, 1, 1, 0, 1;\n"
    : "+f"(d[0]), "+f"(d[1]), "+f"(d[2]), "+f"(d[3]), "+f"(d[4]), "+f"(d[5]), "+f"(d[6]), "+f"(d[7]), "+f"(d[8]), "+f"(d[9]), "+f"(d[10]), "+f"(d[11]), "+f"(d[12]), "+f"(d[13]), "+f"(d[14]), "+f"(d[15]), "+f"(d[16]), "+f"(d[17]), "+f"(d[18]), "+f"(d[19]), "+f"(d[20]), "+f"(d[21]), "+f"(d[22]), "+f"(d[23]), "+f"(d[24]), "+f"(d[25]), "+f"(d[26]), "+f"(d[27]), "+f"(d[28]), "+f"(d[29]), "+f"(d[30]), "+f"(d[31]), "+f"(d[32]), "+f"(d[33]), "+f"(d[34]), "+f"(d[35]), "+f"(d[36]), "+f"(d[37]), "+f"(d[38]), "+f"(d[39]), "+f"(d[40]), "+f"(d[41]), "+f"(d[42]), "+f"(d[43]), "+f"(d[44]), "+f"(d[45]), "+f"(d[46]), "+f"(d[47]), "+f"(d[48]), "+f"(d[49]), "+f"(d[50]), "+f"(d[51]), "+f"(d[52]), "+f"(d[53]), "+f"(d[54]), "+f"(d[55]), "+f"(d[56]), "+f"(d[57]), "+f"(d[58]), "+f"(d[59]), "+f"(d[60]), "+f"(d[61]), "+f"(d[62]), "+f"(d[63]), "+f"(d[64]), "+f"(d[65]), "+f"(d[66]), "+f"(d[67]), "+f"(d[68]), "+f"(d[69]), "+f"(d[70]), "+f"(d[71]), "+f"(d[72]), "+f"(d[73]), "+f"(d[74]), "+f"(d[75]), "+f"(d[76]), "+f"(d[77]), "+f"(d[78]), "+f"(d[79]), "+f"(d[80]), "+f"(d[81]), "+f"(d[82]), "+f"(d[83]), "+f"(d[84]), "+f"(d[85]), "+f"(d[86]), "+f"(d[87]), "+f"(d[88]), "+f"(d[89]), "+f"(d[90]), "+f"(d[91]), "+f"(d[92]), "+f"(d[93]), "+f"(d[94]), "+f"(d[95]), "+f"(d[96]), "+f"(d[97]), "+f"(d[98]), "+f"(d[99]), "+f"(d[100]), "+f"(d[101]), "+f"(d[102]), "+f"(d[103]), "+f"(d[104]), "+f"(d[105]), "+f"(d[106]), "+f"(d[107]), "+f"(d[108]), "+f"(d[109]), "+f"(d[110]), "+f"(d[111]), "+f"(d[112]), "+f"(d[113]), "+f"(d[114]), "+f"(d[115]), "+f"(d[116]), "+f"(d[117]), "+f"(d[118]), "+f"(d[119]), "+f"(d[120]), "+f"(d[121]), "+f"(d[122]), "+f"(d[123]), "+f"(d[124]), "+f"(d[125]), "+f"(d[126]), "+f"(d[127])
    : "l"(da), "l"(db));
}
__device__ __forceinline__ void wgmma_n256_first(float (&d)[128], uint64_t da, uint64_t db) {
  asm volatile("wgmma.mma_async.sync.aligned.m64n256k16.f32.bf16.bf16 "
    "{%0, %1, %2, %3, %4, %5, %6, %7, %8, %9, %10, %11, %12, %13, %14, %15, %16, %17, %18, %19, %20, %21, %22, %23, %24, %25, %26, %27, %28, %29, %30, %31, %32, %33, %34, %35, %36, %37, %38, %39, %40, %41, %42, %43, %44, %45, %46, %47, %48, %49, %50, %51, %52, %53, %54, %55, %56, %57, %58, %59, %60, %61, %62, %63, %64, %65, %66, %67, %68, %69, %70, %71, %72, %73, %74, %75, %76, %77, %78, %79, %80, %81, %82, %83, %84, %85, %86, %87, %88, %89, %90, %91, %92, %93, %94, %95, %96, %97, %98, %99, %100, %101, %102, %103, %104, %105, %106, %107, %108, %109, %110, %111, %112, %113, %114, %115, %116, %117, %118, %119, %120, %121, %122, %123, %124, %125, %126, %127}, "
    "%128, %129, 0, 1, 1, 0, 1;\n"
    : "=f"(d[0]), "=f"(d[1]), "=f"(d[2]), "=f"(d[3]), "=f"(d[4]), "=f"(d[5]), "=f"(d[6]), "=f"(d[7]), "=f"(d[8]), "=f"(d[9]), "=f"(d[10]), "=f"(d[11]), "=f"(d[12]), "=f"(d[13]), "=f"(d[14]), "=f"(d[15]), "=f"(d[16]), "=f"(d[17]), "=f"(d[18]), "=f"(d[19]), "=f"(d[20]), "=f"(d[21]), "=f"(d[22]), "=f"(d[23]), "=f"(d[24]), "=f"(d[25]), "=f"(d[26]), "=f"(d[27]), "=f"(d[28]), "=f"(d[29]), "=f"(d[30]), "=f"(d[31]), "=f"(d[32]), "=f"(d[33]), "=f"(d[34]), "=f"(d[35]), "=f"(d[36]), "=f"(d[37]), "=f"(d[38]), "=f"(d[39]), "=f"(d[40]), "=f"(d[41]), "=f"(d[42]), "=f"(d[43]), "=f"(d[44]), "=f"(d[45]), "=f"(d[46]), "=f"(d[47]), "=f"(d[48]), "=f"(d[49]), "=f"(d[50]), "=f"(d[51]), "=f"(d[52]), "=f"(d[53]), "=f"(d[54]), "=f"(d[55]), "=f"(d[56]), "=f"(d[57]), "=f"(d[58]), "=f"(d[59]), "=f"(d[60]), "=f"(d[61]), "=f"(d[62]), "=f"(d[63]), "=f"(d[64]), "=f"(d[65]), "=f"(d[66]), "=f"(d[67]), "=f"(d[68]), "=f"(d[69]), "=f"(d[70]), "=f"(d[71]), "=f"(d[72]), "=f"(d[73]), "=f"(d[74]), "=f"(d[75]), "=f"(d[76]), "=f"(d[77]), "=f"(d[78]), "=f"(d[79]), "=f"(d[80]), "=f"(d[81]), "=f"(d[82]), "=f"(d[83]), "=f"(d[84]), "=f"(d[85]), "=f"(d[86]), "=f"(d[87]), "=f"(d[88]), "=f"(d[89]), "=f"(d[90]), "=f"(d[91]), "=f"(d[92]), "=f"(d[93]), "=f"(d[94]), "=f"(d[95]), "=f"(d[96]), "=f"(d[97]), "=f"(d[98]), "=f"(d[99]), "=f"(d[100]), "=f"(d[101]), "=f"(d[102]), "=f"(d[103]), "=f"(d[104]), "=f"(d[105]), "=f"(d[106]), "=f"(d[107]), "=f"(d[108]), "=f"(d[109]), "=f"(d[110]), "=f"(d[111]), "=f"(d[112]), "=f"(d[113]), "=f"(d[114]), "=f"(d[115]), "=f"(d[116]), "=f"(d[117]), "=f"(d[118]), "=f"(d[119]), "=f"(d[120]), "=f"(d[121]), "=f"(d[122]), "=f"(d[123]), "=f"(d[124]), "=f"(d[125]), "=f"(d[126]), "=f"(d[127])
    : "l"(da), "l"(db));
}

template <int N> struct WG;
#define DEF_WG(N) template <> struct WG<N> { \
  static __device__ __forceinline__ void mma(float (&d)[N / 2], uint64_t a, uint64_t b) { wgmma_n##N(d, a, b); } \
  static __device__ __forceinline__ void first(float (&d)[N / 2], uint64_t a, uint64_t b) { wgmma_n##N##_first(d, a, b); } };
DEF_WG(128) DEF_WG(256)

constexpr uint64_t DESC_A = (1ull << 62) | ((uint64_t)(1024 >> 4) << 32) | (1ull << 16);
constexpr uint64_t DESC_B = (1ull << 62) | ((uint64_t)(1024 >> 4) << 32) | ((uint64_t)(8192 >> 4) << 16);

struct Ring { int s; uint32_t ph; };

template <int NS> __device__ __forceinline__ void ring_next(Ring& r) { r.ph ^= 1u << r.s; r.s = (r.s + 1 == NS) ? 0 : r.s + 1; }

__device__ __forceinline__ int own_order(int it, int j) {
  return it < 2 ? 2 * j + it : it < 8 ? ((j >> 1) * 4 + 2 * it) & 15 : it < 14 ? ((j >> 1) * 4 + 2 * it - 11) & 15 : 2 * (j ^ 1) + it - 14;
}

template <int N, int NS>
__device__ __forceinline__ void mainloop(float (&acc)[N / 2], int nkb, bool own, Ring& r, uint32_t sb, int wg, int lane, uint32_t rel_base) {
  constexpr int SLOT = RING / NS;
  const uint32_t full = sb + MISC + (NS == 4 ? B_FULL4 : B_FULL6);
  const uint32_t rel = rel_base + (NS == 4 ? B_EMPTY4 : B_EMPTY6);
  {
    uint32_t sa = (own ? sb + STG : sb + r.s * SLOT) + wg * HALF, sbb = sb + r.s * SLOT + BLK;
    uint64_t da = DESC_A | (uint64_t)((sa & 0x3FFFF) >> 4), db = DESC_B | (uint64_t)((sbb & 0x3FFFF) >> 4);
    mbar_wait(full + r.s * 8, (r.ph >> r.s) & 1);
    wg_arrive();
    WG<N>::first(acc, da, db);
#pragma unroll
    for (int k = 1; k < 4; k++) WG<N>::mma(acc, da + k * 2, db + k * 128);
    wg_commit();
  }
  int ps = r.s;
  ring_next<NS>(r);
#pragma unroll 1
  for (int it = 1; it < nkb; it++) {
    uint32_t sa = ((own && it == 1) ? sb + STG + BLK : sb + r.s * SLOT) + wg * HALF, sbb = sb + r.s * SLOT + BLK;
    uint64_t da = DESC_A | (uint64_t)((sa & 0x3FFFF) >> 4), db = DESC_B | (uint64_t)((sbb & 0x3FFFF) >> 4);
    mbar_wait(full + r.s * 8, (r.ph >> r.s) & 1);
    if (own && it == 2 && threadIdx.x < 32) TR(N == 128 ? 47 : r.s == 2 ? 29 : 35);
    wg_arrive();
#pragma unroll
    for (int k = 0; k < 4; k++) WG<N>::mma(acc, da + k * 2, db + k * 128);
    wg_commit();
    wg_wait<1>();
    if (lane < 2) mbar_arrive_cl(rel + ps * 8);
    if (own && it == 2 && lane == 0) mbar_arrive(sb + MISC + B_OWN + wg * 8);
    ps = r.s;
    ring_next<NS>(r);
  }
  wg_wait<0>();
  if (lane < 2) mbar_arrive_cl(rel + ps * 8);
}

__device__ __forceinline__ void ln_publish(const float (&v)[64], uint4* st, int j, int row0, int lane, uint32_t ep) {
  float s0 = 0, s1 = 0;
#pragma unroll
  for (int i = 0; i < 16; i++) { s0 += v[4 * i] + v[4 * i + 1]; s1 += v[4 * i + 2] + v[4 * i + 3]; }
  s0 += __shfl_xor_sync(~0u, s0, 1); s1 += __shfl_xor_sync(~0u, s1, 1);
  s0 += __shfl_xor_sync(~0u, s0, 2); s1 += __shfl_xor_sync(~0u, s1, 2);
  s0 *= (1.f / 128); s1 *= (1.f / 128);
  float q0 = 0, q1 = 0, q2 = 0, q3 = 0;
#pragma unroll
  for (int i = 0; i < 16; i++) {
    float a = v[4 * i] - s0, b = v[4 * i + 1] - s0, c = v[4 * i + 2] - s1, d = v[4 * i + 3] - s1;
    q0 = fmaf(a, a, q0); q1 = fmaf(b, b, q1); q2 = fmaf(c, c, q2); q3 = fmaf(d, d, q3);
  }
  q0 += q1; q2 += q3;
  q0 += __shfl_xor_sync(~0u, q0, 1); q2 += __shfl_xor_sync(~0u, q2, 1);
  q0 += __shfl_xor_sync(~0u, q0, 2); q2 += __shfl_xor_sync(~0u, q2, 2);
  int c = lane & 3;
  if (c < 2) st_rlx4(st + j * 128 + row0 + c * 8, __float_as_uint(c ? s1 : s0), ep, __float_as_uint(c ? q2 : q0), ep);
}
__device__ __forceinline__ void ln_gather(const uint4* st, int row0, int lane, uint32_t ep, float& mu0, float& r0, float& mu1, float& r1) {
  const uint4* p = st + (lane & 3) * 256 + row0;
  uint4 a, b, c, d; uint32_t n = 0;
  while (true) {
    a = ld_rlx4(p); b = ld_rlx4(p + 128); c = ld_rlx4(p + 8); d = ld_rlx4(p + 136);
    if (a.y == ep && a.w == ep && b.y == ep && b.w == ep && c.y == ep && c.w == ep && d.y == ep && d.w == ep) break;
    SPIN_GUARD(n);
  }
  __syncwarp();
  float ma = __uint_as_float(a.x), mb = __uint_as_float(b.x), mc = __uint_as_float(c.x), md = __uint_as_float(d.x);
  mu0 = ma + mb; mu1 = mc + md;
  mu0 += __shfl_xor_sync(~0u, mu0, 1); mu1 += __shfl_xor_sync(~0u, mu1, 1);
  mu0 += __shfl_xor_sync(~0u, mu0, 2); mu1 += __shfl_xor_sync(~0u, mu1, 2);
  mu0 *= 0.125f; mu1 *= 0.125f;
  ma -= mu0; mb -= mu0; mc -= mu1; md -= mu1;
  float q0 = __uint_as_float(a.z) + __uint_as_float(b.z) + 128.f * (ma * ma + mb * mb);
  float q1 = __uint_as_float(c.z) + __uint_as_float(d.z) + 128.f * (mc * mc + md * md);
  q0 += __shfl_xor_sync(~0u, q0, 1); q1 += __shfl_xor_sync(~0u, q1, 1);
  q0 += __shfl_xor_sync(~0u, q0, 2); q1 += __shfl_xor_sync(~0u, q1, 2);
  r0 = rsqrtf(q0 * (1.f / 1024) + 1e-5f); r1 = rsqrtf(q1 * (1.f / 1024) + 1e-5f);
}
__device__ __forceinline__ void load_vec(uint32_t* w, uint32_t sb, int sec, int b, int lane) {
#pragma unroll
  for (int q = 0; q < 2; q++) { uint4 t = lds128(sb + MISC + MODV + sec * 256 + (lane & 3) * 64 + b * 32 + q * 16); w[4 * q] = t.x; w[4 * q + 1] = t.y; w[4 * q + 2] = t.z; w[4 * q + 3] = t.w; }
}
__device__ __forceinline__ void stage_done(uint32_t sb, int wg, int b, int lane) {
  fence_async_smem();
  __syncwarp();
  if (lane == 0) mbar_arrive(sb + MISC + B_RDY + (wg * 2 + b) * 8);
}
__device__ __forceinline__ void ln_apply(const float (&v)[64], float mu0, float r0, float mu1, float r1, uint32_t sb, int sec_shift, int sec_scale, uint32_t stg_row, int wg, int lane) {
  uint32_t sc[16], sh[16];
  const float n0 = -mu0 * r0, n1 = -mu1 * r1;
#pragma unroll
  for (int i = 0; i < 16; i += 2) {
    if ((i & 7) == 0) { load_vec(sc + i, sb, sec_scale, i >> 3, lane); load_vec(sh + i, sb, sec_shift, i >> 3, lane); }
    uint32_t w[4];
#pragma unroll
    for (int u = 0; u < 2; u++) {
      int q = i + u;
      float c0 = bf_lo(sc[q]), c1 = bf_hi(sc[q]), s0 = bf_lo(sh[q]), s1 = bf_hi(sh[q]);
      w[2 * u] = pack2(fmaf(fmaf(v[4 * q], r0, n0), c0, s0), fmaf(fmaf(v[4 * q + 1], r0, n0), c1, s1));
      w[2 * u + 1] = pack2(fmaf(fmaf(v[4 * q + 2], r1, n1), c0, s0), fmaf(fmaf(v[4 * q + 3], r1, n1), c1, s1));
    }
    stsm4(stg_row + (i >> 3) * BLK + ((((i & 7) + (lane >> 4)) ^ (lane & 7)) << 4), w[0], w[1], w[2], w[3]);
    if ((i & 7) == 6) stage_done(sb, wg, i >> 3, lane);
  }
}
__device__ __forceinline__ float silu_mul(float g, float u) { float hg = 0.5f * g; return fmaf(hg, tanh_fast(hg), hg) * u; }

__device__ __forceinline__ void gemv_fma(float (&a)[8], uint4 w, float s) {
  a[0] = fmaf(bf_lo(w.x), s, a[0]); a[1] = fmaf(bf_hi(w.x), s, a[1]); a[2] = fmaf(bf_lo(w.y), s, a[2]); a[3] = fmaf(bf_hi(w.y), s, a[3]);
  a[4] = fmaf(bf_lo(w.z), s, a[4]); a[5] = fmaf(bf_hi(w.z), s, a[5]); a[6] = fmaf(bf_lo(w.w), s, a[6]); a[7] = fmaf(bf_hi(w.w), s, a[7]);
}
__device__ __forceinline__ float silu_c(float v) { return bf_round(__fdividef(v, 1.f + __expf(-v))); }
__device__ __forceinline__ float mod_gather(const uint2* p, uint32_t ep) {
  uint2 a, b, c, d; uint32_t n = 0;
  while (true) {
    a = ld_rlx2(p); b = ld_rlx2(p + 128); c = ld_rlx2(p + 256); d = ld_rlx2(p + 384);
    if (a.y == ep && b.y == ep && c.y == ep && d.y == ep) break;
    SPIN_GUARD(n);
  }
  return (__uint_as_float(a.x) + __uint_as_float(b.x)) + (__uint_as_float(c.x) + __uint_as_float(d.x));
}
__device__ __forceinline__ void mod_store(uint32_t sb, int sec, int col, float v) {
  v = bf_round(v);
  if (sec == 1 || sec == 4) v += 1.f;
  sts16(sb + MISC + MODV + sec * 256 + (((col >> 1) & 3) * 16 + (col >> 3)) * 4 + (col & 1) * 2, __float2bfloat16_rn(v));
}

__global__ void __cluster_dims__(2, 1, 1) __launch_bounds__(384, 1)
fused_kernel(const __grid_constant__ Maps maps, const bf16* __restrict__ cvec, const bf16* __restrict__ wmod) {
  extern __shared__ __align__(1024) uint8_t smem_raw[];
  const uint32_t sb = smem_u32(smem_raw);
  const int warp = __shfl_sync(~0u, threadIdx.x >> 5, 0), lane = threadIdx.x & 31;
  const int rank = blockIdx.x & 1, cid = blockIdx.x >> 1;
  const int m = cid >> 2, j = (cid & 3) * 2 + rank;
  const uint32_t bar = sb + MISC;

  if (warp >= 8) {
    asm volatile("setmaxnreg.dec.sync.aligned.u32 72;");
    Ring r4{0, ~0u}, r6{0, ~0u};
    auto wait4 = [&]() { mbar_wait(bar + B_EMPTY4 + r4.s * 8, (r4.ph >> r4.s) & 1); };
    auto wait6 = [&]() { mbar_wait(bar + B_EMPTY6 + r6.s * 8, (r6.ph >> r6.s) & 1); };
    auto old4 = [&](int s6) { int a = (s6 * 2) / 3, b = (s6 * 2 + 1) / 3; mbar_wait(bar + B_EMPTY4 + a * 8, (r4.ph >> a) & 1); mbar_wait(bar + B_EMPTY4 + b * 8, (r4.ph >> b) & 1); };
    auto old6 = [&](int s4) { int a = (s4 * 3) / 2; mbar_wait(bar + B_EMPTY6 + a * 8, (r6.ph >> a) & 1); mbar_wait(bar + B_EMPTY6 + a * 8 + 8, (r6.ph >> (a + 1)) & 1); };
    if (warp == 8) {
      if (lane == 0) {
        if (sb & 1023) bail();
        for (int w = 0; w < 2; w++) mbar_init(bar + B_X + w * 8, 1);
        fence_async_smem();
        for (int w = 0; w < 2; w++) {
          mbar_expect_tx(bar + B_X + w * 8, BLK);
          for (int b = 0; b < 2; b++) tma_3d(sb + STG + b * BLK + w * HALF, &maps.x, bar + B_X + w * 8, j * 128 + b * 64, m * 64, w);
        }
        for (int s = 0; s < 4; s++) { mbar_init(bar + B_FULL4 + s * 8, 2); mbar_init(bar + B_EMPTY4 + s * 8, 16); mbar_init(bar + B_RDY + s * 8, 4); mbar_init(bar + B_FREE + s * 8, 1); }
        for (int s = 0; s < 6; s++) { mbar_init(bar + B_FULL6 + s * 8, 2); mbar_init(bar + B_EMPTY6 + s * 8, 16); }
        mbar_init(bar + B_MOD, 2); mbar_init(bar + B_HALO, 1); mbar_init(bar + B_HALO + 8, 1); mbar_init(bar + B_OWN, 4); mbar_init(bar + B_OWN + 8, 4);
        asm volatile("fence.mbarrier_init.release.cluster;" ::: "memory");
        fence_async_smem();
      }
      __syncwarp();
      cl_arrive_relaxed();
      if (lane == 0) {
        auto ld4 = [&](const CUtensorMap* m0, int a0, const CUtensorMap* m1, int a1, int kb) {
          const uint32_t full = bar + B_FULL4 + r4.s * 8, d = sb + r4.s * 49152 + BLK;
          wait4(); mbar_expect_tx(full, 2 * BLK);
          tma_3d(d, m0, full, 0, kb * 64, a0); tma_3d(d + BLK, m1, full, 0, kb * 64, a1);
          ring_next<4>(r4);
        };
        auto ld6 = [&](const CUtensorMap* m0, int a0, int kb) {
          const uint32_t full = bar + B_FULL6 + r6.s * 8;
          wait6(); mbar_expect_tx(full, BLK);
          tma_3d(sb + r6.s * 32768 + BLK, m0, full, 0, kb * 64, a0);
          ring_next<6>(r6);
        };
        mbar_wait(bar + B_X, 0);
#pragma unroll 1
        for (int it = 0; it < 16; it++) {
          ld4(&maps.wqkv, 16 + 2 * j, &maps.wqkv, 32 + 2 * j, own_order(it, j));
          if (it == 3) { tma_pf(&maps.wqkv, m * 64, 16 + 2 * j); tma_pf(&maps.wqkv, m * 64, 32 + 2 * j); }
          if (it == 10) { tma_pf(&maps.wqkv, m * 64, 2 * j); tma_pf(&maps.wo, m * 64, 2 * j); }
        }
#pragma unroll 1
        for (int it = 0; it < 32; it++) {
          if (it < 6) old4(r6.s);
          if (it == 12) { tma_pf(&maps.w1, m * 64, 2 * j); tma_pf(&maps.w3, m * 64, 2 * j); }
          if (it < 16) ld6(&maps.wqkv, 2 * j, it); else ld6(&maps.wo, 2 * j, own_order(it - 16, j));
        }
        r4.s = 2;
#pragma unroll 1
        for (int it = 0; it < 48; it++) {
          const int a = 2 * ((it >> 4) * 8 + j);
          if (it < 4) old6(r4.s);
          if (it == 8 || it == 24) { tma_pf(&maps.w1, m * 64, a + 16); tma_pf(&maps.w3, m * 64, a + 16); }
          if (it == 36) { tma_pf(&maps.w1s, m * 64, 48 + j); tma_pf(&maps.w3s, m * 64, 48 + j); }
          if (it == 44) tma_pf(&maps.w2, m * 64, 2 * j);
          ld4(&maps.w1, a, &maps.w3, a, it < 16 ? own_order(it, j) : it & 15);
        }
        r6.s = 3;
#pragma unroll 1
        for (int it = 0; it < 16; it++) {
          if (it < 6) old4(r6.s);
          if (it == 8) tma_pf(&maps.w2, (16 + m) * 64, 2 * j);
          const uint32_t full = bar + B_FULL6 + r6.s * 8;
          wait6(); mbar_expect_tx(full, BLK);
          tma_3d(sb + r6.s * 32768 + BLK, &maps.w1s, full, 0, it * 64, 48 + j);
          tma_3d(sb + r6.s * 32768 + BLK + HALF, &maps.w3s, full, 0, it * 64, 48 + j);
          ring_next<6>(r6);
        }
#pragma unroll 1
        for (int it = 0; it < 56; it++) {
          if (it == 8) tma_pf(&maps.w2, (32 + m) * 64, 2 * j);
          if (it == 24 && m < 8) tma_pf(&maps.w2, (48 + m) * 64, 2 * j);
          ld6(&maps.w2, 2 * j, it);
        }
      }
    } else if (warp == 9) {
      if (lane < 9) prefetch_map(&maps.x + lane);
      const uint32_t ep = g_epoch[blockIdx.x] + 1;
      cl_arrive_relaxed(); cl_wait();
      uint32_t mk0 = 0, mk1 = 0; int line = -1;
      auto need = [&](bool both, int u) {
        const int ln = u >> 5;
        if (ln != line || !(((both ? mk1 : mk0) >> (u & 31)) & 1)) {
          uint32_t n = 0;
          line = ln;
          const uint32_t* p = g_flag + m * 256 + ln * 32 + lane;
          do {
            const uint32_t f0 = ld_flag(p + rank * 128), f1 = ld_flag(p + (rank ^ 1) * 128);
            mk0 = __ballot_sync(~0u, f0 == ep); mk1 = mk0 & __ballot_sync(~0u, f1 == ep);
            SPIN_GUARD(n);
          } while (!(((both ? mk1 : mk0) >> (u & 31)) & 1));
          fence_async();
        }
      };
      auto step = [&](uint32_t empty, uint32_t par, uint32_t full, uint32_t slot, const uint4* blk, int u, int own) {
        if (own >= 2) need(own == 14 || own == 15, u);
        mbar_wait(empty, par);
        if (lane == 0) {
          if (own < 2) mbar_arrive(full);
          else {
            mbar_expect_tx(full, BLK);
            if (own == 14 || own == 15) bulk_ld(slot, blk, BLK, full); else bulk_ld_mc(slot + rank * HALF, blk + rank * 512, HALF, full);
          }
        }
      };
      auto step4 = [&](const uint4* blk, int u, int own) { step(bar + B_EMPTY4 + r4.s * 8, (r4.ph >> r4.s) & 1, bar + B_FULL4 + r4.s * 8, sb + r4.s * 49152, blk, u, own); ring_next<4>(r4); };
      auto step6 = [&](const uint4* blk, int u, int own) { step(bar + B_EMPTY6 + r6.s * 8, (r6.ph >> r6.s) & 1, bar + B_FULL6 + r6.s * 8, sb + r6.s * 32768, blk, u, own); ring_next<6>(r6); };
#pragma unroll 1
      for (int ph = 0; ph < 2; ph++) {
        const int uh = ph ? U_H2 : U_H1;
#pragma unroll 1
        for (int it = 0; it < (ph ? 48 : 16); it++) {
          const int kb = it < 16 ? own_order(it, j) : it & 15;
          if (ph && it < 4) old6(r4.s);
          step4(g_h + (m * 16 + kb) * 1024, uh + kb, it);
          if (it == 2) TR(ph ? 34 : 28);
        }
        r4.s = 2;
        if (ph) r6.s = 3;
#pragma unroll 1
        for (int it = 0; it < (ph ? 72 : 32); it++) {
          if (it < 6) old4(r6.s);
          if (it < 16) step6(g_h + (m * 16 + it) * 1024, uh + it, 16);
          else if (ph) step6(g_hh + (m * 56 + it - 16) * 1024, U_HH + it - 16, 16);
          else { const int kb = own_order(it - 16, j); step6(g_o + (m * 16 + kb) * 1024, U_O + kb, it - 16); if (it == 18) TR(46); }
        }
      }
    } else {
      const int wg = warp - 10;
      const uint32_t ep = g_epoch[blockIdx.x] + 1;
      const uint32_t stg = sb + STG + wg * HALF;
      uint32_t* fl = g_flag + m * 256 + wg * 128;
      const int u = m * 2 + wg, sec = 2 + ((u >> 1) & 3), hf = u & 1, ks = u >> 3;
      uint32_t sc[4];
#pragma unroll
      for (int p = 0; p < 4; p++) sc[p] = pack2(silu_c(__bfloat162float(cvec[ks * 256 + p * 64 + lane])), silu_c(__bfloat162float(cvec[ks * 256 + p * 64 + 32 + lane])));
      cl_arrive_relaxed(); cl_wait();
#pragma unroll 1
      for (int e = 0; e < 7; e++) {
        if (lane == 0) {
          const int kb = e < 3 ? 2 * j : e < 6 ? 2 * (8 * (e - 3) + j) : 48 + j;
          uint4* dst = (e == 1 ? g_o + m * 16 * 1024 : e < 3 ? g_h + m * 16 * 1024 : g_hh + m * 56 * 1024) + kb * 1024 + wg * 512;
          const int unit = (e < 3 ? e * 16 : U_HH) + kb;
#pragma unroll 1
          for (int b = 0; b < (e == 6 ? 1 : 2); b++) {
            mbar_wait(bar + B_RDY + (wg * 2 + b) * 8, e & 1);
            if (wg == 0 && b == 0 && e < 3) TR(e == 0 ? 24 : e == 2 ? 30 : 44);
            bulk_st(dst + b * 1024, stg + b * BLK, HALF);
            bulk_commit();
            bulk_wait_all();
            asm volatile("fence.acq_rel.cta;" ::: "memory");
            st_flag(fl + unit + b, ep);
            if (wg == 0 && e < 3) TR((e == 0 ? 26 : e == 2 ? 32 : 42) + b);
            if (e) mbar_arrive(bar + B_FREE + (wg * 2 + b) * 8);
          }
          if (e == 1) {
            mbar_wait(bar + B_OWN + wg * 8, 1);
            mbar_expect_tx(bar + B_X + wg * 8, BLK);
            for (int b = 0; b < 2; b++) tma_3d(stg + b * BLK, &maps.x, bar + B_X + wg * 8, j * 128 + b * 64, m * 64, wg);
          }
        }
        __syncwarp();
        if (e == 0) {
          const bf16* wp = wmod + (size_t)(ks * 256 + (lane >> 3)) * 6144 + sec * 1024 + j * 128 + hf * 64 + (lane & 7) * 8;
          const uint32_t buf = stg + lane * 16;
          auto fetch = [&](int p) {
#pragma unroll 4
            for (int i = 0; i < 16; i++) cp_async16(buf + (p & 1) * BLK + i * 512, wp + (size_t)(p * 64 + i * 4) * 6144);
            asm volatile("cp.async.commit_group;" ::: "memory");
          };
          mbar_wait(bar + B_OWN + wg * 8, 0);
          float a[8] = {0, 0, 0, 0, 0, 0, 0, 0};
#pragma unroll 1
          for (int p = -2; p < 4; p++) {
            if (p >= 0) {
              const uint32_t sp = p == 0 ? sc[0] : p == 1 ? sc[1] : p == 2 ? sc[2] : sc[3];
              if (p < 3) asm volatile("cp.async.wait_group 1;" ::: "memory"); else asm volatile("cp.async.wait_group 0;" ::: "memory");
#pragma unroll 2
              for (int i = 0; i < 8; i++) {
                const uint32_t sv = __shfl_sync(~0u, sp, i * 4 + (lane >> 3));
                const uint4 w0 = lds128(buf + (p & 1) * BLK + i * 512), w1 = lds128(buf + (p & 1) * BLK + 4096 + i * 512);
                gemv_fma(a, w0, bf_lo(sv)); gemv_fma(a, w1, bf_hi(sv));
              }
            }
            if (p < 2) fetch(p + 2);
          }
          __syncwarp();
          if (lane < 2) mbar_arrive(bar + B_FREE + (wg * 2 + lane) * 8);
#pragma unroll
          for (int i = 0; i < 8; i++) { a[i] += __shfl_xor_sync(~0u, a[i], 8); a[i] += __shfl_xor_sync(~0u, a[i], 16); }
          const int q = lane >> 3;
          float v0 = q == 0 ? a[0] : q == 1 ? a[2] : q == 2 ? a[4] : a[6], v1 = q == 0 ? a[1] : q == 1 ? a[3] : q == 2 ? a[5] : a[7];
          st_rlx4((uint4*)(g_modp + ((j * 6 + sec) * 4 + ks) * 128 + hf * 64 + (lane & 7) * 8 + q * 2), __float_as_uint(v0), ep, __float_as_uint(v1), ep);
          if (wg == 0) TR(48);
#pragma unroll 1
          for (int i = 0; i < 4; i++) {
            const int sec = 2 + wg * 2 + (i >> 1), col = (i & 1) * 64 + lane * 2;
            const uint4* p = (const uint4*)(g_modp + (j * 6 + sec) * 512 + col);
            uint4 a, b, c, d; uint32_t n = 0;
            while (true) {
              a = ld_rlx4(p); b = ld_rlx4(p + 64); c = ld_rlx4(p + 128); d = ld_rlx4(p + 192);
              if (a.y == ep && a.w == ep && b.y == ep && b.w == ep && c.y == ep && c.w == ep && d.y == ep && d.w == ep) break;
              SPIN_GUARD(n);
            }
            mod_store(sb, sec, col, (__uint_as_float(a.x) + __uint_as_float(b.x)) + (__uint_as_float(c.x) + __uint_as_float(d.x)));
            mod_store(sb, sec, col + 1, (__uint_as_float(a.z) + __uint_as_float(b.z)) + (__uint_as_float(c.z) + __uint_as_float(d.z)));
          }
          __syncwarp();
          if (lane == 0) mbar_arrive(bar + B_MOD);
          if (wg == 0) TR(50);
          if (m > 0) {
            mbar_wait(bar + B_EMPTY6, 0);
            const uint4* hp = g_halo + ((m * 8 + j) * 2 + wg) * 512 + lane;
#pragma unroll 1
            for (int b = 0; b < 2; b++) {
              uint4 q[8]; uint32_t n = 0;
              while (true) {
                bool ok = true;
#pragma unroll
                for (int i = 0; i < 8; i++) q[i] = ld_rlx4(hp + (b * 8 + i) * 32);
#pragma unroll
                for (int i = 0; i < 8; i++) ok = ok && q[i].y == ep && q[i].w == ep;
                if (ok) break;
                SPIN_GUARD(n);
              }
#pragma unroll
              for (int i = 0; i < 4; i++) sts128(buf + b * BLK + i * 512, q[2 * i].x, q[2 * i].z, q[2 * i + 1].x, q[2 * i + 1].z);
            }
            __syncwarp();
            if (lane == 0) mbar_arrive(bar + B_HALO + wg * 8);
            if (wg == 0) TR(52);
          }
        }
      }
      if (lane == 0) {
        for (int b = 0; b < 2; b++) {
          mbar_wait(bar + B_RDY + (wg * 2 + b) * 8, b ^ 1);
          tma_store_3d(&maps.out, stg + b * BLK, j * 128 + b * 64, m * 64, wg);
        }
        bulk_commit();
        bulk_wait_read();
      }
      TR(40 + wg);
    }
  } else {
    asm volatile("setmaxnreg.inc.sync.aligned.u32 216;");
    const int wg = warp >> 2, wq = warp & 3, tid = threadIdx.x;
    const int g = lane >> 2, c = lane & 3;
    if (warp == 0) TR(0);
    const int sec0 = (m >> 1) & 1, hf0 = m & 1, ks0 = m >> 2;
    const int row0 = wg * 64 + wq * 16 + g;
    if (c < 2) st_rlx4(g_stat + m * 1024 + j * 128 + row0 + c * 8, 0, 0, 0, 0);
    if (tid < 64) st_rlx2(g_modp + ((j * 6 + sec0) * 4 + ks0) * 128 + hf0 * 64 + tid, 0, 0);
    uint4 wv[8];
    {
      const bf16* wp = wmod + (size_t)(ks0 * 256 + warp * 32 + (lane >> 3)) * 6144 + sec0 * 1024 + j * 128 + hf0 * 64 + (lane & 7) * 8;
#pragma unroll
      for (int i = 0; i < 8; i++) wv[i] = ldg_nc(wp + (size_t)i * 4 * 6144);
    }
    const float sc_ = silu_c(__bfloat162float(cvec[ks0 * 256 + warp * 32 + lane]));
    const uint32_t ep = g_epoch[blockIdx.x] + 1;
    cl_arrive_relaxed(); cl_wait();
    const uint32_t rel = mapa(bar, (lane & 1) ^ rank);
    const uint32_t stg_row = sb + STG + (wg * 64 + wq * 16 + (lane & 15)) * 128;
    const uint32_t fre = bar + B_FREE + wg * 16;
    Ring r4{0, 0}, r6{0, 0};
    {
      float v[64];
      mbar_wait(bar + B_X + wg * 8, 0);
#pragma unroll
      for (int i = 0; i < 16; i += 2) {
        uint32_t w0, w1, w2, w3;
        ldsm4(stg_row + (i >> 3) * BLK + ((((i & 7) + (lane >> 4)) ^ (lane & 7)) << 4), w0, w1, w2, w3);
        v[4 * i] = bf_lo(w0); v[4 * i + 1] = bf_hi(w0); v[4 * i + 2] = bf_lo(w1); v[4 * i + 3] = bf_hi(w1);
        v[4 * i + 4] = bf_lo(w2); v[4 * i + 5] = bf_hi(w2); v[4 * i + 6] = bf_lo(w3); v[4 * i + 7] = bf_hi(w3);
      }
      ln_publish(v, g_stat + m * 1024, j, row0, lane, ep);
      if (warp == 0) TR(1);
      float a[8] = {0, 0, 0, 0, 0, 0, 0, 0};
#pragma unroll
      for (int i = 0; i < 8; i++) gemv_fma(a, wv[i], __shfl_sync(~0u, sc_, i * 4 + (lane >> 3)));
#pragma unroll
      for (int i = 0; i < 8; i++) { a[i] += __shfl_xor_sync(~0u, a[i], 8); a[i] += __shfl_xor_sync(~0u, a[i], 16); }
      if (lane < 8) {
        sts128(sb + RED_OFF + warp * 256 + lane * 32, __float_as_uint(a[0]), __float_as_uint(a[1]), __float_as_uint(a[2]), __float_as_uint(a[3]));
        sts128(sb + RED_OFF + warp * 256 + lane * 32 + 16, __float_as_uint(a[4]), __float_as_uint(a[5]), __float_as_uint(a[6]), __float_as_uint(a[7]));
      }
      named_bar(1, 256);
      if (tid < 64) {
        float s = 0;
#pragma unroll
        for (int w = 0; w < 8; w++) s += lds32f(sb + RED_OFF + w * 256 + tid * 4);
        st_rlx2(g_modp + ((j * 6 + sec0) * 4 + ks0) * 128 + hf0 * 64 + tid, __float_as_uint(s), ep);
      }
      if (warp == 0) TR(2);
      float mu0, r0, mu1, r1;
      ln_gather(g_stat + m * 1024, row0, lane, ep, mu0, r0, mu1, r1);
      mod_store(sb, tid >> 7, tid & 127, mod_gather(g_modp + (j * 6 + (tid >> 7)) * 512 + (tid & 127), ep));
      named_bar(1, 256);
      if (warp == 0) TR(3);
      ln_apply(v, mu0, r0, mu1, r1, sb, 0, 1, stg_row, wg, lane);
      named_bar(2 + wg, 128);
    }
    if (warp == 0) TR(4);
    {
      uint32_t kf[32], vf[32];
      const uint32_t xa = sb + STG + wg * HALF + wq * 2048 + lane * 16;
      {
        float acc[128];
        mainloop<256, 4>(acc, 16, true, r4, sb, wg, lane, rel);
        if (warp == 0) TR(5);
#pragma unroll
        for (int i = 0; i < 32; i++) { kf[i] = pack2(acc[2 * i], acc[2 * i + 1]); vf[i] = movm(pack2(acc[64 + 2 * i], acc[65 + 2 * i])); }
      }
      if (wq == 3) {
        if (m < 15) {
          uint4* hp = g_halo + (((m + 1) * 8 + j) * 2 + wg) * 512 + lane;
#pragma unroll
          for (int i = 0; i < 16; i++) st_rlx4(hp + i * 32, kf[2 * i + 1], ep, vf[2 * i + 1], ep);
        }
      } else {
        mbar_wait(fre, 0);
#pragma unroll
        for (int i = 0; i < 8; i++) sts128(xa + 2048 + (i >> 2) * BLK + (i & 3) * 512, kf[4 * i + 1], vf[4 * i + 1], kf[4 * i + 3], vf[4 * i + 3]);
      }
      if (c < 2) st_rlx4(g_stat + (16 + m) * 1024 + j * 128 + row0 + c * 8, 0, 0, 0, 0);
      if (warp == 0) TR(6);
      float acc[64];
      mainloop<128, 6>(acc, 16, false, r6, sb, wg, lane, rel);
      if (warp == 0) TR(7);
      named_bar(2 + wg, 128);
      const bool first = wq == 0 && m == 0;
      if (wq == 0 && m > 0) mbar_wait(bar + B_HALO + wg * 8, 0);
      const bool up0 = 2 * c > g, up1 = 2 * c + 1 > g;
      const uint32_t mup = (up0 ? 0xffffu : 0u) | (up1 ? 0xffff0000u : 0u);
#pragma unroll
      for (int b = 0; b < 2; b++) {
        uint32_t qf[16], pv[16];
#pragma unroll
        for (int i = 0; i < 4; i++) {
          uint4 q = lds128(xa + b * BLK + i * 512);
          if (first) q = make_uint4(0, 0, 0, 0);
          pv[4 * i] = q.x; pv[4 * i + 1] = q.y; pv[4 * i + 2] = q.z; pv[4 * i + 3] = q.w;
        }
#pragma unroll
        for (int i = 0; i < 16; i++) qf[i] = pack2(acc[32 * b + 2 * i], acc[32 * b + 2 * i + 1]);
        __syncwarp();
        uint32_t pa[2], pb[2];
#pragma unroll
        for (int h = 0; h < 2; h++) {
          float s0[4] = {0, 0, 0, 0}, s1[4] = {0, 0, 0, 0}, s2[4] = {0, 0, 0, 0};
#pragma unroll
          for (int ks = 0; ks < 2; ks++) {
            const int i = 4 * h + 2 * ks, k = 16 * b + 2 * i;
            mma16(s1, qf[2 * i], qf[2 * i + 1], qf[2 * i + 2], qf[2 * i + 3], kf[k], kf[k + 2]);
            mma16(s2, qf[2 * i], qf[2 * i + 1], qf[2 * i + 2], qf[2 * i + 3], kf[k + 1], kf[k + 3]);
            mma16(s0, qf[2 * i], qf[2 * i + 1], qf[2 * i + 2], qf[2 * i + 3], pv[2 * i], pv[2 * i + 2]);
          }
          if (first) { s0[0] = -INFINITY; s0[1] = -INFINITY; }
          float a0 = (up0 ? s0[0] : s1[0]) * SCL, a1 = (up1 ? s0[1] : s1[1]) * SCL;
          float b0 = (up0 ? s1[2] : s2[2]) * SCL, b1 = (up1 ? s1[3] : s2[3]) * SCL;
          float ma = fmaxf(a0, a1), mb = fmaxf(b0, b1);
          ma = fmaxf(ma, __shfl_xor_sync(~0u, ma, 1)); mb = fmaxf(mb, __shfl_xor_sync(~0u, mb, 1));
          ma = fmaxf(ma, __shfl_xor_sync(~0u, ma, 2)); mb = fmaxf(mb, __shfl_xor_sync(~0u, mb, 2));
          a0 = ex2(a0 - ma); a1 = ex2(a1 - ma); b0 = ex2(b0 - mb); b1 = ex2(b1 - mb);
          float sa = a0 + a1, sbm = b0 + b1;
          sa += __shfl_xor_sync(~0u, sa, 1); sbm += __shfl_xor_sync(~0u, sbm, 1);
          sa += __shfl_xor_sync(~0u, sa, 2); sbm += __shfl_xor_sync(~0u, sbm, 2);
          sa = __fdividef(1.f, sa); sbm = __fdividef(1.f, sbm);
          pa[h] = pack2(a0 * sa, a1 * sa); pb[h] = pack2(b0 * sbm, b1 * sbm);
        }
#pragma unroll
        for (int i = 0; i < 8; i += 2) {
          uint32_t of[4];
#pragma unroll
          for (int d = 0; d < 2; d++) {
            float o[4] = {0, 0, 0, 0};
            mma16(o, pa[i >> 2] & ~mup, pb[i >> 2] & mup, 0u, pb[i >> 2] & ~mup, vf[16 * b + 2 * (i + d)], vf[16 * b + 2 * (i + d) + 1]);
            mma8(o, pa[i >> 2] & mup, 0u, pv[2 * (i + d) + 1]);
            of[2 * d] = pack2(o[0], o[1]); of[2 * d + 1] = pack2(o[2], o[3]);
          }
          stsm4(stg_row + b * BLK + (((i + (lane >> 4)) ^ (lane & 7)) << 4), of[0], of[1], of[2], of[3]);
        }
        stage_done(sb, wg, b, lane);
      }
      named_bar(1, 256);
      if (warp == 0) TR(8);
    }
    uint32_t x1[32];
    {
      float acc[64];
      mainloop<128, 6>(acc, 16, true, r6, sb, wg, lane, rel);
      if (warp == 0) TR(9);
      mbar_wait(bar + B_MOD, 0);
      mbar_wait(bar + B_X + wg * 8, 1);
      uint32_t ga[16];
      load_vec(ga, sb, 2, 0, lane); load_vec(ga + 8, sb, 2, 1, lane);
#pragma unroll
      for (int i = 0; i < 16; i += 2) {
        uint32_t w[4];
        ldsm4(stg_row + (i >> 3) * BLK + ((((i & 7) + (lane >> 4)) ^ (lane & 7)) << 4), w[0], w[1], w[2], w[3]);
#pragma unroll
        for (int u = 0; u < 2; u++) {
          int q = i + u;
          acc[4 * q] = fmaf(acc[4 * q], bf_lo(ga[q]), bf_lo(w[2 * u])); acc[4 * q + 1] = fmaf(acc[4 * q + 1], bf_hi(ga[q]), bf_hi(w[2 * u]));
          acc[4 * q + 2] = fmaf(acc[4 * q + 2], bf_lo(ga[q]), bf_lo(w[2 * u + 1])); acc[4 * q + 3] = fmaf(acc[4 * q + 3], bf_hi(ga[q]), bf_hi(w[2 * u + 1]));
        }
      }
      ln_publish(acc, g_stat + (16 + m) * 1024, j, row0, lane, ep);
      if (warp == 0) TR(36);
#pragma unroll
      for (int i = 0; i < 32; i++) x1[i] = pack2(acc[2 * i], acc[2 * i + 1]);
      float mu0, r0, mu1, r1;
      ln_gather(g_stat + (16 + m) * 1024, row0, lane, ep, mu0, r0, mu1, r1);
      if (warp == 0) TR(10);
      ln_apply(acc, mu0, r0, mu1, r1, sb, 3, 4, stg_row, wg, lane);
      named_bar(2 + wg, 128);
      if (warp == 0) TR(11);
    }
    r4.s = 2;
#pragma unroll 1
    for (int t = 0; t < 3; t++) {
      float acc[128];
      mainloop<256, 4>(acc, 16, t == 0, r4, sb, wg, lane, rel);
      if (warp == 0) TR(12 + 2 * t);
#pragma unroll
      for (int i = 0; i < 16; i += 2) {
        if ((i & 7) == 0) mbar_wait(fre + i, t & 1);
        uint32_t w[4];
#pragma unroll
        for (int u = 0; u < 4; u++) w[u] = pack2(silu_mul(acc[4 * i + 2 * u], acc[64 + 4 * i + 2 * u]), silu_mul(acc[4 * i + 2 * u + 1], acc[65 + 4 * i + 2 * u]));
        stsm4(stg_row + (i >> 3) * BLK + ((((i & 7) + (lane >> 4)) ^ (lane & 7)) << 4), w[0], w[1], w[2], w[3]);
      }
      fence_async_smem();
      __syncwarp();
      if (lane < 2) mbar_arrive(bar + B_RDY + (wg * 2 + lane) * 8);
      if (warp == 0) TR(13 + 2 * t);
    }
    r6.s = 3;
    {
      float acc[64];
      mainloop<128, 6>(acc, 16, false, r6, sb, wg, lane, rel);
      if (warp == 0) TR(18);
      mbar_wait(fre, 1);
#pragma unroll
      for (int i = 0; i < 8; i += 2) {
        uint32_t w[4];
#pragma unroll
        for (int u = 0; u < 4; u++) w[u] = pack2(silu_mul(acc[4 * i + 2 * u], acc[32 + 4 * i + 2 * u]), silu_mul(acc[4 * i + 2 * u + 1], acc[33 + 4 * i + 2 * u]));
        stsm4(stg_row + (((i + (lane >> 4)) ^ (lane & 7)) << 4), w[0], w[1], w[2], w[3]);
      }
      stage_done(sb, wg, 0, lane);
      if (warp == 0) TR(19);
    }
    {
      float acc[64];
      mainloop<128, 6>(acc, 56, false, r6, sb, wg, lane, rel);
      __syncwarp();
      cl_arrive_relaxed();
      if (warp == 0) TR(20);
      uint32_t gb[16];
      mbar_wait(fre, 0); mbar_wait(fre + 8, 1);
#pragma unroll
      for (int i = 0; i < 16; i += 2) {
        if ((i & 7) == 0) load_vec(gb + i, sb, 5, i >> 3, lane);
        const uint4 x = make_uint4(x1[2 * i], x1[2 * i + 1], x1[2 * i + 2], x1[2 * i + 3]);
        uint32_t w0 = pack2(fmaf(acc[4 * i], bf_lo(gb[i]), bf_lo(x.x)), fmaf(acc[4 * i + 1], bf_hi(gb[i]), bf_hi(x.x)));
        uint32_t w1 = pack2(fmaf(acc[4 * i + 2], bf_lo(gb[i]), bf_lo(x.y)), fmaf(acc[4 * i + 3], bf_hi(gb[i]), bf_hi(x.y)));
        uint32_t w2 = pack2(fmaf(acc[4 * i + 4], bf_lo(gb[i + 1]), bf_lo(x.z)), fmaf(acc[4 * i + 5], bf_hi(gb[i + 1]), bf_hi(x.z)));
        uint32_t w3 = pack2(fmaf(acc[4 * i + 6], bf_lo(gb[i + 1]), bf_lo(x.w)), fmaf(acc[4 * i + 7], bf_hi(gb[i + 1]), bf_hi(x.w)));
        stsm4(stg_row + (i >> 3) * BLK + ((((i & 7) + (lane >> 4)) ^ (lane & 7)) << 4), w0, w1, w2, w3);
        if ((i & 7) == 6) stage_done(sb, wg, i >> 3, lane);
      }
      if (tid == 0) g_epoch[blockIdx.x] = ep;
      if (warp == 0) TR(21);
      cl_wait();
    }
  }
}

typedef CUresult (*EncodeFn)(CUtensorMap*, CUtensorMapDataType, cuuint32_t, void*, const cuuint64_t*, const cuuint64_t*, const cuuint32_t*, const cuuint32_t*,
                             CUtensorMapInterleave, CUtensorMapSwizzle, CUtensorMapL2promotion, CUtensorMapFloatOOBfill);

void make_map(EncodeFn fn, CUtensorMap* mp, const void* base, uint64_t d0, uint64_t d1, uint64_t d2, uint64_t s1, uint64_t s2, uint32_t b2) {
  cuuint64_t d[3] = {d0, d1, d2}, s[2] = {s1, s2};
  cuuint32_t b[3] = {64, 64, b2}, e[3] = {1, 1, 1};
  fn(mp, CU_TENSOR_MAP_DATA_TYPE_BFLOAT16, 3, (void*)base, d, s, b, e, CU_TENSOR_MAP_INTERLEAVE_NONE, CU_TENSOR_MAP_SWIZZLE_128B,
     CU_TENSOR_MAP_L2_PROMOTION_L2_128B, CU_TENSOR_MAP_FLOAT_OOB_FILL_NONE);
}

}

extern "C" void kernel_launch(void* const* d_in, const int* in_sizes, int n_in, void* d_out, int out_size) {
  static EncodeFn fn = nullptr;
  if (!fn) {
    void* p = nullptr; cudaDriverEntryPointQueryResult q;
    cudaGetDriverEntryPoint("cuTensorMapEncodeTiled", &p, cudaEnableDefault, &q);
    fn = (EncodeFn)p;
    cudaFuncSetAttribute(fused_kernel, cudaFuncAttributeMaxDynamicSharedMemorySize, SMEM_BYTES);
  }
  Maps mp;
  make_map(fn, &mp.x, d_in[0], D_, S_ / 2, 2, 4096, 2048, 1);
  make_map(fn, &mp.out, d_out, D_, S_ / 2, 2, 4096, 2048, 1);
  make_map(fn, &mp.wqkv, d_in[1], 64, D_, 3 * D_ / 64, 3 * D_ * 2, 128, 2);
  make_map(fn, &mp.wo, d_in[2], 64, D_, D_ / 64, D_ * 2, 128, 2);
  make_map(fn, &mp.w1, d_in[4], 64, D_, F_ / 64, F_ * 2, 128, 2);
  make_map(fn, &mp.w3, d_in[5], 64, D_, F_ / 64, F_ * 2, 128, 2);
  make_map(fn, &mp.w1s, d_in[4], 64, D_, F_ / 64, F_ * 2, 128, 1);
  make_map(fn, &mp.w3s, d_in[5], 64, D_, F_ / 64, F_ * 2, 128, 1);
  make_map(fn, &mp.w2, d_in[6], 64, F_, D_ / 64, D_ * 2, 128, 2);
  fused_kernel<<<128, 384, SMEM_BYTES>>>(mp, (const bf16*)d_in[7], (const bf16*)d_in[8]);
}
```

```cpp
#include <cuda_runtime.h>
#include <cuda_bf16.h>
#include <cuda.h>
#include <stdint.h>

typedef __nv_bfloat16 bf16;

#define P1 3
#define PA1 41
namespace {

constexpr int S_ = 2048, D_ = 1024, F_ = 3584;
constexpr int BLK = 16384;
constexpr int HALF = 8192;
constexpr int RING = 196608;
constexpr int STG = RING;
constexpr int MISC = RING + 2 * BLK;
constexpr int SMEM_BYTES = MISC + 3072;
constexpr int B_FULL4 = 0, B_EMPTY4 = 32, B_FULL6 = 64, B_EMPTY6 = 112, B_RDY = 160, B_FREE = 176, B_STORED = 192, B_X = 208, B_MOD = 224, B_HALO = 232, B_OWN = 240, B_GO = 248, B_HH = 256, B_ALL = 272, B_REL = 280, B_HH2 = 288, PACE = 296;
constexpr int MODV = 512;
constexpr int RED_OFF = 0;
constexpr float SCL = 0.17677669529663687f * 1.4426950408889634f;
constexpr int U_HH = 64;

struct Maps { CUtensorMap x, out, wqkv, wo, w1, w3, w1s, w3s, w2; };
struct Weights { const bf16 *qkv, *o, *w13[2], *w2; };

__device__ uint4 g_h[16 * 16 * 1024];
#define g_h1 g_h
__device__ uint4 g_o[16 * 16 * 1024];
__device__ uint4 g_hh[16 * 56 * 1024];
__device__ uint4 g_x1[128 * 8 * 256];
__device__ uint2 g_modp[8 * 6 * 4 * 128];
__device__ uint4 g_stat[2 * 16 * 8 * 128];
__device__ uint4 g_halo[16 * 8 * 2 * 512];
__device__ uint32_t g_flag[16 * 128];
__device__ uint32_t g_epoch[128];
__device__ unsigned long long g_pace[4 * 16];
#define TR(i)
#define TRL(i)
#define TRS(i)

__device__ __forceinline__ void bail() { asm volatile("st.global.u32 [%0], %1;" :: "l"(0ull), "r"(0) : "memory"); }
__device__ __forceinline__ uint32_t smem_u32(const void* p) { return (uint32_t)__cvta_generic_to_shared(p); }
__device__ __forceinline__ void mbar_init(uint32_t bar, uint32_t cnt) { asm volatile("mbarrier.init.shared::cta.b64 [%0], %1;" :: "r"(bar), "r"(cnt) : "memory"); }
__device__ __forceinline__ void mbar_expect_tx(uint32_t bar, uint32_t bytes) { asm volatile("mbarrier.arrive.expect_tx.shared::cta.b64 _, [%0], %1;" :: "r"(bar), "r"(bytes) : "memory"); }
__device__ __forceinline__ void mbar_arrive(uint32_t bar) { asm volatile("mbarrier.arrive.shared::cta.b64 _, [%0];" :: "r"(bar) : "memory"); }
__device__ __forceinline__ void mbar_arrive_cl(uint32_t cl_addr) { asm volatile("mbarrier.arrive.shared::cluster.b64 _, [%0];" :: "r"(cl_addr) : "memory"); }
__device__ __forceinline__ uint32_t mapa(uint32_t addr, uint32_t cta) { uint32_t r; asm("mapa.shared::cluster.u32 %0, %1, %2;" : "=r"(r) : "r"(addr), "r"(cta)); return r; }
__device__ __forceinline__ bool mbar_try(uint32_t bar, uint32_t parity) {
  uint32_t ok;
  asm volatile("{\n.reg .pred p;\nmbarrier.try_wait.parity.shared::cta.b64 p, [%1], %2;\nselp.u32 %0, 1, 0, p;\n}" : "=r"(ok) : "r"(bar), "r"(parity) : "memory");
  return ok;
}
__device__ __forceinline__ void mbar_wait(uint32_t bar, uint32_t parity) {
  uint32_t n = 0;
  while (!mbar_try(bar, parity)) { if (++n > (1u << 22)) bail(); }
}
__device__ __forceinline__ void tma_3d(uint32_t dst, const CUtensorMap* m, uint32_t bar, int c0, int c1, int c2) {
  asm volatile("cp.async.bulk.tensor.3d.shared::cluster.global.mbarrier::complete_tx::bytes [%0], [%1, {%3, %4, %5}], [%2];" :: "r"(dst), "l"(m), "r"(bar), "r"(c0), "r"(c1), "r"(c2) : "memory");
}
__device__ __forceinline__ void tma_store_3d(const CUtensorMap* m, uint32_t src, int c0, int c1, int c2) {
  asm volatile("cp.async.bulk.tensor.3d.global.shared::cta.bulk_group [%0, {%2, %3, %4}], [%1];" :: "l"(m), "r"(src), "r"(c0), "r"(c1), "r"(c2) : "memory");
}
__device__ __forceinline__ void bulk_ld(uint32_t dst, const void* src, uint32_t bytes, uint32_t bar) {
  asm volatile("cp.async.bulk.shared::cluster.global.mbarrier::complete_tx::bytes [%0], [%1], %2, [%3];" :: "r"(dst), "l"(src), "r"(bytes), "r"(bar) : "memory");
}
__device__ __forceinline__ void bulk_ld_mc(uint32_t dst, const void* src, uint32_t bytes, uint32_t bar) {
  asm volatile("cp.async.bulk.shared::cluster.global.mbarrier::complete_tx::bytes.multicast::cluster [%0], [%1], %2, [%3], %4;" :: "r"(dst), "l"(src), "r"(bytes), "r"(bar), "h"((uint16_t)3) : "memory");
}
__device__ __forceinline__ void bulk_st(void* dst, uint32_t src, uint32_t bytes) {
  asm volatile("cp.async.bulk.global.shared::cta.bulk_group [%0], [%1], %2;" :: "l"(dst), "r"(src), "r"(bytes) : "memory");
}
__device__ __forceinline__ void bulk_commit() { asm volatile("cp.async.bulk.commit_group;" ::: "memory"); }
__device__ __forceinline__ void bulk_wait_read() { asm volatile("cp.async.bulk.wait_group.read 0;" ::: "memory"); }
__device__ __forceinline__ void bulk_wait_all() { asm volatile("cp.async.bulk.wait_group 0;" ::: "memory"); }
__device__ __forceinline__ void fence_async_global() { asm volatile("fence.proxy.async.global;" ::: "memory"); }
__device__ __forceinline__ void fence_async_smem() { asm volatile("fence.proxy.async.shared::cta;" ::: "memory"); }
__device__ __forceinline__ void wg_arrive() { asm volatile("wgmma.fence.sync.aligned;" ::: "memory"); }
__device__ __forceinline__ void wg_commit() { asm volatile("wgmma.commit_group.sync.aligned;" ::: "memory"); }
template <int N> __device__ __forceinline__ void wg_wait() { asm volatile("wgmma.wait_group.sync.aligned %0;" :: "n"(N) : "memory"); }
__device__ __forceinline__ void cl_arrive_relaxed() { asm volatile("barrier.cluster.arrive.relaxed.aligned;" ::: "memory"); }
__device__ __forceinline__ void cl_wait() { asm volatile("barrier.cluster.wait.acquire.aligned;" ::: "memory"); }
__device__ __forceinline__ bool elect() { uint32_t p; asm volatile("{\n.reg .pred p;\nelect.sync _|p, 0xffffffff;\nselp.u32 %0, 1, 0, p;\n}" : "=r"(p)); return p; }
__device__ __forceinline__ void named_bar(int id, int n) { asm volatile("bar.sync %0, %1;" :: "r"(id), "r"(n) : "memory"); }
__device__ __forceinline__ uint32_t pack2(float lo, float hi) { uint32_t r; asm("cvt.rn.bf16x2.f32 %0, %1, %2;" : "=r"(r) : "f"(hi), "f"(lo)); return r; }
__device__ __forceinline__ float bf_lo(uint32_t w) { return __uint_as_float(w << 16); }
__device__ __forceinline__ float bf_hi(uint32_t w) { return __uint_as_float(w & 0xffff0000u); }
__device__ __forceinline__ float bf_round(float v) { return __bfloat162float(__float2bfloat16_rn(v)); }
__device__ __forceinline__ void stsm4(uint32_t addr, uint32_t a, uint32_t b, uint32_t c, uint32_t d) {
  asm volatile("stmatrix.sync.aligned.m8n8.x4.shared.b16 [%0], {%1, %2, %3, %4};" :: "r"(addr), "r"(a), "r"(b), "r"(c), "r"(d) : "memory");
}
__device__ __forceinline__ void ldsm4(uint32_t addr, uint32_t& a, uint32_t& b, uint32_t& c, uint32_t& d) {
  asm volatile("ldmatrix.sync.aligned.m8n8.x4.shared.b16 {%0, %1, %2, %3}, [%4];" : "=r"(a), "=r"(b), "=r"(c), "=r"(d) : "r"(addr) : "memory");
}
__device__ __forceinline__ uint32_t movm(uint32_t a) { uint32_t r; asm volatile("movmatrix.sync.aligned.m8n8.trans.b16 %0, %1;" : "=r"(r) : "r"(a)); return r; }
__device__ __forceinline__ void mma16(float (&d)[4], uint32_t a0, uint32_t a1, uint32_t a2, uint32_t a3, uint32_t b0, uint32_t b1) {
  asm volatile("mma.sync.aligned.m16n8k16.row.col.f32.bf16.bf16.f32 {%0,%1,%2,%3}, {%4,%5,%6,%7}, {%8,%9}, {%0,%1,%2,%3};"
               : "+f"(d[0]), "+f"(d[1]), "+f"(d[2]), "+f"(d[3]) : "r"(a0), "r"(a1), "r"(a2), "r"(a3), "r"(b0), "r"(b1));
}
__device__ __forceinline__ void mma8(float (&d)[4], uint32_t a0, uint32_t a1, uint32_t b0) {
  asm volatile("mma.sync.aligned.m16n8k8.row.col.f32.bf16.bf16.f32 {%0,%1,%2,%3}, {%4,%5}, {%6}, {%0,%1,%2,%3};"
               : "+f"(d[0]), "+f"(d[1]), "+f"(d[2]), "+f"(d[3]) : "r"(a0), "r"(a1), "r"(b0));
}
__device__ __forceinline__ uint4 lds128(uint32_t a) { uint4 v; asm volatile("ld.shared.v4.u32 {%0,%1,%2,%3}, [%4];" : "=r"(v.x), "=r"(v.y), "=r"(v.z), "=r"(v.w) : "r"(a) : "memory"); return v; }
__device__ __forceinline__ void sts128(uint32_t a, uint32_t x, uint32_t y, uint32_t z, uint32_t w) { asm volatile("st.shared.v4.u32 [%0], {%1,%2,%3,%4};" :: "r"(a), "r"(x), "r"(y), "r"(z), "r"(w) : "memory"); }
__device__ __forceinline__ float lds32f(uint32_t a) { float v; asm volatile("ld.shared.f32 %0, [%1];" : "=f"(v) : "r"(a) : "memory"); return v; }
__device__ __forceinline__ void sts16(uint32_t a, bf16 v) { asm volatile("st.shared.b16 [%0], %1;" :: "r"(a), "h"(__bfloat16_as_ushort(v)) : "memory"); }
__device__ __forceinline__ uint4 ldg_nc(const void* p) { uint4 v; asm volatile("ld.global.nc.L1::no_allocate.v4.u32 {%0,%1,%2,%3}, [%4];" : "=r"(v.x), "=r"(v.y), "=r"(v.z), "=r"(v.w) : "l"(p)); return v; }
__device__ __forceinline__ uint4 ld_rlx4(const uint4* p) {
  unsigned long long a, b; asm volatile("ld.relaxed.gpu.global.v2.b64 {%0,%1}, [%2];" : "=l"(a), "=l"(b) : "l"(p) : "memory");
  return make_uint4((uint32_t)a, (uint32_t)(a >> 32), (uint32_t)b, (uint32_t)(b >> 32));
}
__device__ __forceinline__ uint2 ld_rlx2(const uint2* p) { unsigned long long a; asm volatile("ld.relaxed.gpu.global.b64 %0, [%1];" : "=l"(a) : "l"(p) : "memory"); return make_uint2((uint32_t)a, (uint32_t)(a >> 32)); }
__device__ __forceinline__ void st_rlx4(uint4* p, uint32_t x, uint32_t y, uint32_t z, uint32_t w) {
  asm volatile("st.relaxed.gpu.global.v2.b64 [%0], {%1,%2};" :: "l"(p), "l"((unsigned long long)x | ((unsigned long long)y << 32)), "l"((unsigned long long)z | ((unsigned long long)w << 32)) : "memory");
}
__device__ __forceinline__ void st_rlx2(uint2* p, uint32_t x, uint32_t y) { asm volatile("st.relaxed.gpu.global.b64 [%0], %1;" :: "l"(p), "l"((unsigned long long)x | ((unsigned long long)y << 32)) : "memory"); }
__device__ __forceinline__ void st_release(uint32_t* p, uint32_t v) { asm volatile("st.release.gpu.global.u32 [%0], %1;" :: "l"(p), "r"(v) : "memory"); }
__device__ __forceinline__ uint32_t ld_acquire(const uint32_t* p) { uint32_t v; asm volatile("ld.acquire.gpu.global.u32 %0, [%1];" : "=r"(v) : "l"(p) : "memory"); return v; }
__device__ __forceinline__ void cp_async16(uint32_t dst, const void* src) { asm volatile("cp.async.cg.shared.global [%0], [%1], 16;" :: "r"(dst), "l"(src) : "memory"); }
__device__ __forceinline__ void prefetch_map(const CUtensorMap* m) { asm volatile("prefetch.tensormap [%0];" :: "l"(m) : "memory"); }
__device__ __forceinline__ unsigned long long gtime() { unsigned long long t; asm volatile("mov.u64 %0, %%globaltimer;" : "=l"(t)); return t; }
__device__ __forceinline__ void pace(uint32_t addr) {
  uint32_t d; asm volatile("ld.shared.u32 %0, [%1];" : "=r"(d) : "r"(addr) : "memory");
  if (d) { const unsigned long long t = gtime() + d; while (gtime() < t) {} }
}
__device__ __forceinline__ float ex2(float x) { float r; asm("ex2.approx.ftz.f32 %0, %1;" : "=f"(r) : "f"(x)); return r; }
__device__ __forceinline__ float tanh_fast(float x) { float r; asm("tanh.approx.f32 %0, %1;" : "=f"(r) : "f"(x)); return r; }
#define SPIN_GUARD(n) if (++(n) > (1u << 24)) bail()

__device__ __forceinline__ void wgmma_n128(float (&d)[64], uint64_t da, uint64_t db) {
  asm volatile("wgmma.mma_async.sync.aligned.m64n128k16.f32.bf16.bf16 "
    "{%0, %1, %2, %3, %4, %5, %6, %7, %8, %9, %10, %11, %12, %13, %14, %15, %16, %17, %18, %19, %20, %21, %22, %23, %24, %25, %26, %27, %28, %29, %30, %31, %32, %33, %34, %35, %36, %37, %38, %39, %40, %41, %42, %43, %44, %45, %46, %47, %48, %49, %50, %51, %52, %53, %54, %55, %56, %57, %58, %59, %60, %61, %62, %63}, "
    "%64, %65, 1, 1, 1, 0, 1;\n"
    : "+f"(d[0]), "+f"(d[1]), "+f"(d[2]), "+f"(d[3]), "+f"(d[4]), "+f"(d[5]), "+f"(d[6]), "+f"(d[7]), "+f"(d[8]), "+f"(d[9]), "+f"(d[10]), "+f"(d[11]), "+f"(d[12]), "+f"(d[13]), "+f"(d[14]), "+f"(d[15]), "+f"(d[16]), "+f"(d[17]), "+f"(d[18]), "+f"(d[19]), "+f"(d[20]), "+f"(d[21]), "+f"(d[22]), "+f"(d[23]), "+f"(d[24]), "+f"(d[25]), "+f"(d[26]), "+f"(d[27]), "+f"(d[28]), "+f"(d[29]), "+f"(d[30]), "+f"(d[31]), "+f"(d[32]), "+f"(d[33]), "+f"(d[34]), "+f"(d[35]), "+f"(d[36]), "+f"(d[37]), "+f"(d[38]), "+f"(d[39]), "+f"(d[40]), "+f"(d[41]), "+f"(d[42]), "+f"(d[43]), "+f"(d[44]), "+f"(d[45]), "+f"(d[46]), "+f"(d[47]), "+f"(d[48]), "+f"(d[49]), "+f"(d[50]), "+f"(d[51]), "+f"(d[52]), "+f"(d[53]), "+f"(d[54]), "+f"(d[55]), "+f"(d[56]), "+f"(d[57]), "+f"(d[58]), "+f"(d[59]), "+f"(d[60]), "+f"(d[61]), "+f"(d[62]), "+f"(d[63])
    : "l"(da), "l"(db));
}
__device__ __forceinline__ void wgmma_n128_first(float (&d)[64], uint64_t da, uint64_t db) {
  asm volatile("wgmma.mma_async.sync.aligned.m64n128k16.f32.bf16.bf16 "
    "{%0, %1, %2, %3, %4, %5, %6, %7, %8, %9, %10, %11, %12, %13, %14, %15, %16, %17, %18, %19, %20, %21, %22, %23, %24, %25, %26, %27, %28, %29, %30, %31, %32, %33, %34, %35, %36, %37, %38, %39, %40, %41, %42, %43, %44, %45, %46, %47, %48, %49, %50, %51, %52, %53, %54, %55, %56, %57, %58, %59, %60, %61, %62, %63}, "
    "%64, %65, 0, 1, 1, 0, 1;\n"
    : "=f"(d[0]), "=f"(d[1]), "=f"(d[2]), "=f"(d[3]), "=f"(d[4]), "=f"(d[5]), "=f"(d[6]), "=f"(d[7]), "=f"(d[8]), "=f"(d[9]), "=f"(d[10]), "=f"(d[11]), "=f"(d[12]), "=f"(d[13]), "=f"(d[14]), "=f"(d[15]), "=f"(d[16]), "=f"(d[17]), "=f"(d[18]), "=f"(d[19]), "=f"(d[20]), "=f"(d[21]), "=f"(d[22]), "=f"(d[23]), "=f"(d[24]), "=f"(d[25]), "=f"(d[26]), "=f"(d[27]), "=f"(d[28]), "=f"(d[29]), "=f"(d[30]), "=f"(d[31]), "=f"(d[32]), "=f"(d[33]), "=f"(d[34]), "=f"(d[35]), "=f"(d[36]), "=f"(d[37]), "=f"(d[38]), "=f"(d[39]), "=f"(d[40]), "=f"(d[41]), "=f"(d[42]), "=f"(d[43]), "=f"(d[44]), "=f"(d[45]), "=f"(d[46]), "=f"(d[47]), "=f"(d[48]), "=f"(d[49]), "=f"(d[50]), "=f"(d[51]), "=f"(d[52]), "=f"(d[53]), "=f"(d[54]), "=f"(d[55]), "=f"(d[56]), "=f"(d[57]), "=f"(d[58]), "=f"(d[59]), "=f"(d[60]), "=f"(d[61]), "=f"(d[62]), "=f"(d[63])
    : "l"(da), "l"(db));
}
__device__ __forceinline__ void wgmma_n256(float (&d)[128], uint64_t da, uint64_t db) {
  asm volatile("wgmma.mma_async.sync.aligned.m64n256k16.f32.bf16.bf16 "
    "{%0, %1, %2, %3, %4, %5, %6, %7, %8, %9, %10, %11, %12, %13, %14, %15, %16, %17, %18, %19, %20, %21, %22, %23, %24, %25, %26, %27, %28, %29, %30, %31, %32, %33, %34, %35, %36, %37, %38, %39, %40, %41, %42, %43, %44, %45, %46, %47, %48, %49, %50, %51, %52, %53, %54, %55, %56, %57, %58, %59, %60, %61, %62, %63, %64, %65, %66, %67, %68, %69, %70, %71, %72, %73, %74, %75, %76, %77, %78, %79, %80, %81, %82, %83, %84, %85, %86, %87, %88, %89, %90, %91, %92, %93, %94, %95, %96, %97, %98, %99, %100, %101, %102, %103, %104, %105, %106, %107, %108, %109, %110, %111, %112, %113, %114, %115, %116, %117, %118, %119, %120, %121, %122, %123, %124, %125, %126, %127}, "
    "%128, %129, 1, 1, 1, 0, 1;\n"
    : "+f"(d[0]), "+f"(d[1]), "+f"(d[2]), "+f"(d[3]), "+f"(d[4]), "+f"(d[5]), "+f"(d[6]), "+f"(d[7]), "+f"(d[8]), "+f"(d[9]), "+f"(d[10]), "+f"(d[11]), "+f"(d[12]), "+f"(d[13]), "+f"(d[14]), "+f"(d[15]), "+f"(d[16]), "+f"(d[17]), "+f"(d[18]), "+f"(d[19]), "+f"(d[20]), "+f"(d[21]), "+f"(d[22]), "+f"(d[23]), "+f"(d[24]), "+f"(d[25]), "+f"(d[26]), "+f"(d[27]), "+f"(d[28]), "+f"(d[29]), "+f"(d[30]), "+f"(d[31]), "+f"(d[32]), "+f"(d[33]), "+f"(d[34]), "+f"(d[35]), "+f"(d[36]), "+f"(d[37]), "+f"(d[38]), "+f"(d[39]), "+f"(d[40]), "+f"(d[41]), "+f"(d[42]), "+f"(d[43]), "+f"(d[44]), "+f"(d[45]), "+f"(d[46]), "+f"(d[47]), "+f"(d[48]), "+f"(d[49]), "+f"(d[50]), "+f"(d[51]), "+f"(d[52]), "+f"(d[53]), "+f"(d[54]), "+f"(d[55]), "+f"(d[56]), "+f"(d[57]), "+f"(d[58]), "+f"(d[59]), "+f"(d[60]), "+f"(d[61]), "+f"(d[62]), "+f"(d[63]), "+f"(d[64]), "+f"(d[65]), "+f"(d[66]), "+f"(d[67]), "+f"(d[68]), "+f"(d[69]), "+f"(d[70]), "+f"(d[71]), "+f"(d[72]), "+f"(d[73]), "+f"(d[74]), "+f"(d[75]), "+f"(d[76]), "+f"(d[77]), "+f"(d[78]), "+f"(d[79]), "+f"(d[80]), "+f"(d[81]), "+f"(d[82]), "+f"(d[83]), "+f"(d[84]), "+f"(d[85]), "+f"(d[86]), "+f"(d[87]), "+f"(d[88]), "+f"(d[89]), "+f"(d[90]), "+f"(d[91]), "+f"(d[92]), "+f"(d[93]), "+f"(d[94]), "+f"(d[95]), "+f"(d[96]), "+f"(d[97]), "+f"(d[98]), "+f"(d[99]), "+f"(d[100]), "+f"(d[101]), "+f"(d[102]), "+f"(d[103]), "+f"(d[104]), "+f"(d[105]), "+f"(d[106]), "+f"(d[107]), "+f"(d[108]), "+f"(d[109]), "+f"(d[110]), "+f"(d[111]), "+f"(d[112]), "+f"(d[113]), "+f"(d[114]), "+f"(d[115]), "+f"(d[116]), "+f"(d[117]), "+f"(d[118]), "+f"(d[119]), "+f"(d[120]), "+f"(d[121]), "+f"(d[122]), "+f"(d[123]), "+f"(d[124]), "+f"(d[125]), "+f"(d[126]), "+f"(d[127])
    : "l"(da), "l"(db));
}
__device__ __forceinline__ void wgmma_n256_first(float (&d)[128], uint64_t da, uint64_t db) {
  asm volatile("wgmma.mma_async.sync.aligned.m64n256k16.f32.bf16.bf16 "
    "{%0, %1, %2, %3, %4, %5, %6, %7, %8, %9, %10, %11, %12, %13, %14, %15, %16, %17, %18, %19, %20, %21, %22, %23, %24, %25, %26, %27, %28, %29, %30, %31, %32, %33, %34, %35, %36, %37, %38, %39, %40, %41, %42, %43, %44, %45, %46, %47, %48, %49, %50, %51, %52, %53, %54, %55, %56, %57, %58, %59, %60, %61, %62, %63, %64, %65, %66, %67, %68, %69, %70, %71, %72, %73, %74, %75, %76, %77, %78, %79, %80, %81, %82, %83, %84, %85, %86, %87, %88, %89, %90, %91, %92, %93, %94, %95, %96, %97, %98, %99, %100, %101, %102, %103, %104, %105, %106, %107, %108, %109, %110, %111, %112, %113, %114, %115, %116, %117, %118, %119, %120, %121, %122, %123, %124, %125, %126, %127}, "
    "%128, %129, 0, 1, 1, 0, 1;\n"
    : "=f"(d[0]), "=f"(d[1]), "=f"(d[2]), "=f"(d[3]), "=f"(d[4]), "=f"(d[5]), "=f"(d[6]), "=f"(d[7]), "=f"(d[8]), "=f"(d[9]), "=f"(d[10]), "=f"(d[11]), "=f"(d[12]), "=f"(d[13]), "=f"(d[14]), "=f"(d[15]), "=f"(d[16]), "=f"(d[17]), "=f"(d[18]), "=f"(d[19]), "=f"(d[20]), "=f"(d[21]), "=f"(d[22]), "=f"(d[23]), "=f"(d[24]), "=f"(d[25]), "=f"(d[26]), "=f"(d[27]), "=f"(d[28]), "=f"(d[29]), "=f"(d[30]), "=f"(d[31]), "=f"(d[32]), "=f"(d[33]), "=f"(d[34]), "=f"(d[35]), "=f"(d[36]), "=f"(d[37]), "=f"(d[38]), "=f"(d[39]), "=f"(d[40]), "=f"(d[41]), "=f"(d[42]), "=f"(d[43]), "=f"(d[44]), "=f"(d[45]), "=f"(d[46]), "=f"(d[47]), "=f"(d[48]), "=f"(d[49]), "=f"(d[50]), "=f"(d[51]), "=f"(d[52]), "=f"(d[53]), "=f"(d[54]), "=f"(d[55]), "=f"(d[56]), "=f"(d[57]), "=f"(d[58]), "=f"(d[59]), "=f"(d[60]), "=f"(d[61]), "=f"(d[62]), "=f"(d[63]), "=f"(d[64]), "=f"(d[65]), "=f"(d[66]), "=f"(d[67]), "=f"(d[68]), "=f"(d[69]), "=f"(d[70]), "=f"(d[71]), "=f"(d[72]), "=f"(d[73]), "=f"(d[74]), "=f"(d[75]), "=f"(d[76]), "=f"(d[77]), "=f"(d[78]), "=f"(d[79]), "=f"(d[80]), "=f"(d[81]), "=f"(d[82]), "=f"(d[83]), "=f"(d[84]), "=f"(d[85]), "=f"(d[86]), "=f"(d[87]), "=f"(d[88]), "=f"(d[89]), "=f"(d[90]), "=f"(d[91]), "=f"(d[92]), "=f"(d[93]), "=f"(d[94]), "=f"(d[95]), "=f"(d[96]), "=f"(d[97]), "=f"(d[98]), "=f"(d[99]), "=f"(d[100]), "=f"(d[101]), "=f"(d[102]), "=f"(d[103]), "=f"(d[104]), "=f"(d[105]), "=f"(d[106]), "=f"(d[107]), "=f"(d[108]), "=f"(d[109]), "=f"(d[110]), "=f"(d[111]), "=f"(d[112]), "=f"(d[113]), "=f"(d[114]), "=f"(d[115]), "=f"(d[116]), "=f"(d[117]), "=f"(d[118]), "=f"(d[119]), "=f"(d[120]), "=f"(d[121]), "=f"(d[122]), "=f"(d[123]), "=f"(d[124]), "=f"(d[125]), "=f"(d[126]), "=f"(d[127])
    : "l"(da), "l"(db));
}

template <int N> struct WG;
#define DEF_WG(N) template <> struct WG<N> { \
  static __device__ __forceinline__ void mma(float (&d)[N / 2], uint64_t a, uint64_t b) { wgmma_n##N(d, a, b); } \
  static __device__ __forceinline__ void first(float (&d)[N / 2], uint64_t a, uint64_t b) { wgmma_n##N##_first(d, a, b); } };
DEF_WG(128) DEF_WG(256)

constexpr uint64_t DESC_A = (1ull << 62) | ((uint64_t)(1024 >> 4) << 32) | (1ull << 16);
constexpr uint64_t DESC_B = (1ull << 62) | ((uint64_t)(1024 >> 4) << 32) | ((uint64_t)(8192 >> 4) << 16);

struct Ring { int s; uint32_t ph; int wrap; };
template <int NS> __device__ __forceinline__ void ring_next(Ring& r) { r.s = (r.s + 1 == NS) ? 0 : r.s + 1; if (r.s == r.wrap) r.ph ^= 1; }

__device__ __forceinline__ int own_order(int it, int j) {
  return it < 2 ? 2 * j + it : it == 2 ? 2 * (j ^ 1) : it == P1 ? 2 * (j ^ 1) + 1 : it < 10 ? ((j >> 1) * 4 + 2 * it - (it > P1 ? 4 : 2)) & 15 : ((j >> 1) * 4 + 2 * it - 15) & 15;
}

template <int N, int NS, class Hook>
__device__ __forceinline__ void mainloop(float (&acc)[N / 2], int nkb, bool own, Ring& r, uint32_t sb, int wg, int lane, uint32_t rel_base, int step0, Hook hook) {
  constexpr int SLOT = RING / NS;
  const uint32_t full = sb + MISC + (NS == 4 ? B_FULL4 : B_FULL6);
  const uint32_t rel = rel_base + (NS == 4 ? B_EMPTY4 : B_EMPTY6);
  {
    uint32_t sa = (own ? sb + STG : sb + r.s * SLOT) + wg * HALF, sbb = sb + r.s * SLOT + BLK;
    uint64_t da = DESC_A | (uint64_t)((sa & 0x3FFFF) >> 4), db = DESC_B | (uint64_t)((sbb & 0x3FFFF) >> 4);
    mbar_wait(full + r.s * 8, r.ph);
    TRS(step0);
    wg_arrive();
    WG<N>::first(acc, da, db);
#pragma unroll
    for (int k = 1; k < 4; k++) WG<N>::mma(acc, da + k * 2, db + k * 128);
    wg_commit();
  }
  int ps = r.s;
  ring_next<NS>(r);
#pragma unroll 1
  for (int it = 1; it < nkb; it++) {
    uint32_t sa = ((own && it == 1) ? sb + STG + BLK : sb + r.s * SLOT) + wg * HALF, sbb = sb + r.s * SLOT + BLK;
    uint64_t da = DESC_A | (uint64_t)((sa & 0x3FFFF) >> 4), db = DESC_B | (uint64_t)((sbb & 0x3FFFF) >> 4);
    mbar_wait(full + r.s * 8, r.ph);
    TRS(step0 + it);
    wg_arrive();
#pragma unroll
    for (int k = 0; k < 4; k++) WG<N>::mma(acc, da + k * 2, db + k * 128);
    wg_commit();
    hook(it);
    wg_wait<1>();
    if (lane < 2) mbar_arrive_cl(rel + ps * 8);
    if (own && it == 2 && lane == 0) mbar_arrive(sb + MISC + B_OWN);
    ps = r.s;
    ring_next<NS>(r);
  }
  wg_wait<0>();
  if (lane < 2) mbar_arrive_cl(rel + ps * 8);
}

__device__ __forceinline__ void ln_publish(const float (&v)[64], uint4* st, int j, int row0, int lane, uint32_t ep) {
  float s0 = 0, s1 = 0, s2 = 0, s3 = 0, q0 = 0, q1 = 0, q2 = 0, q3 = 0;
#pragma unroll
  for (int i = 0; i < 16; i++) {
    s0 += v[4 * i]; s1 += v[4 * i + 1]; s2 += v[4 * i + 2]; s3 += v[4 * i + 3];
    q0 = fmaf(v[4 * i], v[4 * i], q0); q1 = fmaf(v[4 * i + 1], v[4 * i + 1], q1); q2 = fmaf(v[4 * i + 2], v[4 * i + 2], q2); q3 = fmaf(v[4 * i + 3], v[4 * i + 3], q3);
  }
  s0 += s1; s2 += s3; q0 += q1; q2 += q3;
  const bool odd = lane & 1;
  float s = (odd ? s2 : s0) + __shfl_xor_sync(~0u, odd ? s0 : s2, 1), q = (odd ? q2 : q0) + __shfl_xor_sync(~0u, odd ? q0 : q2, 1);
  s += __shfl_xor_sync(~0u, s, 2); q += __shfl_xor_sync(~0u, q, 2);
  if ((lane & 3) < 2) st_rlx4(st + j * 128 + row0 + (lane & 1) * 8, __float_as_uint(s), ep, __float_as_uint(q), ep);
}
__device__ __forceinline__ void ln_gather(const uint4* st, int row0, int lane, uint32_t ep, float& n0, float& r0, float& n1, float& r1) {
  const uint4* p = st + (lane & 2) * 256 + row0 + (lane & 1) * 8;
  uint4 a, b, c, d; uint32_t n = 0;
  while (true) {
    a = ld_rlx4(p); b = ld_rlx4(p + 128); c = ld_rlx4(p + 256); d = ld_rlx4(p + 384);
    if (a.y == ep && a.w == ep && b.y == ep && b.w == ep && c.y == ep && c.w == ep && d.y == ep && d.w == ep) break;
    SPIN_GUARD(n);
  }
  __syncwarp();
  float s = (__uint_as_float(a.x) + __uint_as_float(b.x)) + (__uint_as_float(c.x) + __uint_as_float(d.x));
  float q = (__uint_as_float(a.z) + __uint_as_float(b.z)) + (__uint_as_float(c.z) + __uint_as_float(d.z));
  s += __shfl_xor_sync(~0u, s, 2); q += __shfl_xor_sync(~0u, q, 2);
  s *= 1.f / 1024;
  const float r = rsqrtf(fmaxf(fmaf(-s, s, q * (1.f / 1024)), 0.f) + 1e-5f), nn = -s * r;
  const float ro = __shfl_xor_sync(~0u, r, 1), no = __shfl_xor_sync(~0u, nn, 1);
  const bool odd = lane & 1;
  r0 = odd ? ro : r; n0 = odd ? no : nn; r1 = odd ? r : ro; n1 = odd ? nn : no;
}
__device__ __forceinline__ void load_vec(uint32_t* w, uint32_t sb, int sec, int b, int lane) {
#pragma unroll
  for (int q = 0; q < 2; q++) { uint4 t = lds128(sb + MISC + MODV + sec * 256 + (lane & 3) * 64 + b * 32 + q * 16); w[4 * q] = t.x; w[4 * q + 1] = t.y; w[4 * q + 2] = t.z; w[4 * q + 3] = t.w; }
}
__device__ __forceinline__ void stage_done(uint32_t sb, int wg, int b, int lane) {
  fence_async_smem();
  __syncwarp();
  if (lane == 0) mbar_arrive(sb + MISC + B_RDY + b * 8);
}
__device__ __forceinline__ uint32_t hfma2(uint32_t a, uint32_t b, uint32_t c) { uint32_t r; asm("fma.rn.bf16x2 %0, %1, %2, %3;" : "=r"(r) : "r"(a), "r"(b), "r"(c)); return r; }
__device__ __forceinline__ void ln_apply(const float (&v)[64], float n0, float r0, float n1, float r1, uint32_t sb, int sec_shift, int sec_scale, uint32_t stg_row, int wg, int lane) {
  uint32_t sc[16], sh[16];
#pragma unroll
  for (int i = 0; i < 16; i += 2) {
    if ((i & 7) == 0) { load_vec(sc + i, sb, sec_scale, i >> 3, lane); load_vec(sh + i, sb, sec_shift, i >> 3, lane); }
    if (i == 8) asm volatile("" : "+f"(r0), "+f"(r1) :: "memory");
    uint32_t w[4];
#pragma unroll
    for (int u = 0; u < 2; u++) {
      int q = i + u;
      w[2 * u] = hfma2(pack2(fmaf(v[4 * q], r0, n0), fmaf(v[4 * q + 1], r0, n0)), sc[q], sh[q]);
      w[2 * u + 1] = hfma2(pack2(fmaf(v[4 * q + 2], r1, n1), fmaf(v[4 * q + 3], r1, n1)), sc[q], sh[q]);
    }
    stsm4(stg_row + (i >> 3) * BLK + ((((i & 7) + (lane >> 4)) ^ (lane & 7)) << 4), w[0], w[1], w[2], w[3]);
    if ((i & 7) == 6) stage_done(sb, wg, i >> 3, lane);
  }
}
__device__ __forceinline__ float silu_mul(float g, float u) { float hg = 0.5f * g; return fmaf(hg, tanh_fast(hg), hg) * u; }

__device__ __forceinline__ void gemv_fma(float (&a)[8], uint4 w, float s) {
  a[0] = fmaf(bf_lo(w.x), s, a[0]); a[1] = fmaf(bf_hi(w.x), s, a[1]); a[2] = fmaf(bf_lo(w.y), s, a[2]); a[3] = fmaf(bf_hi(w.y), s, a[3]);
  a[4] = fmaf(bf_lo(w.z), s, a[4]); a[5] = fmaf(bf_hi(w.z), s, a[5]); a[6] = fmaf(bf_lo(w.w), s, a[6]); a[7] = fmaf(bf_hi(w.w), s, a[7]);
}
__device__ __forceinline__ float silu_c(float v) { return bf_round(__fdividef(v, 1.f + __expf(-v))); }
__device__ __forceinline__ float mod_gather(const uint2* p, uint32_t ep) {
  uint2 a, b, c, d; uint32_t n = 0;
  while (true) {
    a = ld_rlx2(p); b = ld_rlx2(p + 128); c = ld_rlx2(p + 256); d = ld_rlx2(p + 384);
    if (a.y == ep && b.y == ep && c.y == ep && d.y == ep) break;
    SPIN_GUARD(n);
  }
  return (__uint_as_float(a.x) + __uint_as_float(b.x)) + (__uint_as_float(c.x) + __uint_as_float(d.x));
}
__device__ __forceinline__ void mod_store(uint32_t sb, int sec, int col, float v) {
  v = bf_round(v);
  if (sec == 1 || sec == 4) v += 1.f;
  sts16(sb + MISC + MODV + sec * 256 + (((col >> 1) & 3) * 16 + (col >> 3)) * 4 + (col & 1) * 2, __float2bfloat16_rn(v));
}

__global__ void __cluster_dims__(2, 1, 1) __launch_bounds__(384, 1)
fused_kernel(const __grid_constant__ Maps maps, const bf16* __restrict__ cvec, const bf16* __restrict__ wmod, const __grid_constant__ Weights wt) {
  extern __shared__ __align__(1024) uint8_t smem_raw[];
  const uint32_t sb = smem_u32(smem_raw);
  const int warp = __shfl_sync(~0u, threadIdx.x >> 5, 0), lane = threadIdx.x & 31;
  const int rank = blockIdx.x & 1, cid = blockIdx.x >> 1;
  const int m = cid >> 2, j = (cid & 3) * 2 + rank;
  const uint32_t bar = sb + MISC;

  if (warp >= 8) {
    asm volatile("setmaxnreg.dec.sync.aligned.u32 56;");
    if (warp < 10) {
      uint32_t s6 = 0, p6 = 1;
      auto next6 = [&]() { if (++s6 == 6) { s6 = 0; p6 ^= 1; } };
      auto drained4 = [&](int q, int late) { if (q < 5) mbar_wait(bar + B_EMPTY4 + (((late ? 0x10332 : 0x32110) >> (4 * q)) & 3) * 8, 1); };
      auto drained6 = [&](int q) { if (q < 3) mbar_wait(bar + B_EMPTY6 + ((0x154 >> (4 * q)) & 7) * 8, q >> 1); };
      auto skip6 = [&]() { mbar_wait(bar + B_EMPTY6 + s6 * 8, p6); if (elect()) mbar_arrive(bar + B_FULL6 + s6 * 8); next6(); };
      if (warp == 8) {
        if (lane == 0) {
          if (sb & 1023) bail();
          for (int b = 0; b < 2; b++) mbar_init(bar + B_X + b * 8, 1);
          fence_async_smem();
          for (int b = 0; b < 2; b++) { mbar_expect_tx(bar + B_X + b * 8, BLK); tma_3d(sb + STG + b * BLK, &maps.x, bar + B_X + b * 8, j * 128 + b * 64, m * 64, 0); }
          for (int s = 0; s < 4; s++) { mbar_init(bar + B_FULL4 + s * 8, 2); mbar_init(bar + B_EMPTY4 + s * 8, 16); }
          for (int s = 0; s < 6; s++) { mbar_init(bar + B_FULL6 + s * 8, 2); mbar_init(bar + B_EMPTY6 + s * 8, 16); }
          for (int b = 0; b < 2; b++) { mbar_init(bar + B_RDY + b * 8, 8); mbar_init(bar + B_FREE + b * 8, 1); mbar_init(bar + B_STORED + b * 8, 1); mbar_init(bar + B_HH + b * 8, 1); }
          mbar_init(bar + B_MOD, 2); mbar_init(bar + B_HALO, 2); mbar_init(bar + B_GO, 1); mbar_init(bar + B_ALL, 1); mbar_init(bar + B_REL, 1); mbar_init(bar + B_HH2, 1); mbar_init(bar + B_OWN, 8);
          asm volatile("fence.mbarrier_init.release.cluster;" ::: "memory");
          fence_async_smem();
        }
        __syncwarp();
        cl_arrive_relaxed();
        auto wide = [&](int s, int par, const CUtensorMap* m0, int a0, const CUtensorMap* m1, int a1, int kb) {
          const uint32_t full = bar + B_FULL4 + s * 8, d = sb + s * 49152 + BLK;
          mbar_wait(full + 32, par);
          if (elect()) { mbar_expect_tx(full, 2 * BLK); tma_3d(d, m0, full, 0, kb * 64, a0); tma_3d(d + BLK, m1, full, 0, kb * 64, a1); }
        };
        auto narrow = [&](const CUtensorMap* m0, int kb) {
          const uint32_t full = bar + B_FULL6 + s6 * 8;
          mbar_wait(full + 48, p6);
          if (elect()) { mbar_expect_tx(full, BLK); tma_3d(sb + s6 * 32768 + BLK, m0, full, 0, kb * 64, 2 * j); }
          next6();
        };
#pragma unroll 1
        for (int it = 0; it < 16; it++) {
          if (it == 2) mbar_wait(bar + B_GO, 0);
          wide(it & 3, ~(it >> 2) & 1, &maps.wqkv, 16 + 2 * j, &maps.wqkv, 32 + 2 * j, own_order(it, j));
        }
#pragma unroll 1
        for (int it = 0; it < 16; it++) { drained4(it, 0); narrow(&maps.wqkv, it); }
#pragma unroll 1
        for (int it = 0; it < 16; it++) narrow(&maps.wo, own_order(it, j));
        skip6();
#pragma unroll 1
        for (int it = 0; it < 48; it++) {
          const int a = (it & 48) + 2 * j;
          drained6(it);
          wide((it + 2) & 3, ~(it >> 2) & 1, &maps.w1, a, &maps.w3, a, it < 16 ? own_order(it, j) : it & 15);
        }
#pragma unroll 1
        for (int it = 0; it < 16; it++) {
          const uint32_t full = bar + B_FULL6 + s6 * 8, d = sb + s6 * 32768 + BLK;
          drained4(it, 1);
          mbar_wait(full + 48, p6);
          if (elect()) { mbar_expect_tx(full, BLK); tma_3d(d, &maps.w1s, full, 0, it * 64, 48 + j); tma_3d(d + HALF, &maps.w3s, full, 0, it * 64, 48 + j); }
          next6();
        }
#pragma unroll 1
        for (int it = 0; it < 56; it++) narrow(&maps.w2, it);
      } else {
        if (lane < 9) prefetch_map(&maps.x + lane);
        const uint32_t ep = g_epoch[blockIdx.x] + 1;
        cl_arrive_relaxed(); cl_wait();
        const uint32_t to_peer = mapa(sb, rank ^ 1) - sb;
        auto plain = [&](uint32_t full, uint32_t empty, int par, uint32_t slot, const uint4* blk) {
          mbar_wait(empty, par);
          if (elect()) { mbar_expect_tx(full, BLK); bulk_ld_mc(slot + rank * HALF, blk + rank * 512, HALF, full); }
        };
        auto plain6 = [&](const uint4* blk) { plain(bar + B_FULL6 + s6 * 8, bar + B_EMPTY6 + s6 * 8, p6, sb + s6 * 32768, blk); next6(); };
        uint32_t ready = 0;
        auto poll = [&](int e) { ready = __ballot_sync(~0u, ld_acquire(g_flag + m * 128 + e * 16 + (lane & 15)) == ep); };
        auto need = [&](int e, uint32_t mask) {
          if ((ready & mask) != mask) {
            uint32_t n = 0;
            do { poll(e); SPIN_GUARD(n); } while ((ready & mask) != mask);
            fence_async_global();
          }
        };
        auto fresh = [&](int e, int it, uint32_t full, uint32_t empty, int par, uint32_t slot, uint4* src) {
          if (it >= 3 && it != P1) {
            const int kb = own_order(it, j);
            if (it < 10) need(e, 1u << kb); else if (it == 10) mbar_wait(bar + B_ALL, e & 1);
            plain(full, empty, par, slot, src + kb * 1024);
          } else {
            if (it == 0) { poll(e); ready = 0; }
            mbar_wait(empty, par);
            if (it < 2) { if (elect()) mbar_arrive(full); }
            else {
              const int b = it > 2;
              if (elect()) mbar_expect_tx(full, BLK);
              mbar_wait(bar + (b ? B_STORED + 8 : B_RDY), e & 1);
              if (b == 0) TR(e == 0 ? 24 : e == 2 ? 30 : 44);
              if (elect()) {
                if (b == 0) {
                  bulk_st(src + 2 * j * 1024, sb + STG, BLK);
                  bulk_commit();
                  bulk_wait_all();
                  mbar_arrive(bar + B_STORED);
                }
                fence_async_global();
                bulk_ld(slot + to_peer, src + (2 * j + b) * 1024, BLK, full + to_peer);
              }
              __syncwarp();
            }
          }
          if (it == (P1 == 3 ? 4 : 3)) TR(e == 0 ? 28 : e == 1 ? 46 : 34);
        };
#pragma unroll 1
        for (int ph = 0; ph < 2; ph++) {
          uint4* h = (ph ? g_h : g_h1) + m * 16384;
#pragma unroll 1
          for (int it = 0; it < 16; it++) {
            const int s = (it + 2 * ph) & 3;
            if (ph) drained6(it);
            fresh(2 * ph, it, bar + B_FULL4 + s * 8, bar + B_EMPTY4 + s * 8, ~(it >> 2) & 1, sb + s * 49152, h);
          }
          if (ph) {
#pragma unroll 1
            for (int it = 16; it < 48; it++) { const int s = (it + 2) & 3; plain(bar + B_FULL4 + s * 8, bar + B_EMPTY4 + s * 8, ~(it >> 2) & 1, sb + s * 49152, h + (it & 15) * 1024); }
          }
#pragma unroll 1
          for (int it = 0; it < 16; it++) { drained4(it, ph); plain6(h + it * 1024); }
          if (!ph) {
#pragma unroll 1
            for (int it = 0; it < 16; it++) { fresh(1, it, bar + B_FULL6 + s6 * 8, bar + B_EMPTY6 + s6 * 8, p6, sb + s6 * 32768, g_o + m * 16384); next6(); }
            skip6();
          }
        }
#pragma unroll 1
        for (int it = 0; it < 56; it++) {
          if (it == 0 || it == 32 || it == 48) mbar_wait(bar + (it == 48 ? B_HH2 : B_HH + (it >> 2)), 0);
          plain6(g_hh + m * 57344 + it * 1024);
        }
      }
    } else {
      const int b = warp - 10;
      const uint32_t ep = g_epoch[blockIdx.x] + 1;
      const uint32_t stg = sb + STG + b * BLK;
      const int u = m * 2 + b, sec = 2 + ((u >> 1) & 3), hf = u & 1, ks = u >> 3;
      uint32_t sc[4];
#pragma unroll
      for (int p = 0; p < 4; p++) sc[p] = pack2(silu_c(__bfloat162float(cvec[ks * 256 + p * 64 + lane])), silu_c(__bfloat162float(cvec[ks * 256 + p * 64 + 32 + lane])));
      cl_arrive_relaxed(); cl_wait();
      auto pf = [&](const bf16* w, int ld, int kb, int col) {
      };
      auto all_there = [&](int u, uint32_t done) {
        const uint32_t* fl = g_flag + m * 128 + u;
        uint32_t n = 0;
        while (!__all_sync(~0u, ld_acquire(fl) == ep)) { __nanosleep(100); SPIN_GUARD(n); }
        fence_async_global();
        if (lane == 0) mbar_arrive(done);
      };
      mbar_wait(bar + B_GO, 0);
      pf(wt.qkv, 3 * D_, m, (1 + b) * D_ + j * 128);
#pragma unroll 1
      for (int e = 0; e < 7 - b; e++) {
        const int kb = (e < 3 ? 2 * j : e < 6 ? 2 * (8 * (e - 3) + j) : 48 + j) + b;
        if (lane == 0) {
          if (e < 3) mbar_wait(bar + B_STORED, e & 1);
          if (e >= 3 || b) {
            mbar_wait(bar + B_RDY + b * 8, e & 1);
            bulk_st((e == 0 ? g_h1 + m * 16384 : e == 1 ? g_o + m * 16384 : e == 2 ? g_h + m * 16384 : g_hh + m * 57344) + kb * 1024, stg, BLK);
            bulk_commit();
            bulk_wait_all();
            if (e < 3) { mbar_arrive(bar + B_STORED + 8); TR(53 + e); }
          }
          if (e) mbar_arrive(bar + B_FREE + b * 8);
          st_release(g_flag + m * 128 + (e < 3 ? e * 16 : U_HH) + kb, ep);
          if (e < 3) TR((e == 0 ? 26 : e == 2 ? 32 : 42) + b);
          if (e == 1) {
            mbar_wait(bar + B_OWN, 1);
            mbar_expect_tx(bar + B_X + b * 8, BLK);
            tma_3d(stg, &maps.x, bar + B_X + b * 8, j * 128 + b * 64, m * 64, 0);
          }
        }
        __syncwarp();
        if (e < 3 && b) all_there(e * 16 + (lane & 15), bar + B_ALL);
        if (e == 4 && b) all_there(U_HH + lane, bar + B_HH);
        if (e >= 1 && e <= 3) pf(wt.w13[b], F_, m, (e - 1) * 1024 + j * 128);
        if (e == 4) { if ((j & 1) == b) { pf(wt.w13[0], F_, m, 3072 + (j >> 1) * 128); pf(wt.w13[1], F_, m, 3072 + (j >> 1) * 128); } else pf(wt.w2, D_, m, j * 128); }
        if (e == 5) pf(wt.w2, D_, 16 + 2 * m + b, j * 128);
        if (e == 6 && m < 8) pf(wt.w2, D_, 48 + m, j * 128);
        if (e == 0) {
          const bf16* wp = wmod + (size_t)(ks * 256 + (lane >> 3)) * 6144 + sec * 1024 + j * 128 + hf * 64 + (lane & 7) * 8;
          const uint32_t buf = stg + lane * 16;
          auto fetch = [&](int p) {
#pragma unroll 4
            for (int i = 0; i < 16; i++) cp_async16(buf + (p & 1) * HALF + i * 512, wp + (size_t)(p * 64 + i * 4) * 6144);
            asm volatile("cp.async.commit_group;" ::: "memory");
          };
          mbar_wait(bar + B_OWN, 0);
          float a[8] = {0, 0, 0, 0, 0, 0, 0, 0};
#pragma unroll 1
          for (int p = -2; p < 4; p++) {
            if (p >= 0) {
              const uint32_t sp = p == 0 ? sc[0] : p == 1 ? sc[1] : p == 2 ? sc[2] : sc[3];
              if (p < 3) asm volatile("cp.async.wait_group 1;" ::: "memory"); else asm volatile("cp.async.wait_group 0;" ::: "memory");
#pragma unroll 2
              for (int i = 0; i < 8; i++) {
                const uint32_t sv = __shfl_sync(~0u, sp, i * 4 + (lane >> 3));
                const uint4 w0 = lds128(buf + (p & 1) * HALF + i * 512), w1 = lds128(buf + (p & 1) * HALF + 4096 + i * 512);
                gemv_fma(a, w0, bf_lo(sv)); gemv_fma(a, w1, bf_hi(sv));
              }
            }
            if (p < 2) fetch(p + 2);
          }
          __syncwarp();
          if (lane == 0) mbar_arrive(bar + B_FREE + b * 8);
#pragma unroll
          for (int i = 0; i < 8; i++) { a[i] += __shfl_xor_sync(~0u, a[i], 8); a[i] += __shfl_xor_sync(~0u, a[i], 16); }
          const int q = lane >> 3;
          float v0 = q == 0 ? a[0] : q == 1 ? a[2] : q == 2 ? a[4] : a[6], v1 = q == 0 ? a[1] : q == 1 ? a[3] : q == 2 ? a[5] : a[7];
          st_rlx4((uint4*)(g_modp + ((j * 6 + sec) * 4 + ks) * 128 + hf * 64 + (lane & 7) * 8 + q * 2), __float_as_uint(v0), ep, __float_as_uint(v1), ep);
          if (b == 0) TR(48);
          if (b) pf(wt.o, D_, m, j * 128); else pf(wt.qkv, 3 * D_, m, j * 128);
          if (m > 0) {
            mbar_wait(bar + B_EMPTY6, 0);
#pragma unroll 1
            for (int w = 0; w < 2; w++) {
              const uint4* hp = g_halo + ((m * 8 + j) * 2 + w) * 512 + b * 256 + lane;
              uint4 q[8]; uint32_t n = 0;
              while (true) {
                bool ok = true;
#pragma unroll
                for (int i = 0; i < 8; i++) q[i] = ld_rlx4(hp + i * 32);
#pragma unroll
                for (int i = 0; i < 8; i++) ok = ok && q[i].y == ep && q[i].w == ep;
                if (ok) break;
                SPIN_GUARD(n);
              }
#pragma unroll
              for (int i = 0; i < 4; i++) sts128(buf + w * HALF + i * 512, q[2 * i].x, q[2 * i].z, q[2 * i + 1].x, q[2 * i + 1].z);
            }
            __syncwarp();
            if (lane == 0) mbar_arrive(bar + B_HALO);
            if (b == 0) TR(52);
          }
#pragma unroll 1
          for (int i = 0; i < 4; i++) {
            const int sec = 2 + b * 2 + (i >> 1), col = (i & 1) * 64 + lane * 2;
            const uint4* p = (const uint4*)(g_modp + (j * 6 + sec) * 512 + col);
            uint4 a, b, c, d; uint32_t n = 0;
            while (true) {
              a = ld_rlx4(p); b = ld_rlx4(p + 64); c = ld_rlx4(p + 128); d = ld_rlx4(p + 192);
              if (a.y == ep && a.w == ep && b.y == ep && b.w == ep && c.y == ep && c.w == ep && d.y == ep && d.w == ep) break;
              SPIN_GUARD(n);
            }
            mod_store(sb, sec, col, (__uint_as_float(a.x) + __uint_as_float(b.x)) + (__uint_as_float(c.x) + __uint_as_float(d.x)));
            mod_store(sb, sec, col + 1, (__uint_as_float(a.z) + __uint_as_float(b.z)) + (__uint_as_float(c.z) + __uint_as_float(d.z)));
          }
          __syncwarp();
          if (lane == 0) mbar_arrive(bar + B_MOD);
          if (b == 0) TR(50);
        }
      }
      if (b) { all_there(U_HH + 32 + (lane & 15), bar + B_HH + 8); all_there(U_HH + 48 + (lane & 7), bar + B_HH2); }
      if (lane == 0) {
        mbar_wait(bar + B_RDY + b * 8, b ^ 1);
        tma_store_3d(&maps.out, stg, j * 128 + b * 64, m * 64, 0);
        bulk_commit();
        bulk_wait_read();
      }
      TR(40 + b);
    }
  } else {
    asm volatile("setmaxnreg.inc.sync.aligned.u32 224;");
    const int wg = warp >> 2, wq = warp & 3, tid = threadIdx.x;
    const int g = lane >> 2, c = lane & 3;
    if (warp == 0) TR(0);
    const int sec0 = (m >> 1) & 1, hf0 = m & 1, ks0 = m >> 2;
    const int row0 = wg * 64 + wq * 16 + g;
    if (c < 2) st_rlx4(g_stat + m * 1024 + j * 128 + row0 + c * 8, 0, 0, 0, 0);
    if (tid < 64) st_rlx2(g_modp + ((j * 6 + sec0) * 4 + ks0) * 128 + hf0 * 64 + tid, 0, 0);
    uint4 wv[8];
    {
      const bf16* wp = wmod + (size_t)(ks0 * 256 + warp * 32 + (lane >> 3)) * 6144 + sec0 * 1024 + j * 128 + hf0 * 64 + (lane & 7) * 8;
#pragma unroll
      for (int i = 0; i < 8; i++) wv[i] = ldg_nc(wp + (size_t)i * 4 * 6144);
    }
    const float sc_ = silu_c(__bfloat162float(cvec[ks0 * 256 + warp * 32 + lane]));
    const uint32_t ep = g_epoch[blockIdx.x] + 1;
    cl_arrive_relaxed(); cl_wait();
    const uint32_t rel = mapa(bar, (lane & 1) ^ rank);
    const uint32_t stg_row = sb + STG + (wg * 64 + wq * 16 + (lane & 15)) * 128;
    const uint32_t fre = bar + B_FREE;
    Ring r4{0, 0, 0}, r6{0, 0, 0};
    {
      float v[64];
      mbar_wait(bar + B_X, 0); mbar_wait(bar + B_X + 8, 0);
#pragma unroll
      for (int i = 0; i < 16; i += 2) {
        uint32_t w0, w1, w2, w3;
        ldsm4(stg_row + (i >> 3) * BLK + ((((i & 7) + (lane >> 4)) ^ (lane & 7)) << 4), w0, w1, w2, w3);
        v[4 * i] = bf_lo(w0); v[4 * i + 1] = bf_hi(w0); v[4 * i + 2] = bf_lo(w1); v[4 * i + 3] = bf_hi(w1);
        v[4 * i + 4] = bf_lo(w2); v[4 * i + 5] = bf_hi(w2); v[4 * i + 6] = bf_lo(w3); v[4 * i + 7] = bf_hi(w3);
      }
      ln_publish(v, g_stat + m * 1024, j, row0, lane, ep);
      if (warp == 0) TR(1);
      float a[8] = {0, 0, 0, 0, 0, 0, 0, 0};
#pragma unroll
      for (int i = 0; i < 8; i++) gemv_fma(a, wv[i], __shfl_sync(~0u, sc_, i * 4 + (lane >> 3)));
#pragma unroll
      for (int i = 0; i < 8; i++) { a[i] += __shfl_xor_sync(~0u, a[i], 8); a[i] += __shfl_xor_sync(~0u, a[i], 16); }
      if (lane < 8) {
        sts128(sb + RED_OFF + warp * 256 + lane * 32, __float_as_uint(a[0]), __float_as_uint(a[1]), __float_as_uint(a[2]), __float_as_uint(a[3]));
        sts128(sb + RED_OFF + warp * 256 + lane * 32 + 16, __float_as_uint(a[4]), __float_as_uint(a[5]), __float_as_uint(a[6]), __float_as_uint(a[7]));
      }
      named_bar(1, 256);
      if (tid == 64) mbar_arrive(bar + B_GO);
      if (tid < 64) {
        float s = 0;
#pragma unroll
        for (int w = 0; w < 8; w++) s += lds32f(sb + RED_OFF + w * 256 + tid * 4);
        st_rlx2(g_modp + ((j * 6 + sec0) * 4 + ks0) * 128 + hf0 * 64 + tid, __float_as_uint(s), ep);
      }
      if (warp == 0) TR(2);
      float mu0, r0, mu1, r1;
      ln_gather(g_stat + m * 1024, row0, lane, ep, mu0, r0, mu1, r1);
      mod_store(sb, tid >> 7, tid & 127, mod_gather(g_modp + (j * 6 + (tid >> 7)) * 512 + (tid & 127), ep));
      named_bar(1, 256);
      if (warp == 0) TR(3);
      ln_apply(v, mu0, r0, mu1, r1, sb, 0, 1, stg_row, wg, lane);
      named_bar(2 + wg, 128);
    }
    if (warp == 0) TR(4);
    {
      uint32_t kf[32], vf[32];
      const uint32_t xa = sb + STG + wg * HALF + wq * 2048 + lane * 16;
      {
        float acc[128];
        mainloop<256, 4>(acc, 16, true, r4, sb, wg, lane, rel, 0, [](int) {});
        if (warp == 0) TR(5);
#pragma unroll
        for (int i = 0; i < 32; i++) { kf[i] = pack2(acc[2 * i], acc[2 * i + 1]); vf[i] = pack2(acc[64 + 2 * i], acc[65 + 2 * i]); }
      }
      if (warp == 0) TR(6);
      float acc[64];
      mainloop<128, 6>(acc, 16, false, r6, sb, wg, lane, rel, 16, [&](int it) {
#pragma unroll
        for (int q = 0; q < 4; q++) {
          if (it == 1 + q) {
#pragma unroll
            for (int i = 8 * q; i < 8 * q + 8; i++) vf[i] = movm(vf[i]);
            if (wq == 3) {
              if (m < 15) {
                uint4* hp = g_halo + (((m + 1) * 8 + j) * 2 + wg) * 512 + lane;
#pragma unroll
                for (int i = 4 * q; i < 4 * q + 4; i++) st_rlx4(hp + i * 32, kf[2 * i + 1], ep, vf[2 * i + 1], ep);
              }
            } else {
              if ((q & 1) == 0) mbar_wait(fre + 4 * q, 0);
#pragma unroll
              for (int i = 2 * q; i < 2 * q + 2; i++) sts128(xa + 2048 + (i >> 2) * BLK + (i & 3) * 512, kf[4 * i + 1], vf[4 * i + 1], kf[4 * i + 3], vf[4 * i + 3]);
            }
          }
        }
        if (it == 5 && c < 2) st_rlx4(g_stat + (16 + m) * 1024 + j * 128 + row0 + c * 8, 0, 0, 0, 0);
      });
      if (warp == 0) TR(7);
      named_bar(2 + wg, 128);
      const bool first = wq == 0 && m == 0;
      if (wq == 0 && m > 0) mbar_wait(bar + B_HALO, 0);
      const bool up0 = 2 * c > g, up1 = 2 * c + 1 > g;
      const uint32_t mup = (up0 ? 0xffffu : 0u) | (up1 ? 0xffff0000u : 0u);
#pragma unroll
      for (int b = 0; b < 2; b++) {
        uint32_t qf[16], pv[16];
#pragma unroll
        for (int i = 0; i < 4; i++) {
          uint4 q = lds128(xa + b * BLK + i * 512);
          if (first) q = make_uint4(0, 0, 0, 0);
          pv[4 * i] = q.x; pv[4 * i + 1] = q.y; pv[4 * i + 2] = q.z; pv[4 * i + 3] = q.w;
        }
#pragma unroll
        for (int i = 0; i < 16; i++) qf[i] = pack2(acc[32 * b + 2 * i], acc[32 * b + 2 * i + 1]);
        __syncwarp();
        uint32_t pa[2], pb[2];
#pragma unroll
        for (int h = 0; h < 2; h++) {
          float s0[4] = {0, 0, 0, 0}, s1[4] = {0, 0, 0, 0}, s2[4] = {0, 0, 0, 0};
#pragma unroll
          for (int ks = 0; ks < 2; ks++) {
            const int i = 4 * h + 2 * ks, k = 16 * b + 2 * i;
            mma16(s1, qf[2 * i], qf[2 * i + 1], qf[2 * i + 2], qf[2 * i + 3], kf[k], kf[k + 2]);
            mma16(s2, qf[2 * i], qf[2 * i + 1], qf[2 * i + 2], qf[2 * i + 3], kf[k + 1], kf[k + 3]);
            mma16(s0, qf[2 * i], qf[2 * i + 1], qf[2 * i + 2], qf[2 * i + 3], pv[2 * i], pv[2 * i + 2]);
          }
          if (first) { s0[0] = -INFINITY; s0[1] = -INFINITY; }
          float a0 = (up0 ? s0[0] : s1[0]) * SCL, a1 = (up1 ? s0[1] : s1[1]) * SCL;
          float b0 = (up0 ? s1[2] : s2[2]) * SCL, b1 = (up1 ? s1[3] : s2[3]) * SCL;
          float ma = fmaxf(a0, a1), mb = fmaxf(b0, b1);
          ma = fmaxf(ma, __shfl_xor_sync(~0u, ma, 1)); mb = fmaxf(mb, __shfl_xor_sync(~0u, mb, 1));
          ma = fmaxf(ma, __shfl_xor_sync(~0u, ma, 2)); mb = fmaxf(mb, __shfl_xor_sync(~0u, mb, 2));
          a0 = ex2(a0 - ma); a1 = ex2(a1 - ma); b0 = ex2(b0 - mb); b1 = ex2(b1 - mb);
          float sa = a0 + a1, sbm = b0 + b1;
          sa += __shfl_xor_sync(~0u, sa, 1); sbm += __shfl_xor_sync(~0u, sbm, 1);
          sa += __shfl_xor_sync(~0u, sa, 2); sbm += __shfl_xor_sync(~0u, sbm, 2);
          sa = __fdividef(1.f, sa); sbm = __fdividef(1.f, sbm);
          pa[h] = pack2(a0 * sa, a1 * sa); pb[h] = pack2(b0 * sbm, b1 * sbm);
        }
#pragma unroll
        for (int i = 0; i < 8; i += 2) {
          uint32_t of[4];
#pragma unroll
          for (int d = 0; d < 2; d++) {
            float o[4] = {0, 0, 0, 0};
            mma16(o, pa[i >> 2] & ~mup, pb[i >> 2] & mup, 0u, pb[i >> 2] & ~mup, vf[16 * b + 2 * (i + d)], vf[16 * b + 2 * (i + d) + 1]);
            mma8(o, pa[i >> 2] & mup, 0u, pv[2 * (i + d) + 1]);
            of[2 * d] = pack2(o[0], o[1]); of[2 * d + 1] = pack2(o[2], o[3]);
          }
          stsm4(stg_row + b * BLK + (((i + (lane >> 4)) ^ (lane & 7)) << 4), of[0], of[1], of[2], of[3]);
        }
        stage_done(sb, wg, b, lane);
      }
      named_bar(1, 256);
      if (warp == 0) TR(8);
    }
    uint32_t pk[64];
    {
      float acc[64];
      mainloop<128, 6>(acc, 16, true, r6, sb, wg, lane, rel, 32, [&](int it) {
        if (it == 14) {
          mbar_wait(bar + B_MOD, 0);
          mbar_wait(bar + B_X, 1); mbar_wait(bar + B_X + 8, 1);
          load_vec(pk + 32, sb, 2, 0, lane); load_vec(pk + 40, sb, 2, 1, lane);
#pragma unroll
          for (int i = 0; i < 16; i += 2) ldsm4(stg_row + (i >> 3) * BLK + ((((i & 7) + (lane >> 4)) ^ (lane & 7)) << 4), pk[2 * i], pk[2 * i + 1], pk[2 * i + 2], pk[2 * i + 3]);
        }
      });
      if (warp == 0) TR(9);
#pragma unroll
      for (int i = 0; i < 32; i++) {
        acc[2 * i] = fmaf(acc[2 * i], bf_lo(pk[32 + (i >> 1)]), bf_lo(pk[i]));
        acc[2 * i + 1] = fmaf(acc[2 * i + 1], bf_hi(pk[32 + (i >> 1)]), bf_hi(pk[i]));
      }
      ln_publish(acc, g_stat + (16 + m) * 1024, j, row0, lane, ep);
      if (warp == 0) TR(36);
      mbar_wait(bar + B_FULL6 + 16, 1);
      if (lane < 2) mbar_arrive_cl(rel + B_EMPTY6 + 16);
      ring_next<6>(r6);
#pragma unroll
      for (int i = 0; i < 32; i++) pk[i] = pack2(acc[2 * i], acc[2 * i + 1]);
      float mu0, r0, mu1, r1;
      ln_gather(g_stat + (16 + m) * 1024, row0, lane, ep, mu0, r0, mu1, r1);
      if (warp == 0) TR(10);
      ln_apply(acc, mu0, r0, mu1, r1, sb, 3, 4, stg_row, wg, lane);
      named_bar(2 + wg, 128);
      if (warp == 0) TR(11);
    }
    uint4* const x1p = g_x1 + blockIdx.x * 2048 + tid;
    auto swiglu = [&](int q, int uo, int par) {
      if ((q & 3) == 0) mbar_wait(fre + 2 * q, par);
      uint32_t w[4];
#pragma unroll
      for (int u = 0; u < 4; u++) {
        const uint32_t gg = pk[4 * q + u], uu = pk[uo + 4 * q + u];
        w[u] = pack2(silu_mul(bf_lo(gg), bf_lo(uu)), silu_mul(bf_hi(gg), bf_hi(uu)));
      }
      stsm4(stg_row + (q >> 2) * BLK + ((((2 * q & 7) + (lane >> 4)) ^ (lane & 7)) << 4), w[0], w[1], w[2], w[3]);
      if ((q & 3) == 3) stage_done(sb, wg, q >> 2, lane);
    };
    r4.s = r4.wrap = 2;
#pragma unroll 1
    for (int t = 0; t < 3; t++) {
      float acc[128];
      mainloop<256, 4>(acc, 16, t == 0, r4, sb, wg, lane, rel, 48 + 16 * t, [&](int it) {
        if (t == 0) {
          if (it == 8) {
#pragma unroll
            for (int i = 0; i < 8; i++) x1p[i * 256] = make_uint4(pk[4 * i], pk[4 * i + 1], pk[4 * i + 2], pk[4 * i + 3]);
          }
        } else {
#pragma unroll
          for (int q = 0; q < 4; q++) if (it == 1 + q) { swiglu(2 * q, 32, ~t & 1); swiglu(2 * q + 1, 32, ~t & 1); }
        }
      });
      if (warp == 0) TR(12 + 2 * t);
#pragma unroll
      for (int i = 0; i < 64; i++) pk[i] = pack2(acc[2 * i], acc[2 * i + 1]);
      if (warp == 0) TR(13 + 2 * t);
    }
    {
      float acc[64];
      mainloop<128, 6>(acc, 16, false, r6, sb, wg, lane, rel, 96, [&](int it) {
#pragma unroll
        for (int q = 0; q < 8; q++) if (it == 1 + q) swiglu(q, 32, 0);
      });
      if (warp == 0) TR(18);
#pragma unroll
      for (int i = 0; i < 32; i++) pk[i] = pack2(acc[2 * i], acc[2 * i + 1]);
      if (warp == 0) TR(19);
    }
    {
      float acc[64];
      mainloop<128, 6>(acc, 56, false, r6, sb, wg, lane, rel, 112, [&](int it) {
#pragma unroll
        for (int q = 0; q < 4; q++) if (it == 1 + q) swiglu(q, 16, 1);
        if (it == 40) {
#pragma unroll
          for (int i = 0; i < 8; i++) { const uint4 x = x1p[i * 256]; pk[4 * i] = x.x; pk[4 * i + 1] = x.y; pk[4 * i + 2] = x.z; pk[4 * i + 3] = x.w; }
          load_vec(pk + 32, sb, 5, 0, lane); load_vec(pk + 40, sb, 5, 1, lane);
          mbar_wait(fre, 0); mbar_wait(fre + 8, 1);
        }
      });
      __syncwarp();
      cl_arrive_relaxed();
      if (warp == 0) TR(20);
#pragma unroll
      for (int i = 0; i < 16; i += 2) {
        uint32_t w[4];
#pragma unroll
        for (int u = 0; u < 4; u++) {
          const int q = 2 * i + u;
          w[u] = pack2(fmaf(acc[2 * q], bf_lo(pk[32 + (q >> 1)]), bf_lo(pk[q])), fmaf(acc[2 * q + 1], bf_hi(pk[32 + (q >> 1)]), bf_hi(pk[q])));
        }
        stsm4(stg_row + (i >> 3) * BLK + ((((i & 7) + (lane >> 4)) ^ (lane & 7)) << 4), w[0], w[1], w[2], w[3]);
        if ((i & 7) == 6) stage_done(sb, wg, i >> 3, lane);
      }
      if (tid == 0) g_epoch[blockIdx.x] = ep;
      if (warp == 0) TR(21);
      cl_wait();
    }
  }
}

typedef CUresult (*EncodeFn)(CUtensorMap*, CUtensorMapDataType, cuuint32_t, void*, const cuuint64_t*, const cuuint64_t*, const cuuint32_t*, const cuuint32_t*,
                             CUtensorMapInterleave, CUtensorMapSwizzle, CUtensorMapL2promotion, CUtensorMapFloatOOBfill);

void make_map(EncodeFn fn, CUtensorMap* mp, const void* base, uint64_t d0, uint64_t d1, uint64_t d2, uint64_t s1, uint64_t s2, uint32_t b2) {
  cuuint64_t d[3] = {d0, d1, d2}, s[2] = {s1, s2};
  cuuint32_t b[3] = {64, 64, b2}, e[3] = {1, 1, 1};
  fn(mp, CU_TENSOR_MAP_DATA_TYPE_BFLOAT16, 3, (void*)base, d, s, b, e, CU_TENSOR_MAP_INTERLEAVE_NONE, CU_TENSOR_MAP_SWIZZLE_128B,
     CU_TENSOR_MAP_L2_PROMOTION_L2_128B, CU_TENSOR_MAP_FLOAT_OOB_FILL_NONE);
}

}

extern "C" void kernel_launch(void* const* d_in, const int* in_sizes, int n_in, void* d_out, int out_size) {
  static EncodeFn fn = nullptr;
  if (!fn) {
    void* p = nullptr; cudaDriverEntryPointQueryResult q;
    cudaGetDriverEntryPoint("cuTensorMapEncodeTiled", &p, cudaEnableDefault, &q);
    fn = (EncodeFn)p;
    cudaFuncSetAttribute(fused_kernel, cudaFuncAttributeMaxDynamicSharedMemorySize, SMEM_BYTES);
  }
  Maps mp;
  make_map(fn, &mp.x, d_in[0], D_, S_ / 2, 2, 4096, 2048, 2);
  make_map(fn, &mp.out, d_out, D_, S_ / 2, 2, 4096, 2048, 2);
  make_map(fn, &mp.wqkv, d_in[1], 64, D_, 3 * D_ / 64, 3 * D_ * 2, 128, 2);
  make_map(fn, &mp.wo, d_in[2], 64, D_, D_ / 64, D_ * 2, 128, 2);
  make_map(fn, &mp.w1, d_in[4], 64, D_, F_ / 64, F_ * 2, 128, 2);
  make_map(fn, &mp.w3, d_in[5], 64, D_, F_ / 64, F_ * 2, 128, 2);
  make_map(fn, &mp.w1s, d_in[4], 64, D_, F_ / 64, F_ * 2, 128, 1);
  make_map(fn, &mp.w3s, d_in[5], 64, D_, F_ / 64, F_ * 2, 128, 1);
  make_map(fn, &mp.w2, d_in[6], 64, F_, D_ / 64, D_ * 2, 128, 2);
  Weights wt{(const bf16*)d_in[1], (const bf16*)d_in[2], {(const bf16*)d_in[4], (const bf16*)d_in[5]}, (const bf16*)d_in[6]};
  fused_kernel<<<128, 384, SMEM_BYTES>>>(mp, (const bf16*)d_in[7], (const bf16*)d_in[8], wt);
}
```

```cpp
#include <cuda_runtime.h>
#include <cuda_bf16.h>
#include <cuda.h>
#include <stdint.h>

typedef __nv_bfloat16 bf16;

#define NPIECE 8
#define PSLEEP 150
#define BYSM 1
#define P1 3
namespace {

constexpr int S_ = 2048, D_ = 1024, F_ = 3584;
constexpr int BLK = 16384;
constexpr int HALF = 8192;
constexpr int RING = 196608;
constexpr int STG = RING;
constexpr int MISC = RING + 2 * BLK;
constexpr int SMEM_BYTES = MISC + 3072;
constexpr int B_FULL4 = 0, B_EMPTY4 = 32, B_FULL6 = 64, B_EMPTY6 = 112, B_RDY = 160, B_FREE = 176, B_STORED = 192, B_X = 208, B_MOD = 224, B_HALO = 232, B_OWN = 240, B_GO = 248, B_HH = 256, B_ALL = 272, B_HH2 = 288;
constexpr int MODV = 512;
constexpr int RED_OFF = 0;
constexpr float SCL = 0.17677669529663687f * 1.4426950408889634f;
constexpr int U_HH = 64;

struct Maps { CUtensorMap x, out, wqkv, wo, w1, w3, w1s, w3s, w2, wmod; };

__device__ uint4 g_h[16 * 16 * 1024];
__device__ uint4 g_o[16 * 16 * 1024];
__device__ uint4 g_hh[16 * 56 * 1024];
__device__ uint4 g_x1[128 * 8 * 256];
__device__ uint2 g_modp[8 * 2 * 4 * 128];
__device__ uint2 g_modv[4 * 1024];
__device__ uint4 g_stat[2 * 16 * 8 * 128];
__device__ uint4 g_halo[16 * 8 * 2 * 512];
__device__ uint32_t g_flag[16 * 128];
__device__ uint32_t g_epoch[132];
#define TR(i)
#define TRS(i)

__device__ __forceinline__ void bail() { asm volatile("st.global.u32 [%0], %1;" :: "l"(0ull), "r"(0) : "memory"); }
__device__ __forceinline__ uint32_t smem_u32(const void* p) { return (uint32_t)__cvta_generic_to_shared(p); }
__device__ __forceinline__ void mbar_init(uint32_t bar, uint32_t cnt) { asm volatile("mbarrier.init.shared::cta.b64 [%0], %1;" :: "r"(bar), "r"(cnt) : "memory"); }
__device__ __forceinline__ void mbar_expect_tx(uint32_t bar, uint32_t bytes) { asm volatile("mbarrier.arrive.expect_tx.shared::cta.b64 _, [%0], %1;" :: "r"(bar), "r"(bytes) : "memory"); }
__device__ __forceinline__ void mbar_arrive(uint32_t bar) { asm volatile("mbarrier.arrive.shared::cta.b64 _, [%0];" :: "r"(bar) : "memory"); }
__device__ __forceinline__ void mbar_arrive_cl(uint32_t cl_addr) { asm volatile("mbarrier.arrive.shared::cluster.b64 _, [%0];" :: "r"(cl_addr) : "memory"); }
__device__ __forceinline__ uint32_t mapa(uint32_t addr, uint32_t cta) { uint32_t r; asm("mapa.shared::cluster.u32 %0, %1, %2;" : "=r"(r) : "r"(addr), "r"(cta)); return r; }
__device__ __forceinline__ void mbar_wait(uint32_t bar, uint32_t parity) {
  asm volatile("{\n.reg .pred p;\n.reg .b32 n;\n.reg .b64 z;\nmov.b32 n, 0;\nmov.b64 z, 0;\n"
               "W: add.u32 n, n, 1;\nsetp.gt.u32 p, n, 0x400000;\n@p st.global.u32 [z], n;\n"
               "mbarrier.try_wait.parity.shared::cta.b64 p, [%0], %1;\n@!p bra W;\n}" :: "r"(bar), "r"(parity) : "memory");
}
__device__ __forceinline__ void tma_3d(uint32_t dst, const CUtensorMap* m, uint32_t bar, int c0, int c1, int c2) {
  asm volatile("cp.async.bulk.tensor.3d.shared::cluster.global.mbarrier::complete_tx::bytes [%0], [%1, {%3, %4, %5}], [%2];" :: "r"(dst), "l"(m), "r"(bar), "r"(c0), "r"(c1), "r"(c2) : "memory");
}
__device__ __forceinline__ void tma_store_3d(const CUtensorMap* m, uint32_t src, int c0, int c1, int c2) {
  asm volatile("cp.async.bulk.tensor.3d.global.shared::cta.bulk_group [%0, {%2, %3, %4}], [%1];" :: "l"(m), "r"(src), "r"(c0), "r"(c1), "r"(c2) : "memory");
}
__device__ __forceinline__ void bulk_ld(uint32_t dst, const void* src, uint32_t bytes, uint32_t bar) {
  asm volatile("cp.async.bulk.shared::cluster.global.mbarrier::complete_tx::bytes [%0], [%1], %2, [%3];" :: "r"(dst), "l"(src), "r"(bytes), "r"(bar) : "memory");
}
__device__ __forceinline__ void bulk_ld_mc(uint32_t dst, const void* src, uint32_t bytes, uint32_t bar) {
  asm volatile("cp.async.bulk.shared::cluster.global.mbarrier::complete_tx::bytes.multicast::cluster [%0], [%1], %2, [%3], %4;" :: "r"(dst), "l"(src), "r"(bytes), "r"(bar), "h"((uint16_t)3) : "memory");
}
__device__ __forceinline__ void bulk_st(void* dst, uint32_t src, uint32_t bytes) {
  asm volatile("cp.async.bulk.global.shared::cta.bulk_group [%0], [%1], %2;" :: "l"(dst), "r"(src), "r"(bytes) : "memory");
}
__device__ __forceinline__ void bulk_commit() { asm volatile("cp.async.bulk.commit_group;" ::: "memory"); }
__device__ __forceinline__ void bulk_wait_read() { asm volatile("cp.async.bulk.wait_group.read 0;" ::: "memory"); }
__device__ __forceinline__ void bulk_wait_all() { asm volatile("cp.async.bulk.wait_group 0;" ::: "memory"); }
__device__ __forceinline__ void fence_async_global() { asm volatile("fence.proxy.async.global;" ::: "memory"); }
__device__ __forceinline__ void fence_async_smem() { asm volatile("fence.proxy.async.shared::cta;" ::: "memory"); }
__device__ __forceinline__ void wg_arrive() { asm volatile("wgmma.fence.sync.aligned;" ::: "memory"); }
__device__ __forceinline__ void wg_commit() { asm volatile("wgmma.commit_group.sync.aligned;" ::: "memory"); }
template <int N> __device__ __forceinline__ void wg_wait() { asm volatile("wgmma.wait_group.sync.aligned %0;" :: "n"(N) : "memory"); }
__device__ __forceinline__ void cl_arrive_relaxed() { asm volatile("barrier.cluster.arrive.relaxed.aligned;" ::: "memory"); }
__device__ __forceinline__ void cl_wait() { asm volatile("barrier.cluster.wait.acquire.aligned;" ::: "memory"); }
__device__ __forceinline__ bool elect() { uint32_t p; asm volatile("{\n.reg .pred p;\nelect.sync _|p, 0xffffffff;\nselp.u32 %0, 1, 0, p;\n}" : "=r"(p)); return p; }
__device__ __forceinline__ void named_bar(int id, int n) { asm volatile("bar.sync %0, %1;" :: "r"(id), "r"(n) : "memory"); }
__device__ __forceinline__ uint32_t pack2(float lo, float hi) { uint32_t r; asm("cvt.rn.bf16x2.f32 %0, %1, %2;" : "=r"(r) : "f"(hi), "f"(lo)); return r; }
__device__ __forceinline__ float bf_lo(uint32_t w) { return __uint_as_float(w << 16); }
__device__ __forceinline__ float bf_hi(uint32_t w) { return __uint_as_float(w & 0xffff0000u); }
__device__ __forceinline__ float bf_round(float v) { return __bfloat162float(__float2bfloat16_rn(v)); }
__device__ __forceinline__ void stsm4(uint32_t addr, uint32_t a, uint32_t b, uint32_t c, uint32_t d) {
  asm volatile("stmatrix.sync.aligned.m8n8.x4.shared.b16 [%0], {%1, %2, %3, %4};" :: "r"(addr), "r"(a), "r"(b), "r"(c), "r"(d) : "memory");
}
__device__ __forceinline__ void ldsm4(uint32_t addr, uint32_t& a, uint32_t& b, uint32_t& c, uint32_t& d) {
  asm volatile("ldmatrix.sync.aligned.m8n8.x4.shared.b16 {%0, %1, %2, %3}, [%4];" : "=r"(a), "=r"(b), "=r"(c), "=r"(d) : "r"(addr) : "memory");
}
__device__ __forceinline__ uint32_t movm(uint32_t a) { uint32_t r; asm volatile("movmatrix.sync.aligned.m8n8.trans.b16 %0, %1;" : "=r"(r) : "r"(a)); return r; }
__device__ __forceinline__ void mma16(float (&d)[4], uint32_t a0, uint32_t a1, uint32_t a2, uint32_t a3, uint32_t b0, uint32_t b1) {
  asm volatile("mma.sync.aligned.m16n8k16.row.col.f32.bf16.bf16.f32 {%0,%1,%2,%3}, {%4,%5,%6,%7}, {%8,%9}, {%0,%1,%2,%3};"
               : "+f"(d[0]), "+f"(d[1]), "+f"(d[2]), "+f"(d[3]) : "r"(a0), "r"(a1), "r"(a2), "r"(a3), "r"(b0), "r"(b1));
}
__device__ __forceinline__ void mma8(float (&d)[4], uint32_t a0, uint32_t a1, uint32_t b0) {
  asm volatile("mma.sync.aligned.m16n8k8.row.col.f32.bf16.bf16.f32 {%0,%1,%2,%3}, {%4,%5}, {%6}, {%0,%1,%2,%3};"
               : "+f"(d[0]), "+f"(d[1]), "+f"(d[2]), "+f"(d[3]) : "r"(a0), "r"(a1), "r"(b0));
}
__device__ __forceinline__ uint4 lds128(uint32_t a) { uint4 v; asm volatile("ld.shared.v4.u32 {%0,%1,%2,%3}, [%4];" : "=r"(v.x), "=r"(v.y), "=r"(v.z), "=r"(v.w) : "r"(a) : "memory"); return v; }
__device__ __forceinline__ void sts128(uint32_t a, uint32_t x, uint32_t y, uint32_t z, uint32_t w) { asm volatile("st.shared.v4.u32 [%0], {%1,%2,%3,%4};" :: "r"(a), "r"(x), "r"(y), "r"(z), "r"(w) : "memory"); }
__device__ __forceinline__ float lds32f(uint32_t a) { float v; asm volatile("ld.shared.f32 %0, [%1];" : "=f"(v) : "r"(a) : "memory"); return v; }
__device__ __forceinline__ void sts16(uint32_t a, bf16 v) { asm volatile("st.shared.b16 [%0], %1;" :: "r"(a), "h"(__bfloat16_as_ushort(v)) : "memory"); }
__device__ __forceinline__ uint4 ldg_nc(const void* p) { uint4 v; asm volatile("ld.global.nc.L1::no_allocate.v4.u32 {%0,%1,%2,%3}, [%4];" : "=r"(v.x), "=r"(v.y), "=r"(v.z), "=r"(v.w) : "l"(p)); return v; }
__device__ __forceinline__ uint4 ld_rlx4(const uint4* p) {
  unsigned long long a, b; asm volatile("ld.relaxed.gpu.global.v2.b64 {%0,%1}, [%2];" : "=l"(a), "=l"(b) : "l"(p) : "memory");
  return make_uint4((uint32_t)a, (uint32_t)(a >> 32), (uint32_t)b, (uint32_t)(b >> 32));
}
__device__ __forceinline__ uint2 ld_rlx2(const uint2* p) { unsigned long long a; asm volatile("ld.relaxed.gpu.global.b64 %0, [%1];" : "=l"(a) : "l"(p) : "memory"); return make_uint2((uint32_t)a, (uint32_t)(a >> 32)); }
__device__ __forceinline__ void st_rlx4(uint4* p, uint32_t x, uint32_t y, uint32_t z, uint32_t w) {
  asm volatile("st.relaxed.gpu.global.v2.b64 [%0], {%1,%2};" :: "l"(p), "l"((unsigned long long)x | ((unsigned long long)y << 32)), "l"((unsigned long long)z | ((unsigned long long)w << 32)) : "memory");
}
__device__ __forceinline__ void st_rlx2(uint2* p, uint32_t x, uint32_t y) { asm volatile("st.relaxed.gpu.global.b64 [%0], %1;" :: "l"(p), "l"((unsigned long long)x | ((unsigned long long)y << 32)) : "memory"); }
__device__ __forceinline__ void st_release(uint32_t* p, uint32_t v) { asm volatile("st.release.gpu.global.u32 [%0], %1;" :: "l"(p), "r"(v) : "memory"); }
__device__ __forceinline__ uint32_t ld_acquire(const uint32_t* p) { uint32_t v; asm volatile("ld.acquire.gpu.global.u32 %0, [%1];" : "=r"(v) : "l"(p) : "memory"); return v; }
__device__ __forceinline__ void prefetch_map(const CUtensorMap* m) { asm volatile("prefetch.tensormap [%0];" :: "l"(m) : "memory"); }
__device__ __forceinline__ float ex2(float x) { float r; asm("ex2.approx.ftz.f32 %0, %1;" : "=f"(r) : "f"(x)); return r; }
__device__ __forceinline__ float tanh_fast(float x) { float r; asm("tanh.approx.f32 %0, %1;" : "=f"(r) : "f"(x)); return r; }
#define SPIN_GUARD(n) if (++(n) > (1u << 24)) bail()

__device__ __forceinline__ void wgmma_n128(float (&d)[64], uint64_t da, uint64_t db) {
  asm volatile("wgmma.mma_async.sync.aligned.m64n128k16.f32.bf16.bf16 "
    "{%0, %1, %2, %3, %4, %5, %6, %7, %8, %9, %10, %11, %12, %13, %14, %15, %16, %17, %18, %19, %20, %21, %22, %23, %24, %25, %26, %27, %28, %29, %30, %31, %32, %33, %34, %35, %36, %37, %38, %39, %40, %41, %42, %43, %44, %45, %46, %47, %48, %49, %50, %51, %52, %53, %54, %55, %56, %57, %58, %59, %60, %61, %62, %63}, "
    "%64, %65, 1, 1, 1, 0, 1;\n"
    : "+f"(d[0]), "+f"(d[1]), "+f"(d[2]), "+f"(d[3]), "+f"(d[4]), "+f"(d[5]), "+f"(d[6]), "+f"(d[7]), "+f"(d[8]), "+f"(d[9]), "+f"(d[10]), "+f"(d[11]), "+f"(d[12]), "+f"(d[13]), "+f"(d[14]), "+f"(d[15]), "+f"(d[16]), "+f"(d[17]), "+f"(d[18]), "+f"(d[19]), "+f"(d[20]), "+f"(d[21]), "+f"(d[22]), "+f"(d[23]), "+f"(d[24]), "+f"(d[25]), "+f"(d[26]), "+f"(d[27]), "+f"(d[28]), "+f"(d[29]), "+f"(d[30]), "+f"(d[31]), "+f"(d[32]), "+f"(d[33]), "+f"(d[34]), "+f"(d[35]), "+f"(d[36]), "+f"(d[37]), "+f"(d[38]), "+f"(d[39]), "+f"(d[40]), "+f"(d[41]), "+f"(d[42]), "+f"(d[43]), "+f"(d[44]), "+f"(d[45]), "+f"(d[46]), "+f"(d[47]), "+f"(d[48]), "+f"(d[49]), "+f"(d[50]), "+f"(d[51]), "+f"(d[52]), "+f"(d[53]), "+f"(d[54]), "+f"(d[55]), "+f"(d[56]), "+f"(d[57]), "+f"(d[58]), "+f"(d[59]), "+f"(d[60]), "+f"(d[61]), "+f"(d[62]), "+f"(d[63])
    : "l"(da), "l"(db));
}
__device__ __forceinline__ void wgmma_n128_first(float (&d)[64], uint64_t da, uint64_t db) {
  asm volatile("wgmma.mma_async.sync.aligned.m64n128k16.f32.bf16.bf16 "
    "{%0, %1, %2, %3, %4, %5, %6, %7, %8, %9, %10, %11, %12, %13, %14, %15, %16, %17, %18, %19, %20, %21, %22, %23, %24, %25, %26, %27, %28, %29, %30, %31, %32, %33, %34, %35, %36, %37, %38, %39, %40, %41, %42, %43, %44, %45, %46, %47, %48, %49, %50, %51, %52, %53, %54, %55, %56, %57, %58, %59, %60, %61, %62, %63}, "
    "%64, %65, 0, 1, 1, 0, 1;\n"
    : "=f"(d[0]), "=f"(d[1]), "=f"(d[2]), "=f"(d[3]), "=f"(d[4]), "=f"(d[5]), "=f"(d[6]), "=f"(d[7]), "=f"(d[8]), "=f"(d[9]), "=f"(d[10]), "=f"(d[11]), "=f"(d[12]), "=f"(d[13]), "=f"(d[14]), "=f"(d[15]), "=f"(d[16]), "=f"(d[17]), "=f"(d[18]), "=f"(d[19]), "=f"(d[20]), "=f"(d[21]), "=f"(d[22]), "=f"(d[23]), "=f"(d[24]), "=f"(d[25]), "=f"(d[26]), "=f"(d[27]), "=f"(d[28]), "=f"(d[29]), "=f"(d[30]), "=f"(d[31]), "=f"(d[32]), "=f"(d[33]), "=f"(d[34]), "=f"(d[35]), "=f"(d[36]), "=f"(d[37]), "=f"(d[38]), "=f"(d[39]), "=f"(d[40]), "=f"(d[41]), "=f"(d[42]), "=f"(d[43]), "=f"(d[44]), "=f"(d[45]), "=f"(d[46]), "=f"(d[47]), "=f"(d[48]), "=f"(d[49]), "=f"(d[50]), "=f"(d[51]), "=f"(d[52]), "=f"(d[53]), "=f"(d[54]), "=f"(d[55]), "=f"(d[56]), "=f"(d[57]), "=f"(d[58]), "=f"(d[59]), "=f"(d[60]), "=f"(d[61]), "=f"(d[62]), "=f"(d[63])
    : "l"(da), "l"(db));
}
__device__ __forceinline__ void wgmma_n256(float (&d)[128], uint64_t da, uint64_t db) {
  asm volatile("wgmma.mma_async.sync.aligned.m64n256k16.f32.bf16.bf16 "
    "{%0, %1, %2, %3, %4, %5, %6, %7, %8, %9, %10, %11, %12, %13, %14, %15, %16, %17, %18, %19, %20, %21, %22, %23, %24, %25, %26, %27, %28, %29, %30, %31, %32, %33, %34, %35, %36, %37, %38, %39, %40, %41, %42, %43, %44, %45, %46, %47, %48, %49, %50, %51, %52, %53, %54, %55, %56, %57, %58, %59, %60, %61, %62, %63, %64, %65, %66, %67, %68, %69, %70, %71, %72, %73, %74, %75, %76, %77, %78, %79, %80, %81, %82, %83, %84, %85, %86, %87, %88, %89, %90, %91, %92, %93, %94, %95, %96, %97, %98, %99, %100, %101, %102, %103, %104, %105, %106, %107, %108, %109, %110, %111, %112, %113, %114, %115, %116, %117, %118, %119, %120, %121, %122, %123, %124, %125, %126, %127}, "
    "%128, %129, 1, 1, 1, 0, 1;\n"
    : "+f"(d[0]), "+f"(d[1]), "+f"(d[2]), "+f"(d[3]), "+f"(d[4]), "+f"(d[5]), "+f"(d[6]), "+f"(d[7]), "+f"(d[8]), "+f"(d[9]), "+f"(d[10]), "+f"(d[11]), "+f"(d[12]), "+f"(d[13]), "+f"(d[14]), "+f"(d[15]), "+f"(d[16]), "+f"(d[17]), "+f"(d[18]), "+f"(d[19]), "+f"(d[20]), "+f"(d[21]), "+f"(d[22]), "+f"(d[23]), "+f"(d[24]), "+f"(d[25]), "+f"(d[26]), "+f"(d[27]), "+f"(d[28]), "+f"(d[29]), "+f"(d[30]), "+f"(d[31]), "+f"(d[32]), "+f"(d[33]), "+f"(d[34]), "+f"(d[35]), "+f"(d[36]), "+f"(d[37]), "+f"(d[38]), "+f"(d[39]), "+f"(d[40]), "+f"(d[41]), "+f"(d[42]), "+f"(d[43]), "+f"(d[44]), "+f"(d[45]), "+f"(d[46]), "+f"(d[47]), "+f"(d[48]), "+f"(d[49]), "+f"(d[50]), "+f"(d[51]), "+f"(d[52]), "+f"(d[53]), "+f"(d[54]), "+f"(d[55]), "+f"(d[56]), "+f"(d[57]), "+f"(d[58]), "+f"(d[59]), "+f"(d[60]), "+f"(d[61]), "+f"(d[62]), "+f"(d[63]), "+f"(d[64]), "+f"(d[65]), "+f"(d[66]), "+f"(d[67]), "+f"(d[68]), "+f"(d[69]), "+f"(d[70]), "+f"(d[71]), "+f"(d[72]), "+f"(d[73]), "+f"(d[74]), "+f"(d[75]), "+f"(d[76]), "+f"(d[77]), "+f"(d[78]), "+f"(d[79]), "+f"(d[80]), "+f"(d[81]), "+f"(d[82]), "+f"(d[83]), "+f"(d[84]), "+f"(d[85]), "+f"(d[86]), "+f"(d[87]), "+f"(d[88]), "+f"(d[89]), "+f"(d[90]), "+f"(d[91]), "+f"(d[92]), "+f"(d[93]), "+f"(d[94]), "+f"(d[95]), "+f"(d[96]), "+f"(d[97]), "+f"(d[98]), "+f"(d[99]), "+f"(d[100]), "+f"(d[101]), "+f"(d[102]), "+f"(d[103]), "+f"(d[104]), "+f"(d[105]), "+f"(d[106]), "+f"(d[107]), "+f"(d[108]), "+f"(d[109]), "+f"(d[110]), "+f"(d[111]), "+f"(d[112]), "+f"(d[113]), "+f"(d[114]), "+f"(d[115]), "+f"(d[116]), "+f"(d[117]), "+f"(d[118]), "+f"(d[119]), "+f"(d[120]), "+f"(d[121]), "+f"(d[122]), "+f"(d[123]), "+f"(d[124]), "+f"(d[125]), "+f"(d[126]), "+f"(d[127])
    : "l"(da), "l"(db));
}
__device__ __forceinline__ void wgmma_n256_first(float (&d)[128], uint64_t da, uint64_t db) {
  asm volatile("wgmma.mma_async.sync.aligned.m64n256k16.f32.bf16.bf16 "
    "{%0, %1, %2, %3, %4, %5, %6, %7, %8, %9, %10, %11, %12, %13, %14, %15, %16, %17, %18, %19, %20, %21, %22, %23, %24, %25, %26, %27, %28, %29, %30, %31, %32, %33, %34, %35, %36, %37, %38, %39, %40, %41, %42, %43, %44, %45, %46, %47, %48, %49, %50, %51, %52, %53, %54, %55, %56, %57, %58, %59, %60, %61, %62, %63, %64, %65, %66, %67, %68, %69, %70, %71, %72, %73, %74, %75, %76, %77, %78, %79, %80, %81, %82, %83, %84, %85, %86, %87, %88, %89, %90, %91, %92, %93, %94, %95, %96, %97, %98, %99, %100, %101, %102, %103, %104, %105, %106, %107, %108, %109, %110, %111, %112, %113, %114, %115, %116, %117, %118, %119, %120, %121, %122, %123, %124, %125, %126, %127}, "
    "%128, %129, 0, 1, 1, 0, 1;\n"
    : "=f"(d[0]), "=f"(d[1]), "=f"(d[2]), "=f"(d[3]), "=f"(d[4]), "=f"(d[5]), "=f"(d[6]), "=f"(d[7]), "=f"(d[8]), "=f"(d[9]), "=f"(d[10]), "=f"(d[11]), "=f"(d[12]), "=f"(d[13]), "=f"(d[14]), "=f"(d[15]), "=f"(d[16]), "=f"(d[17]), "=f"(d[18]), "=f"(d[19]), "=f"(d[20]), "=f"(d[21]), "=f"(d[22]), "=f"(d[23]), "=f"(d[24]), "=f"(d[25]), "=f"(d[26]), "=f"(d[27]), "=f"(d[28]), "=f"(d[29]), "=f"(d[30]), "=f"(d[31]), "=f"(d[32]), "=f"(d[33]), "=f"(d[34]), "=f"(d[35]), "=f"(d[36]), "=f"(d[37]), "=f"(d[38]), "=f"(d[39]), "=f"(d[40]), "=f"(d[41]), "=f"(d[42]), "=f"(d[43]), "=f"(d[44]), "=f"(d[45]), "=f"(d[46]), "=f"(d[47]), "=f"(d[48]), "=f"(d[49]), "=f"(d[50]), "=f"(d[51]), "=f"(d[52]), "=f"(d[53]), "=f"(d[54]), "=f"(d[55]), "=f"(d[56]), "=f"(d[57]), "=f"(d[58]), "=f"(d[59]), "=f"(d[60]), "=f"(d[61]), "=f"(d[62]), "=f"(d[63]), "=f"(d[64]), "=f"(d[65]), "=f"(d[66]), "=f"(d[67]), "=f"(d[68]), "=f"(d[69]), "=f"(d[70]), "=f"(d[71]), "=f"(d[72]), "=f"(d[73]), "=f"(d[74]), "=f"(d[75]), "=f"(d[76]), "=f"(d[77]), "=f"(d[78]), "=f"(d[79]), "=f"(d[80]), "=f"(d[81]), "=f"(d[82]), "=f"(d[83]), "=f"(d[84]), "=f"(d[85]), "=f"(d[86]), "=f"(d[87]), "=f"(d[88]), "=f"(d[89]), "=f"(d[90]), "=f"(d[91]), "=f"(d[92]), "=f"(d[93]), "=f"(d[94]), "=f"(d[95]), "=f"(d[96]), "=f"(d[97]), "=f"(d[98]), "=f"(d[99]), "=f"(d[100]), "=f"(d[101]), "=f"(d[102]), "=f"(d[103]), "=f"(d[104]), "=f"(d[105]), "=f"(d[106]), "=f"(d[107]), "=f"(d[108]), "=f"(d[109]), "=f"(d[110]), "=f"(d[111]), "=f"(d[112]), "=f"(d[113]), "=f"(d[114]), "=f"(d[115]), "=f"(d[116]), "=f"(d[117]), "=f"(d[118]), "=f"(d[119]), "=f"(d[120]), "=f"(d[121]), "=f"(d[122]), "=f"(d[123]), "=f"(d[124]), "=f"(d[125]), "=f"(d[126]), "=f"(d[127])
    : "l"(da), "l"(db));
}

template <int N> struct WG;
#define DEF_WG(N) template <> struct WG<N> { \
  static __device__ __forceinline__ void mma(float (&d)[N / 2], uint64_t a, uint64_t b) { wgmma_n##N(d, a, b); } \
  static __device__ __forceinline__ void first(float (&d)[N / 2], uint64_t a, uint64_t b) { wgmma_n##N##_first(d, a, b); } };
DEF_WG(128) DEF_WG(256)

constexpr uint64_t DESC_A = (1ull << 62) | ((uint64_t)(1024 >> 4) << 32) | (1ull << 16);
constexpr uint64_t DESC_B = (1ull << 62) | ((uint64_t)(1024 >> 4) << 32) | ((uint64_t)(8192 >> 4) << 16);

struct Ring { int s; uint32_t ph; int wrap; };
template <int NS> __device__ __forceinline__ void ring_next(Ring& r) { r.s = (r.s + 1 == NS) ? 0 : r.s + 1; if (r.s == r.wrap) r.ph ^= 1; }

__device__ __forceinline__ int own_order(int it, int j) {
  return it < 2 ? 2 * j + it : it == 2 ? 2 * (j ^ 1) : it == P1 ? 2 * (j ^ 1) + 1 : it < 10 ? ((j >> 1) * 4 + 2 * it - (it > P1 ? 4 : 2)) & 15 : ((j >> 1) * 4 + 2 * it - 15) & 15;
}

template <int V> struct IC { static constexpr int v = V; };
template <int I, int E, class F> __device__ __forceinline__ void static_for(F&& f) { if constexpr (I < E) { f(IC<I>{}); static_for<I + 1, E>(f); } }

template <int N, int NS, int PRE, class Pre, class Mid, class Last>
__device__ __forceinline__ void mainloop(float (&acc)[N / 2], int nkb, bool own, Ring& r, uint32_t sb, int wg, int lane, uint32_t rel_base, int step0, Pre pre, Mid mid, Last last) {
  constexpr int SLOT = RING / NS;
  const uint32_t full = sb + MISC + (NS == 4 ? B_FULL4 : B_FULL6);
  const uint32_t rel = rel_base + (NS == 4 ? B_EMPTY4 : B_EMPTY6);
  const uint32_t s0 = (sb & 0x3FFFF) >> 4, a0 = s0 + wg * (HALF >> 4);
  int ps;
  auto issue = [&](int it, bool first) {
    const uint64_t da = DESC_A | (a0 + ((own && it < 2) ? (STG + it * BLK) >> 4 : r.s * (SLOT >> 4))), db = DESC_B | (s0 + r.s * (SLOT >> 4) + (BLK >> 4));
    mbar_wait(full + r.s * 8, r.ph);
    TRS(step0 + it);
    wg_arrive();
    if (first) WG<N>::first(acc, da, db); else WG<N>::mma(acc, da, db);
#pragma unroll
    for (int k = 1; k < 4; k++) WG<N>::mma(acc, da + k * 2, db + k * 128);
    wg_commit();
  };
  auto retire = [&](int it) {
    wg_wait<1>();
    if (lane < 2) mbar_arrive_cl(rel + ps * 8);
    if (own && it == 2 && lane == 0) mbar_arrive(sb + MISC + B_OWN);
    ps = r.s;
    ring_next<NS>(r);
  };
  issue(0, true);
  ps = r.s;
  ring_next<NS>(r);
  static_for<1, PRE + 1>([&](auto ic) { issue(ic.v, false); pre(ic); retire(ic.v); });
#pragma unroll 1
  for (int it = PRE + 1; it < nkb; it++) { issue(it, false); mid(it); retire(it); }
  last();
  wg_wait<0>();
  if (lane < 2) mbar_arrive_cl(rel + ps * 8);
}

__device__ __forceinline__ void ln_publish(const float (&v)[64], uint4* st, int j, int row0, int lane, uint32_t ep) {
  float s0 = 0, s1 = 0, s2 = 0, s3 = 0, q0 = 0, q1 = 0, q2 = 0, q3 = 0;
#pragma unroll
  for (int i = 0; i < 16; i++) {
    s0 += v[4 * i]; s1 += v[4 * i + 1]; s2 += v[4 * i + 2]; s3 += v[4 * i + 3];
    q0 = fmaf(v[4 * i], v[4 * i], q0); q1 = fmaf(v[4 * i + 1], v[4 * i + 1], q1); q2 = fmaf(v[4 * i + 2], v[4 * i + 2], q2); q3 = fmaf(v[4 * i + 3], v[4 * i + 3], q3);
  }
  s0 += s1; s2 += s3; q0 += q1; q2 += q3;
  const bool odd = lane & 1;
  float s = (odd ? s2 : s0) + __shfl_xor_sync(~0u, odd ? s0 : s2, 1), q = (odd ? q2 : q0) + __shfl_xor_sync(~0u, odd ? q0 : q2, 1);
  s += __shfl_xor_sync(~0u, s, 2); q += __shfl_xor_sync(~0u, q, 2);
  if ((lane & 3) < 2) st_rlx4(st + j * 128 + row0 + (lane & 1) * 8, __float_as_uint(s), ep, __float_as_uint(q), ep);
}
__device__ __forceinline__ void ln_gather(const uint4* st, int row0, int lane, uint32_t ep, float& n0, float& r0, float& n1, float& r1) {
  const uint4* p = st + (lane & 2) * 256 + row0 + (lane & 1) * 8;
  uint4 a, b, c, d; uint32_t n = 0;
  while (true) {
    a = ld_rlx4(p); b = ld_rlx4(p + 128); c = ld_rlx4(p + 256); d = ld_rlx4(p + 384);
    if (a.y == ep && a.w == ep && b.y == ep && b.w == ep && c.y == ep && c.w == ep && d.y == ep && d.w == ep) break;
    SPIN_GUARD(n);
  }
  __syncwarp();
  float s = (__uint_as_float(a.x) + __uint_as_float(b.x)) + (__uint_as_float(c.x) + __uint_as_float(d.x));
  float q = (__uint_as_float(a.z) + __uint_as_float(b.z)) + (__uint_as_float(c.z) + __uint_as_float(d.z));
  s += __shfl_xor_sync(~0u, s, 2); q += __shfl_xor_sync(~0u, q, 2);
  s *= 1.f / 1024;
  const float r = rsqrtf(fmaxf(fmaf(-s, s, q * (1.f / 1024)), 0.f) + 1e-5f), nn = -s * r;
  const float ro = __shfl_xor_sync(~0u, r, 1), no = __shfl_xor_sync(~0u, nn, 1);
  const bool odd = lane & 1;
  r0 = odd ? ro : r; n0 = odd ? no : nn; r1 = odd ? r : ro; n1 = odd ? nn : no;
}
__device__ __forceinline__ void load_vec(uint32_t* w, uint32_t sb, int sec, int b, int lane) {
#pragma unroll
  for (int q = 0; q < 2; q++) { uint4 t = lds128(sb + MISC + MODV + sec * 256 + (lane & 3) * 64 + b * 32 + q * 16); w[4 * q] = t.x; w[4 * q + 1] = t.y; w[4 * q + 2] = t.z; w[4 * q + 3] = t.w; }
}
__device__ __forceinline__ void stage_done(uint32_t sb, int wg, int b, int lane) {
  fence_async_smem();
  __syncwarp();
  if (lane == 0) mbar_arrive(sb + MISC + B_RDY + b * 8);
}
__device__ __forceinline__ uint32_t hfma2(uint32_t a, uint32_t b, uint32_t c) { uint32_t r; asm("fma.rn.bf16x2 %0, %1, %2, %3;" : "=r"(r) : "r"(a), "r"(b), "r"(c)); return r; }
__device__ __forceinline__ void ln_apply(const float (&v)[64], float n0, float r0, float n1, float r1, uint32_t sb, int sec_shift, int sec_scale, uint32_t stg_row, int wg, int lane) {
  uint32_t sc[16], sh[16];
#pragma unroll
  for (int i = 0; i < 16; i += 2) {
    if ((i & 7) == 0) { load_vec(sc + i, sb, sec_scale, i >> 3, lane); load_vec(sh + i, sb, sec_shift, i >> 3, lane); }
    if (i == 8) asm volatile("" : "+f"(r0), "+f"(r1) :: "memory");
    uint32_t w[4];
#pragma unroll
    for (int u = 0; u < 2; u++) {
      int q = i + u;
      w[2 * u] = hfma2(pack2(fmaf(v[4 * q], r0, n0), fmaf(v[4 * q + 1], r0, n0)), sc[q], sh[q]);
      w[2 * u + 1] = hfma2(pack2(fmaf(v[4 * q + 2], r1, n1), fmaf(v[4 * q + 3], r1, n1)), sc[q], sh[q]);
    }
    stsm4(stg_row + (i >> 3) * BLK + ((((i & 7) + (lane >> 4)) ^ (lane & 7)) << 4), w[0], w[1], w[2], w[3]);
    if ((i & 7) == 6) stage_done(sb, wg, i >> 3, lane);
  }
}
__device__ __forceinline__ uint32_t hmul2(uint32_t a, uint32_t b) { uint32_t r; asm("mul.rn.bf16x2 %0, %1, %2;" : "=r"(r) : "r"(a), "r"(b)); return r; }
__device__ __forceinline__ uint32_t silu_mul2(uint32_t g, uint32_t u) {
  const uint32_t h = hmul2(g, 0x3f003f00u);
  const float h0 = bf_lo(h), h1 = bf_hi(h);
  return hmul2(pack2(fmaf(h0, tanh_fast(h0), h0), fmaf(h1, tanh_fast(h1), h1)), u);
}

__device__ __forceinline__ void gemv_fma(float (&a)[8], uint4 w, float s) {
  a[0] = fmaf(bf_lo(w.x), s, a[0]); a[1] = fmaf(bf_hi(w.x), s, a[1]); a[2] = fmaf(bf_lo(w.y), s, a[2]); a[3] = fmaf(bf_hi(w.y), s, a[3]);
  a[4] = fmaf(bf_lo(w.z), s, a[4]); a[5] = fmaf(bf_hi(w.z), s, a[5]); a[6] = fmaf(bf_lo(w.w), s, a[6]); a[7] = fmaf(bf_hi(w.w), s, a[7]);
}
__device__ __forceinline__ float silu_c(float v) { return bf_round(__fdividef(v, 1.f + __expf(-v))); }
__device__ __forceinline__ float mod_gather(const uint2* p, uint32_t ep) {
  uint2 a, b, c, d; uint32_t n = 0;
  while (true) {
    a = ld_rlx2(p); b = ld_rlx2(p + 128); c = ld_rlx2(p + 256); d = ld_rlx2(p + 384);
    if (a.y == ep && b.y == ep && c.y == ep && d.y == ep) break;
    SPIN_GUARD(n);
  }
  return (__uint_as_float(a.x) + __uint_as_float(b.x)) + (__uint_as_float(c.x) + __uint_as_float(d.x));
}
__device__ __forceinline__ void mod_store(uint32_t sb, int sec, int col, float v) {
  v = bf_round(v);
  if (sec == 1 || sec == 4) v += 1.f;
  sts16(sb + MISC + MODV + sec * 256 + (((col >> 1) & 3) * 16 + (col >> 3)) * 4 + (col & 1) * 2, __float2bfloat16_rn(v));
}

__global__ void __cluster_dims__(2, 1, 1) __launch_bounds__(384, 1)
fused_kernel(const __grid_constant__ Maps maps, const bf16* __restrict__ cvec, const bf16* __restrict__ wmod, int by_sm) {
  extern __shared__ __align__(1024) uint8_t smem_raw[];
  const uint32_t sb = smem_u32(smem_raw);
  const int warp = __shfl_sync(~0u, threadIdx.x >> 5, 0), lane = threadIdx.x & 31;
  const int rank = blockIdx.x & 1;
  int cid = (blockIdx.x >> 1) - 2;
  if (by_sm) {
    uint32_t sm; asm("mov.u32 %0, %%smid;" : "=r"(sm));
    const int t = sm >> 1, u = t - 32, gp = t < 32 ? t & 7 : t < 60 ? 1 + u % 7 : 0, idx = t < 32 ? t >> 3 : t < 60 ? 4 + u / 7 : t - 58;
    cid = (t & ~1) == 60 ? t - 62 : ((gp & 1) * 8 + idx) * 4 + (gp >> 1);
  }
  const bool extra = cid < 0;
  const int bid = cid * 2 + rank;
  const int m = cid >> 2, j = (cid & 3) * 2 + rank;
  const uint32_t bar = sb + MISC;

  if (warp >= 8) {
    asm volatile("setmaxnreg.dec.sync.aligned.u32 40;");
    if (extra) {
      if (warp == 8) {
        if (lane == 0) { for (int s = 0; s < 6; s++) { mbar_init(bar + B_FULL6 + s * 8, 1); mbar_init(bar + B_EMPTY6 + s * 8, 8); } fence_async_smem(); }
        __syncwarp();
        asm volatile("bar.arrive 2, 288;" ::: "memory");
#pragma unroll 1
        for (int it = 0, s = 0, par = 1; it < 64; it++) {
          mbar_wait(bar + B_EMPTY6 + s * 8, par);
          if (elect()) { mbar_expect_tx(bar + B_FULL6 + s * 8, 32768); tma_3d(sb + s * 32768, &maps.wmod, bar + B_FULL6 + s * 8, 0, (it & 15) * 64, 12 + (it >> 4) * 4 + bid); }
          if (++s == 6) { s = 0; par ^= 1; }
        }
      }
    } else if (warp < 10) {
      uint32_t s6 = 0, p6 = 1;
      auto next6 = [&]() { if (++s6 == 6) { s6 = 0; p6 ^= 1; } };
      auto drained4 = [&](int q, int late) { if (q < 5) mbar_wait(bar + B_EMPTY4 + (((late ? 0x10332 : 0x32110) >> (4 * q)) & 3) * 8, 1); };
      auto drained6 = [&](int q) { if (q < 3) mbar_wait(bar + B_EMPTY6 + ((0x154 >> (4 * q)) & 7) * 8, q >> 1); };
      auto skip6 = [&]() { mbar_wait(bar + B_EMPTY6 + s6 * 8, p6); if (elect()) mbar_arrive(bar + B_FULL6 + s6 * 8); next6(); };
      if (warp == 8) {
        if (lane == 0) {
          if (sb & 1023) bail();
          for (int b = 0; b < 2; b++) mbar_init(bar + B_X + b * 8, 1);
          fence_async_smem();
          for (int b = 0; b < 2; b++) { mbar_expect_tx(bar + B_X + b * 8, BLK); tma_3d(sb + STG + b * BLK, &maps.x, bar + B_X + b * 8, j * 128 + b * 64, m * 64, 0); }
          for (int s = 0; s < 4; s++) { mbar_init(bar + B_FULL4 + s * 8, 2); mbar_init(bar + B_EMPTY4 + s * 8, 16); }
          for (int s = 0; s < 6; s++) { mbar_init(bar + B_FULL6 + s * 8, 2); mbar_init(bar + B_EMPTY6 + s * 8, 16); }
          for (int b = 0; b < 2; b++) { mbar_init(bar + B_RDY + b * 8, 8); mbar_init(bar + B_FREE + b * 8, 1); mbar_init(bar + B_STORED + b * 8, 1); mbar_init(bar + B_HH + b * 8, 1); }
          mbar_init(bar + B_MOD, 1); mbar_init(bar + B_HALO, 2); mbar_init(bar + B_GO, 1); mbar_init(bar + B_ALL, 1); mbar_init(bar + B_HH2, 1); mbar_init(bar + B_OWN, 8);
          asm volatile("fence.mbarrier_init.release.cluster;" ::: "memory");
          fence_async_smem();
        }
        __syncwarp();
        cl_arrive_relaxed();
        auto wide = [&](int s, int par, const CUtensorMap* m0, int a0, const CUtensorMap* m1, int a1, int kb) {
          const uint32_t full = bar + B_FULL4 + s * 8, d = sb + s * 49152 + BLK;
          mbar_wait(full + 32, par);
          if (elect()) { mbar_expect_tx(full, 2 * BLK); tma_3d(d, m0, full, 0, kb * 64, a0); tma_3d(d + BLK, m1, full, 0, kb * 64, a1); }
        };
        auto narrow = [&](const CUtensorMap* m0, int kb) {
          const uint32_t full = bar + B_FULL6 + s6 * 8;
          mbar_wait(full + 48, p6);
          if (elect()) { mbar_expect_tx(full, BLK); tma_3d(sb + s6 * 32768 + BLK, m0, full, 0, kb * 64, 2 * j); }
          next6();
        };
#pragma unroll 1
        for (int it = 0; it < 16; it++) {
          if (it == 2) mbar_wait(bar + B_GO, 0);
          wide(it & 3, ~(it >> 2) & 1, &maps.wqkv, 16 + 2 * j, &maps.wqkv, 32 + 2 * j, own_order(it, j));
        }
#pragma unroll 1
        for (int it = 0; it < 16; it++) { drained4(it, 0); narrow(&maps.wqkv, it); }
#pragma unroll 1
        for (int it = 0; it < 16; it++) {
          narrow(&maps.wo, own_order(it, j));
          if (it == 10) {
            mbar_wait(bar + B_OWN, 1); mbar_wait(bar + B_STORED + 8, 1);
            if (elect()) for (int b = 0; b < 2; b++) { mbar_expect_tx(bar + B_X + b * 8, BLK); tma_3d(sb + STG + b * BLK, &maps.x, bar + B_X + b * 8, j * 128 + b * 64, m * 64, 0); }
          }
        }
        skip6();
#pragma unroll 1
        for (int it = 0; it < 48; it++) {
          const int s = (it + 2) & 3, par = ~(it >> 2) & 1;
          drained6(it);
          wide(s, par, &maps.w1, (it & 48) + 2 * j, &maps.w3, (it & 48) + 2 * j, it < 16 ? own_order(it, j) : it & 15);
          if (it >= 44) {
            if (it == 44) { mbar_wait(bar + B_FREE, 0); mbar_wait(bar + B_FREE + 8, 0); if (elect()) mbar_expect_tx(bar + B_X, 2 * BLK); }
            if (elect()) bulk_ld(sb + STG + (it - 44) * HALF, g_x1 + bid * 2048 + (it - 44) * 512, HALF, bar + B_X);
          }
        }
#pragma unroll 1
        for (int it = 0; it < 16; it++) {
          const uint32_t full = bar + B_FULL6 + s6 * 8, d = sb + s6 * 32768 + BLK;
          drained4(it, 1);
          mbar_wait(full + 48, p6);
          if (elect()) { mbar_expect_tx(full, BLK); tma_3d(d, &maps.w1s, full, 0, it * 64, 48 + j); tma_3d(d + HALF, &maps.w3s, full, 0, it * 64, 48 + j); }
          next6();
        }
#pragma unroll 1
        for (int it = 0; it < 56; it++) narrow(&maps.w2, it);
      } else {
        if (lane < 9) prefetch_map(&maps.x + lane);
        const uint32_t ep = g_epoch[bid + 4] + 1;
        cl_arrive_relaxed(); cl_wait();
        const uint32_t to_peer = mapa(sb, rank ^ 1) - sb;
        auto plain = [&](uint32_t full, uint32_t empty, int par, uint32_t slot, const uint4* blk) {
          mbar_wait(empty, par);
          if (elect()) { mbar_expect_tx(full, BLK); bulk_ld_mc(slot + rank * HALF, blk + rank * 512, HALF, full); }
        };
        auto plain6 = [&](const uint4* blk) { plain(bar + B_FULL6 + s6 * 8, bar + B_EMPTY6 + s6 * 8, p6, sb + s6 * 32768, blk); next6(); };
        uint32_t ready = 0;
        auto poll = [&](int e) { ready = __ballot_sync(~0u, ld_acquire(g_flag + m * 128 + e * 16 + (lane & 15)) == ep); };
        auto need = [&](int e, uint32_t mask) {
          if ((ready & mask) != mask) {
            uint32_t n = 0;
            do { poll(e); SPIN_GUARD(n); } while ((ready & mask) != mask);
            fence_async_global();
          }
        };
        auto fresh = [&](int e, int it, uint32_t full, uint32_t empty, int par, uint32_t slot, uint4* src) {
          if (it >= 3 && it != P1) {
            const int kb = own_order(it, j);
            if (it < 10) need(e, 1u << kb); else if (it == 10) mbar_wait(bar + B_ALL, e & 1);
            plain(full, empty, par, slot, src + kb * 1024);
          } else {
            if (it == 0) { poll(e); ready = 0; }
            mbar_wait(empty, par);
            if (it < 2) { if (elect()) mbar_arrive(full); }
            else {
              const int b = it > 2;
              if (elect()) mbar_expect_tx(full, BLK);
              mbar_wait(bar + (b ? B_STORED + 8 : B_RDY), e & 1);
              if (b == 0) TR(e == 0 ? 24 : e == 2 ? 30 : 44);
              if (elect()) {
                if (b == 0) {
                  bulk_st(src + 2 * j * 1024, sb + STG, BLK);
                  bulk_commit();
                  bulk_wait_all();
                  mbar_arrive(bar + B_STORED);
                }
                fence_async_global();
                bulk_ld(slot + to_peer, src + (2 * j + b) * 1024, BLK, full + to_peer);
              }
              __syncwarp();
            }
          }
          if (it == (P1 == 3 ? 4 : 3)) TR(e == 0 ? 28 : e == 1 ? 46 : 34);
        };
#pragma unroll 1
        for (int ph = 0; ph < 2; ph++) {
          uint4* h = g_h + m * 16384;
#pragma unroll 1
          for (int it = 0; it < 16; it++) {
            const int s = (it + 2 * ph) & 3;
            if (ph) drained6(it);
            fresh(2 * ph, it, bar + B_FULL4 + s * 8, bar + B_EMPTY4 + s * 8, ~(it >> 2) & 1, sb + s * 49152, h);
          }
          if (ph) {
#pragma unroll 1
            for (int it = 16; it < 48; it++) {
              const int s = (it + 2) & 3;
              const uint32_t full = bar + B_FULL4 + s * 8;
              plain(full, full + 32, ~(it >> 2) & 1, sb + s * 49152, h + (it & 15) * 1024);
            }
          }
#pragma unroll 1
          for (int it = 0; it < 16; it++) { drained4(it, ph); plain6(h + it * 1024); }
          if (!ph) {
#pragma unroll 1
            for (int it = 0; it < 16; it++) { fresh(1, it, bar + B_FULL6 + s6 * 8, bar + B_EMPTY6 + s6 * 8, p6, sb + s6 * 32768, g_o + m * 16384); next6(); }
            skip6();
          }
        }
#pragma unroll 1
        for (int it = 0; it < 56; it++) {
          if (it == 0 || it == 32 || it == 48) mbar_wait(bar + (it == 48 ? B_HH2 : B_HH + (it >> 2)), 0);
          plain6(g_hh + m * 57344 + it * 1024);
        }
      }
    } else {
      const int b = warp - 10;
      const uint32_t ep = g_epoch[bid + 4] + 1;
      const uint32_t stg = sb + STG + b * BLK;
      cl_arrive_relaxed(); cl_wait();
      auto all_there = [&](int u, uint32_t done) {
        const uint32_t* fl = g_flag + u;
        uint32_t n = 0;
        while (!__all_sync(~0u, ld_acquire(fl) == ep)) { __nanosleep(100); SPIN_GUARD(n); }
        fence_async_global();
        if (lane == 0) mbar_arrive(done);
      };
      auto fetch_mod = [&](int sec) {
        const uint4* p = (const uint4*)(g_modv + (sec - 2) * 1024 + j * 128) + lane;
        uint4 v0, v1; uint32_t n = 0;
        while (true) {
          v0 = ld_rlx4(p); v1 = ld_rlx4(p + 32);
          if (v0.y == ep && v0.w == ep && v1.y == ep && v1.w == ep) break;
          SPIN_GUARD(n);
        }
        mod_store(sb, sec, 2 * lane, __uint_as_float(v0.x)); mod_store(sb, sec, 2 * lane + 1, __uint_as_float(v0.z));
        mod_store(sb, sec, 64 + 2 * lane, __uint_as_float(v1.x)); mod_store(sb, sec, 65 + 2 * lane, __uint_as_float(v1.z));
        __syncwarp();
      };
#pragma unroll 1
      for (int e = 0; e < 7 - b; e++) {
        const int kb = (e < 3 ? 2 * j : e < 6 ? 2 * (8 * (e - 3) + j) : 48 + j) + b;
        if (lane == 0) {
          if (e < 3) mbar_wait(bar + B_STORED, e & 1);
          if (e >= 3 || b) {
            mbar_wait(bar + B_RDY + b * 8, e & 1);
            if (e < 3) bulk_st((e == 1 ? g_o : g_h) + m * 16384 + kb * 1024, stg, BLK);
            else {
#pragma unroll 1
              for (int q = 0; q < NPIECE; q++) { if (q) __nanosleep(PSLEEP); bulk_st(g_hh + m * 57344 + kb * 1024 + q * (1024 / NPIECE), stg + q * (BLK / NPIECE), BLK / NPIECE); }
            }
            bulk_commit();
            bulk_wait_all();
            if (e < 3) { mbar_arrive(bar + B_STORED + 8); TR(53 + e); }
          }
          mbar_arrive(bar + B_FREE + b * 8);
          st_release(g_flag + m * 128 + (e < 3 ? e * 16 : U_HH) + kb, ep);
          if (e < 3) TR((e == 0 ? 26 : e == 2 ? 32 : 42) + b);
        }
        __syncwarp();
        if (e < 3 && b) all_there(m * 128 + e * 16 + (lane & 15), bar + B_ALL);
        if (e == 4 && b) all_there(m * 128 + U_HH + lane, bar + B_HH);
        if (!b && (e == 1 || e == 2)) {
#pragma unroll 1
          for (int sec = e == 1 ? 2 : 5; sec < 4 + e; sec++) fetch_mod(sec);
          if (e == 1) { if (lane == 0) mbar_arrive(bar + B_MOD); TR(50); }
        }
        if (e == 0 && m > 0) {
          mbar_wait(bar + B_EMPTY6 + 24, 0);
#pragma unroll 1
          for (int w = 0; w < 4; w++) {
            const uint4* hp = g_halo + ((m * 8 + j) * 2 + (w & 1)) * 512 + b * 256 + (w >> 1) * 128 + lane;
            uint4 q[4]; uint32_t n = 0;
            while (true) {
              bool ok = true;
#pragma unroll
              for (int i = 0; i < 4; i++) q[i] = ld_rlx4(hp + i * 32);
#pragma unroll
              for (int i = 0; i < 4; i++) ok = ok && q[i].y == ep && q[i].w == ep;
              if (ok) break;
              SPIN_GUARD(n);
            }
#pragma unroll
            for (int i = 0; i < 2; i++) sts128(stg + lane * 16 + (w & 1) * HALF + (w >> 1) * 1024 + i * 512, q[2 * i].x, q[2 * i].z, q[2 * i + 1].x, q[2 * i + 1].z);
          }
          __syncwarp();
          if (lane == 0) mbar_arrive(bar + B_HALO);
          if (b == 0) TR(52);
        }
      }
      if (b) { all_there(m * 128 + U_HH + 32 + (lane & 15), bar + B_HH + 8); all_there(m * 128 + U_HH + 48 + (lane & 7), bar + B_HH2); }
      if (lane == 0) {
        mbar_wait(bar + B_RDY + b * 8, b ^ 1);
        tma_store_3d(&maps.out, stg, j * 128 + b * 64, m * 64, 0);
        bulk_commit();
        bulk_wait_read();
      }
      TR(40 + b);
    }
  } else {
    asm volatile("setmaxnreg.inc.sync.aligned.u32 232;");
    const int wg = warp >> 2, wq = warp & 3, tid = threadIdx.x;
    const int g = lane >> 2, c = lane & 3;
    if (extra) {
      const uint32_t ep = g_epoch[bid + 4] + 1;
      float sv[4];
#pragma unroll
      for (int p = 0; p < 4; p++) sv[p] = silu_c(__bfloat162float(cvec[64 * (4 * p + (lane >> 3)) + 8 * warp + (lane & 7)]));
      named_bar(2, 288);
      int s = 0, par = 0;
#pragma unroll 1
      for (int sec = 0; sec < 4; sec++) {
        float a[8] = {0, 0, 0, 0, 0, 0, 0, 0};
#pragma unroll 1
        for (int it = 0; it < 16; it++) {
          const float sc = it < 4 ? sv[0] : it < 8 ? sv[1] : it < 12 ? sv[2] : sv[3];
          mbar_wait(bar + B_FULL6 + s * 8, par);
          uint4 w[8];
#pragma unroll
          for (int i = 0; i < 8; i++) w[i] = lds128(sb + s * 32768 + (warp * 8 + i) * 512 + lane * 16);
#pragma unroll
          for (int i = 0; i < 8; i++) gemv_fma(a, w[i], __shfl_sync(~0u, sc, (it & 3) * 8 + i));
          if (lane == 0) mbar_arrive(bar + B_EMPTY6 + s * 8);
          if (++s == 6) { s = 0; par ^= 1; }
        }
        const uint32_t red = sb + STG + sec * 8192;
        sts128(red + warp * 1024 + lane * 32, __float_as_uint(a[0]), __float_as_uint(a[1]), __float_as_uint(a[2]), __float_as_uint(a[3]));
        sts128(red + warp * 1024 + lane * 32 + 16, __float_as_uint(a[4]), __float_as_uint(a[5]), __float_as_uint(a[6]), __float_as_uint(a[7]));
        named_bar(1, 256);
        float t = 0;
#pragma unroll
        for (int q = 0; q < 8; q++) t += lds32f(red + q * 1024 + tid * 4);
        st_rlx2(g_modv + sec * 1024 + (bid + 4) * 256 + tid, __float_as_uint(t), ep);
      }
      if (tid == 0) g_epoch[bid + 4] = ep;
      return;
    }
    if (warp == 0) TR(0);
    const int sec0 = (m >> 1) & 1, hf0 = m & 1, ks0 = m >> 2;
    const int row0 = wg * 64 + wq * 16 + g;
    if (c < 2) st_rlx4(g_stat + m * 1024 + j * 128 + row0 + c * 8, 0, 0, 0, 0);
    if (tid < 64) st_rlx2(g_modp + ((j * 2 + sec0) * 4 + ks0) * 128 + hf0 * 64 + tid, 0, 0);
    uint4 wv[8];
    {
      const bf16* wp = wmod + (size_t)(ks0 * 256 + warp * 32 + (lane >> 3)) * 6144 + sec0 * 1024 + j * 128 + hf0 * 64 + (lane & 7) * 8;
#pragma unroll
      for (int i = 0; i < 8; i++) wv[i] = ldg_nc(wp + (size_t)i * 4 * 6144);
    }
    const float sc_ = silu_c(__bfloat162float(cvec[ks0 * 256 + warp * 32 + lane]));
    const uint32_t ep = g_epoch[bid + 4] + 1;
    cl_arrive_relaxed(); cl_wait();
    const uint32_t rel = mapa(bar, (lane & 1) ^ rank);
    const uint32_t stg_row = sb + STG + (wg * 64 + wq * 16 + (lane & 15)) * 128;
    const uint32_t fre = bar + B_FREE;
    Ring r4{0, 0, 0}, r6{0, 0, 0};
    auto none = [](auto) {};
    {
      float v[64];
      mbar_wait(bar + B_X, 0); mbar_wait(bar + B_X + 8, 0);
#pragma unroll
      for (int i = 0; i < 16; i += 2) {
        uint32_t w0, w1, w2, w3;
        ldsm4(stg_row + (i >> 3) * BLK + ((((i & 7) + (lane >> 4)) ^ (lane & 7)) << 4), w0, w1, w2, w3);
        v[4 * i] = bf_lo(w0); v[4 * i + 1] = bf_hi(w0); v[4 * i + 2] = bf_lo(w1); v[4 * i + 3] = bf_hi(w1);
        v[4 * i + 4] = bf_lo(w2); v[4 * i + 5] = bf_hi(w2); v[4 * i + 6] = bf_lo(w3); v[4 * i + 7] = bf_hi(w3);
      }
      ln_publish(v, g_stat + m * 1024, j, row0, lane, ep);
      if (warp == 0) TR(1);
      float a[8] = {0, 0, 0, 0, 0, 0, 0, 0};
#pragma unroll
      for (int i = 0; i < 8; i++) gemv_fma(a, wv[i], __shfl_sync(~0u, sc_, i * 4 + (lane >> 3)));
#pragma unroll
      for (int i = 0; i < 8; i++) { a[i] += __shfl_xor_sync(~0u, a[i], 8); a[i] += __shfl_xor_sync(~0u, a[i], 16); }
      if (lane < 8) {
        sts128(sb + RED_OFF + warp * 256 + lane * 32, __float_as_uint(a[0]), __float_as_uint(a[1]), __float_as_uint(a[2]), __float_as_uint(a[3]));
        sts128(sb + RED_OFF + warp * 256 + lane * 32 + 16, __float_as_uint(a[4]), __float_as_uint(a[5]), __float_as_uint(a[6]), __float_as_uint(a[7]));
      }
      named_bar(1, 256);
      if (tid == 64) mbar_arrive(bar + B_GO);
      if (tid < 64) {
        float s = 0;
#pragma unroll
        for (int w = 0; w < 8; w++) s += lds32f(sb + RED_OFF + w * 256 + tid * 4);
        st_rlx2(g_modp + ((j * 2 + sec0) * 4 + ks0) * 128 + hf0 * 64 + tid, __float_as_uint(s), ep);
      }
      if (warp == 0) TR(2);
      float mu0, r0, mu1, r1;
      ln_gather(g_stat + m * 1024, row0, lane, ep, mu0, r0, mu1, r1);
      mod_store(sb, tid >> 7, tid & 127, mod_gather(g_modp + (j * 2 + (tid >> 7)) * 512 + (tid & 127), ep));
      named_bar(1, 256);
      if (warp == 0) TR(3);
      ln_apply(v, mu0, r0, mu1, r1, sb, 0, 1, stg_row, wg, lane);
      named_bar(2 + wg, 128);
    }
    if (warp == 0) TR(4);
    {
      uint32_t kf[32], vf[32];
      const uint32_t xa = sb + STG + wg * HALF + wq * 2048 + lane * 16;
      {
        float acc[128];
        mainloop<256, 4, 0>(acc, 16, true, r4, sb, wg, lane, rel, bid * 192 + 0, none, none, [] {});
        if (warp == 0) TR(5);
#pragma unroll
        for (int i = 0; i < 32; i++) { kf[i] = pack2(acc[2 * i], acc[2 * i + 1]); vf[i] = pack2(acc[64 + 2 * i], acc[65 + 2 * i]); }
      }
      if (warp == 0) TR(6);
      float acc[64];
      mainloop<128, 6, 4>(acc, 16, false, r6, sb, wg, lane, rel, bid * 192 + 16, [&](auto ic) {
        constexpr int q = ic.v - 1;
#pragma unroll
        for (int i = 8 * q; i < 8 * q + 8; i++) vf[i] = movm(vf[i]);
        if ((q & 1) == 0) mbar_wait(fre + 4 * q, 0);
        if (wq == 3) {
          if (m < 15) {
            uint4* hp = g_halo + (((m + 1) * 8 + j) * 2 + wg) * 512 + lane;
#pragma unroll
            for (int i = 4 * q; i < 4 * q + 4; i++) st_rlx4(hp + i * 32, kf[2 * i + 1], ep, vf[2 * i + 1], ep);
          }
        } else {
#pragma unroll
          for (int i = 2 * q; i < 2 * q + 2; i++) sts128(xa + 2048 + (i >> 2) * BLK + (i & 3) * 512, kf[4 * i + 1], vf[4 * i + 1], kf[4 * i + 3], vf[4 * i + 3]);
        }
        if (q == 3 && c < 2) st_rlx4(g_stat + (16 + m) * 1024 + j * 128 + row0 + c * 8, 0, 0, 0, 0);
      }, none, [&] {
        named_bar(2 + wg, 128);
        if (wq == 0 && m > 0) mbar_wait(bar + B_HALO, 0);
      });
      if (warp == 0) TR(7);
      const bool first = wq == 0 && m == 0;
      const bool up0 = 2 * c > g, up1 = 2 * c + 1 > g;
      const uint32_t mup = (up0 ? 0xffffu : 0u) | (up1 ? 0xffff0000u : 0u);
#pragma unroll
      for (int b = 0; b < 2; b++) {
        uint32_t qf[16], pv[16];
#pragma unroll
        for (int i = 0; i < 4; i++) {
          uint4 q = lds128(xa + b * BLK + i * 512);
          if (first) q = make_uint4(0, 0, 0, 0);
          pv[4 * i] = q.x; pv[4 * i + 1] = q.y; pv[4 * i + 2] = q.z; pv[4 * i + 3] = q.w;
        }
#pragma unroll
        for (int i = 0; i < 16; i++) qf[i] = pack2(acc[32 * b + 2 * i], acc[32 * b + 2 * i + 1]);
        __syncwarp();
        uint32_t pa[2], pb[2];
#pragma unroll
        for (int h = 0; h < 2; h++) {
          float s0[4] = {0, 0, 0, 0}, s1[4] = {0, 0, 0, 0}, s2[4] = {0, 0, 0, 0};
#pragma unroll
          for (int ks = 0; ks < 2; ks++) {
            const int i = 4 * h + 2 * ks, k = 16 * b + 2 * i;
            mma16(s1, qf[2 * i], qf[2 * i + 1], qf[2 * i + 2], qf[2 * i + 3], kf[k], kf[k + 2]);
            mma16(s2, qf[2 * i], qf[2 * i + 1], qf[2 * i + 2], qf[2 * i + 3], kf[k + 1], kf[k + 3]);
            mma16(s0, qf[2 * i], qf[2 * i + 1], qf[2 * i + 2], qf[2 * i + 3], pv[2 * i], pv[2 * i + 2]);
          }
          if (first) { s0[0] = -INFINITY; s0[1] = -INFINITY; }
          float a0 = (up0 ? s0[0] : s1[0]) * SCL, a1 = (up1 ? s0[1] : s1[1]) * SCL;
          float b0 = (up0 ? s1[2] : s2[2]) * SCL, b1 = (up1 ? s1[3] : s2[3]) * SCL;
          float ma = fmaxf(a0, a1), mb = fmaxf(b0, b1);
          ma = fmaxf(ma, __shfl_xor_sync(~0u, ma, 1)); mb = fmaxf(mb, __shfl_xor_sync(~0u, mb, 1));
          ma = fmaxf(ma, __shfl_xor_sync(~0u, ma, 2)); mb = fmaxf(mb, __shfl_xor_sync(~0u, mb, 2));
          a0 = ex2(a0 - ma); a1 = ex2(a1 - ma); b0 = ex2(b0 - mb); b1 = ex2(b1 - mb);
          float sa = a0 + a1, sbm = b0 + b1;
          sa += __shfl_xor_sync(~0u, sa, 1); sbm += __shfl_xor_sync(~0u, sbm, 1);
          sa += __shfl_xor_sync(~0u, sa, 2); sbm += __shfl_xor_sync(~0u, sbm, 2);
          sa = __fdividef(1.f, sa); sbm = __fdividef(1.f, sbm);
          pa[h] = pack2(a0 * sa, a1 * sa); pb[h] = pack2(b0 * sbm, b1 * sbm);
        }
#pragma unroll
        for (int i = 0; i < 8; i += 2) {
          uint32_t of[4];
#pragma unroll
          for (int d = 0; d < 2; d++) {
            float o[4] = {0, 0, 0, 0};
            mma16(o, pa[i >> 2] & ~mup, pb[i >> 2] & mup, 0u, pb[i >> 2] & ~mup, vf[16 * b + 2 * (i + d)], vf[16 * b + 2 * (i + d) + 1]);
            mma8(o, pa[i >> 2] & mup, 0u, pv[2 * (i + d) + 1]);
            of[2 * d] = pack2(o[0], o[1]); of[2 * d + 1] = pack2(o[2], o[3]);
          }
          stsm4(stg_row + b * BLK + (((i + (lane >> 4)) ^ (lane & 7)) << 4), of[0], of[1], of[2], of[3]);
        }
        stage_done(sb, wg, b, lane);
      }
      named_bar(1, 256);
      if (warp == 0) TR(8);
    }
    uint32_t pk[64];
    {
      float acc[64];
      mainloop<128, 6, 0>(acc, 16, true, r6, sb, wg, lane, rel, bid * 192 + 32, none, none, [&] {
        mbar_wait(bar + B_MOD, 0); mbar_wait(bar + B_X, 1); mbar_wait(bar + B_X + 8, 1);
        load_vec(pk + 32, sb, 2, 0, lane); load_vec(pk + 40, sb, 2, 1, lane);
#pragma unroll
        for (int i = 0; i < 16; i += 2) ldsm4(stg_row + (i >> 3) * BLK + ((((i & 7) + (lane >> 4)) ^ (lane & 7)) << 4), pk[2 * i], pk[2 * i + 1], pk[2 * i + 2], pk[2 * i + 3]);
      });
      if (warp == 0) TR(9);
#pragma unroll
      for (int i = 0; i < 32; i++) {
        acc[2 * i] = fmaf(acc[2 * i], bf_lo(pk[32 + (i >> 1)]), bf_lo(pk[i]));
        acc[2 * i + 1] = fmaf(acc[2 * i + 1], bf_hi(pk[32 + (i >> 1)]), bf_hi(pk[i]));
      }
      ln_publish(acc, g_stat + (16 + m) * 1024, j, row0, lane, ep);
      if (warp == 0) TR(36);
      mbar_wait(bar + B_FULL6 + 16, 1);
      if (lane < 2) mbar_arrive_cl(rel + B_EMPTY6 + 16);
      ring_next<6>(r6);
#pragma unroll
      for (int i = 0; i < 32; i++) { pk[i] = pack2(acc[2 * i], acc[2 * i + 1]); pk[32 + i] = 0; }
      float mu0, r0, mu1, r1;
      ln_gather(g_stat + (16 + m) * 1024, row0, lane, ep, mu0, r0, mu1, r1);
      if (warp == 0) TR(10);
      ln_apply(acc, mu0, r0, mu1, r1, sb, 3, 4, stg_row, wg, lane);
      named_bar(2 + wg, 128);
      if (warp == 0) TR(11);
    }
    auto swiglu = [&](int q, int uo, int par) {
      if ((q & 3) == 0) mbar_wait(fre + 2 * q, par);
      uint32_t w[4];
#pragma unroll
      for (int u = 0; u < 4; u++) w[u] = silu_mul2(pk[4 * q + u], pk[uo + 4 * q + u]);
      stsm4(stg_row + (q >> 2) * BLK + ((((2 * q & 7) + (lane >> 4)) ^ (lane & 7)) << 4), w[0], w[1], w[2], w[3]);
    };
    r4.s = r4.wrap = 2;
#pragma unroll 1
    for (int t = 0; t < 3; t++) {
      float acc[128];
      mainloop<256, 4, 5>(acc, 16, t == 0, r4, sb, wg, lane, rel, bid * 192 + 48 + 16 * t, [&](auto ic) {
        if (t) {
          if (ic.v == 3 || ic.v == 5) stage_done(sb, wg, ic.v >> 2, lane);
          if (ic.v < 5) { swiglu(2 * ic.v - 2, 32, ~t & 1); swiglu(2 * ic.v - 1, 32, 0); }
        }
      }, [&](int it) {
#pragma unroll
        for (int i = 0; i < 8; i++)
          if (t == 0 && it == 6 + i) g_x1[bid * 2048 + (i >> 2) * 1024 + warp * 128 + (i & 3) * 32 + lane] = make_uint4(pk[4 * i], pk[4 * i + 1], pk[4 * i + 2], pk[4 * i + 3]);
      }, [&] { if (t == 0) fence_async_global(); });
      if (warp == 0) TR(12 + 2 * t);
#pragma unroll
      for (int i = 0; i < 64; i++) pk[i] = pack2(acc[2 * i], acc[2 * i + 1]);
      if (warp == 0) TR(13 + 2 * t);
    }
    uint32_t x1[32];
    {
      float acc[64];
      mainloop<128, 6, 6>(acc, 16, false, r6, sb, wg, lane, rel, bid * 192 + 96, [&](auto ic) {
        if (ic.v == 1) {
          mbar_wait(bar + B_X, 0);
#pragma unroll
          for (int i = 0; i < 8; i++) { const uint4 x = lds128(sb + STG + (i >> 2) * BLK + warp * 2048 + (i & 3) * 512 + lane * 16); x1[4 * i] = x.x; x1[4 * i + 1] = x.y; x1[4 * i + 2] = x.z; x1[4 * i + 3] = x.w; }
          __syncwarp();
        }
        if (ic.v == 4 || ic.v == 6) stage_done(sb, wg, ic.v / 5, lane);
        if (ic.v > 1 && ic.v < 6) { swiglu(2 * ic.v - 4, 32, 0); swiglu(2 * ic.v - 3, 32, 0); }
      }, none, [] {});
      if (warp == 0) TR(18);
#pragma unroll
      for (int i = 0; i < 32; i++) pk[i] = pack2(acc[2 * i], acc[2 * i + 1]);
      if (warp == 0) TR(19);
    }
    {
      float acc[64];
      mainloop<128, 6, 3>(acc, 56, false, r6, sb, wg, lane, rel, bid * 192 + 112, [&](auto ic) {
        if (ic.v == 3) stage_done(sb, wg, 0, lane); else { swiglu(2 * ic.v - 2, 16, 1); swiglu(2 * ic.v - 1, 16, 1); }
      }, none, [&] {
        load_vec(pk + 32, sb, 5, 0, lane); load_vec(pk + 40, sb, 5, 1, lane);
        mbar_wait(fre, 0); mbar_wait(fre + 8, 1);
      });
      __syncwarp();
      cl_arrive_relaxed();
      if (warp == 0) TR(20);
#pragma unroll
      for (int i = 0; i < 16; i += 2) {
        uint32_t w[4];
#pragma unroll
        for (int u = 0; u < 4; u++) {
          const int q = 2 * i + u;
          w[u] = pack2(fmaf(acc[2 * q], bf_lo(pk[32 + (q >> 1)]), bf_lo(x1[q])), fmaf(acc[2 * q + 1], bf_hi(pk[32 + (q >> 1)]), bf_hi(x1[q])));
        }
        stsm4(stg_row + (i >> 3) * BLK + ((((i & 7) + (lane >> 4)) ^ (lane & 7)) << 4), w[0], w[1], w[2], w[3]);
        if ((i & 7) == 6) stage_done(sb, wg, i >> 3, lane);
      }
      if (tid == 0) g_epoch[bid + 4] = ep;
      if (warp == 0) TR(21);
      cl_wait();
    }
  }
}

typedef CUresult (*EncodeFn)(CUtensorMap*, CUtensorMapDataType, cuuint32_t, void*, const cuuint64_t*, const cuuint64_t*, const cuuint32_t*, const cuuint32_t*,
                             CUtensorMapInterleave, CUtensorMapSwizzle, CUtensorMapL2promotion, CUtensorMapFloatOOBfill);

void make_map(EncodeFn fn, CUtensorMap* mp, const void* base, uint64_t d0, uint64_t d1, uint64_t d2, uint64_t s1, uint64_t s2, uint32_t b2, uint32_t b0 = 64) {
  cuuint64_t d[3] = {d0, d1, d2}, s[2] = {s1, s2};
  cuuint32_t b[3] = {b0, 64, b2}, e[3] = {1, 1, 1};
  fn(mp, CU_TENSOR_MAP_DATA_TYPE_BFLOAT16, 3, (void*)base, d, s, b, e, CU_TENSOR_MAP_INTERLEAVE_NONE, b0 == 64 ? CU_TENSOR_MAP_SWIZZLE_128B : CU_TENSOR_MAP_SWIZZLE_NONE,
     CU_TENSOR_MAP_L2_PROMOTION_L2_128B, CU_TENSOR_MAP_FLOAT_OOB_FILL_NONE);
}

__global__ void probe_kernel() {}
int max_clusters(int size) {
  cudaLaunchConfig_t cfg = {};
  cudaLaunchAttribute at;
  at.id = cudaLaunchAttributeClusterDimension; at.val.clusterDim.x = size; at.val.clusterDim.y = 1; at.val.clusterDim.z = 1;
  cfg.gridDim = dim3(size * 66); cfg.blockDim = dim3(384); cfg.dynamicSmemBytes = SMEM_BYTES; cfg.attrs = &at; cfg.numAttrs = 1;
  int n = 0;
  if (cudaOccupancyMaxActiveClusters(&n, probe_kernel, &cfg) != cudaSuccess) { cudaGetLastError(); return 0; }
  return n;
}

}

extern "C" void kernel_launch(void* const* d_in, const int* in_sizes, int n_in, void* d_out, int out_size) {
  static EncodeFn fn = nullptr;
  static int by_sm = 0;
  if (!fn) {
    void* p = nullptr; cudaDriverEntryPointQueryResult q;
    cudaGetDriverEntryPoint("cuTensorMapEncodeTiled", &p, cudaEnableDefault, &q);
    fn = (EncodeFn)p;
    cudaFuncSetAttribute(fused_kernel, cudaFuncAttributeMaxDynamicSharedMemorySize, SMEM_BYTES);
    int dev = 0, sms = 0;
    cudaGetDevice(&dev);
    cudaDeviceGetAttribute(&sms, cudaDevAttrMultiProcessorCount, dev);
    cudaFuncSetAttribute(probe_kernel, cudaFuncAttributeMaxDynamicSharedMemorySize, SMEM_BYTES);
    by_sm = BYSM && sms == 132 && max_clusters(2) == 66 && max_clusters(4) == 30 && max_clusters(6) == 17 && max_clusters(8) == 15;
  }
  Maps mp;
  make_map(fn, &mp.x, d_in[0], D_, S_ / 2, 2, 4096, 2048, 2);
  make_map(fn, &mp.out, d_out, D_, S_ / 2, 2, 4096, 2048, 2);
  make_map(fn, &mp.wqkv, d_in[1], 64, D_, 3 * D_ / 64, 3 * D_ * 2, 128, 2);
  make_map(fn, &mp.wo, d_in[2], 64, D_, D_ / 64, D_ * 2, 128, 2);
  make_map(fn, &mp.w1, d_in[4], 64, D_, F_ / 64, F_ * 2, 128, 2);
  make_map(fn, &mp.w3, d_in[5], 64, D_, F_ / 64, F_ * 2, 128, 2);
  make_map(fn, &mp.w1s, d_in[4], 64, D_, F_ / 64, F_ * 2, 128, 1);
  make_map(fn, &mp.w3s, d_in[5], 64, D_, F_ / 64, F_ * 2, 128, 1);
  make_map(fn, &mp.w2, d_in[6], 64, F_, D_ / 64, D_ * 2, 128, 2);
  make_map(fn, &mp.wmod, d_in[8], 256, D_, 24, 6 * D_ * 2, 512, 1, 256);
  fused_kernel<<<132, 384, SMEM_BYTES>>>(mp, (const bf16*)d_in[7], (const bf16*)d_in[8], by_sm);
}
```

```cpp
#include <cuda_runtime.h>
#include <cuda_bf16.h>
#include <cuda.h>
#include <stdint.h>

typedef __nv_bfloat16 bf16;

#define NPIECE 8
#define PSLEEP 150
#define BGATE 0
#define XSLEEP 2500
#define XDELAY 3000
#define TAILLAG 5
#define BYSM 1
namespace {

constexpr int S_ = 2048, D_ = 1024, F_ = 3584;
constexpr int BLK = 16384;
constexpr int HALF = 8192;
constexpr int RING = 196608;
constexpr int STG = RING;
constexpr int MISC = RING + 2 * BLK;
constexpr int SMEM_BYTES = MISC + 3072;
constexpr int B_FULL4 = 0, B_EMPTY4 = 32, B_FULL6 = 64, B_EMPTY6 = 112, B_RDY = 160, B_FREE = 176, B_LAG = 192, B_X = 208, B_MOD = 224, B_HALO = 232, B_OWN = 240, B_HH = 256, B_ALL = 272, B_HH2 = 288, ZERO = 296;
constexpr int MODV = 512;
constexpr int RED_OFF = 0;
constexpr float SCL = 0.17677669529663687f * 1.4426950408889634f;
constexpr int U_HH = 64;

struct Maps { CUtensorMap x, out, wqkv, wo, w1, w3, w1s, w3s, w2, wmod; };

__device__ uint4 g_h[16 * 16 * 1024];
__device__ uint4 g_o[16 * 16 * 1024];
__device__ uint4 g_hh[16 * 56 * 1024];
__device__ uint4 g_x1[128 * 8 * 256];
__device__ uint2 g_modp[8 * 2 * 4 * 128];
__device__ uint2 g_modv[4 * 1024];
__device__ uint4 g_stat[2 * 16 * 8 * 128];
__device__ uint4 g_halo[16 * 8 * 2 * 512];
__device__ uint32_t g_flag[16 * 128];
__device__ uint32_t g_epoch[132];
#define TR(i)
#define TRS(i)

__device__ __forceinline__ void bail() { asm volatile("st.global.u32 [%0], %1;" :: "l"(0ull), "r"(0) : "memory"); }
__device__ __forceinline__ uint32_t smem_u32(const void* p) { return (uint32_t)__cvta_generic_to_shared(p); }
__device__ __forceinline__ void mbar_init(uint32_t bar, uint32_t cnt) { asm volatile("mbarrier.init.shared::cta.b64 [%0], %1;" :: "r"(bar), "r"(cnt) : "memory"); }
__device__ __forceinline__ void mbar_expect_tx(uint32_t bar, uint32_t bytes) { asm volatile("mbarrier.arrive.expect_tx.shared::cta.b64 _, [%0], %1;" :: "r"(bar), "r"(bytes) : "memory"); }
__device__ __forceinline__ void mbar_arrive(uint32_t bar) { asm volatile("mbarrier.arrive.shared::cta.b64 _, [%0];" :: "r"(bar) : "memory"); }
__device__ __forceinline__ void mbar_arrive_cl(uint32_t cl_addr) { asm volatile("mbarrier.arrive.shared::cluster.b64 _, [%0];" :: "r"(cl_addr) : "memory"); }
__device__ __forceinline__ uint32_t mapa(uint32_t addr, uint32_t cta) { uint32_t r; asm("mapa.shared::cluster.u32 %0, %1, %2;" : "=r"(r) : "r"(addr), "r"(cta)); return r; }
__device__ __forceinline__ void mbar_wait(uint32_t bar, uint32_t parity) {
  asm volatile("{\n.reg .pred p;\n.reg .b32 n;\n.reg .b64 z;\nmov.b32 n, 0;\nmov.b64 z, 0;\n"
               "W: add.u32 n, n, 1;\nsetp.gt.u32 p, n, 0x400000;\n@p st.global.u32 [z], n;\n"
               "mbarrier.try_wait.parity.shared::cta.b64 p, [%0], %1;\n@!p bra W;\n}" :: "r"(bar), "r"(parity) : "memory");
}
__device__ __forceinline__ void tma_3d(uint32_t dst, const CUtensorMap* m, uint32_t bar, int c0, int c1, int c2) {
  asm volatile("cp.async.bulk.tensor.3d.shared::cluster.global.mbarrier::complete_tx::bytes [%0], [%1, {%3, %4, %5}], [%2];" :: "r"(dst), "l"(m), "r"(bar), "r"(c0), "r"(c1), "r"(c2) : "memory");
}
__device__ __forceinline__ void tma_store_3d(const CUtensorMap* m, uint32_t src, int c0, int c1, int c2) {
  asm volatile("cp.async.bulk.tensor.3d.global.shared::cta.bulk_group [%0, {%2, %3, %4}], [%1];" :: "l"(m), "r"(src), "r"(c0), "r"(c1), "r"(c2) : "memory");
}
__device__ __forceinline__ void bulk_ld(uint32_t dst, const void* src, uint32_t bytes, uint32_t bar) {
  asm volatile("cp.async.bulk.shared::cluster.global.mbarrier::complete_tx::bytes [%0], [%1], %2, [%3];" :: "r"(dst), "l"(src), "r"(bytes), "r"(bar) : "memory");
}
__device__ __forceinline__ void bulk_ld_mc(uint32_t dst, const void* src, uint32_t bytes, uint32_t bar) {
  asm volatile("cp.async.bulk.shared::cluster.global.mbarrier::complete_tx::bytes.multicast::cluster [%0], [%1], %2, [%3], %4;" :: "r"(dst), "l"(src), "r"(bytes), "r"(bar), "h"((uint16_t)3) : "memory");
}
__device__ __forceinline__ void bulk_st(void* dst, uint32_t src, uint32_t bytes) {
  asm volatile("cp.async.bulk.global.shared::cta.bulk_group [%0], [%1], %2;" :: "l"(dst), "r"(src), "r"(bytes) : "memory");
}
__device__ __forceinline__ void bulk_commit() { asm volatile("cp.async.bulk.commit_group;" ::: "memory"); }
__device__ __forceinline__ void bulk_wait_read() { asm volatile("cp.async.bulk.wait_group.read 0;" ::: "memory"); }
__device__ __forceinline__ void bulk_wait_all() { asm volatile("cp.async.bulk.wait_group 0;" ::: "memory"); }
__device__ __forceinline__ void fence_async_global() { asm volatile("fence.proxy.async.global;" ::: "memory"); }
__device__ __forceinline__ void fence_async_smem() { asm volatile("fence.proxy.async.shared::cta;" ::: "memory"); }
__device__ __forceinline__ void wg_arrive() { asm volatile("wgmma.fence.sync.aligned;" ::: "memory"); }
__device__ __forceinline__ void wg_commit() { asm volatile("wgmma.commit_group.sync.aligned;" ::: "memory"); }
template <int N> __device__ __forceinline__ void wg_wait() { asm volatile("wgmma.wait_group.sync.aligned %0;" :: "n"(N) : "memory"); }
__device__ __forceinline__ void cl_arrive_relaxed() { asm volatile("barrier.cluster.arrive.relaxed.aligned;" ::: "memory"); }
__device__ __forceinline__ void cl_wait() { asm volatile("barrier.cluster.wait.acquire.aligned;" ::: "memory"); }
__device__ __forceinline__ bool elect() { uint32_t p; asm volatile("{\n.reg .pred p;\nelect.sync _|p, 0xffffffff;\nselp.u32 %0, 1, 0, p;\n}" : "=r"(p)); return p; }
__device__ __forceinline__ void named_bar(int id, int n) { asm volatile("bar.sync %0, %1;" :: "r"(id), "r"(n) : "memory"); }
__device__ __forceinline__ uint32_t pack2(float lo, float hi) { uint32_t r; asm("cvt.rn.bf16x2.f32 %0, %1, %2;" : "=r"(r) : "f"(hi), "f"(lo)); return r; }
__device__ __forceinline__ float bf_lo(uint32_t w) { return __uint_as_float(w << 16); }
__device__ __forceinline__ float bf_hi(uint32_t w) { return __uint_as_float(w & 0xffff0000u); }
__device__ __forceinline__ float bf_round(float v) { return __bfloat162float(__float2bfloat16_rn(v)); }
__device__ __forceinline__ void stsm4(uint32_t addr, uint32_t a, uint32_t b, uint32_t c, uint32_t d) {
  asm volatile("stmatrix.sync.aligned.m8n8.x4.shared.b16 [%0], {%1, %2, %3, %4};" :: "r"(addr), "r"(a), "r"(b), "r"(c), "r"(d) : "memory");
}
__device__ __forceinline__ void ldsm4(uint32_t addr, uint32_t& a, uint32_t& b, uint32_t& c, uint32_t& d) {
  asm volatile("ldmatrix.sync.aligned.m8n8.x4.shared.b16 {%0, %1, %2, %3}, [%4];" : "=r"(a), "=r"(b), "=r"(c), "=r"(d) : "r"(addr) : "memory");
}
__device__ __forceinline__ uint32_t movm(uint32_t a) { uint32_t r; asm volatile("movmatrix.sync.aligned.m8n8.trans.b16 %0, %1;" : "=r"(r) : "r"(a)); return r; }
__device__ __forceinline__ void mma16(float (&d)[4], uint32_t a0, uint32_t a1, uint32_t a2, uint32_t a3, uint32_t b0, uint32_t b1) {
  asm("mma.sync.aligned.m16n8k16.row.col.f32.bf16.bf16.f32 {%0,%1,%2,%3}, {%4,%5,%6,%7}, {%8,%9}, {%0,%1,%2,%3};"
               : "+f"(d[0]), "+f"(d[1]), "+f"(d[2]), "+f"(d[3]) : "r"(a0), "r"(a1), "r"(a2), "r"(a3), "r"(b0), "r"(b1));
}
__device__ __forceinline__ void mma16z(float (&d)[4], uint32_t a0, uint32_t a1, uint32_t a2, uint32_t a3, uint32_t b0, uint32_t b1) {
  asm("mma.sync.aligned.m16n8k16.row.col.f32.bf16.bf16.f32 {%0,%1,%2,%3}, {%4,%5,%6,%7}, {%8,%9}, {%10,%10,%10,%10};"
      : "=f"(d[0]), "=f"(d[1]), "=f"(d[2]), "=f"(d[3]) : "r"(a0), "r"(a1), "r"(a2), "r"(a3), "r"(b0), "r"(b1), "f"(0.f));
}
__device__ __forceinline__ void mma8z(float (&d)[4], uint32_t a0, uint32_t a1, uint32_t b0) {
  asm("mma.sync.aligned.m16n8k8.row.col.f32.bf16.bf16.f32 {%0,%1,%2,%3}, {%4,%5}, {%6}, {%7,%7,%7,%7};"
      : "=f"(d[0]), "=f"(d[1]), "=f"(d[2]), "=f"(d[3]) : "r"(a0), "r"(a1), "r"(b0), "f"(0.f));
}
__device__ __forceinline__ void mma8(float (&d)[4], uint32_t a0, uint32_t a1, uint32_t b0) {
  asm("mma.sync.aligned.m16n8k8.row.col.f32.bf16.bf16.f32 {%0,%1,%2,%3}, {%4,%5}, {%6}, {%0,%1,%2,%3};"
               : "+f"(d[0]), "+f"(d[1]), "+f"(d[2]), "+f"(d[3]) : "r"(a0), "r"(a1), "r"(b0));
}
__device__ __forceinline__ uint4 lds128(uint32_t a) { uint4 v; asm volatile("ld.shared.v4.u32 {%0,%1,%2,%3}, [%4];" : "=r"(v.x), "=r"(v.y), "=r"(v.z), "=r"(v.w) : "r"(a) : "memory"); return v; }
__device__ __forceinline__ void sts128(uint32_t a, uint32_t x, uint32_t y, uint32_t z, uint32_t w) { asm volatile("st.shared.v4.u32 [%0], {%1,%2,%3,%4};" :: "r"(a), "r"(x), "r"(y), "r"(z), "r"(w) : "memory"); }
__device__ __forceinline__ float lds32f(uint32_t a) { float v; asm volatile("ld.shared.f32 %0, [%1];" : "=f"(v) : "r"(a) : "memory"); return v; }
__device__ __forceinline__ void sts16(uint32_t a, bf16 v) { asm volatile("st.shared.b16 [%0], %1;" :: "r"(a), "h"(__bfloat16_as_ushort(v)) : "memory"); }
__device__ __forceinline__ uint4 ldg_nc(const void* p) { uint4 v; asm volatile("ld.global.nc.L1::no_allocate.v4.u32 {%0,%1,%2,%3}, [%4];" : "=r"(v.x), "=r"(v.y), "=r"(v.z), "=r"(v.w) : "l"(p)); return v; }
__device__ __forceinline__ uint4 ld_rlx4(const uint4* p) {
  unsigned long long a, b; asm volatile("ld.relaxed.gpu.global.v2.b64 {%0,%1}, [%2];" : "=l"(a), "=l"(b) : "l"(p) : "memory");
  return make_uint4((uint32_t)a, (uint32_t)(a >> 32), (uint32_t)b, (uint32_t)(b >> 32));
}
__device__ __forceinline__ uint2 ld_rlx2(const uint2* p) { unsigned long long a; asm volatile("ld.relaxed.gpu.global.b64 %0, [%1];" : "=l"(a) : "l"(p) : "memory"); return make_uint2((uint32_t)a, (uint32_t)(a >> 32)); }
__device__ __forceinline__ void st_rlx4(uint4* p, uint32_t x, uint32_t y, uint32_t z, uint32_t w) {
  asm volatile("st.relaxed.gpu.global.v2.b64 [%0], {%1,%2};" :: "l"(p), "l"((unsigned long long)x | ((unsigned long long)y << 32)), "l"((unsigned long long)z | ((unsigned long long)w << 32)) : "memory");
}
__device__ __forceinline__ void st_rlx2(uint2* p, uint32_t x, uint32_t y) { asm volatile("st.relaxed.gpu.global.b64 [%0], %1;" :: "l"(p), "l"((unsigned long long)x | ((unsigned long long)y << 32)) : "memory"); }
__device__ __forceinline__ void st_release(uint32_t* p, uint32_t v) { asm volatile("st.release.gpu.global.u32 [%0], %1;" :: "l"(p), "r"(v) : "memory"); }
__device__ __forceinline__ uint32_t ld_acquire(const uint32_t* p) { uint32_t v; asm volatile("ld.acquire.gpu.global.u32 %0, [%1];" : "=r"(v) : "l"(p) : "memory"); return v; }
__device__ __forceinline__ void prefetch_map(const CUtensorMap* m) { asm volatile("prefetch.tensormap [%0];" :: "l"(m) : "memory"); }
__device__ __forceinline__ float rcp(float x) { float r; asm("rcp.approx.ftz.f32 %0, %1;" : "=f"(r) : "f"(x)); return r; }
__device__ __forceinline__ float ex2(float x) { float r; asm("ex2.approx.ftz.f32 %0, %1;" : "=f"(r) : "f"(x)); return r; }
__device__ __forceinline__ float tanh_fast(float x) { float r; asm("tanh.approx.f32 %0, %1;" : "=f"(r) : "f"(x)); return r; }
#define SPIN_GUARD(n) if (++(n) > (1u << 24)) bail()

__device__ __forceinline__ void wgmma_n128(float (&d)[64], uint64_t da, uint64_t db) {
  asm volatile("wgmma.mma_async.sync.aligned.m64n128k16.f32.bf16.bf16 "
    "{%0, %1, %2, %3, %4, %5, %6, %7, %8, %9, %10, %11, %12, %13, %14, %15, %16, %17, %18, %19, %20, %21, %22, %23, %24, %25, %26, %27, %28, %29, %30, %31, %32, %33, %34, %35, %36, %37, %38, %39, %40, %41, %42, %43, %44, %45, %46, %47, %48, %49, %50, %51, %52, %53, %54, %55, %56, %57, %58, %59, %60, %61, %62, %63}, "
    "%64, %65, 1, 1, 1, 0, 1;\n"
    : "+f"(d[0]), "+f"(d[1]), "+f"(d[2]), "+f"(d[3]), "+f"(d[4]), "+f"(d[5]), "+f"(d[6]), "+f"(d[7]), "+f"(d[8]), "+f"(d[9]), "+f"(d[10]), "+f"(d[11]), "+f"(d[12]), "+f"(d[13]), "+f"(d[14]), "+f"(d[15]), "+f"(d[16]), "+f"(d[17]), "+f"(d[18]), "+f"(d[19]), "+f"(d[20]), "+f"(d[21]), "+f"(d[22]), "+f"(d[23]), "+f"(d[24]), "+f"(d[25]), "+f"(d[26]), "+f"(d[27]), "+f"(d[28]), "+f"(d[29]), "+f"(d[30]), "+f"(d[31]), "+f"(d[32]), "+f"(d[33]), "+f"(d[34]), "+f"(d[35]), "+f"(d[36]), "+f"(d[37]), "+f"(d[38]), "+f"(d[39]), "+f"(d[40]), "+f"(d[41]), "+f"(d[42]), "+f"(d[43]), "+f"(d[44]), "+f"(d[45]), "+f"(d[46]), "+f"(d[47]), "+f"(d[48]), "+f"(d[49]), "+f"(d[50]), "+f"(d[51]), "+f"(d[52]), "+f"(d[53]), "+f"(d[54]), "+f"(d[55]), "+f"(d[56]), "+f"(d[57]), "+f"(d[58]), "+f"(d[59]), "+f"(d[60]), "+f"(d[61]), "+f"(d[62]), "+f"(d[63])
    : "l"(da), "l"(db));
}
__device__ __forceinline__ void wgmma_n128_first(float (&d)[64], uint64_t da, uint64_t db) {
  asm volatile("wgmma.mma_async.sync.aligned.m64n128k16.f32.bf16.bf16 "
    "{%0, %1, %2, %3, %4, %5, %6, %7, %8, %9, %10, %11, %12, %13, %14, %15, %16, %17, %18, %19, %20, %21, %22, %23, %24, %25, %26, %27, %28, %29, %30, %31, %32, %33, %34, %35, %36, %37, %38, %39, %40, %41, %42, %43, %44, %45, %46, %47, %48, %49, %50, %51, %52, %53, %54, %55, %56, %57, %58, %59, %60, %61, %62, %63}, "
    "%64, %65, 0, 1, 1, 0, 1;\n"
    : "=f"(d[0]), "=f"(d[1]), "=f"(d[2]), "=f"(d[3]), "=f"(d[4]), "=f"(d[5]), "=f"(d[6]), "=f"(d[7]), "=f"(d[8]), "=f"(d[9]), "=f"(d[10]), "=f"(d[11]), "=f"(d[12]), "=f"(d[13]), "=f"(d[14]), "=f"(d[15]), "=f"(d[16]), "=f"(d[17]), "=f"(d[18]), "=f"(d[19]), "=f"(d[20]), "=f"(d[21]), "=f"(d[22]), "=f"(d[23]), "=f"(d[24]), "=f"(d[25]), "=f"(d[26]), "=f"(d[27]), "=f"(d[28]), "=f"(d[29]), "=f"(d[30]), "=f"(d[31]), "=f"(d[32]), "=f"(d[33]), "=f"(d[34]), "=f"(d[35]), "=f"(d[36]), "=f"(d[37]), "=f"(d[38]), "=f"(d[39]), "=f"(d[40]), "=f"(d[41]), "=f"(d[42]), "=f"(d[43]), "=f"(d[44]), "=f"(d[45]), "=f"(d[46]), "=f"(d[47]), "=f"(d[48]), "=f"(d[49]), "=f"(d[50]), "=f"(d[51]), "=f"(d[52]), "=f"(d[53]), "=f"(d[54]), "=f"(d[55]), "=f"(d[56]), "=f"(d[57]), "=f"(d[58]), "=f"(d[59]), "=f"(d[60]), "=f"(d[61]), "=f"(d[62]), "=f"(d[63])
    : "l"(da), "l"(db));
}
__device__ __forceinline__ void wgmma_n256(float (&d)[128], uint64_t da, uint64_t db) {
  asm volatile("wgmma.mma_async.sync.aligned.m64n256k16.f32.bf16.bf16 "
    "{%0, %1, %2, %3, %4, %5, %6, %7, %8, %9, %10, %11, %12, %13, %14, %15, %16, %17, %18, %19, %20, %21, %22, %23, %24, %25, %26, %27, %28, %29, %30, %31, %32, %33, %34, %35, %36, %37, %38, %39, %40, %41, %42, %43, %44, %45, %46, %47, %48, %49, %50, %51, %52, %53, %54, %55, %56, %57, %58, %59, %60, %61, %62, %63, %64, %65, %66, %67, %68, %69, %70, %71, %72, %73, %74, %75, %76, %77, %78, %79, %80, %81, %82, %83, %84, %85, %86, %87, %88, %89, %90, %91, %92, %93, %94, %95, %96, %97, %98, %99, %100, %101, %102, %103, %104, %105, %106, %107, %108, %109, %110, %111, %112, %113, %114, %115, %116, %117, %118, %119, %120, %121, %122, %123, %124, %125, %126, %127}, "
    "%128, %129, 1, 1, 1, 0, 1;\n"
    : "+f"(d[0]), "+f"(d[1]), "+f"(d[2]), "+f"(d[3]), "+f"(d[4]), "+f"(d[5]), "+f"(d[6]), "+f"(d[7]), "+f"(d[8]), "+f"(d[9]), "+f"(d[10]), "+f"(d[11]), "+f"(d[12]), "+f"(d[13]), "+f"(d[14]), "+f"(d[15]), "+f"(d[16]), "+f"(d[17]), "+f"(d[18]), "+f"(d[19]), "+f"(d[20]), "+f"(d[21]), "+f"(d[22]), "+f"(d[23]), "+f"(d[24]), "+f"(d[25]), "+f"(d[26]), "+f"(d[27]), "+f"(d[28]), "+f"(d[29]), "+f"(d[30]), "+f"(d[31]), "+f"(d[32]), "+f"(d[33]), "+f"(d[34]), "+f"(d[35]), "+f"(d[36]), "+f"(d[37]), "+f"(d[38]), "+f"(d[39]), "+f"(d[40]), "+f"(d[41]), "+f"(d[42]), "+f"(d[43]), "+f"(d[44]), "+f"(d[45]), "+f"(d[46]), "+f"(d[47]), "+f"(d[48]), "+f"(d[49]), "+f"(d[50]), "+f"(d[51]), "+f"(d[52]), "+f"(d[53]), "+f"(d[54]), "+f"(d[55]), "+f"(d[56]), "+f"(d[57]), "+f"(d[58]), "+f"(d[59]), "+f"(d[60]), "+f"(d[61]), "+f"(d[62]), "+f"(d[63]), "+f"(d[64]), "+f"(d[65]), "+f"(d[66]), "+f"(d[67]), "+f"(d[68]), "+f"(d[69]), "+f"(d[70]), "+f"(d[71]), "+f"(d[72]), "+f"(d[73]), "+f"(d[74]), "+f"(d[75]), "+f"(d[76]), "+f"(d[77]), "+f"(d[78]), "+f"(d[79]), "+f"(d[80]), "+f"(d[81]), "+f"(d[82]), "+f"(d[83]), "+f"(d[84]), "+f"(d[85]), "+f"(d[86]), "+f"(d[87]), "+f"(d[88]), "+f"(d[89]), "+f"(d[90]), "+f"(d[91]), "+f"(d[92]), "+f"(d[93]), "+f"(d[94]), "+f"(d[95]), "+f"(d[96]), "+f"(d[97]), "+f"(d[98]), "+f"(d[99]), "+f"(d[100]), "+f"(d[101]), "+f"(d[102]), "+f"(d[103]), "+f"(d[104]), "+f"(d[105]), "+f"(d[106]), "+f"(d[107]), "+f"(d[108]), "+f"(d[109]), "+f"(d[110]), "+f"(d[111]), "+f"(d[112]), "+f"(d[113]), "+f"(d[114]), "+f"(d[115]), "+f"(d[116]), "+f"(d[117]), "+f"(d[118]), "+f"(d[119]), "+f"(d[120]), "+f"(d[121]), "+f"(d[122]), "+f"(d[123]), "+f"(d[124]), "+f"(d[125]), "+f"(d[126]), "+f"(d[127])
    : "l"(da), "l"(db));
}
__device__ __forceinline__ void wgmma_n256_first(float (&d)[128], uint64_t da, uint64_t db) {
  asm volatile("wgmma.mma_async.sync.aligned.m64n256k16.f32.bf16.bf16 "
    "{%0, %1, %2, %3, %4, %5, %6, %7, %8, %9, %10, %11, %12, %13, %14, %15, %16, %17, %18, %19, %20, %21, %22, %23, %24, %25, %26, %27, %28, %29, %30, %31, %32, %33, %34, %35, %36, %37, %38, %39, %40, %41, %42, %43, %44, %45, %46, %47, %48, %49, %50, %51, %52, %53, %54, %55, %56, %57, %58, %59, %60, %61, %62, %63, %64, %65, %66, %67, %68, %69, %70, %71, %72, %73, %74, %75, %76, %77, %78, %79, %80, %81, %82, %83, %84, %85, %86, %87, %88, %89, %90, %91, %92, %93, %94, %95, %96, %97, %98, %99, %100, %101, %102, %103, %104, %105, %106, %107, %108, %109, %110, %111, %112, %113, %114, %115, %116, %117, %118, %119, %120, %121, %122, %123, %124, %125, %126, %127}, "
    "%128, %129, 0, 1, 1, 0, 1;\n"
    : "=f"(d[0]), "=f"(d[1]), "=f"(d[2]), "=f"(d[3]), "=f"(d[4]), "=f"(d[5]), "=f"(d[6]), "=f"(d[7]), "=f"(d[8]), "=f"(d[9]), "=f"(d[10]), "=f"(d[11]), "=f"(d[12]), "=f"(d[13]), "=f"(d[14]), "=f"(d[15]), "=f"(d[16]), "=f"(d[17]), "=f"(d[18]), "=f"(d[19]), "=f"(d[20]), "=f"(d[21]), "=f"(d[22]), "=f"(d[23]), "=f"(d[24]), "=f"(d[25]), "=f"(d[26]), "=f"(d[27]), "=f"(d[28]), "=f"(d[29]), "=f"(d[30]), "=f"(d[31]), "=f"(d[32]), "=f"(d[33]), "=f"(d[34]), "=f"(d[35]), "=f"(d[36]), "=f"(d[37]), "=f"(d[38]), "=f"(d[39]), "=f"(d[40]), "=f"(d[41]), "=f"(d[42]), "=f"(d[43]), "=f"(d[44]), "=f"(d[45]), "=f"(d[46]), "=f"(d[47]), "=f"(d[48]), "=f"(d[49]), "=f"(d[50]), "=f"(d[51]), "=f"(d[52]), "=f"(d[53]), "=f"(d[54]), "=f"(d[55]), "=f"(d[56]), "=f"(d[57]), "=f"(d[58]), "=f"(d[59]), "=f"(d[60]), "=f"(d[61]), "=f"(d[62]), "=f"(d[63]), "=f"(d[64]), "=f"(d[65]), "=f"(d[66]), "=f"(d[67]), "=f"(d[68]), "=f"(d[69]), "=f"(d[70]), "=f"(d[71]), "=f"(d[72]), "=f"(d[73]), "=f"(d[74]), "=f"(d[75]), "=f"(d[76]), "=f"(d[77]), "=f"(d[78]), "=f"(d[79]), "=f"(d[80]), "=f"(d[81]), "=f"(d[82]), "=f"(d[83]), "=f"(d[84]), "=f"(d[85]), "=f"(d[86]), "=f"(d[87]), "=f"(d[88]), "=f"(d[89]), "=f"(d[90]), "=f"(d[91]), "=f"(d[92]), "=f"(d[93]), "=f"(d[94]), "=f"(d[95]), "=f"(d[96]), "=f"(d[97]), "=f"(d[98]), "=f"(d[99]), "=f"(d[100]), "=f"(d[101]), "=f"(d[102]), "=f"(d[103]), "=f"(d[104]), "=f"(d[105]), "=f"(d[106]), "=f"(d[107]), "=f"(d[108]), "=f"(d[109]), "=f"(d[110]), "=f"(d[111]), "=f"(d[112]), "=f"(d[113]), "=f"(d[114]), "=f"(d[115]), "=f"(d[116]), "=f"(d[117]), "=f"(d[118]), "=f"(d[119]), "=f"(d[120]), "=f"(d[121]), "=f"(d[122]), "=f"(d[123]), "=f"(d[124]), "=f"(d[125]), "=f"(d[126]), "=f"(d[127])
    : "l"(da), "l"(db));
}

template <int N> struct WG;
#define DEF_WG(N) template <> struct WG<N> { \
  static __device__ __forceinline__ void mma(float (&d)[N / 2], uint64_t a, uint64_t b) { wgmma_n##N(d, a, b); } \
  static __device__ __forceinline__ void first(float (&d)[N / 2], uint64_t a, uint64_t b) { wgmma_n##N##_first(d, a, b); } };
DEF_WG(128) DEF_WG(256)

constexpr uint64_t DESC_A = (1ull << 62) | ((uint64_t)(1024 >> 4) << 32) | (1ull << 16);
constexpr uint64_t DESC_B = (1ull << 62) | ((uint64_t)(1024 >> 4) << 32) | ((uint64_t)(8192 >> 4) << 16);

struct Ring { int s; uint32_t ph; int wrap; };
template <int NS> __device__ __forceinline__ void ring_next(Ring& r) { r.s = (r.s + 1 == NS) ? 0 : r.s + 1; if (r.s == r.wrap) r.ph ^= 1; }

__device__ __forceinline__ int own_order(int it, int j) {
  return it < 2 ? 2 * j + it : it < 4 ? 2 * (j ^ 1) + it - 2 : ((j >> 1) * 4 + 2 * it - (it < 10 ? 4 : 15)) & 15;
}

template <int V> struct IC { static constexpr int v = V; };
template <int I, int E, class F> __device__ __forceinline__ void static_for(F&& f) { if constexpr (I < E) { f(IC<I>{}); static_for<I + 1, E>(f); } }

template <int N, int NS, int PRE, class Pre, class Mid, class Last>
__device__ __forceinline__ void mainloop(float (&acc)[N / 2], int nkb, bool own, Ring& r, uint32_t sb, int wg, int lane, uint32_t rel_base, int step0, Pre pre, Mid mid, Last last) {
  constexpr int SLOT = RING / NS;
  const uint32_t full = sb + MISC + (NS == 4 ? B_FULL4 : B_FULL6);
  const uint32_t rel = rel_base + (NS == 4 ? B_EMPTY4 : B_EMPTY6);
  const uint32_t s0 = (sb & 0x3FFFF) >> 4, a0 = s0 + wg * (HALF >> 4);
  int ps;
  auto issue = [&](int it, bool first) {
    const uint64_t da = DESC_A | (a0 + ((own && it < 2) ? (STG + it * BLK) >> 4 : r.s * (SLOT >> 4))), db = DESC_B | (s0 + r.s * (SLOT >> 4) + (BLK >> 4));
    mbar_wait(full + r.s * 8, r.ph);
    TRS(step0 + it);
    wg_arrive();
    if (first) WG<N>::first(acc, da, db); else WG<N>::mma(acc, da, db);
#pragma unroll
    for (int k = 1; k < 4; k++) WG<N>::mma(acc, da + k * 2, db + k * 128);
    wg_commit();
  };
  auto retire = [&](int it) {
    wg_wait<1>();
    if (lane < 2) mbar_arrive_cl(rel + ps * 8);
    if (own && it == 2 && lane == 0) mbar_arrive(sb + MISC + B_OWN);
    ps = r.s;
    ring_next<NS>(r);
  };
  issue(0, true);
  ps = r.s;
  ring_next<NS>(r);
  static_for<1, PRE + 1>([&](auto ic) { issue(ic.v, false); pre(ic); retire(ic.v); });
#pragma unroll 1
  for (int it = PRE + 1; it < nkb; it++) {
    if (TAILLAG && it == 56 - TAILLAG && wg == 1) mbar_wait(sb + MISC + B_LAG, 0);
    issue(it, false); mid(it); retire(it);
  }
  last();
  wg_wait<0>();
  if (lane < 2) mbar_arrive_cl(rel + ps * 8);
}

__device__ __forceinline__ void ln_publish(const float (&v)[64], uint4* st, int j, int row0, int lane, uint32_t ep) {
  float s0 = 0, s1 = 0, s2 = 0, s3 = 0, q0 = 0, q1 = 0, q2 = 0, q3 = 0;
#pragma unroll
  for (int i = 0; i < 16; i++) {
    s0 += v[4 * i]; s1 += v[4 * i + 1]; s2 += v[4 * i + 2]; s3 += v[4 * i + 3];
    q0 = fmaf(v[4 * i], v[4 * i], q0); q1 = fmaf(v[4 * i + 1], v[4 * i + 1], q1); q2 = fmaf(v[4 * i + 2], v[4 * i + 2], q2); q3 = fmaf(v[4 * i + 3], v[4 * i + 3], q3);
  }
  s0 += s1; s2 += s3; q0 += q1; q2 += q3;
  const bool odd = lane & 1;
  float s = (odd ? s2 : s0) + __shfl_xor_sync(~0u, odd ? s0 : s2, 1), q = (odd ? q2 : q0) + __shfl_xor_sync(~0u, odd ? q0 : q2, 1);
  s += __shfl_xor_sync(~0u, s, 2); q += __shfl_xor_sync(~0u, q, 2);
  if ((lane & 3) < 2) st_rlx4(st + j * 128 + row0 + (lane & 1) * 8, __float_as_uint(s), ep, __float_as_uint(q), ep);
}
__device__ __forceinline__ void ln_gather(const uint4* st, int row0, int lane, uint32_t ep, float& n0, float& r0, float& n1, float& r1) {
  const uint4* p = st + (lane & 2) * 256 + row0 + (lane & 1) * 8;
  uint4 a, b, c, d; uint32_t n = 0;
  while (true) {
    a = ld_rlx4(p); b = ld_rlx4(p + 128); c = ld_rlx4(p + 256); d = ld_rlx4(p + 384);
    if (a.y == ep && a.w == ep && b.y == ep && b.w == ep && c.y == ep && c.w == ep && d.y == ep && d.w == ep) break;
    SPIN_GUARD(n);
  }
  __syncwarp();
  float s = (__uint_as_float(a.x) + __uint_as_float(b.x)) + (__uint_as_float(c.x) + __uint_as_float(d.x));
  float q = (__uint_as_float(a.z) + __uint_as_float(b.z)) + (__uint_as_float(c.z) + __uint_as_float(d.z));
  s += __shfl_xor_sync(~0u, s, 2); q += __shfl_xor_sync(~0u, q, 2);
  s *= 1.f / 1024;
  const float r = rsqrtf(fmaxf(fmaf(-s, s, q * (1.f / 1024)), 0.f) + 1e-5f), nn = -s * r;
  const float ro = __shfl_xor_sync(~0u, r, 1), no = __shfl_xor_sync(~0u, nn, 1);
  const bool odd = lane & 1;
  r0 = odd ? ro : r; n0 = odd ? no : nn; r1 = odd ? r : ro; n1 = odd ? nn : no;
}
__device__ __forceinline__ void load_vec(uint32_t* w, uint32_t sb, int sec, int b, int lane) {
#pragma unroll
  for (int q = 0; q < 2; q++) { uint4 t = lds128(sb + MISC + MODV + sec * 256 + (lane & 3) * 64 + b * 32 + q * 16); w[4 * q] = t.x; w[4 * q + 1] = t.y; w[4 * q + 2] = t.z; w[4 * q + 3] = t.w; }
}
__device__ __forceinline__ void stage_done(uint32_t sb, int wg, int b, int lane) {
  fence_async_smem();
  __syncwarp();
  if (lane == 0) mbar_arrive(sb + MISC + B_RDY + b * 8);
}
__device__ __forceinline__ uint32_t hfma2(uint32_t a, uint32_t b, uint32_t c) { uint32_t r; asm("fma.rn.bf16x2 %0, %1, %2, %3;" : "=r"(r) : "r"(a), "r"(b), "r"(c)); return r; }
__device__ __forceinline__ void ln_apply(const float (&v)[64], const uint4* st, int row0, uint32_t ep, uint32_t sb, int sec_shift, int sec_scale, uint32_t stg_row, int wg, int lane) {
  uint32_t sc[16], sh[16];
#pragma unroll
  for (int b = 0; b < 2; b++) { load_vec(sc + 8 * b, sb, sec_scale, b, lane); load_vec(sh + 8 * b, sb, sec_shift, b, lane); }
  float n0, r0, n1, r1;
  ln_gather(st, row0, lane, ep, n0, r0, n1, r1);
#pragma unroll
  for (int i = 0; i < 16; i += 2) {
    if (i == 8) { const float z = lds32f(sb + MISC + ZERO); n0 += z; n1 += z; }
    uint32_t w[4];
#pragma unroll
    for (int u = 0; u < 2; u++) {
      int q = i + u;
      w[2 * u] = hfma2(pack2(fmaf(v[4 * q], r0, n0), fmaf(v[4 * q + 1], r0, n0)), sc[q], sh[q]);
      w[2 * u + 1] = hfma2(pack2(fmaf(v[4 * q + 2], r1, n1), fmaf(v[4 * q + 3], r1, n1)), sc[q], sh[q]);
    }
    stsm4(stg_row + (i >> 3) * BLK + ((((i & 7) + (lane >> 4)) ^ (lane & 7)) << 4), w[0], w[1], w[2], w[3]);
    if ((i & 7) == 6) stage_done(sb, wg, i >> 3, lane);
  }
}
__device__ __forceinline__ uint32_t hmul2(uint32_t a, uint32_t b) { uint32_t r; asm("mul.rn.bf16x2 %0, %1, %2;" : "=r"(r) : "r"(a), "r"(b)); return r; }
__device__ __forceinline__ uint32_t silu_mul2(uint32_t g, uint32_t u) {
  const uint32_t h = hmul2(g, 0x3f003f00u);
  const float h0 = bf_lo(h), h1 = bf_hi(h);
  return hmul2(pack2(fmaf(h0, tanh_fast(h0), h0), fmaf(h1, tanh_fast(h1), h1)), u);
}

__device__ __forceinline__ void gemv_fma(float (&a)[8], uint4 w, float s) {
  a[0] = fmaf(bf_lo(w.x), s, a[0]); a[1] = fmaf(bf_hi(w.x), s, a[1]); a[2] = fmaf(bf_lo(w.y), s, a[2]); a[3] = fmaf(bf_hi(w.y), s, a[3]);
  a[4] = fmaf(bf_lo(w.z), s, a[4]); a[5] = fmaf(bf_hi(w.z), s, a[5]); a[6] = fmaf(bf_lo(w.w), s, a[6]); a[7] = fmaf(bf_hi(w.w), s, a[7]);
}
__device__ __forceinline__ float silu_c(float v) { return bf_round(__fdividef(v, 1.f + __expf(-v))); }
__device__ __forceinline__ float mod_gather(const uint2* p, uint32_t ep) {
  uint2 a, b, c, d; uint32_t n = 0;
  while (true) {
    a = ld_rlx2(p); b = ld_rlx2(p + 128); c = ld_rlx2(p + 256); d = ld_rlx2(p + 384);
    if (a.y == ep && b.y == ep && c.y == ep && d.y == ep) break;
    SPIN_GUARD(n);
  }
  return (__uint_as_float(a.x) + __uint_as_float(b.x)) + (__uint_as_float(c.x) + __uint_as_float(d.x));
}
__device__ __forceinline__ void mod_store(uint32_t sb, int sec, int col, float v) {
  v = bf_round(v);
  if (sec == 1 || sec == 4) v += 1.f;
  sts16(sb + MISC + MODV + sec * 256 + (((col >> 1) & 3) * 16 + (col >> 3)) * 4 + (col & 1) * 2, __float2bfloat16_rn(v));
}

__global__ void __cluster_dims__(2, 1, 1) __launch_bounds__(384, 1)
fused_kernel(const __grid_constant__ Maps maps, const bf16* __restrict__ cvec, const bf16* __restrict__ wmod, int by_sm) {
  extern __shared__ __align__(1024) uint8_t smem_raw[];
  const uint32_t sb = smem_u32(smem_raw);
  const int warp = __shfl_sync(~0u, threadIdx.x >> 5, 0), lane = threadIdx.x & 31;
  const int rank = blockIdx.x & 1;
  int cid = (blockIdx.x >> 1) - 2;
  if (by_sm) {
    uint32_t sm; asm("mov.u32 %0, %%smid;" : "=r"(sm));
    const int t = sm >> 1, u = t - 32, gp = t < 32 ? t & 7 : t < 60 ? 1 + u % 7 : 0, idx = t < 32 ? t >> 3 : t < 60 ? 4 + u / 7 : t - 58;
    cid = (t & ~1) == 60 ? t - 62 : ((gp & 1) * 8 + idx) * 4 + (gp >> 1);
  }
  const bool extra = cid < 0;
  const int bid = cid * 2 + rank;
  const int m = cid >> 2, j = (cid & 3) * 2 + rank;
  const uint32_t bar = sb + MISC;

  if (warp >= 8) {
    asm volatile("setmaxnreg.dec.sync.aligned.u32 40;");
    if (extra) {
      if (warp == 8) {
        if (lane == 0) { for (int s = 0; s < 6; s++) { mbar_init(bar + B_FULL6 + s * 8, 1); mbar_init(bar + B_EMPTY6 + s * 8, 8); } fence_async_smem(); }
        __syncwarp();
        asm volatile("bar.arrive 2, 288;" ::: "memory");
        __nanosleep(XSLEEP);
#pragma unroll 1
        for (int it = 0, s = 0, par = 1; it < 64; it++) {
          mbar_wait(bar + B_EMPTY6 + s * 8, par);
          if (elect()) { mbar_expect_tx(bar + B_FULL6 + s * 8, 32768); tma_3d(sb + s * 32768, &maps.wmod, bar + B_FULL6 + s * 8, 0, (it & 15) * 64, 12 + (it >> 4) * 4 + bid); }
          if (++s == 6) { s = 0; par ^= 1; }
        }
      }
    } else if (warp < 10) {
      uint32_t s6 = 0, p6 = 1;
      auto next6 = [&]() { if (++s6 == 6) { s6 = 0; p6 ^= 1; } };
      auto drained4 = [&](int q, int late) { if (q < 5) mbar_wait(bar + B_EMPTY4 + (((late ? 0x10332 : 0x32110) >> (4 * q)) & 3) * 8, 1); };
      auto drained6 = [&](int q) { if (q < 3) mbar_wait(bar + B_EMPTY6 + ((0x154 >> (4 * q)) & 7) * 8, q >> 1); };
      auto skip6 = [&]() { mbar_wait(bar + B_EMPTY6 + s6 * 8, p6); if (elect()) mbar_arrive(bar + B_FULL6 + s6 * 8); next6(); };
      if (warp == 8) {
        const uint32_t t_start = clock();
        if (lane == 0) {
          if (sb & 1023) bail();
          for (int b = 0; b < 2; b++) mbar_init(bar + B_X + b * 8, 1);
          for (int s = 0; s < 4; s++) { mbar_init(bar + B_FULL4 + s * 8, 2); mbar_init(bar + B_EMPTY4 + s * 8, 16); }
          for (int s = 0; s < 6; s++) { mbar_init(bar + B_FULL6 + s * 8, 2); mbar_init(bar + B_EMPTY6 + s * 8, 16); }
          for (int b = 0; b < 2; b++) { mbar_init(bar + B_RDY + b * 8, 8); mbar_init(bar + B_FREE + b * 8, 1); mbar_init(bar + B_HH + b * 8, 1); }
          mbar_init(bar + B_MOD, 1); mbar_init(bar + B_LAG, 4); mbar_init(bar + B_HALO, 2); mbar_init(bar + B_ALL, 1); mbar_init(bar + B_HH2, 1); mbar_init(bar + B_OWN, 8);
          asm volatile("st.shared.u32 [%0], 0;" :: "r"(bar + ZERO) : "memory");
          asm volatile("fence.mbarrier_init.release.cluster;" ::: "memory");
          fence_async_smem();
        }
        __syncwarp();
        cl_arrive_relaxed();
        while ((uint32_t)clock() - t_start < XDELAY) {}
        if (elect()) for (int b = 0; b < 2; b++) { mbar_expect_tx(bar + B_X + b * 8, BLK); tma_3d(sb + STG + b * BLK, &maps.x, bar + B_X + b * 8, j * 128 + b * 64, m * 64, 0); }
        auto wide = [&](int s, int par, const CUtensorMap* m0, int a0, const CUtensorMap* m1, int a1, int kb) {
          const uint32_t full = bar + B_FULL4 + s * 8, d = sb + s * 49152 + BLK;
          mbar_wait(full + 32, par);
          if (elect()) { mbar_expect_tx(full, 2 * BLK); tma_3d(d, m0, full, 0, kb * 64, a0); tma_3d(d + BLK, m1, full, 0, kb * 64, a1); }
        };
        auto narrow = [&](const CUtensorMap* m0, int kb) {
          const uint32_t full = bar + B_FULL6 + s6 * 8;
          mbar_wait(full + 48, p6);
          if (elect()) { mbar_expect_tx(full, BLK); tma_3d(sb + s6 * 32768 + BLK, m0, full, 0, kb * 64, 2 * j); }
          next6();
        };
#pragma unroll 1
        for (int it = 0; it < 16; it++) {
          if (it == BGATE) mbar_wait(bar + B_X + 8, 0);
          wide(it & 3, ~(it >> 2) & 1, &maps.wqkv, 16 + 2 * j, &maps.wqkv, 32 + 2 * j, own_order(it, j));
        }
#pragma unroll 1
        for (int it = 0; it < 16; it++) { drained4(it, 0); narrow(&maps.wqkv, it); }
#pragma unroll 1
        for (int it = 0; it < 16; it++) {
          narrow(&maps.wo, own_order(it, j));
          if (it == 10) {
            mbar_wait(bar + B_OWN, 1); mbar_wait(bar + B_FREE + 8, 1);
            if (elect()) for (int b = 0; b < 2; b++) { mbar_expect_tx(bar + B_X + b * 8, BLK); tma_3d(sb + STG + b * BLK, &maps.x, bar + B_X + b * 8, j * 128 + b * 64, m * 64, 0); }
          }
        }
        skip6();
#pragma unroll 1
        for (int it = 0; it < 48; it++) {
          const int s = (it + 2) & 3, par = ~(it >> 2) & 1;
          drained6(it);
          wide(s, par, &maps.w1, (it & 48) + 2 * j, &maps.w3, (it & 48) + 2 * j, it < 16 ? own_order(it, j) : it & 15);
          if (it >= 44) {
            if (it == 44) { mbar_wait(bar + B_FREE, 0); mbar_wait(bar + B_FREE + 8, 0); if (elect()) mbar_expect_tx(bar + B_X, 2 * BLK); }
            if (elect()) bulk_ld(sb + STG + (it - 44) * HALF, g_x1 + bid * 2048 + (it - 44) * 512, HALF, bar + B_X);
          }
        }
#pragma unroll 1
        for (int it = 0; it < 16; it++) {
          const uint32_t full = bar + B_FULL6 + s6 * 8, d = sb + s6 * 32768 + BLK;
          drained4(it, 1);
          mbar_wait(full + 48, p6);
          if (elect()) { mbar_expect_tx(full, BLK); tma_3d(d, &maps.w1s, full, 0, it * 64, 48 + j); tma_3d(d + HALF, &maps.w3s, full, 0, it * 64, 48 + j); }
          next6();
        }
#pragma unroll 1
        for (int it = 0; it < 56; it++) narrow(&maps.w2, it);
      } else {
        if (lane < 9) prefetch_map(&maps.x + lane);
        const uint32_t ep = g_epoch[bid + 4] + 1;
        cl_arrive_relaxed(); cl_wait();
        auto plain = [&](uint32_t full, uint32_t empty, int par, uint32_t slot, const uint4* blk) {
          mbar_wait(empty, par);
          if (elect()) { mbar_expect_tx(full, BLK); bulk_ld_mc(slot + rank * HALF, blk + rank * 512, HALF, full); }
        };
        auto plain6 = [&](const uint4* blk) { plain(bar + B_FULL6 + s6 * 8, bar + B_EMPTY6 + s6 * 8, p6, sb + s6 * 32768, blk); next6(); };
        uint32_t ready = 0;
        auto poll = [&](int e) { ready = __ballot_sync(~0u, ld_acquire(g_flag + m * 128 + e * 16 + (lane & 15)) == ep); };
        auto need = [&](int e, uint32_t mask) {
          if ((ready & mask) != mask) {
            uint32_t n = 0;
            do { poll(e); SPIN_GUARD(n); } while ((ready & mask) != mask);
            fence_async_global();
          }
        };
        auto fresh = [&](int e, int it, uint32_t full, uint32_t empty, int par, uint32_t slot, uint4* src) {
          if (it >= 4) {
            const int kb = own_order(it, j);
            if (it < 10) need(e, 1u << kb); else if (it == 10) mbar_wait(bar + B_ALL, e & 1);
            plain(full, empty, par, slot, src + kb * 1024);
          } else {
            if (it == 0) { poll(e); ready = 0; }
            mbar_wait(empty, par);
            if (it < 2) { if (elect()) mbar_arrive(full); }
            else {
              const int b = it & 1;
              const uint32_t to_peer = mapa(sb, rank ^ 1) - sb;
              if (elect()) mbar_expect_tx(full, BLK);
              mbar_wait(bar + (b ? B_FREE + 8 : B_RDY), e & 1);
              if (b == 0) TR(e == 0 ? 24 : e == 2 ? 30 : 44);
              if (elect()) {
                if (b == 0) {
                  bulk_st(src + 2 * j * 1024, sb + STG, BLK);
                  bulk_commit();
                  bulk_wait_all();
                  mbar_arrive(bar + B_FREE);
                }
                fence_async_global();
                bulk_ld(slot + to_peer, src + (2 * j + b) * 1024, BLK, full + to_peer);
              }
              __syncwarp();
            }
          }
          if (it == 4) TR(e == 0 ? 28 : e == 1 ? 46 : 34);
        };
#pragma unroll 1
        for (int ph = 0; ph < 2; ph++) {
          uint4* h = g_h + m * 16384;
#pragma unroll 1
          for (int it = 0; it < 16; it++) {
            const int s = (it + 2 * ph) & 3;
            if (ph) drained6(it);
            fresh(2 * ph, it, bar + B_FULL4 + s * 8, bar + B_EMPTY4 + s * 8, ~(it >> 2) & 1, sb + s * 49152, h);
          }
          if (ph) {
#pragma unroll 1
            for (int it = 16; it < 48; it++) {
              const int s = (it + 2) & 3;
              const uint32_t full = bar + B_FULL4 + s * 8;
              plain(full, full + 32, ~(it >> 2) & 1, sb + s * 49152, h + (it & 15) * 1024);
            }
          }
#pragma unroll 1
          for (int it = 0; it < 16; it++) { drained4(it, ph); plain6(h + it * 1024); }
          if (!ph) {
#pragma unroll 1
            for (int it = 0; it < 16; it++) { fresh(1, it, bar + B_FULL6 + s6 * 8, bar + B_EMPTY6 + s6 * 8, p6, sb + s6 * 32768, g_o + m * 16384); next6(); }
            skip6();
          }
        }
#pragma unroll 1
        for (int it = 0; it < 56; it++) {
          if (it == 0 || it == 32 || it == 48) mbar_wait(bar + (it == 48 ? B_HH2 : B_HH + (it >> 2)), 0);
          plain6(g_hh + m * 57344 + it * 1024);
        }
      }
    } else {
      const int b = warp - 10;
      const uint32_t ep = g_epoch[bid + 4] + 1;
      const uint32_t stg = sb + STG + b * BLK;
      cl_arrive_relaxed(); cl_wait();
      auto all_there = [&](int u, uint32_t done) {
        const uint32_t* fl = g_flag + u;
        uint32_t n = 0;
        while (!__all_sync(~0u, ld_acquire(fl) == ep)) { __nanosleep(100); SPIN_GUARD(n); }
        fence_async_global();
        if (lane == 0) mbar_arrive(done);
      };
      auto fetch_mod = [&](int sec) {
        const uint4* p = (const uint4*)(g_modv + (sec - 2) * 1024 + j * 128) + lane;
        uint4 v0, v1; uint32_t n = 0;
        while (true) {
          v0 = ld_rlx4(p); v1 = ld_rlx4(p + 32);
          if (v0.y == ep && v0.w == ep && v1.y == ep && v1.w == ep) break;
          SPIN_GUARD(n);
        }
        mod_store(sb, sec, 2 * lane, __uint_as_float(v0.x)); mod_store(sb, sec, 2 * lane + 1, __uint_as_float(v0.z));
        mod_store(sb, sec, 64 + 2 * lane, __uint_as_float(v1.x)); mod_store(sb, sec, 65 + 2 * lane, __uint_as_float(v1.z));
        __syncwarp();
      };
#pragma unroll 1
      for (int e = 0; e < 7 - b; e++) {
        if (lane == 0) {
          if (e < 3) {
            mbar_wait(bar + B_FREE, e & 1);
            if (b) {
              mbar_wait(bar + B_RDY + 8, e & 1);
              bulk_st((e == 1 ? g_o : g_h) + m * 16384 + (2 * j + 1) * 1024, stg, BLK);
              bulk_commit();
              bulk_wait_all();
              mbar_arrive(bar + B_FREE + 8);
              TR(53 + e);
            }
            st_release(g_flag + m * 128 + e * 16 + 2 * j + b, ep);
            TR((e == 0 ? 26 : e == 2 ? 32 : 42) + b);
          } else {
            const int kb = (e < 6 ? 2 * (8 * (e - 3) + j) : 48 + j) + b;
            mbar_wait(bar + B_RDY + b * 8, e & 1);
#pragma unroll 1
            for (int q = 0; q < NPIECE; q++) { if (q) __nanosleep(PSLEEP); bulk_st(g_hh + m * 57344 + kb * 1024 + q * (1024 / NPIECE), stg + q * (BLK / NPIECE), BLK / NPIECE); }
            bulk_commit();
            bulk_wait_all();
            mbar_arrive(bar + B_FREE + b * 8);
            st_release(g_flag + m * 128 + U_HH + kb, ep);
          }
        }
        __syncwarp();
        if (e < 3 && b) all_there(m * 128 + e * 16 + (lane & 15), bar + B_ALL);
        if (e == 4 && b) all_there(m * 128 + U_HH + lane, bar + B_HH);
        if (!b && (e == 1 || e == 2)) {
#pragma unroll 1
          for (int sec = e == 1 ? 2 : 5; sec < 4 + e; sec++) fetch_mod(sec);
          if (e == 1) { if (lane == 0) mbar_arrive(bar + B_MOD); TR(50); }
        }
        if (e == 0) {
          mbar_wait(bar + B_EMPTY6 + 24, 0);
#pragma unroll 1
          for (int w = 0; w < 4; w++) {
            const uint4* hp = g_halo + ((m * 8 + j) * 2 + (w & 1)) * 512 + b * 256 + (w >> 1) * 128 + lane;
            uint4 q[4] = {}; uint32_t n = 0;
            while (m > 0) {
              bool ok = true;
#pragma unroll
              for (int i = 0; i < 4; i++) q[i] = ld_rlx4(hp + i * 32);
#pragma unroll
              for (int i = 0; i < 4; i++) ok = ok && q[i].y == ep && q[i].w == ep;
              if (ok) break;
              SPIN_GUARD(n);
            }
#pragma unroll
            for (int i = 0; i < 2; i++) sts128(stg + lane * 16 + (w & 1) * HALF + (w >> 1) * 1024 + i * 512, q[2 * i].x, q[2 * i + 1].x, q[2 * i].z, q[2 * i + 1].z);
          }
          __syncwarp();
          if (lane == 0) mbar_arrive(bar + B_HALO);
          if (b == 0) TR(52);
        }
      }
      if (b) { all_there(m * 128 + U_HH + 32 + (lane & 15), bar + B_HH + 8); all_there(m * 128 + U_HH + 48 + (lane & 7), bar + B_HH2); }
    }
  } else {
    asm volatile("setmaxnreg.inc.sync.aligned.u32 232;");
    const int wg = warp >> 2, wq = warp & 3, tid = threadIdx.x;
    const int g = lane >> 2, c = lane & 3;
    if (extra) {
      const uint32_t ep = g_epoch[bid + 4] + 1;
      float sv[4];
#pragma unroll
      for (int p = 0; p < 4; p++) sv[p] = silu_c(__bfloat162float(cvec[64 * (4 * p + (lane >> 3)) + 8 * warp + (lane & 7)]));
      named_bar(2, 288);
      int s = 0, par = 0;
#pragma unroll 1
      for (int sec = 0; sec < 4; sec++) {
        float a[8] = {0, 0, 0, 0, 0, 0, 0, 0};
#pragma unroll 1
        for (int it = 0; it < 16; it++) {
          const float sc = it < 4 ? sv[0] : it < 8 ? sv[1] : it < 12 ? sv[2] : sv[3];
          mbar_wait(bar + B_FULL6 + s * 8, par);
          uint4 w[8];
#pragma unroll
          for (int i = 0; i < 8; i++) w[i] = lds128(sb + s * 32768 + (warp * 8 + i) * 512 + lane * 16);
#pragma unroll
          for (int i = 0; i < 8; i++) gemv_fma(a, w[i], __shfl_sync(~0u, sc, (it & 3) * 8 + i));
          if (lane == 0) mbar_arrive(bar + B_EMPTY6 + s * 8);
          if (++s == 6) { s = 0; par ^= 1; }
        }
        const uint32_t red = sb + STG + sec * 8192;
        sts128(red + warp * 1024 + lane * 32, __float_as_uint(a[0]), __float_as_uint(a[1]), __float_as_uint(a[2]), __float_as_uint(a[3]));
        sts128(red + warp * 1024 + lane * 32 + 16, __float_as_uint(a[4]), __float_as_uint(a[5]), __float_as_uint(a[6]), __float_as_uint(a[7]));
        named_bar(1, 256);
        float t = 0;
#pragma unroll
        for (int q = 0; q < 8; q++) t += lds32f(red + q * 1024 + tid * 4);
        st_rlx2(g_modv + sec * 1024 + (bid + 4) * 256 + tid, __float_as_uint(t), ep);
      }
      if (tid == 0) g_epoch[bid + 4] = ep;
      return;
    }
    if (warp == 0) TR(0);
    const int sec0 = (m >> 1) & 1, hf0 = m & 1, ks0 = m >> 2;
    const int row0 = wg * 64 + wq * 16 + g;
    if (c < 2) st_rlx4(g_stat + m * 1024 + j * 128 + row0 + c * 8, 0, 0, 0, 0);
    if (tid < 64) st_rlx2(g_modp + ((j * 2 + sec0) * 4 + ks0) * 128 + hf0 * 64 + tid, 0, 0);
    uint4 wv[8];
    {
      const bf16* wp = wmod + (size_t)(ks0 * 256 + warp * 32 + (lane >> 3)) * 6144 + sec0 * 1024 + j * 128 + hf0 * 64 + (lane & 7) * 8;
#pragma unroll
      for (int i = 0; i < 8; i++) wv[i] = ldg_nc(wp + (size_t)i * 4 * 6144);
    }
    const float sc_ = silu_c(__bfloat162float(cvec[ks0 * 256 + warp * 32 + lane]));
    const uint32_t ep = g_epoch[bid + 4] + 1;
    cl_arrive_relaxed(); cl_wait();
    const uint32_t rel = mapa(bar, (lane & 1) ^ rank);
    const uint32_t stg_row = sb + STG + (wg * 64 + wq * 16 + (lane & 15)) * 128;
    const uint32_t fre = bar + B_FREE;
    Ring r4{0, 0, 0}, r6{0, 0, 0};
    auto none = [](auto) {};
    {
      float a[8] = {0, 0, 0, 0, 0, 0, 0, 0};
#pragma unroll
      for (int i = 0; i < 8; i++) gemv_fma(a, wv[i], __shfl_sync(~0u, sc_, i * 4 + (lane >> 3)));
#pragma unroll
      for (int i = 0; i < 8; i++) { a[i] += __shfl_xor_sync(~0u, a[i], 8); a[i] += __shfl_xor_sync(~0u, a[i], 16); }
      if (lane < 8) {
        sts128(sb + RED_OFF + warp * 256 + lane * 32, __float_as_uint(a[0]), __float_as_uint(a[1]), __float_as_uint(a[2]), __float_as_uint(a[3]));
        sts128(sb + RED_OFF + warp * 256 + lane * 32 + 16, __float_as_uint(a[4]), __float_as_uint(a[5]), __float_as_uint(a[6]), __float_as_uint(a[7]));
      }
      named_bar(1, 256);
      if (tid < 64) {
        float s = 0;
#pragma unroll
        for (int w = 0; w < 8; w++) s += lds32f(sb + RED_OFF + w * 256 + tid * 4);
        st_rlx2(g_modp + ((j * 2 + sec0) * 4 + ks0) * 128 + hf0 * 64 + tid, __float_as_uint(s), ep);
      }
      if (warp == 0) TR(1);
      float v[64];
      mbar_wait(bar + B_X, 0); mbar_wait(bar + B_X + 8, 0);
#pragma unroll
      for (int i = 0; i < 16; i += 2) {
        uint32_t w0, w1, w2, w3;
        ldsm4(stg_row + (i >> 3) * BLK + ((((i & 7) + (lane >> 4)) ^ (lane & 7)) << 4), w0, w1, w2, w3);
        v[4 * i] = bf_lo(w0); v[4 * i + 1] = bf_hi(w0); v[4 * i + 2] = bf_lo(w1); v[4 * i + 3] = bf_hi(w1);
        v[4 * i + 4] = bf_lo(w2); v[4 * i + 5] = bf_hi(w2); v[4 * i + 6] = bf_lo(w3); v[4 * i + 7] = bf_hi(w3);
      }
      ln_publish(v, g_stat + m * 1024, j, row0, lane, ep);
      if (warp == 0) TR(2);
      mod_store(sb, tid >> 7, tid & 127, mod_gather(g_modp + (j * 2 + (tid >> 7)) * 512 + (tid & 127), ep));
      named_bar(1, 256);
      if (warp == 0) TR(3);
      ln_apply(v, g_stat + m * 1024, row0, ep, sb, 0, 1, stg_row, wg, lane);
      named_bar(2 + wg, 128);
    }
    if (warp == 0) TR(4);
    {
      uint32_t kf[32], vf[32], pv[32];
      const bool first = wq == 0 && m == 0;
      const uint32_t xa = sb + STG + wg * HALF + wq * 2048 + lane * 16;
      {
        float acc[128];
        mainloop<256, 4, 0>(acc, 16, true, r4, sb, wg, lane, rel, bid * 192 + 0, none, none, [] {});
        if (warp == 0) TR(5);
#pragma unroll
        for (int i = 0; i < 32; i++) { kf[i] = pack2(acc[2 * i], acc[2 * i + 1]); vf[i] = pack2(acc[64 + 2 * i], acc[65 + 2 * i]); }
      }
      if (warp == 0) TR(6);
      float acc[64];
      mainloop<128, 6, 4>(acc, 16, false, r6, sb, wg, lane, rel, bid * 192 + 16, [&](auto ic) {
        constexpr int q = ic.v - 1;
#pragma unroll
        for (int i = 8 * q; i < 8 * q + 8; i++) vf[i] = movm(vf[i]);
        if ((q & 1) == 0) mbar_wait(fre + 4 * q, 0);
        if (wq == 3) {
          if (m < 15) {
            uint4* hp = g_halo + (((m + 1) * 8 + j) * 2 + wg) * 512 + lane;
#pragma unroll
            for (int i = 4 * q; i < 4 * q + 4; i++) st_rlx4(hp + i * 32, kf[2 * i + 1], ep, vf[2 * i + 1], ep);
          }
        } else {
#pragma unroll
          for (int i = 2 * q; i < 2 * q + 2; i++) sts128(xa + 2048 + (i >> 2) * BLK + (i & 3) * 512, kf[4 * i + 1], kf[4 * i + 3], vf[4 * i + 1], vf[4 * i + 3]);
        }
        if (q == 3 && c < 2) st_rlx4(g_stat + (16 + m) * 1024 + j * 128 + row0 + c * 8, 0, 0, 0, 0);
      }, none, [&] {
        named_bar(2 + wg, 128);
        if (wq == 0) mbar_wait(bar + B_HALO, 0);
#pragma unroll
        for (int i = 0; i < 8; i++) {
          uint4 q = lds128(xa + (i >> 2) * BLK + (i & 3) * 512);
          pv[4 * i] = q.x; pv[4 * i + 1] = q.y; pv[4 * i + 2] = q.z; pv[4 * i + 3] = q.w;
        }
        __syncwarp();
      });
      if (warp == 0) TR(7);
      int gz = g;
#pragma unroll
      for (int b = 0; b < 2; b++) {
        const bool up0 = 2 * c > gz, up1 = 2 * c + 1 > gz;
        const uint32_t mup = (up0 ? 0xffffu : 0u) | (up1 ? 0xffff0000u : 0u);
        float l[2][4], mx[4];
#pragma unroll
        for (int h = 0; h < 2; h++) {
          uint32_t q[8];
          const int k = 16 * b + 8 * h;
#pragma unroll
          for (int i = 0; i < 8; i++) q[i] = pack2(acc[2 * k + 2 * i], acc[2 * k + 2 * i + 1]);
          float s0[4], s1[4], s2[4];
          mma16z(s0, q[0], q[1], q[2], q[3], pv[k], pv[k + 1]); mma16z(s1, q[0], q[1], q[2], q[3], kf[k], kf[k + 2]); mma16z(s2, q[0], q[1], q[2], q[3], kf[k + 1], kf[k + 3]);
          mma16(s0, q[4], q[5], q[6], q[7], pv[k + 4], pv[k + 5]); mma16(s1, q[4], q[5], q[6], q[7], kf[k + 4], kf[k + 6]); mma16(s2, q[4], q[5], q[6], q[7], kf[k + 5], kf[k + 7]);
          if (first) { s0[0] = -INFINITY; s0[1] = -INFINITY; }
          l[h][0] = up0 ? s0[0] : s1[0]; l[h][1] = up1 ? s0[1] : s1[1]; l[h][2] = up0 ? s1[2] : s2[2]; l[h][3] = up1 ? s1[3] : s2[3];
          mx[2 * h] = fmaxf(l[h][0], l[h][1]); mx[2 * h + 1] = fmaxf(l[h][2], l[h][3]);
        }
#pragma unroll
        for (int o = 1; o < 4; o <<= 1) {
#pragma unroll
          for (int h = 0; h < 4; h++) mx[h] = fmaxf(mx[h], __shfl_xor_sync(~0u, mx[h], o));
        }
#pragma unroll
        for (int h = 0; h < 2; h++) {
          const float n0 = -mx[2 * h] * SCL, n1 = -mx[2 * h + 1] * SCL;
          const uint32_t pa = pack2(ex2(fmaf(l[h][0], SCL, n0)), ex2(fmaf(l[h][1], SCL, n0))), pb = pack2(ex2(fmaf(l[h][2], SCL, n1)), ex2(fmaf(l[h][3], SCL, n1)));
          float sm[4];
          mma8z(sm, pa, pb, 0x3f803f80u);
          const float ia = rcp(sm[0]), ib = rcp(sm[2]);
#pragma unroll
          for (int i = 8 * b + 4 * h; i < 8 * b + 4 * h + 4; i += 2) {
            uint32_t of[4];
#pragma unroll
            for (int d = 0; d < 2; d++) {
              float o[4];
              mma16z(o, pa & ~mup, pb & mup, 0u, pb & ~mup, vf[2 * (i + d)], vf[2 * (i + d) + 1]);
              mma8(o, pa & mup, 0u, pv[2 * i + 2 + d]);
              of[2 * d] = pack2(o[0] * ia, o[1] * ia); of[2 * d + 1] = pack2(o[2] * ib, o[3] * ib);
            }
            stsm4(stg_row + b * BLK + ((((i & 7) + (lane >> 4)) ^ (lane & 7)) << 4), of[0], of[1], of[2], of[3]);
          }
        }
        stage_done(sb, wg, b, lane);
        if (b == 0) gz += __float_as_uint(lds32f(bar + ZERO));
      }
      named_bar(1, 256);
      if (warp == 0) TR(8);
    }
    uint32_t pk[64];
    {
      float acc[64];
      mainloop<128, 6, 0>(acc, 16, true, r6, sb, wg, lane, rel, bid * 192 + 32, none, none, [&] {
        mbar_wait(bar + B_MOD, 0); mbar_wait(bar + B_X, 1); mbar_wait(bar + B_X + 8, 1);
        load_vec(pk + 32, sb, 2, 0, lane); load_vec(pk + 40, sb, 2, 1, lane);
#pragma unroll
        for (int i = 0; i < 16; i += 2) ldsm4(stg_row + (i >> 3) * BLK + ((((i & 7) + (lane >> 4)) ^ (lane & 7)) << 4), pk[2 * i], pk[2 * i + 1], pk[2 * i + 2], pk[2 * i + 3]);
      });
      if (warp == 0) TR(9);
#pragma unroll
      for (int i = 0; i < 32; i++) {
        acc[2 * i] = fmaf(acc[2 * i], bf_lo(pk[32 + (i >> 1)]), bf_lo(pk[i]));
        acc[2 * i + 1] = fmaf(acc[2 * i + 1], bf_hi(pk[32 + (i >> 1)]), bf_hi(pk[i]));
      }
      ln_publish(acc, g_stat + (16 + m) * 1024, j, row0, lane, ep);
      if (warp == 0) TR(36);
      mbar_wait(bar + B_FULL6 + 16, 1);
      if (lane < 2) mbar_arrive_cl(rel + B_EMPTY6 + 16);
      ring_next<6>(r6);
#pragma unroll
      for (int i = 0; i < 32; i++) { pk[i] = pack2(acc[2 * i], acc[2 * i + 1]); pk[32 + i] = 0; }
      ln_apply(acc, g_stat + (16 + m) * 1024, row0, ep, sb, 3, 4, stg_row, wg, lane);
      named_bar(2 + wg, 128);
      if (warp == 0) TR(11);
    }
    auto swiglu = [&](int q, int uo, int par) {
      if ((q & 3) == 0) mbar_wait(fre + 2 * q, par);
      uint32_t w[4];
#pragma unroll
      for (int u = 0; u < 4; u++) w[u] = silu_mul2(pk[4 * q + u], pk[uo + 4 * q + u]);
      stsm4(stg_row + (q >> 2) * BLK + ((((2 * q & 7) + (lane >> 4)) ^ (lane & 7)) << 4), w[0], w[1], w[2], w[3]);
    };
    r4.s = r4.wrap = 2;
#pragma unroll 1
    for (int t = 0; t < 3; t++) {
      float acc[128];
      mainloop<256, 4, 5>(acc, 16, t == 0, r4, sb, wg, lane, rel, bid * 192 + 48 + 16 * t, [&](auto ic) {
        if (t) {
          if (ic.v == 3 || ic.v == 5) stage_done(sb, wg, ic.v >> 2, lane);
          if (ic.v < 5) { swiglu(2 * ic.v - 2, 32, ~t & 1); swiglu(2 * ic.v - 1, 32, 0); }
        }
      }, [&](int it) {
#pragma unroll
        for (int i = 0; i < 8; i++)
          if (t == 0 && it == 6 + i) g_x1[bid * 2048 + (i >> 2) * 1024 + warp * 128 + (i & 3) * 32 + lane] = make_uint4(pk[4 * i], pk[4 * i + 1], pk[4 * i + 2], pk[4 * i + 3]);
      }, [&] { if (t == 0) fence_async_global(); });
      if (warp == 0) TR(12 + 2 * t);
#pragma unroll
      for (int i = 0; i < 64; i++) pk[i] = pack2(acc[2 * i], acc[2 * i + 1]);
      if (warp == 0) TR(13 + 2 * t);
    }
    uint32_t x1[32];
    {
      float acc[64];
      mainloop<128, 6, 6>(acc, 16, false, r6, sb, wg, lane, rel, bid * 192 + 96, [&](auto ic) {
        if (ic.v == 1) {
          mbar_wait(bar + B_X, 0);
#pragma unroll
          for (int i = 0; i < 8; i++) { const uint4 x = lds128(sb + STG + (i >> 2) * BLK + warp * 2048 + (i & 3) * 512 + lane * 16); x1[4 * i] = x.x; x1[4 * i + 1] = x.y; x1[4 * i + 2] = x.z; x1[4 * i + 3] = x.w; }
          __syncwarp();
        }
        if (ic.v == 4 || ic.v == 6) stage_done(sb, wg, ic.v / 5, lane);
        if (ic.v > 1 && ic.v < 6) { swiglu(2 * ic.v - 4, 32, 0); swiglu(2 * ic.v - 3, 32, 0); }
      }, none, [] {});
      if (warp == 0) TR(18);
#pragma unroll
      for (int i = 0; i < 32; i++) pk[i] = pack2(acc[2 * i], acc[2 * i + 1]);
      if (warp == 0) TR(19);
    }
    {
      float acc[64];
      mainloop<128, 6, 3>(acc, 56, false, r6, sb, wg, lane, rel, bid * 192 + 112, [&](auto ic) {
        if (ic.v == 3) stage_done(sb, wg, 0, lane); else { swiglu(2 * ic.v - 2, 16, 1); swiglu(2 * ic.v - 1, 16, 1); }
      }, none, [&] {
        if (TAILLAG && wg == 0 && lane == 0) mbar_arrive(bar + B_LAG);
        load_vec(pk + 32, sb, 5, 0, lane); load_vec(pk + 40, sb, 5, 1, lane);
        mbar_wait(fre, 0); mbar_wait(fre + 8, 1);
      });
      __syncwarp();
      cl_arrive_relaxed();
      if (warp == 0) TR(20);
#pragma unroll
      for (int i = 0; i < 16; i += 2) {
        uint32_t w[4];
#pragma unroll
        for (int u = 0; u < 4; u++) {
          const int q = 2 * i + u;
          w[u] = pack2(fmaf(acc[2 * q], bf_lo(pk[32 + (q >> 1)]), bf_lo(x1[q])), fmaf(acc[2 * q + 1], bf_hi(pk[32 + (q >> 1)]), bf_hi(x1[q])));
        }
        stsm4(stg_row + (i >> 3) * BLK + ((((i & 7) + (lane >> 4)) ^ (lane & 7)) << 4), w[0], w[1], w[2], w[3]);
        if ((i & 7) == 6) {
          fence_async_smem();
          named_bar(2 + wg, 128);
          if (wq == 0 && elect()) { tma_store_3d(&maps.out, sb + STG + (i >> 3) * BLK + wg * HALF, j * 128 + (i >> 3) * 64, m * 64, wg); bulk_commit(); }
          if (i < 8) x1[16] |= __float_as_uint(lds32f(bar + ZERO));
        }
      }
      if (wq == 0) bulk_wait_read();
      if (wq == 0) TR(40 + wg);
      if (tid == 0) g_epoch[bid + 4] = ep;
      if (warp == 0) TR(21);
      cl_wait();
    }
  }
}

typedef CUresult (*EncodeFn)(CUtensorMap*, CUtensorMapDataType, cuuint32_t, void*, const cuuint64_t*, const cuuint64_t*, const cuuint32_t*, const cuuint32_t*,
                             CUtensorMapInterleave, CUtensorMapSwizzle, CUtensorMapL2promotion, CUtensorMapFloatOOBfill);

void make_map(EncodeFn fn, CUtensorMap* mp, const void* base, uint64_t d0, uint64_t d1, uint64_t d2, uint64_t s1, uint64_t s2, uint32_t b2, uint32_t b0 = 64) {
  cuuint64_t d[3] = {d0, d1, d2}, s[2] = {s1, s2};
  cuuint32_t b[3] = {b0, 64, b2}, e[3] = {1, 1, 1};
  fn(mp, CU_TENSOR_MAP_DATA_TYPE_BFLOAT16, 3, (void*)base, d, s, b, e, CU_TENSOR_MAP_INTERLEAVE_NONE, b0 == 64 ? CU_TENSOR_MAP_SWIZZLE_128B : CU_TENSOR_MAP_SWIZZLE_NONE,
     CU_TENSOR_MAP_L2_PROMOTION_L2_128B, CU_TENSOR_MAP_FLOAT_OOB_FILL_NONE);
}

__global__ void probe_kernel() {}
int max_clusters(int size) {
  cudaLaunchConfig_t cfg = {};
  cudaLaunchAttribute at;
  at.id = cudaLaunchAttributeClusterDimension; at.val.clusterDim.x = size; at.val.clusterDim.y = 1; at.val.clusterDim.z = 1;
  cfg.gridDim = dim3(size * 66); cfg.blockDim = dim3(384); cfg.dynamicSmemBytes = SMEM_BYTES; cfg.attrs = &at; cfg.numAttrs = 1;
  int n = 0;
  if (cudaOccupancyMaxActiveClusters(&n, probe_kernel, &cfg) != cudaSuccess) { cudaGetLastError(); return 0; }
  return n;
}

}

extern "C" void kernel_launch(void* const* d_in, const int* in_sizes, int n_in, void* d_out, int out_size) {
  static EncodeFn fn = nullptr;
  static int by_sm = 0;
  if (!fn) {
    void* p = nullptr; cudaDriverEntryPointQueryResult q;
    cudaGetDriverEntryPoint("cuTensorMapEncodeTiled", &p, cudaEnableDefault, &q);
    fn = (EncodeFn)p;
    cudaFuncSetAttribute(fused_kernel, cudaFuncAttributeMaxDynamicSharedMemorySize, SMEM_BYTES);
    int dev = 0, sms = 0;
    cudaGetDevice(&dev);
    cudaDeviceGetAttribute(&sms, cudaDevAttrMultiProcessorCount, dev);
    cudaFuncSetAttribute(probe_kernel, cudaFuncAttributeMaxDynamicSharedMemorySize, SMEM_BYTES);
    by_sm = BYSM && sms == 132 && max_clusters(2) == 66 && max_clusters(4) == 30 && max_clusters(6) == 17 && max_clusters(8) == 15;
  }
  Maps mp;
  make_map(fn, &mp.x, d_in[0], D_, S_ / 2, 2, 4096, 2048, 2);
  make_map(fn, &mp.out, d_out, D_, S_ / 2, 2, 4096, 2048, 1);
  make_map(fn, &mp.wqkv, d_in[1], 64, D_, 3 * D_ / 64, 3 * D_ * 2, 128, 2);
  make_map(fn, &mp.wo, d_in[2], 64, D_, D_ / 64, D_ * 2, 128, 2);
  make_map(fn, &mp.w1, d_in[4], 64, D_, F_ / 64, F_ * 2, 128, 2);
  make_map(fn, &mp.w3, d_in[5], 64, D_, F_ / 64, F_ * 2, 128, 2);
  make_map(fn, &mp.w1s, d_in[4], 64, D_, F_ / 64, F_ * 2, 128, 1);
  make_map(fn, &mp.w3s, d_in[5], 64, D_, F_ / 64, F_ * 2, 128, 1);
  make_map(fn, &mp.w2, d_in[6], 64, F_, D_ / 64, D_ * 2, 128, 2);
  make_map(fn, &mp.wmod, d_in[8], 256, D_, 24, 6 * D_ * 2, 512, 1, 256);
  fused_kernel<<<132, 384, SMEM_BYTES>>>(mp, (const bf16*)d_in[7], (const bf16*)d_in[8], by_sm);
}
```

```cpp
#include <cuda_runtime.h>
#include <cuda_bf16.h>
#include <cuda.h>
#include <stdint.h>

typedef __nv_bfloat16 bf16;

#define NPIECE 4
#define PSLEEP 300
#define XSLEEP 4000
#define XDELAY 2500
#define TAILLAG 5
#define HSLEEP 400
#define BYSM 1
namespace {

constexpr int S_ = 2048, D_ = 1024, F_ = 3584;
constexpr int BLK = 16384;
constexpr int HALF = 8192;
constexpr int RING = 196608;
constexpr int STG = RING;
constexpr int MISC = RING + 2 * BLK;
constexpr int SMEM_BYTES = MISC + 3072;
constexpr int B_FULL4 = 0, B_EMPTY4 = 32, B_FULL6 = 64, B_EMPTY6 = 112, B_RDY = 160, B_FREE = 176, B_LAG = 192, B_X = 208, B_MOD = 224, B_HALO = 232, B_OWN = 240, B_HH = 256, B_ALL = 272, B_HH2 = 288, ZERO = 296;
constexpr int MODV = 512;
constexpr int RED_OFF = 0;
constexpr float SCL = 0.17677669529663687f * 1.4426950408889634f;
constexpr int U_HH = 64;

struct Maps { CUtensorMap x, out, wqkv, wo, w1, w3, w1s, w3s, w2, wmod; };

__device__ uint4 g_h[16 * 16 * 1024];
__device__ uint4 g_o[16 * 16 * 1024];
__device__ uint4 g_hh[16 * 56 * 1024];
__device__ uint4 g_x1[128 * 8 * 256];
__device__ uint2 g_modp[8 * 2 * 4 * 128];
__device__ uint2 g_modv[4 * 1024];
__device__ uint4 g_stat[2 * 16 * 8 * 128];
__device__ uint4 g_halo[16 * 8 * 2 * 512];
__device__ uint32_t g_flag[16 * 128];
__device__ uint32_t g_epoch[132];
#define TR(i)
#define TRS(i)

__device__ __forceinline__ void bail() { asm volatile("st.global.u32 [%0], %1;" :: "l"(0ull), "r"(0) : "memory"); }
__device__ __forceinline__ uint32_t smem_u32(const void* p) { return (uint32_t)__cvta_generic_to_shared(p); }
__device__ __forceinline__ void mbar_init(uint32_t bar, uint32_t cnt) { asm volatile("mbarrier.init.shared::cta.b64 [%0], %1;" :: "r"(bar), "r"(cnt) : "memory"); }
__device__ __forceinline__ void mbar_expect_tx(uint32_t bar, uint32_t bytes) { asm volatile("mbarrier.arrive.expect_tx.shared::cta.b64 _, [%0], %1;" :: "r"(bar), "r"(bytes) : "memory"); }
__device__ __forceinline__ void mbar_arrive(uint32_t bar) { asm volatile("mbarrier.arrive.shared::cta.b64 _, [%0];" :: "r"(bar) : "memory"); }
__device__ __forceinline__ void mbar_arrive_cl(uint32_t cl_addr) { asm volatile("mbarrier.arrive.shared::cluster.b64 _, [%0];" :: "r"(cl_addr) : "memory"); }
__device__ __forceinline__ uint32_t mapa(uint32_t addr, uint32_t cta) { uint32_t r; asm("mapa.shared::cluster.u32 %0, %1, %2;" : "=r"(r) : "r"(addr), "r"(cta)); return r; }
__device__ __forceinline__ void mbar_wait(uint32_t bar, uint32_t parity) {
  asm volatile("{\n.reg .pred p;\n.reg .b32 n;\n.reg .b64 z;\nmov.b32 n, 0;\nmov.b64 z, 0;\n"
               "W: add.u32 n, n, 1;\nsetp.gt.u32 p, n, 0x400000;\n@p st.global.u32 [z], n;\n"
               "mbarrier.try_wait.parity.shared::cta.b64 p, [%0], %1;\n@!p bra W;\n}" :: "r"(bar), "r"(parity) : "memory");
}
__device__ __forceinline__ void tma_3d(uint32_t dst, const CUtensorMap* m, uint32_t bar, int c0, int c1, int c2) {
  asm volatile("cp.async.bulk.tensor.3d.shared::cluster.global.mbarrier::complete_tx::bytes [%0], [%1, {%3, %4, %5}], [%2];" :: "r"(dst), "l"(m), "r"(bar), "r"(c0), "r"(c1), "r"(c2) : "memory");
}
__device__ __forceinline__ void tma_store_3d(const CUtensorMap* m, uint32_t src, int c0, int c1, int c2) {
  asm volatile("cp.async.bulk.tensor.3d.global.shared::cta.bulk_group [%0, {%2, %3, %4}], [%1];" :: "l"(m), "r"(src), "r"(c0), "r"(c1), "r"(c2) : "memory");
}
__device__ __forceinline__ void bulk_ld(uint32_t dst, const void* src, uint32_t bytes, uint32_t bar) {
  asm volatile("cp.async.bulk.shared::cluster.global.mbarrier::complete_tx::bytes [%0], [%1], %2, [%3];" :: "r"(dst), "l"(src), "r"(bytes), "r"(bar) : "memory");
}
__device__ __forceinline__ void bulk_ld_mc(uint32_t dst, const void* src, uint32_t bytes, uint32_t bar) {
  asm volatile("cp.async.bulk.shared::cluster.global.mbarrier::complete_tx::bytes.multicast::cluster [%0], [%1], %2, [%3], %4;" :: "r"(dst), "l"(src), "r"(bytes), "r"(bar), "h"((uint16_t)3) : "memory");
}
__device__ __forceinline__ void bulk_st(void* dst, uint32_t src, uint32_t bytes) {
  asm volatile("cp.async.bulk.global.shared::cta.bulk_group [%0], [%1], %2;" :: "l"(dst), "r"(src), "r"(bytes) : "memory");
}
__device__ __forceinline__ void bulk_commit() { asm volatile("cp.async.bulk.commit_group;" ::: "memory"); }
__device__ __forceinline__ void bulk_wait_read() { asm volatile("cp.async.bulk.wait_group.read 0;" ::: "memory"); }
__device__ __forceinline__ void bulk_wait_all() { asm volatile("cp.async.bulk.wait_group 0;" ::: "memory"); }
__device__ __forceinline__ void fence_async_global() { asm volatile("fence.proxy.async.global;" ::: "memory"); }
__device__ __forceinline__ void fence_async_smem() { asm volatile("fence.proxy.async.shared::cta;" ::: "memory"); }
__device__ __forceinline__ void wg_arrive() { asm volatile("wgmma.fence.sync.aligned;" ::: "memory"); }
__device__ __forceinline__ void wg_commit() { asm volatile("wgmma.commit_group.sync.aligned;" ::: "memory"); }
template <int N> __device__ __forceinline__ void wg_wait() { asm volatile("wgmma.wait_group.sync.aligned %0;" :: "n"(N) : "memory"); }
__device__ __forceinline__ void cl_arrive_relaxed() { asm volatile("barrier.cluster.arrive.relaxed.aligned;" ::: "memory"); }
__device__ __forceinline__ void cl_wait() { asm volatile("barrier.cluster.wait.acquire.aligned;" ::: "memory"); }
__device__ __forceinline__ bool elect() { uint32_t p; asm volatile("{\n.reg .pred p;\nelect.sync _|p, 0xffffffff;\nselp.u32 %0, 1, 0, p;\n}" : "=r"(p)); return p; }
__device__ __forceinline__ void named_bar(int id, int n) { asm volatile("bar.sync %0, %1;" :: "r"(id), "r"(n) : "memory"); }
__device__ __forceinline__ uint32_t pack2(float lo, float hi) { uint32_t r; asm("cvt.rn.bf16x2.f32 %0, %1, %2;" : "=r"(r) : "f"(hi), "f"(lo)); return r; }
__device__ __forceinline__ float bf_lo(uint32_t w) { return __uint_as_float(w << 16); }
__device__ __forceinline__ float bf_hi(uint32_t w) { return __uint_as_float(w & 0xffff0000u); }
__device__ __forceinline__ float bf_round(float v) { return __bfloat162float(__float2bfloat16_rn(v)); }
__device__ __forceinline__ void stsm4(uint32_t addr, uint32_t a, uint32_t b, uint32_t c, uint32_t d) {
  asm volatile("stmatrix.sync.aligned.m8n8.x4.shared.b16 [%0], {%1, %2, %3, %4};" :: "r"(addr), "r"(a), "r"(b), "r"(c), "r"(d) : "memory");
}
__device__ __forceinline__ void ldsm4(uint32_t addr, uint32_t& a, uint32_t& b, uint32_t& c, uint32_t& d) {
  asm volatile("ldmatrix.sync.aligned.m8n8.x4.shared.b16 {%0, %1, %2, %3}, [%4];" : "=r"(a), "=r"(b), "=r"(c), "=r"(d) : "r"(addr) : "memory");
}
__device__ __forceinline__ uint32_t movm(uint32_t a) { uint32_t r; asm volatile("movmatrix.sync.aligned.m8n8.trans.b16 %0, %1;" : "=r"(r) : "r"(a)); return r; }
__device__ __forceinline__ void mma16(float (&d)[4], uint32_t a0, uint32_t a1, uint32_t a2, uint32_t a3, uint32_t b0, uint32_t b1) {
  asm("mma.sync.aligned.m16n8k16.row.col.f32.bf16.bf16.f32 {%0,%1,%2,%3}, {%4,%5,%6,%7}, {%8,%9}, {%0,%1,%2,%3};"
               : "+f"(d[0]), "+f"(d[1]), "+f"(d[2]), "+f"(d[3]) : "r"(a0), "r"(a1), "r"(a2), "r"(a3), "r"(b0), "r"(b1));
}
__device__ __forceinline__ void mma16z(float (&d)[4], uint32_t a0, uint32_t a1, uint32_t a2, uint32_t a3, uint32_t b0, uint32_t b1) {
  asm("mma.sync.aligned.m16n8k16.row.col.f32.bf16.bf16.f32 {%0,%1,%2,%3}, {%4,%5,%6,%7}, {%8,%9}, {%10,%10,%10,%10};"
      : "=f"(d[0]), "=f"(d[1]), "=f"(d[2]), "=f"(d[3]) : "r"(a0), "r"(a1), "r"(a2), "r"(a3), "r"(b0), "r"(b1), "f"(0.f));
}
__device__ __forceinline__ void mma8z(float (&d)[4], uint32_t a0, uint32_t a1, uint32_t b0) {
  asm("mma.sync.aligned.m16n8k8.row.col.f32.bf16.bf16.f32 {%0,%1,%2,%3}, {%4,%5}, {%6}, {%7,%7,%7,%7};"
      : "=f"(d[0]), "=f"(d[1]), "=f"(d[2]), "=f"(d[3]) : "r"(a0), "r"(a1), "r"(b0), "f"(0.f));
}
__device__ __forceinline__ void mma8(float (&d)[4], uint32_t a0, uint32_t a1, uint32_t b0) {
  asm("mma.sync.aligned.m16n8k8.row.col.f32.bf16.bf16.f32 {%0,%1,%2,%3}, {%4,%5}, {%6}, {%0,%1,%2,%3};"
               : "+f"(d[0]), "+f"(d[1]), "+f"(d[2]), "+f"(d[3]) : "r"(a0), "r"(a1), "r"(b0));
}
__device__ __forceinline__ uint4 lds128(uint32_t a) { uint4 v; asm volatile("ld.shared.v4.u32 {%0,%1,%2,%3}, [%4];" : "=r"(v.x), "=r"(v.y), "=r"(v.z), "=r"(v.w) : "r"(a) : "memory"); return v; }
__device__ __forceinline__ void sts128(uint32_t a, uint32_t x, uint32_t y, uint32_t z, uint32_t w) { asm volatile("st.shared.v4.u32 [%0], {%1,%2,%3,%4};" :: "r"(a), "r"(x), "r"(y), "r"(z), "r"(w) : "memory"); }
__device__ __forceinline__ float lds32f(uint32_t a) { float v; asm volatile("ld.shared.f32 %0, [%1];" : "=f"(v) : "r"(a) : "memory"); return v; }
__device__ __forceinline__ void sts16(uint32_t a, bf16 v) { asm volatile("st.shared.b16 [%0], %1;" :: "r"(a), "h"(__bfloat16_as_ushort(v)) : "memory"); }
__device__ __forceinline__ uint4 ldg_nc(const void* p) { uint4 v; asm volatile("ld.global.nc.L1::no_allocate.v4.u32 {%0,%1,%2,%3}, [%4];" : "=r"(v.x), "=r"(v.y), "=r"(v.z), "=r"(v.w) : "l"(p)); return v; }
__device__ __forceinline__ uint4 ld_rlx4(const uint4* p) {
  unsigned long long a, b; asm volatile("ld.relaxed.gpu.global.v2.b64 {%0,%1}, [%2];" : "=l"(a), "=l"(b) : "l"(p) : "memory");
  return make_uint4((uint32_t)a, (uint32_t)(a >> 32), (uint32_t)b, (uint32_t)(b >> 32));
}
__device__ __forceinline__ uint2 ld_rlx2(const uint2* p) { unsigned long long a; asm volatile("ld.relaxed.gpu.global.b64 %0, [%1];" : "=l"(a) : "l"(p) : "memory"); return make_uint2((uint32_t)a, (uint32_t)(a >> 32)); }
__device__ __forceinline__ void st_rlx4(uint4* p, uint32_t x, uint32_t y, uint32_t z, uint32_t w) {
  asm volatile("st.relaxed.gpu.global.v2.b64 [%0], {%1,%2};" :: "l"(p), "l"((unsigned long long)x | ((unsigned long long)y << 32)), "l"((unsigned long long)z | ((unsigned long long)w << 32)) : "memory");
}
__device__ __forceinline__ void st_rlx2(uint2* p, uint32_t x, uint32_t y) { asm volatile("st.relaxed.gpu.global.b64 [%0], %1;" :: "l"(p), "l"((unsigned long long)x | ((unsigned long long)y << 32)) : "memory"); }
__device__ __forceinline__ void st_release(uint32_t* p, uint32_t v) { asm volatile("st.release.gpu.global.u32 [%0], %1;" :: "l"(p), "r"(v) : "memory"); }
__device__ __forceinline__ uint32_t ld_acquire(const uint32_t* p) { uint32_t v; asm volatile("ld.acquire.gpu.global.u32 %0, [%1];" : "=r"(v) : "l"(p) : "memory"); return v; }
__device__ __forceinline__ void prefetch_map(const CUtensorMap* m) { asm volatile("prefetch.tensormap [%0];" :: "l"(m) : "memory"); }
__device__ __forceinline__ float rcp(float x) { float r; asm("rcp.approx.ftz.f32 %0, %1;" : "=f"(r) : "f"(x)); return r; }
__device__ __forceinline__ float ex2(float x) { float r; asm("ex2.approx.ftz.f32 %0, %1;" : "=f"(r) : "f"(x)); return r; }
__device__ __forceinline__ float tanh_fast(float x) { float r; asm("tanh.approx.f32 %0, %1;" : "=f"(r) : "f"(x)); return r; }
#define SPIN_GUARD(n) if (++(n) > (1u << 24)) bail()

__device__ __forceinline__ void wgmma_n128(float (&d)[64], uint64_t da, uint64_t db) {
  asm volatile("wgmma.mma_async.sync.aligned.m64n128k16.f32.bf16.bf16 "
    "{%0, %1, %2, %3, %4, %5, %6, %7, %8, %9, %10, %11, %12, %13, %14, %15, %16, %17, %18, %19, %20, %21, %22, %23, %24, %25, %26, %27, %28, %29, %30, %31, %32, %33, %34, %35, %36, %37, %38, %39, %40, %41, %42, %43, %44, %45, %46, %47, %48, %49, %50, %51, %52, %53, %54, %55, %56, %57, %58, %59, %60, %61, %62, %63}, "
    "%64, %65, 1, 1, 1, 0, 1;\n"
    : "+f"(d[0]), "+f"(d[1]), "+f"(d[2]), "+f"(d[3]), "+f"(d[4]), "+f"(d[5]), "+f"(d[6]), "+f"(d[7]), "+f"(d[8]), "+f"(d[9]), "+f"(d[10]), "+f"(d[11]), "+f"(d[12]), "+f"(d[13]), "+f"(d[14]), "+f"(d[15]), "+f"(d[16]), "+f"(d[17]), "+f"(d[18]), "+f"(d[19]), "+f"(d[20]), "+f"(d[21]), "+f"(d[22]), "+f"(d[23]), "+f"(d[24]), "+f"(d[25]), "+f"(d[26]), "+f"(d[27]), "+f"(d[28]), "+f"(d[29]), "+f"(d[30]), "+f"(d[31]), "+f"(d[32]), "+f"(d[33]), "+f"(d[34]), "+f"(d[35]), "+f"(d[36]), "+f"(d[37]), "+f"(d[38]), "+f"(d[39]), "+f"(d[40]), "+f"(d[41]), "+f"(d[42]), "+f"(d[43]), "+f"(d[44]), "+f"(d[45]), "+f"(d[46]), "+f"(d[47]), "+f"(d[48]), "+f"(d[49]), "+f"(d[50]), "+f"(d[51]), "+f"(d[52]), "+f"(d[53]), "+f"(d[54]), "+f"(d[55]), "+f"(d[56]), "+f"(d[57]), "+f"(d[58]), "+f"(d[59]), "+f"(d[60]), "+f"(d[61]), "+f"(d[62]), "+f"(d[63])
    : "l"(da), "l"(db));
}
__device__ __forceinline__ void wgmma_n128_first(float (&d)[64], uint64_t da, uint64_t db) {
  asm volatile("wgmma.mma_async.sync.aligned.m64n128k16.f32.bf16.bf16 "
    "{%0, %1, %2, %3, %4, %5, %6, %7, %8, %9, %10, %11, %12, %13, %14, %15, %16, %17, %18, %19, %20, %21, %22, %23, %24, %25, %26, %27, %28, %29, %30, %31, %32, %33, %34, %35, %36, %37, %38, %39, %40, %41, %42, %43, %44, %45, %46, %47, %48, %49, %50, %51, %52, %53, %54, %55, %56, %57, %58, %59, %60, %61, %62, %63}, "
    "%64, %65, 0, 1, 1, 0, 1;\n"
    : "=f"(d[0]), "=f"(d[1]), "=f"(d[2]), "=f"(d[3]), "=f"(d[4]), "=f"(d[5]), "=f"(d[6]), "=f"(d[7]), "=f"(d[8]), "=f"(d[9]), "=f"(d[10]), "=f"(d[11]), "=f"(d[12]), "=f"(d[13]), "=f"(d[14]), "=f"(d[15]), "=f"(d[16]), "=f"(d[17]), "=f"(d[18]), "=f"(d[19]), "=f"(d[20]), "=f"(d[21]), "=f"(d[22]), "=f"(d[23]), "=f"(d[24]), "=f"(d[25]), "=f"(d[26]), "=f"(d[27]), "=f"(d[28]), "=f"(d[29]), "=f"(d[30]), "=f"(d[31]), "=f"(d[32]), "=f"(d[33]), "=f"(d[34]), "=f"(d[35]), "=f"(d[36]), "=f"(d[37]), "=f"(d[38]), "=f"(d[39]), "=f"(d[40]), "=f"(d[41]), "=f"(d[42]), "=f"(d[43]), "=f"(d[44]), "=f"(d[45]), "=f"(d[46]), "=f"(d[47]), "=f"(d[48]), "=f"(d[49]), "=f"(d[50]), "=f"(d[51]), "=f"(d[52]), "=f"(d[53]), "=f"(d[54]), "=f"(d[55]), "=f"(d[56]), "=f"(d[57]), "=f"(d[58]), "=f"(d[59]), "=f"(d[60]), "=f"(d[61]), "=f"(d[62]), "=f"(d[63])
    : "l"(da), "l"(db));
}
__device__ __forceinline__ void wgmma_n256(float (&d)[128], uint64_t da, uint64_t db) {
  asm volatile("wgmma.mma_async.sync.aligned.m64n256k16.f32.bf16.bf16 "
    "{%0, %1, %2, %3, %4, %5, %6, %7, %8, %9, %10, %11, %12, %13, %14, %15, %16, %17, %18, %19, %20, %21, %22, %23, %24, %25, %26, %27, %28, %29, %30, %31, %32, %33, %34, %35, %36, %37, %38, %39, %40, %41, %42, %43, %44, %45, %46, %47, %48, %49, %50, %51, %52, %53, %54, %55, %56, %57, %58, %59, %60, %61, %62, %63, %64, %65, %66, %67, %68, %69, %70, %71, %72, %73, %74, %75, %76, %77, %78, %79, %80, %81, %82, %83, %84, %85, %86, %87, %88, %89, %90, %91, %92, %93, %94, %95, %96, %97, %98, %99, %100, %101, %102, %103, %104, %105, %106, %107, %108, %109, %110, %111, %112, %113, %114, %115, %116, %117, %118, %119, %120, %121, %122, %123, %124, %125, %126, %127}, "
    "%128, %129, 1, 1, 1, 0, 1;\n"
    : "+f"(d[0]), "+f"(d[1]), "+f"(d[2]), "+f"(d[3]), "+f"(d[4]), "+f"(d[5]), "+f"(d[6]), "+f"(d[7]), "+f"(d[8]), "+f"(d[9]), "+f"(d[10]), "+f"(d[11]), "+f"(d[12]), "+f"(d[13]), "+f"(d[14]), "+f"(d[15]), "+f"(d[16]), "+f"(d[17]), "+f"(d[18]), "+f"(d[19]), "+f"(d[20]), "+f"(d[21]), "+f"(d[22]), "+f"(d[23]), "+f"(d[24]), "+f"(d[25]), "+f"(d[26]), "+f"(d[27]), "+f"(d[28]), "+f"(d[29]), "+f"(d[30]), "+f"(d[31]), "+f"(d[32]), "+f"(d[33]), "+f"(d[34]), "+f"(d[35]), "+f"(d[36]), "+f"(d[37]), "+f"(d[38]), "+f"(d[39]), "+f"(d[40]), "+f"(d[41]), "+f"(d[42]), "+f"(d[43]), "+f"(d[44]), "+f"(d[45]), "+f"(d[46]), "+f"(d[47]), "+f"(d[48]), "+f"(d[49]), "+f"(d[50]), "+f"(d[51]), "+f"(d[52]), "+f"(d[53]), "+f"(d[54]), "+f"(d[55]), "+f"(d[56]), "+f"(d[57]), "+f"(d[58]), "+f"(d[59]), "+f"(d[60]), "+f"(d[61]), "+f"(d[62]), "+f"(d[63]), "+f"(d[64]), "+f"(d[65]), "+f"(d[66]), "+f"(d[67]), "+f"(d[68]), "+f"(d[69]), "+f"(d[70]), "+f"(d[71]), "+f"(d[72]), "+f"(d[73]), "+f"(d[74]), "+f"(d[75]), "+f"(d[76]), "+f"(d[77]), "+f"(d[78]), "+f"(d[79]), "+f"(d[80]), "+f"(d[81]), "+f"(d[82]), "+f"(d[83]), "+f"(d[84]), "+f"(d[85]), "+f"(d[86]), "+f"(d[87]), "+f"(d[88]), "+f"(d[89]), "+f"(d[90]), "+f"(d[91]), "+f"(d[92]), "+f"(d[93]), "+f"(d[94]), "+f"(d[95]), "+f"(d[96]), "+f"(d[97]), "+f"(d[98]), "+f"(d[99]), "+f"(d[100]), "+f"(d[101]), "+f"(d[102]), "+f"(d[103]), "+f"(d[104]), "+f"(d[105]), "+f"(d[106]), "+f"(d[107]), "+f"(d[108]), "+f"(d[109]), "+f"(d[110]), "+f"(d[111]), "+f"(d[112]), "+f"(d[113]), "+f"(d[114]), "+f"(d[115]), "+f"(d[116]), "+f"(d[117]), "+f"(d[118]), "+f"(d[119]), "+f"(d[120]), "+f"(d[121]), "+f"(d[122]), "+f"(d[123]), "+f"(d[124]), "+f"(d[125]), "+f"(d[126]), "+f"(d[127])
    : "l"(da), "l"(db));
}
__device__ __forceinline__ void wgmma_n256_first(float (&d)[128], uint64_t da, uint64_t db) {
  asm volatile("wgmma.mma_async.sync.aligned.m64n256k16.f32.bf16.bf16 "
    "{%0, %1, %2, %3, %4, %5, %6, %7, %8, %9, %10, %11, %12, %13, %14, %15, %16, %17, %18, %19, %20, %21, %22, %23, %24, %25, %26, %27, %28, %29, %30, %31, %32, %33, %34, %35, %36, %37, %38, %39, %40, %41, %42, %43, %44, %45, %46, %47, %48, %49, %50, %51, %52, %53, %54, %55, %56, %57, %58, %59, %60, %61, %62, %63, %64, %65, %66, %67, %68, %69, %70, %71, %72, %73, %74, %75, %76, %77, %78, %79, %80, %81, %82, %83, %84, %85, %86, %87, %88, %89, %90, %91, %92, %93, %94, %95, %96, %97, %98, %99, %100, %101, %102, %103, %104, %105, %106, %107, %108, %109, %110, %111, %112, %113, %114, %115, %116, %117, %118, %119, %120, %121, %122, %123, %124, %125, %126, %127}, "
    "%128, %129, 0, 1, 1, 0, 1;\n"
    : "=f"(d[0]), "=f"(d[1]), "=f"(d[2]), "=f"(d[3]), "=f"(d[4]), "=f"(d[5]), "=f"(d[6]), "=f"(d[7]), "=f"(d[8]), "=f"(d[9]), "=f"(d[10]), "=f"(d[11]), "=f"(d[12]), "=f"(d[13]), "=f"(d[14]), "=f"(d[15]), "=f"(d[16]), "=f"(d[17]), "=f"(d[18]), "=f"(d[19]), "=f"(d[20]), "=f"(d[21]), "=f"(d[22]), "=f"(d[23]), "=f"(d[24]), "=f"(d[25]), "=f"(d[26]), "=f"(d[27]), "=f"(d[28]), "=f"(d[29]), "=f"(d[30]), "=f"(d[31]), "=f"(d[32]), "=f"(d[33]), "=f"(d[34]), "=f"(d[35]), "=f"(d[36]), "=f"(d[37]), "=f"(d[38]), "=f"(d[39]), "=f"(d[40]), "=f"(d[41]), "=f"(d[42]), "=f"(d[43]), "=f"(d[44]), "=f"(d[45]), "=f"(d[46]), "=f"(d[47]), "=f"(d[48]), "=f"(d[49]), "=f"(d[50]), "=f"(d[51]), "=f"(d[52]), "=f"(d[53]), "=f"(d[54]), "=f"(d[55]), "=f"(d[56]), "=f"(d[57]), "=f"(d[58]), "=f"(d[59]), "=f"(d[60]), "=f"(d[61]), "=f"(d[62]), "=f"(d[63]), "=f"(d[64]), "=f"(d[65]), "=f"(d[66]), "=f"(d[67]), "=f"(d[68]), "=f"(d[69]), "=f"(d[70]), "=f"(d[71]), "=f"(d[72]), "=f"(d[73]), "=f"(d[74]), "=f"(d[75]), "=f"(d[76]), "=f"(d[77]), "=f"(d[78]), "=f"(d[79]), "=f"(d[80]), "=f"(d[81]), "=f"(d[82]), "=f"(d[83]), "=f"(d[84]), "=f"(d[85]), "=f"(d[86]), "=f"(d[87]), "=f"(d[88]), "=f"(d[89]), "=f"(d[90]), "=f"(d[91]), "=f"(d[92]), "=f"(d[93]), "=f"(d[94]), "=f"(d[95]), "=f"(d[96]), "=f"(d[97]), "=f"(d[98]), "=f"(d[99]), "=f"(d[100]), "=f"(d[101]), "=f"(d[102]), "=f"(d[103]), "=f"(d[104]), "=f"(d[105]), "=f"(d[106]), "=f"(d[107]), "=f"(d[108]), "=f"(d[109]), "=f"(d[110]), "=f"(d[111]), "=f"(d[112]), "=f"(d[113]), "=f"(d[114]), "=f"(d[115]), "=f"(d[116]), "=f"(d[117]), "=f"(d[118]), "=f"(d[119]), "=f"(d[120]), "=f"(d[121]), "=f"(d[122]), "=f"(d[123]), "=f"(d[124]), "=f"(d[125]), "=f"(d[126]), "=f"(d[127])
    : "l"(da), "l"(db));
}

template <int N> struct WG;
#define DEF_WG(N) template <> struct WG<N> { \
  static __device__ __forceinline__ void mma(float (&d)[N / 2], uint64_t a, uint64_t b) { wgmma_n##N(d, a, b); } \
  static __device__ __forceinline__ void first(float (&d)[N / 2], uint64_t a, uint64_t b) { wgmma_n##N##_first(d, a, b); } };
DEF_WG(128) DEF_WG(256)

constexpr uint64_t DESC_A = (1ull << 62) | ((uint64_t)(1024 >> 4) << 32) | (1ull << 16);
constexpr uint64_t DESC_B = (1ull << 62) | ((uint64_t)(1024 >> 4) << 32) | ((uint64_t)(8192 >> 4) << 16);

struct Ring { int s; uint32_t ph; int wrap; };
template <int NS> __device__ __forceinline__ void ring_next(Ring& r) { r.s = (r.s + 1 == NS) ? 0 : r.s + 1; if (r.s == r.wrap) r.ph ^= 1; }

__device__ __forceinline__ int own_order(int it, int j) {
  return it < 2 ? 2 * j + it : it < 4 ? 2 * (j ^ 1) + it - 2 : ((j >> 1) * 4 + 2 * it - (it < 10 ? 4 : 15)) & 15;
}

template <int V> struct IC { static constexpr int v = V; };
template <int I, int E, class F> __device__ __forceinline__ void static_for(F&& f) { if constexpr (I < E) { f(IC<I>{}); static_for<I + 1, E>(f); } }

template <int N, int NS, int PRE, class Pre, class Mid, class Last>
__device__ __forceinline__ void mainloop(float (&acc)[N / 2], int nkb, bool own, Ring& r, uint32_t sb, int wg, int lane, uint32_t rel_base, int step0, Pre pre, Mid mid, Last last) {
  constexpr int SLOT = RING / NS;
  const uint32_t full = sb + MISC + (NS == 4 ? B_FULL4 : B_FULL6);
  const uint32_t rel = rel_base + (NS == 4 ? B_EMPTY4 : B_EMPTY6);
  const uint32_t s0 = (sb & 0x3FFFF) >> 4, a0 = s0 + wg * (HALF >> 4);
  int ps;
  auto issue = [&](int it, bool first) {
    const uint64_t da = DESC_A | (a0 + ((own && it < 2) ? (STG + it * BLK) >> 4 : r.s * (SLOT >> 4))), db = DESC_B | (s0 + r.s * (SLOT >> 4) + (BLK >> 4));
    mbar_wait(full + r.s * 8, r.ph);
    TRS(step0 + it);
    wg_arrive();
    if (first) WG<N>::first(acc, da, db); else WG<N>::mma(acc, da, db);
#pragma unroll
    for (int k = 1; k < 4; k++) WG<N>::mma(acc, da + k * 2, db + k * 128);
    wg_commit();
  };
  auto retire = [&](int it) {
    wg_wait<1>();
    if (lane < 2) mbar_arrive_cl(rel + ps * 8);
    if (own && it == 2 && lane == 0) mbar_arrive(sb + MISC + B_OWN);
    ps = r.s;
    ring_next<NS>(r);
  };
  issue(0, true);
  ps = r.s;
  ring_next<NS>(r);
  static_for<1, PRE + 1>([&](auto ic) { issue(ic.v, false); pre(ic); retire(ic.v); });
#pragma unroll 1
  for (int it = PRE + 1; it < nkb; it++) {
    if (TAILLAG && it == 56 - TAILLAG && wg == 1) mbar_wait(sb + MISC + B_LAG, 0);
    issue(it, false); mid(it); retire(it);
  }
  last();
  wg_wait<0>();
  if (lane < 2) mbar_arrive_cl(rel + ps * 8);
}

__device__ __forceinline__ void ln_publish(const float (&v)[64], uint4* st, int j, int row0, int lane, uint32_t ep) {
  float s0 = 0, s1 = 0, s2 = 0, s3 = 0, q0 = 0, q1 = 0, q2 = 0, q3 = 0;
#pragma unroll
  for (int i = 0; i < 16; i++) {
    s0 += v[4 * i]; s1 += v[4 * i + 1]; s2 += v[4 * i + 2]; s3 += v[4 * i + 3];
    q0 = fmaf(v[4 * i], v[4 * i], q0); q1 = fmaf(v[4 * i + 1], v[4 * i + 1], q1); q2 = fmaf(v[4 * i + 2], v[4 * i + 2], q2); q3 = fmaf(v[4 * i + 3], v[4 * i + 3], q3);
  }
  s0 += s1; s2 += s3; q0 += q1; q2 += q3;
  const bool odd = lane & 1;
  float s = (odd ? s2 : s0) + __shfl_xor_sync(~0u, odd ? s0 : s2, 1), q = (odd ? q2 : q0) + __shfl_xor_sync(~0u, odd ? q0 : q2, 1);
  s += __shfl_xor_sync(~0u, s, 2); q += __shfl_xor_sync(~0u, q, 2);
  if ((lane & 3) < 2) st_rlx4(st + j * 128 + row0 + (lane & 1) * 8, __float_as_uint(s), ep, __float_as_uint(q), ep);
}
__device__ __forceinline__ void ln_gather(const uint4* st, int row0, int lane, uint32_t ep, float& n0, float& r0, float& n1, float& r1) {
  const uint4* p = st + (lane & 2) * 256 + row0 + (lane & 1) * 8;
  uint4 a, b, c, d; uint32_t n = 0;
  while (true) {
    a = ld_rlx4(p); b = ld_rlx4(p + 128); c = ld_rlx4(p + 256); d = ld_rlx4(p + 384);
    if (a.y == ep && a.w == ep && b.y == ep && b.w == ep && c.y == ep && c.w == ep && d.y == ep && d.w == ep) break;
    SPIN_GUARD(n);
  }
  __syncwarp();
  float s = (__uint_as_float(a.x) + __uint_as_float(b.x)) + (__uint_as_float(c.x) + __uint_as_float(d.x));
  float q = (__uint_as_float(a.z) + __uint_as_float(b.z)) + (__uint_as_float(c.z) + __uint_as_float(d.z));
  s += __shfl_xor_sync(~0u, s, 2); q += __shfl_xor_sync(~0u, q, 2);
  s *= 1.f / 1024;
  const float r = rsqrtf(fmaxf(fmaf(-s, s, q * (1.f / 1024)), 0.f) + 1e-5f), nn = -s * r;
  const float ro = __shfl_xor_sync(~0u, r, 1), no = __shfl_xor_sync(~0u, nn, 1);
  const bool odd = lane & 1;
  r0 = odd ? ro : r; n0 = odd ? no : nn; r1 = odd ? r : ro; n1 = odd ? nn : no;
}
__device__ __forceinline__ void load_vec(uint32_t* w, uint32_t sb, int sec, int b, int lane) {
#pragma unroll
  for (int q = 0; q < 2; q++) { uint4 t = lds128(sb + MISC + MODV + sec * 256 + (lane & 3) * 64 + b * 32 + q * 16); w[4 * q] = t.x; w[4 * q + 1] = t.y; w[4 * q + 2] = t.z; w[4 * q + 3] = t.w; }
}
__device__ __forceinline__ void stage_done(uint32_t sb, int wg, int b, int lane) {
  fence_async_smem();
  __syncwarp();
  if (lane == 0) mbar_arrive(sb + MISC + B_RDY + b * 8);
}
__device__ __forceinline__ uint32_t hfma2(uint32_t a, uint32_t b, uint32_t c) { uint32_t r; asm("fma.rn.bf16x2 %0, %1, %2, %3;" : "=r"(r) : "r"(a), "r"(b), "r"(c)); return r; }
__device__ __forceinline__ void ln_apply(const float (&v)[64], const uint4* st, int row0, uint32_t ep, uint32_t sb, int sec_shift, int sec_scale, uint32_t stg_row, int wg, int lane) {
  uint32_t sc[16], sh[16];
#pragma unroll
  for (int b = 0; b < 2; b++) { load_vec(sc + 8 * b, sb, sec_scale, b, lane); load_vec(sh + 8 * b, sb, sec_shift, b, lane); }
  float n0, r0, n1, r1;
  ln_gather(st, row0, lane, ep, n0, r0, n1, r1);
#pragma unroll
  for (int i = 0; i < 16; i += 2) {
    if (i == 8) { const float z = lds32f(sb + MISC + ZERO); n0 += z; n1 += z; }
    uint32_t w[4];
#pragma unroll
    for (int u = 0; u < 2; u++) {
      int q = i + u;
      w[2 * u] = hfma2(pack2(fmaf(v[4 * q], r0, n0), fmaf(v[4 * q + 1], r0, n0)), sc[q], sh[q]);
      w[2 * u + 1] = hfma2(pack2(fmaf(v[4 * q + 2], r1, n1), fmaf(v[4 * q + 3], r1, n1)), sc[q], sh[q]);
    }
    stsm4(stg_row + (i >> 3) * BLK + ((((i & 7) + (lane >> 4)) ^ (lane & 7)) << 4), w[0], w[1], w[2], w[3]);
    if ((i & 7) == 6) stage_done(sb, wg, i >> 3, lane);
  }
}
__device__ __forceinline__ uint32_t hmul2(uint32_t a, uint32_t b) { uint32_t r; asm("mul.rn.bf16x2 %0, %1, %2;" : "=r"(r) : "r"(a), "r"(b)); return r; }
__device__ __forceinline__ uint32_t silu_mul2(uint32_t g, uint32_t u) {
  const uint32_t h = hmul2(g, 0x3f003f00u);
  const float h0 = bf_lo(h), h1 = bf_hi(h);
  return hmul2(pack2(fmaf(h0, tanh_fast(h0), h0), fmaf(h1, tanh_fast(h1), h1)), u);
}

__device__ __forceinline__ void gemv_fma(float (&a)[8], uint4 w, float s) {
  a[0] = fmaf(bf_lo(w.x), s, a[0]); a[1] = fmaf(bf_hi(w.x), s, a[1]); a[2] = fmaf(bf_lo(w.y), s, a[2]); a[3] = fmaf(bf_hi(w.y), s, a[3]);
  a[4] = fmaf(bf_lo(w.z), s, a[4]); a[5] = fmaf(bf_hi(w.z), s, a[5]); a[6] = fmaf(bf_lo(w.w), s, a[6]); a[7] = fmaf(bf_hi(w.w), s, a[7]);
}
__device__ __forceinline__ float silu_c(float v) { return bf_round(__fdividef(v, 1.f + __expf(-v))); }
__device__ __forceinline__ float mod_gather(const uint2* p, uint32_t ep) {
  uint2 a, b, c, d; uint32_t n = 0;
  while (true) {
    a = ld_rlx2(p); b = ld_rlx2(p + 128); c = ld_rlx2(p + 256); d = ld_rlx2(p + 384);
    if (a.y == ep && b.y == ep && c.y == ep && d.y == ep) break;
    SPIN_GUARD(n);
  }
  return (__uint_as_float(a.x) + __uint_as_float(b.x)) + (__uint_as_float(c.x) + __uint_as_float(d.x));
}
__device__ __forceinline__ void mod_store(uint32_t sb, int sec, int col, float v) {
  v = bf_round(v);
  if (sec == 1 || sec == 4) v += 1.f;
  sts16(sb + MISC + MODV + sec * 256 + (((col >> 1) & 3) * 16 + (col >> 3)) * 4 + (col & 1) * 2, __float2bfloat16_rn(v));
}

__global__ void __cluster_dims__(2, 1, 1) __launch_bounds__(384, 1)
fused_kernel(const bf16* __restrict__ cvec, const bf16* __restrict__ wmod, int by_sm, const __grid_constant__ Maps maps) {
  extern __shared__ __align__(1024) uint8_t smem_raw[];
  const uint32_t sb = smem_u32(smem_raw);
  const int warp = __shfl_sync(~0u, threadIdx.x >> 5, 0), lane = threadIdx.x & 31;
  const int rank = blockIdx.x & 1;
  int cid = (blockIdx.x >> 1) - 2;
  if (by_sm) {
    uint32_t sm; asm("mov.u32 %0, %%smid;" : "=r"(sm));
    const int t = sm >> 1, u = t - 32, gp = t < 32 ? t & 7 : t < 60 ? 1 + u % 7 : 0, idx = t < 32 ? t >> 3 : t < 60 ? 4 + u / 7 : t - 58;
    cid = (t & ~1) == 60 ? t - 62 : ((gp & 1) * 8 + idx) * 4 + (gp >> 1);
  }
  const bool extra = cid < 0;
  const int bid = cid * 2 + rank;
  const int m = cid >> 2, j = (cid & 3) * 2 + rank;
  const uint32_t bar = sb + MISC;

  if (warp >= 8) {
    asm volatile("setmaxnreg.dec.sync.aligned.u32 40;");
    if (extra) {
      if (warp == 8) {
        if (lane == 0) { for (int s = 0; s < 6; s++) { mbar_init(bar + B_FULL6 + s * 8, 1); mbar_init(bar + B_EMPTY6 + s * 8, 8); } fence_async_smem(); }
        __syncwarp();
        asm volatile("bar.arrive 2, 288;" ::: "memory");
        __nanosleep(XSLEEP);
#pragma unroll 1
        for (int it = 0, s = 0, par = 1; it < 64; it++) {
          mbar_wait(bar + B_EMPTY6 + s * 8, par);
          if (elect()) { mbar_expect_tx(bar + B_FULL6 + s * 8, 32768); tma_3d(sb + s * 32768, &maps.wmod, bar + B_FULL6 + s * 8, 0, (it & 15) * 64, 12 + (it >> 4) * 4 + bid); }
          if (++s == 6) { s = 0; par ^= 1; }
        }
      }
    } else if (warp < 10) {
      uint32_t s6 = 0, p6 = 1;
      auto next6 = [&]() { if (++s6 == 6) { s6 = 0; p6 ^= 1; } };
      auto drained4 = [&](int q, int late) { if (q < 5) mbar_wait(bar + B_EMPTY4 + (((late ? 0x10332 : 0x32110) >> (4 * q)) & 3) * 8, 1); };
      auto drained6 = [&](int q) { if (q < 3) mbar_wait(bar + B_EMPTY6 + ((0x154 >> (4 * q)) & 7) * 8, q >> 1); };
      auto skip6 = [&]() { mbar_wait(bar + B_EMPTY6 + s6 * 8, p6); if (elect()) mbar_arrive(bar + B_FULL6 + s6 * 8); next6(); };
      if (warp == 8) {
        const uint32_t t_start = clock();
        if (lane == 0) {
          if (sb & 1023) bail();
          for (int b = 0; b < 2; b++) mbar_init(bar + B_X + b * 8, 1);
          for (int s = 0; s < 4; s++) { mbar_init(bar + B_FULL4 + s * 8, 2); mbar_init(bar + B_EMPTY4 + s * 8, 16); }
          for (int s = 0; s < 6; s++) { mbar_init(bar + B_FULL6 + s * 8, 2); mbar_init(bar + B_EMPTY6 + s * 8, 16); }
          for (int b = 0; b < 2; b++) { mbar_init(bar + B_RDY + b * 8, 8); mbar_init(bar + B_FREE + b * 8, 1); mbar_init(bar + B_HH + b * 8, 1); }
          mbar_init(bar + B_MOD, 1); mbar_init(bar + B_LAG, 4); mbar_init(bar + B_HALO, 2); mbar_init(bar + B_ALL, 1); mbar_init(bar + B_HH2, 1); mbar_init(bar + B_OWN, 8);
          asm volatile("st.shared.u32 [%0], 0;" :: "r"(bar + ZERO) : "memory");
          asm volatile("fence.mbarrier_init.release.cluster;" ::: "memory");
          fence_async_smem();
        }
        __syncwarp();
        cl_arrive_relaxed();
        auto wide = [&](int s, int par, const CUtensorMap* m0, int a0, const CUtensorMap* m1, int a1, int kb) {
          const uint32_t full = bar + B_FULL4 + s * 8, d = sb + s * 49152 + BLK;
          mbar_wait(full + 32, par);
          if (elect()) { mbar_expect_tx(full, 2 * BLK); tma_3d(d, m0, full, 0, kb * 64, a0); tma_3d(d + BLK, m1, full, 0, kb * 64, a1); }
        };
        auto narrow = [&](const CUtensorMap* m0, int kb) {
          const uint32_t full = bar + B_FULL6 + s6 * 8;
          mbar_wait(full + 48, p6);
          if (elect()) { mbar_expect_tx(full, BLK); tma_3d(sb + s6 * 32768 + BLK, m0, full, 0, kb * 64, 2 * j); }
          next6();
        };
#pragma unroll 1
        for (int it = 0; it < 16; it++) {
          if (it == 0) {
            while ((uint32_t)clock() - t_start < XDELAY) {}
            if (elect()) for (int b = 0; b < 2; b++) { mbar_expect_tx(bar + B_X + b * 8, BLK); tma_3d(sb + STG + b * BLK, &maps.x, bar + B_X + b * 8, j * 128 + b * 64, m * 64, 0); }
            mbar_wait(bar + B_X + 8, 0);
          }
          wide(it & 3, ~(it >> 2) & 1, &maps.wqkv, 16 + 2 * j, &maps.wqkv, 32 + 2 * j, own_order(it, j));
        }
#pragma unroll 1
        for (int it = 0; it < 16; it++) { drained4(it, 0); narrow(&maps.wqkv, it); }
#pragma unroll 1
        for (int it = 0; it < 16; it++) {
          narrow(&maps.wo, own_order(it, j));
          if (it == 10) {
            mbar_wait(bar + B_OWN, 1); mbar_wait(bar + B_FREE + 8, 1);
            if (elect()) for (int b = 0; b < 2; b++) { mbar_expect_tx(bar + B_X + b * 8, BLK); tma_3d(sb + STG + b * BLK, &maps.x, bar + B_X + b * 8, j * 128 + b * 64, m * 64, 0); }
          }
        }
        skip6();
#pragma unroll 1
        for (int it = 0; it < 48; it++) {
          const int s = (it + 2) & 3, par = ~(it >> 2) & 1;
          drained6(it);
          wide(s, par, &maps.w1, (it & 48) + 2 * j, &maps.w3, (it & 48) + 2 * j, it < 16 ? own_order(it, j) : it & 15);
          if (it >= 44) {
            if (it == 44) { mbar_wait(bar + B_FREE, 0); mbar_wait(bar + B_FREE + 8, 0); if (elect()) mbar_expect_tx(bar + B_X, 2 * BLK); }
            if (elect()) bulk_ld(sb + STG + (it - 44) * HALF, g_x1 + bid * 2048 + (it - 44) * 512, HALF, bar + B_X);
          }
        }
#pragma unroll 1
        for (int it = 0; it < 16; it++) {
          const uint32_t full = bar + B_FULL6 + s6 * 8, d = sb + s6 * 32768 + BLK;
          drained4(it, 1);
          mbar_wait(full + 48, p6);
          if (elect()) { mbar_expect_tx(full, BLK); tma_3d(d, &maps.w1s, full, 0, it * 64, 48 + j); tma_3d(d + HALF, &maps.w3s, full, 0, it * 64, 48 + j); }
          next6();
        }
#pragma unroll 1
        for (int it = 0; it < 56; it++) narrow(&maps.w2, it);
      } else {
        if (lane < 9) prefetch_map(&maps.x + lane);
        const uint32_t ep = g_epoch[bid + 4] + 1;
        cl_arrive_relaxed(); cl_wait();
        auto plain = [&](uint32_t full, uint32_t empty, int par, uint32_t slot, const uint4* blk) {
          mbar_wait(empty, par);
          if (elect()) { mbar_expect_tx(full, BLK); bulk_ld_mc(slot + rank * HALF, blk + rank * 512, HALF, full); }
        };
        auto plain6 = [&](const uint4* blk) { plain(bar + B_FULL6 + s6 * 8, bar + B_EMPTY6 + s6 * 8, p6, sb + s6 * 32768, blk); next6(); };
        uint32_t ready = 0;
        auto poll = [&](int e) { ready = __ballot_sync(~0u, ld_acquire(g_flag + m * 128 + e * 16 + (lane & 15)) == ep); };
        auto need = [&](int e, uint32_t mask) {
          if ((ready & mask) != mask) {
            uint32_t n = 0;
            do { poll(e); SPIN_GUARD(n); } while ((ready & mask) != mask);
            fence_async_global();
          }
        };
        auto fresh = [&](int e, int it, uint32_t full, uint32_t empty, int par, uint32_t slot, uint4* src) {
          if (it >= 4) {
            const int kb = own_order(it, j);
            if (it < 10) need(e, 1u << kb); else if (it == 10) mbar_wait(bar + B_ALL, e & 1);
            plain(full, empty, par, slot, src + kb * 1024);
          } else {
            if (it == 0) { poll(e); ready = 0; }
            mbar_wait(empty, par);
            if (it < 2) { if (elect()) mbar_arrive(full); }
            else {
              const int b = it & 1;
              const uint32_t to_peer = mapa(sb, rank ^ 1) - sb;
              if (elect()) mbar_expect_tx(full, BLK);
              mbar_wait(bar + (b ? B_FREE + 8 : B_RDY), e & 1);
              if (b == 0) TR(e == 0 ? 24 : e == 2 ? 30 : 44);
              if (elect()) {
                if (b == 0) {
                  bulk_st(src + 2 * j * 1024, sb + STG, BLK);
                  bulk_commit();
                  bulk_wait_all();
                  mbar_arrive(bar + B_FREE);
                }
                fence_async_global();
                bulk_ld(slot + to_peer, src + (2 * j + b) * 1024, BLK, full + to_peer);
              }
              __syncwarp();
            }
          }
          if (it == 4) TR(e == 0 ? 28 : e == 1 ? 46 : 34);
        };
#pragma unroll 1
        for (int ph = 0; ph < 2; ph++) {
          uint4* h = g_h + m * 16384;
#pragma unroll 1
          for (int it = 0; it < 16; it++) {
            const int s = (it + 2 * ph) & 3;
            if (ph) drained6(it);
            fresh(2 * ph, it, bar + B_FULL4 + s * 8, bar + B_EMPTY4 + s * 8, ~(it >> 2) & 1, sb + s * 49152, h);
          }
          if (ph) {
#pragma unroll 1
            for (int it = 16; it < 48; it++) {
              const int s = (it + 2) & 3;
              const uint32_t full = bar + B_FULL4 + s * 8;
              plain(full, full + 32, ~(it >> 2) & 1, sb + s * 49152, h + (it & 15) * 1024);
            }
          }
#pragma unroll 1
          for (int it = 0; it < 16; it++) { drained4(it, ph); plain6(h + it * 1024); }
          if (!ph) {
#pragma unroll 1
            for (int it = 0; it < 16; it++) { fresh(1, it, bar + B_FULL6 + s6 * 8, bar + B_EMPTY6 + s6 * 8, p6, sb + s6 * 32768, g_o + m * 16384); next6(); }
            skip6();
          }
        }
#pragma unroll 1
        for (int it = 0; it < 56; it++) {
          if (it == 0 || it == 32 || it == 48) mbar_wait(bar + (it == 48 ? B_HH2 : B_HH + (it >> 2)), 0);
          plain6(g_hh + m * 57344 + it * 1024);
        }
      }
    } else {
      const int b = warp - 10;
      const uint32_t ep = g_epoch[bid + 4] + 1;
      const uint32_t stg = sb + STG + b * BLK;
      cl_arrive_relaxed(); cl_wait();
      auto all_there = [&](int u, uint32_t done) {
        const uint32_t* fl = g_flag + u;
        uint32_t n = 0;
        while (!__all_sync(~0u, ld_acquire(fl) == ep)) { __nanosleep(100); SPIN_GUARD(n); }
        fence_async_global();
        if (lane == 0) mbar_arrive(done);
      };
      auto fetch_mod = [&](int sec) {
        const uint4* p = (const uint4*)(g_modv + (sec - 2) * 1024 + j * 128) + lane;
        uint4 v0, v1; uint32_t n = 0;
        while (true) {
          v0 = ld_rlx4(p); v1 = ld_rlx4(p + 32);
          if (v0.y == ep && v0.w == ep && v1.y == ep && v1.w == ep) break;
          SPIN_GUARD(n);
        }
        mod_store(sb, sec, 2 * lane, __uint_as_float(v0.x)); mod_store(sb, sec, 2 * lane + 1, __uint_as_float(v0.z));
        mod_store(sb, sec, 64 + 2 * lane, __uint_as_float(v1.x)); mod_store(sb, sec, 65 + 2 * lane, __uint_as_float(v1.z));
        __syncwarp();
      };
#pragma unroll 1
      for (int e = 0; e < 7 - b; e++) {
        if (lane == 0) {
          if (e < 3) {
            mbar_wait(bar + B_FREE, e & 1);
            if (b) {
              mbar_wait(bar + B_RDY + 8, e & 1);
              bulk_st((e == 1 ? g_o : g_h) + m * 16384 + (2 * j + 1) * 1024, stg, BLK);
              bulk_commit();
              bulk_wait_all();
              mbar_arrive(bar + B_FREE + 8);
              TR(53 + e);
            }
            st_release(g_flag + m * 128 + e * 16 + 2 * j + b, ep);
            TR((e == 0 ? 26 : e == 2 ? 32 : 42) + b);
          } else {
            const int kb = (e < 6 ? 2 * (8 * (e - 3) + j) : 48 + j) + b;
            mbar_wait(bar + B_RDY + b * 8, e & 1);
#pragma unroll 1
            for (int q = 0; q < NPIECE; q++) { if (q) __nanosleep(PSLEEP); bulk_st(g_hh + m * 57344 + kb * 1024 + q * (1024 / NPIECE), stg + q * (BLK / NPIECE), BLK / NPIECE); }
            bulk_commit();
            bulk_wait_all();
            mbar_arrive(bar + B_FREE + b * 8);
            st_release(g_flag + m * 128 + U_HH + kb, ep);
          }
        }
        __syncwarp();
        if (e < 3 && b) all_there(m * 128 + e * 16 + (lane & 15), bar + B_ALL);
        if (e == 4 && b) all_there(m * 128 + U_HH + lane, bar + B_HH);
        if (!b && (e == 1 || e == 2)) {
#pragma unroll 1
          for (int sec = e == 1 ? 2 : 5; sec < 4 + e; sec++) fetch_mod(sec);
          if (e == 1) { if (lane == 0) mbar_arrive(bar + B_MOD); TR(50); }
        }
        if (e == 0) {
          mbar_wait(bar + B_EMPTY6 + 24, 0);
          if (HSLEEP) __nanosleep(HSLEEP);
#pragma unroll 1
          for (int w = 0; w < 4; w++) {
            const uint4* hp = g_halo + ((m * 8 + j) * 2 + (w & 1)) * 512 + b * 256 + (w >> 1) * 128 + lane;
            uint4 q[4] = {}; uint32_t n = 0;
            while (m > 0) {
              bool ok = true;
#pragma unroll
              for (int i = 0; i < 4; i++) q[i] = ld_rlx4(hp + i * 32);
#pragma unroll
              for (int i = 0; i < 4; i++) ok = ok && q[i].y == ep && q[i].w == ep;
              if (ok) break;
              SPIN_GUARD(n);
            }
#pragma unroll
            for (int i = 0; i < 2; i++) sts128(stg + lane * 16 + (w & 1) * HALF + (w >> 1) * 1024 + i * 512, q[2 * i].x, q[2 * i + 1].x, q[2 * i].z, q[2 * i + 1].z);
          }
          __syncwarp();
          if (lane == 0) mbar_arrive(bar + B_HALO);
          if (b == 0) TR(52);
        }
      }
      if (b) { all_there(m * 128 + U_HH + 32 + (lane & 15), bar + B_HH + 8); all_there(m * 128 + U_HH + 48 + (lane & 7), bar + B_HH2); }
    }
  } else {
    const int wg = warp >> 2, wq = warp & 3, tid = threadIdx.x;
    const int g = lane >> 2, c = lane & 3;
    const int sec0 = (m >> 1) & 1, hf0 = m & 1, ks0 = (m >> 2) & 3;
    uint4 wv[8];
    uint32_t ep0; uint16_t cv_;
    asm volatile("ld.global.nc.u16 %0, [%1];" : "=h"(cv_) : "l"(cvec + ks0 * 256 + warp * 32 + lane));
    asm volatile("ld.global.u32 %0, [%1];" : "=r"(ep0) : "l"(g_epoch + bid + 4));
    if (!extra) {
      const bf16* wp = wmod + (size_t)(ks0 * 256 + warp * 32 + (lane >> 3)) * 6144 + sec0 * 1024 + j * 128 + hf0 * 64 + (lane & 7) * 8;
#pragma unroll
      for (int i = 0; i < 8; i++) wv[i] = ldg_nc(wp + (size_t)i * 4 * 6144);
    }
    asm volatile("setmaxnreg.inc.sync.aligned.u32 232;" ::: "memory");
    if (__builtin_expect(extra, 0)) {
      const uint32_t ep = ep0 + 1;
      float sv[4];
#pragma unroll
      for (int p = 0; p < 4; p++) sv[p] = silu_c(__bfloat162float(cvec[64 * (4 * p + (lane >> 3)) + 8 * warp + (lane & 7)]));
      named_bar(2, 288);
      int s = 0, par = 0;
#pragma unroll 1
      for (int sec = 0; sec < 4; sec++) {
        float a[8] = {0, 0, 0, 0, 0, 0, 0, 0};
#pragma unroll 1
        for (int it = 0; it < 16; it++) {
          const float sc = it < 4 ? sv[0] : it < 8 ? sv[1] : it < 12 ? sv[2] : sv[3];
          mbar_wait(bar + B_FULL6 + s * 8, par);
          uint4 w[8];
#pragma unroll
          for (int i = 0; i < 8; i++) w[i] = lds128(sb + s * 32768 + (warp * 8 + i) * 512 + lane * 16);
#pragma unroll
          for (int i = 0; i < 8; i++) gemv_fma(a, w[i], __shfl_sync(~0u, sc, (it & 3) * 8 + i));
          if (lane == 0) mbar_arrive(bar + B_EMPTY6 + s * 8);
          if (++s == 6) { s = 0; par ^= 1; }
        }
        const uint32_t red = sb + STG + sec * 8192;
        sts128(red + warp * 1024 + lane * 32, __float_as_uint(a[0]), __float_as_uint(a[1]), __float_as_uint(a[2]), __float_as_uint(a[3]));
        sts128(red + warp * 1024 + lane * 32 + 16, __float_as_uint(a[4]), __float_as_uint(a[5]), __float_as_uint(a[6]), __float_as_uint(a[7]));
        named_bar(1, 256);
        float t = 0;
#pragma unroll
        for (int q = 0; q < 8; q++) t += lds32f(red + q * 1024 + tid * 4);
        st_rlx2(g_modv + sec * 1024 + (bid + 4) * 256 + tid, __float_as_uint(t), ep);
      }
      if (tid == 0) g_epoch[bid + 4] = ep;
      return;
    }
    if (warp == 0) TR(0);
    const int row0 = wg * 64 + wq * 16 + g;
    if (c < 2) st_rlx4(g_stat + m * 1024 + j * 128 + row0 + c * 8, 0, 0, 0, 0);
    if (tid < 64) st_rlx2(g_modp + ((j * 2 + sec0) * 4 + ks0) * 128 + hf0 * 64 + tid, 0, 0);
    cl_arrive_relaxed(); cl_wait();
    uint32_t ep;
    asm volatile("add.u32 %0, %1, 1;" : "=r"(ep) : "r"(ep0) : "memory");
    const float sc_ = silu_c(__uint_as_float((uint32_t)cv_ << 16));
    const uint32_t rel = mapa(bar, (lane & 1) ^ rank);
    const uint32_t stg_row = sb + STG + (wg * 64 + wq * 16 + (lane & 15)) * 128;
    const uint32_t fre = bar + B_FREE;
    Ring r4{0, 0, 0}, r6{0, 0, 0};
    auto none = [](auto) {};
    {
      float a[8] = {0, 0, 0, 0, 0, 0, 0, 0};
#pragma unroll
      for (int i = 0; i < 8; i++) gemv_fma(a, wv[i], __shfl_sync(~0u, sc_, i * 4 + (lane >> 3)));
#pragma unroll
      for (int i = 0; i < 8; i++) { a[i] += __shfl_xor_sync(~0u, a[i], 8); a[i] += __shfl_xor_sync(~0u, a[i], 16); }
      if (lane < 8) {
        sts128(sb + RED_OFF + warp * 256 + lane * 32, __float_as_uint(a[0]), __float_as_uint(a[1]), __float_as_uint(a[2]), __float_as_uint(a[3]));
        sts128(sb + RED_OFF + warp * 256 + lane * 32 + 16, __float_as_uint(a[4]), __float_as_uint(a[5]), __float_as_uint(a[6]), __float_as_uint(a[7]));
      }
      named_bar(1, 256);
      if (tid < 64) {
        float s = 0;
#pragma unroll
        for (int w = 0; w < 8; w++) s += lds32f(sb + RED_OFF + w * 256 + tid * 4);
        st_rlx2(g_modp + ((j * 2 + sec0) * 4 + ks0) * 128 + hf0 * 64 + tid, __float_as_uint(s), ep);
      }
      if (warp == 0) TR(1);
      float v[64];
      mbar_wait(bar + B_X, 0); mbar_wait(bar + B_X + 8, 0);
#pragma unroll
      for (int i = 0; i < 16; i += 2) {
        uint32_t w0, w1, w2, w3;
        ldsm4(stg_row + (i >> 3) * BLK + ((((i & 7) + (lane >> 4)) ^ (lane & 7)) << 4), w0, w1, w2, w3);
        v[4 * i] = bf_lo(w0); v[4 * i + 1] = bf_hi(w0); v[4 * i + 2] = bf_lo(w1); v[4 * i + 3] = bf_hi(w1);
        v[4 * i + 4] = bf_lo(w2); v[4 * i + 5] = bf_hi(w2); v[4 * i + 6] = bf_lo(w3); v[4 * i + 7] = bf_hi(w3);
      }
      ln_publish(v, g_stat + m * 1024, j, row0, lane, ep);
      if (warp == 0) TR(2);
      mod_store(sb, tid >> 7, tid & 127, mod_gather(g_modp + (j * 2 + (tid >> 7)) * 512 + (tid & 127), ep));
      named_bar(1, 256);
      if (warp == 0) TR(3);
      ln_apply(v, g_stat + m * 1024, row0, ep, sb, 0, 1, stg_row, wg, lane);
      named_bar(2 + wg, 128);
    }
    if (warp == 0) TR(4);
    {
      uint32_t kf[32], vf[32], pv[32];
      const bool first = wq == 0 && m == 0;
      const uint32_t xa = sb + STG + wg * HALF + wq * 2048 + lane * 16;
      {
        float acc[128];
        mainloop<256, 4, 0>(acc, 16, true, r4, sb, wg, lane, rel, bid * 192 + 0, none, none, [&] {
          mbar_wait(fre + 8, 0);
          if (c < 2) st_rlx4(g_stat + (16 + m) * 1024 + j * 128 + row0 + c * 8, 0, 0, 0, 0);
        });
        if (warp == 0) TR(5);
#pragma unroll
        for (int i = 0; i < 32; i++) { kf[i] = pack2(acc[2 * i], acc[2 * i + 1]); vf[i] = pack2(acc[64 + 2 * i], acc[65 + 2 * i]); }
      }
      if (warp == 0) TR(6);
      float acc[64];
      constexpr int QP = 2;
      mainloop<128, 6, 8 / QP>(acc, 16, false, r6, sb, wg, lane, rel, bid * 192 + 16, [&](auto ic) {
        constexpr int q = (ic.v - 1) * QP;
#pragma unroll
        for (int i = 4 * q; i < 4 * (q + QP); i++) vf[i] = movm(vf[i]);
        if (wq == 3) {
          if (m < 15) {
            uint4* hp = g_halo + (((m + 1) * 8 + j) * 2 + wg) * 512 + lane;
#pragma unroll
            for (int i = 2 * q; i < 2 * (q + QP); i++) st_rlx4(hp + i * 32, kf[2 * i + 1], ep, vf[2 * i + 1], ep);
          }
        } else {
#pragma unroll
          for (int i = q; i < q + QP; i++) sts128(xa + 2048 + (i >> 2) * BLK + (i & 3) * 512, kf[4 * i + 1], kf[4 * i + 3], vf[4 * i + 1], vf[4 * i + 3]);
        }
      }, none, [&] {
        named_bar(2 + wg, 128);
        if (wq == 0) mbar_wait(bar + B_HALO, 0);
#pragma unroll
        for (int i = 0; i < 8; i++) {
          uint4 q = lds128(xa + (i >> 2) * BLK + (i & 3) * 512);
          pv[4 * i] = q.x; pv[4 * i + 1] = q.y; pv[4 * i + 2] = q.z; pv[4 * i + 3] = q.w;
        }
        __syncwarp();
      });
      if (warp == 0) TR(7);
      int gz = g;
#pragma unroll
      for (int b = 0; b < 2; b++) {
        const bool up0 = 2 * c > gz, up1 = 2 * c + 1 > gz;
        const uint32_t mup = (up0 ? 0xffffu : 0u) | (up1 ? 0xffff0000u : 0u);
        float l[2][4], mx[4];
#pragma unroll
        for (int h = 0; h < 2; h++) {
          uint32_t q[8];
          const int k = 16 * b + 8 * h;
#pragma unroll
          for (int i = 0; i < 8; i++) q[i] = pack2(acc[2 * k + 2 * i], acc[2 * k + 2 * i + 1]);
          float s0[4], s1[4], s2[4];
          mma16z(s0, q[0], q[1], q[2], q[3], pv[k], pv[k + 1]); mma16z(s1, q[0], q[1], q[2], q[3], kf[k], kf[k + 2]); mma16z(s2, q[0], q[1], q[2], q[3], kf[k + 1], kf[k + 3]);
          mma16(s0, q[4], q[5], q[6], q[7], pv[k + 4], pv[k + 5]); mma16(s1, q[4], q[5], q[6], q[7], kf[k + 4], kf[k + 6]); mma16(s2, q[4], q[5], q[6], q[7], kf[k + 5], kf[k + 7]);
          if (first) { s0[0] = -INFINITY; s0[1] = -INFINITY; }
          l[h][0] = up0 ? s0[0] : s1[0]; l[h][1] = up1 ? s0[1] : s1[1]; l[h][2] = up0 ? s1[2] : s2[2]; l[h][3] = up1 ? s1[3] : s2[3];
          mx[2 * h] = fmaxf(l[h][0], l[h][1]); mx[2 * h + 1] = fmaxf(l[h][2], l[h][3]);
        }
#pragma unroll
        for (int o = 1; o < 4; o <<= 1) {
#pragma unroll
          for (int h = 0; h < 4; h++) mx[h] = fmaxf(mx[h], __shfl_xor_sync(~0u, mx[h], o));
        }
#pragma unroll
        for (int h = 0; h < 2; h++) {
          const float n0 = -mx[2 * h] * SCL, n1 = -mx[2 * h + 1] * SCL;
          const uint32_t pa = pack2(ex2(fmaf(l[h][0], SCL, n0)), ex2(fmaf(l[h][1], SCL, n0))), pb = pack2(ex2(fmaf(l[h][2], SCL, n1)), ex2(fmaf(l[h][3], SCL, n1)));
          float sm[4];
          mma8z(sm, pa, pb, 0x3f803f80u);
          const float ia = rcp(sm[0]), ib = rcp(sm[2]);
#pragma unroll
          for (int i = 8 * b + 4 * h; i < 8 * b + 4 * h + 4; i += 2) {
            uint32_t of[4];
#pragma unroll
            for (int d = 0; d < 2; d++) {
              float o[4];
              mma16z(o, pa & ~mup, pb & mup, 0u, pb & ~mup, vf[2 * (i + d)], vf[2 * (i + d) + 1]);
              mma8(o, pa & mup, 0u, pv[2 * i + 2 + d]);
              of[2 * d] = pack2(o[0] * ia, o[1] * ia); of[2 * d + 1] = pack2(o[2] * ib, o[3] * ib);
            }
            stsm4(stg_row + b * BLK + ((((i & 7) + (lane >> 4)) ^ (lane & 7)) << 4), of[0], of[1], of[2], of[3]);
          }
        }
        stage_done(sb, wg, b, lane);
        if (b == 0) gz += __float_as_uint(lds32f(bar + ZERO));
      }
      named_bar(1, 256);
      if (warp == 0) TR(8);
    }
    uint32_t pk[64];
    {
      float acc[64];
      mainloop<128, 6, 0>(acc, 16, true, r6, sb, wg, lane, rel, bid * 192 + 32, none, none, [&] {
        mbar_wait(bar + B_MOD, 0); mbar_wait(bar + B_X, 1); mbar_wait(bar + B_X + 8, 1);
        load_vec(pk + 32, sb, 2, 0, lane); load_vec(pk + 40, sb, 2, 1, lane);
#pragma unroll
        for (int i = 0; i < 16; i += 2) ldsm4(stg_row + (i >> 3) * BLK + ((((i & 7) + (lane >> 4)) ^ (lane & 7)) << 4), pk[2 * i], pk[2 * i + 1], pk[2 * i + 2], pk[2 * i + 3]);
      });
      if (warp == 0) TR(9);
#pragma unroll
      for (int i = 0; i < 32; i++) {
        acc[2 * i] = fmaf(acc[2 * i], bf_lo(pk[32 + (i >> 1)]), bf_lo(pk[i]));
        acc[2 * i + 1] = fmaf(acc[2 * i + 1], bf_hi(pk[32 + (i >> 1)]), bf_hi(pk[i]));
      }
      ln_publish(acc, g_stat + (16 + m) * 1024, j, row0, lane, ep);
      if (warp == 0) TR(36);
      mbar_wait(bar + B_FULL6 + 16, 1);
      if (lane < 2) mbar_arrive_cl(rel + B_EMPTY6 + 16);
      ring_next<6>(r6);
#pragma unroll
      for (int i = 0; i < 32; i++) { pk[i] = pack2(acc[2 * i], acc[2 * i + 1]); pk[32 + i] = 0; }
      ln_apply(acc, g_stat + (16 + m) * 1024, row0, ep, sb, 3, 4, stg_row, wg, lane);
      named_bar(2 + wg, 128);
      if (warp == 0) TR(11);
    }
    auto swiglu = [&](int q, int uo, int par) {
      if ((q & 3) == 0 && par >= 0) mbar_wait(fre + 2 * q, par);
      uint32_t w[4];
#pragma unroll
      for (int u = 0; u < 4; u++) w[u] = silu_mul2(pk[4 * q + u], pk[uo + 4 * q + u]);
      stsm4(stg_row + (q >> 2) * BLK + ((((2 * q & 7) + (lane >> 4)) ^ (lane & 7)) << 4), w[0], w[1], w[2], w[3]);
    };
    r4.s = r4.wrap = 2;
#pragma unroll 1
    for (int t = 0; t < 3; t++) {
      float acc[128];
      mainloop<256, 4, 5>(acc, 16, t == 0, r4, sb, wg, lane, rel, bid * 192 + 48 + 16 * t, [&](auto ic) {
        if (t) {
          if (ic.v == 3 || ic.v == 5) stage_done(sb, wg, ic.v >> 2, lane);
          if (ic.v < 5) { swiglu(2 * ic.v - 2, 32, ~t & 1); swiglu(2 * ic.v - 1, 32, 0); }
        }
      }, [&](int it) {
#pragma unroll
        for (int i = 0; i < 8; i++)
          if (t == 0 && it == 6 + i) g_x1[bid * 2048 + (i >> 2) * 1024 + warp * 128 + (i & 3) * 32 + lane] = make_uint4(pk[4 * i], pk[4 * i + 1], pk[4 * i + 2], pk[4 * i + 3]);
      }, [&] { if (t == 0) fence_async_global(); else if (t == 2) mbar_wait(bar + B_X, 0); });
      if (warp == 0) TR(12 + 2 * t);
#pragma unroll
      for (int i = 0; i < 64; i++) pk[i] = pack2(acc[2 * i], acc[2 * i + 1]);
      if (warp == 0) TR(13 + 2 * t);
    }
    uint32_t x1[32];
    {
      float acc[64];
      mainloop<128, 6, 12>(acc, 16, false, r6, sb, wg, lane, rel, bid * 192 + 96, [&](auto ic) {
        constexpr int b = ic.v > 6, q = ic.v - 6 * b;
        if (q == 1) {
#pragma unroll
          for (int i = 4 * b; i < 4 * b + 4; i++) { const uint4 x = lds128(sb + STG + b * BLK + warp * 2048 + (i & 3) * 512 + lane * 16); x1[4 * i] = x.x; x1[4 * i + 1] = x.y; x1[4 * i + 2] = x.z; x1[4 * i + 3] = x.w; }
          __syncwarp();
        } else if (q < 6) swiglu(4 * b + q - 2, 32, -1);
        else stage_done(sb, wg, b, lane);
      }, none, [] {});
      if (warp == 0) TR(18);
#pragma unroll
      for (int i = 0; i < 32; i++) pk[i] = pack2(acc[2 * i], acc[2 * i + 1]);
      if (warp == 0) TR(19);
    }
    {
      float acc[64];
      mainloop<128, 6, 5>(acc, 56, false, r6, sb, wg, lane, rel, bid * 192 + 112, [&](auto ic) {
        if (ic.v == 5) stage_done(sb, wg, 0, lane); else swiglu(ic.v - 1, 16, 1);
      }, none, [&] {
        if (TAILLAG && wg == 0 && lane == 0) mbar_arrive(bar + B_LAG);
        load_vec(pk + 32, sb, 5, 0, lane); load_vec(pk + 40, sb, 5, 1, lane);
        mbar_wait(fre, 0); mbar_wait(fre + 8, 1);
      });
      __syncwarp();
      cl_arrive_relaxed();
      if (warp == 0) TR(20);
#pragma unroll
      for (int i = 0; i < 16; i += 2) {
        uint32_t w[4];
#pragma unroll
        for (int u = 0; u < 4; u++) {
          const int q = 2 * i + u;
          w[u] = pack2(fmaf(acc[2 * q], bf_lo(pk[32 + (q >> 1)]), bf_lo(x1[q])), fmaf(acc[2 * q + 1], bf_hi(pk[32 + (q >> 1)]), bf_hi(x1[q])));
        }
        stsm4(stg_row + (i >> 3) * BLK + ((((i & 7) + (lane >> 4)) ^ (lane & 7)) << 4), w[0], w[1], w[2], w[3]);
        if ((i & 7) == 6) {
          fence_async_smem();
          named_bar(2 + wg, 128);
          if (wq == 0 && elect()) { tma_store_3d(&maps.out, sb + STG + (i >> 3) * BLK + wg * HALF, j * 128 + (i >> 3) * 64, m * 64, wg); bulk_commit(); }
          if (i < 8) x1[16] |= __float_as_uint(lds32f(bar + ZERO));
        }
      }
      if (wq == 0) bulk_wait_read();
      if (wq == 0) TR(40 + wg);
      if (tid == 0) g_epoch[bid + 4] = ep;
      if (warp == 0) TR(21);
      cl_wait();
    }
  }
}

typedef CUresult (*EncodeFn)(CUtensorMap*, CUtensorMapDataType, cuuint32_t, void*, const cuuint64_t*, const cuuint64_t*, const cuuint32_t*, const cuuint32_t*,
                             CUtensorMapInterleave, CUtensorMapSwizzle, CUtensorMapL2promotion, CUtensorMapFloatOOBfill);

void make_map(EncodeFn fn, CUtensorMap* mp, const void* base, uint64_t d0, uint64_t d1, uint64_t d2, uint64_t s1, uint64_t s2, uint32_t b2, uint32_t b0 = 64) {
  cuuint64_t d[3] = {d0, d1, d2}, s[2] = {s1, s2};
  cuuint32_t b[3] = {b0, 64, b2}, e[3] = {1, 1, 1};
  fn(mp, CU_TENSOR_MAP_DATA_TYPE_BFLOAT16, 3, (void*)base, d, s, b, e, CU_TENSOR_MAP_INTERLEAVE_NONE, b0 == 64 ? CU_TENSOR_MAP_SWIZZLE_128B : CU_TENSOR_MAP_SWIZZLE_NONE,
     CU_TENSOR_MAP_L2_PROMOTION_L2_128B, CU_TENSOR_MAP_FLOAT_OOB_FILL_NONE);
}

__global__ void probe_kernel() {}
int max_clusters(int size) {
  cudaLaunchConfig_t cfg = {};
  cudaLaunchAttribute at;
  at.id = cudaLaunchAttributeClusterDimension; at.val.clusterDim.x = size; at.val.clusterDim.y = 1; at.val.clusterDim.z = 1;
  cfg.gridDim = dim3(size * 66); cfg.blockDim = dim3(384); cfg.dynamicSmemBytes = SMEM_BYTES; cfg.attrs = &at; cfg.numAttrs = 1;
  int n = 0;
  if (cudaOccupancyMaxActiveClusters(&n, probe_kernel, &cfg) != cudaSuccess) { cudaGetLastError(); return 0; }
  return n;
}

}

extern "C" void kernel_launch(void* const* d_in, const int* in_sizes, int n_in, void* d_out, int out_size) {
  static EncodeFn fn = nullptr;
  static int by_sm = 0;
  if (!fn) {
    void* p = nullptr; cudaDriverEntryPointQueryResult q;
    cudaGetDriverEntryPoint("cuTensorMapEncodeTiled", &p, cudaEnableDefault, &q);
    fn = (EncodeFn)p;
    cudaFuncSetAttribute(fused_kernel, cudaFuncAttributeMaxDynamicSharedMemorySize, SMEM_BYTES);
    int dev = 0, sms = 0;
    cudaGetDevice(&dev);
    cudaDeviceGetAttribute(&sms, cudaDevAttrMultiProcessorCount, dev);
    cudaFuncSetAttribute(probe_kernel, cudaFuncAttributeMaxDynamicSharedMemorySize, SMEM_BYTES);
    by_sm = BYSM && sms == 132 && max_clusters(2) == 66 && max_clusters(4) == 30 && max_clusters(6) == 17 && max_clusters(8) == 15;
  }
  Maps mp;
  make_map(fn, &mp.x, d_in[0], D_, S_ / 2, 2, 4096, 2048, 2);
  make_map(fn, &mp.out, d_out, D_, S_ / 2, 2, 4096, 2048, 1);
  make_map(fn, &mp.wqkv, d_in[1], 64, D_, 3 * D_ / 64, 3 * D_ * 2, 128, 2);
  make_map(fn, &mp.wo, d_in[2], 64, D_, D_ / 64, D_ * 2, 128, 2);
  make_map(fn, &mp.w1, d_in[4], 64, D_, F_ / 64, F_ * 2, 128, 2);
  make_map(fn, &mp.w3, d_in[5], 64, D_, F_ / 64, F_ * 2, 128, 2);
  make_map(fn, &mp.w1s, d_in[4], 64, D_, F_ / 64, F_ * 2, 128, 1);
  make_map(fn, &mp.w3s, d_in[5], 64, D_, F_ / 64, F_ * 2, 128, 1);
  make_map(fn, &mp.w2, d_in[6], 64, F_, D_ / 64, D_ * 2, 128, 2);
  make_map(fn, &mp.wmod, d_in[8], 256, D_, 24, 6 * D_ * 2, 512, 1, 256);
  fused_kernel<<<132, 384, SMEM_BYTES>>>((const bf16*)d_in[7], (const bf16*)d_in[8], by_sm, mp);
}
```

```cpp
#include <cuda_runtime.h>
#include <cuda_bf16.h>
#include <cuda.h>
#include <stdint.h>

typedef __nv_bfloat16 bf16;

#define NPIECE 4
#define PSLEEP 300
#define XSLEEP 4000
#define XDELAY 2500
#define TAILLAG 5
#define HSLEEP 400
#define BYSM 1
namespace {

constexpr int S_ = 2048, D_ = 1024, F_ = 3584;
constexpr int BLK = 16384;
constexpr int HALF = 8192;
constexpr int RING = 196608;
constexpr int STG = RING;
constexpr int MISC = RING + 2 * BLK;
constexpr int SMEM_BYTES = MISC + 3072;
constexpr int B_FULL4 = 0, B_EMPTY4 = 32, B_FULL6 = 64, B_EMPTY6 = 112, B_RDY = 160, B_FREE = 176, B_LAG = 192, B_X = 208, B_MOD = 224, B_HALO = 232, B_OWN = 240, B_HH = 256, B_ALL = 272, B_HH2 = 288, ZERO = 296;
constexpr int MODV = 512;
constexpr int RED_OFF = 0;
constexpr float SCL = 0.17677669529663687f * 1.4426950408889634f;
constexpr int U_HH = 64;

struct Maps { CUtensorMap x, out, wqkv, wo, w1, w3, w1s, w3s, w2, wmod; };

struct Scratch {
  uint4 h[16 * 16 * 1024];
  uint4 o[16 * 16 * 1024];
  uint4 hh[16 * 56 * 1024];
  uint4 x1[128 * 8 * 256];
  uint4 stat[2 * 16 * 8 * 128];
  uint4 halo[16 * 8 * 2 * 512];
  uint2 modp[8 * 2 * 4 * 128];
  uint2 modv[4 * 1024];
  uint32_t flag[16 * 128];
  uint32_t epoch[132];
};
__device__ __align__(1024) Scratch g_scratch;
#define TR(i)
#define TRS(i)

__device__ __forceinline__ void bail() { asm volatile("st.global.u32 [%0], %1;" :: "l"(0ull), "r"(0) : "memory"); }
__device__ __forceinline__ uint32_t smem_u32(const void* p) { return (uint32_t)__cvta_generic_to_shared(p); }
__device__ __forceinline__ void mbar_init(uint32_t bar, uint32_t cnt) { asm volatile("mbarrier.init.shared::cta.b64 [%0], %1;" :: "r"(bar), "r"(cnt) : "memory"); }
__device__ __forceinline__ void mbar_expect_tx(uint32_t bar, uint32_t bytes) { asm volatile("mbarrier.arrive.expect_tx.shared::cta.b64 _, [%0], %1;" :: "r"(bar), "r"(bytes) : "memory"); }
__device__ __forceinline__ void mbar_arrive(uint32_t bar) { asm volatile("mbarrier.arrive.shared::cta.b64 _, [%0];" :: "r"(bar) : "memory"); }
__device__ __forceinline__ void mbar_arrive_cl(uint32_t cl_addr) { asm volatile("mbarrier.arrive.shared::cluster.b64 _, [%0];" :: "r"(cl_addr) : "memory"); }
__device__ __forceinline__ uint32_t mapa(uint32_t addr, uint32_t cta) { uint32_t r; asm("mapa.shared::cluster.u32 %0, %1, %2;" : "=r"(r) : "r"(addr), "r"(cta)); return r; }
__device__ __forceinline__ void mbar_wait(uint32_t bar, uint32_t parity) {
  asm volatile("{\n.reg .pred p;\n.reg .b32 n;\n.reg .b64 z;\nmov.b32 n, 0;\nmov.b64 z, 0;\n"
               "W: add.u32 n, n, 1;\nsetp.gt.u32 p, n, 0x400000;\n@p st.global.u32 [z], n;\n"
               "mbarrier.try_wait.parity.shared::cta.b64 p, [%0], %1;\n@!p bra W;\n}" :: "r"(bar), "r"(parity) : "memory");
}
__device__ __forceinline__ void tma_3d(uint32_t dst, const CUtensorMap* m, uint32_t bar, int c0, int c1, int c2) {
  asm volatile("cp.async.bulk.tensor.3d.shared::cluster.global.mbarrier::complete_tx::bytes [%0], [%1, {%3, %4, %5}], [%2];" :: "r"(dst), "l"(m), "r"(bar), "r"(c0), "r"(c1), "r"(c2) : "memory");
}
__device__ __forceinline__ void tma_store_3d(const CUtensorMap* m, uint32_t src, int c0, int c1, int c2) {
  asm volatile("cp.async.bulk.tensor.3d.global.shared::cta.bulk_group [%0, {%2, %3, %4}], [%1];" :: "l"(m), "r"(src), "r"(c0), "r"(c1), "r"(c2) : "memory");
}
__device__ __forceinline__ void bulk_ld(uint32_t dst, const void* src, uint32_t bytes, uint32_t bar) {
  asm volatile("cp.async.bulk.shared::cluster.global.mbarrier::complete_tx::bytes [%0], [%1], %2, [%3];" :: "r"(dst), "l"(src), "r"(bytes), "r"(bar) : "memory");
}
__device__ __forceinline__ void bulk_ld_mc(uint32_t dst, const void* src, uint32_t bytes, uint32_t bar) {
  asm volatile("cp.async.bulk.shared::cluster.global.mbarrier::complete_tx::bytes.multicast::cluster [%0], [%1], %2, [%3], %4;" :: "r"(dst), "l"(src), "r"(bytes), "r"(bar), "h"((uint16_t)3) : "memory");
}
__device__ __forceinline__ void bulk_st(void* dst, uint32_t src, uint32_t bytes) {
  asm volatile("cp.async.bulk.global.shared::cta.bulk_group [%0], [%1], %2;" :: "l"(dst), "r"(src), "r"(bytes) : "memory");
}
__device__ __forceinline__ void bulk_commit() { asm volatile("cp.async.bulk.commit_group;" ::: "memory"); }
__device__ __forceinline__ void bulk_wait_read() { asm volatile("cp.async.bulk.wait_group.read 0;" ::: "memory"); }
__device__ __forceinline__ void bulk_wait_all() { asm volatile("cp.async.bulk.wait_group 0;" ::: "memory"); }
__device__ __forceinline__ void fence_async_global() { asm volatile("fence.proxy.async.global;" ::: "memory"); }
__device__ __forceinline__ void fence_async_smem() { asm volatile("fence.proxy.async.shared::cta;" ::: "memory"); }
__device__ __forceinline__ void wg_arrive() { asm volatile("wgmma.fence.sync.aligned;" ::: "memory"); }
__device__ __forceinline__ void wg_commit() { asm volatile("wgmma.commit_group.sync.aligned;" ::: "memory"); }
template <int N> __device__ __forceinline__ void wg_wait() { asm volatile("wgmma.wait_group.sync.aligned %0;" :: "n"(N) : "memory"); }
__device__ __forceinline__ void cl_arrive_relaxed() { asm volatile("barrier.cluster.arrive.relaxed.aligned;" ::: "memory"); }
__device__ __forceinline__ void cl_wait() { asm volatile("barrier.cluster.wait.acquire.aligned;" ::: "memory"); }
__device__ __forceinline__ bool elect() { uint32_t p; asm volatile("{\n.reg .pred p;\nelect.sync _|p, 0xffffffff;\nselp.u32 %0, 1, 0, p;\n}" : "=r"(p)); return p; }
__device__ __forceinline__ void named_bar(int id, int n) { asm volatile("bar.sync %0, %1;" :: "r"(id), "r"(n) : "memory"); }
__device__ __forceinline__ uint32_t pack2(float lo, float hi) { uint32_t r; asm("cvt.rn.bf16x2.f32 %0, %1, %2;" : "=r"(r) : "f"(hi), "f"(lo)); return r; }
__device__ __forceinline__ float bf_lo(uint32_t w) { return __uint_as_float(w << 16); }
__device__ __forceinline__ float bf_hi(uint32_t w) { return __uint_as_float(w & 0xffff0000u); }
__device__ __forceinline__ float bf_round(float v) { return __bfloat162float(__float2bfloat16_rn(v)); }
__device__ __forceinline__ void stsm4(uint32_t addr, uint32_t a, uint32_t b, uint32_t c, uint32_t d) {
  asm volatile("stmatrix.sync.aligned.m8n8.x4.shared.b16 [%0], {%1, %2, %3, %4};" :: "r"(addr), "r"(a), "r"(b), "r"(c), "r"(d) : "memory");
}
__device__ __forceinline__ void ldsm4(uint32_t addr, uint32_t& a, uint32_t& b, uint32_t& c, uint32_t& d) {
  asm volatile("ldmatrix.sync.aligned.m8n8.x4.shared.b16 {%0, %1, %2, %3}, [%4];" : "=r"(a), "=r"(b), "=r"(c), "=r"(d) : "r"(addr) : "memory");
}
__device__ __forceinline__ uint32_t movm(uint32_t a) { uint32_t r; asm volatile("movmatrix.sync.aligned.m8n8.trans.b16 %0, %1;" : "=r"(r) : "r"(a)); return r; }
__device__ __forceinline__ void mma16(float (&d)[4], uint32_t a0, uint32_t a1, uint32_t a2, uint32_t a3, uint32_t b0, uint32_t b1) {
  asm("mma.sync.aligned.m16n8k16.row.col.f32.bf16.bf16.f32 {%0,%1,%2,%3}, {%4,%5,%6,%7}, {%8,%9}, {%0,%1,%2,%3};"
               : "+f"(d[0]), "+f"(d[1]), "+f"(d[2]), "+f"(d[3]) : "r"(a0), "r"(a1), "r"(a2), "r"(a3), "r"(b0), "r"(b1));
}
__device__ __forceinline__ void mma16z(float (&d)[4], uint32_t a0, uint32_t a1, uint32_t a2, uint32_t a3, uint32_t b0, uint32_t b1) {
  asm("mma.sync.aligned.m16n8k16.row.col.f32.bf16.bf16.f32 {%0,%1,%2,%3}, {%4,%5,%6,%7}, {%8,%9}, {%10,%10,%10,%10};"
      : "=f"(d[0]), "=f"(d[1]), "=f"(d[2]), "=f"(d[3]) : "r"(a0), "r"(a1), "r"(a2), "r"(a3), "r"(b0), "r"(b1), "f"(0.f));
}
__device__ __forceinline__ void mma8z(float (&d)[4], uint32_t a0, uint32_t a1, uint32_t b0) {
  asm("mma.sync.aligned.m16n8k8.row.col.f32.bf16.bf16.f32 {%0,%1,%2,%3}, {%4,%5}, {%6}, {%7,%7,%7,%7};"
      : "=f"(d[0]), "=f"(d[1]), "=f"(d[2]), "=f"(d[3]) : "r"(a0), "r"(a1), "r"(b0), "f"(0.f));
}
__device__ __forceinline__ void mma8(float (&d)[4], uint32_t a0, uint32_t a1, uint32_t b0) {
  asm("mma.sync.aligned.m16n8k8.row.col.f32.bf16.bf16.f32 {%0,%1,%2,%3}, {%4,%5}, {%6}, {%0,%1,%2,%3};"
               : "+f"(d[0]), "+f"(d[1]), "+f"(d[2]), "+f"(d[3]) : "r"(a0), "r"(a1), "r"(b0));
}
__device__ __forceinline__ uint4 lds128(uint32_t a) { uint4 v; asm volatile("ld.shared.v4.u32 {%0,%1,%2,%3}, [%4];" : "=r"(v.x), "=r"(v.y), "=r"(v.z), "=r"(v.w) : "r"(a) : "memory"); return v; }
__device__ __forceinline__ void sts128(uint32_t a, uint32_t x, uint32_t y, uint32_t z, uint32_t w) { asm volatile("st.shared.v4.u32 [%0], {%1,%2,%3,%4};" :: "r"(a), "r"(x), "r"(y), "r"(z), "r"(w) : "memory"); }
__device__ __forceinline__ float lds32f(uint32_t a) { float v; asm volatile("ld.shared.f32 %0, [%1];" : "=f"(v) : "r"(a) : "memory"); return v; }
__device__ __forceinline__ void sts16(uint32_t a, bf16 v) { asm volatile("st.shared.b16 [%0], %1;" :: "r"(a), "h"(__bfloat16_as_ushort(v)) : "memory"); }
__device__ __forceinline__ uint4 ldg_nc(const void* p) { uint4 v; asm volatile("ld.global.nc.L1::no_allocate.v4.u32 {%0,%1,%2,%3}, [%4];" : "=r"(v.x), "=r"(v.y), "=r"(v.z), "=r"(v.w) : "l"(p)); return v; }
__device__ __forceinline__ uint4 ld_rlx4(const uint4* p) {
  unsigned long long a, b; asm volatile("ld.relaxed.gpu.global.v2.b64 {%0,%1}, [%2];" : "=l"(a), "=l"(b) : "l"(p) : "memory");
  return make_uint4((uint32_t)a, (uint32_t)(a >> 32), (uint32_t)b, (uint32_t)(b >> 32));
}
__device__ __forceinline__ uint2 ld_rlx2(const uint2* p) { unsigned long long a; asm volatile("ld.relaxed.gpu.global.b64 %0, [%1];" : "=l"(a) : "l"(p) : "memory"); return make_uint2((uint32_t)a, (uint32_t)(a >> 32)); }
__device__ __forceinline__ void st_rlx4(uint4* p, uint32_t x, uint32_t y, uint32_t z, uint32_t w) {
  asm volatile("st.relaxed.gpu.global.v2.b64 [%0], {%1,%2};" :: "l"(p), "l"((unsigned long long)x | ((unsigned long long)y << 32)), "l"((unsigned long long)z | ((unsigned long long)w << 32)) : "memory");
}
__device__ __forceinline__ void st_rlx2(uint2* p, uint32_t x, uint32_t y) { asm volatile("st.relaxed.gpu.global.b64 [%0], %1;" :: "l"(p), "l"((unsigned long long)x | ((unsigned long long)y << 32)) : "memory"); }
__device__ __forceinline__ void st_release(uint32_t* p, uint32_t v) { asm volatile("st.release.gpu.global.u32 [%0], %1;" :: "l"(p), "r"(v) : "memory"); }
__device__ __forceinline__ uint32_t ld_acquire(const uint32_t* p) { uint32_t v; asm volatile("ld.acquire.gpu.global.u32 %0, [%1];" : "=r"(v) : "l"(p) : "memory"); return v; }
__device__ __forceinline__ void prefetch_map(const CUtensorMap* m) { asm volatile("prefetch.tensormap [%0];" :: "l"(m) : "memory"); }
__device__ __forceinline__ float rcp(float x) { float r; asm("rcp.approx.ftz.f32 %0, %1;" : "=f"(r) : "f"(x)); return r; }
__device__ __forceinline__ float ex2(float x) { float r; asm("ex2.approx.ftz.f32 %0, %1;" : "=f"(r) : "f"(x)); return r; }
__device__ __forceinline__ float tanh_fast(float x) { float r; asm("tanh.approx.f32 %0, %1;" : "=f"(r) : "f"(x)); return r; }
#define SPIN_GUARD(n) if (++(n) > (1u << 24)) bail()

__device__ __forceinline__ void wgmma_n128(float (&d)[64], uint64_t da, uint64_t db) {
  asm volatile("wgmma.mma_async.sync.aligned.m64n128k16.f32.bf16.bf16 "
    "{%0, %1, %2, %3, %4, %5, %6, %7, %8, %9, %10, %11, %12, %13, %14, %15, %16, %17, %18, %19, %20, %21, %22, %23, %24, %25, %26, %27, %28, %29, %30, %31, %32, %33, %34, %35, %36, %37, %38, %39, %40, %41, %42, %43, %44, %45, %46, %47, %48, %49, %50, %51, %52, %53, %54, %55, %56, %57, %58, %59, %60, %61, %62, %63}, "
    "%64, %65, 1, 1, 1, 0, 1;\n"
    : "+f"(d[0]), "+f"(d[1]), "+f"(d[2]), "+f"(d[3]), "+f"(d[4]), "+f"(d[5]), "+f"(d[6]), "+f"(d[7]), "+f"(d[8]), "+f"(d[9]), "+f"(d[10]), "+f"(d[11]), "+f"(d[12]), "+f"(d[13]), "+f"(d[14]), "+f"(d[15]), "+f"(d[16]), "+f"(d[17]), "+f"(d[18]), "+f"(d[19]), "+f"(d[20]), "+f"(d[21]), "+f"(d[22]), "+f"(d[23]), "+f"(d[24]), "+f"(d[25]), "+f"(d[26]), "+f"(d[27]), "+f"(d[28]), "+f"(d[29]), "+f"(d[30]), "+f"(d[31]), "+f"(d[32]), "+f"(d[33]), "+f"(d[34]), "+f"(d[35]), "+f"(d[36]), "+f"(d[37]), "+f"(d[38]), "+f"(d[39]), "+f"(d[40]), "+f"(d[41]), "+f"(d[42]), "+f"(d[43]), "+f"(d[44]), "+f"(d[45]), "+f"(d[46]), "+f"(d[47]), "+f"(d[48]), "+f"(d[49]), "+f"(d[50]), "+f"(d[51]), "+f"(d[52]), "+f"(d[53]), "+f"(d[54]), "+f"(d[55]), "+f"(d[56]), "+f"(d[57]), "+f"(d[58]), "+f"(d[59]), "+f"(d[60]), "+f"(d[61]), "+f"(d[62]), "+f"(d[63])
    : "l"(da), "l"(db));
}
__device__ __forceinline__ void wgmma_n128_first(float (&d)[64], uint64_t da, uint64_t db) {
  asm volatile("wgmma.mma_async.sync.aligned.m64n128k16.f32.bf16.bf16 "
    "{%0, %1, %2, %3, %4, %5, %6, %7, %8, %9, %10, %11, %12, %13, %14, %15, %16, %17, %18, %19, %20, %21, %22, %23, %24, %25, %26, %27, %28, %29, %30, %31, %32, %33, %34, %35, %36, %37, %38, %39, %40, %41, %42, %43, %44, %45, %46, %47, %48, %49, %50, %51, %52, %53, %54, %55, %56, %57, %58, %59, %60, %61, %62, %63}, "
    "%64, %65, 0, 1, 1, 0, 1;\n"
    : "=f"(d[0]), "=f"(d[1]), "=f"(d[2]), "=f"(d[3]), "=f"(d[4]), "=f"(d[5]), "=f"(d[6]), "=f"(d[7]), "=f"(d[8]), "=f"(d[9]), "=f"(d[10]), "=f"(d[11]), "=f"(d[12]), "=f"(d[13]), "=f"(d[14]), "=f"(d[15]), "=f"(d[16]), "=f"(d[17]), "=f"(d[18]), "=f"(d[19]), "=f"(d[20]), "=f"(d[21]), "=f"(d[22]), "=f"(d[23]), "=f"(d[24]), "=f"(d[25]), "=f"(d[26]), "=f"(d[27]), "=f"(d[28]), "=f"(d[29]), "=f"(d[30]), "=f"(d[31]), "=f"(d[32]), "=f"(d[33]), "=f"(d[34]), "=f"(d[35]), "=f"(d[36]), "=f"(d[37]), "=f"(d[38]), "=f"(d[39]), "=f"(d[40]), "=f"(d[41]), "=f"(d[42]), "=f"(d[43]), "=f"(d[44]), "=f"(d[45]), "=f"(d[46]), "=f"(d[47]), "=f"(d[48]), "=f"(d[49]), "=f"(d[50]), "=f"(d[51]), "=f"(d[52]), "=f"(d[53]), "=f"(d[54]), "=f"(d[55]), "=f"(d[56]), "=f"(d[57]), "=f"(d[58]), "=f"(d[59]), "=f"(d[60]), "=f"(d[61]), "=f"(d[62]), "=f"(d[63])
    : "l"(da), "l"(db));
}
__device__ __forceinline__ void wgmma_n256(float (&d)[128], uint64_t da, uint64_t db) {
  asm volatile("wgmma.mma_async.sync.aligned.m64n256k16.f32.bf16.bf16 "
    "{%0, %1, %2, %3, %4, %5, %6, %7, %8, %9, %10, %11, %12, %13, %14, %15, %16, %17, %18, %19, %20, %21, %22, %23, %24, %25, %26, %27, %28, %29, %30, %31, %32, %33, %34, %35, %36, %37, %38, %39, %40, %41, %42, %43, %44, %45, %46, %47, %48, %49, %50, %51, %52, %53, %54, %55, %56, %57, %58, %59, %60, %61, %62, %63, %64, %65, %66, %67, %68, %69, %70, %71, %72, %73, %74, %75, %76, %77, %78, %79, %80, %81, %82, %83, %84, %85, %86, %87, %88, %89, %90, %91, %92, %93, %94, %95, %96, %97, %98, %99, %100, %101, %102, %103, %104, %105, %106, %107, %108, %109, %110, %111, %112, %113, %114, %115, %116, %117, %118, %119, %120, %121, %122, %123, %124, %125, %126, %127}, "
    "%128, %129, 1, 1, 1, 0, 1;\n"
    : "+f"(d[0]), "+f"(d[1]), "+f"(d[2]), "+f"(d[3]), "+f"(d[4]), "+f"(d[5]), "+f"(d[6]), "+f"(d[7]), "+f"(d[8]), "+f"(d[9]), "+f"(d[10]), "+f"(d[11]), "+f"(d[12]), "+f"(d[13]), "+f"(d[14]), "+f"(d[15]), "+f"(d[16]), "+f"(d[17]), "+f"(d[18]), "+f"(d[19]), "+f"(d[20]), "+f"(d[21]), "+f"(d[22]), "+f"(d[23]), "+f"(d[24]), "+f"(d[25]), "+f"(d[26]), "+f"(d[27]), "+f"(d[28]), "+f"(d[29]), "+f"(d[30]), "+f"(d[31]), "+f"(d[32]), "+f"(d[33]), "+f"(d[34]), "+f"(d[35]), "+f"(d[36]), "+f"(d[37]), "+f"(d[38]), "+f"(d[39]), "+f"(d[40]), "+f"(d[41]), "+f"(d[42]), "+f"(d[43]), "+f"(d[44]), "+f"(d[45]), "+f"(d[46]), "+f"(d[47]), "+f"(d[48]), "+f"(d[49]), "+f"(d[50]), "+f"(d[51]), "+f"(d[52]), "+f"(d[53]), "+f"(d[54]), "+f"(d[55]), "+f"(d[56]), "+f"(d[57]), "+f"(d[58]), "+f"(d[59]), "+f"(d[60]), "+f"(d[61]), "+f"(d[62]), "+f"(d[63]), "+f"(d[64]), "+f"(d[65]), "+f"(d[66]), "+f"(d[67]), "+f"(d[68]), "+f"(d[69]), "+f"(d[70]), "+f"(d[71]), "+f"(d[72]), "+f"(d[73]), "+f"(d[74]), "+f"(d[75]), "+f"(d[76]), "+f"(d[77]), "+f"(d[78]), "+f"(d[79]), "+f"(d[80]), "+f"(d[81]), "+f"(d[82]), "+f"(d[83]), "+f"(d[84]), "+f"(d[85]), "+f"(d[86]), "+f"(d[87]), "+f"(d[88]), "+f"(d[89]), "+f"(d[90]), "+f"(d[91]), "+f"(d[92]), "+f"(d[93]), "+f"(d[94]), "+f"(d[95]), "+f"(d[96]), "+f"(d[97]), "+f"(d[98]), "+f"(d[99]), "+f"(d[100]), "+f"(d[101]), "+f"(d[102]), "+f"(d[103]), "+f"(d[104]), "+f"(d[105]), "+f"(d[106]), "+f"(d[107]), "+f"(d[108]), "+f"(d[109]), "+f"(d[110]), "+f"(d[111]), "+f"(d[112]), "+f"(d[113]), "+f"(d[114]), "+f"(d[115]), "+f"(d[116]), "+f"(d[117]), "+f"(d[118]), "+f"(d[119]), "+f"(d[120]), "+f"(d[121]), "+f"(d[122]), "+f"(d[123]), "+f"(d[124]), "+f"(d[125]), "+f"(d[126]), "+f"(d[127])
    : "l"(da), "l"(db));
}
__device__ __forceinline__ void wgmma_n256_first(float (&d)[128], uint64_t da, uint64_t db) {
  asm volatile("wgmma.mma_async.sync.aligned.m64n256k16.f32.bf16.bf16 "
    "{%0, %1, %2, %3, %4, %5, %6, %7, %8, %9, %10, %11, %12, %13, %14, %15, %16, %17, %18, %19, %20, %21, %22, %23, %24, %25, %26, %27, %28, %29, %30, %31, %32, %33, %34, %35, %36, %37, %38, %39, %40, %41, %42, %43, %44, %45, %46, %47, %48, %49, %50, %51, %52, %53, %54, %55, %56, %57, %58, %59, %60, %61, %62, %63, %64, %65, %66, %67, %68, %69, %70, %71, %72, %73, %74, %75, %76, %77, %78, %79, %80, %81, %82, %83, %84, %85, %86, %87, %88, %89, %90, %91, %92, %93, %94, %95, %96, %97, %98, %99, %100, %101, %102, %103, %104, %105, %106, %107, %108, %109, %110, %111, %112, %113, %114, %115, %116, %117, %118, %119, %120, %121, %122, %123, %124, %125, %126, %127}, "
    "%128, %129, 0, 1, 1, 0, 1;\n"
    : "=f"(d[0]), "=f"(d[1]), "=f"(d[2]), "=f"(d[3]), "=f"(d[4]), "=f"(d[5]), "=f"(d[6]), "=f"(d[7]), "=f"(d[8]), "=f"(d[9]), "=f"(d[10]), "=f"(d[11]), "=f"(d[12]), "=f"(d[13]), "=f"(d[14]), "=f"(d[15]), "=f"(d[16]), "=f"(d[17]), "=f"(d[18]), "=f"(d[19]), "=f"(d[20]), "=f"(d[21]), "=f"(d[22]), "=f"(d[23]), "=f"(d[24]), "=f"(d[25]), "=f"(d[26]), "=f"(d[27]), "=f"(d[28]), "=f"(d[29]), "=f"(d[30]), "=f"(d[31]), "=f"(d[32]), "=f"(d[33]), "=f"(d[34]), "=f"(d[35]), "=f"(d[36]), "=f"(d[37]), "=f"(d[38]), "=f"(d[39]), "=f"(d[40]), "=f"(d[41]), "=f"(d[42]), "=f"(d[43]), "=f"(d[44]), "=f"(d[45]), "=f"(d[46]), "=f"(d[47]), "=f"(d[48]), "=f"(d[49]), "=f"(d[50]), "=f"(d[51]), "=f"(d[52]), "=f"(d[53]), "=f"(d[54]), "=f"(d[55]), "=f"(d[56]), "=f"(d[57]), "=f"(d[58]), "=f"(d[59]), "=f"(d[60]), "=f"(d[61]), "=f"(d[62]), "=f"(d[63]), "=f"(d[64]), "=f"(d[65]), "=f"(d[66]), "=f"(d[67]), "=f"(d[68]), "=f"(d[69]), "=f"(d[70]), "=f"(d[71]), "=f"(d[72]), "=f"(d[73]), "=f"(d[74]), "=f"(d[75]), "=f"(d[76]), "=f"(d[77]), "=f"(d[78]), "=f"(d[79]), "=f"(d[80]), "=f"(d[81]), "=f"(d[82]), "=f"(d[83]), "=f"(d[84]), "=f"(d[85]), "=f"(d[86]), "=f"(d[87]), "=f"(d[88]), "=f"(d[89]), "=f"(d[90]), "=f"(d[91]), "=f"(d[92]), "=f"(d[93]), "=f"(d[94]), "=f"(d[95]), "=f"(d[96]), "=f"(d[97]), "=f"(d[98]), "=f"(d[99]), "=f"(d[100]), "=f"(d[101]), "=f"(d[102]), "=f"(d[103]), "=f"(d[104]), "=f"(d[105]), "=f"(d[106]), "=f"(d[107]), "=f"(d[108]), "=f"(d[109]), "=f"(d[110]), "=f"(d[111]), "=f"(d[112]), "=f"(d[113]), "=f"(d[114]), "=f"(d[115]), "=f"(d[116]), "=f"(d[117]), "=f"(d[118]), "=f"(d[119]), "=f"(d[120]), "=f"(d[121]), "=f"(d[122]), "=f"(d[123]), "=f"(d[124]), "=f"(d[125]), "=f"(d[126]), "=f"(d[127])
    : "l"(da), "l"(db));
}

template <int N> struct WG;
#define DEF_WG(N) template <> struct WG<N> { \
  static __device__ __forceinline__ void mma(float (&d)[N / 2], uint64_t a, uint64_t b) { wgmma_n##N(d, a, b); } \
  static __device__ __forceinline__ void first(float (&d)[N / 2], uint64_t a, uint64_t b) { wgmma_n##N##_first(d, a, b); } };
DEF_WG(128) DEF_WG(256)

constexpr uint64_t DESC_A = (1ull << 62) | ((uint64_t)(1024 >> 4) << 32) | (1ull << 16);
constexpr uint64_t DESC_B = (1ull << 62) | ((uint64_t)(1024 >> 4) << 32) | ((uint64_t)(8192 >> 4) << 16);

struct Ring { int s; uint32_t ph; int wrap; };
template <int NS> __device__ __forceinline__ void ring_next(Ring& r) { r.s = (r.s + 1 == NS) ? 0 : r.s + 1; if (r.s == r.wrap) r.ph ^= 1; }

__device__ __forceinline__ int own_order(int it, int j) {
  return it < 2 ? 2 * j + it : it < 4 ? 2 * (j ^ 1) + it - 2 : ((j >> 1) * 4 + 2 * it - (it < 10 ? 4 : 15)) & 15;
}

template <int V> struct IC { static constexpr int v = V; };
template <int I, int E, class F> __device__ __forceinline__ void static_for(F&& f) { if constexpr (I < E) { f(IC<I>{}); static_for<I + 1, E>(f); } }

template <int N, int NS, int PRE, class Pre, class Mid, class Last>
__device__ __forceinline__ void mainloop(float (&acc)[N / 2], int nkb, bool own, Ring& r, uint32_t sb, int wg, int lane, uint32_t rel_base, int step0, Pre pre, Mid mid, Last last) {
  constexpr int SLOT = RING / NS;
  const uint32_t full = sb + MISC + (NS == 4 ? B_FULL4 : B_FULL6);
  const uint32_t rel = rel_base + (NS == 4 ? B_EMPTY4 : B_EMPTY6);
  const uint32_t s0 = (sb & 0x3FFFF) >> 4, a0 = s0 + wg * (HALF >> 4);
  int ps;
  auto issue = [&](int it, bool first) {
    const uint64_t da = DESC_A | (a0 + ((own && it < 2) ? (STG + it * BLK) >> 4 : r.s * (SLOT >> 4))), db = DESC_B | (s0 + r.s * (SLOT >> 4) + (BLK >> 4));
    mbar_wait(full + r.s * 8, r.ph);
    TRS(step0 + it);
    wg_arrive();
    if (first) WG<N>::first(acc, da, db); else WG<N>::mma(acc, da, db);
#pragma unroll
    for (int k = 1; k < 4; k++) WG<N>::mma(acc, da + k * 2, db + k * 128);
    wg_commit();
  };
  auto retire = [&](int it) {
    wg_wait<1>();
    if (lane < 2) mbar_arrive_cl(rel + ps * 8);
    if (own && it == 2 && lane == 0) mbar_arrive(sb + MISC + B_OWN);
    ps = r.s;
    ring_next<NS>(r);
  };
  issue(0, true);
  ps = r.s;
  ring_next<NS>(r);
  static_for<1, PRE + 1>([&](auto ic) { issue(ic.v, false); pre(ic); retire(ic.v); });
#pragma unroll 1
  for (int it = PRE + 1; it < nkb; it++) {
    if (TAILLAG && it == 56 - TAILLAG && wg == 1) mbar_wait(sb + MISC + B_LAG, 0);
    issue(it, false); mid(it); retire(it);
  }
  last();
  wg_wait<0>();
  if (lane < 2) mbar_arrive_cl(rel + ps * 8);
}

__device__ __forceinline__ void ln_publish(const float (&v)[64], uint4* st, int j, int row0, int lane, uint32_t ep) {
  float s0 = 0, s1 = 0, s2 = 0, s3 = 0, q0 = 0, q1 = 0, q2 = 0, q3 = 0;
#pragma unroll
  for (int i = 0; i < 16; i++) {
    s0 += v[4 * i]; s1 += v[4 * i + 1]; s2 += v[4 * i + 2]; s3 += v[4 * i + 3];
    q0 = fmaf(v[4 * i], v[4 * i], q0); q1 = fmaf(v[4 * i + 1], v[4 * i + 1], q1); q2 = fmaf(v[4 * i + 2], v[4 * i + 2], q2); q3 = fmaf(v[4 * i + 3], v[4 * i + 3], q3);
  }
  s0 += s1; s2 += s3; q0 += q1; q2 += q3;
  const bool odd = lane & 1;
  float s = (odd ? s2 : s0) + __shfl_xor_sync(~0u, odd ? s0 : s2, 1), q = (odd ? q2 : q0) + __shfl_xor_sync(~0u, odd ? q0 : q2, 1);
  s += __shfl_xor_sync(~0u, s, 2); q += __shfl_xor_sync(~0u, q, 2);
  if ((lane & 3) < 2) st_rlx4(st + j * 128 + row0 + (lane & 1) * 8, __float_as_uint(s), ep, __float_as_uint(q), ep);
}
__device__ __forceinline__ void ln_gather(const uint4* st, int row0, int lane, uint32_t ep, float& n0, float& r0, float& n1, float& r1) {
  const uint4* p = st + (lane & 2) * 256 + row0 + (lane & 1) * 8;
  uint4 a, b, c, d; uint32_t n = 0;
  while (true) {
    a = ld_rlx4(p); b = ld_rlx4(p + 128); c = ld_rlx4(p + 256); d = ld_rlx4(p + 384);
    if (a.y == ep && a.w == ep && b.y == ep && b.w == ep && c.y == ep && c.w == ep && d.y == ep && d.w == ep) break;
    SPIN_GUARD(n);
  }
  __syncwarp();
  float s = (__uint_as_float(a.x) + __uint_as_float(b.x)) + (__uint_as_float(c.x) + __uint_as_float(d.x));
  float q = (__uint_as_float(a.z) + __uint_as_float(b.z)) + (__uint_as_float(c.z) + __uint_as_float(d.z));
  s += __shfl_xor_sync(~0u, s, 2); q += __shfl_xor_sync(~0u, q, 2);
  s *= 1.f / 1024;
  const float r = rsqrtf(fmaxf(fmaf(-s, s, q * (1.f / 1024)), 0.f) + 1e-5f), nn = -s * r;
  const float ro = __shfl_xor_sync(~0u, r, 1), no = __shfl_xor_sync(~0u, nn, 1);
  const bool odd = lane & 1;
  r0 = odd ? ro : r; n0 = odd ? no : nn; r1 = odd ? r : ro; n1 = odd ? nn : no;
}
__device__ __forceinline__ void load_vec(uint32_t* w, uint32_t sb, int sec, int b, int lane) {
#pragma unroll
  for (int q = 0; q < 2; q++) { uint4 t = lds128(sb + MISC + MODV + sec * 256 + (lane & 3) * 64 + b * 32 + q * 16); w[4 * q] = t.x; w[4 * q + 1] = t.y; w[4 * q + 2] = t.z; w[4 * q + 3] = t.w; }
}
__device__ __forceinline__ void stage_done(uint32_t sb, int wg, int b, int lane) {
  fence_async_smem();
  __syncwarp();
  if (lane == 0) mbar_arrive(sb + MISC + B_RDY + b * 8);
}
__device__ __forceinline__ uint32_t hfma2(uint32_t a, uint32_t b, uint32_t c) { uint32_t r; asm("fma.rn.bf16x2 %0, %1, %2, %3;" : "=r"(r) : "r"(a), "r"(b), "r"(c)); return r; }
__device__ __forceinline__ void ln_apply(const float (&v)[64], const uint4* st, int row0, uint32_t ep, uint32_t sb, int sec_shift, int sec_scale, uint32_t stg_row, int wg, int lane) {
  uint32_t sc[16], sh[16];
#pragma unroll
  for (int b = 0; b < 2; b++) { load_vec(sc + 8 * b, sb, sec_scale, b, lane); load_vec(sh + 8 * b, sb, sec_shift, b, lane); }
  float n0, r0, n1, r1;
  ln_gather(st, row0, lane, ep, n0, r0, n1, r1);
#pragma unroll
  for (int i = 0; i < 16; i += 2) {
    if (i == 8) { const float z = lds32f(sb + MISC + ZERO); n0 += z; n1 += z; }
    uint32_t w[4];
#pragma unroll
    for (int u = 0; u < 2; u++) {
      int q = i + u;
      w[2 * u] = hfma2(pack2(fmaf(v[4 * q], r0, n0), fmaf(v[4 * q + 1], r0, n0)), sc[q], sh[q]);
      w[2 * u + 1] = hfma2(pack2(fmaf(v[4 * q + 2], r1, n1), fmaf(v[4 * q + 3], r1, n1)), sc[q], sh[q]);
    }
    stsm4(stg_row + (i >> 3) * BLK + ((((i & 7) + (lane >> 4)) ^ (lane & 7)) << 4), w[0], w[1], w[2], w[3]);
    if ((i & 7) == 6) stage_done(sb, wg, i >> 3, lane);
  }
}
__device__ __forceinline__ uint32_t hmul2(uint32_t a, uint32_t b) { uint32_t r; asm("mul.rn.bf16x2 %0, %1, %2;" : "=r"(r) : "r"(a), "r"(b)); return r; }
__device__ __forceinline__ uint32_t silu_mul2(uint32_t g, uint32_t u) {
  const uint32_t h = hmul2(g, 0x3f003f00u);
  const float h0 = bf_lo(h), h1 = bf_hi(h);
  return hmul2(pack2(fmaf(h0, tanh_fast(h0), h0), fmaf(h1, tanh_fast(h1), h1)), u);
}

__device__ __forceinline__ void gemv_fma(float (&a)[8], uint4 w, float s) {
  a[0] = fmaf(bf_lo(w.x), s, a[0]); a[1] = fmaf(bf_hi(w.x), s, a[1]); a[2] = fmaf(bf_lo(w.y), s, a[2]); a[3] = fmaf(bf_hi(w.y), s, a[3]);
  a[4] = fmaf(bf_lo(w.z), s, a[4]); a[5] = fmaf(bf_hi(w.z), s, a[5]); a[6] = fmaf(bf_lo(w.w), s, a[6]); a[7] = fmaf(bf_hi(w.w), s, a[7]);
}
__device__ __forceinline__ float silu_c(float v) { return bf_round(__fdividef(v, 1.f + __expf(-v))); }
__device__ __forceinline__ float mod_gather(const uint2* p, uint32_t ep) {
  uint2 a, b, c, d; uint32_t n = 0;
  while (true) {
    a = ld_rlx2(p); b = ld_rlx2(p + 128); c = ld_rlx2(p + 256); d = ld_rlx2(p + 384);
    if (a.y == ep && b.y == ep && c.y == ep && d.y == ep) break;
    SPIN_GUARD(n);
  }
  return (__uint_as_float(a.x) + __uint_as_float(b.x)) + (__uint_as_float(c.x) + __uint_as_float(d.x));
}
__device__ __forceinline__ void mod_store(uint32_t sb, int sec, int col, float v) {
  v = bf_round(v);
  if (sec == 1 || sec == 4) v += 1.f;
  sts16(sb + MISC + MODV + sec * 256 + (((col >> 1) & 3) * 16 + (col >> 3)) * 4 + (col & 1) * 2, __float2bfloat16_rn(v));
}

__global__ void __cluster_dims__(2, 1, 1) __launch_bounds__(384, 1)
fused_kernel(const bf16* __restrict__ cvec, const bf16* __restrict__ wmod, Scratch* gs, int by_sm, const __grid_constant__ Maps maps) {
  extern __shared__ __align__(1024) uint8_t smem_raw[];
  const uint32_t sb = smem_u32(smem_raw);
  const int warp = __shfl_sync(~0u, threadIdx.x >> 5, 0), lane = threadIdx.x & 31;
  const int rank = blockIdx.x & 1;
  int cid = (blockIdx.x >> 1) - 2;
  if (by_sm) {
    uint32_t sm; asm("mov.u32 %0, %%smid;" : "=r"(sm));
    const int t = sm >> 1, u = t - 32, gp = t < 32 ? t & 7 : t < 60 ? 1 + u % 7 : 0, idx = t < 32 ? t >> 3 : t < 60 ? 4 + u / 7 : t - 58;
    cid = (t & ~1) == 60 ? t - 62 : ((gp & 1) * 8 + idx) * 4 + (gp >> 1);
  }
  const bool extra = cid < 0;
  const int bid = cid * 2 + rank;
  const int m = cid >> 2, j = (cid & 3) * 2 + rank;
  const uint32_t bar = sb + MISC;

  if (warp >= 8) {
    asm volatile("setmaxnreg.dec.sync.aligned.u32 40;");
    if (extra) {
      if (warp == 8) {
        if (lane == 0) { for (int s = 0; s < 6; s++) { mbar_init(bar + B_FULL6 + s * 8, 1); mbar_init(bar + B_EMPTY6 + s * 8, 8); } fence_async_smem(); }
        __syncwarp();
        asm volatile("bar.arrive 2, 288;" ::: "memory");
        __nanosleep(XSLEEP);
#pragma unroll 1
        for (int it = 0, s = 0, par = 1; it < 64; it++) {
          mbar_wait(bar + B_EMPTY6 + s * 8, par);
          if (elect()) { mbar_expect_tx(bar + B_FULL6 + s * 8, 32768); tma_3d(sb + s * 32768, &maps.wmod, bar + B_FULL6 + s * 8, 0, (it & 15) * 64, 12 + (it >> 4) * 4 + bid); }
          if (++s == 6) { s = 0; par ^= 1; }
        }
      }
    } else if (warp < 10) {
      uint32_t s6 = 0, p6 = 1;
      auto next6 = [&]() { if (++s6 == 6) { s6 = 0; p6 ^= 1; } };
      auto drained4 = [&](int q, int late) { if (q < 5) mbar_wait(bar + B_EMPTY4 + (((late ? 0x10332 : 0x32110) >> (4 * q)) & 3) * 8, 1); };
      auto drained6 = [&](int q) { if (q < 3) mbar_wait(bar + B_EMPTY6 + ((0x154 >> (4 * q)) & 7) * 8, q >> 1); };
      auto skip6 = [&]() { mbar_wait(bar + B_EMPTY6 + s6 * 8, p6); if (elect()) mbar_arrive(bar + B_FULL6 + s6 * 8); next6(); };
      if (warp == 8) {
        const uint32_t t_start = clock();
        if (lane == 0) {
          if (sb & 1023) bail();
          for (int b = 0; b < 2; b++) mbar_init(bar + B_X + b * 8, 1);
          for (int s = 0; s < 4; s++) { mbar_init(bar + B_FULL4 + s * 8, 2); mbar_init(bar + B_EMPTY4 + s * 8, 16); }
          for (int s = 0; s < 6; s++) { mbar_init(bar + B_FULL6 + s * 8, 2); mbar_init(bar + B_EMPTY6 + s * 8, 16); }
          for (int b = 0; b < 2; b++) { mbar_init(bar + B_RDY + b * 8, 8); mbar_init(bar + B_FREE + b * 8, 1); mbar_init(bar + B_HH + b * 8, 1); }
          mbar_init(bar + B_MOD, 1); mbar_init(bar + B_LAG, 4); mbar_init(bar + B_HALO, 2); mbar_init(bar + B_ALL, 1); mbar_init(bar + B_HH2, 1); mbar_init(bar + B_OWN, 8);
          asm volatile("st.shared.u32 [%0], 0;" :: "r"(bar + ZERO) : "memory");
          asm volatile("fence.mbarrier_init.release.cluster;" ::: "memory");
          fence_async_smem();
        }
        __syncwarp();
        cl_arrive_relaxed();
        auto wide = [&](int s, int par, const CUtensorMap* m0, int a0, const CUtensorMap* m1, int a1, int kb) {
          const uint32_t full = bar + B_FULL4 + s * 8, d = sb + s * 49152 + BLK;
          mbar_wait(full + 32, par);
          if (elect()) { mbar_expect_tx(full, 2 * BLK); tma_3d(d, m0, full, 0, kb * 64, a0); tma_3d(d + BLK, m1, full, 0, kb * 64, a1); }
        };
        auto narrow = [&](const CUtensorMap* m0, int kb) {
          const uint32_t full = bar + B_FULL6 + s6 * 8;
          mbar_wait(full + 48, p6);
          if (elect()) { mbar_expect_tx(full, BLK); tma_3d(sb + s6 * 32768 + BLK, m0, full, 0, kb * 64, 2 * j); }
          next6();
        };
#pragma unroll 1
        for (int it = 0; it < 16; it++) {
          if (it == 0) {
            while ((uint32_t)clock() - t_start < XDELAY) {}
            if (elect()) for (int b = 0; b < 2; b++) { mbar_expect_tx(bar + B_X + b * 8, BLK); tma_3d(sb + STG + b * BLK, &maps.x, bar + B_X + b * 8, j * 128 + b * 64, m * 64, 0); }
            mbar_wait(bar + B_X + 8, 0);
          }
          wide(it & 3, ~(it >> 2) & 1, &maps.wqkv, 16 + 2 * j, &maps.wqkv, 32 + 2 * j, own_order(it, j));
        }
#pragma unroll 1
        for (int it = 0; it < 16; it++) { drained4(it, 0); narrow(&maps.wqkv, it); }
#pragma unroll 1
        for (int it = 0; it < 16; it++) {
          narrow(&maps.wo, own_order(it, j));
          if (it == 10) {
            mbar_wait(bar + B_OWN, 1); mbar_wait(bar + B_FREE + 8, 1);
            if (elect()) for (int b = 0; b < 2; b++) { mbar_expect_tx(bar + B_X + b * 8, BLK); tma_3d(sb + STG + b * BLK, &maps.x, bar + B_X + b * 8, j * 128 + b * 64, m * 64, 0); }
          }
        }
        skip6();
#pragma unroll 1
        for (int it = 0; it < 48; it++) {
          const int s = (it + 2) & 3, par = ~(it >> 2) & 1;
          drained6(it);
          wide(s, par, &maps.w1, (it & 48) + 2 * j, &maps.w3, (it & 48) + 2 * j, it < 16 ? own_order(it, j) : it & 15);
          if (it >= 44) {
            if (it == 44) { mbar_wait(bar + B_FREE, 0); mbar_wait(bar + B_FREE + 8, 0); if (elect()) mbar_expect_tx(bar + B_X, 2 * BLK); }
            if (elect()) bulk_ld(sb + STG + (it - 44) * HALF, gs->x1 + bid * 2048 + (it - 44) * 512, HALF, bar + B_X);
          }
        }
#pragma unroll 1
        for (int it = 0; it < 16; it++) {
          const uint32_t full = bar + B_FULL6 + s6 * 8, d = sb + s6 * 32768 + BLK;
          drained4(it, 1);
          mbar_wait(full + 48, p6);
          if (elect()) { mbar_expect_tx(full, BLK); tma_3d(d, &maps.w1s, full, 0, it * 64, 48 + j); tma_3d(d + HALF, &maps.w3s, full, 0, it * 64, 48 + j); }
          next6();
        }
#pragma unroll 1
        for (int it = 0; it < 56; it++) narrow(&maps.w2, it);
      } else {
        if (lane < 9) prefetch_map(&maps.x + lane);
        const uint32_t ep = gs->epoch[bid + 4] + 1;
        cl_arrive_relaxed(); cl_wait();
        auto plain = [&](uint32_t full, uint32_t empty, int par, uint32_t slot, const uint4* blk) {
          mbar_wait(empty, par);
          if (elect()) { mbar_expect_tx(full, BLK); bulk_ld_mc(slot + rank * HALF, blk + rank * 512, HALF, full); }
        };
        auto plain6 = [&](const uint4* blk) { plain(bar + B_FULL6 + s6 * 8, bar + B_EMPTY6 + s6 * 8, p6, sb + s6 * 32768, blk); next6(); };
        uint32_t ready = 0;
        auto poll = [&](int e) { ready = __ballot_sync(~0u, ld_acquire(gs->flag + m * 128 + e * 16 + (lane & 15)) == ep); };
        auto need = [&](int e, uint32_t mask) {
          if ((ready & mask) != mask) {
            uint32_t n = 0;
            do { poll(e); SPIN_GUARD(n); } while ((ready & mask) != mask);
            fence_async_global();
          }
        };
        auto fresh = [&](int e, int it, uint32_t full, uint32_t empty, int par, uint32_t slot, uint4* src) {
          if (it >= 4) {
            const int kb = own_order(it, j);
            if (it < 10) need(e, 1u << kb); else if (it == 10) mbar_wait(bar + B_ALL, e & 1);
            plain(full, empty, par, slot, src + kb * 1024);
          } else {
            if (it == 0) { poll(e); ready = 0; }
            mbar_wait(empty, par);
            if (it < 2) { if (elect()) mbar_arrive(full); }
            else {
              const int b = it & 1;
              const uint32_t to_peer = mapa(sb, rank ^ 1) - sb;
              if (elect()) mbar_expect_tx(full, BLK);
              mbar_wait(bar + (b ? B_FREE + 8 : B_RDY), e & 1);
              if (b == 0) TR(e == 0 ? 24 : e == 2 ? 30 : 44);
              if (elect()) {
                if (b == 0) {
                  bulk_st(src + 2 * j * 1024, sb + STG, BLK);
                  bulk_commit();
                  bulk_wait_all();
                  mbar_arrive(bar + B_FREE);
                }
                fence_async_global();
                bulk_ld(slot + to_peer, src + (2 * j + b) * 1024, BLK, full + to_peer);
              }
              __syncwarp();
            }
          }
          if (it == 4) TR(e == 0 ? 28 : e == 1 ? 46 : 34);
        };
#pragma unroll 1
        for (int ph = 0; ph < 2; ph++) {
          uint4* h = gs->h + m * 16384;
#pragma unroll 1
          for (int it = 0; it < 16; it++) {
            const int s = (it + 2 * ph) & 3;
            if (ph) drained6(it);
            fresh(2 * ph, it, bar + B_FULL4 + s * 8, bar + B_EMPTY4 + s * 8, ~(it >> 2) & 1, sb + s * 49152, h);
          }
          if (ph) {
#pragma unroll 1
            for (int it = 16; it < 48; it++) {
              const int s = (it + 2) & 3;
              const uint32_t full = bar + B_FULL4 + s * 8;
              plain(full, full + 32, ~(it >> 2) & 1, sb + s * 49152, h + (it & 15) * 1024);
            }
          }
#pragma unroll 1
          for (int it = 0; it < 16; it++) { drained4(it, ph); plain6(h + it * 1024); }
          if (!ph) {
#pragma unroll 1
            for (int it = 0; it < 16; it++) { fresh(1, it, bar + B_FULL6 + s6 * 8, bar + B_EMPTY6 + s6 * 8, p6, sb + s6 * 32768, gs->o + m * 16384); next6(); }
            skip6();
          }
        }
#pragma unroll 1
        for (int it = 0; it < 56; it++) {
          if (it == 0 || it == 32 || it == 48) mbar_wait(bar + (it == 48 ? B_HH2 : B_HH + (it >> 2)), 0);
          plain6(gs->hh + m * 57344 + it * 1024);
        }
      }
    } else {
      const int b = warp - 10;
      const uint32_t ep = gs->epoch[bid + 4] + 1;
      const uint32_t stg = sb + STG + b * BLK;
      cl_arrive_relaxed(); cl_wait();
      auto all_there = [&](int u, uint32_t done) {
        const uint32_t* fl = gs->flag + u;
        uint32_t n = 0;
        while (!__all_sync(~0u, ld_acquire(fl) == ep)) { __nanosleep(100); SPIN_GUARD(n); }
        fence_async_global();
        if (lane == 0) mbar_arrive(done);
      };
      auto fetch_mod = [&](int sec) {
        const uint4* p = (const uint4*)(gs->modv + (sec - 2) * 1024 + j * 128) + lane;
        uint4 v0, v1; uint32_t n = 0;
        while (true) {
          v0 = ld_rlx4(p); v1 = ld_rlx4(p + 32);
          if (v0.y == ep && v0.w == ep && v1.y == ep && v1.w == ep) break;
          SPIN_GUARD(n);
        }
        mod_store(sb, sec, 2 * lane, __uint_as_float(v0.x)); mod_store(sb, sec, 2 * lane + 1, __uint_as_float(v0.z));
        mod_store(sb, sec, 64 + 2 * lane, __uint_as_float(v1.x)); mod_store(sb, sec, 65 + 2 * lane, __uint_as_float(v1.z));
        __syncwarp();
      };
#pragma unroll 1
      for (int e = 0; e < 7 - b; e++) {
        if (lane == 0) {
          if (e < 3) {
            mbar_wait(bar + B_FREE, e & 1);
            if (b) {
              mbar_wait(bar + B_RDY + 8, e & 1);
              bulk_st((e == 1 ? gs->o : gs->h) + m * 16384 + (2 * j + 1) * 1024, stg, BLK);
              bulk_commit();
              bulk_wait_all();
              mbar_arrive(bar + B_FREE + 8);
              TR(53 + e);
            }
            st_release(gs->flag + m * 128 + e * 16 + 2 * j + b, ep);
            TR((e == 0 ? 26 : e == 2 ? 32 : 42) + b);
          } else {
            const int kb = (e < 6 ? 2 * (8 * (e - 3) + j) : 48 + j) + b;
            mbar_wait(bar + B_RDY + b * 8, e & 1);
#pragma unroll 1
            for (int q = 0; q < NPIECE; q++) { if (q) __nanosleep(PSLEEP); bulk_st(gs->hh + m * 57344 + kb * 1024 + q * (1024 / NPIECE), stg + q * (BLK / NPIECE), BLK / NPIECE); }
            bulk_commit();
            bulk_wait_all();
            mbar_arrive(bar + B_FREE + b * 8);
            st_release(gs->flag + m * 128 + U_HH + kb, ep);
          }
        }
        __syncwarp();
        if (e < 3 && b) all_there(m * 128 + e * 16 + (lane & 15), bar + B_ALL);
        if (e == 4 && b) all_there(m * 128 + U_HH + lane, bar + B_HH);
        if (!b && (e == 1 || e == 2)) {
#pragma unroll 1
          for (int sec = e == 1 ? 2 : 5; sec < 4 + e; sec++) fetch_mod(sec);
          if (e == 1) { if (lane == 0) mbar_arrive(bar + B_MOD); TR(50); }
        }
        if (e == 0) {
          mbar_wait(bar + B_EMPTY6 + 24, 0);
          if (HSLEEP) __nanosleep(HSLEEP);
#pragma unroll 1
          for (int w = 0; w < 4; w++) {
            const uint4* hp = gs->halo + ((m * 8 + j) * 2 + (w & 1)) * 512 + b * 256 + (w >> 1) * 128 + lane;
            uint4 q[4] = {}; uint32_t n = 0;
            while (m > 0) {
              bool ok = true;
#pragma unroll
              for (int i = 0; i < 4; i++) q[i] = ld_rlx4(hp + i * 32);
#pragma unroll
              for (int i = 0; i < 4; i++) ok = ok && q[i].y == ep && q[i].w == ep;
              if (ok) break;
              SPIN_GUARD(n);
            }
#pragma unroll
            for (int i = 0; i < 2; i++) sts128(stg + lane * 16 + (w & 1) * HALF + (w >> 1) * 1024 + i * 512, q[2 * i].x, q[2 * i + 1].x, q[2 * i].z, q[2 * i + 1].z);
          }
          __syncwarp();
          if (lane == 0) mbar_arrive(bar + B_HALO);
          if (b == 0) TR(52);
        }
      }
      if (b) { all_there(m * 128 + U_HH + 32 + (lane & 15), bar + B_HH + 8); all_there(m * 128 + U_HH + 48 + (lane & 7), bar + B_HH2); }
    }
  } else {
    const int wg = warp >> 2, wq = warp & 3, tid = threadIdx.x;
    const int g = lane >> 2, c = lane & 3;
    const int sec0 = (m >> 1) & 1, hf0 = m & 1, ks0 = (m >> 2) & 3;
    uint4 wv[8];
    uint32_t ep0; uint16_t cv_;
    asm volatile("ld.global.nc.u16 %0, [%1];" : "=h"(cv_) : "l"(cvec + ks0 * 256 + warp * 32 + lane));
    asm volatile("ld.global.u32 %0, [%1];" : "=r"(ep0) : "l"(gs->epoch + bid + 4));
    if (!extra) {
      const bf16* wp = wmod + (size_t)(ks0 * 256 + warp * 32 + (lane >> 3)) * 6144 + sec0 * 1024 + j * 128 + hf0 * 64 + (lane & 7) * 8;
#pragma unroll
      for (int i = 0; i < 8; i++) wv[i] = ldg_nc(wp + (size_t)i * 4 * 6144);
    }
    asm volatile("setmaxnreg.inc.sync.aligned.u32 232;" ::: "memory");
    if (__builtin_expect(extra, 0)) {
      const uint32_t ep = ep0 + 1;
      float sv[4];
#pragma unroll
      for (int p = 0; p < 4; p++) sv[p] = silu_c(__bfloat162float(cvec[64 * (4 * p + (lane >> 3)) + 8 * warp + (lane & 7)]));
      named_bar(2, 288);
      int s = 0, par = 0;
#pragma unroll 1
      for (int sec = 0; sec < 4; sec++) {
        float a[8] = {0, 0, 0, 0, 0, 0, 0, 0};
#pragma unroll 1
        for (int it = 0; it < 16; it++) {
          const float sc = it < 4 ? sv[0] : it < 8 ? sv[1] : it < 12 ? sv[2] : sv[3];
          mbar_wait(bar + B_FULL6 + s * 8, par);
          uint4 w[8];
#pragma unroll
          for (int i = 0; i < 8; i++) w[i] = lds128(sb + s * 32768 + (warp * 8 + i) * 512 + lane * 16);
#pragma unroll
          for (int i = 0; i < 8; i++) gemv_fma(a, w[i], __shfl_sync(~0u, sc, (it & 3) * 8 + i));
          if (lane == 0) mbar_arrive(bar + B_EMPTY6 + s * 8);
          if (++s == 6) { s = 0; par ^= 1; }
        }
        const uint32_t red = sb + STG + sec * 8192;
        sts128(red + warp * 1024 + lane * 32, __float_as_uint(a[0]), __float_as_uint(a[1]), __float_as_uint(a[2]), __float_as_uint(a[3]));
        sts128(red + warp * 1024 + lane * 32 + 16, __float_as_uint(a[4]), __float_as_uint(a[5]), __float_as_uint(a[6]), __float_as_uint(a[7]));
        named_bar(1, 256);
        float t = 0;
#pragma unroll
        for (int q = 0; q < 8; q++) t += lds32f(red + q * 1024 + tid * 4);
        st_rlx2(gs->modv + sec * 1024 + (bid + 4) * 256 + tid, __float_as_uint(t), ep);
      }
      if (tid == 0) gs->epoch[bid + 4] = ep;
      return;
    }
    if (warp == 0) TR(0);
    const int row0 = wg * 64 + wq * 16 + g;
    if (c < 2) st_rlx4(gs->stat + m * 1024 + j * 128 + row0 + c * 8, 0, 0, 0, 0);
    if (tid < 64) st_rlx2(gs->modp + ((j * 2 + sec0) * 4 + ks0) * 128 + hf0 * 64 + tid, 0, 0);
    cl_arrive_relaxed(); cl_wait();
    uint32_t ep;
    asm volatile("add.u32 %0, %1, 1;" : "=r"(ep) : "r"(ep0) : "memory");
    const float sc_ = silu_c(__uint_as_float((uint32_t)cv_ << 16));
    const uint32_t rel = mapa(bar, (lane & 1) ^ rank);
    const uint32_t stg_row = sb + STG + (wg * 64 + wq * 16 + (lane & 15)) * 128;
    const uint32_t fre = bar + B_FREE;
    Ring r4{0, 0, 0}, r6{0, 0, 0};
    auto none = [](auto) {};
    {
      float a[8] = {0, 0, 0, 0, 0, 0, 0, 0};
#pragma unroll
      for (int i = 0; i < 8; i++) gemv_fma(a, wv[i], __shfl_sync(~0u, sc_, i * 4 + (lane >> 3)));
#pragma unroll
      for (int i = 0; i < 8; i++) { a[i] += __shfl_xor_sync(~0u, a[i], 8); a[i] += __shfl_xor_sync(~0u, a[i], 16); }
      if (lane < 8) {
        sts128(sb + RED_OFF + warp * 256 + lane * 32, __float_as_uint(a[0]), __float_as_uint(a[1]), __float_as_uint(a[2]), __float_as_uint(a[3]));
        sts128(sb + RED_OFF + warp * 256 + lane * 32 + 16, __float_as_uint(a[4]), __float_as_uint(a[5]), __float_as_uint(a[6]), __float_as_uint(a[7]));
      }
      named_bar(1, 256);
      if (tid < 64) {
        float s = 0;
#pragma unroll
        for (int w = 0; w < 8; w++) s += lds32f(sb + RED_OFF + w * 256 + tid * 4);
        st_rlx2(gs->modp + ((j * 2 + sec0) * 4 + ks0) * 128 + hf0 * 64 + tid, __float_as_uint(s), ep);
      }
      if (warp == 0) TR(1);
      float v[64];
      mbar_wait(bar + B_X, 0); mbar_wait(bar + B_X + 8, 0);
#pragma unroll
      for (int i = 0; i < 16; i += 2) {
        uint32_t w0, w1, w2, w3;
        ldsm4(stg_row + (i >> 3) * BLK + ((((i & 7) + (lane >> 4)) ^ (lane & 7)) << 4), w0, w1, w2, w3);
        v[4 * i] = bf_lo(w0); v[4 * i + 1] = bf_hi(w0); v[4 * i + 2] = bf_lo(w1); v[4 * i + 3] = bf_hi(w1);
        v[4 * i + 4] = bf_lo(w2); v[4 * i + 5] = bf_hi(w2); v[4 * i + 6] = bf_lo(w3); v[4 * i + 7] = bf_hi(w3);
      }
      ln_publish(v, gs->stat + m * 1024, j, row0, lane, ep);
      if (warp == 0) TR(2);
      mod_store(sb, tid >> 7, tid & 127, mod_gather(gs->modp + (j * 2 + (tid >> 7)) * 512 + (tid & 127), ep));
      named_bar(1, 256);
      if (warp == 0) TR(3);
      ln_apply(v, gs->stat + m * 1024, row0, ep, sb, 0, 1, stg_row, wg, lane);
      named_bar(2 + wg, 128);
    }
    if (warp == 0) TR(4);
    {
      uint32_t kf[32], vf[32], pv[32];
      const bool first = wq == 0 && m == 0;
      const uint32_t xa = sb + STG + wg * HALF + wq * 2048 + lane * 16;
      {
        float acc[128];
        mainloop<256, 4, 0>(acc, 16, true, r4, sb, wg, lane, rel, bid * 192 + 0, none, none, [&] {
          mbar_wait(fre + 8, 0);
          if (c < 2) st_rlx4(gs->stat + (16 + m) * 1024 + j * 128 + row0 + c * 8, 0, 0, 0, 0);
        });
        if (warp == 0) TR(5);
#pragma unroll
        for (int i = 0; i < 32; i++) { kf[i] = pack2(acc[2 * i], acc[2 * i + 1]); vf[i] = pack2(acc[64 + 2 * i], acc[65 + 2 * i]); }
      }
      if (warp == 0) TR(6);
      float acc[64];
      constexpr int QP = 2;
      mainloop<128, 6, 8 / QP>(acc, 16, false, r6, sb, wg, lane, rel, bid * 192 + 16, [&](auto ic) {
        constexpr int q = (ic.v - 1) * QP;
#pragma unroll
        for (int i = 4 * q; i < 4 * (q + QP); i++) vf[i] = movm(vf[i]);
        if (wq == 3) {
          if (m < 15) {
            uint4* hp = gs->halo + (((m + 1) * 8 + j) * 2 + wg) * 512 + lane;
#pragma unroll
            for (int i = 2 * q; i < 2 * (q + QP); i++) st_rlx4(hp + i * 32, kf[2 * i + 1], ep, vf[2 * i + 1], ep);
          }
        } else {
#pragma unroll
          for (int i = q; i < q + QP; i++) sts128(xa + 2048 + (i >> 2) * BLK + (i & 3) * 512, kf[4 * i + 1], kf[4 * i + 3], vf[4 * i + 1], vf[4 * i + 3]);
        }
      }, none, [&] {
        named_bar(2 + wg, 128);
        if (wq == 0) mbar_wait(bar + B_HALO, 0);
#pragma unroll
        for (int i = 0; i < 8; i++) {
          uint4 q = lds128(xa + (i >> 2) * BLK + (i & 3) * 512);
          pv[4 * i] = q.x; pv[4 * i + 1] = q.y; pv[4 * i + 2] = q.z; pv[4 * i + 3] = q.w;
        }
        __syncwarp();
      });
      if (warp == 0) TR(7);
      int gz = g;
#pragma unroll
      for (int b = 0; b < 2; b++) {
        const bool up0 = 2 * c > gz, up1 = 2 * c + 1 > gz;
        const uint32_t mup = (up0 ? 0xffffu : 0u) | (up1 ? 0xffff0000u : 0u);
        float l[2][4], mx[4];
#pragma unroll
        for (int h = 0; h < 2; h++) {
          uint32_t q[8];
          const int k = 16 * b + 8 * h;
#pragma unroll
          for (int i = 0; i < 8; i++) q[i] = pack2(acc[2 * k + 2 * i], acc[2 * k + 2 * i + 1]);
          float s0[4], s1[4], s2[4];
          mma16z(s0, q[0], q[1], q[2], q[3], pv[k], pv[k + 1]); mma16z(s1, q[0], q[1], q[2], q[3], kf[k], kf[k + 2]); mma16z(s2, q[0], q[1], q[2], q[3], kf[k + 1], kf[k + 3]);
          mma16(s0, q[4], q[5], q[6], q[7], pv[k + 4], pv[k + 5]); mma16(s1, q[4], q[5], q[6], q[7], kf[k + 4], kf[k + 6]); mma16(s2, q[4], q[5], q[6], q[7], kf[k + 5], kf[k + 7]);
          if (first) { s0[0] = -INFINITY; s0[1] = -INFINITY; }
          l[h][0] = up0 ? s0[0] : s1[0]; l[h][1] = up1 ? s0[1] : s1[1]; l[h][2] = up0 ? s1[2] : s2[2]; l[h][3] = up1 ? s1[3] : s2[3];
          mx[2 * h] = fmaxf(l[h][0], l[h][1]); mx[2 * h + 1] = fmaxf(l[h][2], l[h][3]);
        }
#pragma unroll
        for (int o = 1; o < 4; o <<= 1) {
#pragma unroll
          for (int h = 0; h < 4; h++) mx[h] = fmaxf(mx[h], __shfl_xor_sync(~0u, mx[h], o));
        }
#pragma unroll
        for (int h = 0; h < 2; h++) {
          const float n0 = -mx[2 * h] * SCL, n1 = -mx[2 * h + 1] * SCL;
          const uint32_t pa = pack2(ex2(fmaf(l[h][0], SCL, n0)), ex2(fmaf(l[h][1], SCL, n0))), pb = pack2(ex2(fmaf(l[h][2], SCL, n1)), ex2(fmaf(l[h][3], SCL, n1)));
          float sm[4];
          mma8z(sm, pa, pb, 0x3f803f80u);
          const float ia = rcp(sm[0]), ib = rcp(sm[2]);
#pragma unroll
          for (int i = 8 * b + 4 * h; i < 8 * b + 4 * h + 4; i += 2) {
            uint32_t of[4];
#pragma unroll
            for (int d = 0; d < 2; d++) {
              float o[4];
              mma16z(o, pa & ~mup, pb & mup, 0u, pb & ~mup, vf[2 * (i + d)], vf[2 * (i + d) + 1]);
              mma8(o, pa & mup, 0u, pv[2 * i + 2 + d]);
              of[2 * d] = pack2(o[0] * ia, o[1] * ia); of[2 * d + 1] = pack2(o[2] * ib, o[3] * ib);
            }
            stsm4(stg_row + b * BLK + ((((i & 7) + (lane >> 4)) ^ (lane & 7)) << 4), of[0], of[1], of[2], of[3]);
          }
        }
        stage_done(sb, wg, b, lane);
        if (b == 0) gz += __float_as_uint(lds32f(bar + ZERO));
      }
      named_bar(1, 256);
      if (warp == 0) TR(8);
    }
    uint32_t pk[64];
    {
      float acc[64];
      mainloop<128, 6, 0>(acc, 16, true, r6, sb, wg, lane, rel, bid * 192 + 32, none, none, [&] {
        mbar_wait(bar + B_MOD, 0); mbar_wait(bar + B_X, 1); mbar_wait(bar + B_X + 8, 1);
        load_vec(pk + 32, sb, 2, 0, lane); load_vec(pk + 40, sb, 2, 1, lane);
#pragma unroll
        for (int i = 0; i < 16; i += 2) ldsm4(stg_row + (i >> 3) * BLK + ((((i & 7) + (lane >> 4)) ^ (lane & 7)) << 4), pk[2 * i], pk[2 * i + 1], pk[2 * i + 2], pk[2 * i + 3]);
      });
      if (warp == 0) TR(9);
#pragma unroll
      for (int i = 0; i < 32; i++) {
        acc[2 * i] = fmaf(acc[2 * i], bf_lo(pk[32 + (i >> 1)]), bf_lo(pk[i]));
        acc[2 * i + 1] = fmaf(acc[2 * i + 1], bf_hi(pk[32 + (i >> 1)]), bf_hi(pk[i]));
      }
      ln_publish(acc, gs->stat + (16 + m) * 1024, j, row0, lane, ep);
      if (warp == 0) TR(36);
      mbar_wait(bar + B_FULL6 + 16, 1);
      if (lane < 2) mbar_arrive_cl(rel + B_EMPTY6 + 16);
      ring_next<6>(r6);
#pragma unroll
      for (int i = 0; i < 32; i++) { pk[i] = pack2(acc[2 * i], acc[2 * i + 1]); pk[32 + i] = 0; }
      ln_apply(acc, gs->stat + (16 + m) * 1024, row0, ep, sb, 3, 4, stg_row, wg, lane);
      named_bar(2 + wg, 128);
      if (warp == 0) TR(11);
    }
    auto swiglu = [&](int q, int uo, int par) {
      if ((q & 3) == 0 && par >= 0) mbar_wait(fre + 2 * q, par);
      uint32_t w[4];
#pragma unroll
      for (int u = 0; u < 4; u++) w[u] = silu_mul2(pk[4 * q + u], pk[uo + 4 * q + u]);
      stsm4(stg_row + (q >> 2) * BLK + ((((2 * q & 7) + (lane >> 4)) ^ (lane & 7)) << 4), w[0], w[1], w[2], w[3]);
    };
    r4.s = r4.wrap = 2;
#pragma unroll 1
    for (int t = 0; t < 3; t++) {
      float acc[128];
      mainloop<256, 4, 5>(acc, 16, t == 0, r4, sb, wg, lane, rel, bid * 192 + 48 + 16 * t, [&](auto ic) {
        if (t) {
          if (ic.v == 3 || ic.v == 5) stage_done(sb, wg, ic.v >> 2, lane);
          if (ic.v < 5) { swiglu(2 * ic.v - 2, 32, ~t & 1); swiglu(2 * ic.v - 1, 32, 0); }
        }
      }, [&](int it) {
#pragma unroll
        for (int i = 0; i < 8; i++)
          if (t == 0 && it == 6 + i) gs->x1[bid * 2048 + (i >> 2) * 1024 + warp * 128 + (i & 3) * 32 + lane] = make_uint4(pk[4 * i], pk[4 * i + 1], pk[4 * i + 2], pk[4 * i + 3]);
      }, [&] { if (t == 0) fence_async_global(); else if (t == 2) mbar_wait(bar + B_X, 0); });
      if (warp == 0) TR(12 + 2 * t);
#pragma unroll
      for (int i = 0; i < 64; i++) pk[i] = pack2(acc[2 * i], acc[2 * i + 1]);
      if (warp == 0) TR(13 + 2 * t);
    }
    uint32_t x1[32];
    {
      float acc[64];
      mainloop<128, 6, 12>(acc, 16, false, r6, sb, wg, lane, rel, bid * 192 + 96, [&](auto ic) {
        constexpr int b = ic.v > 6, q = ic.v - 6 * b;
        if (q == 1) {
#pragma unroll
          for (int i = 4 * b; i < 4 * b + 4; i++) { const uint4 x = lds128(sb + STG + b * BLK + warp * 2048 + (i & 3) * 512 + lane * 16); x1[4 * i] = x.x; x1[4 * i + 1] = x.y; x1[4 * i + 2] = x.z; x1[4 * i + 3] = x.w; }
          __syncwarp();
        } else if (q < 6) swiglu(4 * b + q - 2, 32, -1);
        else stage_done(sb, wg, b, lane);
      }, none, [] {});
      if (warp == 0) TR(18);
#pragma unroll
      for (int i = 0; i < 32; i++) pk[i] = pack2(acc[2 * i], acc[2 * i + 1]);
      if (warp == 0) TR(19);
    }
    {
      float acc[64];
      mainloop<128, 6, 5>(acc, 56, false, r6, sb, wg, lane, rel, bid * 192 + 112, [&](auto ic) {
        if (ic.v == 5) stage_done(sb, wg, 0, lane); else swiglu(ic.v - 1, 16, 1);
      }, none, [&] {
        if (TAILLAG && wg == 0 && lane == 0) mbar_arrive(bar + B_LAG);
        load_vec(pk + 32, sb, 5, 0, lane); load_vec(pk + 40, sb, 5, 1, lane);
        mbar_wait(fre, 0); mbar_wait(fre + 8, 1);
      });
      __syncwarp();
      cl_arrive_relaxed();
      if (warp == 0) TR(20);
#pragma unroll
      for (int i = 0; i < 16; i += 2) {
        uint32_t w[4];
#pragma unroll
        for (int u = 0; u < 4; u++) {
          const int q = 2 * i + u;
          w[u] = pack2(fmaf(acc[2 * q], bf_lo(pk[32 + (q >> 1)]), bf_lo(x1[q])), fmaf(acc[2 * q + 1], bf_hi(pk[32 + (q >> 1)]), bf_hi(x1[q])));
        }
        stsm4(stg_row + (i >> 3) * BLK + ((((i & 7) + (lane >> 4)) ^ (lane & 7)) << 4), w[0], w[1], w[2], w[3]);
        if ((i & 7) == 6) {
          fence_async_smem();
          named_bar(2 + wg, 128);
          if (wq == 0 && elect()) { tma_store_3d(&maps.out, sb + STG + (i >> 3) * BLK + wg * HALF, j * 128 + (i >> 3) * 64, m * 64, wg); bulk_commit(); }
          if (i < 8) x1[16] |= __float_as_uint(lds32f(bar + ZERO));
        }
      }
      if (wq == 0) bulk_wait_read();
      if (wq == 0) TR(40 + wg);
      if (tid == 0) gs->epoch[bid + 4] = ep;
      if (warp == 0) TR(21);
      cl_wait();
    }
  }
}

typedef CUresult (*EncodeFn)(CUtensorMap*, CUtensorMapDataType, cuuint32_t, void*, const cuuint64_t*, const cuuint64_t*, const cuuint32_t*, const cuuint32_t*,
                             CUtensorMapInterleave, CUtensorMapSwizzle, CUtensorMapL2promotion, CUtensorMapFloatOOBfill);

void make_map(EncodeFn fn, CUtensorMap* mp, const void* base, uint64_t d0, uint64_t d1, uint64_t d2, uint64_t s1, uint64_t s2, uint32_t b2, uint32_t b0 = 64) {
  cuuint64_t d[3] = {d0, d1, d2}, s[2] = {s1, s2};
  cuuint32_t b[3] = {b0, 64, b2}, e[3] = {1, 1, 1};
  fn(mp, CU_TENSOR_MAP_DATA_TYPE_BFLOAT16, 3, (void*)base, d, s, b, e, CU_TENSOR_MAP_INTERLEAVE_NONE, b0 == 64 ? CU_TENSOR_MAP_SWIZZLE_128B : CU_TENSOR_MAP_SWIZZLE_NONE,
     CU_TENSOR_MAP_L2_PROMOTION_L2_128B, CU_TENSOR_MAP_FLOAT_OOB_FILL_NONE);
}

__global__ void probe_kernel() {}
int max_clusters(int size) {
  cudaLaunchConfig_t cfg = {};
  cudaLaunchAttribute at;
  at.id = cudaLaunchAttributeClusterDimension; at.val.clusterDim.x = size; at.val.clusterDim.y = 1; at.val.clusterDim.z = 1;
  cfg.gridDim = dim3(size * 66); cfg.blockDim = dim3(384); cfg.dynamicSmemBytes = SMEM_BYTES; cfg.attrs = &at; cfg.numAttrs = 1;
  int n = 0;
  if (cudaOccupancyMaxActiveClusters(&n, probe_kernel, &cfg) != cudaSuccess) { cudaGetLastError(); return 0; }
  return n;
}

}

extern "C" void kernel_launch(void* const* d_in, const int* in_sizes, int n_in, void* d_out, int out_size) {
  static EncodeFn fn = nullptr;
  static int by_sm = 0;
  static Scratch* gs = nullptr;
  if (!fn) {
    void* p = nullptr; cudaDriverEntryPointQueryResult q;
    cudaGetDriverEntryPoint("cuTensorMapEncodeTiled", &p, cudaEnableDefault, &q);
    fn = (EncodeFn)p;
    cudaFuncSetAttribute(fused_kernel, cudaFuncAttributeMaxDynamicSharedMemorySize, SMEM_BYTES);
    int dev = 0, sms = 0;
    cudaGetSymbolAddress((void**)&gs, g_scratch);
    cudaGetDevice(&dev);
    cudaDeviceGetAttribute(&sms, cudaDevAttrMultiProcessorCount, dev);
    cudaFuncSetAttribute(probe_kernel, cudaFuncAttributeMaxDynamicSharedMemorySize, SMEM_BYTES);
    by_sm = BYSM && sms == 132 && max_clusters(2) == 66 && max_clusters(4) == 30 && max_clusters(6) == 17 && max_clusters(8) == 15;
  }
  Maps mp;
  make_map(fn, &mp.x, d_in[0], D_, S_ / 2, 2, 4096, 2048, 2);
  make_map(fn, &mp.out, d_out, D_, S_ / 2, 2, 4096, 2048, 1);
  make_map(fn, &mp.wqkv, d_in[1], 64, D_, 3 * D_ / 64, 3 * D_ * 2, 128, 2);
  make_map(fn, &mp.wo, d_in[2], 64, D_, D_ / 64, D_ * 2, 128, 2);
  make_map(fn, &mp.w1, d_in[4], 64, D_, F_ / 64, F_ * 2, 128, 2);
  make_map(fn, &mp.w3, d_in[5], 64, D_, F_ / 64, F_ * 2, 128, 2);
  make_map(fn, &mp.w1s, d_in[4], 64, D_, F_ / 64, F_ * 2, 128, 1);
  make_map(fn, &mp.w3s, d_in[5], 64, D_, F_ / 64, F_ * 2, 128, 1);
  make_map(fn, &mp.w2, d_in[6], 64, F_, D_ / 64, D_ * 2, 128, 2);
  make_map(fn, &mp.wmod, d_in[8], 256, D_, 24, 6 * D_ * 2, 512, 1, 256);
  fused_kernel<<<132, 384, SMEM_BYTES>>>((const bf16*)d_in[7], (const bf16*)d_in[8], gs, by_sm, mp);
}
```

```cpp
#include <cuda_runtime.h>
#include <cuda_bf16.h>
#include <cuda.h>
#include <stdint.h>

typedef __nv_bfloat16 bf16;

#define NPIECE 4
#define PSLEEP 300
#define XSLEEP 4000
#define XDELAY 2000
#define TAILLAG 5
#define HSLEEP 400
#define BYSM 1
namespace {

constexpr int S_ = 2048, D_ = 1024, F_ = 3584;
constexpr int BLK = 16384;
constexpr int HALF = 8192;
constexpr int RING = 196608;
constexpr int STG = RING;
constexpr int MISC = RING + 2 * BLK;
constexpr int SMEM_BYTES = MISC + 3072;
constexpr int B_FULL4 = 0, B_EMPTY4 = 32, B_FULL6 = 64, B_EMPTY6 = 112, B_RDY = 160, B_FREE = 176, B_LAG = 192, B_X = 208, B_MOD = 224, B_HALO = 232, B_OWN = 240, B_HH = 256, B_ALL = 272, B_HH2 = 288, ZERO = 296;
constexpr int MODV = 512;
constexpr int RED_OFF = 0;
constexpr float SCL = 0.17677669529663687f * 1.4426950408889634f;
constexpr int U_HH = 64;

struct Maps { CUtensorMap x, out, wqkv, wo, w1, w3, w1s, w3s, w2, wmod; };

struct Scratch {
  uint4 h[16 * 16 * 1024];
  uint4 o[16 * 16 * 1024];
  uint4 hh[16 * 56 * 1024];
  uint4 x1[128 * 8 * 256];
  uint4 stat[2 * 16 * 8 * 128];
  uint4 halo[16 * 8 * 2 * 512];
  uint2 modp[8 * 2 * 4 * 128];
  uint2 modv[4 * 1024];
  uint32_t flag[16 * 128];
  uint32_t epoch[132];
};
__device__ __align__(1024) Scratch g_scratch;
#define TR(i)
#define TRS(i)
#define STEP0 gs->flag

__device__ __forceinline__ void bail() { asm volatile("st.global.u32 [%0], %1;" :: "l"(0ull), "r"(0) : "memory"); }
__device__ __forceinline__ uint32_t smem_u32(const void* p) { return (uint32_t)__cvta_generic_to_shared(p); }
__device__ __forceinline__ void mbar_init(uint32_t bar, uint32_t cnt) { asm volatile("mbarrier.init.shared::cta.b64 [%0], %1;" :: "r"(bar), "r"(cnt) : "memory"); }
__device__ __forceinline__ void mbar_expect_tx(uint32_t bar, uint32_t bytes) { asm volatile("mbarrier.arrive.expect_tx.shared::cta.b64 _, [%0], %1;" :: "r"(bar), "r"(bytes) : "memory"); }
__device__ __forceinline__ void mbar_arrive(uint32_t bar) { asm volatile("mbarrier.arrive.shared::cta.b64 _, [%0];" :: "r"(bar) : "memory"); }
__device__ __forceinline__ void mbar_arrive_cl(uint32_t cl_addr) { asm volatile("mbarrier.arrive.shared::cluster.b64 _, [%0];" :: "r"(cl_addr) : "memory"); }
__device__ __forceinline__ uint32_t mapa(uint32_t addr, uint32_t cta) { uint32_t r; asm("mapa.shared::cluster.u32 %0, %1, %2;" : "=r"(r) : "r"(addr), "r"(cta)); return r; }
__device__ __forceinline__ void mbar_wait(uint32_t bar, uint32_t parity) {
  asm volatile("{\n.reg .pred p;\n.reg .b32 n;\n.reg .b64 z;\nmov.b32 n, 0;\nmov.b64 z, 0;\n"
               "W: add.u32 n, n, 1;\nsetp.gt.u32 p, n, 0x400000;\n@p st.global.u32 [z], n;\n"
               "mbarrier.try_wait.parity.shared::cta.b64 p, [%0], %1;\n@!p bra W;\n}" :: "r"(bar), "r"(parity) : "memory");
}
__device__ __forceinline__ void tma_3d(uint32_t dst, const CUtensorMap* m, uint32_t bar, int c0, int c1, int c2) {
  asm volatile("cp.async.bulk.tensor.3d.shared::cluster.global.mbarrier::complete_tx::bytes [%0], [%1, {%3, %4, %5}], [%2];" :: "r"(dst), "l"(m), "r"(bar), "r"(c0), "r"(c1), "r"(c2) : "memory");
}
__device__ __forceinline__ void tma_store_3d(const CUtensorMap* m, uint32_t src, int c0, int c1, int c2) {
  asm volatile("cp.async.bulk.tensor.3d.global.shared::cta.bulk_group [%0, {%2, %3, %4}], [%1];" :: "l"(m), "r"(src), "r"(c0), "r"(c1), "r"(c2) : "memory");
}
__device__ __forceinline__ void bulk_ld(uint32_t dst, const void* src, uint32_t bytes, uint32_t bar) {
  asm volatile("cp.async.bulk.shared::cluster.global.mbarrier::complete_tx::bytes [%0], [%1], %2, [%3];" :: "r"(dst), "l"(src), "r"(bytes), "r"(bar) : "memory");
}
__device__ __forceinline__ void bulk_ld_mc(uint32_t dst, const void* src, uint32_t bytes, uint32_t bar) {
  asm volatile("cp.async.bulk.shared::cluster.global.mbarrier::complete_tx::bytes.multicast::cluster [%0], [%1], %2, [%3], %4;" :: "r"(dst), "l"(src), "r"(bytes), "r"(bar), "h"((uint16_t)3) : "memory");
}
__device__ __forceinline__ void bulk_st(void* dst, uint32_t src, uint32_t bytes) {
  asm volatile("cp.async.bulk.global.shared::cta.bulk_group [%0], [%1], %2;" :: "l"(dst), "r"(src), "r"(bytes) : "memory");
}
__device__ __forceinline__ void bulk_commit() { asm volatile("cp.async.bulk.commit_group;" ::: "memory"); }
__device__ __forceinline__ void bulk_wait_read() { asm volatile("cp.async.bulk.wait_group.read 0;" ::: "memory"); }
__device__ __forceinline__ void bulk_wait_all() { asm volatile("cp.async.bulk.wait_group 0;" ::: "memory"); }
__device__ __forceinline__ void fence_async_global() { asm volatile("fence.proxy.async.global;" ::: "memory"); }
__device__ __forceinline__ void fence_async_smem() { asm volatile("fence.proxy.async.shared::cta;" ::: "memory"); }
__device__ __forceinline__ void wg_arrive() { asm volatile("wgmma.fence.sync.aligned;" ::: "memory"); }
__device__ __forceinline__ void wg_commit() { asm volatile("wgmma.commit_group.sync.aligned;" ::: "memory"); }
template <int N> __device__ __forceinline__ void wg_wait() { asm volatile("wgmma.wait_group.sync.aligned %0;" :: "n"(N) : "memory"); }
__device__ __forceinline__ void cl_arrive_relaxed() { asm volatile("barrier.cluster.arrive.relaxed.aligned;" ::: "memory"); }
__device__ __forceinline__ void cl_wait() { asm volatile("barrier.cluster.wait.acquire.aligned;" ::: "memory"); }
__device__ __forceinline__ bool elect() { uint32_t p; asm volatile("{\n.reg .pred p;\nelect.sync _|p, 0xffffffff;\nselp.u32 %0, 1, 0, p;\n}" : "=r"(p)); return p; }
__device__ __forceinline__ void named_bar(int id, int n) { asm volatile("bar.sync %0, %1;" :: "r"(id), "r"(n) : "memory"); }
__device__ __forceinline__ uint32_t pack2(float lo, float hi) { uint32_t r; asm("cvt.rn.bf16x2.f32 %0, %1, %2;" : "=r"(r) : "f"(hi), "f"(lo)); return r; }
__device__ __forceinline__ float bf_lo(uint32_t w) { return __uint_as_float(w << 16); }
__device__ __forceinline__ float bf_hi(uint32_t w) { return __uint_as_float(w & 0xffff0000u); }
__device__ __forceinline__ float bf_round(float v) { return __bfloat162float(__float2bfloat16_rn(v)); }
__device__ __forceinline__ void stsm4(uint32_t addr, uint32_t a, uint32_t b, uint32_t c, uint32_t d) {
  asm volatile("stmatrix.sync.aligned.m8n8.x4.shared.b16 [%0], {%1, %2, %3, %4};" :: "r"(addr), "r"(a), "r"(b), "r"(c), "r"(d) : "memory");
}
__device__ __forceinline__ void ldsm4(uint32_t addr, uint32_t& a, uint32_t& b, uint32_t& c, uint32_t& d) {
  asm volatile("ldmatrix.sync.aligned.m8n8.x4.shared.b16 {%0, %1, %2, %3}, [%4];" : "=r"(a), "=r"(b), "=r"(c), "=r"(d) : "r"(addr) : "memory");
}
__device__ __forceinline__ uint32_t movm(uint32_t a) { uint32_t r; asm volatile("movmatrix.sync.aligned.m8n8.trans.b16 %0, %1;" : "=r"(r) : "r"(a)); return r; }
__device__ __forceinline__ void mma16(float (&d)[4], uint32_t a0, uint32_t a1, uint32_t a2, uint32_t a3, uint32_t b0, uint32_t b1) {
  asm("mma.sync.aligned.m16n8k16.row.col.f32.bf16.bf16.f32 {%0,%1,%2,%3}, {%4,%5,%6,%7}, {%8,%9}, {%0,%1,%2,%3};"
               : "+f"(d[0]), "+f"(d[1]), "+f"(d[2]), "+f"(d[3]) : "r"(a0), "r"(a1), "r"(a2), "r"(a3), "r"(b0), "r"(b1));
}
__device__ __forceinline__ void mma16z(float (&d)[4], uint32_t a0, uint32_t a1, uint32_t a2, uint32_t a3, uint32_t b0, uint32_t b1) {
  asm("mma.sync.aligned.m16n8k16.row.col.f32.bf16.bf16.f32 {%0,%1,%2,%3}, {%4,%5,%6,%7}, {%8,%9}, {%10,%10,%10,%10};"
      : "=f"(d[0]), "=f"(d[1]), "=f"(d[2]), "=f"(d[3]) : "r"(a0), "r"(a1), "r"(a2), "r"(a3), "r"(b0), "r"(b1), "f"(0.f));
}
__device__ __forceinline__ void mma8z(float (&d)[4], uint32_t a0, uint32_t a1, uint32_t b0) {
  asm("mma.sync.aligned.m16n8k8.row.col.f32.bf16.bf16.f32 {%0,%1,%2,%3}, {%4,%5}, {%6}, {%7,%7,%7,%7};"
      : "=f"(d[0]), "=f"(d[1]), "=f"(d[2]), "=f"(d[3]) : "r"(a0), "r"(a1), "r"(b0), "f"(0.f));
}
__device__ __forceinline__ void mma8(float (&d)[4], uint32_t a0, uint32_t a1, uint32_t b0) {
  asm("mma.sync.aligned.m16n8k8.row.col.f32.bf16.bf16.f32 {%0,%1,%2,%3}, {%4,%5}, {%6}, {%0,%1,%2,%3};"
               : "+f"(d[0]), "+f"(d[1]), "+f"(d[2]), "+f"(d[3]) : "r"(a0), "r"(a1), "r"(b0));
}
__device__ __forceinline__ uint4 lds128(uint32_t a) { uint4 v; asm volatile("ld.shared.v4.u32 {%0,%1,%2,%3}, [%4];" : "=r"(v.x), "=r"(v.y), "=r"(v.z), "=r"(v.w) : "r"(a) : "memory"); return v; }
__device__ __forceinline__ void sts128(uint32_t a, uint32_t x, uint32_t y, uint32_t z, uint32_t w) { asm volatile("st.shared.v4.u32 [%0], {%1,%2,%3,%4};" :: "r"(a), "r"(x), "r"(y), "r"(z), "r"(w) : "memory"); }
__device__ __forceinline__ float lds32f(uint32_t a) { float v; asm volatile("ld.shared.f32 %0, [%1];" : "=f"(v) : "r"(a) : "memory"); return v; }
__device__ __forceinline__ void sts16(uint32_t a, bf16 v) { asm volatile("st.shared.b16 [%0], %1;" :: "r"(a), "h"(__bfloat16_as_ushort(v)) : "memory"); }
__device__ __forceinline__ uint4 ldg_nc(const void* p) { uint4 v; asm volatile("ld.global.nc.L1::no_allocate.v4.u32 {%0,%1,%2,%3}, [%4];" : "=r"(v.x), "=r"(v.y), "=r"(v.z), "=r"(v.w) : "l"(p)); return v; }
__device__ __forceinline__ uint4 ld_rlx4(const uint4* p) {
  unsigned long long a, b; asm volatile("ld.relaxed.gpu.global.v2.b64 {%0,%1}, [%2];" : "=l"(a), "=l"(b) : "l"(p) : "memory");
  return make_uint4((uint32_t)a, (uint32_t)(a >> 32), (uint32_t)b, (uint32_t)(b >> 32));
}
__device__ __forceinline__ uint2 ld_rlx2(const uint2* p) { unsigned long long a; asm volatile("ld.relaxed.gpu.global.b64 %0, [%1];" : "=l"(a) : "l"(p) : "memory"); return make_uint2((uint32_t)a, (uint32_t)(a >> 32)); }
__device__ __forceinline__ void st_rlx4(uint4* p, uint32_t x, uint32_t y, uint32_t z, uint32_t w) {
  asm volatile("st.relaxed.gpu.global.v2.b64 [%0], {%1,%2};" :: "l"(p), "l"((unsigned long long)x | ((unsigned long long)y << 32)), "l"((unsigned long long)z | ((unsigned long long)w << 32)) : "memory");
}
__device__ __forceinline__ void st_rlx2(uint2* p, uint32_t x, uint32_t y) { asm volatile("st.relaxed.gpu.global.b64 [%0], %1;" :: "l"(p), "l"((unsigned long long)x | ((unsigned long long)y << 32)) : "memory"); }
__device__ __forceinline__ void st_release(uint32_t* p, uint32_t v) { asm volatile("st.release.gpu.global.u32 [%0], %1;" :: "l"(p), "r"(v) : "memory"); }
__device__ __forceinline__ uint32_t ld_acquire(const uint32_t* p) { uint32_t v; asm volatile("ld.acquire.gpu.global.u32 %0, [%1];" : "=r"(v) : "l"(p) : "memory"); return v; }
__device__ __forceinline__ void prefetch_map(const CUtensorMap* m) { asm volatile("prefetch.tensormap [%0];" :: "l"(m) : "memory"); }
__device__ __forceinline__ float rcp(float x) { float r; asm("rcp.approx.ftz.f32 %0, %1;" : "=f"(r) : "f"(x)); return r; }
__device__ __forceinline__ float ex2(float x) { float r; asm("ex2.approx.ftz.f32 %0, %1;" : "=f"(r) : "f"(x)); return r; }
__device__ __forceinline__ float tanh_fast(float x) { float r; asm("tanh.approx.f32 %0, %1;" : "=f"(r) : "f"(x)); return r; }
#define SPIN_GUARD(n) if (++(n) > (1u << 24)) bail()

__device__ __forceinline__ void wgmma_n128(float (&d)[64], uint64_t da, uint64_t db) {
  asm volatile("wgmma.mma_async.sync.aligned.m64n128k16.f32.bf16.bf16 "
    "{%0, %1, %2, %3, %4, %5, %6, %7, %8, %9, %10, %11, %12, %13, %14, %15, %16, %17, %18, %19, %20, %21, %22, %23, %24, %25, %26, %27, %28, %29, %30, %31, %32, %33, %34, %35, %36, %37, %38, %39, %40, %41, %42, %43, %44, %45, %46, %47, %48, %49, %50, %51, %52, %53, %54, %55, %56, %57, %58, %59, %60, %61, %62, %63}, "
    "%64, %65, 1, 1, 1, 0, 1;\n"
    : "+f"(d[0]), "+f"(d[1]), "+f"(d[2]), "+f"(d[3]), "+f"(d[4]), "+f"(d[5]), "+f"(d[6]), "+f"(d[7]), "+f"(d[8]), "+f"(d[9]), "+f"(d[10]), "+f"(d[11]), "+f"(d[12]), "+f"(d[13]), "+f"(d[14]), "+f"(d[15]), "+f"(d[16]), "+f"(d[17]), "+f"(d[18]), "+f"(d[19]), "+f"(d[20]), "+f"(d[21]), "+f"(d[22]), "+f"(d[23]), "+f"(d[24]), "+f"(d[25]), "+f"(d[26]), "+f"(d[27]), "+f"(d[28]), "+f"(d[29]), "+f"(d[30]), "+f"(d[31]), "+f"(d[32]), "+f"(d[33]), "+f"(d[34]), "+f"(d[35]), "+f"(d[36]), "+f"(d[37]), "+f"(d[38]), "+f"(d[39]), "+f"(d[40]), "+f"(d[41]), "+f"(d[42]), "+f"(d[43]), "+f"(d[44]), "+f"(d[45]), "+f"(d[46]), "+f"(d[47]), "+f"(d[48]), "+f"(d[49]), "+f"(d[50]), "+f"(d[51]), "+f"(d[52]), "+f"(d[53]), "+f"(d[54]), "+f"(d[55]), "+f"(d[56]), "+f"(d[57]), "+f"(d[58]), "+f"(d[59]), "+f"(d[60]), "+f"(d[61]), "+f"(d[62]), "+f"(d[63])
    : "l"(da), "l"(db));
}
__device__ __forceinline__ void wgmma_n128_first(float (&d)[64], uint64_t da, uint64_t db) {
  asm volatile("wgmma.mma_async.sync.aligned.m64n128k16.f32.bf16.bf16 "
    "{%0, %1, %2, %3, %4, %5, %6, %7, %8, %9, %10, %11, %12, %13, %14, %15, %16, %17, %18, %19, %20, %21, %22, %23, %24, %25, %26, %27, %28, %29, %30, %31, %32, %33, %34, %35, %36, %37, %38, %39, %40, %41, %42, %43, %44, %45, %46, %47, %48, %49, %50, %51, %52, %53, %54, %55, %56, %57, %58, %59, %60, %61, %62, %63}, "
    "%64, %65, 0, 1, 1, 0, 1;\n"
    : "=f"(d[0]), "=f"(d[1]), "=f"(d[2]), "=f"(d[3]), "=f"(d[4]), "=f"(d[5]), "=f"(d[6]), "=f"(d[7]), "=f"(d[8]), "=f"(d[9]), "=f"(d[10]), "=f"(d[11]), "=f"(d[12]), "=f"(d[13]), "=f"(d[14]), "=f"(d[15]), "=f"(d[16]), "=f"(d[17]), "=f"(d[18]), "=f"(d[19]), "=f"(d[20]), "=f"(d[21]), "=f"(d[22]), "=f"(d[23]), "=f"(d[24]), "=f"(d[25]), "=f"(d[26]), "=f"(d[27]), "=f"(d[28]), "=f"(d[29]), "=f"(d[30]), "=f"(d[31]), "=f"(d[32]), "=f"(d[33]), "=f"(d[34]), "=f"(d[35]), "=f"(d[36]), "=f"(d[37]), "=f"(d[38]), "=f"(d[39]), "=f"(d[40]), "=f"(d[41]), "=f"(d[42]), "=f"(d[43]), "=f"(d[44]), "=f"(d[45]), "=f"(d[46]), "=f"(d[47]), "=f"(d[48]), "=f"(d[49]), "=f"(d[50]), "=f"(d[51]), "=f"(d[52]), "=f"(d[53]), "=f"(d[54]), "=f"(d[55]), "=f"(d[56]), "=f"(d[57]), "=f"(d[58]), "=f"(d[59]), "=f"(d[60]), "=f"(d[61]), "=f"(d[62]), "=f"(d[63])
    : "l"(da), "l"(db));
}
__device__ __forceinline__ void wgmma_n256(float (&d)[128], uint64_t da, uint64_t db) {
  asm volatile("wgmma.mma_async.sync.aligned.m64n256k16.f32.bf16.bf16 "
    "{%0, %1, %2, %3, %4, %5, %6, %7, %8, %9, %10, %11, %12, %13, %14, %15, %16, %17, %18, %19, %20, %21, %22, %23, %24, %25, %26, %27, %28, %29, %30, %31, %32, %33, %34, %35, %36, %37, %38, %39, %40, %41, %42, %43, %44, %45, %46, %47, %48, %49, %50, %51, %52, %53, %54, %55, %56, %57, %58, %59, %60, %61, %62, %63, %64, %65, %66, %67, %68, %69, %70, %71, %72, %73, %74, %75, %76, %77, %78, %79, %80, %81, %82, %83, %84, %85, %86, %87, %88, %89, %90, %91, %92, %93, %94, %95, %96, %97, %98, %99, %100, %101, %102, %103, %104, %105, %106, %107, %108, %109, %110, %111, %112, %113, %114, %115, %116, %117, %118, %119, %120, %121, %122, %123, %124, %125, %126, %127}, "
    "%128, %129, 1, 1, 1, 0, 1;\n"
    : "+f"(d[0]), "+f"(d[1]), "+f"(d[2]), "+f"(d[3]), "+f"(d[4]), "+f"(d[5]), "+f"(d[6]), "+f"(d[7]), "+f"(d[8]), "+f"(d[9]), "+f"(d[10]), "+f"(d[11]), "+f"(d[12]), "+f"(d[13]), "+f"(d[14]), "+f"(d[15]), "+f"(d[16]), "+f"(d[17]), "+f"(d[18]), "+f"(d[19]), "+f"(d[20]), "+f"(d[21]), "+f"(d[22]), "+f"(d[23]), "+f"(d[24]), "+f"(d[25]), "+f"(d[26]), "+f"(d[27]), "+f"(d[28]), "+f"(d[29]), "+f"(d[30]), "+f"(d[31]), "+f"(d[32]), "+f"(d[33]), "+f"(d[34]), "+f"(d[35]), "+f"(d[36]), "+f"(d[37]), "+f"(d[38]), "+f"(d[39]), "+f"(d[40]), "+f"(d[41]), "+f"(d[42]), "+f"(d[43]), "+f"(d[44]), "+f"(d[45]), "+f"(d[46]), "+f"(d[47]), "+f"(d[48]), "+f"(d[49]), "+f"(d[50]), "+f"(d[51]), "+f"(d[52]), "+f"(d[53]), "+f"(d[54]), "+f"(d[55]), "+f"(d[56]), "+f"(d[57]), "+f"(d[58]), "+f"(d[59]), "+f"(d[60]), "+f"(d[61]), "+f"(d[62]), "+f"(d[63]), "+f"(d[64]), "+f"(d[65]), "+f"(d[66]), "+f"(d[67]), "+f"(d[68]), "+f"(d[69]), "+f"(d[70]), "+f"(d[71]), "+f"(d[72]), "+f"(d[73]), "+f"(d[74]), "+f"(d[75]), "+f"(d[76]), "+f"(d[77]), "+f"(d[78]), "+f"(d[79]), "+f"(d[80]), "+f"(d[81]), "+f"(d[82]), "+f"(d[83]), "+f"(d[84]), "+f"(d[85]), "+f"(d[86]), "+f"(d[87]), "+f"(d[88]), "+f"(d[89]), "+f"(d[90]), "+f"(d[91]), "+f"(d[92]), "+f"(d[93]), "+f"(d[94]), "+f"(d[95]), "+f"(d[96]), "+f"(d[97]), "+f"(d[98]), "+f"(d[99]), "+f"(d[100]), "+f"(d[101]), "+f"(d[102]), "+f"(d[103]), "+f"(d[104]), "+f"(d[105]), "+f"(d[106]), "+f"(d[107]), "+f"(d[108]), "+f"(d[109]), "+f"(d[110]), "+f"(d[111]), "+f"(d[112]), "+f"(d[113]), "+f"(d[114]), "+f"(d[115]), "+f"(d[116]), "+f"(d[117]), "+f"(d[118]), "+f"(d[119]), "+f"(d[120]), "+f"(d[121]), "+f"(d[122]), "+f"(d[123]), "+f"(d[124]), "+f"(d[125]), "+f"(d[126]), "+f"(d[127])
    : "l"(da), "l"(db));
}
__device__ __forceinline__ void wgmma_n256_first(float (&d)[128], uint64_t da, uint64_t db) {
  asm volatile("wgmma.mma_async.sync.aligned.m64n256k16.f32.bf16.bf16 "
    "{%0, %1, %2, %3, %4, %5, %6, %7, %8, %9, %10, %11, %12, %13, %14, %15, %16, %17, %18, %19, %20, %21, %22, %23, %24, %25, %26, %27, %28, %29, %30, %31, %32, %33, %34, %35, %36, %37, %38, %39, %40, %41, %42, %43, %44, %45, %46, %47, %48, %49, %50, %51, %52, %53, %54, %55, %56, %57, %58, %59, %60, %61, %62, %63, %64, %65, %66, %67, %68, %69, %70, %71, %72, %73, %74, %75, %76, %77, %78, %79, %80, %81, %82, %83, %84, %85, %86, %87, %88, %89, %90, %91, %92, %93, %94, %95, %96, %97, %98, %99, %100, %101, %102, %103, %104, %105, %106, %107, %108, %109, %110, %111, %112, %113, %114, %115, %116, %117, %118, %119, %120, %121, %122, %123, %124, %125, %126, %127}, "
    "%128, %129, 0, 1, 1, 0, 1;\n"
    : "=f"(d[0]), "=f"(d[1]), "=f"(d[2]), "=f"(d[3]), "=f"(d[4]), "=f"(d[5]), "=f"(d[6]), "=f"(d[7]), "=f"(d[8]), "=f"(d[9]), "=f"(d[10]), "=f"(d[11]), "=f"(d[12]), "=f"(d[13]), "=f"(d[14]), "=f"(d[15]), "=f"(d[16]), "=f"(d[17]), "=f"(d[18]), "=f"(d[19]), "=f"(d[20]), "=f"(d[21]), "=f"(d[22]), "=f"(d[23]), "=f"(d[24]), "=f"(d[25]), "=f"(d[26]), "=f"(d[27]), "=f"(d[28]), "=f"(d[29]), "=f"(d[30]), "=f"(d[31]), "=f"(d[32]), "=f"(d[33]), "=f"(d[34]), "=f"(d[35]), "=f"(d[36]), "=f"(d[37]), "=f"(d[38]), "=f"(d[39]), "=f"(d[40]), "=f"(d[41]), "=f"(d[42]), "=f"(d[43]), "=f"(d[44]), "=f"(d[45]), "=f"(d[46]), "=f"(d[47]), "=f"(d[48]), "=f"(d[49]), "=f"(d[50]), "=f"(d[51]), "=f"(d[52]), "=f"(d[53]), "=f"(d[54]), "=f"(d[55]), "=f"(d[56]), "=f"(d[57]), "=f"(d[58]), "=f"(d[59]), "=f"(d[60]), "=f"(d[61]), "=f"(d[62]), "=f"(d[63]), "=f"(d[64]), "=f"(d[65]), "=f"(d[66]), "=f"(d[67]), "=f"(d[68]), "=f"(d[69]), "=f"(d[70]), "=f"(d[71]), "=f"(d[72]), "=f"(d[73]), "=f"(d[74]), "=f"(d[75]), "=f"(d[76]), "=f"(d[77]), "=f"(d[78]), "=f"(d[79]), "=f"(d[80]), "=f"(d[81]), "=f"(d[82]), "=f"(d[83]), "=f"(d[84]), "=f"(d[85]), "=f"(d[86]), "=f"(d[87]), "=f"(d[88]), "=f"(d[89]), "=f"(d[90]), "=f"(d[91]), "=f"(d[92]), "=f"(d[93]), "=f"(d[94]), "=f"(d[95]), "=f"(d[96]), "=f"(d[97]), "=f"(d[98]), "=f"(d[99]), "=f"(d[100]), "=f"(d[101]), "=f"(d[102]), "=f"(d[103]), "=f"(d[104]), "=f"(d[105]), "=f"(d[106]), "=f"(d[107]), "=f"(d[108]), "=f"(d[109]), "=f"(d[110]), "=f"(d[111]), "=f"(d[112]), "=f"(d[113]), "=f"(d[114]), "=f"(d[115]), "=f"(d[116]), "=f"(d[117]), "=f"(d[118]), "=f"(d[119]), "=f"(d[120]), "=f"(d[121]), "=f"(d[122]), "=f"(d[123]), "=f"(d[124]), "=f"(d[125]), "=f"(d[126]), "=f"(d[127])
    : "l"(da), "l"(db));
}

template <int N> struct WG;
#define DEF_WG(N) template <> struct WG<N> { \
  static __device__ __forceinline__ void mma(float (&d)[N / 2], uint64_t a, uint64_t b) { wgmma_n##N(d, a, b); } \
  static __device__ __forceinline__ void first(float (&d)[N / 2], uint64_t a, uint64_t b) { wgmma_n##N##_first(d, a, b); } };
DEF_WG(128) DEF_WG(256)

constexpr uint64_t DESC_A = (1ull << 62) | ((uint64_t)(1024 >> 4) << 32) | (1ull << 16);
constexpr uint64_t DESC_B = (1ull << 62) | ((uint64_t)(1024 >> 4) << 32) | ((uint64_t)(8192 >> 4) << 16);

struct Ring { int s; uint32_t ph; int wrap; };
template <int NS> __device__ __forceinline__ void ring_next(Ring& r) { r.s = (r.s + 1 == NS) ? 0 : r.s + 1; if (r.s == r.wrap) r.ph ^= 1; }

__device__ __forceinline__ int own_order(int it, int j) {
  return it < 2 ? 2 * j + it : it < 4 ? 2 * (j ^ 1) + it - 2 : ((j >> 1) * 4 + 2 * it - (it < 10 ? 4 : 15)) & 15;
}

template <int V> struct IC { static constexpr int v = V; };
template <int I, int E, class F> __device__ __forceinline__ void static_for(F&& f) { if constexpr (I < E) { f(IC<I>{}); static_for<I + 1, E>(f); } }

template <int N, int NS, int PRE, class Pre, class Mid, class Last>
__device__ __forceinline__ void mainloop(float (&acc)[N / 2], int nkb, bool own, Ring& r, uint32_t sb, int wg, int lane, uint32_t rel_base, uint32_t* step0, Pre pre, Mid mid, Last last) {
  constexpr int SLOT = RING / NS;
  const uint32_t full = sb + MISC + (NS == 4 ? B_FULL4 : B_FULL6);
  const uint32_t rel = rel_base + (NS == 4 ? B_EMPTY4 : B_EMPTY6);
  const uint32_t s0 = (sb & 0x3FFFF) >> 4, a0 = s0 + wg * (HALF >> 4);
  int ps;
  auto issue = [&](int it, bool first) {
    const uint64_t da = DESC_A | (a0 + ((own && it < 2) ? (STG + it * BLK) >> 4 : r.s * (SLOT >> 4))), db = DESC_B | (s0 + r.s * (SLOT >> 4) + (BLK >> 4));
    mbar_wait(full + r.s * 8, r.ph);
    TRS(it);
    wg_arrive();
    if (first) WG<N>::first(acc, da, db); else WG<N>::mma(acc, da, db);
#pragma unroll
    for (int k = 1; k < 4; k++) WG<N>::mma(acc, da + k * 2, db + k * 128);
    wg_commit();
  };
  auto retire = [&](int it) {
    wg_wait<1>();
    if (lane < 2) mbar_arrive_cl(rel + ps * 8);
    if (own && it == 2 && lane == 0) mbar_arrive(sb + MISC + B_OWN);
    ps = r.s;
    ring_next<NS>(r);
  };
  issue(0, true);
  ps = r.s;
  ring_next<NS>(r);
  static_for<1, PRE + 1>([&](auto ic) { issue(ic.v, false); pre(ic); retire(ic.v); });
#pragma unroll 1
  for (int it = PRE + 1; it < nkb; it++) {
    if (TAILLAG && it == 56 - TAILLAG && wg == 1) mbar_wait(sb + MISC + B_LAG, 0);
    issue(it, false); mid(it); retire(it);
  }
  last();
  wg_wait<0>();
  if (lane < 2) mbar_arrive_cl(rel + ps * 8);
}

__device__ __forceinline__ void ln_publish(const float (&v)[64], uint4* st, int j, int row0, int lane, uint32_t ep) {
  float s0 = 0, s1 = 0, s2 = 0, s3 = 0, q0 = 0, q1 = 0, q2 = 0, q3 = 0;
#pragma unroll
  for (int i = 0; i < 16; i++) {
    s0 += v[4 * i]; s1 += v[4 * i + 1]; s2 += v[4 * i + 2]; s3 += v[4 * i + 3];
    q0 = fmaf(v[4 * i], v[4 * i], q0); q1 = fmaf(v[4 * i + 1], v[4 * i + 1], q1); q2 = fmaf(v[4 * i + 2], v[4 * i + 2], q2); q3 = fmaf(v[4 * i + 3], v[4 * i + 3], q3);
  }
  s0 += s1; s2 += s3; q0 += q1; q2 += q3;
  const bool odd = lane & 1;
  float s = (odd ? s2 : s0) + __shfl_xor_sync(~0u, odd ? s0 : s2, 1), q = (odd ? q2 : q0) + __shfl_xor_sync(~0u, odd ? q0 : q2, 1);
  s += __shfl_xor_sync(~0u, s, 2); q += __shfl_xor_sync(~0u, q, 2);
  if ((lane & 3) < 2) st_rlx4(st + j * 128 + row0 + (lane & 1) * 8, __float_as_uint(s), ep, __float_as_uint(q), ep);
}
__device__ __forceinline__ void ln_gather(const uint4* st, int row0, int lane, uint32_t ep, float& n0, float& r0, float& n1, float& r1) {
  const uint4* p = st + (lane & 2) * 256 + row0 + (lane & 1) * 8;
  uint4 a, b, c, d; uint32_t n = 0;
  while (true) {
    a = ld_rlx4(p); b = ld_rlx4(p + 128); c = ld_rlx4(p + 256); d = ld_rlx4(p + 384);
    if (a.y == ep && a.w == ep && b.y == ep && b.w == ep && c.y == ep && c.w == ep && d.y == ep && d.w == ep) break;
    SPIN_GUARD(n);
  }
  __syncwarp();
  float s = (__uint_as_float(a.x) + __uint_as_float(b.x)) + (__uint_as_float(c.x) + __uint_as_float(d.x));
  float q = (__uint_as_float(a.z) + __uint_as_float(b.z)) + (__uint_as_float(c.z) + __uint_as_float(d.z));
  s += __shfl_xor_sync(~0u, s, 2); q += __shfl_xor_sync(~0u, q, 2);
  s *= 1.f / 1024;
  const float r = rsqrtf(fmaxf(fmaf(-s, s, q * (1.f / 1024)), 0.f) + 1e-5f), nn = -s * r;
  const float ro = __shfl_xor_sync(~0u, r, 1), no = __shfl_xor_sync(~0u, nn, 1);
  const bool odd = lane & 1;
  r0 = odd ? ro : r; n0 = odd ? no : nn; r1 = odd ? r : ro; n1 = odd ? nn : no;
}
__device__ __forceinline__ void load_vec(uint32_t* w, uint32_t sb, int sec, int b, int lane) {
#pragma unroll
  for (int q = 0; q < 2; q++) { uint4 t = lds128(sb + MISC + MODV + sec * 256 + (lane & 3) * 64 + b * 32 + q * 16); w[4 * q] = t.x; w[4 * q + 1] = t.y; w[4 * q + 2] = t.z; w[4 * q + 3] = t.w; }
}
__device__ __forceinline__ void stage_done(uint32_t sb, int wg, int b, int lane) {
  fence_async_smem();
  __syncwarp();
  if (lane == 0) mbar_arrive(sb + MISC + B_RDY + b * 8);
}
__device__ __forceinline__ uint32_t hfma2(uint32_t a, uint32_t b, uint32_t c) { uint32_t r; asm("fma.rn.bf16x2 %0, %1, %2, %3;" : "=r"(r) : "r"(a), "r"(b), "r"(c)); return r; }
__device__ __forceinline__ void ln_apply(const float (&v)[64], const uint4* st, int row0, uint32_t ep, uint32_t sb, int sec_shift, int sec_scale, uint32_t stg_row, int wg, int lane) {
  uint32_t sc[16], sh[16];
#pragma unroll
  for (int b = 0; b < 2; b++) { load_vec(sc + 8 * b, sb, sec_scale, b, lane); load_vec(sh + 8 * b, sb, sec_shift, b, lane); }
  float n0, r0, n1, r1;
  ln_gather(st, row0, lane, ep, n0, r0, n1, r1);
#pragma unroll
  for (int i = 0; i < 16; i += 2) {
    if (i == 8) { const float z = lds32f(sb + MISC + ZERO); n0 += z; n1 += z; }
    uint32_t w[4];
#pragma unroll
    for (int u = 0; u < 2; u++) {
      int q = i + u;
      w[2 * u] = hfma2(pack2(fmaf(v[4 * q], r0, n0), fmaf(v[4 * q + 1], r0, n0)), sc[q], sh[q]);
      w[2 * u + 1] = hfma2(pack2(fmaf(v[4 * q + 2], r1, n1), fmaf(v[4 * q + 3], r1, n1)), sc[q], sh[q]);
    }
    stsm4(stg_row + (i >> 3) * BLK + ((((i & 7) + (lane >> 4)) ^ (lane & 7)) << 4), w[0], w[1], w[2], w[3]);
    if ((i & 7) == 6) stage_done(sb, wg, i >> 3, lane);
  }
}
__device__ __forceinline__ uint32_t hmul2(uint32_t a, uint32_t b) { uint32_t r; asm("mul.rn.bf16x2 %0, %1, %2;" : "=r"(r) : "r"(a), "r"(b)); return r; }
__device__ __forceinline__ uint32_t silu_mul2(uint32_t g, uint32_t u) {
  const uint32_t h = hmul2(g, 0x3f003f00u);
  const float h0 = bf_lo(h), h1 = bf_hi(h);
  return hmul2(pack2(fmaf(h0, tanh_fast(h0), h0), fmaf(h1, tanh_fast(h1), h1)), u);
}

__device__ __forceinline__ void gemv_fma(float (&a)[8], uint4 w, float s) {
  a[0] = fmaf(bf_lo(w.x), s, a[0]); a[1] = fmaf(bf_hi(w.x), s, a[1]); a[2] = fmaf(bf_lo(w.y), s, a[2]); a[3] = fmaf(bf_hi(w.y), s, a[3]);
  a[4] = fmaf(bf_lo(w.z), s, a[4]); a[5] = fmaf(bf_hi(w.z), s, a[5]); a[6] = fmaf(bf_lo(w.w), s, a[6]); a[7] = fmaf(bf_hi(w.w), s, a[7]);
}
__device__ __forceinline__ float silu_c(float v) { return bf_round(__fdividef(v, 1.f + __expf(-v))); }
__device__ __forceinline__ float mod_gather(const uint2* p, uint32_t ep) {
  uint2 a, b, c, d; uint32_t n = 0;
  while (true) {
    a = ld_rlx2(p); b = ld_rlx2(p + 128); c = ld_rlx2(p + 256); d = ld_rlx2(p + 384);
    if (a.y == ep && b.y == ep && c.y == ep && d.y == ep) break;
    SPIN_GUARD(n);
  }
  return (__uint_as_float(a.x) + __uint_as_float(b.x)) + (__uint_as_float(c.x) + __uint_as_float(d.x));
}
__device__ __forceinline__ void mod_store(uint32_t sb, int sec, int col, float v) {
  v = bf_round(v);
  if (sec == 1 || sec == 4) v += 1.f;
  sts16(sb + MISC + MODV + sec * 256 + (((col >> 1) & 3) * 16 + (col >> 3)) * 4 + (col & 1) * 2, __float2bfloat16_rn(v));
}

__global__ void __cluster_dims__(2, 1, 1) __launch_bounds__(384, 1)
fused_kernel(const bf16* __restrict__ cvec, const bf16* __restrict__ wmod, Scratch* gs, int by_sm, const __grid_constant__ Maps maps) {
  extern __shared__ __align__(1024) uint8_t smem_raw[];
  const uint32_t sb = smem_u32(smem_raw);
  const int warp = __shfl_sync(~0u, threadIdx.x >> 5, 0), lane = threadIdx.x & 31;
  const int rank = blockIdx.x & 1;
  uint32_t sm; asm("mov.u32 %0, %%smid;" : "=r"(sm));
  const int t = sm >> 1, v = t < 32 ? t : t < 60 ? t + 1 + (((t - 32) * 37) >> 8) : (t - 58) * 8;
  const int cid = !by_sm ? (blockIdx.x >> 1) - 2 : (t & ~1) == 60 ? t - 62 : (v & 1) * 32 + ((v >> 1) & 31);
  const bool extra = cid < 0;
  const int bid = cid * 2 + rank;
  const int m = cid >> 2, j = (cid & 3) * 2 + rank;
  const uint32_t bar = sb + MISC;

  if (warp >= 8) {
    asm volatile("setmaxnreg.dec.sync.aligned.u32 40;");
    if (extra) {
      if (warp == 8) {
        if (lane == 0) { for (int s = 0; s < 6; s++) { mbar_init(bar + B_FULL6 + s * 8, 1); mbar_init(bar + B_EMPTY6 + s * 8, 8); } fence_async_smem(); }
        __syncwarp();
        asm volatile("bar.arrive 2, 288;" ::: "memory");
        __nanosleep(XSLEEP);
#pragma unroll 1
        for (int it = 0, s = 0, par = 1; it < 64; it++) {
          mbar_wait(bar + B_EMPTY6 + s * 8, par);
          if (elect()) { mbar_expect_tx(bar + B_FULL6 + s * 8, 32768); tma_3d(sb + s * 32768, &maps.wmod, bar + B_FULL6 + s * 8, 0, (it & 15) * 64, 12 + (it >> 4) * 4 + bid); }
          if (++s == 6) { s = 0; par ^= 1; }
        }
      }
    } else if (warp < 10) {
      uint32_t s6 = 0, p6 = 1;
      auto next6 = [&]() { if (++s6 == 6) { s6 = 0; p6 ^= 1; } };
      auto drained4 = [&](int q, int late) { if (q < 5) mbar_wait(bar + B_EMPTY4 + (((late ? 0x10332 : 0x32110) >> (4 * q)) & 3) * 8, 1); };
      auto drained6 = [&](int q) { if (q < 3) mbar_wait(bar + B_EMPTY6 + ((0x154 >> (4 * q)) & 7) * 8, q >> 1); };
      auto skip6 = [&]() { mbar_wait(bar + B_EMPTY6 + s6 * 8, p6); if (elect()) mbar_arrive(bar + B_FULL6 + s6 * 8); next6(); };
      if (warp == 8) {
        const uint32_t t_start = clock();
        if (lane == 0) {
          if (sb & 1023) bail();
          for (int b = 0; b < 2; b++) mbar_init(bar + B_X + b * 8, 1);
          for (int s = 0; s < 4; s++) { mbar_init(bar + B_FULL4 + s * 8, 2); mbar_init(bar + B_EMPTY4 + s * 8, 16); }
          for (int s = 0; s < 6; s++) { mbar_init(bar + B_FULL6 + s * 8, 2); mbar_init(bar + B_EMPTY6 + s * 8, 16); }
          for (int b = 0; b < 2; b++) { mbar_init(bar + B_RDY + b * 8, 8); mbar_init(bar + B_FREE + b * 8, 1); mbar_init(bar + B_HH + b * 8, 1); }
          mbar_init(bar + B_MOD, 1); mbar_init(bar + B_LAG, 4); mbar_init(bar + B_HALO, 2); mbar_init(bar + B_ALL, 1); mbar_init(bar + B_HH2, 1); mbar_init(bar + B_OWN, 8);
          asm volatile("st.shared.u32 [%0], 0;" :: "r"(bar + ZERO) : "memory");
          asm volatile("fence.mbarrier_init.release.cluster;" ::: "memory");
          fence_async_smem();
        }
        __syncwarp();
        cl_arrive_relaxed();
        auto wide = [&](int s, int par, const CUtensorMap* m0, int a0, const CUtensorMap* m1, int a1, int kb) {
          const uint32_t full = bar + B_FULL4 + s * 8, d = sb + s * 49152 + BLK;
          mbar_wait(full + 32, par);
          if (elect()) { mbar_expect_tx(full, 2 * BLK); tma_3d(d, m0, full, 0, kb * 64, a0); tma_3d(d + BLK, m1, full, 0, kb * 64, a1); }
        };
        auto narrow = [&](const CUtensorMap* m0, int kb) {
          const uint32_t full = bar + B_FULL6 + s6 * 8;
          mbar_wait(full + 48, p6);
          if (elect()) { mbar_expect_tx(full, BLK); tma_3d(sb + s6 * 32768 + BLK, m0, full, 0, kb * 64, 2 * j); }
          next6();
        };
#pragma unroll 1
        for (int it = 0; it < 16; it++) {
          if (it == 0) {
            while ((uint32_t)clock() - t_start < XDELAY) {}
            if (elect()) for (int b = 0; b < 2; b++) { mbar_expect_tx(bar + B_X + b * 8, BLK); tma_3d(sb + STG + b * BLK, &maps.x, bar + B_X + b * 8, j * 128 + b * 64, m * 64, 0); }
            mbar_wait(bar + B_X + 8, 0);
          }
          wide(it & 3, ~(it >> 2) & 1, &maps.wqkv, 16 + 2 * j, &maps.wqkv, 32 + 2 * j, own_order(it, j));
        }
#pragma unroll 1
        for (int it = 0; it < 16; it++) { drained4(it, 0); narrow(&maps.wqkv, it); }
#pragma unroll 1
        for (int it = 0; it < 16; it++) {
          narrow(&maps.wo, own_order(it, j));
          if (it == 10) {
            mbar_wait(bar + B_OWN, 1); mbar_wait(bar + B_FREE + 8, 1);
            if (elect()) for (int b = 0; b < 2; b++) { mbar_expect_tx(bar + B_X + b * 8, BLK); tma_3d(sb + STG + b * BLK, &maps.x, bar + B_X + b * 8, j * 128 + b * 64, m * 64, 0); }
          }
        }
        skip6();
#pragma unroll 1
        for (int it = 0; it < 48; it++) {
          const int s = (it + 2) & 3, par = ~(it >> 2) & 1;
          drained6(it);
          wide(s, par, &maps.w1, (it & 48) + 2 * j, &maps.w3, (it & 48) + 2 * j, it < 16 ? own_order(it, j) : it & 15);
          if (it >= 44) {
            if (it == 44) { mbar_wait(bar + B_FREE, 0); mbar_wait(bar + B_FREE + 8, 0); if (elect()) mbar_expect_tx(bar + B_X, 2 * BLK); }
            if (elect()) bulk_ld(sb + STG + (it - 44) * HALF, gs->x1 + bid * 2048 + (it - 44) * 512, HALF, bar + B_X);
          }
        }
#pragma unroll 1
        for (int it = 0; it < 16; it++) {
          const uint32_t full = bar + B_FULL6 + s6 * 8, d = sb + s6 * 32768 + BLK;
          drained4(it, 1);
          mbar_wait(full + 48, p6);
          if (elect()) { mbar_expect_tx(full, BLK); tma_3d(d, &maps.w1s, full, 0, it * 64, 48 + j); tma_3d(d + HALF, &maps.w3s, full, 0, it * 64, 48 + j); }
          next6();
        }
#pragma unroll 1
        for (int it = 0; it < 56; it++) narrow(&maps.w2, it);
      } else {
        if (lane < 9) prefetch_map(&maps.x + lane);
        const uint32_t ep = gs->epoch[bid + 4] + 1;
        cl_arrive_relaxed(); cl_wait();
        auto plain = [&](uint32_t full, uint32_t empty, int par, uint32_t slot, const uint4* blk) {
          mbar_wait(empty, par);
          if (elect()) { mbar_expect_tx(full, BLK); bulk_ld_mc(slot + rank * HALF, blk + rank * 512, HALF, full); }
        };
        auto plain6 = [&](const uint4* blk) { plain(bar + B_FULL6 + s6 * 8, bar + B_EMPTY6 + s6 * 8, p6, sb + s6 * 32768, blk); next6(); };
        uint32_t ready = 0;
        auto poll = [&](int e) { ready = __ballot_sync(~0u, ld_acquire(gs->flag + m * 128 + e * 16 + (lane & 15)) == ep); };
        auto need = [&](int e, uint32_t mask) {
          if ((ready & mask) != mask) {
            uint32_t n = 0;
            do { poll(e); SPIN_GUARD(n); } while ((ready & mask) != mask);
            fence_async_global();
          }
        };
        auto fresh = [&](int e, int it, uint32_t full, uint32_t empty, int par, uint32_t slot, uint4* src) {
          if (it >= 4) {
            const int kb = own_order(it, j);
            if (it < 10) need(e, 1u << kb); else if (it == 10) mbar_wait(bar + B_ALL, e & 1);
            plain(full, empty, par, slot, src + kb * 1024);
          } else {
            if (it == 0) { poll(e); ready = 0; }
            mbar_wait(empty, par);
            if (it < 2) { if (elect()) mbar_arrive(full); }
            else {
              const int b = it & 1;
              const uint32_t to_peer = mapa(sb, rank ^ 1) - sb;
              if (elect()) mbar_expect_tx(full, BLK);
              mbar_wait(bar + (b ? B_FREE + 8 : B_RDY), e & 1);
              if (b == 0) TR(e == 0 ? 24 : e == 2 ? 30 : 44);
              if (elect()) {
                if (b == 0) {
                  bulk_st(src + 2 * j * 1024, sb + STG, BLK);
                  bulk_commit();
                  bulk_wait_all();
                  mbar_arrive(bar + B_FREE);
                }
                fence_async_global();
                bulk_ld(slot + to_peer, src + (2 * j + b) * 1024, BLK, full + to_peer);
              }
              __syncwarp();
            }
          }
          if (it == 4) TR(e == 0 ? 28 : e == 1 ? 46 : 34);
        };
#pragma unroll 1
        for (int ph = 0; ph < 2; ph++) {
          uint4* h = gs->h + m * 16384;
#pragma unroll 1
          for (int it = 0; it < 16; it++) {
            const int s = (it + 2 * ph) & 3;
            if (ph) drained6(it);
            fresh(2 * ph, it, bar + B_FULL4 + s * 8, bar + B_EMPTY4 + s * 8, ~(it >> 2) & 1, sb + s * 49152, h);
          }
          if (ph) {
#pragma unroll 1
            for (int it = 16; it < 48; it++) {
              const int s = (it + 2) & 3;
              const uint32_t full = bar + B_FULL4 + s * 8;
              plain(full, full + 32, ~(it >> 2) & 1, sb + s * 49152, h + (it & 15) * 1024);
            }
          }
#pragma unroll 1
          for (int it = 0; it < 16; it++) { drained4(it, ph); plain6(h + it * 1024); }
          if (!ph) {
#pragma unroll 1
            for (int it = 0; it < 16; it++) { fresh(1, it, bar + B_FULL6 + s6 * 8, bar + B_EMPTY6 + s6 * 8, p6, sb + s6 * 32768, gs->o + m * 16384); next6(); }
            skip6();
          }
        }
#pragma unroll 1
        for (int it = 0; it < 56; it++) {
          if (it == 0 || it == 32 || it == 48) mbar_wait(bar + (it == 48 ? B_HH2 : B_HH + (it >> 2)), 0);
          plain6(gs->hh + m * 57344 + it * 1024);
        }
      }
    } else {
      const int b = warp - 10;
      const uint32_t ep = gs->epoch[bid + 4] + 1;
      const uint32_t stg = sb + STG + b * BLK;
      cl_arrive_relaxed(); cl_wait();
      auto all_there = [&](int u, uint32_t done) {
        const uint32_t* fl = gs->flag + u;
        uint32_t n = 0;
        while (!__all_sync(~0u, ld_acquire(fl) == ep)) { __nanosleep(100); SPIN_GUARD(n); }
        fence_async_global();
        if (lane == 0) mbar_arrive(done);
      };
      auto fetch_mod = [&](int sec) {
        const uint4* p = (const uint4*)(gs->modv + (sec - 2) * 1024 + j * 128) + lane;
        uint4 v0, v1; uint32_t n = 0;
        while (true) {
          v0 = ld_rlx4(p); v1 = ld_rlx4(p + 32);
          if (v0.y == ep && v0.w == ep && v1.y == ep && v1.w == ep) break;
          SPIN_GUARD(n);
        }
        mod_store(sb, sec, 2 * lane, __uint_as_float(v0.x)); mod_store(sb, sec, 2 * lane + 1, __uint_as_float(v0.z));
        mod_store(sb, sec, 64 + 2 * lane, __uint_as_float(v1.x)); mod_store(sb, sec, 65 + 2 * lane, __uint_as_float(v1.z));
        __syncwarp();
      };
#pragma unroll 1
      for (int e = 0; e < 7 - b; e++) {
        if (lane == 0) {
          if (e < 3) {
            mbar_wait(bar + B_FREE, e & 1);
            if (b) {
              mbar_wait(bar + B_RDY + 8, e & 1);
              bulk_st((e == 1 ? gs->o : gs->h) + m * 16384 + (2 * j + 1) * 1024, stg, BLK);
              bulk_commit();
              bulk_wait_all();
              mbar_arrive(bar + B_FREE + 8);
              TR(53 + e);
            }
            st_release(gs->flag + m * 128 + e * 16 + 2 * j + b, ep);
            TR((e == 0 ? 26 : e == 2 ? 32 : 42) + b);
          } else {
            const int kb = (e < 6 ? 2 * (8 * (e - 3) + j) : 48 + j) + b;
            mbar_wait(bar + B_RDY + b * 8, e & 1);
#pragma unroll 1
            for (int q = 0; q < NPIECE; q++) { if (q) __nanosleep(PSLEEP); bulk_st(gs->hh + m * 57344 + kb * 1024 + q * (1024 / NPIECE), stg + q * (BLK / NPIECE), BLK / NPIECE); }
            bulk_commit();
            bulk_wait_all();
            mbar_arrive(bar + B_FREE + b * 8);
            st_release(gs->flag + m * 128 + U_HH + kb, ep);
          }
        }
        __syncwarp();
        if (e < 3 && b) all_there(m * 128 + e * 16 + (lane & 15), bar + B_ALL);
        if (e == 4 && b) all_there(m * 128 + U_HH + lane, bar + B_HH);
        if (!b && (e == 1 || e == 2)) {
#pragma unroll 1
          for (int sec = e == 1 ? 2 : 5; sec < 4 + e; sec++) fetch_mod(sec);
          if (e == 1) { if (lane == 0) mbar_arrive(bar + B_MOD); TR(50); }
        }
        if (e == 0) {
          mbar_wait(bar + B_EMPTY6 + 24, 0);
          if (HSLEEP) __nanosleep(HSLEEP);
#pragma unroll 1
          for (int w = 0; w < 4; w++) {
            const uint4* hp = gs->halo + ((m * 8 + j) * 2 + (w & 1)) * 512 + b * 256 + (w >> 1) * 128 + lane;
            uint4 q[4] = {}; uint32_t n = 0;
            while (m > 0) {
              bool ok = true;
#pragma unroll
              for (int i = 0; i < 4; i++) q[i] = ld_rlx4(hp + i * 32);
#pragma unroll
              for (int i = 0; i < 4; i++) ok = ok && q[i].y == ep && q[i].w == ep;
              if (ok) break;
              SPIN_GUARD(n);
            }
#pragma unroll
            for (int i = 0; i < 2; i++) sts128(stg + lane * 16 + (w & 1) * HALF + (w >> 1) * 1024 + i * 512, q[2 * i].x, q[2 * i + 1].x, q[2 * i].z, q[2 * i + 1].z);
          }
          __syncwarp();
          if (lane == 0) mbar_arrive(bar + B_HALO);
          if (b == 0) TR(52);
        }
      }
      if (b) { all_there(m * 128 + U_HH + 32 + (lane & 15), bar + B_HH + 8); all_there(m * 128 + U_HH + 48 + (lane & 7), bar + B_HH2); }
    }
  } else {
    const int wg = warp >> 2, wq = warp & 3, tid = threadIdx.x;
    const int g = lane >> 2, c = lane & 3;
    const int sec0 = (m >> 1) & 1, hf0 = m & 1, ks0 = (m >> 2) & 3;
    uint4 wv[8];
    uint32_t ep0; uint16_t cv_;
    asm volatile("ld.global.nc.u16 %0, [%1];" : "=h"(cv_) : "l"(cvec + ks0 * 256 + warp * 32 + lane));
    asm volatile("ld.global.u32 %0, [%1];" : "=r"(ep0) : "l"(gs->epoch + bid + 4));
    if (!extra) {
      const bf16* wp = wmod + (size_t)(ks0 * 256 + warp * 32 + (lane >> 3)) * 6144 + sec0 * 1024 + j * 128 + hf0 * 64 + (lane & 7) * 8;
#pragma unroll
      for (int i = 0; i < 8; i++) wv[i] = ldg_nc(wp + (size_t)i * 4 * 6144);
    }
    asm volatile("setmaxnreg.inc.sync.aligned.u32 232;" ::: "memory");
    if (__builtin_expect(extra, 0)) {
      const uint32_t ep = ep0 + 1;
      float sv[4];
#pragma unroll
      for (int p = 0; p < 4; p++) sv[p] = silu_c(__bfloat162float(cvec[64 * (4 * p + (lane >> 3)) + 8 * warp + (lane & 7)]));
      named_bar(2, 288);
      int s = 0, par = 0;
#pragma unroll 1
      for (int sec = 0; sec < 4; sec++) {
        float a[8] = {0, 0, 0, 0, 0, 0, 0, 0};
#pragma unroll 1
        for (int it = 0; it < 16; it++) {
          const float sc = it < 4 ? sv[0] : it < 8 ? sv[1] : it < 12 ? sv[2] : sv[3];
          mbar_wait(bar + B_FULL6 + s * 8, par);
          uint4 w[8];
#pragma unroll
          for (int i = 0; i < 8; i++) w[i] = lds128(sb + s * 32768 + (warp * 8 + i) * 512 + lane * 16);
#pragma unroll
          for (int i = 0; i < 8; i++) gemv_fma(a, w[i], __shfl_sync(~0u, sc, (it & 3) * 8 + i));
          if (lane == 0) mbar_arrive(bar + B_EMPTY6 + s * 8);
          if (++s == 6) { s = 0; par ^= 1; }
        }
        const uint32_t red = sb + STG + sec * 8192;
        sts128(red + warp * 1024 + lane * 32, __float_as_uint(a[0]), __float_as_uint(a[1]), __float_as_uint(a[2]), __float_as_uint(a[3]));
        sts128(red + warp * 1024 + lane * 32 + 16, __float_as_uint(a[4]), __float_as_uint(a[5]), __float_as_uint(a[6]), __float_as_uint(a[7]));
        named_bar(1, 256);
        float t = 0;
#pragma unroll
        for (int q = 0; q < 8; q++) t += lds32f(red + q * 1024 + tid * 4);
        st_rlx2(gs->modv + sec * 1024 + (bid + 4) * 256 + tid, __float_as_uint(t), ep);
      }
      if (tid == 0) gs->epoch[bid + 4] = ep;
      return;
    }
    if (warp == 0) TR(0);
    const int row0 = wg * 64 + wq * 16 + g;
    if (c < 2) st_rlx4(gs->stat + m * 1024 + j * 128 + row0 + c * 8, 0, 0, 0, 0);
    if (tid < 64) st_rlx2(gs->modp + ((j * 2 + sec0) * 4 + ks0) * 128 + hf0 * 64 + tid, 0, 0);
    cl_arrive_relaxed(); cl_wait();
    uint32_t ep;
    asm volatile("add.u32 %0, %1, 1;" : "=r"(ep) : "r"(ep0) : "memory");
    const float sc_ = silu_c(__uint_as_float((uint32_t)cv_ << 16));
    const uint32_t rel = mapa(bar, (lane & 1) ^ rank);
    const uint32_t stg_row = sb + STG + (wg * 64 + wq * 16 + (lane & 15)) * 128;
    const uint32_t fre = bar + B_FREE;
    Ring r4{0, 0, 0}, r6{0, 0, 0};
    auto none = [](auto) {};
    {
      float a[8] = {0, 0, 0, 0, 0, 0, 0, 0};
#pragma unroll
      for (int i = 0; i < 8; i++) gemv_fma(a, wv[i], __shfl_sync(~0u, sc_, i * 4 + (lane >> 3)));
#pragma unroll
      for (int i = 0; i < 8; i++) { a[i] += __shfl_xor_sync(~0u, a[i], 8); a[i] += __shfl_xor_sync(~0u, a[i], 16); }
      if (lane < 8) {
        sts128(sb + RED_OFF + warp * 256 + lane * 32, __float_as_uint(a[0]), __float_as_uint(a[1]), __float_as_uint(a[2]), __float_as_uint(a[3]));
        sts128(sb + RED_OFF + warp * 256 + lane * 32 + 16, __float_as_uint(a[4]), __float_as_uint(a[5]), __float_as_uint(a[6]), __float_as_uint(a[7]));
      }
      named_bar(1, 256);
      if (tid < 64) {
        float s = 0;
#pragma unroll
        for (int w = 0; w < 8; w++) s += lds32f(sb + RED_OFF + w * 256 + tid * 4);
        st_rlx2(gs->modp + ((j * 2 + sec0) * 4 + ks0) * 128 + hf0 * 64 + tid, __float_as_uint(s), ep);
      }
      if (warp == 0) TR(1);
      float v[64];
      mbar_wait(bar + B_X, 0); mbar_wait(bar + B_X + 8, 0);
#pragma unroll
      for (int i = 0; i < 16; i += 2) {
        uint32_t w0, w1, w2, w3;
        ldsm4(stg_row + (i >> 3) * BLK + ((((i & 7) + (lane >> 4)) ^ (lane & 7)) << 4), w0, w1, w2, w3);
        v[4 * i] = bf_lo(w0); v[4 * i + 1] = bf_hi(w0); v[4 * i + 2] = bf_lo(w1); v[4 * i + 3] = bf_hi(w1);
        v[4 * i + 4] = bf_lo(w2); v[4 * i + 5] = bf_hi(w2); v[4 * i + 6] = bf_lo(w3); v[4 * i + 7] = bf_hi(w3);
      }
      ln_publish(v, gs->stat + m * 1024, j, row0, lane, ep);
      if (warp == 0) TR(2);
      mod_store(sb, tid >> 7, tid & 127, mod_gather(gs->modp + (j * 2 + (tid >> 7)) * 512 + (tid & 127), ep));
      named_bar(1, 256);
      if (warp == 0) TR(3);
      ln_apply(v, gs->stat + m * 1024, row0, ep, sb, 0, 1, stg_row, wg, lane);
      named_bar(2 + wg, 128);
    }
    if (warp == 0) TR(4);
    {
      uint32_t kf[32], vf[32], pv[32];
      const bool first = wq == 0 && m == 0;
      const uint32_t xa = sb + STG + wg * HALF + wq * 2048 + lane * 16;
      {
        float acc[128];
        mainloop<256, 4, 0>(acc, 16, true, r4, sb, wg, lane, rel, STEP0 + 0, none, none, [&] {
          mbar_wait(fre + 8, 0);
          if (c < 2) st_rlx4(gs->stat + (16 + m) * 1024 + j * 128 + row0 + c * 8, 0, 0, 0, 0);
        });
        if (warp == 0) TR(5);
#pragma unroll
        for (int i = 0; i < 32; i++) { kf[i] = pack2(acc[2 * i], acc[2 * i + 1]); vf[i] = pack2(acc[64 + 2 * i], acc[65 + 2 * i]); }
      }
      if (warp == 0) TR(6);
      float acc[64];
      constexpr int QP = 2;
      mainloop<128, 6, 8 / QP>(acc, 16, false, r6, sb, wg, lane, rel, STEP0 + 16, [&](auto ic) {
        constexpr int q = (ic.v - 1) * QP;
#pragma unroll
        for (int i = 4 * q; i < 4 * (q + QP); i++) vf[i] = movm(vf[i]);
        if (wq == 3) {
          if (m < 15) {
            uint4* hp = gs->halo + (((m + 1) * 8 + j) * 2 + wg) * 512 + lane;
#pragma unroll
            for (int i = 2 * q; i < 2 * (q + QP); i++) st_rlx4(hp + i * 32, kf[2 * i + 1], ep, vf[2 * i + 1], ep);
          }
        } else {
#pragma unroll
          for (int i = q; i < q + QP; i++) sts128(xa + 2048 + (i >> 2) * BLK + (i & 3) * 512, kf[4 * i + 1], kf[4 * i + 3], vf[4 * i + 1], vf[4 * i + 3]);
        }
      }, none, [&] {
        named_bar(2 + wg, 128);
        if (wq == 0) mbar_wait(bar + B_HALO, 0);
#pragma unroll
        for (int i = 0; i < 8; i++) {
          uint4 q = lds128(xa + (i >> 2) * BLK + (i & 3) * 512);
          pv[4 * i] = q.x; pv[4 * i + 1] = q.y; pv[4 * i + 2] = q.z; pv[4 * i + 3] = q.w;
        }
        __syncwarp();
      });
      if (warp == 0) TR(7);
      int gz = g;
#pragma unroll
      for (int b = 0; b < 2; b++) {
        const bool up0 = 2 * c > gz, up1 = 2 * c + 1 > gz;
        const uint32_t mup = (up0 ? 0xffffu : 0u) | (up1 ? 0xffff0000u : 0u);
        float l[2][4], mx[4];
#pragma unroll
        for (int h = 0; h < 2; h++) {
          uint32_t q[8];
          const int k = 16 * b + 8 * h;
#pragma unroll
          for (int i = 0; i < 8; i++) q[i] = pack2(acc[2 * k + 2 * i], acc[2 * k + 2 * i + 1]);
          float s0[4], s1[4], s2[4];
          mma16z(s0, q[0], q[1], q[2], q[3], pv[k], pv[k + 1]); mma16z(s1, q[0], q[1], q[2], q[3], kf[k], kf[k + 2]); mma16z(s2, q[0], q[1], q[2], q[3], kf[k + 1], kf[k + 3]);
          mma16(s0, q[4], q[5], q[6], q[7], pv[k + 4], pv[k + 5]); mma16(s1, q[4], q[5], q[6], q[7], kf[k + 4], kf[k + 6]); mma16(s2, q[4], q[5], q[6], q[7], kf[k + 5], kf[k + 7]);
          if (first) { s0[0] = -INFINITY; s0[1] = -INFINITY; }
          l[h][0] = up0 ? s0[0] : s1[0]; l[h][1] = up1 ? s0[1] : s1[1]; l[h][2] = up0 ? s1[2] : s2[2]; l[h][3] = up1 ? s1[3] : s2[3];
          mx[2 * h] = fmaxf(l[h][0], l[h][1]); mx[2 * h + 1] = fmaxf(l[h][2], l[h][3]);
        }
#pragma unroll
        for (int o = 1; o < 4; o <<= 1) {
#pragma unroll
          for (int h = 0; h < 4; h++) mx[h] = fmaxf(mx[h], __shfl_xor_sync(~0u, mx[h], o));
        }
#pragma unroll
        for (int h = 0; h < 2; h++) {
          const float n0 = -mx[2 * h] * SCL, n1 = -mx[2 * h + 1] * SCL;
          const uint32_t pa = pack2(ex2(fmaf(l[h][0], SCL, n0)), ex2(fmaf(l[h][1], SCL, n0))), pb = pack2(ex2(fmaf(l[h][2], SCL, n1)), ex2(fmaf(l[h][3], SCL, n1)));
          float sm[4];
          mma8z(sm, pa, pb, 0x3f803f80u);
          const float ia = rcp(sm[0]), ib = rcp(sm[2]);
#pragma unroll
          for (int i = 8 * b + 4 * h; i < 8 * b + 4 * h + 4; i += 2) {
            uint32_t of[4];
#pragma unroll
            for (int d = 0; d < 2; d++) {
              float o[4];
              mma16z(o, pa & ~mup, pb & mup, 0u, pb & ~mup, vf[2 * (i + d)], vf[2 * (i + d) + 1]);
              mma8(o, pa & mup, 0u, pv[2 * i + 2 + d]);
              of[2 * d] = pack2(o[0] * ia, o[1] * ia); of[2 * d + 1] = pack2(o[2] * ib, o[3] * ib);
            }
            stsm4(stg_row + b * BLK + ((((i & 7) + (lane >> 4)) ^ (lane & 7)) << 4), of[0], of[1], of[2], of[3]);
          }
        }
        stage_done(sb, wg, b, lane);
        if (b == 0) gz += __float_as_uint(lds32f(bar + ZERO));
      }
      named_bar(1, 256);
      if (warp == 0) TR(8);
    }
    uint32_t pk[64];
    {
      float acc[64];
      mainloop<128, 6, 0>(acc, 16, true, r6, sb, wg, lane, rel, STEP0 + 32, none, none, [&] {
        mbar_wait(bar + B_MOD, 0); mbar_wait(bar + B_X, 1); mbar_wait(bar + B_X + 8, 1);
        load_vec(pk + 32, sb, 2, 0, lane); load_vec(pk + 40, sb, 2, 1, lane);
#pragma unroll
        for (int i = 0; i < 16; i += 2) ldsm4(stg_row + (i >> 3) * BLK + ((((i & 7) + (lane >> 4)) ^ (lane & 7)) << 4), pk[2 * i], pk[2 * i + 1], pk[2 * i + 2], pk[2 * i + 3]);
      });
      if (warp == 0) TR(9);
#pragma unroll
      for (int i = 0; i < 32; i++) {
        acc[2 * i] = fmaf(acc[2 * i], bf_lo(pk[32 + (i >> 1)]), bf_lo(pk[i]));
        acc[2 * i + 1] = fmaf(acc[2 * i + 1], bf_hi(pk[32 + (i >> 1)]), bf_hi(pk[i]));
      }
      ln_publish(acc, gs->stat + (16 + m) * 1024, j, row0, lane, ep);
      if (warp == 0) TR(36);
      mbar_wait(bar + B_FULL6 + 16, 1);
      if (lane < 2) mbar_arrive_cl(rel + B_EMPTY6 + 16);
      ring_next<6>(r6);
#pragma unroll
      for (int i = 0; i < 32; i++) { pk[i] = pack2(acc[2 * i], acc[2 * i + 1]); pk[32 + i] = 0; }
      ln_apply(acc, gs->stat + (16 + m) * 1024, row0, ep, sb, 3, 4, stg_row, wg, lane);
      named_bar(2 + wg, 128);
      if (warp == 0) TR(11);
    }
    auto swiglu = [&](int q, int uo, int par) {
      if ((q & 3) == 0 && par >= 0) mbar_wait(fre + 2 * q, par);
      uint32_t w[4];
#pragma unroll
      for (int u = 0; u < 4; u++) w[u] = silu_mul2(pk[4 * q + u], pk[uo + 4 * q + u]);
      stsm4(stg_row + (q >> 2) * BLK + ((((2 * q & 7) + (lane >> 4)) ^ (lane & 7)) << 4), w[0], w[1], w[2], w[3]);
    };
    r4.s = r4.wrap = 2;
#pragma unroll 1
    for (int t = 0; t < 3; t++) {
      float acc[128];
      mainloop<256, 4, 5>(acc, 16, t == 0, r4, sb, wg, lane, rel, STEP0 + 48 + 16 * t, [&](auto ic) {
        if (t) {
          if (ic.v == 3 || ic.v == 5) stage_done(sb, wg, ic.v >> 2, lane);
          if (ic.v < 5) { swiglu(2 * ic.v - 2, 32, ~t & 1); swiglu(2 * ic.v - 1, 32, 0); }
        }
      }, [&](int it) {
#pragma unroll
        for (int i = 0; i < 8; i++)
          if (t == 0 && it == 6 + i) gs->x1[bid * 2048 + (i >> 2) * 1024 + warp * 128 + (i & 3) * 32 + lane] = make_uint4(pk[4 * i], pk[4 * i + 1], pk[4 * i + 2], pk[4 * i + 3]);
      }, [&] { if (t == 0) fence_async_global(); else if (t == 2) mbar_wait(bar + B_X, 0); });
      if (warp == 0) TR(12 + 2 * t);
#pragma unroll
      for (int i = 0; i < 64; i++) pk[i] = pack2(acc[2 * i], acc[2 * i + 1]);
      if (warp == 0) TR(13 + 2 * t);
    }
    uint32_t x1[32];
    {
      float acc[64];
      mainloop<128, 6, 12>(acc, 16, false, r6, sb, wg, lane, rel, STEP0 + 96, [&](auto ic) {
        constexpr int b = ic.v > 6, q = ic.v - 6 * b;
        if (q == 1) {
#pragma unroll
          for (int i = 4 * b; i < 4 * b + 4; i++) { const uint4 x = lds128(sb + STG + b * BLK + warp * 2048 + (i & 3) * 512 + lane * 16); x1[4 * i] = x.x; x1[4 * i + 1] = x.y; x1[4 * i + 2] = x.z; x1[4 * i + 3] = x.w; }
          __syncwarp();
        } else if (q < 6) swiglu(4 * b + q - 2, 32, -1);
        else stage_done(sb, wg, b, lane);
      }, none, [] {});
      if (warp == 0) TR(18);
#pragma unroll
      for (int i = 0; i < 32; i++) pk[i] = pack2(acc[2 * i], acc[2 * i + 1]);
      if (warp == 0) TR(19);
    }
    {
      float acc[64];
      mainloop<128, 6, 5>(acc, 56, false, r6, sb, wg, lane, rel, STEP0 + 112, [&](auto ic) {
        if (ic.v == 5) stage_done(sb, wg, 0, lane); else swiglu(ic.v - 1, 16, 1);
      }, none, [&] {
        if (TAILLAG && wg == 0 && lane == 0) mbar_arrive(bar + B_LAG);
        load_vec(pk + 32, sb, 5, 0, lane); load_vec(pk + 40, sb, 5, 1, lane);
        mbar_wait(fre, 0); mbar_wait(fre + 8, 1);
      });
      __syncwarp();
      cl_arrive_relaxed();
      if (warp == 0) TR(20);
#pragma unroll
      for (int i = 0; i < 16; i += 2) {
        uint32_t w[4];
#pragma unroll
        for (int u = 0; u < 4; u++) {
          const int q = 2 * i + u;
          w[u] = pack2(fmaf(acc[2 * q], bf_lo(pk[32 + (q >> 1)]), bf_lo(x1[q])), fmaf(acc[2 * q + 1], bf_hi(pk[32 + (q >> 1)]), bf_hi(x1[q])));
        }
        stsm4(stg_row + (i >> 3) * BLK + ((((i & 7) + (lane >> 4)) ^ (lane & 7)) << 4), w[0], w[1], w[2], w[3]);
        if ((i & 7) == 6) {
          fence_async_smem();
          named_bar(2 + wg, 128);
          if (wq == 0 && elect()) { tma_store_3d(&maps.out, sb + STG + (i >> 3) * BLK + wg * HALF, j * 128 + (i >> 3) * 64, m * 64, wg); bulk_commit(); }
          if (i < 8) x1[16] |= __float_as_uint(lds32f(bar + ZERO));
        }
      }
      if (wq == 0) bulk_wait_read();
      if (wq == 0) TR(40 + wg);
      if (tid == 0) gs->epoch[bid + 4] = ep;
      if (warp == 0) TR(21);
      cl_wait();
    }
  }
}

typedef CUresult (*EncodeFn)(CUtensorMap*, CUtensorMapDataType, cuuint32_t, void*, const cuuint64_t*, const cuuint64_t*, const cuuint32_t*, const cuuint32_t*,
                             CUtensorMapInterleave, CUtensorMapSwizzle, CUtensorMapL2promotion, CUtensorMapFloatOOBfill);

void make_map(EncodeFn fn, CUtensorMap* mp, const void* base, uint64_t d0, uint64_t d1, uint64_t d2, uint64_t s1, uint64_t s2, uint32_t b2, uint32_t b0 = 64) {
  cuuint64_t d[3] = {d0, d1, d2}, s[2] = {s1, s2};
  cuuint32_t b[3] = {b0, 64, b2}, e[3] = {1, 1, 1};
  fn(mp, CU_TENSOR_MAP_DATA_TYPE_BFLOAT16, 3, (void*)base, d, s, b, e, CU_TENSOR_MAP_INTERLEAVE_NONE, b0 == 64 ? CU_TENSOR_MAP_SWIZZLE_128B : CU_TENSOR_MAP_SWIZZLE_NONE,
     CU_TENSOR_MAP_L2_PROMOTION_L2_128B, CU_TENSOR_MAP_FLOAT_OOB_FILL_NONE);
}

__global__ void probe_kernel() {}
int max_clusters(int size) {
  cudaLaunchConfig_t cfg = {};
  cudaLaunchAttribute at;
  at.id = cudaLaunchAttributeClusterDimension; at.val.clusterDim.x = size; at.val.clusterDim.y = 1; at.val.clusterDim.z = 1;
  cfg.gridDim = dim3(size * 66); cfg.blockDim = dim3(384); cfg.dynamicSmemBytes = SMEM_BYTES; cfg.attrs = &at; cfg.numAttrs = 1;
  int n = 0;
  if (cudaOccupancyMaxActiveClusters(&n, probe_kernel, &cfg) != cudaSuccess) { cudaGetLastError(); return 0; }
  return n;
}

}

extern "C" void kernel_launch(void* const* d_in, const int* in_sizes, int n_in, void* d_out, int out_size) {
  static EncodeFn fn = nullptr;
  static int by_sm = 0;
  static Scratch* gs = nullptr;
  if (!fn) {
    void* p = nullptr; cudaDriverEntryPointQueryResult q;
    cudaGetDriverEntryPoint("cuTensorMapEncodeTiled", &p, cudaEnableDefault, &q);
    fn = (EncodeFn)p;
    cudaFuncSetAttribute(fused_kernel, cudaFuncAttributeMaxDynamicSharedMemorySize, SMEM_BYTES);
    int dev = 0, sms = 0;
    cudaGetSymbolAddress((void**)&gs, g_scratch);
    cudaGetDevice(&dev);
    cudaDeviceGetAttribute(&sms, cudaDevAttrMultiProcessorCount, dev);
    cudaFuncSetAttribute(probe_kernel, cudaFuncAttributeMaxDynamicSharedMemorySize, SMEM_BYTES);
    by_sm = BYSM && sms == 132 && max_clusters(2) == 66 && max_clusters(4) == 30 && max_clusters(6) == 17 && max_clusters(8) == 15;
  }
  Maps mp;
  make_map(fn, &mp.x, d_in[0], D_, S_ / 2, 2, 4096, 2048, 2);
  make_map(fn, &mp.out, d_out, D_, S_ / 2, 2, 4096, 2048, 1);
  make_map(fn, &mp.wqkv, d_in[1], 64, D_, 3 * D_ / 64, 3 * D_ * 2, 128, 2);
  make_map(fn, &mp.wo, d_in[2], 64, D_, D_ / 64, D_ * 2, 128, 2);
  make_map(fn, &mp.w1, d_in[4], 64, D_, F_ / 64, F_ * 2, 128, 2);
  make_map(fn, &mp.w3, d_in[5], 64, D_, F_ / 64, F_ * 2, 128, 2);
  make_map(fn, &mp.w1s, d_in[4], 64, D_, F_ / 64, F_ * 2, 128, 1);
  make_map(fn, &mp.w3s, d_in[5], 64, D_, F_ / 64, F_ * 2, 128, 1);
  make_map(fn, &mp.w2, d_in[6], 64, F_, D_ / 64, D_ * 2, 128, 2);
  make_map(fn, &mp.wmod, d_in[8], 256, D_, 24, 6 * D_ * 2, 512, 1, 256);
  fused_kernel<<<132, 384, SMEM_BYTES>>>((const bf16*)d_in[7], (const bf16*)d_in[8], gs, by_sm, mp);
}
```

```cpp
#include <cuda_runtime.h>
#include <cuda_bf16.h>
#include <cuda.h>
#include <stdint.h>

typedef __nv_bfloat16 bf16;

#define NPIECE 4
#define PSLEEP 300
#define XSLEEP 4000
#define XDELAY 2000
#define TAILLAG 5
#define HSLEEP 400
#define XRE 12
#define B1D 900
#define KEEPX 0
#define BYSM 1
namespace {

constexpr int S_ = 2048, D_ = 1024, F_ = 3584;
constexpr int BLK = 16384;
constexpr int HALF = 8192;
constexpr int RING = 196608;
constexpr int STG = RING;
constexpr int MISC = RING + 2 * BLK;
constexpr int SMEM_BYTES = MISC + 3072;
constexpr int B_FULL4 = 0, B_EMPTY4 = 32, B_FULL6 = 64, B_EMPTY6 = 112, B_RDY = 160, B_FREE = 176, B_LAG = 192, B_X = 208, B_MOD = 224, B_HALO = 232, B_OWN = 240, B_HH = 256, B_ALL = 272, B_HH2 = 288, ZERO = 296;
constexpr int MODV = 512;
constexpr int RED_OFF = 0;
constexpr float SCL = 0.17677669529663687f * 1.4426950408889634f;
constexpr int U_HH = 64;

struct Maps { CUtensorMap x, out, wqkv, wo, w1, w3, w1s, w3s, w2, wmod; };

struct Scratch {
  uint4 h[16 * 16 * 1024];
  uint4 o[16 * 16 * 1024];
  uint4 hh[16 * 56 * 1024];
  uint4 x1[128 * 8 * 256];
  uint4 stat[2 * 16 * 8 * 128];
  uint4 halo[16 * 8 * 2 * 512];
  uint2 modp[8 * 2 * 4 * 128];
  uint2 modv[4 * 1024];
  uint32_t flag[16 * 128];
  uint32_t epoch[132];
};
__device__ __align__(1024) Scratch g_scratch;
#define TR(i)
#define TRS(i)
#define STEP0 gs->flag

__device__ __forceinline__ void bail() { asm volatile("st.global.u32 [%0], %1;" :: "l"(0ull), "r"(0) : "memory"); }
__device__ __forceinline__ uint32_t smem_u32(const void* p) { return (uint32_t)__cvta_generic_to_shared(p); }
__device__ __forceinline__ void mbar_init(uint32_t bar, uint32_t cnt) { asm volatile("mbarrier.init.shared::cta.b64 [%0], %1;" :: "r"(bar), "r"(cnt) : "memory"); }
__device__ __forceinline__ void mbar_expect_tx(uint32_t bar, uint32_t bytes) { asm volatile("mbarrier.arrive.expect_tx.shared::cta.b64 _, [%0], %1;" :: "r"(bar), "r"(bytes) : "memory"); }
__device__ __forceinline__ void mbar_arrive(uint32_t bar) { asm volatile("mbarrier.arrive.shared::cta.b64 _, [%0];" :: "r"(bar) : "memory"); }
__device__ __forceinline__ void mbar_arrive_cl(uint32_t cl_addr) { asm volatile("mbarrier.arrive.shared::cluster.b64 _, [%0];" :: "r"(cl_addr) : "memory"); }
__device__ __forceinline__ uint32_t mapa(uint32_t addr, uint32_t cta) { uint32_t r; asm("mapa.shared::cluster.u32 %0, %1, %2;" : "=r"(r) : "r"(addr), "r"(cta)); return r; }
__device__ __forceinline__ void mbar_wait(uint32_t bar, uint32_t parity) {
  asm volatile("{\n.reg .pred p;\n.reg .b32 n;\n.reg .b64 z;\nmov.b32 n, 0;\nmov.b64 z, 0;\n"
               "W: add.u32 n, n, 1;\nsetp.gt.u32 p, n, 0x400000;\n@p st.global.u32 [z], n;\n"
               "mbarrier.try_wait.parity.shared::cta.b64 p, [%0], %1;\n@!p bra W;\n}" :: "r"(bar), "r"(parity) : "memory");
}
__device__ __forceinline__ void tma_3d(uint32_t dst, const CUtensorMap* m, uint32_t bar, int c0, int c1, int c2) {
  asm volatile("cp.async.bulk.tensor.3d.shared::cluster.global.mbarrier::complete_tx::bytes [%0], [%1, {%3, %4, %5}], [%2];" :: "r"(dst), "l"(m), "r"(bar), "r"(c0), "r"(c1), "r"(c2) : "memory");
}
__device__ __forceinline__ void tma_store_3d(const CUtensorMap* m, uint32_t src, int c0, int c1, int c2) {
  asm volatile("cp.async.bulk.tensor.3d.global.shared::cta.bulk_group [%0, {%2, %3, %4}], [%1];" :: "l"(m), "r"(src), "r"(c0), "r"(c1), "r"(c2) : "memory");
}
__device__ __forceinline__ void bulk_ld(uint32_t dst, const void* src, uint32_t bytes, uint32_t bar) {
  asm volatile("cp.async.bulk.shared::cluster.global.mbarrier::complete_tx::bytes [%0], [%1], %2, [%3];" :: "r"(dst), "l"(src), "r"(bytes), "r"(bar) : "memory");
}
__device__ __forceinline__ void bulk_ld_mc(uint32_t dst, const void* src, uint32_t bytes, uint32_t bar) {
  asm volatile("cp.async.bulk.shared::cluster.global.mbarrier::complete_tx::bytes.multicast::cluster [%0], [%1], %2, [%3], %4;" :: "r"(dst), "l"(src), "r"(bytes), "r"(bar), "h"((uint16_t)3) : "memory");
}
__device__ __forceinline__ void bulk_st(void* dst, uint32_t src, uint32_t bytes) {
  asm volatile("cp.async.bulk.global.shared::cta.bulk_group [%0], [%1], %2;" :: "l"(dst), "r"(src), "r"(bytes) : "memory");
}
__device__ __forceinline__ void bulk_commit() { asm volatile("cp.async.bulk.commit_group;" ::: "memory"); }
__device__ __forceinline__ void bulk_wait_read() { asm volatile("cp.async.bulk.wait_group.read 0;" ::: "memory"); }
__device__ __forceinline__ void bulk_wait_all() { asm volatile("cp.async.bulk.wait_group 0;" ::: "memory"); }
__device__ __forceinline__ void fence_async_global() { asm volatile("fence.proxy.async.global;" ::: "memory"); }
__device__ __forceinline__ void fence_async_smem() { asm volatile("fence.proxy.async.shared::cta;" ::: "memory"); }
__device__ __forceinline__ void wg_arrive() { asm volatile("wgmma.fence.sync.aligned;" ::: "memory"); }
__device__ __forceinline__ void wg_commit() { asm volatile("wgmma.commit_group.sync.aligned;" ::: "memory"); }
template <int N> __device__ __forceinline__ void wg_wait() { asm volatile("wgmma.wait_group.sync.aligned %0;" :: "n"(N) : "memory"); }
__device__ __forceinline__ void cl_arrive_relaxed() { asm volatile("barrier.cluster.arrive.relaxed.aligned;" ::: "memory"); }
__device__ __forceinline__ void cl_wait() { asm volatile("barrier.cluster.wait.acquire.aligned;" ::: "memory"); }
__device__ __forceinline__ bool elect() { uint32_t p; asm volatile("{\n.reg .pred p;\nelect.sync _|p, 0xffffffff;\nselp.u32 %0, 1, 0, p;\n}" : "=r"(p)); return p; }
__device__ __forceinline__ void named_bar(int id, int n) { asm volatile("bar.sync %0, %1;" :: "r"(id), "r"(n) : "memory"); }
__device__ __forceinline__ uint32_t pack2(float lo, float hi) { uint32_t r; asm("cvt.rn.bf16x2.f32 %0, %1, %2;" : "=r"(r) : "f"(hi), "f"(lo)); return r; }
__device__ __forceinline__ float bf_lo(uint32_t w) { return __uint_as_float(w << 16); }
__device__ __forceinline__ float bf_hi(uint32_t w) { return __uint_as_float(w & 0xffff0000u); }
__device__ __forceinline__ float bf_round(float v) { return __bfloat162float(__float2bfloat16_rn(v)); }
__device__ __forceinline__ void stsm4(uint32_t addr, uint32_t a, uint32_t b, uint32_t c, uint32_t d) {
  asm volatile("stmatrix.sync.aligned.m8n8.x4.shared.b16 [%0], {%1, %2, %3, %4};" :: "r"(addr), "r"(a), "r"(b), "r"(c), "r"(d) : "memory");
}
__device__ __forceinline__ void ldsm4(uint32_t addr, uint32_t& a, uint32_t& b, uint32_t& c, uint32_t& d) {
  asm volatile("ldmatrix.sync.aligned.m8n8.x4.shared.b16 {%0, %1, %2, %3}, [%4];" : "=r"(a), "=r"(b), "=r"(c), "=r"(d) : "r"(addr) : "memory");
}
__device__ __forceinline__ uint32_t movm(uint32_t a) { uint32_t r; asm volatile("movmatrix.sync.aligned.m8n8.trans.b16 %0, %1;" : "=r"(r) : "r"(a)); return r; }
__device__ __forceinline__ void mma16(float (&d)[4], uint32_t a0, uint32_t a1, uint32_t a2, uint32_t a3, uint32_t b0, uint32_t b1) {
  asm("mma.sync.aligned.m16n8k16.row.col.f32.bf16.bf16.f32 {%0,%1,%2,%3}, {%4,%5,%6,%7}, {%8,%9}, {%0,%1,%2,%3};"
               : "+f"(d[0]), "+f"(d[1]), "+f"(d[2]), "+f"(d[3]) : "r"(a0), "r"(a1), "r"(a2), "r"(a3), "r"(b0), "r"(b1));
}
__device__ __forceinline__ void mma16z(float (&d)[4], uint32_t a0, uint32_t a1, uint32_t a2, uint32_t a3, uint32_t b0, uint32_t b1) {
  asm("mma.sync.aligned.m16n8k16.row.col.f32.bf16.bf16.f32 {%0,%1,%2,%3}, {%4,%5,%6,%7}, {%8,%9}, {%10,%10,%10,%10};"
      : "=f"(d[0]), "=f"(d[1]), "=f"(d[2]), "=f"(d[3]) : "r"(a0), "r"(a1), "r"(a2), "r"(a3), "r"(b0), "r"(b1), "f"(0.f));
}
__device__ __forceinline__ void mma8z(float (&d)[4], uint32_t a0, uint32_t a1, uint32_t b0) {
  asm("mma.sync.aligned.m16n8k8.row.col.f32.bf16.bf16.f32 {%0,%1,%2,%3}, {%4,%5}, {%6}, {%7,%7,%7,%7};"
      : "=f"(d[0]), "=f"(d[1]), "=f"(d[2]), "=f"(d[3]) : "r"(a0), "r"(a1), "r"(b0), "f"(0.f));
}
__device__ __forceinline__ void mma8(float (&d)[4], uint32_t a0, uint32_t a1, uint32_t b0) {
  asm("mma.sync.aligned.m16n8k8.row.col.f32.bf16.bf16.f32 {%0,%1,%2,%3}, {%4,%5}, {%6}, {%0,%1,%2,%3};"
               : "+f"(d[0]), "+f"(d[1]), "+f"(d[2]), "+f"(d[3]) : "r"(a0), "r"(a1), "r"(b0));
}
__device__ __forceinline__ uint4 lds128(uint32_t a) { uint4 v; asm volatile("ld.shared.v4.u32 {%0,%1,%2,%3}, [%4];" : "=r"(v.x), "=r"(v.y), "=r"(v.z), "=r"(v.w) : "r"(a) : "memory"); return v; }
__device__ __forceinline__ void sts128(uint32_t a, uint32_t x, uint32_t y, uint32_t z, uint32_t w) { asm volatile("st.shared.v4.u32 [%0], {%1,%2,%3,%4};" :: "r"(a), "r"(x), "r"(y), "r"(z), "r"(w) : "memory"); }
__device__ __forceinline__ float lds32f(uint32_t a) { float v; asm volatile("ld.shared.f32 %0, [%1];" : "=f"(v) : "r"(a) : "memory"); return v; }
__device__ __forceinline__ void sts16(uint32_t a, bf16 v) { asm volatile("st.shared.b16 [%0], %1;" :: "r"(a), "h"(__bfloat16_as_ushort(v)) : "memory"); }
__device__ __forceinline__ uint4 ldg_nc(const void* p) { uint4 v; asm volatile("ld.global.nc.L1::no_allocate.v4.u32 {%0,%1,%2,%3}, [%4];" : "=r"(v.x), "=r"(v.y), "=r"(v.z), "=r"(v.w) : "l"(p)); return v; }
__device__ __forceinline__ uint4 ld_rlx4(const uint4* p) {
  unsigned long long a, b; asm volatile("ld.relaxed.gpu.global.v2.b64 {%0,%1}, [%2];" : "=l"(a), "=l"(b) : "l"(p) : "memory");
  return make_uint4((uint32_t)a, (uint32_t)(a >> 32), (uint32_t)b, (uint32_t)(b >> 32));
}
__device__ __forceinline__ uint2 ld_rlx2(const uint2* p) { unsigned long long a; asm volatile("ld.relaxed.gpu.global.b64 %0, [%1];" : "=l"(a) : "l"(p) : "memory"); return make_uint2((uint32_t)a, (uint32_t)(a >> 32)); }
__device__ __forceinline__ void st_rlx4(uint4* p, uint32_t x, uint32_t y, uint32_t z, uint32_t w) {
  asm volatile("st.relaxed.gpu.global.v2.b64 [%0], {%1,%2};" :: "l"(p), "l"((unsigned long long)x | ((unsigned long long)y << 32)), "l"((unsigned long long)z | ((unsigned long long)w << 32)) : "memory");
}
__device__ __forceinline__ void st_rlx2(uint2* p, uint32_t x, uint32_t y) { asm volatile("st.relaxed.gpu.global.b64 [%0], %1;" :: "l"(p), "l"((unsigned long long)x | ((unsigned long long)y << 32)) : "memory"); }
__device__ __forceinline__ void st_release(uint32_t* p, uint32_t v) { asm volatile("st.release.gpu.global.u32 [%0], %1;" :: "l"(p), "r"(v) : "memory"); }
__device__ __forceinline__ uint32_t ld_acquire(const uint32_t* p) { uint32_t v; asm volatile("ld.acquire.gpu.global.u32 %0, [%1];" : "=r"(v) : "l"(p) : "memory"); return v; }
__device__ __forceinline__ void prefetch_map(const CUtensorMap* m) { asm volatile("prefetch.tensormap [%0];" :: "l"(m) : "memory"); }
__device__ __forceinline__ float rcp(float x) { float r; asm("rcp.approx.ftz.f32 %0, %1;" : "=f"(r) : "f"(x)); return r; }
__device__ __forceinline__ float ex2(float x) { float r; asm("ex2.approx.ftz.f32 %0, %1;" : "=f"(r) : "f"(x)); return r; }
__device__ __forceinline__ float tanh_fast(float x) { float r; asm("tanh.approx.f32 %0, %1;" : "=f"(r) : "f"(x)); return r; }
#define SPIN_GUARD(n) if (++(n) > (1u << 24)) bail()

__device__ __forceinline__ void wgmma_n128(float (&d)[64], uint64_t da, uint64_t db) {
  asm volatile("wgmma.mma_async.sync.aligned.m64n128k16.f32.bf16.bf16 "
    "{%0, %1, %2, %3, %4, %5, %6, %7, %8, %9, %10, %11, %12, %13, %14, %15, %16, %17, %18, %19, %20, %21, %22, %23, %24, %25, %26, %27, %28, %29, %30, %31, %32, %33, %34, %35, %36, %37, %38, %39, %40, %41, %42, %43, %44, %45, %46, %47, %48, %49, %50, %51, %52, %53, %54, %55, %56, %57, %58, %59, %60, %61, %62, %63}, "
    "%64, %65, 1, 1, 1, 0, 1;\n"
    : "+f"(d[0]), "+f"(d[1]), "+f"(d[2]), "+f"(d[3]), "+f"(d[4]), "+f"(d[5]), "+f"(d[6]), "+f"(d[7]), "+f"(d[8]), "+f"(d[9]), "+f"(d[10]), "+f"(d[11]), "+f"(d[12]), "+f"(d[13]), "+f"(d[14]), "+f"(d[15]), "+f"(d[16]), "+f"(d[17]), "+f"(d[18]), "+f"(d[19]), "+f"(d[20]), "+f"(d[21]), "+f"(d[22]), "+f"(d[23]), "+f"(d[24]), "+f"(d[25]), "+f"(d[26]), "+f"(d[27]), "+f"(d[28]), "+f"(d[29]), "+f"(d[30]), "+f"(d[31]), "+f"(d[32]), "+f"(d[33]), "+f"(d[34]), "+f"(d[35]), "+f"(d[36]), "+f"(d[37]), "+f"(d[38]), "+f"(d[39]), "+f"(d[40]), "+f"(d[41]), "+f"(d[42]), "+f"(d[43]), "+f"(d[44]), "+f"(d[45]), "+f"(d[46]), "+f"(d[47]), "+f"(d[48]), "+f"(d[49]), "+f"(d[50]), "+f"(d[51]), "+f"(d[52]), "+f"(d[53]), "+f"(d[54]), "+f"(d[55]), "+f"(d[56]), "+f"(d[57]), "+f"(d[58]), "+f"(d[59]), "+f"(d[60]), "+f"(d[61]), "+f"(d[62]), "+f"(d[63])
    : "l"(da), "l"(db));
}
__device__ __forceinline__ void wgmma_n128_first(float (&d)[64], uint64_t da, uint64_t db) {
  asm volatile("wgmma.mma_async.sync.aligned.m64n128k16.f32.bf16.bf16 "
    "{%0, %1, %2, %3, %4, %5, %6, %7, %8, %9, %10, %11, %12, %13, %14, %15, %16, %17, %18, %19, %20, %21, %22, %23, %24, %25, %26, %27, %28, %29, %30, %31, %32, %33, %34, %35, %36, %37, %38, %39, %40, %41, %42, %43, %44, %45, %46, %47, %48, %49, %50, %51, %52, %53, %54, %55, %56, %57, %58, %59, %60, %61, %62, %63}, "
    "%64, %65, 0, 1, 1, 0, 1;\n"
    : "=f"(d[0]), "=f"(d[1]), "=f"(d[2]), "=f"(d[3]), "=f"(d[4]), "=f"(d[5]), "=f"(d[6]), "=f"(d[7]), "=f"(d[8]), "=f"(d[9]), "=f"(d[10]), "=f"(d[11]), "=f"(d[12]), "=f"(d[13]), "=f"(d[14]), "=f"(d[15]), "=f"(d[16]), "=f"(d[17]), "=f"(d[18]), "=f"(d[19]), "=f"(d[20]), "=f"(d[21]), "=f"(d[22]), "=f"(d[23]), "=f"(d[24]), "=f"(d[25]), "=f"(d[26]), "=f"(d[27]), "=f"(d[28]), "=f"(d[29]), "=f"(d[30]), "=f"(d[31]), "=f"(d[32]), "=f"(d[33]), "=f"(d[34]), "=f"(d[35]), "=f"(d[36]), "=f"(d[37]), "=f"(d[38]), "=f"(d[39]), "=f"(d[40]), "=f"(d[41]), "=f"(d[42]), "=f"(d[43]), "=f"(d[44]), "=f"(d[45]), "=f"(d[46]), "=f"(d[47]), "=f"(d[48]), "=f"(d[49]), "=f"(d[50]), "=f"(d[51]), "=f"(d[52]), "=f"(d[53]), "=f"(d[54]), "=f"(d[55]), "=f"(d[56]), "=f"(d[57]), "=f"(d[58]), "=f"(d[59]), "=f"(d[60]), "=f"(d[61]), "=f"(d[62]), "=f"(d[63])
    : "l"(da), "l"(db));
}
__device__ __forceinline__ void wgmma_n256(float (&d)[128], uint64_t da, uint64_t db) {
  asm volatile("wgmma.mma_async.sync.aligned.m64n256k16.f32.bf16.bf16 "
    "{%0, %1, %2, %3, %4, %5, %6, %7, %8, %9, %10, %11, %12, %13, %14, %15, %16, %17, %18, %19, %20, %21, %22, %23, %24, %25, %26, %27, %28, %29, %30, %31, %32, %33, %34, %35, %36, %37, %38, %39, %40, %41, %42, %43, %44, %45, %46, %47, %48, %49, %50, %51, %52, %53, %54, %55, %56, %57, %58, %59, %60, %61, %62, %63, %64, %65, %66, %67, %68, %69, %70, %71, %72, %73, %74, %75, %76, %77, %78, %79, %80, %81, %82, %83, %84, %85, %86, %87, %88, %89, %90, %91, %92, %93, %94, %95, %96, %97, %98, %99, %100, %101, %102, %103, %104, %105, %106, %107, %108, %109, %110, %111, %112, %113, %114, %115, %116, %117, %118, %119, %120, %121, %122, %123, %124, %125, %126, %127}, "
    "%128, %129, 1, 1, 1, 0, 1;\n"
    : "+f"(d[0]), "+f"(d[1]), "+f"(d[2]), "+f"(d[3]), "+f"(d[4]), "+f"(d[5]), "+f"(d[6]), "+f"(d[7]), "+f"(d[8]), "+f"(d[9]), "+f"(d[10]), "+f"(d[11]), "+f"(d[12]), "+f"(d[13]), "+f"(d[14]), "+f"(d[15]), "+f"(d[16]), "+f"(d[17]), "+f"(d[18]), "+f"(d[19]), "+f"(d[20]), "+f"(d[21]), "+f"(d[22]), "+f"(d[23]), "+f"(d[24]), "+f"(d[25]), "+f"(d[26]), "+f"(d[27]), "+f"(d[28]), "+f"(d[29]), "+f"(d[30]), "+f"(d[31]), "+f"(d[32]), "+f"(d[33]), "+f"(d[34]), "+f"(d[35]), "+f"(d[36]), "+f"(d[37]), "+f"(d[38]), "+f"(d[39]), "+f"(d[40]), "+f"(d[41]), "+f"(d[42]), "+f"(d[43]), "+f"(d[44]), "+f"(d[45]), "+f"(d[46]), "+f"(d[47]), "+f"(d[48]), "+f"(d[49]), "+f"(d[50]), "+f"(d[51]), "+f"(d[52]), "+f"(d[53]), "+f"(d[54]), "+f"(d[55]), "+f"(d[56]), "+f"(d[57]), "+f"(d[58]), "+f"(d[59]), "+f"(d[60]), "+f"(d[61]), "+f"(d[62]), "+f"(d[63]), "+f"(d[64]), "+f"(d[65]), "+f"(d[66]), "+f"(d[67]), "+f"(d[68]), "+f"(d[69]), "+f"(d[70]), "+f"(d[71]), "+f"(d[72]), "+f"(d[73]), "+f"(d[74]), "+f"(d[75]), "+f"(d[76]), "+f"(d[77]), "+f"(d[78]), "+f"(d[79]), "+f"(d[80]), "+f"(d[81]), "+f"(d[82]), "+f"(d[83]), "+f"(d[84]), "+f"(d[85]), "+f"(d[86]), "+f"(d[87]), "+f"(d[88]), "+f"(d[89]), "+f"(d[90]), "+f"(d[91]), "+f"(d[92]), "+f"(d[93]), "+f"(d[94]), "+f"(d[95]), "+f"(d[96]), "+f"(d[97]), "+f"(d[98]), "+f"(d[99]), "+f"(d[100]), "+f"(d[101]), "+f"(d[102]), "+f"(d[103]), "+f"(d[104]), "+f"(d[105]), "+f"(d[106]), "+f"(d[107]), "+f"(d[108]), "+f"(d[109]), "+f"(d[110]), "+f"(d[111]), "+f"(d[112]), "+f"(d[113]), "+f"(d[114]), "+f"(d[115]), "+f"(d[116]), "+f"(d[117]), "+f"(d[118]), "+f"(d[119]), "+f"(d[120]), "+f"(d[121]), "+f"(d[122]), "+f"(d[123]), "+f"(d[124]), "+f"(d[125]), "+f"(d[126]), "+f"(d[127])
    : "l"(da), "l"(db));
}
__device__ __forceinline__ void wgmma_n256_first(float (&d)[128], uint64_t da, uint64_t db) {
  asm volatile("wgmma.mma_async.sync.aligned.m64n256k16.f32.bf16.bf16 "
    "{%0, %1, %2, %3, %4, %5, %6, %7, %8, %9, %10, %11, %12, %13, %14, %15, %16, %17, %18, %19, %20, %21, %22, %23, %24, %25, %26, %27, %28, %29, %30, %31, %32, %33, %34, %35, %36, %37, %38, %39, %40, %41, %42, %43, %44, %45, %46, %47, %48, %49, %50, %51, %52, %53, %54, %55, %56, %57, %58, %59, %60, %61, %62, %63, %64, %65, %66, %67, %68, %69, %70, %71, %72, %73, %74, %75, %76, %77, %78, %79, %80, %81, %82, %83, %84, %85, %86, %87, %88, %89, %90, %91, %92, %93, %94, %95, %96, %97, %98, %99, %100, %101, %102, %103, %104, %105, %106, %107, %108, %109, %110, %111, %112, %113, %114, %115, %116, %117, %118, %119, %120, %121, %122, %123, %124, %125, %126, %127}, "
    "%128, %129, 0, 1, 1, 0, 1;\n"
    : "=f"(d[0]), "=f"(d[1]), "=f"(d[2]), "=f"(d[3]), "=f"(d[4]), "=f"(d[5]), "=f"(d[6]), "=f"(d[7]), "=f"(d[8]), "=f"(d[9]), "=f"(d[10]), "=f"(d[11]), "=f"(d[12]), "=f"(d[13]), "=f"(d[14]), "=f"(d[15]), "=f"(d[16]), "=f"(d[17]), "=f"(d[18]), "=f"(d[19]), "=f"(d[20]), "=f"(d[21]), "=f"(d[22]), "=f"(d[23]), "=f"(d[24]), "=f"(d[25]), "=f"(d[26]), "=f"(d[27]), "=f"(d[28]), "=f"(d[29]), "=f"(d[30]), "=f"(d[31]), "=f"(d[32]), "=f"(d[33]), "=f"(d[34]), "=f"(d[35]), "=f"(d[36]), "=f"(d[37]), "=f"(d[38]), "=f"(d[39]), "=f"(d[40]), "=f"(d[41]), "=f"(d[42]), "=f"(d[43]), "=f"(d[44]), "=f"(d[45]), "=f"(d[46]), "=f"(d[47]), "=f"(d[48]), "=f"(d[49]), "=f"(d[50]), "=f"(d[51]), "=f"(d[52]), "=f"(d[53]), "=f"(d[54]), "=f"(d[55]), "=f"(d[56]), "=f"(d[57]), "=f"(d[58]), "=f"(d[59]), "=f"(d[60]), "=f"(d[61]), "=f"(d[62]), "=f"(d[63]), "=f"(d[64]), "=f"(d[65]), "=f"(d[66]), "=f"(d[67]), "=f"(d[68]), "=f"(d[69]), "=f"(d[70]), "=f"(d[71]), "=f"(d[72]), "=f"(d[73]), "=f"(d[74]), "=f"(d[75]), "=f"(d[76]), "=f"(d[77]), "=f"(d[78]), "=f"(d[79]), "=f"(d[80]), "=f"(d[81]), "=f"(d[82]), "=f"(d[83]), "=f"(d[84]), "=f"(d[85]), "=f"(d[86]), "=f"(d[87]), "=f"(d[88]), "=f"(d[89]), "=f"(d[90]), "=f"(d[91]), "=f"(d[92]), "=f"(d[93]), "=f"(d[94]), "=f"(d[95]), "=f"(d[96]), "=f"(d[97]), "=f"(d[98]), "=f"(d[99]), "=f"(d[100]), "=f"(d[101]), "=f"(d[102]), "=f"(d[103]), "=f"(d[104]), "=f"(d[105]), "=f"(d[106]), "=f"(d[107]), "=f"(d[108]), "=f"(d[109]), "=f"(d[110]), "=f"(d[111]), "=f"(d[112]), "=f"(d[113]), "=f"(d[114]), "=f"(d[115]), "=f"(d[116]), "=f"(d[117]), "=f"(d[118]), "=f"(d[119]), "=f"(d[120]), "=f"(d[121]), "=f"(d[122]), "=f"(d[123]), "=f"(d[124]), "=f"(d[125]), "=f"(d[126]), "=f"(d[127])
    : "l"(da), "l"(db));
}

template <int N> struct WG;
#define DEF_WG(N) template <> struct WG<N> { \
  static __device__ __forceinline__ void mma(float (&d)[N / 2], uint64_t a, uint64_t b) { wgmma_n##N(d, a, b); } \
  static __device__ __forceinline__ void first(float (&d)[N / 2], uint64_t a, uint64_t b) { wgmma_n##N##_first(d, a, b); } };
DEF_WG(128) DEF_WG(256)

constexpr uint64_t DESC_A = (1ull << 62) | ((uint64_t)(1024 >> 4) << 32) | (1ull << 16);
constexpr uint64_t DESC_B = (1ull << 62) | ((uint64_t)(1024 >> 4) << 32) | ((uint64_t)(8192 >> 4) << 16);

struct Ring { int s; uint32_t ph; int wrap; };
template <int NS> __device__ __forceinline__ void ring_next(Ring& r) { r.s = (r.s + 1 == NS) ? 0 : r.s + 1; if (r.s == r.wrap) r.ph ^= 1; }

__device__ __forceinline__ int own_order(int it, int j) {
  return it < 2 ? 2 * j + it : it < 4 ? 2 * (j ^ 1) + it - 2 : ((j >> 1) * 4 + 2 * it - (it < 10 ? 4 : 15)) & 15;
}

template <int V> struct IC { static constexpr int v = V; };
template <int I, int E, class F> __device__ __forceinline__ void static_for(F&& f) { if constexpr (I < E) { f(IC<I>{}); static_for<I + 1, E>(f); } }

template <int N, int NS, int PRE, class Pre, class Mid, class Last>
__device__ __forceinline__ void mainloop(float (&acc)[N / 2], int nkb, bool own, Ring& r, uint32_t sb, int wg, int lane, uint32_t rel_base, uint32_t* step0, Pre pre, Mid mid, Last last) {
  constexpr int SLOT = RING / NS;
  const uint32_t full = sb + MISC + (NS == 4 ? B_FULL4 : B_FULL6);
  const uint32_t rel = rel_base + (NS == 4 ? B_EMPTY4 : B_EMPTY6);
  const uint32_t s0 = (sb & 0x3FFFF) >> 4, a0 = s0 + wg * (HALF >> 4);
  int ps;
  auto issue = [&](int it, bool first) {
    const uint64_t da = DESC_A | (a0 + ((own && it < 2) ? (STG + it * BLK) >> 4 : r.s * (SLOT >> 4))), db = DESC_B | (s0 + r.s * (SLOT >> 4) + (BLK >> 4));
    mbar_wait(full + r.s * 8, r.ph);
    TRS(it);
    wg_arrive();
    if (first) WG<N>::first(acc, da, db); else WG<N>::mma(acc, da, db);
#pragma unroll
    for (int k = 1; k < 4; k++) WG<N>::mma(acc, da + k * 2, db + k * 128);
    wg_commit();
  };
  auto retire = [&](int it) {
    wg_wait<1>();
    if (lane < 2) mbar_arrive_cl(rel + ps * 8);
    if (own && it == 2 && lane == 0) mbar_arrive(sb + MISC + B_OWN);
    ps = r.s;
    ring_next<NS>(r);
  };
  issue(0, true);
  ps = r.s;
  ring_next<NS>(r);
  static_for<1, PRE + 1>([&](auto ic) { issue(ic.v, false); pre(ic); retire(ic.v); });
#pragma unroll 1
  for (int it = PRE + 1; it < nkb; it++) {
    if (TAILLAG && it == 56 - TAILLAG && wg == 1) mbar_wait(sb + MISC + B_LAG, 0);
    issue(it, false); mid(it); retire(it);
  }
  last();
  wg_wait<0>();
  if (lane < 2) mbar_arrive_cl(rel + ps * 8);
}

__device__ __forceinline__ void ln_publish(const float (&v)[64], uint4* st, int j, int row0, int lane, uint32_t ep) {
  float s0 = 0, s1 = 0, s2 = 0, s3 = 0, q0 = 0, q1 = 0, q2 = 0, q3 = 0;
#pragma unroll
  for (int i = 0; i < 16; i++) {
    s0 += v[4 * i]; s1 += v[4 * i + 1]; s2 += v[4 * i + 2]; s3 += v[4 * i + 3];
    q0 = fmaf(v[4 * i], v[4 * i], q0); q1 = fmaf(v[4 * i + 1], v[4 * i + 1], q1); q2 = fmaf(v[4 * i + 2], v[4 * i + 2], q2); q3 = fmaf(v[4 * i + 3], v[4 * i + 3], q3);
  }
  s0 += s1; s2 += s3; q0 += q1; q2 += q3;
  const bool odd = lane & 1;
  float s = (odd ? s2 : s0) + __shfl_xor_sync(~0u, odd ? s0 : s2, 1), q = (odd ? q2 : q0) + __shfl_xor_sync(~0u, odd ? q0 : q2, 1);
  s += __shfl_xor_sync(~0u, s, 2); q += __shfl_xor_sync(~0u, q, 2);
  if ((lane & 3) < 2) st_rlx4(st + j * 128 + row0 + (lane & 1) * 8, __float_as_uint(s), ep, __float_as_uint(q), ep);
}
__device__ __forceinline__ void ln_gather(const uint4* st, int row0, int lane, uint32_t ep, float& n0, float& r0, float& n1, float& r1) {
  const uint4* p = st + (lane & 2) * 256 + row0 + (lane & 1) * 8;
  uint4 a, b, c, d; uint32_t n = 0;
  while (true) {
    a = ld_rlx4(p); b = ld_rlx4(p + 128); c = ld_rlx4(p + 256); d = ld_rlx4(p + 384);
    if (a.y == ep && a.w == ep && b.y == ep && b.w == ep && c.y == ep && c.w == ep && d.y == ep && d.w == ep) break;
    SPIN_GUARD(n);
  }
  __syncwarp();
  float s = (__uint_as_float(a.x) + __uint_as_float(b.x)) + (__uint_as_float(c.x) + __uint_as_float(d.x));
  float q = (__uint_as_float(a.z) + __uint_as_float(b.z)) + (__uint_as_float(c.z) + __uint_as_float(d.z));
  s += __shfl_xor_sync(~0u, s, 2); q += __shfl_xor_sync(~0u, q, 2);
  s *= 1.f / 1024;
  const float r = rsqrtf(fmaxf(fmaf(-s, s, q * (1.f / 1024)), 0.f) + 1e-5f), nn = -s * r;
  const float ro = __shfl_xor_sync(~0u, r, 1), no = __shfl_xor_sync(~0u, nn, 1);
  const bool odd = lane & 1;
  r0 = odd ? ro : r; n0 = odd ? no : nn; r1 = odd ? r : ro; n1 = odd ? nn : no;
}
__device__ __forceinline__ void load_vec(uint32_t* w, uint32_t sb, int sec, int b, int lane) {
#pragma unroll
  for (int q = 0; q < 2; q++) { uint4 t = lds128(sb + MISC + MODV + sec * 256 + (lane & 3) * 64 + b * 32 + q * 16); w[4 * q] = t.x; w[4 * q + 1] = t.y; w[4 * q + 2] = t.z; w[4 * q + 3] = t.w; }
}
__device__ __forceinline__ void stage_done(uint32_t sb, int wg, int b, int lane) {
  fence_async_smem();
  __syncwarp();
  if (lane == 0) mbar_arrive(sb + MISC + B_RDY + b * 8);
}
__device__ __forceinline__ uint32_t hfma2(uint32_t a, uint32_t b, uint32_t c) { uint32_t r; asm("fma.rn.bf16x2 %0, %1, %2, %3;" : "=r"(r) : "r"(a), "r"(b), "r"(c)); return r; }
__device__ __forceinline__ void ln_apply(const float (&v)[64], const uint4* st, int row0, uint32_t ep, uint32_t sb, int sec_shift, int sec_scale, uint32_t stg_row, int wg, int lane) {
  uint32_t sc[16], sh[16];
#pragma unroll
  for (int b = 0; b < 2; b++) { load_vec(sc + 8 * b, sb, sec_scale, b, lane); load_vec(sh + 8 * b, sb, sec_shift, b, lane); }
  float n0, r0, n1, r1;
  ln_gather(st, row0, lane, ep, n0, r0, n1, r1);
#pragma unroll
  for (int i = 0; i < 16; i += 2) {
    if (i == 8) { const float z = lds32f(sb + MISC + ZERO); n0 += z; n1 += z; }
    uint32_t w[4];
#pragma unroll
    for (int u = 0; u < 2; u++) {
      int q = i + u;
      w[2 * u] = hfma2(pack2(fmaf(v[4 * q], r0, n0), fmaf(v[4 * q + 1], r0, n0)), sc[q], sh[q]);
      w[2 * u + 1] = hfma2(pack2(fmaf(v[4 * q + 2], r1, n1), fmaf(v[4 * q + 3], r1, n1)), sc[q], sh[q]);
    }
    stsm4(stg_row + (i >> 3) * BLK + ((((i & 7) + (lane >> 4)) ^ (lane & 7)) << 4), w[0], w[1], w[2], w[3]);
    if ((i & 7) == 6) stage_done(sb, wg, i >> 3, lane);
  }
}
__device__ __forceinline__ uint32_t hmul2(uint32_t a, uint32_t b) { uint32_t r; asm("mul.rn.bf16x2 %0, %1, %2;" : "=r"(r) : "r"(a), "r"(b)); return r; }
__device__ __forceinline__ uint32_t silu_mul2(uint32_t g, uint32_t u) {
  const uint32_t h = hmul2(g, 0x3f003f00u);
  const float h0 = bf_lo(h), h1 = bf_hi(h);
  return hmul2(pack2(fmaf(h0, tanh_fast(h0), h0), fmaf(h1, tanh_fast(h1), h1)), u);
}

__device__ __forceinline__ void gemv_fma(float (&a)[8], uint4 w, float s) {
  a[0] = fmaf(bf_lo(w.x), s, a[0]); a[1] = fmaf(bf_hi(w.x), s, a[1]); a[2] = fmaf(bf_lo(w.y), s, a[2]); a[3] = fmaf(bf_hi(w.y), s, a[3]);
  a[4] = fmaf(bf_lo(w.z), s, a[4]); a[5] = fmaf(bf_hi(w.z), s, a[5]); a[6] = fmaf(bf_lo(w.w), s, a[6]); a[7] = fmaf(bf_hi(w.w), s, a[7]);
}
__device__ __forceinline__ float silu_c(float v) { return bf_round(__fdividef(v, 1.f + __expf(-v))); }
__device__ __forceinline__ float mod_gather(const uint2* p, uint32_t ep) {
  uint2 a, b, c, d; uint32_t n = 0;
  while (true) {
    a = ld_rlx2(p); b = ld_rlx2(p + 128); c = ld_rlx2(p + 256); d = ld_rlx2(p + 384);
    if (a.y == ep && b.y == ep && c.y == ep && d.y == ep) break;
    SPIN_GUARD(n);
  }
  return (__uint_as_float(a.x) + __uint_as_float(b.x)) + (__uint_as_float(c.x) + __uint_as_float(d.x));
}
__device__ __forceinline__ void mod_store(uint32_t sb, int sec, int col, float v) {
  v = bf_round(v);
  if (sec == 1 || sec == 4) v += 1.f;
  sts16(sb + MISC + MODV + sec * 256 + (((col >> 1) & 3) * 16 + (col >> 3)) * 4 + (col & 1) * 2, __float2bfloat16_rn(v));
}

__global__ void __cluster_dims__(2, 1, 1) __launch_bounds__(384, 1)
fused_kernel(const bf16* __restrict__ cvec, const bf16* __restrict__ wmod, Scratch* gs, int by_sm, const __grid_constant__ Maps maps) {
  extern __shared__ __align__(1024) uint8_t smem_raw[];
  const uint32_t sb = smem_u32(smem_raw);
  const int warp = __shfl_sync(~0u, threadIdx.x >> 5, 0), lane = threadIdx.x & 31;
  const int rank = blockIdx.x & 1;
  uint32_t sm; asm("mov.u32 %0, %%smid;" : "=r"(sm));
  const int t = sm >> 1, v = t < 32 ? t : t < 60 ? t + 1 + (((t - 32) * 37) >> 8) : (t - 58) * 8;
  const int cid = !by_sm ? (blockIdx.x >> 1) - 2 : (t & ~1) == 60 ? t - 62 : (v & 1) * 32 + ((v >> 1) & 31);
  const bool extra = cid < 0;
  const int bid = cid * 2 + rank;
  const int m = cid >> 2, j = (cid & 3) * 2 + rank;
  const uint32_t bar = sb + MISC;

  if (warp >= 8) {
    asm volatile("setmaxnreg.dec.sync.aligned.u32 40;");
    if (extra) {
      if (warp == 8) {
        if (lane == 0) { for (int s = 0; s < 6; s++) { mbar_init(bar + B_FULL6 + s * 8, 1); mbar_init(bar + B_EMPTY6 + s * 8, 8); } fence_async_smem(); }
        __syncwarp();
        asm volatile("bar.arrive 2, 288;" ::: "memory");
        __nanosleep(XSLEEP);
#pragma unroll 1
        for (int it = 0, s = 0, par = 1; it < 64; it++) {
          mbar_wait(bar + B_EMPTY6 + s * 8, par);
          if (elect()) { mbar_expect_tx(bar + B_FULL6 + s * 8, 32768); tma_3d(sb + s * 32768, &maps.wmod, bar + B_FULL6 + s * 8, 0, (it & 15) * 64, 12 + (it >> 4) * 4 + bid); }
          if (++s == 6) { s = 0; par ^= 1; }
        }
      }
    } else if (warp < 10) {
      uint32_t s6 = 0, p6 = 1;
      auto next6 = [&]() { if (++s6 == 6) { s6 = 0; p6 ^= 1; } };
      auto drained4 = [&](int q, int late) { if (q < 5) mbar_wait(bar + B_EMPTY4 + (((late ? 0x10332 : 0x32110) >> (4 * q)) & 3) * 8, 1); };
      auto drained6 = [&](int q) { if (q < 3) mbar_wait(bar + B_EMPTY6 + ((0x154 >> (4 * q)) & 7) * 8, q >> 1); };
      auto skip6 = [&]() { mbar_wait(bar + B_EMPTY6 + s6 * 8, p6); if (elect()) mbar_arrive(bar + B_FULL6 + s6 * 8); next6(); };
      if (warp == 8) {
        const uint32_t t_start = clock();
        if (lane == 0) {
          if (sb & 1023) bail();
          for (int b = 0; b < 2; b++) mbar_init(bar + B_X + b * 8, 1);
          for (int s = 0; s < 4; s++) { mbar_init(bar + B_FULL4 + s * 8, 2); mbar_init(bar + B_EMPTY4 + s * 8, 16); }
          for (int s = 0; s < 6; s++) { mbar_init(bar + B_FULL6 + s * 8, 2); mbar_init(bar + B_EMPTY6 + s * 8, 16); }
          for (int b = 0; b < 2; b++) { mbar_init(bar + B_RDY + b * 8, 8); mbar_init(bar + B_FREE + b * 8, 1); mbar_init(bar + B_HH + b * 8, 1); }
          mbar_init(bar + B_MOD, 1); mbar_init(bar + B_LAG, 4); mbar_init(bar + B_HALO, 2); mbar_init(bar + B_ALL, 1); mbar_init(bar + B_HH2, 1); mbar_init(bar + B_OWN, 8);
          asm volatile("st.shared.u32 [%0], 0;" :: "r"(bar + ZERO) : "memory");
          asm volatile("fence.mbarrier_init.release.cluster;" ::: "memory");
          fence_async_smem();
        }
        __syncwarp();
        cl_arrive_relaxed();
        auto wide = [&](int s, int par, const CUtensorMap* m0, int a0, const CUtensorMap* m1, int a1, int kb) {
          const uint32_t full = bar + B_FULL4 + s * 8, d = sb + s * 49152 + BLK;
          mbar_wait(full + 32, par);
          if (elect()) { mbar_expect_tx(full, 2 * BLK); tma_3d(d, m0, full, 0, kb * 64, a0); tma_3d(d + BLK, m1, full, 0, kb * 64, a1); }
        };
        auto narrow = [&](const CUtensorMap* m0, int kb) {
          const uint32_t full = bar + B_FULL6 + s6 * 8;
          mbar_wait(full + 48, p6);
          if (elect()) { mbar_expect_tx(full, BLK); tma_3d(sb + s6 * 32768 + BLK, m0, full, 0, kb * 64, 2 * j); }
          next6();
        };
#pragma unroll 1
        for (int it = 0; it < 16; it++) {
          if (it == 0) {
            while ((uint32_t)clock() - t_start < XDELAY) {}
            if (elect()) for (int b = 0; b < 2; b++) { mbar_expect_tx(bar + B_X + b * 8, BLK); tma_3d(sb + STG + b * BLK, &maps.x, bar + B_X + b * 8, j * 128 + b * 64, m * 64, 0); }
            mbar_wait(bar + B_X + 8, 0);
          }
          wide(it & 3, ~(it >> 2) & 1, &maps.wqkv, 16 + 2 * j, &maps.wqkv, 32 + 2 * j, own_order(it, j));
        }
#pragma unroll 1
        for (int it = 0; it < 16; it++) { drained4(it, 0); narrow(&maps.wqkv, it); }
#pragma unroll 1
        for (int it = 0; it < 16; it++) {
          narrow(&maps.wo, own_order(it, j));
          if (!KEEPX && it == XRE) {
            mbar_wait(bar + B_OWN, 1); mbar_wait(bar + B_FREE + 8, 1);
            if (elect()) for (int b = 0; b < 2; b++) { mbar_expect_tx(bar + B_X + b * 8, BLK); tma_3d(sb + STG + b * BLK, &maps.x, bar + B_X + b * 8, j * 128 + b * 64, m * 64, 0); }
          }
        }
        skip6();
#pragma unroll 1
        for (int it = 0; it < 48; it++) {
          const int s = (it + 2) & 3, par = ~(it >> 2) & 1;
          drained6(it);
          wide(s, par, &maps.w1, (it & 48) + 2 * j, &maps.w3, (it & 48) + 2 * j, it < 16 ? own_order(it, j) : it & 15);
          if (it >= 44) {
            if (it == 44) { mbar_wait(bar + B_FREE, 0); mbar_wait(bar + B_FREE + 8, 0); if (elect()) mbar_expect_tx(bar + B_X, 2 * BLK); }
            if (elect()) bulk_ld(sb + STG + (it - 44) * HALF, gs->x1 + bid * 2048 + (it - 44) * 512, HALF, bar + B_X);
          }
        }
#pragma unroll 1
        for (int it = 0; it < 16; it++) {
          const uint32_t full = bar + B_FULL6 + s6 * 8, d = sb + s6 * 32768 + BLK;
          drained4(it, 1);
          mbar_wait(full + 48, p6);
          if (elect()) { mbar_expect_tx(full, BLK); tma_3d(d, &maps.w1s, full, 0, it * 64, 48 + j); tma_3d(d + HALF, &maps.w3s, full, 0, it * 64, 48 + j); }
          next6();
        }
#pragma unroll 1
        for (int it = 0; it < 56; it++) narrow(&maps.w2, it);
      } else {
        if (lane < 9) prefetch_map(&maps.x + lane);
        const uint32_t ep = gs->epoch[bid + 4] + 1;
        cl_arrive_relaxed(); cl_wait();
        auto plain = [&](uint32_t full, uint32_t empty, int par, uint32_t slot, const uint4* blk) {
          mbar_wait(empty, par);
          if (elect()) { mbar_expect_tx(full, BLK); bulk_ld_mc(slot + rank * HALF, blk + rank * 512, HALF, full); }
        };
        auto plain6 = [&](const uint4* blk) { plain(bar + B_FULL6 + s6 * 8, bar + B_EMPTY6 + s6 * 8, p6, sb + s6 * 32768, blk); next6(); };
        uint32_t ready = 0;
        auto poll = [&](int e) { ready = __ballot_sync(~0u, ld_acquire(gs->flag + m * 128 + e * 16 + (lane & 15)) == ep); };
        auto need = [&](int e, uint32_t mask) {
          if ((ready & mask) != mask) {
            uint32_t n = 0;
            do { poll(e); SPIN_GUARD(n); } while ((ready & mask) != mask);
            fence_async_global();
          }
        };
        auto fresh = [&](int e, int it, uint32_t full, uint32_t empty, int par, uint32_t slot, uint4* src) {
          if (it >= 4) {
            const int kb = own_order(it, j);
            if (it < 10) need(e, 1u << kb); else if (it == 10) mbar_wait(bar + B_ALL, e & 1);
            plain(full, empty, par, slot, src + kb * 1024);
          } else {
            if (it == 0) { poll(e); ready = 0; }
            mbar_wait(empty, par);
            if (it < 2) { if (elect()) mbar_arrive(full); }
            else {
              const int b = it > 2;
              const uint32_t to_peer = mapa(sb, rank ^ 1) - sb;
              if (elect()) mbar_expect_tx(full, BLK);
              mbar_wait(bar + (b ? B_FREE + 8 : B_RDY), e & 1);
              if (b == 0) TR(e == 0 ? 24 : e == 2 ? 30 : 44);
              if (elect()) {
                if (b == 0) {
                  bulk_st(src + 2 * j * 1024, sb + STG, BLK);
                  bulk_commit();
                  bulk_wait_all();
                  mbar_arrive(bar + B_FREE);
                }
                fence_async_global();
                bulk_ld(slot + to_peer, src + (2 * j + b) * 1024, BLK, full + to_peer);
              }
              __syncwarp();
            }
          }
          if (it == 4) TR(e == 0 ? 28 : e == 1 ? 46 : 34);
        };
#pragma unroll 1
        for (int ph = 0; ph < 2; ph++) {
          uint4* h = gs->h + m * 16384;
#pragma unroll 1
          for (int it = 0; it < 16; it++) {
            const int s = (it + 2 * ph) & 3;
            if (ph) drained6(it);
            fresh(2 * ph, it, bar + B_FULL4 + s * 8, bar + B_EMPTY4 + s * 8, ~(it >> 2) & 1, sb + s * 49152, h);
          }
          if (ph) {
#pragma unroll 1
            for (int it = 16; it < 48; it++) {
              const int s = (it + 2) & 3;
              const uint32_t full = bar + B_FULL4 + s * 8;
              plain(full, full + 32, ~(it >> 2) & 1, sb + s * 49152, h + (it & 15) * 1024);
            }
          }
#pragma unroll 1
          for (int it = 0; it < 16; it++) { drained4(it, ph); plain6(h + it * 1024); }
          if (!ph) {
#pragma unroll 1
            for (int it = 0; it < 16; it++) { fresh(1, it, bar + B_FULL6 + s6 * 8, bar + B_EMPTY6 + s6 * 8, p6, sb + s6 * 32768, gs->o + m * 16384); next6(); }
            skip6();
          }
        }
#pragma unroll 1
        for (int it = 0; it < 56; it++) {
          if (it == 0 || it == 32 || it == 48) mbar_wait(bar + (it == 48 ? B_HH2 : B_HH + (it >> 2)), 0);
          plain6(gs->hh + m * 57344 + it * 1024);
        }
      }
    } else {
      const int b = warp - 10;
      const uint32_t ep = gs->epoch[bid + 4] + 1;
      const uint32_t stg = sb + STG + b * BLK;
      cl_arrive_relaxed(); cl_wait();
      auto all_there = [&](int u, uint32_t done) {
        const uint32_t* fl = gs->flag + u;
        uint32_t n = 0;
        while (!__all_sync(~0u, ld_acquire(fl) == ep)) { __nanosleep(100); SPIN_GUARD(n); }
        fence_async_global();
        if (lane == 0) mbar_arrive(done);
      };
      auto fetch_mod = [&](int sec) {
        const uint4* p = (const uint4*)(gs->modv + (sec - 2) * 1024 + j * 128) + lane;
        uint4 v0, v1; uint32_t n = 0;
        while (true) {
          v0 = ld_rlx4(p); v1 = ld_rlx4(p + 32);
          if (v0.y == ep && v0.w == ep && v1.y == ep && v1.w == ep) break;
          SPIN_GUARD(n);
        }
        mod_store(sb, sec, 2 * lane, __uint_as_float(v0.x)); mod_store(sb, sec, 2 * lane + 1, __uint_as_float(v0.z));
        mod_store(sb, sec, 64 + 2 * lane, __uint_as_float(v1.x)); mod_store(sb, sec, 65 + 2 * lane, __uint_as_float(v1.z));
        __syncwarp();
      };
#pragma unroll 1
      for (int e = 0; e < 7 - b; e++) {
        if (lane == 0) {
          if (e < 3) {
            mbar_wait(bar + B_FREE, e & 1);
            if (b) {
              const uint32_t t0 = clock();
              while ((uint32_t)clock() - t0 < B1D) {}
              mbar_wait(bar + B_RDY + 8, e & 1);
              bulk_st((e == 1 ? gs->o : gs->h) + m * 16384 + (2 * j + 1) * 1024, stg, BLK);
              bulk_commit();
              bulk_wait_all();
              mbar_arrive(bar + B_FREE + 8);
              TR(53 + e);
            }
            st_release(gs->flag + m * 128 + e * 16 + 2 * j + b, ep);
            TR((e == 0 ? 26 : e == 2 ? 32 : 42) + b);
          } else {
            const int kb = (e < 6 ? 2 * (8 * (e - 3) + j) : 48 + j) + b;
            mbar_wait(bar + B_RDY + b * 8, e & 1);
#pragma unroll 1
            for (int q = 0; q < NPIECE; q++) { if (q) __nanosleep(PSLEEP); bulk_st(gs->hh + m * 57344 + kb * 1024 + q * (1024 / NPIECE), stg + q * (BLK / NPIECE), BLK / NPIECE); }
            bulk_commit();
            bulk_wait_all();
            mbar_arrive(bar + B_FREE + b * 8);
            st_release(gs->flag + m * 128 + U_HH + kb, ep);
          }
        }
        __syncwarp();
        if (e < 3 && b) all_there(m * 128 + e * 16 + (lane & 15), bar + B_ALL);
        if (e == 4 && b) all_there(m * 128 + U_HH + lane, bar + B_HH);
        if (!b && (e == 1 || e == 2)) {
#pragma unroll 1
          for (int sec = e == 1 ? 2 : 5; sec < 4 + e; sec++) fetch_mod(sec);
          if (e == 1) { if (lane == 0) mbar_arrive(bar + B_MOD); TR(50); }
        }
        if (e == 0) {
          mbar_wait(bar + B_EMPTY6 + 24, 0);
          if (HSLEEP) __nanosleep(HSLEEP);
#pragma unroll 1
          for (int w = 0; w < 4; w++) {
            const uint4* hp = gs->halo + ((m * 8 + j) * 2 + (w & 1)) * 512 + b * 256 + (w >> 1) * 128 + lane;
            uint4 q[4] = {}; uint32_t n = 0;
            while (m > 0) {
              bool ok = true;
#pragma unroll
              for (int i = 0; i < 4; i++) q[i] = ld_rlx4(hp + i * 32);
#pragma unroll
              for (int i = 0; i < 4; i++) ok = ok && q[i].y == ep && q[i].w == ep;
              if (ok) break;
              SPIN_GUARD(n);
            }
#pragma unroll
            for (int i = 0; i < 2; i++) sts128(stg + lane * 16 + (w & 1) * HALF + (w >> 1) * 1024 + i * 512, q[2 * i].x, q[2 * i + 1].x, q[2 * i].z, q[2 * i + 1].z);
          }
          __syncwarp();
          if (lane == 0) mbar_arrive(bar + B_HALO);
          if (b == 0) TR(52);
        }
      }
      if (b) { all_there(m * 128 + U_HH + 32 + (lane & 15), bar + B_HH + 8); all_there(m * 128 + U_HH + 48 + (lane & 7), bar + B_HH2); }
    }
  } else {
    const int wg = warp >> 2, wq = warp & 3, tid = threadIdx.x;
    const int g = lane >> 2, c = lane & 3;
    const int sec0 = (m >> 1) & 1, hf0 = m & 1, ks0 = (m >> 2) & 3;
    uint4 wv[8];
    uint32_t ep0; uint16_t cv_;
    asm volatile("ld.global.nc.u16 %0, [%1];" : "=h"(cv_) : "l"(cvec + ks0 * 256 + warp * 32 + lane));
    asm volatile("ld.global.u32 %0, [%1];" : "=r"(ep0) : "l"(gs->epoch + bid + 4));
    if (!extra) {
      const bf16* wp = wmod + (size_t)(ks0 * 256 + warp * 32 + (lane >> 3)) * 6144 + sec0 * 1024 + j * 128 + hf0 * 64 + (lane & 7) * 8;
#pragma unroll
      for (int i = 0; i < 8; i++) wv[i] = ldg_nc(wp + (size_t)i * 4 * 6144);
    }
    asm volatile("setmaxnreg.inc.sync.aligned.u32 232;" ::: "memory");
    if (__builtin_expect(extra, 0)) {
      const uint32_t ep = ep0 + 1;
      float sv[4];
#pragma unroll
      for (int p = 0; p < 4; p++) sv[p] = silu_c(__bfloat162float(cvec[64 * (4 * p + (lane >> 3)) + 8 * warp + (lane & 7)]));
      named_bar(2, 288);
      int s = 0, par = 0;
#pragma unroll 1
      for (int sec = 0; sec < 4; sec++) {
        float a[8] = {0, 0, 0, 0, 0, 0, 0, 0};
#pragma unroll 1
        for (int it = 0; it < 16; it++) {
          const float sc = it < 4 ? sv[0] : it < 8 ? sv[1] : it < 12 ? sv[2] : sv[3];
          mbar_wait(bar + B_FULL6 + s * 8, par);
          uint4 w[8];
#pragma unroll
          for (int i = 0; i < 8; i++) w[i] = lds128(sb + s * 32768 + (warp * 8 + i) * 512 + lane * 16);
#pragma unroll
          for (int i = 0; i < 8; i++) gemv_fma(a, w[i], __shfl_sync(~0u, sc, (it & 3) * 8 + i));
          if (lane == 0) mbar_arrive(bar + B_EMPTY6 + s * 8);
          if (++s == 6) { s = 0; par ^= 1; }
        }
        const uint32_t red = sb + STG + sec * 8192;
        sts128(red + warp * 1024 + lane * 32, __float_as_uint(a[0]), __float_as_uint(a[1]), __float_as_uint(a[2]), __float_as_uint(a[3]));
        sts128(red + warp * 1024 + lane * 32 + 16, __float_as_uint(a[4]), __float_as_uint(a[5]), __float_as_uint(a[6]), __float_as_uint(a[7]));
        named_bar(1, 256);
        float t = 0;
#pragma unroll
        for (int q = 0; q < 8; q++) t += lds32f(red + q * 1024 + tid * 4);
        st_rlx2(gs->modv + sec * 1024 + (bid + 4) * 256 + tid, __float_as_uint(t), ep);
      }
      if (tid == 0) gs->epoch[bid + 4] = ep;
      return;
    }
    if (warp == 0) TR(0);
    const int row0 = wg * 64 + wq * 16 + g;
    if (c < 2) st_rlx4(gs->stat + m * 1024 + j * 128 + row0 + c * 8, 0, 0, 0, 0);
    if (tid < 64) st_rlx2(gs->modp + ((j * 2 + sec0) * 4 + ks0) * 128 + hf0 * 64 + tid, 0, 0);
    cl_arrive_relaxed(); cl_wait();
    uint32_t ep;
    asm volatile("add.u32 %0, %1, 1;" : "=r"(ep) : "r"(ep0) : "memory");
    const float sc_ = silu_c(__uint_as_float((uint32_t)cv_ << 16));
    const uint32_t rel = mapa(bar, (lane & 1) ^ rank);
    const uint32_t stg_row = sb + STG + (wg * 64 + wq * 16 + (lane & 15)) * 128;
    const uint32_t fre = bar + B_FREE;
    Ring r4{0, 0, 0}, r6{0, 0, 0};
    auto none = [](auto) {};
    {
      float a[8] = {0, 0, 0, 0, 0, 0, 0, 0};
#pragma unroll
      for (int i = 0; i < 8; i++) gemv_fma(a, wv[i], __shfl_sync(~0u, sc_, i * 4 + (lane >> 3)));
#pragma unroll
      for (int i = 0; i < 8; i++) { a[i] += __shfl_xor_sync(~0u, a[i], 8); a[i] += __shfl_xor_sync(~0u, a[i], 16); }
      if (lane < 8) {
        sts128(sb + RED_OFF + warp * 256 + lane * 32, __float_as_uint(a[0]), __float_as_uint(a[1]), __float_as_uint(a[2]), __float_as_uint(a[3]));
        sts128(sb + RED_OFF + warp * 256 + lane * 32 + 16, __float_as_uint(a[4]), __float_as_uint(a[5]), __float_as_uint(a[6]), __float_as_uint(a[7]));
      }
      named_bar(1, 256);
      if (tid < 64) {
        float s = 0;
#pragma unroll
        for (int w = 0; w < 8; w++) s += lds32f(sb + RED_OFF + w * 256 + tid * 4);
        st_rlx2(gs->modp + ((j * 2 + sec0) * 4 + ks0) * 128 + hf0 * 64 + tid, __float_as_uint(s), ep);
      }
      if (warp == 0) TR(1);
      float v[64];
      mbar_wait(bar + B_X, 0); mbar_wait(bar + B_X + 8, 0);
#pragma unroll
      for (int i = 0; i < 16; i += 2) {
        uint32_t w0, w1, w2, w3;
        ldsm4(stg_row + (i >> 3) * BLK + ((((i & 7) + (lane >> 4)) ^ (lane & 7)) << 4), w0, w1, w2, w3);
        v[4 * i] = bf_lo(w0); v[4 * i + 1] = bf_hi(w0); v[4 * i + 2] = bf_lo(w1); v[4 * i + 3] = bf_hi(w1);
        v[4 * i + 4] = bf_lo(w2); v[4 * i + 5] = bf_hi(w2); v[4 * i + 6] = bf_lo(w3); v[4 * i + 7] = bf_hi(w3);
      }
      ln_publish(v, gs->stat + m * 1024, j, row0, lane, ep);
      if (warp == 0) TR(2);
      mod_store(sb, tid >> 7, tid & 127, mod_gather(gs->modp + (j * 2 + (tid >> 7)) * 512 + (tid & 127), ep));
      named_bar(1, 256);
      if (warp == 0) TR(3);
      ln_apply(v, gs->stat + m * 1024, row0, ep, sb, 0, 1, stg_row, wg, lane);
      named_bar(2 + wg, 128);
    }
    if (warp == 0) TR(4);
    {
      uint32_t kf[32], vf[32], pv[32];
      const bool first = wq == 0 && m == 0;
      const uint32_t xa = sb + STG + wg * HALF + wq * 2048 + lane * 16;
      {
        float acc[128];
        mainloop<256, 4, 0>(acc, 16, true, r4, sb, wg, lane, rel, STEP0 + 0, none, none, [&] {
          mbar_wait(fre + 8, 0);
          if (c < 2) st_rlx4(gs->stat + (16 + m) * 1024 + j * 128 + row0 + c * 8, 0, 0, 0, 0);
        });
        if (warp == 0) TR(5);
#pragma unroll
        for (int i = 0; i < 32; i++) { kf[i] = pack2(acc[2 * i], acc[2 * i + 1]); vf[i] = pack2(acc[64 + 2 * i], acc[65 + 2 * i]); }
      }
      if (warp == 0) TR(6);
      float acc[64];
      constexpr int QP = 2;
      mainloop<128, 6, 8 / QP>(acc, 16, false, r6, sb, wg, lane, rel, STEP0 + 16, [&](auto ic) {
        constexpr int q = (ic.v - 1) * QP;
#pragma unroll
        for (int i = 4 * q; i < 4 * (q + QP); i++) vf[i] = movm(vf[i]);
        if (wq == 3) {
          if (m < 15) {
            uint4* hp = gs->halo + (((m + 1) * 8 + j) * 2 + wg) * 512 + lane;
#pragma unroll
            for (int i = 2 * q; i < 2 * (q + QP); i++) st_rlx4(hp + i * 32, kf[2 * i + 1], ep, vf[2 * i + 1], ep);
          }
        } else {
#pragma unroll
          for (int i = q; i < q + QP; i++) sts128(xa + 2048 + (i >> 2) * BLK + (i & 3) * 512, kf[4 * i + 1], kf[4 * i + 3], vf[4 * i + 1], vf[4 * i + 3]);
        }
      }, none, [&] {
        named_bar(2 + wg, 128);
        if (wq == 0) mbar_wait(bar + B_HALO, 0);
#pragma unroll
        for (int i = 0; i < 8; i++) {
          uint4 q = lds128(xa + (i >> 2) * BLK + (i & 3) * 512);
          pv[4 * i] = q.x; pv[4 * i + 1] = q.y; pv[4 * i + 2] = q.z; pv[4 * i + 3] = q.w;
        }
        __syncwarp();
      });
      if (warp == 0) TR(7);
      int gz = g;
#pragma unroll
      for (int b = 0; b < 2; b++) {
        const bool up0 = 2 * c > gz, up1 = 2 * c + 1 > gz;
        const uint32_t mup = (up0 ? 0xffffu : 0u) | (up1 ? 0xffff0000u : 0u);
        float l[2][4], mx[4];
#pragma unroll
        for (int h = 0; h < 2; h++) {
          uint32_t q[8];
          const int k = 16 * b + 8 * h;
#pragma unroll
          for (int i = 0; i < 8; i++) q[i] = pack2(acc[2 * k + 2 * i], acc[2 * k + 2 * i + 1]);
          float s0[4], s1[4], s2[4];
          mma16z(s0, q[0], q[1], q[2], q[3], pv[k], pv[k + 1]); mma16z(s1, q[0], q[1], q[2], q[3], kf[k], kf[k + 2]); mma16z(s2, q[0], q[1], q[2], q[3], kf[k + 1], kf[k + 3]);
          mma16(s0, q[4], q[5], q[6], q[7], pv[k + 4], pv[k + 5]); mma16(s1, q[4], q[5], q[6], q[7], kf[k + 4], kf[k + 6]); mma16(s2, q[4], q[5], q[6], q[7], kf[k + 5], kf[k + 7]);
          if (first) { s0[0] = -INFINITY; s0[1] = -INFINITY; }
          l[h][0] = up0 ? s0[0] : s1[0]; l[h][1] = up1 ? s0[1] : s1[1]; l[h][2] = up0 ? s1[2] : s2[2]; l[h][3] = up1 ? s1[3] : s2[3];
          mx[2 * h] = fmaxf(l[h][0], l[h][1]); mx[2 * h + 1] = fmaxf(l[h][2], l[h][3]);
        }
#pragma unroll
        for (int o = 1; o < 4; o <<= 1) {
#pragma unroll
          for (int h = 0; h < 4; h++) mx[h] = fmaxf(mx[h], __shfl_xor_sync(~0u, mx[h], o));
        }
#pragma unroll
        for (int h = 0; h < 2; h++) {
          const float n0 = -mx[2 * h] * SCL, n1 = -mx[2 * h + 1] * SCL;
          const uint32_t pa = pack2(ex2(fmaf(l[h][0], SCL, n0)), ex2(fmaf(l[h][1], SCL, n0))), pb = pack2(ex2(fmaf(l[h][2], SCL, n1)), ex2(fmaf(l[h][3], SCL, n1)));
          float sm[4];
          mma8z(sm, pa, pb, 0x3f803f80u);
          const float ia = rcp(sm[0]), ib = rcp(sm[2]);
#pragma unroll
          for (int i = 8 * b + 4 * h; i < 8 * b + 4 * h + 4; i += 2) {
            uint32_t of[4];
#pragma unroll
            for (int d = 0; d < 2; d++) {
              float o[4];
              mma16z(o, pa & ~mup, pb & mup, 0u, pb & ~mup, vf[2 * (i + d)], vf[2 * (i + d) + 1]);
              mma8(o, pa & mup, 0u, pv[2 * i + 2 + d]);
              of[2 * d] = pack2(o[0] * ia, o[1] * ia); of[2 * d + 1] = pack2(o[2] * ib, o[3] * ib);
            }
            stsm4(stg_row + b * BLK + ((((i & 7) + (lane >> 4)) ^ (lane & 7)) << 4), of[0], of[1], of[2], of[3]);
          }
        }
        stage_done(sb, wg, b, lane);
        if (b == 0) gz += __float_as_uint(lds32f(bar + ZERO));
      }
      named_bar(1, 256);
      if (warp == 0) TR(8);
    }
    uint32_t pk[64];
    {
      float acc[64];
      mainloop<128, 6, 0>(acc, 16, true, r6, sb, wg, lane, rel, STEP0 + 32, none, none, [&] {
        mbar_wait(bar + B_MOD, 0); mbar_wait(bar + B_X, 1); mbar_wait(bar + B_X + 8, 1);
        load_vec(pk + 32, sb, 2, 0, lane); load_vec(pk + 40, sb, 2, 1, lane);
#pragma unroll
        for (int i = 0; i < 16; i += 2) ldsm4(stg_row + (i >> 3) * BLK + ((((i & 7) + (lane >> 4)) ^ (lane & 7)) << 4), pk[2 * i], pk[2 * i + 1], pk[2 * i + 2], pk[2 * i + 3]);
      });
      if (warp == 0) TR(9);
#pragma unroll
      for (int i = 0; i < 32; i++) {
        acc[2 * i] = fmaf(acc[2 * i], bf_lo(pk[32 + (i >> 1)]), bf_lo(pk[i]));
        acc[2 * i + 1] = fmaf(acc[2 * i + 1], bf_hi(pk[32 + (i >> 1)]), bf_hi(pk[i]));
      }
      ln_publish(acc, gs->stat + (16 + m) * 1024, j, row0, lane, ep);
      if (warp == 0) TR(36);
      mbar_wait(bar + B_FULL6 + 16, 1);
      if (lane < 2) mbar_arrive_cl(rel + B_EMPTY6 + 16);
      ring_next<6>(r6);
#pragma unroll
      for (int i = 0; i < 32; i++) { pk[i] = pack2(acc[2 * i], acc[2 * i + 1]); pk[32 + i] = 0; }
      ln_apply(acc, gs->stat + (16 + m) * 1024, row0, ep, sb, 3, 4, stg_row, wg, lane);
      named_bar(2 + wg, 128);
      if (warp == 0) TR(11);
    }
    auto swiglu = [&](int q, int uo, int par) {
      if ((q & 3) == 0 && par >= 0) mbar_wait(fre + 2 * q, par);
      uint32_t w[4];
#pragma unroll
      for (int u = 0; u < 4; u++) w[u] = silu_mul2(pk[4 * q + u], pk[uo + 4 * q + u]);
      stsm4(stg_row + (q >> 2) * BLK + ((((2 * q & 7) + (lane >> 4)) ^ (lane & 7)) << 4), w[0], w[1], w[2], w[3]);
    };
    r4.s = r4.wrap = 2;
#pragma unroll 1
    for (int t = 0; t < 3; t++) {
      float acc[128];
      mainloop<256, 4, 5>(acc, 16, t == 0, r4, sb, wg, lane, rel, STEP0 + 48 + 16 * t, [&](auto ic) {
        if (t) {
          if (ic.v == 3 || ic.v == 5) stage_done(sb, wg, ic.v >> 2, lane);
          if (ic.v < 5) { swiglu(2 * ic.v - 2, 32, ~t & 1); swiglu(2 * ic.v - 1, 32, 0); }
        }
      }, [&](int it) {
#pragma unroll
        for (int i = 0; i < 8; i++)
          if (t == 0 && it == 6 + i) gs->x1[bid * 2048 + (i >> 2) * 1024 + warp * 128 + (i & 3) * 32 + lane] = make_uint4(pk[4 * i], pk[4 * i + 1], pk[4 * i + 2], pk[4 * i + 3]);
      }, [&] { if (t == 0) fence_async_global(); else if (t == 2) mbar_wait(bar + B_X, KEEPX); });
      if (warp == 0) TR(12 + 2 * t);
#pragma unroll
      for (int i = 0; i < 64; i++) pk[i] = pack2(acc[2 * i], acc[2 * i + 1]);
      if (warp == 0) TR(13 + 2 * t);
    }
    uint32_t x1[32];
    {
      float acc[64];
      mainloop<128, 6, 12>(acc, 16, false, r6, sb, wg, lane, rel, STEP0 + 96, [&](auto ic) {
        constexpr int b = ic.v > 6, q = ic.v - 6 * b;
        if (q == 1) {
#pragma unroll
          for (int i = 4 * b; i < 4 * b + 4; i++) { const uint4 x = lds128(sb + STG + b * BLK + warp * 2048 + (i & 3) * 512 + lane * 16); x1[4 * i] = x.x; x1[4 * i + 1] = x.y; x1[4 * i + 2] = x.z; x1[4 * i + 3] = x.w; }
          __syncwarp();
        } else if (q < 6) swiglu(4 * b + q - 2, 32, -1);
        else stage_done(sb, wg, b, lane);
      }, none, [] {});
      if (warp == 0) TR(18);
#pragma unroll
      for (int i = 0; i < 32; i++) pk[i] = pack2(acc[2 * i], acc[2 * i + 1]);
      if (warp == 0) TR(19);
    }
    {
      float acc[64];
      mainloop<128, 6, 5>(acc, 56, false, r6, sb, wg, lane, rel, STEP0 + 112, [&](auto ic) {
        if (ic.v == 5) stage_done(sb, wg, 0, lane); else swiglu(ic.v - 1, 16, 1);
      }, none, [&] {
        if (TAILLAG && wg == 0 && lane == 0) mbar_arrive(bar + B_LAG);
        load_vec(pk + 32, sb, 5, 0, lane); load_vec(pk + 40, sb, 5, 1, lane);
        mbar_wait(fre, 0); mbar_wait(fre + 8, 1);
      });
      __syncwarp();
      cl_arrive_relaxed();
      if (warp == 0) TR(20);
#pragma unroll
      for (int i = 0; i < 16; i += 2) {
        uint32_t w[4];
#pragma unroll
        for (int u = 0; u < 4; u++) {
          const int q = 2 * i + u;
          w[u] = pack2(fmaf(acc[2 * q], bf_lo(pk[32 + (q >> 1)]), bf_lo(x1[q])), fmaf(acc[2 * q + 1], bf_hi(pk[32 + (q >> 1)]), bf_hi(x1[q])));
        }
        stsm4(stg_row + (i >> 3) * BLK + ((((i & 7) + (lane >> 4)) ^ (lane & 7)) << 4), w[0], w[1], w[2], w[3]);
        if ((i & 7) == 6) {
          fence_async_smem();
          named_bar(2 + wg, 128);
          if (wq == 0 && elect()) { tma_store_3d(&maps.out, sb + STG + (i >> 3) * BLK + wg * HALF, j * 128 + (i >> 3) * 64, m * 64, wg); bulk_commit(); }
          if (i < 8) x1[16] |= __float_as_uint(lds32f(bar + ZERO));
        }
      }
      if (wq == 0) bulk_wait_read();
      if (wq == 0) TR(40 + wg);
      if (tid == 0) gs->epoch[bid + 4] = ep;
      if (warp == 0) TR(21);
      cl_wait();
    }
  }
}

typedef CUresult (*EncodeFn)(CUtensorMap*, CUtensorMapDataType, cuuint32_t, void*, const cuuint64_t*, const cuuint64_t*, const cuuint32_t*, const cuuint32_t*,
                             CUtensorMapInterleave, CUtensorMapSwizzle, CUtensorMapL2promotion, CUtensorMapFloatOOBfill);

void make_map(EncodeFn fn, CUtensorMap* mp, const void* base, uint64_t d0, uint64_t d1, uint64_t d2, uint64_t s1, uint64_t s2, uint32_t b2, uint32_t b0 = 64) {
  cuuint64_t d[3] = {d0, d1, d2}, s[2] = {s1, s2};
  cuuint32_t b[3] = {b0, 64, b2}, e[3] = {1, 1, 1};
  fn(mp, CU_TENSOR_MAP_DATA_TYPE_BFLOAT16, 3, (void*)base, d, s, b, e, CU_TENSOR_MAP_INTERLEAVE_NONE, b0 == 64 ? CU_TENSOR_MAP_SWIZZLE_128B : CU_TENSOR_MAP_SWIZZLE_NONE,
     CU_TENSOR_MAP_L2_PROMOTION_L2_128B, CU_TENSOR_MAP_FLOAT_OOB_FILL_NONE);
}

__global__ void probe_kernel() {}
int max_clusters(int size) {
  cudaLaunchConfig_t cfg = {};
  cudaLaunchAttribute at;
  at.id = cudaLaunchAttributeClusterDimension; at.val.clusterDim.x = size; at.val.clusterDim.y = 1; at.val.clusterDim.z = 1;
  cfg.gridDim = dim3(size * 66); cfg.blockDim = dim3(384); cfg.dynamicSmemBytes = SMEM_BYTES; cfg.attrs = &at; cfg.numAttrs = 1;
  int n = 0;
  if (cudaOccupancyMaxActiveClusters(&n, probe_kernel, &cfg) != cudaSuccess) { cudaGetLastError(); return 0; }
  return n;
}

}

extern "C" void kernel_launch(void* const* d_in, const int* in_sizes, int n_in, void* d_out, int out_size) {
  static EncodeFn fn = nullptr;
  static int by_sm = 0;
  static Scratch* gs = nullptr;
  if (!fn) {
    void* p = nullptr; cudaDriverEntryPointQueryResult q;
    cudaGetDriverEntryPoint("cuTensorMapEncodeTiled", &p, cudaEnableDefault, &q);
    fn = (EncodeFn)p;
    cudaFuncSetAttribute(fused_kernel, cudaFuncAttributeMaxDynamicSharedMemorySize, SMEM_BYTES);
    int dev = 0, sms = 0;
    cudaGetSymbolAddress((void**)&gs, g_scratch);
    cudaGetDevice(&dev);
    cudaDeviceGetAttribute(&sms, cudaDevAttrMultiProcessorCount, dev);
    cudaFuncSetAttribute(probe_kernel, cudaFuncAttributeMaxDynamicSharedMemorySize, SMEM_BYTES);
    by_sm = BYSM && sms == 132 && max_clusters(2) == 66 && max_clusters(4) == 30 && max_clusters(6) == 17 && max_clusters(8) == 15;
  }
  Maps mp;
  make_map(fn, &mp.x, d_in[0], D_, S_ / 2, 2, 4096, 2048, 2);
  make_map(fn, &mp.out, d_out, D_, S_ / 2, 2, 4096, 2048, 1);
  make_map(fn, &mp.wqkv, d_in[1], 64, D_, 3 * D_ / 64, 3 * D_ * 2, 128, 2);
  make_map(fn, &mp.wo, d_in[2], 64, D_, D_ / 64, D_ * 2, 128, 2);
  make_map(fn, &mp.w1, d_in[4], 64, D_, F_ / 64, F_ * 2, 128, 2);
  make_map(fn, &mp.w3, d_in[5], 64, D_, F_ / 64, F_ * 2, 128, 2);
  make_map(fn, &mp.w1s, d_in[4], 64, D_, F_ / 64, F_ * 2, 128, 1);
  make_map(fn, &mp.w3s, d_in[5], 64, D_, F_ / 64, F_ * 2, 128, 1);
  make_map(fn, &mp.w2, d_in[6], 64, F_, D_ / 64, D_ * 2, 128, 2);
  make_map(fn, &mp.wmod, d_in[8], 256, D_, 24, 6 * D_ * 2, 512, 1, 256);
  fused_kernel<<<132, 384, SMEM_BYTES>>>((const bf16*)d_in[7], (const bf16*)d_in[8], gs, by_sm, mp);
}
```

```cpp
#include <cuda_runtime.h>
#include <cuda_bf16.h>
#include <cuda.h>
#include <stdint.h>

typedef __nv_bfloat16 bf16;

#define NPIECE 4
#define PSLEEP 300
#define XSLEEP 4000
#define XDELAY 2000
#define TAILLAG 5
#define HSLEEP 400
#define B1D 900
#define BYSM 1
namespace {

constexpr int S_ = 2048, D_ = 1024, F_ = 3584;
constexpr int BLK = 16384;
constexpr int HALF = 8192;
constexpr int RING = 196608;
constexpr int STG = RING;
constexpr int MISC = RING + 2 * BLK;
constexpr int SMEM_BYTES = MISC + 3072;
constexpr int B_FULL4 = 0, B_EMPTY4 = 32, B_FULL6 = 64, B_EMPTY6 = 112, B_RDY = 160, B_FREE = 176, B_LAG = 192, B_X = 208, B_MOD = 224, B_HALO = 232, B_HH = 256, B_ALL = 272, B_HH2 = 288, ZERO = 296;
constexpr int MODV = 512;
constexpr int RED_OFF = 0;
constexpr float SCL = 0.17677669529663687f * 1.4426950408889634f;
constexpr int U_HH = 64;

struct Maps { CUtensorMap x, out, wqkv, wo, w1, w3, w1s, w3s, w2, wmod; };

struct Scratch {
  uint4 h[16 * 16 * 1024];
  uint4 o[16 * 16 * 1024];
  uint4 hh[16 * 56 * 1024];
  uint4 x1[128 * 8 * 256];
  uint4 stat[2 * 16 * 8 * 128];
  uint4 halo[16 * 8 * 2 * 512];
  uint2 modp[8 * 2 * 4 * 128];
  uint2 modv[4 * 1024];
  uint32_t flag[16 * 128];
  uint32_t epoch[132];
};
__device__ __align__(1024) Scratch g_scratch;
#define TR(i)
#define TRS(i)
#define STEP0 gs->flag

__device__ __forceinline__ void bail() { asm volatile("st.global.u32 [%0], %1;" :: "l"(0ull), "r"(0) : "memory"); }
__device__ __forceinline__ uint32_t smem_u32(const void* p) { return (uint32_t)__cvta_generic_to_shared(p); }
__device__ __forceinline__ void mbar_init(uint32_t bar, uint32_t cnt) { asm volatile("mbarrier.init.shared::cta.b64 [%0], %1;" :: "r"(bar), "r"(cnt) : "memory"); }
__device__ __forceinline__ void mbar_expect_tx(uint32_t bar, uint32_t bytes) { asm volatile("mbarrier.arrive.expect_tx.shared::cta.b64 _, [%0], %1;" :: "r"(bar), "r"(bytes) : "memory"); }
__device__ __forceinline__ void mbar_arrive(uint32_t bar) { asm volatile("mbarrier.arrive.shared::cta.b64 _, [%0];" :: "r"(bar) : "memory"); }
__device__ __forceinline__ void mbar_arrive_cl(uint32_t cl_addr) { asm volatile("mbarrier.arrive.shared::cluster.b64 _, [%0];" :: "r"(cl_addr) : "memory"); }
__device__ __forceinline__ uint32_t mapa(uint32_t addr, uint32_t cta) { uint32_t r; asm("mapa.shared::cluster.u32 %0, %1, %2;" : "=r"(r) : "r"(addr), "r"(cta)); return r; }
__device__ __forceinline__ void mbar_wait(uint32_t bar, uint32_t parity) {
  asm volatile("{\n.reg .pred p;\n.reg .b32 n;\n.reg .b64 z;\nmov.b32 n, 0;\nmov.b64 z, 0;\n"
               "W: add.u32 n, n, 1;\nsetp.gt.u32 p, n, 0x400000;\n@p st.global.u32 [z], n;\n"
               "mbarrier.try_wait.parity.shared::cta.b64 p, [%0], %1;\n@!p bra W;\n}" :: "r"(bar), "r"(parity) : "memory");
}
__device__ __forceinline__ void tma_3d(uint32_t dst, const CUtensorMap* m, uint32_t bar, int c0, int c1, int c2) {
  asm volatile("cp.async.bulk.tensor.3d.shared::cluster.global.mbarrier::complete_tx::bytes [%0], [%1, {%3, %4, %5}], [%2];" :: "r"(dst), "l"(m), "r"(bar), "r"(c0), "r"(c1), "r"(c2) : "memory");
}
__device__ __forceinline__ void tma_store_3d(const CUtensorMap* m, uint32_t src, int c0, int c1, int c2) {
  asm volatile("cp.async.bulk.tensor.3d.global.shared::cta.bulk_group [%0, {%2, %3, %4}], [%1];" :: "l"(m), "r"(src), "r"(c0), "r"(c1), "r"(c2) : "memory");
}
__device__ __forceinline__ void bulk_ld(uint32_t dst, const void* src, uint32_t bytes, uint32_t bar) {
  asm volatile("cp.async.bulk.shared::cluster.global.mbarrier::complete_tx::bytes [%0], [%1], %2, [%3];" :: "r"(dst), "l"(src), "r"(bytes), "r"(bar) : "memory");
}
__device__ __forceinline__ void bulk_ld_mc(uint32_t dst, const void* src, uint32_t bytes, uint32_t bar) {
  asm volatile("cp.async.bulk.shared::cluster.global.mbarrier::complete_tx::bytes.multicast::cluster [%0], [%1], %2, [%3], %4;" :: "r"(dst), "l"(src), "r"(bytes), "r"(bar), "h"((uint16_t)3) : "memory");
}
__device__ __forceinline__ void bulk_st(void* dst, uint32_t src, uint32_t bytes) {
  asm volatile("cp.async.bulk.global.shared::cta.bulk_group [%0], [%1], %2;" :: "l"(dst), "r"(src), "r"(bytes) : "memory");
}
__device__ __forceinline__ void bulk_commit() { asm volatile("cp.async.bulk.commit_group;" ::: "memory"); }
__device__ __forceinline__ void bulk_wait_read() { asm volatile("cp.async.bulk.wait_group.read 0;" ::: "memory"); }
__device__ __forceinline__ void bulk_wait_all() { asm volatile("cp.async.bulk.wait_group 0;" ::: "memory"); }
__device__ __forceinline__ void fence_async_global() { asm volatile("fence.proxy.async.global;" ::: "memory"); }
__device__ __forceinline__ void fence_async_smem() { asm volatile("fence.proxy.async.shared::cta;" ::: "memory"); }
__device__ __forceinline__ void wg_arrive() { asm volatile("wgmma.fence.sync.aligned;" ::: "memory"); }
__device__ __forceinline__ void wg_commit() { asm volatile("wgmma.commit_group.sync.aligned;" ::: "memory"); }
template <int N> __device__ __forceinline__ void wg_wait() { asm volatile("wgmma.wait_group.sync.aligned %0;" :: "n"(N) : "memory"); }
__device__ __forceinline__ void cl_arrive_relaxed() { asm volatile("barrier.cluster.arrive.relaxed.aligned;" ::: "memory"); }
__device__ __forceinline__ void cl_wait() { asm volatile("barrier.cluster.wait.acquire.aligned;" ::: "memory"); }
__device__ __forceinline__ bool elect() { uint32_t p; asm volatile("{\n.reg .pred p;\nelect.sync _|p, 0xffffffff;\nselp.u32 %0, 1, 0, p;\n}" : "=r"(p)); return p; }
__device__ __forceinline__ void named_bar(int id, int n) { asm volatile("bar.sync %0, %1;" :: "r"(id), "r"(n) : "memory"); }
__device__ __forceinline__ uint32_t pack2(float lo, float hi) { uint32_t r; asm("cvt.rn.bf16x2.f32 %0, %1, %2;" : "=r"(r) : "f"(hi), "f"(lo)); return r; }
__device__ __forceinline__ float bf_lo(uint32_t w) { return __uint_as_float(w << 16); }
__device__ __forceinline__ float bf_hi(uint32_t w) { return __uint_as_float(w & 0xffff0000u); }
__device__ __forceinline__ float bf_round(float v) { return __bfloat162float(__float2bfloat16_rn(v)); }
__device__ __forceinline__ void stsm4(uint32_t addr, uint32_t a, uint32_t b, uint32_t c, uint32_t d) {
  asm volatile("stmatrix.sync.aligned.m8n8.x4.shared.b16 [%0], {%1, %2, %3, %4};" :: "r"(addr), "r"(a), "r"(b), "r"(c), "r"(d) : "memory");
}
__device__ __forceinline__ void ldsm4(uint32_t addr, uint32_t& a, uint32_t& b, uint32_t& c, uint32_t& d) {
  asm volatile("ldmatrix.sync.aligned.m8n8.x4.shared.b16 {%0, %1, %2, %3}, [%4];" : "=r"(a), "=r"(b), "=r"(c), "=r"(d) : "r"(addr) : "memory");
}
__device__ __forceinline__ uint32_t movm(uint32_t a) { uint32_t r; asm volatile("movmatrix.sync.aligned.m8n8.trans.b16 %0, %1;" : "=r"(r) : "r"(a)); return r; }
__device__ __forceinline__ void mma16(float (&d)[4], uint32_t a0, uint32_t a1, uint32_t a2, uint32_t a3, uint32_t b0, uint32_t b1) {
  asm("mma.sync.aligned.m16n8k16.row.col.f32.bf16.bf16.f32 {%0,%1,%2,%3}, {%4,%5,%6,%7}, {%8,%9}, {%0,%1,%2,%3};"
               : "+f"(d[0]), "+f"(d[1]), "+f"(d[2]), "+f"(d[3]) : "r"(a0), "r"(a1), "r"(a2), "r"(a3), "r"(b0), "r"(b1));
}
__device__ __forceinline__ void mma16z(float (&d)[4], uint32_t a0, uint32_t a1, uint32_t a2, uint32_t a3, uint32_t b0, uint32_t b1) {
  asm("mma.sync.aligned.m16n8k16.row.col.f32.bf16.bf16.f32 {%0,%1,%2,%3}, {%4,%5,%6,%7}, {%8,%9}, {%10,%10,%10,%10};"
      : "=f"(d[0]), "=f"(d[1]), "=f"(d[2]), "=f"(d[3]) : "r"(a0), "r"(a1), "r"(a2), "r"(a3), "r"(b0), "r"(b1), "f"(0.f));
}
__device__ __forceinline__ void mma8z(float (&d)[4], uint32_t a0, uint32_t a1, uint32_t b0) {
  asm("mma.sync.aligned.m16n8k8.row.col.f32.bf16.bf16.f32 {%0,%1,%2,%3}, {%4,%5}, {%6}, {%7,%7,%7,%7};"
      : "=f"(d[0]), "=f"(d[1]), "=f"(d[2]), "=f"(d[3]) : "r"(a0), "r"(a1), "r"(b0), "f"(0.f));
}
__device__ __forceinline__ void mma8(float (&d)[4], uint32_t a0, uint32_t a1, uint32_t b0) {
  asm("mma.sync.aligned.m16n8k8.row.col.f32.bf16.bf16.f32 {%0,%1,%2,%3}, {%4,%5}, {%6}, {%0,%1,%2,%3};"
               : "+f"(d[0]), "+f"(d[1]), "+f"(d[2]), "+f"(d[3]) : "r"(a0), "r"(a1), "r"(b0));
}
__device__ __forceinline__ uint4 lds128(uint32_t a) { uint4 v; asm volatile("ld.shared.v4.u32 {%0,%1,%2,%3}, [%4];" : "=r"(v.x), "=r"(v.y), "=r"(v.z), "=r"(v.w) : "r"(a) : "memory"); return v; }
__device__ __forceinline__ void sts128(uint32_t a, uint32_t x, uint32_t y, uint32_t z, uint32_t w) { asm volatile("st.shared.v4.u32 [%0], {%1,%2,%3,%4};" :: "r"(a), "r"(x), "r"(y), "r"(z), "r"(w) : "memory"); }
__device__ __forceinline__ float lds32f(uint32_t a) { float v; asm volatile("ld.shared.f32 %0, [%1];" : "=f"(v) : "r"(a) : "memory"); return v; }
__device__ __forceinline__ void sts16(uint32_t a, bf16 v) { asm volatile("st.shared.b16 [%0], %1;" :: "r"(a), "h"(__bfloat16_as_ushort(v)) : "memory"); }
__device__ __forceinline__ uint4 ldg_nc(const void* p) { uint4 v; asm volatile("ld.global.nc.L1::no_allocate.v4.u32 {%0,%1,%2,%3}, [%4];" : "=r"(v.x), "=r"(v.y), "=r"(v.z), "=r"(v.w) : "l"(p)); return v; }
__device__ __forceinline__ uint4 ld_rlx4(const uint4* p) {
  unsigned long long a, b; asm volatile("ld.relaxed.gpu.global.v2.b64 {%0,%1}, [%2];" : "=l"(a), "=l"(b) : "l"(p) : "memory");
  return make_uint4((uint32_t)a, (uint32_t)(a >> 32), (uint32_t)b, (uint32_t)(b >> 32));
}
__device__ __forceinline__ uint2 ld_rlx2(const uint2* p) { unsigned long long a; asm volatile("ld.relaxed.gpu.global.b64 %0, [%1];" : "=l"(a) : "l"(p) : "memory"); return make_uint2((uint32_t)a, (uint32_t)(a >> 32)); }
__device__ __forceinline__ void st_rlx4(uint4* p, uint32_t x, uint32_t y, uint32_t z, uint32_t w) {
  asm volatile("st.relaxed.gpu.global.v2.b64 [%0], {%1,%2};" :: "l"(p), "l"((unsigned long long)x | ((unsigned long long)y << 32)), "l"((unsigned long long)z | ((unsigned long long)w << 32)) : "memory");
}
__device__ __forceinline__ void st_rlx2(uint2* p, uint32_t x, uint32_t y) { asm volatile("st.relaxed.gpu.global.b64 [%0], %1;" :: "l"(p), "l"((unsigned long long)x | ((unsigned long long)y << 32)) : "memory"); }
__device__ __forceinline__ void st_release(uint32_t* p, uint32_t v) { asm volatile("st.release.gpu.global.u32 [%0], %1;" :: "l"(p), "r"(v) : "memory"); }
__device__ __forceinline__ uint32_t ld_acquire(const uint32_t* p) { uint32_t v; asm volatile("ld.acquire.gpu.global.u32 %0, [%1];" : "=r"(v) : "l"(p) : "memory"); return v; }
__device__ __forceinline__ void prefetch_map(const CUtensorMap* m) { asm volatile("prefetch.tensormap [%0];" :: "l"(m) : "memory"); }
__device__ __forceinline__ float rcp(float x) { float r; asm("rcp.approx.ftz.f32 %0, %1;" : "=f"(r) : "f"(x)); return r; }
__device__ __forceinline__ float ex2(float x) { float r; asm("ex2.approx.ftz.f32 %0, %1;" : "=f"(r) : "f"(x)); return r; }
__device__ __forceinline__ float tanh_fast(float x) { float r; asm("tanh.approx.f32 %0, %1;" : "=f"(r) : "f"(x)); return r; }
#define SPIN_GUARD(n) if (++(n) > (1u << 24)) bail()

__device__ __forceinline__ void wgmma_n128(float (&d)[64], uint64_t da, uint64_t db) {
  asm volatile("wgmma.mma_async.sync.aligned.m64n128k16.f32.bf16.bf16 "
    "{%0, %1, %2, %3, %4, %5, %6, %7, %8, %9, %10, %11, %12, %13, %14, %15, %16, %17, %18, %19, %20, %21, %22, %23, %24, %25, %26, %27, %28, %29, %30, %31, %32, %33, %34, %35, %36, %37, %38, %39, %40, %41, %42, %43, %44, %45, %46, %47, %48, %49, %50, %51, %52, %53, %54, %55, %56, %57, %58, %59, %60, %61, %62, %63}, "
    "%64, %65, 1, 1, 1, 0, 1;\n"
    : "+f"(d[0]), "+f"(d[1]), "+f"(d[2]), "+f"(d[3]), "+f"(d[4]), "+f"(d[5]), "+f"(d[6]), "+f"(d[7]), "+f"(d[8]), "+f"(d[9]), "+f"(d[10]), "+f"(d[11]), "+f"(d[12]), "+f"(d[13]), "+f"(d[14]), "+f"(d[15]), "+f"(d[16]), "+f"(d[17]), "+f"(d[18]), "+f"(d[19]), "+f"(d[20]), "+f"(d[21]), "+f"(d[22]), "+f"(d[23]), "+f"(d[24]), "+f"(d[25]), "+f"(d[26]), "+f"(d[27]), "+f"(d[28]), "+f"(d[29]), "+f"(d[30]), "+f"(d[31]), "+f"(d[32]), "+f"(d[33]), "+f"(d[34]), "+f"(d[35]), "+f"(d[36]), "+f"(d[37]), "+f"(d[38]), "+f"(d[39]), "+f"(d[40]), "+f"(d[41]), "+f"(d[42]), "+f"(d[43]), "+f"(d[44]), "+f"(d[45]), "+f"(d[46]), "+f"(d[47]), "+f"(d[48]), "+f"(d[49]), "+f"(d[50]), "+f"(d[51]), "+f"(d[52]), "+f"(d[53]), "+f"(d[54]), "+f"(d[55]), "+f"(d[56]), "+f"(d[57]), "+f"(d[58]), "+f"(d[59]), "+f"(d[60]), "+f"(d[61]), "+f"(d[62]), "+f"(d[63])
    : "l"(da), "l"(db));
}
__device__ __forceinline__ void wgmma_n128_first(float (&d)[64], uint64_t da, uint64_t db) {
  asm volatile("wgmma.mma_async.sync.aligned.m64n128k16.f32.bf16.bf16 "
    "{%0, %1, %2, %3, %4, %5, %6, %7, %8, %9, %10, %11, %12, %13, %14, %15, %16, %17, %18, %19, %20, %21, %22, %23, %24, %25, %26, %27, %28, %29, %30, %31, %32, %33, %34, %35, %36, %37, %38, %39, %40, %41, %42, %43, %44, %45, %46, %47, %48, %49, %50, %51, %52, %53, %54, %55, %56, %57, %58, %59, %60, %61, %62, %63}, "
    "%64, %65, 0, 1, 1, 0, 1;\n"
    : "=f"(d[0]), "=f"(d[1]), "=f"(d[2]), "=f"(d[3]), "=f"(d[4]), "=f"(d[5]), "=f"(d[6]), "=f"(d[7]), "=f"(d[8]), "=f"(d[9]), "=f"(d[10]), "=f"(d[11]), "=f"(d[12]), "=f"(d[13]), "=f"(d[14]), "=f"(d[15]), "=f"(d[16]), "=f"(d[17]), "=f"(d[18]), "=f"(d[19]), "=f"(d[20]), "=f"(d[21]), "=f"(d[22]), "=f"(d[23]), "=f"(d[24]), "=f"(d[25]), "=f"(d[26]), "=f"(d[27]), "=f"(d[28]), "=f"(d[29]), "=f"(d[30]), "=f"(d[31]), "=f"(d[32]), "=f"(d[33]), "=f"(d[34]), "=f"(d[35]), "=f"(d[36]), "=f"(d[37]), "=f"(d[38]), "=f"(d[39]), "=f"(d[40]), "=f"(d[41]), "=f"(d[42]), "=f"(d[43]), "=f"(d[44]), "=f"(d[45]), "=f"(d[46]), "=f"(d[47]), "=f"(d[48]), "=f"(d[49]), "=f"(d[50]), "=f"(d[51]), "=f"(d[52]), "=f"(d[53]), "=f"(d[54]), "=f"(d[55]), "=f"(d[56]), "=f"(d[57]), "=f"(d[58]), "=f"(d[59]), "=f"(d[60]), "=f"(d[61]), "=f"(d[62]), "=f"(d[63])
    : "l"(da), "l"(db));
}
__device__ __forceinline__ void wgmma_n256(float (&d)[128], uint64_t da, uint64_t db) {
  asm volatile("wgmma.mma_async.sync.aligned.m64n256k16.f32.bf16.bf16 "
    "{%0, %1, %2, %3, %4, %5, %6, %7, %8, %9, %10, %11, %12, %13, %14, %15, %16, %17, %18, %19, %20, %21, %22, %23, %24, %25, %26, %27, %28, %29, %30, %31, %32, %33, %34, %35, %36, %37, %38, %39, %40, %41, %42, %43, %44, %45, %46, %47, %48, %49, %50, %51, %52, %53, %54, %55, %56, %57, %58, %59, %60, %61, %62, %63, %64, %65, %66, %67, %68, %69, %70, %71, %72, %73, %74, %75, %76, %77, %78, %79, %80, %81, %82, %83, %84, %85, %86, %87, %88, %89, %90, %91, %92, %93, %94, %95, %96, %97, %98, %99, %100, %101, %102, %103, %104, %105, %106, %107, %108, %109, %110, %111, %112, %113, %114, %115, %116, %117, %118, %119, %120, %121, %122, %123, %124, %125, %126, %127}, "
    "%128, %129, 1, 1, 1, 0, 1;\n"
    : "+f"(d[0]), "+f"(d[1]), "+f"(d[2]), "+f"(d[3]), "+f"(d[4]), "+f"(d[5]), "+f"(d[6]), "+f"(d[7]), "+f"(d[8]), "+f"(d[9]), "+f"(d[10]), "+f"(d[11]), "+f"(d[12]), "+f"(d[13]), "+f"(d[14]), "+f"(d[15]), "+f"(d[16]), "+f"(d[17]), "+f"(d[18]), "+f"(d[19]), "+f"(d[20]), "+f"(d[21]), "+f"(d[22]), "+f"(d[23]), "+f"(d[24]), "+f"(d[25]), "+f"(d[26]), "+f"(d[27]), "+f"(d[28]), "+f"(d[29]), "+f"(d[30]), "+f"(d[31]), "+f"(d[32]), "+f"(d[33]), "+f"(d[34]), "+f"(d[35]), "+f"(d[36]), "+f"(d[37]), "+f"(d[38]), "+f"(d[39]), "+f"(d[40]), "+f"(d[41]), "+f"(d[42]), "+f"(d[43]), "+f"(d[44]), "+f"(d[45]), "+f"(d[46]), "+f"(d[47]), "+f"(d[48]), "+f"(d[49]), "+f"(d[50]), "+f"(d[51]), "+f"(d[52]), "+f"(d[53]), "+f"(d[54]), "+f"(d[55]), "+f"(d[56]), "+f"(d[57]), "+f"(d[58]), "+f"(d[59]), "+f"(d[60]), "+f"(d[61]), "+f"(d[62]), "+f"(d[63]), "+f"(d[64]), "+f"(d[65]), "+f"(d[66]), "+f"(d[67]), "+f"(d[68]), "+f"(d[69]), "+f"(d[70]), "+f"(d[71]), "+f"(d[72]), "+f"(d[73]), "+f"(d[74]), "+f"(d[75]), "+f"(d[76]), "+f"(d[77]), "+f"(d[78]), "+f"(d[79]), "+f"(d[80]), "+f"(d[81]), "+f"(d[82]), "+f"(d[83]), "+f"(d[84]), "+f"(d[85]), "+f"(d[86]), "+f"(d[87]), "+f"(d[88]), "+f"(d[89]), "+f"(d[90]), "+f"(d[91]), "+f"(d[92]), "+f"(d[93]), "+f"(d[94]), "+f"(d[95]), "+f"(d[96]), "+f"(d[97]), "+f"(d[98]), "+f"(d[99]), "+f"(d[100]), "+f"(d[101]), "+f"(d[102]), "+f"(d[103]), "+f"(d[104]), "+f"(d[105]), "+f"(d[106]), "+f"(d[107]), "+f"(d[108]), "+f"(d[109]), "+f"(d[110]), "+f"(d[111]), "+f"(d[112]), "+f"(d[113]), "+f"(d[114]), "+f"(d[115]), "+f"(d[116]), "+f"(d[117]), "+f"(d[118]), "+f"(d[119]), "+f"(d[120]), "+f"(d[121]), "+f"(d[122]), "+f"(d[123]), "+f"(d[124]), "+f"(d[125]), "+f"(d[126]), "+f"(d[127])
    : "l"(da), "l"(db));
}
__device__ __forceinline__ void wgmma_n256_first(float (&d)[128], uint64_t da, uint64_t db) {
  asm volatile("wgmma.mma_async.sync.aligned.m64n256k16.f32.bf16.bf16 "
    "{%0, %1, %2, %3, %4, %5, %6, %7, %8, %9, %10, %11, %12, %13, %14, %15, %16, %17, %18, %19, %20, %21, %22, %23, %24, %25, %26, %27, %28, %29, %30, %31, %32, %33, %34, %35, %36, %37, %38, %39, %40, %41, %42, %43, %44, %45, %46, %47, %48, %49, %50, %51, %52, %53, %54, %55, %56, %57, %58, %59, %60, %61, %62, %63, %64, %65, %66, %67, %68, %69, %70, %71, %72, %73, %74, %75, %76, %77, %78, %79, %80, %81, %82, %83, %84, %85, %86, %87, %88, %89, %90, %91, %92, %93, %94, %95, %96, %97, %98, %99, %100, %101, %102, %103, %104, %105, %106, %107, %108, %109, %110, %111, %112, %113, %114, %115, %116, %117, %118, %119, %120, %121, %122, %123, %124, %125, %126, %127}, "
    "%128, %129, 0, 1, 1, 0, 1;\n"
    : "=f"(d[0]), "=f"(d[1]), "=f"(d[2]), "=f"(d[3]), "=f"(d[4]), "=f"(d[5]), "=f"(d[6]), "=f"(d[7]), "=f"(d[8]), "=f"(d[9]), "=f"(d[10]), "=f"(d[11]), "=f"(d[12]), "=f"(d[13]), "=f"(d[14]), "=f"(d[15]), "=f"(d[16]), "=f"(d[17]), "=f"(d[18]), "=f"(d[19]), "=f"(d[20]), "=f"(d[21]), "=f"(d[22]), "=f"(d[23]), "=f"(d[24]), "=f"(d[25]), "=f"(d[26]), "=f"(d[27]), "=f"(d[28]), "=f"(d[29]), "=f"(d[30]), "=f"(d[31]), "=f"(d[32]), "=f"(d[33]), "=f"(d[34]), "=f"(d[35]), "=f"(d[36]), "=f"(d[37]), "=f"(d[38]), "=f"(d[39]), "=f"(d[40]), "=f"(d[41]), "=f"(d[42]), "=f"(d[43]), "=f"(d[44]), "=f"(d[45]), "=f"(d[46]), "=f"(d[47]), "=f"(d[48]), "=f"(d[49]), "=f"(d[50]), "=f"(d[51]), "=f"(d[52]), "=f"(d[53]), "=f"(d[54]), "=f"(d[55]), "=f"(d[56]), "=f"(d[57]), "=f"(d[58]), "=f"(d[59]), "=f"(d[60]), "=f"(d[61]), "=f"(d[62]), "=f"(d[63]), "=f"(d[64]), "=f"(d[65]), "=f"(d[66]), "=f"(d[67]), "=f"(d[68]), "=f"(d[69]), "=f"(d[70]), "=f"(d[71]), "=f"(d[72]), "=f"(d[73]), "=f"(d[74]), "=f"(d[75]), "=f"(d[76]), "=f"(d[77]), "=f"(d[78]), "=f"(d[79]), "=f"(d[80]), "=f"(d[81]), "=f"(d[82]), "=f"(d[83]), "=f"(d[84]), "=f"(d[85]), "=f"(d[86]), "=f"(d[87]), "=f"(d[88]), "=f"(d[89]), "=f"(d[90]), "=f"(d[91]), "=f"(d[92]), "=f"(d[93]), "=f"(d[94]), "=f"(d[95]), "=f"(d[96]), "=f"(d[97]), "=f"(d[98]), "=f"(d[99]), "=f"(d[100]), "=f"(d[101]), "=f"(d[102]), "=f"(d[103]), "=f"(d[104]), "=f"(d[105]), "=f"(d[106]), "=f"(d[107]), "=f"(d[108]), "=f"(d[109]), "=f"(d[110]), "=f"(d[111]), "=f"(d[112]), "=f"(d[113]), "=f"(d[114]), "=f"(d[115]), "=f"(d[116]), "=f"(d[117]), "=f"(d[118]), "=f"(d[119]), "=f"(d[120]), "=f"(d[121]), "=f"(d[122]), "=f"(d[123]), "=f"(d[124]), "=f"(d[125]), "=f"(d[126]), "=f"(d[127])
    : "l"(da), "l"(db));
}

template <int N> struct WG;
#define DEF_WG(N) template <> struct WG<N> { \
  static __device__ __forceinline__ void mma(float (&d)[N / 2], uint64_t a, uint64_t b) { wgmma_n##N(d, a, b); } \
  static __device__ __forceinline__ void first(float (&d)[N / 2], uint64_t a, uint64_t b) { wgmma_n##N##_first(d, a, b); } };
DEF_WG(128) DEF_WG(256)

constexpr uint64_t DESC_A = (1ull << 62) | ((uint64_t)(1024 >> 4) << 32) | (1ull << 16);
constexpr uint64_t DESC_B = (1ull << 62) | ((uint64_t)(1024 >> 4) << 32) | ((uint64_t)(8192 >> 4) << 16);

struct Ring { int s; uint32_t ph; int wrap; };
template <int NS> __device__ __forceinline__ void ring_next(Ring& r) { r.s = (r.s + 1 == NS) ? 0 : r.s + 1; if (r.s == r.wrap) r.ph ^= 1; }

__device__ __forceinline__ int own_order(int it, int j) {
  return it < 2 ? 2 * j + it : it < 4 ? 2 * (j ^ 1) + it - 2 : ((j >> 1) * 4 + 2 * it - (it < 10 ? 4 : 15)) & 15;
}

template <int V> struct IC { static constexpr int v = V; };
template <int I, int E, class F> __device__ __forceinline__ void static_for(F&& f) { if constexpr (I < E) { f(IC<I>{}); static_for<I + 1, E>(f); } }

template <int N, int NS, int PRE, class Pre, class Mid, class Last>
__device__ __forceinline__ void mainloop(float (&acc)[N / 2], int nkb, bool own, Ring& r, uint32_t sb, int wg, int lane, uint32_t rel_base, uint32_t* step0, Pre pre, Mid mid, Last last) {
  constexpr int SLOT = RING / NS;
  const uint32_t full = sb + MISC + (NS == 4 ? B_FULL4 : B_FULL6);
  const uint32_t rel = rel_base + (NS == 4 ? B_EMPTY4 : B_EMPTY6);
  const uint32_t s0 = (sb & 0x3FFFF) >> 4, a0 = s0 + wg * (HALF >> 4);
  int ps;
  auto issue = [&](int it, bool first) {
    const uint64_t da = DESC_A | (a0 + ((own && it < 2) ? (STG + it * BLK) >> 4 : r.s * (SLOT >> 4))), db = DESC_B | (s0 + r.s * (SLOT >> 4) + (BLK >> 4));
    mbar_wait(full + r.s * 8, r.ph);
    TRS(it);
    wg_arrive();
    if (first) WG<N>::first(acc, da, db); else WG<N>::mma(acc, da, db);
#pragma unroll
    for (int k = 1; k < 4; k++) WG<N>::mma(acc, da + k * 2, db + k * 128);
    wg_commit();
  };
  auto retire = [&](int it) {
    wg_wait<1>();
    if (lane < 2) mbar_arrive_cl(rel + ps * 8);
    ps = r.s;
    ring_next<NS>(r);
  };
  issue(0, true);
  ps = r.s;
  ring_next<NS>(r);
  static_for<1, PRE + 1>([&](auto ic) { issue(ic.v, false); pre(ic); retire(ic.v); });
#pragma unroll 1
  for (int it = PRE + 1; it < nkb; it++) {
    if (TAILLAG && it == 56 - TAILLAG && wg == 1) mbar_wait(sb + MISC + B_LAG, 0);
    issue(it, false); mid(it); retire(it);
  }
  last();
  wg_wait<0>();
  if (lane < 2) mbar_arrive_cl(rel + ps * 8);
}

__device__ __forceinline__ void ln_publish(const float (&v)[64], uint4* st, int j, int row0, int lane, uint32_t ep) {
  float s0 = 0, s1 = 0, s2 = 0, s3 = 0, q0 = 0, q1 = 0, q2 = 0, q3 = 0;
#pragma unroll
  for (int i = 0; i < 16; i++) {
    s0 += v[4 * i]; s1 += v[4 * i + 1]; s2 += v[4 * i + 2]; s3 += v[4 * i + 3];
    q0 = fmaf(v[4 * i], v[4 * i], q0); q1 = fmaf(v[4 * i + 1], v[4 * i + 1], q1); q2 = fmaf(v[4 * i + 2], v[4 * i + 2], q2); q3 = fmaf(v[4 * i + 3], v[4 * i + 3], q3);
  }
  s0 += s1; s2 += s3; q0 += q1; q2 += q3;
  const bool odd = lane & 1;
  float s = (odd ? s2 : s0) + __shfl_xor_sync(~0u, odd ? s0 : s2, 1), q = (odd ? q2 : q0) + __shfl_xor_sync(~0u, odd ? q0 : q2, 1);
  s += __shfl_xor_sync(~0u, s, 2); q += __shfl_xor_sync(~0u, q, 2);
  if ((lane & 3) < 2) st_rlx4(st + j * 128 + row0 + (lane & 1) * 8, __float_as_uint(s), ep, __float_as_uint(q), ep);
}
__device__ __forceinline__ void ln_gather(const uint4* st, int row0, int lane, uint32_t ep, float& n0, float& r0, float& n1, float& r1) {
  const uint4* p = st + (lane & 2) * 256 + row0 + (lane & 1) * 8;
  uint4 a, b, c, d; uint32_t n = 0;
  while (true) {
    a = ld_rlx4(p); b = ld_rlx4(p + 128); c = ld_rlx4(p + 256); d = ld_rlx4(p + 384);
    if (a.y == ep && a.w == ep && b.y == ep && b.w == ep && c.y == ep && c.w == ep && d.y == ep && d.w == ep) break;
    SPIN_GUARD(n);
  }
  __syncwarp();
  float s = (__uint_as_float(a.x) + __uint_as_float(b.x)) + (__uint_as_float(c.x) + __uint_as_float(d.x));
  float q = (__uint_as_float(a.z) + __uint_as_float(b.z)) + (__uint_as_float(c.z) + __uint_as_float(d.z));
  s += __shfl_xor_sync(~0u, s, 2); q += __shfl_xor_sync(~0u, q, 2);
  s *= 1.f / 1024;
  const float r = rsqrtf(fmaxf(fmaf(-s, s, q * (1.f / 1024)), 0.f) + 1e-5f), nn = -s * r;
  const float ro = __shfl_xor_sync(~0u, r, 1), no = __shfl_xor_sync(~0u, nn, 1);
  const bool odd = lane & 1;
  r0 = odd ? ro : r; n0 = odd ? no : nn; r1 = odd ? r : ro; n1 = odd ? nn : no;
}
__device__ __forceinline__ void load_vec(uint32_t* w, uint32_t sb, int sec, int b, int lane) {
#pragma unroll
  for (int q = 0; q < 2; q++) { uint4 t = lds128(sb + MISC + MODV + sec * 256 + (lane & 3) * 64 + b * 32 + q * 16); w[4 * q] = t.x; w[4 * q + 1] = t.y; w[4 * q + 2] = t.z; w[4 * q + 3] = t.w; }
}
__device__ __forceinline__ void stage_done(uint32_t sb, int wg, int b, int lane) {
  fence_async_smem();
  __syncwarp();
  if (lane == 0) mbar_arrive(sb + MISC + B_RDY + b * 8);
}
__device__ __forceinline__ uint32_t hfma2(uint32_t a, uint32_t b, uint32_t c) { uint32_t r; asm("fma.rn.bf16x2 %0, %1, %2, %3;" : "=r"(r) : "r"(a), "r"(b), "r"(c)); return r; }
__device__ __forceinline__ void ln_apply(const float (&v)[64], const uint4* st, int row0, uint32_t ep, uint32_t sb, int sec_shift, int sec_scale, uint32_t stg_row, int wg, int lane) {
  uint32_t sc[16], sh[16];
#pragma unroll
  for (int b = 0; b < 2; b++) { load_vec(sc + 8 * b, sb, sec_scale, b, lane); load_vec(sh + 8 * b, sb, sec_shift, b, lane); }
  float n0, r0, n1, r1;
  ln_gather(st, row0, lane, ep, n0, r0, n1, r1);
#pragma unroll
  for (int i = 0; i < 16; i += 2) {
    if (i == 8) { const float z = lds32f(sb + MISC + ZERO); n0 += z; n1 += z; }
    uint32_t w[4];
#pragma unroll
    for (int u = 0; u < 2; u++) {
      int q = i + u;
      w[2 * u] = hfma2(pack2(fmaf(v[4 * q], r0, n0), fmaf(v[4 * q + 1], r0, n0)), sc[q], sh[q]);
      w[2 * u + 1] = hfma2(pack2(fmaf(v[4 * q + 2], r1, n1), fmaf(v[4 * q + 3], r1, n1)), sc[q], sh[q]);
    }
    stsm4(stg_row + (i >> 3) * BLK + ((((i & 7) + (lane >> 4)) ^ (lane & 7)) << 4), w[0], w[1], w[2], w[3]);
    if ((i & 7) == 6) stage_done(sb, wg, i >> 3, lane);
  }
}
__device__ __forceinline__ uint32_t hmul2(uint32_t a, uint32_t b) { uint32_t r; asm("mul.rn.bf16x2 %0, %1, %2;" : "=r"(r) : "r"(a), "r"(b)); return r; }
__device__ __forceinline__ uint32_t silu_mul2(uint32_t g, uint32_t u) {
  const uint32_t h = hmul2(g, 0x3f003f00u);
  const float h0 = bf_lo(h), h1 = bf_hi(h);
  return hmul2(pack2(fmaf(h0, tanh_fast(h0), h0), fmaf(h1, tanh_fast(h1), h1)), u);
}

__device__ __forceinline__ void gemv_fma(float (&a)[8], uint4 w, float s) {
  a[0] = fmaf(bf_lo(w.x), s, a[0]); a[1] = fmaf(bf_hi(w.x), s, a[1]); a[2] = fmaf(bf_lo(w.y), s, a[2]); a[3] = fmaf(bf_hi(w.y), s, a[3]);
  a[4] = fmaf(bf_lo(w.z), s, a[4]); a[5] = fmaf(bf_hi(w.z), s, a[5]); a[6] = fmaf(bf_lo(w.w), s, a[6]); a[7] = fmaf(bf_hi(w.w), s, a[7]);
}
__device__ __forceinline__ float silu_c(float v) { return bf_round(__fdividef(v, 1.f + __expf(-v))); }
__device__ __forceinline__ float mod_gather(const uint2* p, uint32_t ep) {
  uint2 a, b, c, d; uint32_t n = 0;
  while (true) {
    a = ld_rlx2(p); b = ld_rlx2(p + 128); c = ld_rlx2(p + 256); d = ld_rlx2(p + 384);
    if (a.y == ep && b.y == ep && c.y == ep && d.y == ep) break;
    SPIN_GUARD(n);
  }
  return (__uint_as_float(a.x) + __uint_as_float(b.x)) + (__uint_as_float(c.x) + __uint_as_float(d.x));
}
__device__ __forceinline__ void mod_store(uint32_t sb, int sec, int col, float v) {
  v = bf_round(v);
  if (sec == 1 || sec == 4) v += 1.f;
  sts16(sb + MISC + MODV + sec * 256 + (((col >> 1) & 3) * 16 + (col >> 3)) * 4 + (col & 1) * 2, __float2bfloat16_rn(v));
}

__global__ void __cluster_dims__(2, 1, 1) __launch_bounds__(384, 1)
fused_kernel(const bf16* __restrict__ cvec, const bf16* __restrict__ wmod, Scratch* gs, int by_sm, const __grid_constant__ Maps maps) {
  extern __shared__ __align__(1024) uint8_t smem_raw[];
  const uint32_t sb = smem_u32(smem_raw);
  const int warp = __shfl_sync(~0u, threadIdx.x >> 5, 0), lane = threadIdx.x & 31;
  const int rank = blockIdx.x & 1;
  uint32_t sm; asm("mov.u32 %0, %%smid;" : "=r"(sm));
  const int t = sm >> 1, v = t < 32 ? t : t < 60 ? t + 1 + (((t - 32) * 37) >> 8) : (t - 58) * 8;
  const int cid = !by_sm ? (blockIdx.x >> 1) - 2 : (t & ~1) == 60 ? t - 62 : (v & 1) * 32 + ((v >> 1) & 31);
  const bool extra = cid < 0;
  const int bid = cid * 2 + rank;
  const int m = cid >> 2, j = (cid & 3) * 2 + rank;
  const uint32_t bar = sb + MISC;

  if (warp >= 8) {
    asm volatile("setmaxnreg.dec.sync.aligned.u32 40;");
    if (extra) {
      if (warp == 8) {
        if (lane == 0) { for (int s = 0; s < 6; s++) { mbar_init(bar + B_FULL6 + s * 8, 1); mbar_init(bar + B_EMPTY6 + s * 8, 8); } fence_async_smem(); }
        __syncwarp();
        asm volatile("bar.arrive 2, 288;" ::: "memory");
        __nanosleep(XSLEEP);
#pragma unroll 1
        for (int it = 0, s = 0, par = 1; it < 64; it++) {
          mbar_wait(bar + B_EMPTY6 + s * 8, par);
          if (elect()) { mbar_expect_tx(bar + B_FULL6 + s * 8, 32768); tma_3d(sb + s * 32768, &maps.wmod, bar + B_FULL6 + s * 8, 0, (it & 15) * 64, 12 + (it >> 4) * 4 + bid); }
          if (++s == 6) { s = 0; par ^= 1; }
        }
      }
    } else if (warp < 10) {
      uint32_t s6 = 0, p6 = 1;
      auto next6 = [&]() { if (++s6 == 6) { s6 = 0; p6 ^= 1; } };
      auto drained4 = [&](int q, int late) { if (q < 5) mbar_wait(bar + B_EMPTY4 + (((late ? 0x10332 : 0x32110) >> (4 * q)) & 3) * 8, 1); };
      auto drained6 = [&](int q) { if (q < 3) mbar_wait(bar + B_EMPTY6 + ((0x154 >> (4 * q)) & 7) * 8, q >> 1); };
      auto skip6 = [&]() { mbar_wait(bar + B_EMPTY6 + s6 * 8, p6); if (elect()) mbar_arrive(bar + B_FULL6 + s6 * 8); next6(); };
      if (warp == 8) {
        const uint32_t t_start = clock();
        if (lane == 0) {
          if (sb & 1023) bail();
          for (int b = 0; b < 2; b++) mbar_init(bar + B_X + b * 8, 1);
          for (int s = 0; s < 4; s++) { mbar_init(bar + B_FULL4 + s * 8, 2); mbar_init(bar + B_EMPTY4 + s * 8, 16); }
          for (int s = 0; s < 6; s++) { mbar_init(bar + B_FULL6 + s * 8, 2); mbar_init(bar + B_EMPTY6 + s * 8, 16); }
          for (int b = 0; b < 2; b++) { mbar_init(bar + B_RDY + b * 8, 8); mbar_init(bar + B_FREE + b * 8, 1); mbar_init(bar + B_HH + b * 8, 1); }
          mbar_init(bar + B_MOD, 1); mbar_init(bar + B_LAG, 4); mbar_init(bar + B_HALO, 2); mbar_init(bar + B_ALL, 1); mbar_init(bar + B_HH2, 1);
          asm volatile("st.shared.u32 [%0], 0;" :: "r"(bar + ZERO) : "memory");
          asm volatile("fence.mbarrier_init.release.cluster;" ::: "memory");
          fence_async_smem();
        }
        __syncwarp();
        cl_arrive_relaxed();
        auto wide = [&](int s, int par, const CUtensorMap* m0, int a0, const CUtensorMap* m1, int a1, int kb) {
          const uint32_t full = bar + B_FULL4 + s * 8, d = sb + s * 49152 + BLK;
          mbar_wait(full + 32, par);
          if (elect()) { mbar_expect_tx(full, 2 * BLK); tma_3d(d, m0, full, 0, kb * 64, a0); tma_3d(d + BLK, m1, full, 0, kb * 64, a1); }
        };
        auto narrow = [&](const CUtensorMap* m0, int kb) {
          const uint32_t full = bar + B_FULL6 + s6 * 8;
          mbar_wait(full + 48, p6);
          if (elect()) { mbar_expect_tx(full, BLK); tma_3d(sb + s6 * 32768 + BLK, m0, full, 0, kb * 64, 2 * j); }
          next6();
        };
#pragma unroll 1
        for (int it = 0; it < 16; it++) {
          if (it == 0) {
            while ((uint32_t)clock() - t_start < XDELAY) {}
            if (elect()) for (int b = 0; b < 2; b++) { mbar_expect_tx(bar + B_X + b * 8, BLK); tma_3d(sb + STG + b * BLK, &maps.x, bar + B_X + b * 8, j * 128 + b * 64, m * 64, 0); }
            mbar_wait(bar + B_X + 8, 0);
          }
          wide(it & 3, ~(it >> 2) & 1, &maps.wqkv, 16 + 2 * j, &maps.wqkv, 32 + 2 * j, own_order(it, j));
        }
#pragma unroll 1
        for (int it = 0; it < 16; it++) { drained4(it, 0); narrow(&maps.wqkv, it); }
#pragma unroll 1
        for (int it = 0; it < 16; it++) narrow(&maps.wo, own_order(it, j));
        skip6();
#pragma unroll 1
        for (int it = 0; it < 48; it++) {
          const int s = (it + 2) & 3, par = ~(it >> 2) & 1;
          drained6(it);
          wide(s, par, &maps.w1, (it & 48) + 2 * j, &maps.w3, (it & 48) + 2 * j, it < 16 ? own_order(it, j) : it & 15);
          if (it >= 44) {
            if (it == 44) { mbar_wait(bar + B_FREE, 0); mbar_wait(bar + B_FREE + 8, 0); if (elect()) mbar_expect_tx(bar + B_X, 2 * BLK); }
            if (elect()) bulk_ld(sb + STG + (it - 44) * HALF, gs->x1 + bid * 2048 + (it - 44) * 512, HALF, bar + B_X);
          }
        }
#pragma unroll 1
        for (int it = 0; it < 16; it++) {
          const uint32_t full = bar + B_FULL6 + s6 * 8, d = sb + s6 * 32768 + BLK;
          drained4(it, 1);
          mbar_wait(full + 48, p6);
          if (elect()) { mbar_expect_tx(full, BLK); tma_3d(d, &maps.w1s, full, 0, it * 64, 48 + j); tma_3d(d + HALF, &maps.w3s, full, 0, it * 64, 48 + j); }
          next6();
        }
#pragma unroll 1
        for (int it = 0; it < 56; it++) narrow(&maps.w2, it);
      } else {
        if (lane < 9) prefetch_map(&maps.x + lane);
        const uint32_t ep = gs->epoch[bid + 4] + 1;
        cl_arrive_relaxed(); cl_wait();
        auto plain = [&](uint32_t full, uint32_t empty, int par, uint32_t slot, const uint4* blk) {
          mbar_wait(empty, par);
          if (elect()) { mbar_expect_tx(full, BLK); bulk_ld_mc(slot + rank * HALF, blk + rank * 512, HALF, full); }
        };
        auto plain6 = [&](const uint4* blk) { plain(bar + B_FULL6 + s6 * 8, bar + B_EMPTY6 + s6 * 8, p6, sb + s6 * 32768, blk); next6(); };
        uint32_t ready = 0;
        auto poll = [&](int e) { ready = __ballot_sync(~0u, ld_acquire(gs->flag + m * 128 + e * 16 + (lane & 15)) == ep); };
        auto need = [&](int e, uint32_t mask) {
          if ((ready & mask) != mask) {
            uint32_t n = 0;
            do { poll(e); SPIN_GUARD(n); } while ((ready & mask) != mask);
            fence_async_global();
          }
        };
        auto fresh = [&](int e, int it, uint32_t full, uint32_t empty, int par, uint32_t slot, uint4* src) {
          if (it >= 4) {
            const int kb = own_order(it, j);
            if (it < 10) need(e, 1u << kb); else if (it == 10) mbar_wait(bar + B_ALL, e & 1);
            plain(full, empty, par, slot, src + kb * 1024);
          } else {
            if (it == 0) { poll(e); ready = 0; }
            mbar_wait(empty, par);
            if (it < 2) { if (elect()) mbar_arrive(full); }
            else {
              const int b = it > 2;
              const uint32_t to_peer = mapa(sb, rank ^ 1) - sb;
              if (elect()) mbar_expect_tx(full, BLK);
              mbar_wait(bar + (b ? B_FREE + 8 : B_RDY), e & 1);
              if (b == 0) TR(e == 0 ? 24 : e == 2 ? 30 : 44);
              if (elect()) {
                if (b == 0) {
                  bulk_st(src + 2 * j * 1024, sb + STG, BLK);
                  bulk_commit();
                  bulk_wait_all();
                  mbar_arrive(bar + B_FREE);
                }
                fence_async_global();
                bulk_ld(slot + to_peer, src + (2 * j + b) * 1024, BLK, full + to_peer);
              }
              __syncwarp();
            }
          }
          if (it == 4) TR(e == 0 ? 28 : e == 1 ? 46 : 34);
        };
#pragma unroll 1
        for (int ph = 0; ph < 2; ph++) {
          uint4* h = gs->h + m * 16384;
#pragma unroll 1
          for (int it = 0; it < 16; it++) {
            const int s = (it + 2 * ph) & 3;
            if (ph) drained6(it);
            fresh(2 * ph, it, bar + B_FULL4 + s * 8, bar + B_EMPTY4 + s * 8, ~(it >> 2) & 1, sb + s * 49152, h);
          }
          if (ph) {
#pragma unroll 1
            for (int it = 16; it < 48; it++) {
              const int s = (it + 2) & 3;
              const uint32_t full = bar + B_FULL4 + s * 8;
              plain(full, full + 32, ~(it >> 2) & 1, sb + s * 49152, h + (it & 15) * 1024);
            }
          }
#pragma unroll 1
          for (int it = 0; it < 16; it++) { drained4(it, ph); plain6(h + it * 1024); }
          if (!ph) {
#pragma unroll 1
            for (int it = 0; it < 16; it++) { fresh(1, it, bar + B_FULL6 + s6 * 8, bar + B_EMPTY6 + s6 * 8, p6, sb + s6 * 32768, gs->o + m * 16384); next6(); }
            skip6();
          }
        }
#pragma unroll 1
        for (int it = 0; it < 56; it++) {
          if (it == 0 || it == 32 || it == 48) mbar_wait(bar + (it == 48 ? B_HH2 : B_HH + (it >> 2)), 0);
          plain6(gs->hh + m * 57344 + it * 1024);
        }
      }
    } else {
      const int b = warp - 10;
      const uint32_t ep = gs->epoch[bid + 4] + 1;
      const uint32_t stg = sb + STG + b * BLK;
      cl_arrive_relaxed(); cl_wait();
      auto all_there = [&](int u, uint32_t done) {
        const uint32_t* fl = gs->flag + u;
        uint32_t n = 0;
        while (!__all_sync(~0u, ld_acquire(fl) == ep)) { __nanosleep(100); SPIN_GUARD(n); }
        fence_async_global();
        if (lane == 0) mbar_arrive(done);
      };
      auto fetch_mod = [&](int sec) {
        const uint4* p = (const uint4*)(gs->modv + (sec - 2) * 1024 + j * 128) + lane;
        uint4 v0, v1; uint32_t n = 0;
        while (true) {
          v0 = ld_rlx4(p); v1 = ld_rlx4(p + 32);
          if (v0.y == ep && v0.w == ep && v1.y == ep && v1.w == ep) break;
          SPIN_GUARD(n);
        }
        mod_store(sb, sec, 2 * lane, __uint_as_float(v0.x)); mod_store(sb, sec, 2 * lane + 1, __uint_as_float(v0.z));
        mod_store(sb, sec, 64 + 2 * lane, __uint_as_float(v1.x)); mod_store(sb, sec, 65 + 2 * lane, __uint_as_float(v1.z));
        __syncwarp();
      };
#pragma unroll 1
      for (int e = 0; e < 7 - b; e++) {
        if (lane == 0) {
          if (e < 3) {
            mbar_wait(bar + B_FREE, e & 1);
            if (b) {
              const uint32_t t0 = clock();
              while ((uint32_t)clock() - t0 < B1D) {}
              mbar_wait(bar + B_RDY + 8, e & 1);
              bulk_st((e == 1 ? gs->o : gs->h) + m * 16384 + (2 * j + 1) * 1024, stg, BLK);
              bulk_commit();
              bulk_wait_all();
              mbar_arrive(bar + B_FREE + 8);
              TR(53 + e);
            }
            st_release(gs->flag + m * 128 + e * 16 + 2 * j + b, ep);
            TR((e == 0 ? 26 : e == 2 ? 32 : 42) + b);
          } else {
            const int kb = (e < 6 ? 2 * (8 * (e - 3) + j) : 48 + j) + b;
            mbar_wait(bar + B_RDY + b * 8, e & 1);
#pragma unroll 1
            for (int q = 0; q < NPIECE; q++) { if (q) __nanosleep(PSLEEP); bulk_st(gs->hh + m * 57344 + kb * 1024 + q * (1024 / NPIECE), stg + q * (BLK / NPIECE), BLK / NPIECE); }
            bulk_commit();
            bulk_wait_all();
            mbar_arrive(bar + B_FREE + b * 8);
            st_release(gs->flag + m * 128 + U_HH + kb, ep);
          }
        }
        __syncwarp();
        if (e < 3 && b) all_there(m * 128 + e * 16 + (lane & 15), bar + B_ALL);
        if (e == 4 && b) all_there(m * 128 + U_HH + lane, bar + B_HH);
        if (!b && (e == 1 || e == 2)) {
#pragma unroll 1
          for (int sec = e == 1 ? 2 : 5; sec < 4 + e; sec++) fetch_mod(sec);
          if (e == 1) { if (lane == 0) mbar_arrive(bar + B_MOD); TR(50); }
        }
        if (e == 0) {
          mbar_wait(bar + B_EMPTY6 + 24, 0);
          if (HSLEEP) __nanosleep(HSLEEP);
#pragma unroll 1
          for (int w = 0; w < 4; w++) {
            const uint4* hp = gs->halo + ((m * 8 + j) * 2 + (w & 1)) * 512 + b * 256 + (w >> 1) * 128 + lane;
            uint4 q[4] = {}; uint32_t n = 0;
            while (m > 0) {
              bool ok = true;
#pragma unroll
              for (int i = 0; i < 4; i++) q[i] = ld_rlx4(hp + i * 32);
#pragma unroll
              for (int i = 0; i < 4; i++) ok = ok && q[i].y == ep && q[i].w == ep;
              if (ok) break;
              SPIN_GUARD(n);
            }
#pragma unroll
            for (int i = 0; i < 2; i++) sts128(stg + lane * 16 + (w & 1) * HALF + (w >> 1) * 1024 + i * 512, q[2 * i].x, q[2 * i + 1].x, q[2 * i].z, q[2 * i + 1].z);
          }
          __syncwarp();
          if (lane == 0) mbar_arrive(bar + B_HALO);
          if (b == 0) TR(52);
        }
      }
      if (b) { all_there(m * 128 + U_HH + 32 + (lane & 15), bar + B_HH + 8); all_there(m * 128 + U_HH + 48 + (lane & 7), bar + B_HH2); }
    }
  } else {
    const int wg = warp >> 2, wq = warp & 3, tid = threadIdx.x;
    const int g = lane >> 2, c = lane & 3;
    const int sec0 = (m >> 1) & 1, hf0 = m & 1, ks0 = (m >> 2) & 3;
    uint4 wv[8];
    uint32_t ep0; uint16_t cv_;
    asm volatile("ld.global.nc.u16 %0, [%1];" : "=h"(cv_) : "l"(cvec + ks0 * 256 + warp * 32 + lane));
    asm volatile("ld.global.u32 %0, [%1];" : "=r"(ep0) : "l"(gs->epoch + bid + 4));
    if (!extra) {
      const bf16* wp = wmod + (size_t)(ks0 * 256 + warp * 32 + (lane >> 3)) * 6144 + sec0 * 1024 + j * 128 + hf0 * 64 + (lane & 7) * 8;
#pragma unroll
      for (int i = 0; i < 8; i++) wv[i] = ldg_nc(wp + (size_t)i * 4 * 6144);
    }
    asm volatile("setmaxnreg.inc.sync.aligned.u32 232;" ::: "memory");
    if (__builtin_expect(extra, 0)) {
      const uint32_t ep = ep0 + 1;
      float sv[4];
#pragma unroll
      for (int p = 0; p < 4; p++) sv[p] = silu_c(__bfloat162float(cvec[64 * (4 * p + (lane >> 3)) + 8 * warp + (lane & 7)]));
      named_bar(2, 288);
      int s = 0, par = 0;
#pragma unroll 1
      for (int sec = 0; sec < 4; sec++) {
        float a[8] = {0, 0, 0, 0, 0, 0, 0, 0};
#pragma unroll 1
        for (int it = 0; it < 16; it++) {
          const float sc = it < 4 ? sv[0] : it < 8 ? sv[1] : it < 12 ? sv[2] : sv[3];
          mbar_wait(bar + B_FULL6 + s * 8, par);
          uint4 w[8];
#pragma unroll
          for (int i = 0; i < 8; i++) w[i] = lds128(sb + s * 32768 + (warp * 8 + i) * 512 + lane * 16);
#pragma unroll
          for (int i = 0; i < 8; i++) gemv_fma(a, w[i], __shfl_sync(~0u, sc, (it & 3) * 8 + i));
          if (lane == 0) mbar_arrive(bar + B_EMPTY6 + s * 8);
          if (++s == 6) { s = 0; par ^= 1; }
        }
        const uint32_t red = sb + STG + sec * 8192;
        sts128(red + warp * 1024 + lane * 32, __float_as_uint(a[0]), __float_as_uint(a[1]), __float_as_uint(a[2]), __float_as_uint(a[3]));
        sts128(red + warp * 1024 + lane * 32 + 16, __float_as_uint(a[4]), __float_as_uint(a[5]), __float_as_uint(a[6]), __float_as_uint(a[7]));
        named_bar(1, 256);
        float t = 0;
#pragma unroll
        for (int q = 0; q < 8; q++) t += lds32f(red + q * 1024 + tid * 4);
        st_rlx2(gs->modv + sec * 1024 + (bid + 4) * 256 + tid, __float_as_uint(t), ep);
      }
      if (tid == 0) gs->epoch[bid + 4] = ep;
      return;
    }
    if (warp == 0) TR(0);
    const int row0 = wg * 64 + wq * 16 + g;
    if (c < 2) st_rlx4(gs->stat + m * 1024 + j * 128 + row0 + c * 8, 0, 0, 0, 0);
    if (tid < 64) st_rlx2(gs->modp + ((j * 2 + sec0) * 4 + ks0) * 128 + hf0 * 64 + tid, 0, 0);
    cl_arrive_relaxed(); cl_wait();
    uint32_t ep;
    asm volatile("add.u32 %0, %1, 1;" : "=r"(ep) : "r"(ep0) : "memory");
    const float sc_ = silu_c(__uint_as_float((uint32_t)cv_ << 16));
    const uint32_t rel = mapa(bar, (lane & 1) ^ rank);
    const uint32_t stg_row = sb + STG + (wg * 64 + wq * 16 + (lane & 15)) * 128;
    const uint32_t fre = bar + B_FREE;
    Ring r4{0, 0, 0}, r6{0, 0, 0};
    auto none = [](auto) {};
    uint32_t xk[32];
    {
      float a[8] = {0, 0, 0, 0, 0, 0, 0, 0};
#pragma unroll
      for (int i = 0; i < 8; i++) gemv_fma(a, wv[i], __shfl_sync(~0u, sc_, i * 4 + (lane >> 3)));
#pragma unroll
      for (int i = 0; i < 8; i++) { a[i] += __shfl_xor_sync(~0u, a[i], 8); a[i] += __shfl_xor_sync(~0u, a[i], 16); }
      if (lane < 8) {
        sts128(sb + RED_OFF + warp * 256 + lane * 32, __float_as_uint(a[0]), __float_as_uint(a[1]), __float_as_uint(a[2]), __float_as_uint(a[3]));
        sts128(sb + RED_OFF + warp * 256 + lane * 32 + 16, __float_as_uint(a[4]), __float_as_uint(a[5]), __float_as_uint(a[6]), __float_as_uint(a[7]));
      }
      named_bar(1, 256);
      if (tid < 64) {
        float s = 0;
#pragma unroll
        for (int w = 0; w < 8; w++) s += lds32f(sb + RED_OFF + w * 256 + tid * 4);
        st_rlx2(gs->modp + ((j * 2 + sec0) * 4 + ks0) * 128 + hf0 * 64 + tid, __float_as_uint(s), ep);
      }
      if (warp == 0) TR(1);
      float v[64];
      mbar_wait(bar + B_X, 0); mbar_wait(bar + B_X + 8, 0);
#pragma unroll
      for (int i = 0; i < 16; i += 2) {
        uint32_t w0, w1, w2, w3;
        ldsm4(stg_row + (i >> 3) * BLK + ((((i & 7) + (lane >> 4)) ^ (lane & 7)) << 4), w0, w1, w2, w3);
        xk[2 * i] = w0; xk[2 * i + 1] = w1; xk[2 * i + 2] = w2; xk[2 * i + 3] = w3;
        v[4 * i] = bf_lo(w0); v[4 * i + 1] = bf_hi(w0); v[4 * i + 2] = bf_lo(w1); v[4 * i + 3] = bf_hi(w1);
        v[4 * i + 4] = bf_lo(w2); v[4 * i + 5] = bf_hi(w2); v[4 * i + 6] = bf_lo(w3); v[4 * i + 7] = bf_hi(w3);
      }
      ln_publish(v, gs->stat + m * 1024, j, row0, lane, ep);
      if (warp == 0) TR(2);
      mod_store(sb, tid >> 7, tid & 127, mod_gather(gs->modp + (j * 2 + (tid >> 7)) * 512 + (tid & 127), ep));
      named_bar(1, 256);
      if (warp == 0) TR(3);
      ln_apply(v, gs->stat + m * 1024, row0, ep, sb, 0, 1, stg_row, wg, lane);
      named_bar(2 + wg, 128);
    }
    if (warp == 0) TR(4);
    {
      uint32_t kf[32], vf[32], pv[32];
      const bool first = wq == 0 && m == 0;
      const uint32_t xa = sb + STG + wg * HALF + wq * 2048 + lane * 16;
      {
        float acc[128];
        mainloop<256, 4, 0>(acc, 16, true, r4, sb, wg, lane, rel, STEP0 + 0, none, none, [&] {
          mbar_wait(fre + 8, 0);
          if (c < 2) st_rlx4(gs->stat + (16 + m) * 1024 + j * 128 + row0 + c * 8, 0, 0, 0, 0);
        });
        if (warp == 0) TR(5);
#pragma unroll
        for (int i = 0; i < 32; i++) { kf[i] = pack2(acc[2 * i], acc[2 * i + 1]); vf[i] = pack2(acc[64 + 2 * i], acc[65 + 2 * i]); }
      }
      if (warp == 0) TR(6);
      float acc[64];
      constexpr int QP = 2;
      mainloop<128, 6, 8 / QP>(acc, 16, false, r6, sb, wg, lane, rel, STEP0 + 16, [&](auto ic) {
        constexpr int q = (ic.v - 1) * QP;
#pragma unroll
        for (int i = 4 * q; i < 4 * (q + QP); i++) vf[i] = movm(vf[i]);
        if (wq == 3) {
          if (m < 15) {
            uint4* hp = gs->halo + (((m + 1) * 8 + j) * 2 + wg) * 512 + lane;
#pragma unroll
            for (int i = 2 * q; i < 2 * (q + QP); i++) st_rlx4(hp + i * 32, kf[2 * i + 1], ep, vf[2 * i + 1], ep);
          }
        } else {
#pragma unroll
          for (int i = q; i < q + QP; i++) sts128(xa + 2048 + (i >> 2) * BLK + (i & 3) * 512, kf[4 * i + 1], kf[4 * i + 3], vf[4 * i + 1], vf[4 * i + 3]);
        }
      }, none, [&] {
        named_bar(2 + wg, 128);
        if (wq == 0) mbar_wait(bar + B_HALO, 0);
#pragma unroll
        for (int i = 0; i < 8; i++) {
          uint4 q = lds128(xa + (i >> 2) * BLK + (i & 3) * 512);
          pv[4 * i] = q.x; pv[4 * i + 1] = q.y; pv[4 * i + 2] = q.z; pv[4 * i + 3] = q.w;
        }
        __syncwarp();
      });
      if (warp == 0) TR(7);
      int gz = g;
#pragma unroll
      for (int b = 0; b < 2; b++) {
        const bool up0 = 2 * c > gz, up1 = 2 * c + 1 > gz;
        const uint32_t mup = (up0 ? 0xffffu : 0u) | (up1 ? 0xffff0000u : 0u);
        float l[2][4], mx[4];
#pragma unroll
        for (int h = 0; h < 2; h++) {
          uint32_t q[8];
          const int k = 16 * b + 8 * h;
#pragma unroll
          for (int i = 0; i < 8; i++) q[i] = pack2(acc[2 * k + 2 * i], acc[2 * k + 2 * i + 1]);
          float s0[4], s1[4], s2[4];
          mma16z(s0, q[0], q[1], q[2], q[3], pv[k], pv[k + 1]); mma16z(s1, q[0], q[1], q[2], q[3], kf[k], kf[k + 2]); mma16z(s2, q[0], q[1], q[2], q[3], kf[k + 1], kf[k + 3]);
          mma16(s0, q[4], q[5], q[6], q[7], pv[k + 4], pv[k + 5]); mma16(s1, q[4], q[5], q[6], q[7], kf[k + 4], kf[k + 6]); mma16(s2, q[4], q[5], q[6], q[7], kf[k + 5], kf[k + 7]);
          if (first) { s0[0] = -INFINITY; s0[1] = -INFINITY; }
          l[h][0] = up0 ? s0[0] : s1[0]; l[h][1] = up1 ? s0[1] : s1[1]; l[h][2] = up0 ? s1[2] : s2[2]; l[h][3] = up1 ? s1[3] : s2[3];
          mx[2 * h] = fmaxf(l[h][0], l[h][1]); mx[2 * h + 1] = fmaxf(l[h][2], l[h][3]);
        }
#pragma unroll
        for (int o = 1; o < 4; o <<= 1) {
#pragma unroll
          for (int h = 0; h < 4; h++) mx[h] = fmaxf(mx[h], __shfl_xor_sync(~0u, mx[h], o));
        }
#pragma unroll
        for (int h = 0; h < 2; h++) {
          const float n0 = -mx[2 * h] * SCL, n1 = -mx[2 * h + 1] * SCL;
          const uint32_t pa = pack2(ex2(fmaf(l[h][0], SCL, n0)), ex2(fmaf(l[h][1], SCL, n0))), pb = pack2(ex2(fmaf(l[h][2], SCL, n1)), ex2(fmaf(l[h][3], SCL, n1)));
          float sm[4];
          mma8z(sm, pa, pb, 0x3f803f80u);
          const float ia = rcp(sm[0]), ib = rcp(sm[2]);
#pragma unroll
          for (int i = 8 * b + 4 * h; i < 8 * b + 4 * h + 4; i += 2) {
            uint32_t of[4];
#pragma unroll
            for (int d = 0; d < 2; d++) {
              float o[4];
              mma16z(o, pa & ~mup, pb & mup, 0u, pb & ~mup, vf[2 * (i + d)], vf[2 * (i + d) + 1]);
              mma8(o, pa & mup, 0u, pv[2 * i + 2 + d]);
              of[2 * d] = pack2(o[0] * ia, o[1] * ia); of[2 * d + 1] = pack2(o[2] * ib, o[3] * ib);
            }
            stsm4(stg_row + b * BLK + ((((i & 7) + (lane >> 4)) ^ (lane & 7)) << 4), of[0], of[1], of[2], of[3]);
          }
        }
        stage_done(sb, wg, b, lane);
        if (b == 0) gz += __float_as_uint(lds32f(bar + ZERO));
      }
      named_bar(1, 256);
      if (warp == 0) TR(8);
    }
    uint32_t pk[64];
    {
      float acc[64];
      mainloop<128, 6, 0>(acc, 16, true, r6, sb, wg, lane, rel, STEP0 + 32, none, none, [&] {
        mbar_wait(bar + B_MOD, 0); mbar_wait(fre + 8, 1);
        load_vec(pk + 32, sb, 2, 0, lane); load_vec(pk + 40, sb, 2, 1, lane);
#pragma unroll
        for (int i = 0; i < 32; i++) { pk[i] = xk[i]; asm volatile("" : "+r"(pk[i])); }
      });
      if (warp == 0) TR(9);
#pragma unroll
      for (int i = 0; i < 32; i++) {
        acc[2 * i] = fmaf(acc[2 * i], bf_lo(pk[32 + (i >> 1)]), bf_lo(pk[i]));
        acc[2 * i + 1] = fmaf(acc[2 * i + 1], bf_hi(pk[32 + (i >> 1)]), bf_hi(pk[i]));
      }
      ln_publish(acc, gs->stat + (16 + m) * 1024, j, row0, lane, ep);
      if (warp == 0) TR(36);
      mbar_wait(bar + B_FULL6 + 16, 1);
      if (lane < 2) mbar_arrive_cl(rel + B_EMPTY6 + 16);
      ring_next<6>(r6);
#pragma unroll
      for (int i = 0; i < 32; i++) { pk[i] = pack2(acc[2 * i], acc[2 * i + 1]); pk[32 + i] = 0; }
      ln_apply(acc, gs->stat + (16 + m) * 1024, row0, ep, sb, 3, 4, stg_row, wg, lane);
      named_bar(2 + wg, 128);
      if (warp == 0) TR(11);
    }
    auto swiglu = [&](int q, int uo, int par) {
      if ((q & 3) == 0 && par >= 0) mbar_wait(fre + 2 * q, par);
      uint32_t w[4];
#pragma unroll
      for (int u = 0; u < 4; u++) w[u] = silu_mul2(pk[4 * q + u], pk[uo + 4 * q + u]);
      stsm4(stg_row + (q >> 2) * BLK + ((((2 * q & 7) + (lane >> 4)) ^ (lane & 7)) << 4), w[0], w[1], w[2], w[3]);
    };
    r4.s = r4.wrap = 2;
#pragma unroll 1
    for (int t = 0; t < 3; t++) {
      float acc[128];
      mainloop<256, 4, 5>(acc, 16, t == 0, r4, sb, wg, lane, rel, STEP0 + 48 + 16 * t, [&](auto ic) {
        if (t) {
          if (ic.v == 3 || ic.v == 5) stage_done(sb, wg, ic.v >> 2, lane);
          if (ic.v < 5) { swiglu(2 * ic.v - 2, 32, ~t & 1); swiglu(2 * ic.v - 1, 32, 0); }
        }
      }, [&](int it) {
#pragma unroll
        for (int i = 0; i < 8; i++)
          if (t == 0 && it == 6 + i) gs->x1[bid * 2048 + (i >> 2) * 1024 + warp * 128 + (i & 3) * 32 + lane] = make_uint4(pk[4 * i], pk[4 * i + 1], pk[4 * i + 2], pk[4 * i + 3]);
      }, [&] { if (t == 0) fence_async_global(); else if (t == 2) mbar_wait(bar + B_X, 1); });
      if (warp == 0) TR(12 + 2 * t);
#pragma unroll
      for (int i = 0; i < 64; i++) pk[i] = pack2(acc[2 * i], acc[2 * i + 1]);
      if (warp == 0) TR(13 + 2 * t);
    }
    uint32_t x1[32];
    {
      float acc[64];
      mainloop<128, 6, 12>(acc, 16, false, r6, sb, wg, lane, rel, STEP0 + 96, [&](auto ic) {
        constexpr int b = ic.v > 6, q = ic.v - 6 * b;
        if (q == 1) {
#pragma unroll
          for (int i = 4 * b; i < 4 * b + 4; i++) { const uint4 x = lds128(sb + STG + b * BLK + warp * 2048 + (i & 3) * 512 + lane * 16); x1[4 * i] = x.x; x1[4 * i + 1] = x.y; x1[4 * i + 2] = x.z; x1[4 * i + 3] = x.w; }
          __syncwarp();
        } else if (q < 6) swiglu(4 * b + q - 2, 32, -1);
        else stage_done(sb, wg, b, lane);
      }, none, [] {});
      if (warp == 0) TR(18);
#pragma unroll
      for (int i = 0; i < 32; i++) pk[i] = pack2(acc[2 * i], acc[2 * i + 1]);
      if (warp == 0) TR(19);
    }
    {
      float acc[64];
      mainloop<128, 6, 5>(acc, 56, false, r6, sb, wg, lane, rel, STEP0 + 112, [&](auto ic) {
        if (ic.v == 5) stage_done(sb, wg, 0, lane); else swiglu(ic.v - 1, 16, 1);
      }, none, [&] {
        if (TAILLAG && wg == 0 && lane == 0) mbar_arrive(bar + B_LAG);
        load_vec(pk + 32, sb, 5, 0, lane); load_vec(pk + 40, sb, 5, 1, lane);
        mbar_wait(fre, 0); mbar_wait(fre + 8, 1);
      });
      __syncwarp();
      cl_arrive_relaxed();
      if (warp == 0) TR(20);
#pragma unroll
      for (int i = 0; i < 16; i += 2) {
        uint32_t w[4];
#pragma unroll
        for (int u = 0; u < 4; u++) {
          const int q = 2 * i + u;
          w[u] = pack2(fmaf(acc[2 * q], bf_lo(pk[32 + (q >> 1)]), bf_lo(x1[q])), fmaf(acc[2 * q + 1], bf_hi(pk[32 + (q >> 1)]), bf_hi(x1[q])));
        }
        stsm4(stg_row + (i >> 3) * BLK + ((((i & 7) + (lane >> 4)) ^ (lane & 7)) << 4), w[0], w[1], w[2], w[3]);
        if ((i & 7) == 6) {
          fence_async_smem();
          named_bar(2 + wg, 128);
          if (wq == 0 && elect()) { tma_store_3d(&maps.out, sb + STG + (i >> 3) * BLK + wg * HALF, j * 128 + (i >> 3) * 64, m * 64, wg); bulk_commit(); }
          if (i < 8) x1[16] |= __float_as_uint(lds32f(bar + ZERO));
        }
      }
      if (wq == 0) bulk_wait_read();
      if (wq == 0) TR(40 + wg);
      if (tid == 0) gs->epoch[bid + 4] = ep;
      if (warp == 0) TR(21);
      cl_wait();
    }
  }
}

typedef CUresult (*EncodeFn)(CUtensorMap*, CUtensorMapDataType, cuuint32_t, void*, const cuuint64_t*, const cuuint64_t*, const cuuint32_t*, const cuuint32_t*,
                             CUtensorMapInterleave, CUtensorMapSwizzle, CUtensorMapL2promotion, CUtensorMapFloatOOBfill);

void make_map(EncodeFn fn, CUtensorMap* mp, const void* base, uint64_t d0, uint64_t d1, uint64_t d2, uint64_t s1, uint64_t s2, uint32_t b2, uint32_t b0 = 64) {
  cuuint64_t d[3] = {d0, d1, d2}, s[2] = {s1, s2};
  cuuint32_t b[3] = {b0, 64, b2}, e[3] = {1, 1, 1};
  fn(mp, CU_TENSOR_MAP_DATA_TYPE_BFLOAT16, 3, (void*)base, d, s, b, e, CU_TENSOR_MAP_INTERLEAVE_NONE, b0 == 64 ? CU_TENSOR_MAP_SWIZZLE_128B : CU_TENSOR_MAP_SWIZZLE_NONE,
     CU_TENSOR_MAP_L2_PROMOTION_L2_128B, CU_TENSOR_MAP_FLOAT_OOB_FILL_NONE);
}

__global__ void probe_kernel() {}
int max_clusters(int size) {
  cudaLaunchConfig_t cfg = {};
  cudaLaunchAttribute at;
  at.id = cudaLaunchAttributeClusterDimension; at.val.clusterDim.x = size; at.val.clusterDim.y = 1; at.val.clusterDim.z = 1;
  cfg.gridDim = dim3(size * 66); cfg.blockDim = dim3(384); cfg.dynamicSmemBytes = SMEM_BYTES; cfg.attrs = &at; cfg.numAttrs = 1;
  int n = 0;
  if (cudaOccupancyMaxActiveClusters(&n, probe_kernel, &cfg) != cudaSuccess) { cudaGetLastError(); return 0; }
  return n;
}

}

extern "C" void kernel_launch(void* const* d_in, const int* in_sizes, int n_in, void* d_out, int out_size) {
  static EncodeFn fn = nullptr;
  static int by_sm = 0;
  static Scratch* gs = nullptr;
  if (!fn) {
    void* p = nullptr; cudaDriverEntryPointQueryResult q;
    cudaGetDriverEntryPoint("cuTensorMapEncodeTiled", &p, cudaEnableDefault, &q);
    fn = (EncodeFn)p;
    cudaFuncSetAttribute(fused_kernel, cudaFuncAttributeMaxDynamicSharedMemorySize, SMEM_BYTES);
    int dev = 0, sms = 0;
    cudaGetSymbolAddress((void**)&gs, g_scratch);
    cudaGetDevice(&dev);
    cudaDeviceGetAttribute(&sms, cudaDevAttrMultiProcessorCount, dev);
    cudaFuncSetAttribute(probe_kernel, cudaFuncAttributeMaxDynamicSharedMemorySize, SMEM_BYTES);
    by_sm = BYSM && sms == 132 && max_clusters(2) == 66 && max_clusters(4) == 30 && max_clusters(6) == 17 && max_clusters(8) == 15;
  }
  Maps mp;
  make_map(fn, &mp.x, d_in[0], D_, S_ / 2, 2, 4096, 2048, 2);
  make_map(fn, &mp.out, d_out, D_, S_ / 2, 2, 4096, 2048, 1);
  make_map(fn, &mp.wqkv, d_in[1], 64, D_, 3 * D_ / 64, 3 * D_ * 2, 128, 2);
  make_map(fn, &mp.wo, d_in[2], 64, D_, D_ / 64, D_ * 2, 128, 2);
  make_map(fn, &mp.w1, d_in[4], 64, D_, F_ / 64, F_ * 2, 128, 2);
  make_map(fn, &mp.w3, d_in[5], 64, D_, F_ / 64, F_ * 2, 128, 2);
  make_map(fn, &mp.w1s, d_in[4], 64, D_, F_ / 64, F_ * 2, 128, 1);
  make_map(fn, &mp.w3s, d_in[5], 64, D_, F_ / 64, F_ * 2, 128, 1);
  make_map(fn, &mp.w2, d_in[6], 64, F_, D_ / 64, D_ * 2, 128, 2);
  make_map(fn, &mp.wmod, d_in[8], 256, D_, 24, 6 * D_ * 2, 512, 1, 256);
  fused_kernel<<<132, 384, SMEM_BYTES>>>((const bf16*)d_in[7], (const bf16*)d_in[8], gs, by_sm, mp);
}
```

```cpp
#include <cuda_runtime.h>
#include <cuda_bf16.h>
#include <cuda.h>
#include <stdint.h>

typedef __nv_bfloat16 bf16;

#define NPIECE 4
#define PSLEEP 300
#define XSLEEP 4000
#define XDELAY 2000
#define TAILLAG 5
#define HSLEEP 400
#define B1D 900
#define B1P 3800
#define BYSM 1
namespace {

constexpr int S_ = 2048, D_ = 1024, F_ = 3584;
constexpr int BLK = 16384;
constexpr int HALF = 8192;
constexpr int RING = 196608;
constexpr int STG = RING;
constexpr int MISC = RING + 2 * BLK;
constexpr int SMEM_BYTES = MISC + 3072;
constexpr int B_FULL4 = 0, B_EMPTY4 = 32, B_FULL6 = 64, B_EMPTY6 = 112, B_RDY = 160, B_FREE = 176, B_LAG = 192, B_X = 208, B_MOD = 224, B_HALO = 232, B_HH = 256, B_ALL = 272, B_HH2 = 288, ZERO = 296;
constexpr int MODV = 512;
constexpr int RED_OFF = 0;
constexpr float SCL = 0.17677669529663687f * 1.4426950408889634f;
constexpr int U_HH = 64;

struct Maps { CUtensorMap x, out, wqkv, wo, w1, w3, w1s, w3s, w2, wmod; };

struct Scratch {
  uint4 h[16 * 16 * 1024];
  uint4 o[16 * 16 * 1024];
  uint4 hh[16 * 56 * 1024];
  uint4 x1[128 * 8 * 256];
  uint4 stat[2 * 16 * 8 * 128];
  uint4 halo[16 * 8 * 2 * 512];
  uint2 modp[8 * 2 * 4 * 128];
  uint2 modv[4 * 1024];
  uint32_t flag[16 * 128];
  uint32_t epoch[132];
};
__device__ __align__(1024) Scratch g_scratch;
#define TR(i)
#define TRS(i)
#define STEP0 gs->flag

__device__ __forceinline__ void bail() { asm volatile("st.global.u32 [%0], %1;" :: "l"(0ull), "r"(0) : "memory"); }
__device__ __forceinline__ uint32_t smem_u32(const void* p) { return (uint32_t)__cvta_generic_to_shared(p); }
__device__ __forceinline__ void mbar_init(uint32_t bar, uint32_t cnt) { asm volatile("mbarrier.init.shared::cta.b64 [%0], %1;" :: "r"(bar), "r"(cnt) : "memory"); }
__device__ __forceinline__ void mbar_expect_tx(uint32_t bar, uint32_t bytes) { asm volatile("mbarrier.arrive.expect_tx.shared::cta.b64 _, [%0], %1;" :: "r"(bar), "r"(bytes) : "memory"); }
__device__ __forceinline__ void mbar_arrive(uint32_t bar) { asm volatile("mbarrier.arrive.shared::cta.b64 _, [%0];" :: "r"(bar) : "memory"); }
__device__ __forceinline__ void mbar_arrive_cl(uint32_t cl_addr) { asm volatile("mbarrier.arrive.shared::cluster.b64 _, [%0];" :: "r"(cl_addr) : "memory"); }
__device__ __forceinline__ uint32_t mapa(uint32_t addr, uint32_t cta) { uint32_t r; asm("mapa.shared::cluster.u32 %0, %1, %2;" : "=r"(r) : "r"(addr), "r"(cta)); return r; }
__device__ __forceinline__ void mbar_wait(uint32_t bar, uint32_t parity) {
  asm volatile("{\n.reg .pred p;\n.reg .b32 n;\n.reg .b64 z;\nmov.b32 n, 0;\nmov.b64 z, 0;\n"
               "W: add.u32 n, n, 1;\nsetp.gt.u32 p, n, 0x400000;\n@p st.global.u32 [z], n;\n"
               "mbarrier.try_wait.parity.shared::cta.b64 p, [%0], %1;\n@!p bra W;\n}" :: "r"(bar), "r"(parity) : "memory");
}
__device__ __forceinline__ void tma_3d(uint32_t dst, const CUtensorMap* m, uint32_t bar, int c0, int c1, int c2) {
  asm volatile("cp.async.bulk.tensor.3d.shared::cluster.global.mbarrier::complete_tx::bytes [%0], [%1, {%3, %4, %5}], [%2];" :: "r"(dst), "l"(m), "r"(bar), "r"(c0), "r"(c1), "r"(c2) : "memory");
}
__device__ __forceinline__ void tma_store_3d(const CUtensorMap* m, uint32_t src, int c0, int c1, int c2) {
  asm volatile("cp.async.bulk.tensor.3d.global.shared::cta.bulk_group [%0, {%2, %3, %4}], [%1];" :: "l"(m), "r"(src), "r"(c0), "r"(c1), "r"(c2) : "memory");
}
__device__ __forceinline__ void bulk_ld(uint32_t dst, const void* src, uint32_t bytes, uint32_t bar) {
  asm volatile("cp.async.bulk.shared::cluster.global.mbarrier::complete_tx::bytes [%0], [%1], %2, [%3];" :: "r"(dst), "l"(src), "r"(bytes), "r"(bar) : "memory");
}
__device__ __forceinline__ void bulk_ld_mc(uint32_t dst, const void* src, uint32_t bytes, uint32_t bar) {
  asm volatile("cp.async.bulk.shared::cluster.global.mbarrier::complete_tx::bytes.multicast::cluster [%0], [%1], %2, [%3], %4;" :: "r"(dst), "l"(src), "r"(bytes), "r"(bar), "h"((uint16_t)3) : "memory");
}
__device__ __forceinline__ void bulk_push(uint32_t dst_cl, uint32_t src, uint32_t bytes, uint32_t bar_cl) {
  asm volatile("cp.async.bulk.shared::cluster.shared::cta.mbarrier::complete_tx::bytes [%0], [%1], %2, [%3];" :: "r"(dst_cl), "r"(src), "r"(bytes), "r"(bar_cl) : "memory");
}
__device__ __forceinline__ void bulk_st(void* dst, uint32_t src, uint32_t bytes) {
  asm volatile("cp.async.bulk.global.shared::cta.bulk_group [%0], [%1], %2;" :: "l"(dst), "r"(src), "r"(bytes) : "memory");
}
__device__ __forceinline__ void bulk_commit() { asm volatile("cp.async.bulk.commit_group;" ::: "memory"); }
__device__ __forceinline__ void bulk_wait_read() { asm volatile("cp.async.bulk.wait_group.read 0;" ::: "memory"); }
__device__ __forceinline__ void bulk_wait_all() { asm volatile("cp.async.bulk.wait_group 0;" ::: "memory"); }
__device__ __forceinline__ void fence_async_global() { asm volatile("fence.proxy.async.global;" ::: "memory"); }
__device__ __forceinline__ void fence_async_smem() { asm volatile("fence.proxy.async.shared::cta;" ::: "memory"); }
__device__ __forceinline__ void wg_arrive() { asm volatile("wgmma.fence.sync.aligned;" ::: "memory"); }
__device__ __forceinline__ void wg_commit() { asm volatile("wgmma.commit_group.sync.aligned;" ::: "memory"); }
template <int N> __device__ __forceinline__ void wg_wait() { asm volatile("wgmma.wait_group.sync.aligned %0;" :: "n"(N) : "memory"); }
__device__ __forceinline__ void cl_arrive_relaxed() { asm volatile("barrier.cluster.arrive.relaxed.aligned;" ::: "memory"); }
__device__ __forceinline__ void cl_wait() { asm volatile("barrier.cluster.wait.acquire.aligned;" ::: "memory"); }
__device__ __forceinline__ bool elect() { uint32_t p; asm volatile("{\n.reg .pred p;\nelect.sync _|p, 0xffffffff;\nselp.u32 %0, 1, 0, p;\n}" : "=r"(p)); return p; }
__device__ __forceinline__ void named_bar(int id, int n) { asm volatile("bar.sync %0, %1;" :: "r"(id), "r"(n) : "memory"); }
__device__ __forceinline__ uint32_t pack2(float lo, float hi) { uint32_t r; asm("cvt.rn.bf16x2.f32 %0, %1, %2;" : "=r"(r) : "f"(hi), "f"(lo)); return r; }
__device__ __forceinline__ float bf_lo(uint32_t w) { return __uint_as_float(w << 16); }
__device__ __forceinline__ float bf_hi(uint32_t w) { return __uint_as_float(w & 0xffff0000u); }
__device__ __forceinline__ float bf_round(float v) { return __bfloat162float(__float2bfloat16_rn(v)); }
__device__ __forceinline__ void stsm4(uint32_t addr, uint32_t a, uint32_t b, uint32_t c, uint32_t d) {
  asm volatile("stmatrix.sync.aligned.m8n8.x4.shared.b16 [%0], {%1, %2, %3, %4};" :: "r"(addr), "r"(a), "r"(b), "r"(c), "r"(d) : "memory");
}
__device__ __forceinline__ void ldsm4(uint32_t addr, uint32_t& a, uint32_t& b, uint32_t& c, uint32_t& d) {
  asm volatile("ldmatrix.sync.aligned.m8n8.x4.shared.b16 {%0, %1, %2, %3}, [%4];" : "=r"(a), "=r"(b), "=r"(c), "=r"(d) : "r"(addr) : "memory");
}
__device__ __forceinline__ uint32_t movm(uint32_t a) { uint32_t r; asm volatile("movmatrix.sync.aligned.m8n8.trans.b16 %0, %1;" : "=r"(r) : "r"(a)); return r; }
__device__ __forceinline__ void mma16(float (&d)[4], uint32_t a0, uint32_t a1, uint32_t a2, uint32_t a3, uint32_t b0, uint32_t b1) {
  asm("mma.sync.aligned.m16n8k16.row.col.f32.bf16.bf16.f32 {%0,%1,%2,%3}, {%4,%5,%6,%7}, {%8,%9}, {%0,%1,%2,%3};"
               : "+f"(d[0]), "+f"(d[1]), "+f"(d[2]), "+f"(d[3]) : "r"(a0), "r"(a1), "r"(a2), "r"(a3), "r"(b0), "r"(b1));
}
__device__ __forceinline__ void mma16z(float (&d)[4], uint32_t a0, uint32_t a1, uint32_t a2, uint32_t a3, uint32_t b0, uint32_t b1) {
  asm("mma.sync.aligned.m16n8k16.row.col.f32.bf16.bf16.f32 {%0,%1,%2,%3}, {%4,%5,%6,%7}, {%8,%9}, {%10,%10,%10,%10};"
      : "=f"(d[0]), "=f"(d[1]), "=f"(d[2]), "=f"(d[3]) : "r"(a0), "r"(a1), "r"(a2), "r"(a3), "r"(b0), "r"(b1), "f"(0.f));
}
__device__ __forceinline__ void mma8z(float (&d)[4], uint32_t a0, uint32_t a1, uint32_t b0) {
  asm("mma.sync.aligned.m16n8k8.row.col.f32.bf16.bf16.f32 {%0,%1,%2,%3}, {%4,%5}, {%6}, {%7,%7,%7,%7};"
      : "=f"(d[0]), "=f"(d[1]), "=f"(d[2]), "=f"(d[3]) : "r"(a0), "r"(a1), "r"(b0), "f"(0.f));
}
__device__ __forceinline__ void mma8(float (&d)[4], uint32_t a0, uint32_t a1, uint32_t b0) {
  asm("mma.sync.aligned.m16n8k8.row.col.f32.bf16.bf16.f32 {%0,%1,%2,%3}, {%4,%5}, {%6}, {%0,%1,%2,%3};"
               : "+f"(d[0]), "+f"(d[1]), "+f"(d[2]), "+f"(d[3]) : "r"(a0), "r"(a1), "r"(b0));
}
__device__ __forceinline__ uint4 lds128(uint32_t a) { uint4 v; asm volatile("ld.shared.v4.u32 {%0,%1,%2,%3}, [%4];" : "=r"(v.x), "=r"(v.y), "=r"(v.z), "=r"(v.w) : "r"(a) : "memory"); return v; }
__device__ __forceinline__ void sts128(uint32_t a, uint32_t x, uint32_t y, uint32_t z, uint32_t w) { asm volatile("st.shared.v4.u32 [%0], {%1,%2,%3,%4};" :: "r"(a), "r"(x), "r"(y), "r"(z), "r"(w) : "memory"); }
__device__ __forceinline__ float lds32f(uint32_t a) { float v; asm volatile("ld.shared.f32 %0, [%1];" : "=f"(v) : "r"(a) : "memory"); return v; }
__device__ __forceinline__ void sts16(uint32_t a, bf16 v) { asm volatile("st.shared.b16 [%0], %1;" :: "r"(a), "h"(__bfloat16_as_ushort(v)) : "memory"); }
__device__ __forceinline__ uint4 ldg_nc(const void* p) { uint4 v; asm volatile("ld.global.nc.L1::no_allocate.v4.u32 {%0,%1,%2,%3}, [%4];" : "=r"(v.x), "=r"(v.y), "=r"(v.z), "=r"(v.w) : "l"(p)); return v; }
__device__ __forceinline__ uint4 ld_rlx4(const uint4* p) {
  unsigned long long a, b; asm volatile("ld.relaxed.gpu.global.v2.b64 {%0,%1}, [%2];" : "=l"(a), "=l"(b) : "l"(p) : "memory");
  return make_uint4((uint32_t)a, (uint32_t)(a >> 32), (uint32_t)b, (uint32_t)(b >> 32));
}
__device__ __forceinline__ uint2 ld_rlx2(const uint2* p) { unsigned long long a; asm volatile("ld.relaxed.gpu.global.b64 %0, [%1];" : "=l"(a) : "l"(p) : "memory"); return make_uint2((uint32_t)a, (uint32_t)(a >> 32)); }
__device__ __forceinline__ void st_rlx4(uint4* p, uint32_t x, uint32_t y, uint32_t z, uint32_t w) {
  asm volatile("st.relaxed.gpu.global.v2.b64 [%0], {%1,%2};" :: "l"(p), "l"((unsigned long long)x | ((unsigned long long)y << 32)), "l"((unsigned long long)z | ((unsigned long long)w << 32)) : "memory");
}
__device__ __forceinline__ void st_rlx2(uint2* p, uint32_t x, uint32_t y) { asm volatile("st.relaxed.gpu.global.b64 [%0], %1;" :: "l"(p), "l"((unsigned long long)x | ((unsigned long long)y << 32)) : "memory"); }
__device__ __forceinline__ void st_release(uint32_t* p, uint32_t v) { asm volatile("st.release.gpu.global.u32 [%0], %1;" :: "l"(p), "r"(v) : "memory"); }
__device__ __forceinline__ uint32_t ld_acquire(const uint32_t* p) { uint32_t v; asm volatile("ld.acquire.gpu.global.u32 %0, [%1];" : "=r"(v) : "l"(p) : "memory"); return v; }
__device__ __forceinline__ void prefetch_map(const CUtensorMap* m) { asm volatile("prefetch.tensormap [%0];" :: "l"(m) : "memory"); }
__device__ __forceinline__ float rcp(float x) { float r; asm("rcp.approx.ftz.f32 %0, %1;" : "=f"(r) : "f"(x)); return r; }
__device__ __forceinline__ float ex2(float x) { float r; asm("ex2.approx.ftz.f32 %0, %1;" : "=f"(r) : "f"(x)); return r; }
__device__ __forceinline__ float tanh_fast(float x) { float r; asm("tanh.approx.f32 %0, %1;" : "=f"(r) : "f"(x)); return r; }
#define SPIN_GUARD(n) if (++(n) > (1u << 24)) bail()

__device__ __forceinline__ void wgmma_n128(float (&d)[64], uint64_t da, uint64_t db) {
  asm volatile("wgmma.mma_async.sync.aligned.m64n128k16.f32.bf16.bf16 "
    "{%0, %1, %2, %3, %4, %5, %6, %7, %8, %9, %10, %11, %12, %13, %14, %15, %16, %17, %18, %19, %20, %21, %22, %23, %24, %25, %26, %27, %28, %29, %30, %31, %32, %33, %34, %35, %36, %37, %38, %39, %40, %41, %42, %43, %44, %45, %46, %47, %48, %49, %50, %51, %52, %53, %54, %55, %56, %57, %58, %59, %60, %61, %62, %63}, "
    "%64, %65, 1, 1, 1, 0, 1;\n"
    : "+f"(d[0]), "+f"(d[1]), "+f"(d[2]), "+f"(d[3]), "+f"(d[4]), "+f"(d[5]), "+f"(d[6]), "+f"(d[7]), "+f"(d[8]), "+f"(d[9]), "+f"(d[10]), "+f"(d[11]), "+f"(d[12]), "+f"(d[13]), "+f"(d[14]), "+f"(d[15]), "+f"(d[16]), "+f"(d[17]), "+f"(d[18]), "+f"(d[19]), "+f"(d[20]), "+f"(d[21]), "+f"(d[22]), "+f"(d[23]), "+f"(d[24]), "+f"(d[25]), "+f"(d[26]), "+f"(d[27]), "+f"(d[28]), "+f"(d[29]), "+f"(d[30]), "+f"(d[31]), "+f"(d[32]), "+f"(d[33]), "+f"(d[34]), "+f"(d[35]), "+f"(d[36]), "+f"(d[37]), "+f"(d[38]), "+f"(d[39]), "+f"(d[40]), "+f"(d[41]), "+f"(d[42]), "+f"(d[43]), "+f"(d[44]), "+f"(d[45]), "+f"(d[46]), "+f"(d[47]), "+f"(d[48]), "+f"(d[49]), "+f"(d[50]), "+f"(d[51]), "+f"(d[52]), "+f"(d[53]), "+f"(d[54]), "+f"(d[55]), "+f"(d[56]), "+f"(d[57]), "+f"(d[58]), "+f"(d[59]), "+f"(d[60]), "+f"(d[61]), "+f"(d[62]), "+f"(d[63])
    : "l"(da), "l"(db));
}
__device__ __forceinline__ void wgmma_n128_first(float (&d)[64], uint64_t da, uint64_t db) {
  asm volatile("wgmma.mma_async.sync.aligned.m64n128k16.f32.bf16.bf16 "
    "{%0, %1, %2, %3, %4, %5, %6, %7, %8, %9, %10, %11, %12, %13, %14, %15, %16, %17, %18, %19, %20, %21, %22, %23, %24, %25, %26, %27, %28, %29, %30, %31, %32, %33, %34, %35, %36, %37, %38, %39, %40, %41, %42, %43, %44, %45, %46, %47, %48, %49, %50, %51, %52, %53, %54, %55, %56, %57, %58, %59, %60, %61, %62, %63}, "
    "%64, %65, 0, 1, 1, 0, 1;\n"
    : "=f"(d[0]), "=f"(d[1]), "=f"(d[2]), "=f"(d[3]), "=f"(d[4]), "=f"(d[5]), "=f"(d[6]), "=f"(d[7]), "=f"(d[8]), "=f"(d[9]), "=f"(d[10]), "=f"(d[11]), "=f"(d[12]), "=f"(d[13]), "=f"(d[14]), "=f"(d[15]), "=f"(d[16]), "=f"(d[17]), "=f"(d[18]), "=f"(d[19]), "=f"(d[20]), "=f"(d[21]), "=f"(d[22]), "=f"(d[23]), "=f"(d[24]), "=f"(d[25]), "=f"(d[26]), "=f"(d[27]), "=f"(d[28]), "=f"(d[29]), "=f"(d[30]), "=f"(d[31]), "=f"(d[32]), "=f"(d[33]), "=f"(d[34]), "=f"(d[35]), "=f"(d[36]), "=f"(d[37]), "=f"(d[38]), "=f"(d[39]), "=f"(d[40]), "=f"(d[41]), "=f"(d[42]), "=f"(d[43]), "=f"(d[44]), "=f"(d[45]), "=f"(d[46]), "=f"(d[47]), "=f"(d[48]), "=f"(d[49]), "=f"(d[50]), "=f"(d[51]), "=f"(d[52]), "=f"(d[53]), "=f"(d[54]), "=f"(d[55]), "=f"(d[56]), "=f"(d[57]), "=f"(d[58]), "=f"(d[59]), "=f"(d[60]), "=f"(d[61]), "=f"(d[62]), "=f"(d[63])
    : "l"(da), "l"(db));
}
__device__ __forceinline__ void wgmma_n256(float (&d)[128], uint64_t da, uint64_t db) {
  asm volatile("wgmma.mma_async.sync.aligned.m64n256k16.f32.bf16.bf16 "
    "{%0, %1, %2, %3, %4, %5, %6, %7, %8, %9, %10, %11, %12, %13, %14, %15, %16, %17, %18, %19, %20, %21, %22, %23, %24, %25, %26, %27, %28, %29, %30, %31, %32, %33, %34, %35, %36, %37, %38, %39, %40, %41, %42, %43, %44, %45, %46, %47, %48, %49, %50, %51, %52, %53, %54, %55, %56, %57, %58, %59, %60, %61, %62, %63, %64, %65, %66, %67, %68, %69, %70, %71, %72, %73, %74, %75, %76, %77, %78, %79, %80, %81, %82, %83, %84, %85, %86, %87, %88, %89, %90, %91, %92, %93, %94, %95, %96, %97, %98, %99, %100, %101, %102, %103, %104, %105, %106, %107, %108, %109, %110, %111, %112, %113, %114, %115, %116, %117, %118, %119, %120, %121, %122, %123, %124, %125, %126, %127}, "
    "%128, %129, 1, 1, 1, 0, 1;\n"
    : "+f"(d[0]), "+f"(d[1]), "+f"(d[2]), "+f"(d[3]), "+f"(d[4]), "+f"(d[5]), "+f"(d[6]), "+f"(d[7]), "+f"(d[8]), "+f"(d[9]), "+f"(d[10]), "+f"(d[11]), "+f"(d[12]), "+f"(d[13]), "+f"(d[14]), "+f"(d[15]), "+f"(d[16]), "+f"(d[17]), "+f"(d[18]), "+f"(d[19]), "+f"(d[20]), "+f"(d[21]), "+f"(d[22]), "+f"(d[23]), "+f"(d[24]), "+f"(d[25]), "+f"(d[26]), "+f"(d[27]), "+f"(d[28]), "+f"(d[29]), "+f"(d[30]), "+f"(d[31]), "+f"(d[32]), "+f"(d[33]), "+f"(d[34]), "+f"(d[35]), "+f"(d[36]), "+f"(d[37]), "+f"(d[38]), "+f"(d[39]), "+f"(d[40]), "+f"(d[41]), "+f"(d[42]), "+f"(d[43]), "+f"(d[44]), "+f"(d[45]), "+f"(d[46]), "+f"(d[47]), "+f"(d[48]), "+f"(d[49]), "+f"(d[50]), "+f"(d[51]), "+f"(d[52]), "+f"(d[53]), "+f"(d[54]), "+f"(d[55]), "+f"(d[56]), "+f"(d[57]), "+f"(d[58]), "+f"(d[59]), "+f"(d[60]), "+f"(d[61]), "+f"(d[62]), "+f"(d[63]), "+f"(d[64]), "+f"(d[65]), "+f"(d[66]), "+f"(d[67]), "+f"(d[68]), "+f"(d[69]), "+f"(d[70]), "+f"(d[71]), "+f"(d[72]), "+f"(d[73]), "+f"(d[74]), "+f"(d[75]), "+f"(d[76]), "+f"(d[77]), "+f"(d[78]), "+f"(d[79]), "+f"(d[80]), "+f"(d[81]), "+f"(d[82]), "+f"(d[83]), "+f"(d[84]), "+f"(d[85]), "+f"(d[86]), "+f"(d[87]), "+f"(d[88]), "+f"(d[89]), "+f"(d[90]), "+f"(d[91]), "+f"(d[92]), "+f"(d[93]), "+f"(d[94]), "+f"(d[95]), "+f"(d[96]), "+f"(d[97]), "+f"(d[98]), "+f"(d[99]), "+f"(d[100]), "+f"(d[101]), "+f"(d[102]), "+f"(d[103]), "+f"(d[104]), "+f"(d[105]), "+f"(d[106]), "+f"(d[107]), "+f"(d[108]), "+f"(d[109]), "+f"(d[110]), "+f"(d[111]), "+f"(d[112]), "+f"(d[113]), "+f"(d[114]), "+f"(d[115]), "+f"(d[116]), "+f"(d[117]), "+f"(d[118]), "+f"(d[119]), "+f"(d[120]), "+f"(d[121]), "+f"(d[122]), "+f"(d[123]), "+f"(d[124]), "+f"(d[125]), "+f"(d[126]), "+f"(d[127])
    : "l"(da), "l"(db));
}
__device__ __forceinline__ void wgmma_n256_first(float (&d)[128], uint64_t da, uint64_t db) {
  asm volatile("wgmma.mma_async.sync.aligned.m64n256k16.f32.bf16.bf16 "
    "{%0, %1, %2, %3, %4, %5, %6, %7, %8, %9, %10, %11, %12, %13, %14, %15, %16, %17, %18, %19, %20, %21, %22, %23, %24, %25, %26, %27, %28, %29, %30, %31, %32, %33, %34, %35, %36, %37, %38, %39, %40, %41, %42, %43, %44, %45, %46, %47, %48, %49, %50, %51, %52, %53, %54, %55, %56, %57, %58, %59, %60, %61, %62, %63, %64, %65, %66, %67, %68, %69, %70, %71, %72, %73, %74, %75, %76, %77, %78, %79, %80, %81, %82, %83, %84, %85, %86, %87, %88, %89, %90, %91, %92, %93, %94, %95, %96, %97, %98, %99, %100, %101, %102, %103, %104, %105, %106, %107, %108, %109, %110, %111, %112, %113, %114, %115, %116, %117, %118, %119, %120, %121, %122, %123, %124, %125, %126, %127}, "
    "%128, %129, 0, 1, 1, 0, 1;\n"
    : "=f"(d[0]), "=f"(d[1]), "=f"(d[2]), "=f"(d[3]), "=f"(d[4]), "=f"(d[5]), "=f"(d[6]), "=f"(d[7]), "=f"(d[8]), "=f"(d[9]), "=f"(d[10]), "=f"(d[11]), "=f"(d[12]), "=f"(d[13]), "=f"(d[14]), "=f"(d[15]), "=f"(d[16]), "=f"(d[17]), "=f"(d[18]), "=f"(d[19]), "=f"(d[20]), "=f"(d[21]), "=f"(d[22]), "=f"(d[23]), "=f"(d[24]), "=f"(d[25]), "=f"(d[26]), "=f"(d[27]), "=f"(d[28]), "=f"(d[29]), "=f"(d[30]), "=f"(d[31]), "=f"(d[32]), "=f"(d[33]), "=f"(d[34]), "=f"(d[35]), "=f"(d[36]), "=f"(d[37]), "=f"(d[38]), "=f"(d[39]), "=f"(d[40]), "=f"(d[41]), "=f"(d[42]), "=f"(d[43]), "=f"(d[44]), "=f"(d[45]), "=f"(d[46]), "=f"(d[47]), "=f"(d[48]), "=f"(d[49]), "=f"(d[50]), "=f"(d[51]), "=f"(d[52]), "=f"(d[53]), "=f"(d[54]), "=f"(d[55]), "=f"(d[56]), "=f"(d[57]), "=f"(d[58]), "=f"(d[59]), "=f"(d[60]), "=f"(d[61]), "=f"(d[62]), "=f"(d[63]), "=f"(d[64]), "=f"(d[65]), "=f"(d[66]), "=f"(d[67]), "=f"(d[68]), "=f"(d[69]), "=f"(d[70]), "=f"(d[71]), "=f"(d[72]), "=f"(d[73]), "=f"(d[74]), "=f"(d[75]), "=f"(d[76]), "=f"(d[77]), "=f"(d[78]), "=f"(d[79]), "=f"(d[80]), "=f"(d[81]), "=f"(d[82]), "=f"(d[83]), "=f"(d[84]), "=f"(d[85]), "=f"(d[86]), "=f"(d[87]), "=f"(d[88]), "=f"(d[89]), "=f"(d[90]), "=f"(d[91]), "=f"(d[92]), "=f"(d[93]), "=f"(d[94]), "=f"(d[95]), "=f"(d[96]), "=f"(d[97]), "=f"(d[98]), "=f"(d[99]), "=f"(d[100]), "=f"(d[101]), "=f"(d[102]), "=f"(d[103]), "=f"(d[104]), "=f"(d[105]), "=f"(d[106]), "=f"(d[107]), "=f"(d[108]), "=f"(d[109]), "=f"(d[110]), "=f"(d[111]), "=f"(d[112]), "=f"(d[113]), "=f"(d[114]), "=f"(d[115]), "=f"(d[116]), "=f"(d[117]), "=f"(d[118]), "=f"(d[119]), "=f"(d[120]), "=f"(d[121]), "=f"(d[122]), "=f"(d[123]), "=f"(d[124]), "=f"(d[125]), "=f"(d[126]), "=f"(d[127])
    : "l"(da), "l"(db));
}

template <int N> struct WG;
#define DEF_WG(N) template <> struct WG<N> { \
  static __device__ __forceinline__ void mma(float (&d)[N / 2], uint64_t a, uint64_t b) { wgmma_n##N(d, a, b); } \
  static __device__ __forceinline__ void first(float (&d)[N / 2], uint64_t a, uint64_t b) { wgmma_n##N##_first(d, a, b); } };
DEF_WG(128) DEF_WG(256)

constexpr uint64_t DESC_A = (1ull << 62) | ((uint64_t)(1024 >> 4) << 32) | (1ull << 16);
constexpr uint64_t DESC_B = (1ull << 62) | ((uint64_t)(1024 >> 4) << 32) | ((uint64_t)(8192 >> 4) << 16);

struct Ring { int s; uint32_t ph; int wrap; };
template <int NS> __device__ __forceinline__ void ring_next(Ring& r) { r.s = (r.s + 1 == NS) ? 0 : r.s + 1; if (r.s == r.wrap) r.ph ^= 1; }

__device__ __forceinline__ int own_order(int it, int j) {
  return it < 2 ? 2 * j + it : it < 4 ? 2 * (j ^ 1) + it - 2 : ((j >> 1) * 4 + 2 * it - (it < 10 ? 4 : 15)) & 15;
}

template <int V> struct IC { static constexpr int v = V; };
template <int I, int E, class F> __device__ __forceinline__ void static_for(F&& f) { if constexpr (I < E) { f(IC<I>{}); static_for<I + 1, E>(f); } }

template <int N, int NS, int PRE, class Pre, class Mid, class Last>
__device__ __forceinline__ void mainloop(float (&acc)[N / 2], int nkb, bool own, Ring& r, uint32_t sb, int wg, int lane, uint32_t rel_base, uint32_t* step0, Pre pre, Mid mid, Last last) {
  constexpr int SLOT = RING / NS;
  const uint32_t full = sb + MISC + (NS == 4 ? B_FULL4 : B_FULL6);
  const uint32_t rel = rel_base + (NS == 4 ? B_EMPTY4 : B_EMPTY6);
  const uint32_t s0 = (sb & 0x3FFFF) >> 4, a0 = s0 + wg * (HALF >> 4);
  int ps;
  auto issue = [&](int it, bool first) {
    const uint64_t da = DESC_A | (a0 + ((own && it < 2) ? (STG + it * BLK) >> 4 : r.s * (SLOT >> 4))), db = DESC_B | (s0 + r.s * (SLOT >> 4) + (BLK >> 4));
    mbar_wait(full + r.s * 8, r.ph);
    TRS(it);
    wg_arrive();
    if (first) WG<N>::first(acc, da, db); else WG<N>::mma(acc, da, db);
#pragma unroll
    for (int k = 1; k < 4; k++) WG<N>::mma(acc, da + k * 2, db + k * 128);
    wg_commit();
  };
  auto retire = [&](int it) {
    wg_wait<1>();
    if (lane < 2) mbar_arrive_cl(rel + ps * 8);
    ps = r.s;
    ring_next<NS>(r);
  };
  issue(0, true);
  ps = r.s;
  ring_next<NS>(r);
  static_for<1, PRE + 1>([&](auto ic) { issue(ic.v, false); pre(ic); retire(ic.v); });
#pragma unroll 1
  for (int it = PRE + 1; it < nkb; it++) {
    if (TAILLAG && it == 56 - TAILLAG && wg == 1) mbar_wait(sb + MISC + B_LAG, 0);
    issue(it, false); mid(it); retire(it);
  }
  last();
  wg_wait<0>();
  if (lane < 2) mbar_arrive_cl(rel + ps * 8);
}

__device__ __forceinline__ void ln_publish(const float (&v)[64], uint4* st, int j, int row0, int lane, uint32_t ep) {
  float s0 = 0, s1 = 0, s2 = 0, s3 = 0, q0 = 0, q1 = 0, q2 = 0, q3 = 0;
#pragma unroll
  for (int i = 0; i < 16; i++) {
    s0 += v[4 * i]; s1 += v[4 * i + 1]; s2 += v[4 * i + 2]; s3 += v[4 * i + 3];
    q0 = fmaf(v[4 * i], v[4 * i], q0); q1 = fmaf(v[4 * i + 1], v[4 * i + 1], q1); q2 = fmaf(v[4 * i + 2], v[4 * i + 2], q2); q3 = fmaf(v[4 * i + 3], v[4 * i + 3], q3);
  }
  s0 += s1; s2 += s3; q0 += q1; q2 += q3;
  const bool odd = lane & 1;
  float s = (odd ? s2 : s0) + __shfl_xor_sync(~0u, odd ? s0 : s2, 1), q = (odd ? q2 : q0) + __shfl_xor_sync(~0u, odd ? q0 : q2, 1);
  s += __shfl_xor_sync(~0u, s, 2); q += __shfl_xor_sync(~0u, q, 2);
  if ((lane & 3) < 2) st_rlx4(st + j * 128 + row0 + (lane & 1) * 8, __float_as_uint(s), ep, __float_as_uint(q), ep);
}
__device__ __forceinline__ void ln_gather(const uint4* st, int row0, int lane, uint32_t ep, float& n0, float& r0, float& n1, float& r1) {
  const uint4* p = st + (lane & 2) * 256 + row0 + (lane & 1) * 8;
  uint4 a, b, c, d; uint32_t n = 0;
  while (true) {
    a = ld_rlx4(p); b = ld_rlx4(p + 128); c = ld_rlx4(p + 256); d = ld_rlx4(p + 384);
    if (a.y == ep && a.w == ep && b.y == ep && b.w == ep && c.y == ep && c.w == ep && d.y == ep && d.w == ep) break;
    SPIN_GUARD(n);
  }
  __syncwarp();
  float s = (__uint_as_float(a.x) + __uint_as_float(b.x)) + (__uint_as_float(c.x) + __uint_as_float(d.x));
  float q = (__uint_as_float(a.z) + __uint_as_float(b.z)) + (__uint_as_float(c.z) + __uint_as_float(d.z));
  s += __shfl_xor_sync(~0u, s, 2); q += __shfl_xor_sync(~0u, q, 2);
  s *= 1.f / 1024;
  const float r = rsqrtf(fmaxf(fmaf(-s, s, q * (1.f / 1024)), 0.f) + 1e-5f), nn = -s * r;
  const float ro = __shfl_xor_sync(~0u, r, 1), no = __shfl_xor_sync(~0u, nn, 1);
  const bool odd = lane & 1;
  r0 = odd ? ro : r; n0 = odd ? no : nn; r1 = odd ? r : ro; n1 = odd ? nn : no;
}
__device__ __forceinline__ void load_vec(uint32_t* w, uint32_t sb, int sec, int b, int lane) {
#pragma unroll
  for (int q = 0; q < 2; q++) { uint4 t = lds128(sb + MISC + MODV + sec * 256 + (lane & 3) * 64 + b * 32 + q * 16); w[4 * q] = t.x; w[4 * q + 1] = t.y; w[4 * q + 2] = t.z; w[4 * q + 3] = t.w; }
}
__device__ __forceinline__ void stage_done(uint32_t sb, int wg, int b, int lane) {
  fence_async_smem();
  __syncwarp();
  if (lane == 0) mbar_arrive(sb + MISC + B_RDY + b * 8);
}
__device__ __forceinline__ uint32_t hfma2(uint32_t a, uint32_t b, uint32_t c) { uint32_t r; asm("fma.rn.bf16x2 %0, %1, %2, %3;" : "=r"(r) : "r"(a), "r"(b), "r"(c)); return r; }
__device__ __forceinline__ void ln_apply(const float (&v)[64], const uint4* st, int row0, uint32_t ep, uint32_t sb, int sec_shift, int sec_scale, uint32_t stg_row, int wg, int lane) {
  uint32_t sc[16], sh[16];
#pragma unroll
  for (int b = 0; b < 2; b++) { load_vec(sc + 8 * b, sb, sec_scale, b, lane); load_vec(sh + 8 * b, sb, sec_shift, b, lane); }
  float n0, r0, n1, r1;
  ln_gather(st, row0, lane, ep, n0, r0, n1, r1);
#pragma unroll
  for (int i = 0; i < 16; i += 2) {
    if (i == 8) { const float z = lds32f(sb + MISC + ZERO); n0 += z; n1 += z; }
    uint32_t w[4];
#pragma unroll
    for (int u = 0; u < 2; u++) {
      int q = i + u;
      w[2 * u] = hfma2(pack2(fmaf(v[4 * q], r0, n0), fmaf(v[4 * q + 1], r0, n0)), sc[q], sh[q]);
      w[2 * u + 1] = hfma2(pack2(fmaf(v[4 * q + 2], r1, n1), fmaf(v[4 * q + 3], r1, n1)), sc[q], sh[q]);
    }
    stsm4(stg_row + (i >> 3) * BLK + ((((i & 7) + (lane >> 4)) ^ (lane & 7)) << 4), w[0], w[1], w[2], w[3]);
    if ((i & 7) == 6) stage_done(sb, wg, i >> 3, lane);
  }
}
__device__ __forceinline__ uint32_t hmul2(uint32_t a, uint32_t b) { uint32_t r; asm("mul.rn.bf16x2 %0, %1, %2;" : "=r"(r) : "r"(a), "r"(b)); return r; }
__device__ __forceinline__ uint32_t silu_mul2(uint32_t g, uint32_t u) {
  const uint32_t h = hmul2(g, 0x3f003f00u);
  const float h0 = bf_lo(h), h1 = bf_hi(h);
  return hmul2(pack2(fmaf(h0, tanh_fast(h0), h0), fmaf(h1, tanh_fast(h1), h1)), u);
}

__device__ __forceinline__ void gemv_fma(float (&a)[8], uint4 w, float s) {
  a[0] = fmaf(bf_lo(w.x), s, a[0]); a[1] = fmaf(bf_hi(w.x), s, a[1]); a[2] = fmaf(bf_lo(w.y), s, a[2]); a[3] = fmaf(bf_hi(w.y), s, a[3]);
  a[4] = fmaf(bf_lo(w.z), s, a[4]); a[5] = fmaf(bf_hi(w.z), s, a[5]); a[6] = fmaf(bf_lo(w.w), s, a[6]); a[7] = fmaf(bf_hi(w.w), s, a[7]);
}
__device__ __forceinline__ float silu_c(float v) { return bf_round(__fdividef(v, 1.f + __expf(-v))); }
__device__ __forceinline__ float mod_gather(const uint2* p, uint32_t ep) {
  uint2 a, b, c, d; uint32_t n = 0;
  while (true) {
    a = ld_rlx2(p); b = ld_rlx2(p + 128); c = ld_rlx2(p + 256); d = ld_rlx2(p + 384);
    if (a.y == ep && b.y == ep && c.y == ep && d.y == ep) break;
    SPIN_GUARD(n);
  }
  return (__uint_as_float(a.x) + __uint_as_float(b.x)) + (__uint_as_float(c.x) + __uint_as_float(d.x));
}
__device__ __forceinline__ void mod_store(uint32_t sb, int sec, int col, float v) {
  v = bf_round(v);
  if (sec == 1 || sec == 4) v += 1.f;
  sts16(sb + MISC + MODV + sec * 256 + (((col >> 1) & 3) * 16 + (col >> 3)) * 4 + (col & 1) * 2, __float2bfloat16_rn(v));
}

__global__ void __cluster_dims__(2, 1, 1) __launch_bounds__(384, 1)
fused_kernel(const bf16* __restrict__ cvec, const bf16* __restrict__ wmod, Scratch* gs, int by_sm, const __grid_constant__ Maps maps) {
  extern __shared__ __align__(1024) uint8_t smem_raw[];
  const uint32_t sb = smem_u32(smem_raw);
  const int warp = __shfl_sync(~0u, threadIdx.x >> 5, 0), lane = threadIdx.x & 31;
  const int rank = blockIdx.x & 1;
  uint32_t sm; asm("mov.u32 %0, %%smid;" : "=r"(sm));
  const int t = sm >> 1, v = t < 32 ? t : t < 60 ? t + 1 + (((t - 32) * 37) >> 8) : (t - 58) * 8;
  const int cid = !by_sm ? (blockIdx.x >> 1) - 2 : (t & ~1) == 60 ? t - 62 : (v & 1) * 32 + ((v >> 1) & 31);
  const bool extra = cid < 0;
  const int bid = cid * 2 + rank;
  const int m = cid >> 2, j = (cid & 3) * 2 + rank;
  const uint32_t bar = sb + MISC;

  if (warp >= 8) {
    asm volatile("setmaxnreg.dec.sync.aligned.u32 40;");
    if (extra) {
      if (warp == 8) {
        if (lane == 0) { for (int s = 0; s < 6; s++) { mbar_init(bar + B_FULL6 + s * 8, 1); mbar_init(bar + B_EMPTY6 + s * 8, 8); } fence_async_smem(); }
        __syncwarp();
        asm volatile("bar.arrive 2, 288;" ::: "memory");
        __nanosleep(XSLEEP);
#pragma unroll 1
        for (int it = 0, s = 0, par = 1; it < 64; it++) {
          mbar_wait(bar + B_EMPTY6 + s * 8, par);
          if (elect()) { mbar_expect_tx(bar + B_FULL6 + s * 8, 32768); tma_3d(sb + s * 32768, &maps.wmod, bar + B_FULL6 + s * 8, 0, (it & 15) * 64, 12 + (it >> 4) * 4 + bid); }
          if (++s == 6) { s = 0; par ^= 1; }
        }
      }
    } else if (warp < 10) {
      uint32_t s6 = 0, p6 = 1;
      auto next6 = [&]() { if (++s6 == 6) { s6 = 0; p6 ^= 1; } };
      auto drained4 = [&](int q, int late) { if (q < 5) mbar_wait(bar + B_EMPTY4 + (((late ? 0x10332 : 0x32110) >> (4 * q)) & 3) * 8, 1); };
      auto drained6 = [&](int q) { if (q < 3) mbar_wait(bar + B_EMPTY6 + ((0x154 >> (4 * q)) & 7) * 8, q >> 1); };
      auto skip6 = [&]() { mbar_wait(bar + B_EMPTY6 + s6 * 8, p6); if (elect()) mbar_arrive(bar + B_FULL6 + s6 * 8); next6(); };
      if (warp == 8) {
        const uint32_t t_start = clock();
        if (lane == 0) {
          if (sb & 1023) bail();
          for (int b = 0; b < 2; b++) mbar_init(bar + B_X + b * 8, 1);
          for (int s = 0; s < 4; s++) { mbar_init(bar + B_FULL4 + s * 8, 2); mbar_init(bar + B_EMPTY4 + s * 8, 16); }
          for (int s = 0; s < 6; s++) { mbar_init(bar + B_FULL6 + s * 8, 2); mbar_init(bar + B_EMPTY6 + s * 8, 16); }
          for (int b = 0; b < 2; b++) { mbar_init(bar + B_RDY + b * 8, 8); mbar_init(bar + B_FREE + b * 8, 1); mbar_init(bar + B_HH + b * 8, 1); }
          mbar_init(bar + B_MOD, 1); mbar_init(bar + B_LAG, 4); mbar_init(bar + B_HALO, 2); mbar_init(bar + B_ALL, 1); mbar_init(bar + B_HH2, 1);
          asm volatile("st.shared.u32 [%0], 0;" :: "r"(bar + ZERO) : "memory");
          asm volatile("fence.mbarrier_init.release.cluster;" ::: "memory");
          fence_async_smem();
        }
        __syncwarp();
        cl_arrive_relaxed();
        auto wide = [&](int s, int par, const CUtensorMap* m0, int a0, const CUtensorMap* m1, int a1, int kb) {
          const uint32_t full = bar + B_FULL4 + s * 8, d = sb + s * 49152 + BLK;
          mbar_wait(full + 32, par);
          if (elect()) { mbar_expect_tx(full, 2 * BLK); tma_3d(d, m0, full, 0, kb * 64, a0); tma_3d(d + BLK, m1, full, 0, kb * 64, a1); }
        };
        auto narrow = [&](const CUtensorMap* m0, int kb) {
          const uint32_t full = bar + B_FULL6 + s6 * 8;
          mbar_wait(full + 48, p6);
          if (elect()) { mbar_expect_tx(full, BLK); tma_3d(sb + s6 * 32768 + BLK, m0, full, 0, kb * 64, 2 * j); }
          next6();
        };
#pragma unroll 1
        for (int it = 0; it < 16; it++) {
          if (it == 0) {
            while ((uint32_t)clock() - t_start < XDELAY) {}
            if (elect()) for (int b = 0; b < 2; b++) { mbar_expect_tx(bar + B_X + b * 8, BLK); tma_3d(sb + STG + b * BLK, &maps.x, bar + B_X + b * 8, j * 128 + b * 64, m * 64, 0); }
            mbar_wait(bar + B_X + 8, 0);
          }
          wide(it & 3, ~(it >> 2) & 1, &maps.wqkv, 16 + 2 * j, &maps.wqkv, 32 + 2 * j, own_order(it, j));
        }
#pragma unroll 1
        for (int it = 0; it < 16; it++) { drained4(it, 0); narrow(&maps.wqkv, it); }
#pragma unroll 1
        for (int it = 0; it < 16; it++) narrow(&maps.wo, own_order(it, j));
        skip6();
#pragma unroll 1
        for (int it = 0; it < 48; it++) {
          const int s = (it + 2) & 3, par = ~(it >> 2) & 1;
          drained6(it);
          wide(s, par, &maps.w1, (it & 48) + 2 * j, &maps.w3, (it & 48) + 2 * j, it < 16 ? own_order(it, j) : it & 15);
          if (it >= 44) {
            if (it == 44) { mbar_wait(bar + B_FREE, 0); mbar_wait(bar + B_FREE + 8, 0); if (elect()) mbar_expect_tx(bar + B_X, 2 * BLK); }
            if (elect()) bulk_ld(sb + STG + (it - 44) * HALF, gs->x1 + bid * 2048 + (it - 44) * 512, HALF, bar + B_X);
          }
        }
#pragma unroll 1
        for (int it = 0; it < 16; it++) {
          const uint32_t full = bar + B_FULL6 + s6 * 8, d = sb + s6 * 32768 + BLK;
          drained4(it, 1);
          mbar_wait(full + 48, p6);
          if (elect()) { mbar_expect_tx(full, BLK); tma_3d(d, &maps.w1s, full, 0, it * 64, 48 + j); tma_3d(d + HALF, &maps.w3s, full, 0, it * 64, 48 + j); }
          next6();
        }
#pragma unroll 1
        for (int it = 0; it < 56; it++) narrow(&maps.w2, it);
      } else {
        if (lane < 9) prefetch_map(&maps.x + lane);
        const uint32_t ep = gs->epoch[bid + 4] + 1;
        cl_arrive_relaxed(); cl_wait();
        auto plain = [&](uint32_t full, uint32_t empty, int par, uint32_t slot, const uint4* blk) {
          mbar_wait(empty, par);
          if (elect()) { mbar_expect_tx(full, BLK); bulk_ld_mc(slot + rank * HALF, blk + rank * 512, HALF, full); }
        };
        auto plain6 = [&](const uint4* blk) { plain(bar + B_FULL6 + s6 * 8, bar + B_EMPTY6 + s6 * 8, p6, sb + s6 * 32768, blk); next6(); };
        uint32_t ready = 0;
        auto poll = [&](int e) { ready = __ballot_sync(~0u, ld_acquire(gs->flag + m * 128 + e * 16 + (lane & 15)) == ep); };
        auto need = [&](int e, uint32_t mask) {
          if ((ready & mask) != mask) {
            uint32_t n = 0;
            do { poll(e); SPIN_GUARD(n); } while ((ready & mask) != mask);
            fence_async_global();
          }
        };
        auto fresh = [&](int e, int it, uint32_t full, uint32_t empty, int par, uint32_t slot, uint4* src) {
          if (it >= 4) {
            const int kb = own_order(it, j);
            if (it < 10) need(e, 1u << kb); else if (it == 10) mbar_wait(bar + B_ALL, e & 1);
            plain(full, empty, par, slot, src + kb * 1024);
          } else {
            if (it == 0) { poll(e); ready = 0; }
            mbar_wait(empty, par);
            if (it < 2) { if (elect()) mbar_arrive(full); }
            else {
              const int b = it > 2;
              const uint32_t to_peer = mapa(sb, rank ^ 1) - sb;
              if (elect()) mbar_expect_tx(full, BLK);
              const bool push = e != 1;
              mbar_wait(bar + (b ? (push ? B_RDY + 8 : B_FREE + 8) : B_RDY), e & 1);
              if (b == 0) TR(e == 0 ? 24 : e == 2 ? 30 : 44);
              if (elect()) {
                if (b == 0) {
                  bulk_st(src + 2 * j * 1024, sb + STG, BLK);
                  bulk_commit();
                  bulk_wait_all();
                  mbar_arrive(bar + B_FREE);
                }
                if (b && push) bulk_push(slot + to_peer, sb + STG + BLK, BLK, full + to_peer);
                else {
                  fence_async_global();
                  bulk_ld(slot + to_peer, src + (2 * j + b) * 1024, BLK, full + to_peer);
                }
              }
              __syncwarp();
            }
          }
          if (it == 4) TR(e == 0 ? 28 : e == 1 ? 46 : 34);
        };
#pragma unroll 1
        for (int ph = 0; ph < 2; ph++) {
          uint4* h = gs->h + m * 16384;
#pragma unroll 1
          for (int it = 0; it < 16; it++) {
            const int s = (it + 2 * ph) & 3;
            if (ph) drained6(it);
            fresh(2 * ph, it, bar + B_FULL4 + s * 8, bar + B_EMPTY4 + s * 8, ~(it >> 2) & 1, sb + s * 49152, h);
          }
          if (ph) {
#pragma unroll 1
            for (int it = 16; it < 48; it++) {
              const int s = (it + 2) & 3;
              const uint32_t full = bar + B_FULL4 + s * 8;
              plain(full, full + 32, ~(it >> 2) & 1, sb + s * 49152, h + (it & 15) * 1024);
            }
          }
#pragma unroll 1
          for (int it = 0; it < 16; it++) { drained4(it, ph); plain6(h + it * 1024); }
          if (!ph) {
#pragma unroll 1
            for (int it = 0; it < 16; it++) { fresh(1, it, bar + B_FULL6 + s6 * 8, bar + B_EMPTY6 + s6 * 8, p6, sb + s6 * 32768, gs->o + m * 16384); next6(); }
            skip6();
          }
        }
#pragma unroll 1
        for (int it = 0; it < 56; it++) {
          if (it == 0 || it == 32 || it == 48) mbar_wait(bar + (it == 48 ? B_HH2 : B_HH + (it >> 2)), 0);
          plain6(gs->hh + m * 57344 + it * 1024);
        }
      }
    } else {
      const int b = warp - 10;
      const uint32_t ep = gs->epoch[bid + 4] + 1;
      const uint32_t stg = sb + STG + b * BLK;
      cl_arrive_relaxed(); cl_wait();
      auto all_there = [&](int u, uint32_t done) {
        const uint32_t* fl = gs->flag + u;
        uint32_t n = 0;
        while (!__all_sync(~0u, ld_acquire(fl) == ep)) { __nanosleep(100); SPIN_GUARD(n); }
        fence_async_global();
        if (lane == 0) mbar_arrive(done);
      };
      auto fetch_mod = [&](int sec) {
        const uint4* p = (const uint4*)(gs->modv + (sec - 2) * 1024 + j * 128) + lane;
        uint4 v0, v1; uint32_t n = 0;
        while (true) {
          v0 = ld_rlx4(p); v1 = ld_rlx4(p + 32);
          if (v0.y == ep && v0.w == ep && v1.y == ep && v1.w == ep) break;
          SPIN_GUARD(n);
        }
        mod_store(sb, sec, 2 * lane, __uint_as_float(v0.x)); mod_store(sb, sec, 2 * lane + 1, __uint_as_float(v0.z));
        mod_store(sb, sec, 64 + 2 * lane, __uint_as_float(v1.x)); mod_store(sb, sec, 65 + 2 * lane, __uint_as_float(v1.z));
        __syncwarp();
      };
#pragma unroll 1
      for (int e = 0; e < 7 - b; e++) {
        if (lane == 0) {
          if (e < 3) {
            mbar_wait(bar + B_FREE, e & 1);
            if (b) {
              const uint32_t t0 = clock();
              while ((uint32_t)clock() - t0 < (e != 1 ? B1P : B1D)) {}
              mbar_wait(bar + B_RDY + 8, e & 1);
              bulk_st((e == 1 ? gs->o : gs->h) + m * 16384 + (2 * j + 1) * 1024, stg, BLK);
              bulk_commit();
              bulk_wait_all();
              mbar_arrive(bar + B_FREE + 8);
              TR(53 + e);
            }
            st_release(gs->flag + m * 128 + e * 16 + 2 * j + b, ep);
            TR((e == 0 ? 26 : e == 2 ? 32 : 42) + b);
          } else {
            const int kb = (e < 6 ? 2 * (8 * (e - 3) + j) : 48 + j) + b;
            mbar_wait(bar + B_RDY + b * 8, e & 1);
#pragma unroll 1
            for (int q = 0; q < NPIECE; q++) { if (q) __nanosleep(PSLEEP); bulk_st(gs->hh + m * 57344 + kb * 1024 + q * (1024 / NPIECE), stg + q * (BLK / NPIECE), BLK / NPIECE); }
            bulk_commit();
            bulk_wait_all();
            mbar_arrive(bar + B_FREE + b * 8);
            st_release(gs->flag + m * 128 + U_HH + kb, ep);
          }
        }
        __syncwarp();
        if (e < 3 && b) all_there(m * 128 + e * 16 + (lane & 15), bar + B_ALL);
        if (e == 4 && b) all_there(m * 128 + U_HH + lane, bar + B_HH);
        if (!b && (e == 1 || e == 2)) {
#pragma unroll 1
          for (int sec = e == 1 ? 2 : 5; sec < 4 + e; sec++) fetch_mod(sec);
          if (e == 1) { if (lane == 0) mbar_arrive(bar + B_MOD); TR(50); }
        }
        if (e == 0) {
          mbar_wait(bar + B_EMPTY6 + 24, 0);
          if (HSLEEP) __nanosleep(HSLEEP);
#pragma unroll 1
          for (int w = 0; w < 4; w++) {
            const uint4* hp = gs->halo + ((m * 8 + j) * 2 + (w & 1)) * 512 + b * 256 + (w >> 1) * 128 + lane;
            uint4 q[4] = {}; uint32_t n = 0;
            while (m > 0) {
              bool ok = true;
#pragma unroll
              for (int i = 0; i < 4; i++) q[i] = ld_rlx4(hp + i * 32);
#pragma unroll
              for (int i = 0; i < 4; i++) ok = ok && q[i].y == ep && q[i].w == ep;
              if (ok) break;
              SPIN_GUARD(n);
            }
#pragma unroll
            for (int i = 0; i < 2; i++) sts128(stg + lane * 16 + (w & 1) * HALF + (w >> 1) * 1024 + i * 512, q[2 * i].x, q[2 * i + 1].x, q[2 * i].z, q[2 * i + 1].z);
          }
          __syncwarp();
          if (lane == 0) mbar_arrive(bar + B_HALO);
          if (b == 0) TR(52);
        }
      }
      if (b) { all_there(m * 128 + U_HH + 32 + (lane & 15), bar + B_HH + 8); all_there(m * 128 + U_HH + 48 + (lane & 7), bar + B_HH2); }
    }
  } else {
    const int wg = warp >> 2, wq = warp & 3, tid = threadIdx.x;
    const int g = lane >> 2, c = lane & 3;
    const int sec0 = (m >> 1) & 1, hf0 = m & 1, ks0 = (m >> 2) & 3;
    uint4 wv[8];
    uint32_t ep0; uint16_t cv_;
    asm volatile("ld.global.nc.u16 %0, [%1];" : "=h"(cv_) : "l"(cvec + ks0 * 256 + warp * 32 + lane));
    asm volatile("ld.global.u32 %0, [%1];" : "=r"(ep0) : "l"(gs->epoch + bid + 4));
    if (!extra) {
      const bf16* wp = wmod + (size_t)(ks0 * 256 + warp * 32 + (lane >> 3)) * 6144 + sec0 * 1024 + j * 128 + hf0 * 64 + (lane & 7) * 8;
#pragma unroll
      for (int i = 0; i < 8; i++) wv[i] = ldg_nc(wp + (size_t)i * 4 * 6144);
    }
    asm volatile("setmaxnreg.inc.sync.aligned.u32 232;" ::: "memory");
    if (__builtin_expect(extra, 0)) {
      const uint32_t ep = ep0 + 1;
      float sv[4];
#pragma unroll
      for (int p = 0; p < 4; p++) sv[p] = silu_c(__bfloat162float(cvec[64 * (4 * p + (lane >> 3)) + 8 * warp + (lane & 7)]));
      named_bar(2, 288);
      int s = 0, par = 0;
#pragma unroll 1
      for (int sec = 0; sec < 4; sec++) {
        float a[8] = {0, 0, 0, 0, 0, 0, 0, 0};
#pragma unroll 1
        for (int it = 0; it < 16; it++) {
          const float sc = it < 4 ? sv[0] : it < 8 ? sv[1] : it < 12 ? sv[2] : sv[3];
          mbar_wait(bar + B_FULL6 + s * 8, par);
          uint4 w[8];
#pragma unroll
          for (int i = 0; i < 8; i++) w[i] = lds128(sb + s * 32768 + (warp * 8 + i) * 512 + lane * 16);
#pragma unroll
          for (int i = 0; i < 8; i++) gemv_fma(a, w[i], __shfl_sync(~0u, sc, (it & 3) * 8 + i));
          if (lane == 0) mbar_arrive(bar + B_EMPTY6 + s * 8);
          if (++s == 6) { s = 0; par ^= 1; }
        }
        const uint32_t red = sb + STG + sec * 8192;
        sts128(red + warp * 1024 + lane * 32, __float_as_uint(a[0]), __float_as_uint(a[1]), __float_as_uint(a[2]), __float_as_uint(a[3]));
        sts128(red + warp * 1024 + lane * 32 + 16, __float_as_uint(a[4]), __float_as_uint(a[5]), __float_as_uint(a[6]), __float_as_uint(a[7]));
        named_bar(1, 256);
        float t = 0;
#pragma unroll
        for (int q = 0; q < 8; q++) t += lds32f(red + q * 1024 + tid * 4);
        st_rlx2(gs->modv + sec * 1024 + (bid + 4) * 256 + tid, __float_as_uint(t), ep);
      }
      if (tid == 0) gs->epoch[bid + 4] = ep;
      return;
    }
    if (warp == 0) TR(0);
    const int row0 = wg * 64 + wq * 16 + g;
    if (c < 2) st_rlx4(gs->stat + m * 1024 + j * 128 + row0 + c * 8, 0, 0, 0, 0);
    if (tid < 64) st_rlx2(gs->modp + ((j * 2 + sec0) * 4 + ks0) * 128 + hf0 * 64 + tid, 0, 0);
    cl_arrive_relaxed(); cl_wait();
    uint32_t ep;
    asm volatile("add.u32 %0, %1, 1;" : "=r"(ep) : "r"(ep0) : "memory");
    const float sc_ = silu_c(__uint_as_float((uint32_t)cv_ << 16));
    const uint32_t rel = mapa(bar, (lane & 1) ^ rank);
    const uint32_t stg_row = sb + STG + (wg * 64 + wq * 16 + (lane & 15)) * 128;
    const uint32_t fre = bar + B_FREE;
    Ring r4{0, 0, 0}, r6{0, 0, 0};
    auto none = [](auto) {};
    uint32_t xk[32];
    {
      float a[8] = {0, 0, 0, 0, 0, 0, 0, 0};
#pragma unroll
      for (int i = 0; i < 8; i++) gemv_fma(a, wv[i], __shfl_sync(~0u, sc_, i * 4 + (lane >> 3)));
#pragma unroll
      for (int i = 0; i < 8; i++) { a[i] += __shfl_xor_sync(~0u, a[i], 8); a[i] += __shfl_xor_sync(~0u, a[i], 16); }
      if (lane < 8) {
        sts128(sb + RED_OFF + warp * 256 + lane * 32, __float_as_uint(a[0]), __float_as_uint(a[1]), __float_as_uint(a[2]), __float_as_uint(a[3]));
        sts128(sb + RED_OFF + warp * 256 + lane * 32 + 16, __float_as_uint(a[4]), __float_as_uint(a[5]), __float_as_uint(a[6]), __float_as_uint(a[7]));
      }
      named_bar(1, 256);
      if (tid < 64) {
        float s = 0;
#pragma unroll
        for (int w = 0; w < 8; w++) s += lds32f(sb + RED_OFF + w * 256 + tid * 4);
        st_rlx2(gs->modp + ((j * 2 + sec0) * 4 + ks0) * 128 + hf0 * 64 + tid, __float_as_uint(s), ep);
      }
      if (warp == 0) TR(1);
      float v[64];
      mbar_wait(bar + B_X, 0); mbar_wait(bar + B_X + 8, 0);
#pragma unroll
      for (int i = 0; i < 16; i += 2) {
        uint32_t w0, w1, w2, w3;
        ldsm4(stg_row + (i >> 3) * BLK + ((((i & 7) + (lane >> 4)) ^ (lane & 7)) << 4), w0, w1, w2, w3);
        xk[2 * i] = w0; xk[2 * i + 1] = w1; xk[2 * i + 2] = w2; xk[2 * i + 3] = w3;
        v[4 * i] = bf_lo(w0); v[4 * i + 1] = bf_hi(w0); v[4 * i + 2] = bf_lo(w1); v[4 * i + 3] = bf_hi(w1);
        v[4 * i + 4] = bf_lo(w2); v[4 * i + 5] = bf_hi(w2); v[4 * i + 6] = bf_lo(w3); v[4 * i + 7] = bf_hi(w3);
      }
      ln_publish(v, gs->stat + m * 1024, j, row0, lane, ep);
      if (warp == 0) TR(2);
      mod_store(sb, tid >> 7, tid & 127, mod_gather(gs->modp + (j * 2 + (tid >> 7)) * 512 + (tid & 127), ep));
      named_bar(1, 256);
      if (warp == 0) TR(3);
      ln_apply(v, gs->stat + m * 1024, row0, ep, sb, 0, 1, stg_row, wg, lane);
      named_bar(2 + wg, 128);
    }
    if (warp == 0) TR(4);
    {
      uint32_t kf[32], vf[32], pv[32];
      const bool first = wq == 0 && m == 0;
      const uint32_t xa = sb + STG + wg * HALF + wq * 2048 + lane * 16;
      {
        float acc[128];
        mainloop<256, 4, 0>(acc, 16, true, r4, sb, wg, lane, rel, STEP0 + 0, none, none, [&] {
          mbar_wait(fre + 8, 0);
          if (c < 2) st_rlx4(gs->stat + (16 + m) * 1024 + j * 128 + row0 + c * 8, 0, 0, 0, 0);
        });
        if (warp == 0) TR(5);
#pragma unroll
        for (int i = 0; i < 32; i++) { kf[i] = pack2(acc[2 * i], acc[2 * i + 1]); vf[i] = pack2(acc[64 + 2 * i], acc[65 + 2 * i]); }
      }
      if (warp == 0) TR(6);
      float acc[64];
      constexpr int QP = 2;
      mainloop<128, 6, 8 / QP>(acc, 16, false, r6, sb, wg, lane, rel, STEP0 + 16, [&](auto ic) {
        constexpr int q = (ic.v - 1) * QP;
#pragma unroll
        for (int i = 4 * q; i < 4 * (q + QP); i++) vf[i] = movm(vf[i]);
        if (wq == 3) {
          if (m < 15) {
            uint4* hp = gs->halo + (((m + 1) * 8 + j) * 2 + wg) * 512 + lane;
#pragma unroll
            for (int i = 2 * q; i < 2 * (q + QP); i++) st_rlx4(hp + i * 32, kf[2 * i + 1], ep, vf[2 * i + 1], ep);
          }
        } else {
#pragma unroll
          for (int i = q; i < q + QP; i++) sts128(xa + 2048 + (i >> 2) * BLK + (i & 3) * 512, kf[4 * i + 1], kf[4 * i + 3], vf[4 * i + 1], vf[4 * i + 3]);
        }
      }, none, [&] {
        named_bar(2 + wg, 128);
        if (wq == 0) mbar_wait(bar + B_HALO, 0);
#pragma unroll
        for (int i = 0; i < 8; i++) {
          uint4 q = lds128(xa + (i >> 2) * BLK + (i & 3) * 512);
          pv[4 * i] = q.x; pv[4 * i + 1] = q.y; pv[4 * i + 2] = q.z; pv[4 * i + 3] = q.w;
        }
        __syncwarp();
      });
      if (warp == 0) TR(7);
      int gz = g;
#pragma unroll
      for (int b = 0; b < 2; b++) {
        const bool up0 = 2 * c > gz, up1 = 2 * c + 1 > gz;
        const uint32_t mup = (up0 ? 0xffffu : 0u) | (up1 ? 0xffff0000u : 0u);
        float l[2][4], mx[4];
#pragma unroll
        for (int h = 0; h < 2; h++) {
          uint32_t q[8];
          const int k = 16 * b + 8 * h;
#pragma unroll
          for (int i = 0; i < 8; i++) q[i] = pack2(acc[2 * k + 2 * i], acc[2 * k + 2 * i + 1]);
          float s0[4], s1[4], s2[4];
          mma16z(s0, q[0], q[1], q[2], q[3], pv[k], pv[k + 1]); mma16z(s1, q[0], q[1], q[2], q[3], kf[k], kf[k + 2]); mma16z(s2, q[0], q[1], q[2], q[3], kf[k + 1], kf[k + 3]);
          mma16(s0, q[4], q[5], q[6], q[7], pv[k + 4], pv[k + 5]); mma16(s1, q[4], q[5], q[6], q[7], kf[k + 4], kf[k + 6]); mma16(s2, q[4], q[5], q[6], q[7], kf[k + 5], kf[k + 7]);
          if (first) { s0[0] = -INFINITY; s0[1] = -INFINITY; }
          l[h][0] = up0 ? s0[0] : s1[0]; l[h][1] = up1 ? s0[1] : s1[1]; l[h][2] = up0 ? s1[2] : s2[2]; l[h][3] = up1 ? s1[3] : s2[3];
          mx[2 * h] = fmaxf(l[h][0], l[h][1]); mx[2 * h + 1] = fmaxf(l[h][2], l[h][3]);
        }
#pragma unroll
        for (int o = 1; o < 4; o <<= 1) {
#pragma unroll
          for (int h = 0; h < 4; h++) mx[h] = fmaxf(mx[h], __shfl_xor_sync(~0u, mx[h], o));
        }
#pragma unroll
        for (int h = 0; h < 2; h++) {
          const float n0 = -mx[2 * h] * SCL, n1 = -mx[2 * h + 1] * SCL;
          const uint32_t pa = pack2(ex2(fmaf(l[h][0], SCL, n0)), ex2(fmaf(l[h][1], SCL, n0))), pb = pack2(ex2(fmaf(l[h][2], SCL, n1)), ex2(fmaf(l[h][3], SCL, n1)));
          float sm[4];
          mma8z(sm, pa, pb, 0x3f803f80u);
          const float ia = rcp(sm[0]), ib = rcp(sm[2]);
#pragma unroll
          for (int i = 8 * b + 4 * h; i < 8 * b + 4 * h + 4; i += 2) {
            uint32_t of[4];
#pragma unroll
            for (int d = 0; d < 2; d++) {
              float o[4];
              mma16z(o, pa & ~mup, pb & mup, 0u, pb & ~mup, vf[2 * (i + d)], vf[2 * (i + d) + 1]);
              mma8(o, pa & mup, 0u, pv[2 * i + 2 + d]);
              of[2 * d] = pack2(o[0] * ia, o[1] * ia); of[2 * d + 1] = pack2(o[2] * ib, o[3] * ib);
            }
            stsm4(stg_row + b * BLK + ((((i & 7) + (lane >> 4)) ^ (lane & 7)) << 4), of[0], of[1], of[2], of[3]);
          }
        }
        stage_done(sb, wg, b, lane);
        if (b == 0) gz += __float_as_uint(lds32f(bar + ZERO));
      }
      named_bar(1, 256);
      if (warp == 0) TR(8);
    }
    uint32_t pk[64];
    {
      float acc[64];
      mainloop<128, 6, 0>(acc, 16, true, r6, sb, wg, lane, rel, STEP0 + 32, none, none, [&] {
        mbar_wait(bar + B_MOD, 0); mbar_wait(fre + 8, 1);
        load_vec(pk + 32, sb, 2, 0, lane); load_vec(pk + 40, sb, 2, 1, lane);
#pragma unroll
        for (int i = 0; i < 32; i++) { pk[i] = xk[i]; asm volatile("" : "+r"(pk[i])); }
      });
      if (warp == 0) TR(9);
#pragma unroll
      for (int i = 0; i < 32; i++) {
        acc[2 * i] = fmaf(acc[2 * i], bf_lo(pk[32 + (i >> 1)]), bf_lo(pk[i]));
        acc[2 * i + 1] = fmaf(acc[2 * i + 1], bf_hi(pk[32 + (i >> 1)]), bf_hi(pk[i]));
      }
      ln_publish(acc, gs->stat + (16 + m) * 1024, j, row0, lane, ep);
      if (warp == 0) TR(36);
      mbar_wait(bar + B_FULL6 + 16, 1);
      if (lane < 2) mbar_arrive_cl(rel + B_EMPTY6 + 16);
      ring_next<6>(r6);
#pragma unroll
      for (int i = 0; i < 32; i++) { pk[i] = pack2(acc[2 * i], acc[2 * i + 1]); pk[32 + i] = 0; }
      ln_apply(acc, gs->stat + (16 + m) * 1024, row0, ep, sb, 3, 4, stg_row, wg, lane);
      named_bar(2 + wg, 128);
      if (warp == 0) TR(11);
    }
    auto swiglu = [&](int q, int uo, int par) {
      if ((q & 3) == 0 && par >= 0) mbar_wait(fre + 2 * q, par);
      uint32_t w[4];
#pragma unroll
      for (int u = 0; u < 4; u++) w[u] = silu_mul2(pk[4 * q + u], pk[uo + 4 * q + u]);
      stsm4(stg_row + (q >> 2) * BLK + ((((2 * q & 7) + (lane >> 4)) ^ (lane & 7)) << 4), w[0], w[1], w[2], w[3]);
    };
    r4.s = r4.wrap = 2;
#pragma unroll 1
    for (int t = 0; t < 3; t++) {
      float acc[128];
      mainloop<256, 4, 5>(acc, 16, t == 0, r4, sb, wg, lane, rel, STEP0 + 48 + 16 * t, [&](auto ic) {
        if (t) {
          if (ic.v == 3 || ic.v == 5) stage_done(sb, wg, ic.v >> 2, lane);
          if (ic.v < 5) { swiglu(2 * ic.v - 2, 32, ~t & 1); swiglu(2 * ic.v - 1, 32, 0); }
        }
      }, [&](int it) {
#pragma unroll
        for (int i = 0; i < 8; i++)
          if (t == 0 && it == 6 + i) gs->x1[bid * 2048 + (i >> 2) * 1024 + warp * 128 + (i & 3) * 32 + lane] = make_uint4(pk[4 * i], pk[4 * i + 1], pk[4 * i + 2], pk[4 * i + 3]);
      }, [&] { if (t == 0) fence_async_global(); else if (t == 2) mbar_wait(bar + B_X, 1); });
      if (warp == 0) TR(12 + 2 * t);
#pragma unroll
      for (int i = 0; i < 64; i++) pk[i] = pack2(acc[2 * i], acc[2 * i + 1]);
      if (warp == 0) TR(13 + 2 * t);
    }
    uint32_t x1[32];
    {
      float acc[64];
      mainloop<128, 6, 12>(acc, 16, false, r6, sb, wg, lane, rel, STEP0 + 96, [&](auto ic) {
        constexpr int b = ic.v > 6, q = ic.v - 6 * b;
        if (q == 1) {
#pragma unroll
          for (int i = 4 * b; i < 4 * b + 4; i++) { const uint4 x = lds128(sb + STG + b * BLK + warp * 2048 + (i & 3) * 512 + lane * 16); x1[4 * i] = x.x; x1[4 * i + 1] = x.y; x1[4 * i + 2] = x.z; x1[4 * i + 3] = x.w; }
          __syncwarp();
        } else if (q < 6) swiglu(4 * b + q - 2, 32, -1);
        else stage_done(sb, wg, b, lane);
      }, none, [] {});
      if (warp == 0) TR(18);
#pragma unroll
      for (int i = 0; i < 32; i++) pk[i] = pack2(acc[2 * i], acc[2 * i + 1]);
      if (warp == 0) TR(19);
    }
    {
      float acc[64];
      mainloop<128, 6, 5>(acc, 56, false, r6, sb, wg, lane, rel, STEP0 + 112, [&](auto ic) {
        if (ic.v == 5) stage_done(sb, wg, 0, lane); else swiglu(ic.v - 1, 16, 1);
      }, none, [&] {
        if (TAILLAG && wg == 0 && lane == 0) mbar_arrive(bar + B_LAG);
        load_vec(pk + 32, sb, 5, 0, lane); load_vec(pk + 40, sb, 5, 1, lane);
        mbar_wait(fre, 0); mbar_wait(fre + 8, 1);
      });
      __syncwarp();
      cl_arrive_relaxed();
      if (warp == 0) TR(20);
#pragma unroll
      for (int i = 0; i < 16; i += 2) {
        uint32_t w[4];
#pragma unroll
        for (int u = 0; u < 4; u++) {
          const int q = 2 * i + u;
          w[u] = pack2(fmaf(acc[2 * q], bf_lo(pk[32 + (q >> 1)]), bf_lo(x1[q])), fmaf(acc[2 * q + 1], bf_hi(pk[32 + (q >> 1)]), bf_hi(x1[q])));
        }
        stsm4(stg_row + (i >> 3) * BLK + ((((i & 7) + (lane >> 4)) ^ (lane & 7)) << 4), w[0], w[1], w[2], w[3]);
        if ((i & 7) == 6) {
          fence_async_smem();
          named_bar(2 + wg, 128);
          if (wq == 0 && elect()) { tma_store_3d(&maps.out, sb + STG + (i >> 3) * BLK + wg * HALF, j * 128 + (i >> 3) * 64, m * 64, wg); bulk_commit(); }
          if (i < 8) x1[16] |= __float_as_uint(lds32f(bar + ZERO));
        }
      }
      if (wq == 0) bulk_wait_read();
      if (wq == 0) TR(40 + wg);
      if (tid == 0) gs->epoch[bid + 4] = ep;
      if (warp == 0) TR(21);
      cl_wait();
    }
  }
}

typedef CUresult (*EncodeFn)(CUtensorMap*, CUtensorMapDataType, cuuint32_t, void*, const cuuint64_t*, const cuuint64_t*, const cuuint32_t*, const cuuint32_t*,
                             CUtensorMapInterleave, CUtensorMapSwizzle, CUtensorMapL2promotion, CUtensorMapFloatOOBfill);

void make_map(EncodeFn fn, CUtensorMap* mp, const void* base, uint64_t d0, uint64_t d1, uint64_t d2, uint64_t s1, uint64_t s2, uint32_t b2, uint32_t b0 = 64) {
  cuuint64_t d[3] = {d0, d1, d2}, s[2] = {s1, s2};
  cuuint32_t b[3] = {b0, 64, b2}, e[3] = {1, 1, 1};
  fn(mp, CU_TENSOR_MAP_DATA_TYPE_BFLOAT16, 3, (void*)base, d, s, b, e, CU_TENSOR_MAP_INTERLEAVE_NONE, b0 == 64 ? CU_TENSOR_MAP_SWIZZLE_128B : CU_TENSOR_MAP_SWIZZLE_NONE,
     CU_TENSOR_MAP_L2_PROMOTION_L2_128B, CU_TENSOR_MAP_FLOAT_OOB_FILL_NONE);
}

__global__ void probe_kernel() {}
int max_clusters(int size) {
  cudaLaunchConfig_t cfg = {};
  cudaLaunchAttribute at;
  at.id = cudaLaunchAttributeClusterDimension; at.val.clusterDim.x = size; at.val.clusterDim.y = 1; at.val.clusterDim.z = 1;
  cfg.gridDim = dim3(size * 66); cfg.blockDim = dim3(384); cfg.dynamicSmemBytes = SMEM_BYTES; cfg.attrs = &at; cfg.numAttrs = 1;
  int n = 0;
  if (cudaOccupancyMaxActiveClusters(&n, probe_kernel, &cfg) != cudaSuccess) { cudaGetLastError(); return 0; }
  return n;
}

}

extern "C" void kernel_launch(void* const* d_in, const int* in_sizes, int n_in, void* d_out, int out_size) {
  static EncodeFn fn = nullptr;
  static int by_sm = 0;
  static Scratch* gs = nullptr;
  if (!fn) {
    void* p = nullptr; cudaDriverEntryPointQueryResult q;
    cudaGetDriverEntryPoint("cuTensorMapEncodeTiled", &p, cudaEnableDefault, &q);
    fn = (EncodeFn)p;
    cudaFuncSetAttribute(fused_kernel, cudaFuncAttributeMaxDynamicSharedMemorySize, SMEM_BYTES);
    int dev = 0, sms = 0;
    cudaGetSymbolAddress((void**)&gs, g_scratch);
    cudaGetDevice(&dev);
    cudaDeviceGetAttribute(&sms, cudaDevAttrMultiProcessorCount, dev);
    cudaFuncSetAttribute(probe_kernel, cudaFuncAttributeMaxDynamicSharedMemorySize, SMEM_BYTES);
    by_sm = BYSM && sms == 132 && max_clusters(2) == 66 && max_clusters(4) == 30 && max_clusters(6) == 17 && max_clusters(8) == 15;
  }
  Maps mp;
  make_map(fn, &mp.x, d_in[0], D_, S_ / 2, 2, 4096, 2048, 2);
  make_map(fn, &mp.out, d_out, D_, S_ / 2, 2, 4096, 2048, 1);
  make_map(fn, &mp.wqkv, d_in[1], 64, D_, 3 * D_ / 64, 3 * D_ * 2, 128, 2);
  make_map(fn, &mp.wo, d_in[2], 64, D_, D_ / 64, D_ * 2, 128, 2);
  make_map(fn, &mp.w1, d_in[4], 64, D_, F_ / 64, F_ * 2, 128, 2);
  make_map(fn, &mp.w3, d_in[5], 64, D_, F_ / 64, F_ * 2, 128, 2);
  make_map(fn, &mp.w1s, d_in[4], 64, D_, F_ / 64, F_ * 2, 128, 1);
  make_map(fn, &mp.w3s, d_in[5], 64, D_, F_ / 64, F_ * 2, 128, 1);
  make_map(fn, &mp.w2, d_in[6], 64, F_, D_ / 64, D_ * 2, 128, 2);
  make_map(fn, &mp.wmod, d_in[8], 256, D_, 24, 6 * D_ * 2, 512, 1, 256);
  fused_kernel<<<132, 384, SMEM_BYTES>>>((const bf16*)d_in[7], (const bf16*)d_in[8], gs, by_sm, mp);
}
```

```cpp
#include <cuda_runtime.h>
#include <cuda_bf16.h>
#include <cuda.h>
#include <stdint.h>

typedef __nv_bfloat16 bf16;

#define NPIECE 4
#define PSLEEP 300
#define XSLEEP 4000
#define XDELAY 2000
#define TAILLAG 5
#define HSLEEP 400
#define B1D 900
#define B1P 3500
#define WOLAG 2
#define B1P2 3200
#define BYSM 1
namespace {

constexpr int S_ = 2048, D_ = 1024, F_ = 3584;
constexpr int BLK = 16384;
constexpr int HALF = 8192;
constexpr int RING = 196608;
constexpr int STG = RING;
constexpr int MISC = RING + 2 * BLK;
constexpr int SMEM_BYTES = MISC + 3072;
constexpr int B_FULL4 = 0, B_EMPTY4 = 32, B_FULL6 = 64, B_EMPTY6 = 112, B_RDY = 160, B_FREE = 176, B_LAG = 192, B_X = 208, B_MOD = 224, B_HALO = 232, B_HH = 256, B_ALL = 272, B_HH2 = 288, ZERO = 296;
constexpr int MODV = 512;
constexpr int RED_OFF = 0;
constexpr float SCL = 0.17677669529663687f * 1.4426950408889634f;
constexpr int U_HH = 64;

struct Maps { CUtensorMap x, out, wqkv, wo, w1, w3, w1s, w3s, w2, wmod; };

struct Scratch {
  uint4 h[16 * 16 * 1024];
  uint4 o[16 * 16 * 1024];
  uint4 hh[16 * 56 * 1024];
  uint4 x1[128 * 8 * 256];
  uint4 stat[2 * 16 * 8 * 128];
  uint4 halo[16 * 8 * 2 * 512];
  uint2 modp[8 * 2 * 4 * 128];
  uint2 modv[4 * 1024];
  uint32_t flag[16 * 128];
  uint32_t epoch[132];
};
__device__ __align__(1024) Scratch g_scratch;
#define TR(i)
#define TRS(i)
#define STEP0 gs->flag
#define TRW(i) (void)step0

__device__ __forceinline__ void bail() { asm volatile("st.global.u32 [%0], %1;" :: "l"(0ull), "r"(0) : "memory"); }
__device__ __forceinline__ uint32_t smem_u32(const void* p) { return (uint32_t)__cvta_generic_to_shared(p); }
__device__ __forceinline__ void mbar_init(uint32_t bar, uint32_t cnt) { asm volatile("mbarrier.init.shared::cta.b64 [%0], %1;" :: "r"(bar), "r"(cnt) : "memory"); }
__device__ __forceinline__ void mbar_expect_tx(uint32_t bar, uint32_t bytes) { asm volatile("mbarrier.arrive.expect_tx.shared::cta.b64 _, [%0], %1;" :: "r"(bar), "r"(bytes) : "memory"); }
__device__ __forceinline__ void mbar_arrive(uint32_t bar) { asm volatile("mbarrier.arrive.shared::cta.b64 _, [%0];" :: "r"(bar) : "memory"); }
__device__ __forceinline__ void mbar_arrive_cl(uint32_t cl_addr) { asm volatile("mbarrier.arrive.shared::cluster.b64 _, [%0];" :: "r"(cl_addr) : "memory"); }
__device__ __forceinline__ uint32_t mapa(uint32_t addr, uint32_t cta) { uint32_t r; asm("mapa.shared::cluster.u32 %0, %1, %2;" : "=r"(r) : "r"(addr), "r"(cta)); return r; }
__device__ __forceinline__ void mbar_wait(uint32_t bar, uint32_t parity) {
  asm volatile("{\n.reg .pred p;\n.reg .b32 n;\n.reg .b64 z;\nmov.b32 n, 0;\nmov.b64 z, 0;\n"
               "W: add.u32 n, n, 1;\nsetp.gt.u32 p, n, 0x400000;\n@p st.global.u32 [z], n;\n"
               "mbarrier.try_wait.parity.shared::cta.b64 p, [%0], %1;\n@!p bra W;\n}" :: "r"(bar), "r"(parity) : "memory");
}
__device__ __forceinline__ void tma_3d(uint32_t dst, const CUtensorMap* m, uint32_t bar, int c0, int c1, int c2) {
  asm volatile("cp.async.bulk.tensor.3d.shared::cluster.global.mbarrier::complete_tx::bytes [%0], [%1, {%3, %4, %5}], [%2];" :: "r"(dst), "l"(m), "r"(bar), "r"(c0), "r"(c1), "r"(c2) : "memory");
}
__device__ __forceinline__ void tma_store_3d(const CUtensorMap* m, uint32_t src, int c0, int c1, int c2) {
  asm volatile("cp.async.bulk.tensor.3d.global.shared::cta.bulk_group [%0, {%2, %3, %4}], [%1];" :: "l"(m), "r"(src), "r"(c0), "r"(c1), "r"(c2) : "memory");
}
__device__ __forceinline__ void bulk_ld(uint32_t dst, const void* src, uint32_t bytes, uint32_t bar) {
  asm volatile("cp.async.bulk.shared::cluster.global.mbarrier::complete_tx::bytes [%0], [%1], %2, [%3];" :: "r"(dst), "l"(src), "r"(bytes), "r"(bar) : "memory");
}
__device__ __forceinline__ void bulk_ld_mc(uint32_t dst, const void* src, uint32_t bytes, uint32_t bar) {
  asm volatile("cp.async.bulk.shared::cluster.global.mbarrier::complete_tx::bytes.multicast::cluster [%0], [%1], %2, [%3], %4;" :: "r"(dst), "l"(src), "r"(bytes), "r"(bar), "h"((uint16_t)3) : "memory");
}
__device__ __forceinline__ void bulk_push(uint32_t dst_cl, uint32_t src, uint32_t bytes, uint32_t bar_cl) {
  asm volatile("cp.async.bulk.shared::cluster.shared::cta.mbarrier::complete_tx::bytes [%0], [%1], %2, [%3];" :: "r"(dst_cl), "r"(src), "r"(bytes), "r"(bar_cl) : "memory");
}
__device__ __forceinline__ void bulk_st(void* dst, uint32_t src, uint32_t bytes) {
  asm volatile("cp.async.bulk.global.shared::cta.bulk_group [%0], [%1], %2;" :: "l"(dst), "r"(src), "r"(bytes) : "memory");
}
__device__ __forceinline__ void bulk_commit() { asm volatile("cp.async.bulk.commit_group;" ::: "memory"); }
__device__ __forceinline__ void bulk_wait_read() { asm volatile("cp.async.bulk.wait_group.read 0;" ::: "memory"); }
__device__ __forceinline__ void bulk_wait_all() { asm volatile("cp.async.bulk.wait_group 0;" ::: "memory"); }
__device__ __forceinline__ void fence_async_global() { asm volatile("fence.proxy.async.global;" ::: "memory"); }
__device__ __forceinline__ void fence_async_smem() { asm volatile("fence.proxy.async.shared::cta;" ::: "memory"); }
__device__ __forceinline__ void wg_arrive() { asm volatile("wgmma.fence.sync.aligned;" ::: "memory"); }
__device__ __forceinline__ void wg_commit() { asm volatile("wgmma.commit_group.sync.aligned;" ::: "memory"); }
template <int N> __device__ __forceinline__ void wg_wait() { asm volatile("wgmma.wait_group.sync.aligned %0;" :: "n"(N) : "memory"); }
__device__ __forceinline__ void cl_arrive_relaxed() { asm volatile("barrier.cluster.arrive.relaxed.aligned;" ::: "memory"); }
__device__ __forceinline__ void cl_wait() { asm volatile("barrier.cluster.wait.acquire.aligned;" ::: "memory"); }
__device__ __forceinline__ bool elect() { uint32_t p; asm volatile("{\n.reg .pred p;\nelect.sync _|p, 0xffffffff;\nselp.u32 %0, 1, 0, p;\n}" : "=r"(p)); return p; }
__device__ __forceinline__ void named_bar(int id, int n) { asm volatile("bar.sync %0, %1;" :: "r"(id), "r"(n) : "memory"); }
__device__ __forceinline__ uint32_t pack2(float lo, float hi) { uint32_t r; asm("cvt.rn.bf16x2.f32 %0, %1, %2;" : "=r"(r) : "f"(hi), "f"(lo)); return r; }
__device__ __forceinline__ float bf_lo(uint32_t w) { return __uint_as_float(w << 16); }
__device__ __forceinline__ float bf_hi(uint32_t w) { return __uint_as_float(w & 0xffff0000u); }
__device__ __forceinline__ float bf_round(float v) { return __bfloat162float(__float2bfloat16_rn(v)); }
__device__ __forceinline__ void stsm4(uint32_t addr, uint32_t a, uint32_t b, uint32_t c, uint32_t d) {
  asm volatile("stmatrix.sync.aligned.m8n8.x4.shared.b16 [%0], {%1, %2, %3, %4};" :: "r"(addr), "r"(a), "r"(b), "r"(c), "r"(d) : "memory");
}
__device__ __forceinline__ void ldsm4(uint32_t addr, uint32_t& a, uint32_t& b, uint32_t& c, uint32_t& d) {
  asm volatile("ldmatrix.sync.aligned.m8n8.x4.shared.b16 {%0, %1, %2, %3}, [%4];" : "=r"(a), "=r"(b), "=r"(c), "=r"(d) : "r"(addr) : "memory");
}
__device__ __forceinline__ uint32_t movm(uint32_t a) { uint32_t r; asm volatile("movmatrix.sync.aligned.m8n8.trans.b16 %0, %1;" : "=r"(r) : "r"(a)); return r; }
__device__ __forceinline__ void mma16(float (&d)[4], uint32_t a0, uint32_t a1, uint32_t a2, uint32_t a3, uint32_t b0, uint32_t b1) {
  asm("mma.sync.aligned.m16n8k16.row.col.f32.bf16.bf16.f32 {%0,%1,%2,%3}, {%4,%5,%6,%7}, {%8,%9}, {%0,%1,%2,%3};"
               : "+f"(d[0]), "+f"(d[1]), "+f"(d[2]), "+f"(d[3]) : "r"(a0), "r"(a1), "r"(a2), "r"(a3), "r"(b0), "r"(b1));
}
__device__ __forceinline__ void mma16z(float (&d)[4], uint32_t a0, uint32_t a1, uint32_t a2, uint32_t a3, uint32_t b0, uint32_t b1) {
  asm("mma.sync.aligned.m16n8k16.row.col.f32.bf16.bf16.f32 {%0,%1,%2,%3}, {%4,%5,%6,%7}, {%8,%9}, {%10,%10,%10,%10};"
      : "=f"(d[0]), "=f"(d[1]), "=f"(d[2]), "=f"(d[3]) : "r"(a0), "r"(a1), "r"(a2), "r"(a3), "r"(b0), "r"(b1), "f"(0.f));
}
__device__ __forceinline__ void mma8z(float (&d)[4], uint32_t a0, uint32_t a1, uint32_t b0) {
  asm("mma.sync.aligned.m16n8k8.row.col.f32.bf16.bf16.f32 {%0,%1,%2,%3}, {%4,%5}, {%6}, {%7,%7,%7,%7};"
      : "=f"(d[0]), "=f"(d[1]), "=f"(d[2]), "=f"(d[3]) : "r"(a0), "r"(a1), "r"(b0), "f"(0.f));
}
__device__ __forceinline__ void mma8(float (&d)[4], uint32_t a0, uint32_t a1, uint32_t b0) {
  asm("mma.sync.aligned.m16n8k8.row.col.f32.bf16.bf16.f32 {%0,%1,%2,%3}, {%4,%5}, {%6}, {%0,%1,%2,%3};"
               : "+f"(d[0]), "+f"(d[1]), "+f"(d[2]), "+f"(d[3]) : "r"(a0), "r"(a1), "r"(b0));
}
__device__ __forceinline__ uint4 lds128(uint32_t a) { uint4 v; asm volatile("ld.shared.v4.u32 {%0,%1,%2,%3}, [%4];" : "=r"(v.x), "=r"(v.y), "=r"(v.z), "=r"(v.w) : "r"(a) : "memory"); return v; }
__device__ __forceinline__ void sts128(uint32_t a, uint32_t x, uint32_t y, uint32_t z, uint32_t w) { asm volatile("st.shared.v4.u32 [%0], {%1,%2,%3,%4};" :: "r"(a), "r"(x), "r"(y), "r"(z), "r"(w) : "memory"); }
__device__ __forceinline__ float lds32f(uint32_t a) { float v; asm volatile("ld.shared.f32 %0, [%1];" : "=f"(v) : "r"(a) : "memory"); return v; }
__device__ __forceinline__ void sts16(uint32_t a, bf16 v) { asm volatile("st.shared.b16 [%0], %1;" :: "r"(a), "h"(__bfloat16_as_ushort(v)) : "memory"); }
__device__ __forceinline__ uint4 ldg_nc(const void* p) { uint4 v; asm volatile("ld.global.nc.L1::no_allocate.v4.u32 {%0,%1,%2,%3}, [%4];" : "=r"(v.x), "=r"(v.y), "=r"(v.z), "=r"(v.w) : "l"(p)); return v; }
__device__ __forceinline__ uint4 ld_rlx4(const uint4* p) {
  unsigned long long a, b; asm volatile("ld.relaxed.gpu.global.v2.b64 {%0,%1}, [%2];" : "=l"(a), "=l"(b) : "l"(p) : "memory");
  return make_uint4((uint32_t)a, (uint32_t)(a >> 32), (uint32_t)b, (uint32_t)(b >> 32));
}
__device__ __forceinline__ uint2 ld_rlx2(const uint2* p) { unsigned long long a; asm volatile("ld.relaxed.gpu.global.b64 %0, [%1];" : "=l"(a) : "l"(p) : "memory"); return make_uint2((uint32_t)a, (uint32_t)(a >> 32)); }
__device__ __forceinline__ void st_rlx4(uint4* p, uint32_t x, uint32_t y, uint32_t z, uint32_t w) {
  asm volatile("st.relaxed.gpu.global.v2.b64 [%0], {%1,%2};" :: "l"(p), "l"((unsigned long long)x | ((unsigned long long)y << 32)), "l"((unsigned long long)z | ((unsigned long long)w << 32)) : "memory");
}
__device__ __forceinline__ void st_rlx2(uint2* p, uint32_t x, uint32_t y) { asm volatile("st.relaxed.gpu.global.b64 [%0], %1;" :: "l"(p), "l"((unsigned long long)x | ((unsigned long long)y << 32)) : "memory"); }
__device__ __forceinline__ void st_release(uint32_t* p, uint32_t v) { asm volatile("st.release.gpu.global.u32 [%0], %1;" :: "l"(p), "r"(v) : "memory"); }
__device__ __forceinline__ uint32_t ld_acquire(const uint32_t* p) { uint32_t v; asm volatile("ld.acquire.gpu.global.u32 %0, [%1];" : "=r"(v) : "l"(p) : "memory"); return v; }
__device__ __forceinline__ void prefetch_map(const CUtensorMap* m) { asm volatile("prefetch.tensormap [%0];" :: "l"(m) : "memory"); }
__device__ __forceinline__ float rcp(float x) { float r; asm("rcp.approx.ftz.f32 %0, %1;" : "=f"(r) : "f"(x)); return r; }
__device__ __forceinline__ float ex2(float x) { float r; asm("ex2.approx.ftz.f32 %0, %1;" : "=f"(r) : "f"(x)); return r; }
__device__ __forceinline__ float tanh_fast(float x) { float r; asm("tanh.approx.f32 %0, %1;" : "=f"(r) : "f"(x)); return r; }
#define SPIN_GUARD(n) if (++(n) > (1u << 24)) bail()

__device__ __forceinline__ void wgmma_n128(float (&d)[64], uint64_t da, uint64_t db) {
  asm volatile("wgmma.mma_async.sync.aligned.m64n128k16.f32.bf16.bf16 "
    "{%0, %1, %2, %3, %4, %5, %6, %7, %8, %9, %10, %11, %12, %13, %14, %15, %16, %17, %18, %19, %20, %21, %22, %23, %24, %25, %26, %27, %28, %29, %30, %31, %32, %33, %34, %35, %36, %37, %38, %39, %40, %41, %42, %43, %44, %45, %46, %47, %48, %49, %50, %51, %52, %53, %54, %55, %56, %57, %58, %59, %60, %61, %62, %63}, "
    "%64, %65, 1, 1, 1, 0, 1;\n"
    : "+f"(d[0]), "+f"(d[1]), "+f"(d[2]), "+f"(d[3]), "+f"(d[4]), "+f"(d[5]), "+f"(d[6]), "+f"(d[7]), "+f"(d[8]), "+f"(d[9]), "+f"(d[10]), "+f"(d[11]), "+f"(d[12]), "+f"(d[13]), "+f"(d[14]), "+f"(d[15]), "+f"(d[16]), "+f"(d[17]), "+f"(d[18]), "+f"(d[19]), "+f"(d[20]), "+f"(d[21]), "+f"(d[22]), "+f"(d[23]), "+f"(d[24]), "+f"(d[25]), "+f"(d[26]), "+f"(d[27]), "+f"(d[28]), "+f"(d[29]), "+f"(d[30]), "+f"(d[31]), "+f"(d[32]), "+f"(d[33]), "+f"(d[34]), "+f"(d[35]), "+f"(d[36]), "+f"(d[37]), "+f"(d[38]), "+f"(d[39]), "+f"(d[40]), "+f"(d[41]), "+f"(d[42]), "+f"(d[43]), "+f"(d[44]), "+f"(d[45]), "+f"(d[46]), "+f"(d[47]), "+f"(d[48]), "+f"(d[49]), "+f"(d[50]), "+f"(d[51]), "+f"(d[52]), "+f"(d[53]), "+f"(d[54]), "+f"(d[55]), "+f"(d[56]), "+f"(d[57]), "+f"(d[58]), "+f"(d[59]), "+f"(d[60]), "+f"(d[61]), "+f"(d[62]), "+f"(d[63])
    : "l"(da), "l"(db));
}
__device__ __forceinline__ void wgmma_n128_first(float (&d)[64], uint64_t da, uint64_t db) {
  asm volatile("wgmma.mma_async.sync.aligned.m64n128k16.f32.bf16.bf16 "
    "{%0, %1, %2, %3, %4, %5, %6, %7, %8, %9, %10, %11, %12, %13, %14, %15, %16, %17, %18, %19, %20, %21, %22, %23, %24, %25, %26, %27, %28, %29, %30, %31, %32, %33, %34, %35, %36, %37, %38, %39, %40, %41, %42, %43, %44, %45, %46, %47, %48, %49, %50, %51, %52, %53, %54, %55, %56, %57, %58, %59, %60, %61, %62, %63}, "
    "%64, %65, 0, 1, 1, 0, 1;\n"
    : "=f"(d[0]), "=f"(d[1]), "=f"(d[2]), "=f"(d[3]), "=f"(d[4]), "=f"(d[5]), "=f"(d[6]), "=f"(d[7]), "=f"(d[8]), "=f"(d[9]), "=f"(d[10]), "=f"(d[11]), "=f"(d[12]), "=f"(d[13]), "=f"(d[14]), "=f"(d[15]), "=f"(d[16]), "=f"(d[17]), "=f"(d[18]), "=f"(d[19]), "=f"(d[20]), "=f"(d[21]), "=f"(d[22]), "=f"(d[23]), "=f"(d[24]), "=f"(d[25]), "=f"(d[26]), "=f"(d[27]), "=f"(d[28]), "=f"(d[29]), "=f"(d[30]), "=f"(d[31]), "=f"(d[32]), "=f"(d[33]), "=f"(d[34]), "=f"(d[35]), "=f"(d[36]), "=f"(d[37]), "=f"(d[38]), "=f"(d[39]), "=f"(d[40]), "=f"(d[41]), "=f"(d[42]), "=f"(d[43]), "=f"(d[44]), "=f"(d[45]), "=f"(d[46]), "=f"(d[47]), "=f"(d[48]), "=f"(d[49]), "=f"(d[50]), "=f"(d[51]), "=f"(d[52]), "=f"(d[53]), "=f"(d[54]), "=f"(d[55]), "=f"(d[56]), "=f"(d[57]), "=f"(d[58]), "=f"(d[59]), "=f"(d[60]), "=f"(d[61]), "=f"(d[62]), "=f"(d[63])
    : "l"(da), "l"(db));
}
__device__ __forceinline__ void wgmma_n256(float (&d)[128], uint64_t da, uint64_t db) {
  asm volatile("wgmma.mma_async.sync.aligned.m64n256k16.f32.bf16.bf16 "
    "{%0, %1, %2, %3, %4, %5, %6, %7, %8, %9, %10, %11, %12, %13, %14, %15, %16, %17, %18, %19, %20, %21, %22, %23, %24, %25, %26, %27, %28, %29, %30, %31, %32, %33, %34, %35, %36, %37, %38, %39, %40, %41, %42, %43, %44, %45, %46, %47, %48, %49, %50, %51, %52, %53, %54, %55, %56, %57, %58, %59, %60, %61, %62, %63, %64, %65, %66, %67, %68, %69, %70, %71, %72, %73, %74, %75, %76, %77, %78, %79, %80, %81, %82, %83, %84, %85, %86, %87, %88, %89, %90, %91, %92, %93, %94, %95, %96, %97, %98, %99, %100, %101, %102, %103, %104, %105, %106, %107, %108, %109, %110, %111, %112, %113, %114, %115, %116, %117, %118, %119, %120, %121, %122, %123, %124, %125, %126, %127}, "
    "%128, %129, 1, 1, 1, 0, 1;\n"
    : "+f"(d[0]), "+f"(d[1]), "+f"(d[2]), "+f"(d[3]), "+f"(d[4]), "+f"(d[5]), "+f"(d[6]), "+f"(d[7]), "+f"(d[8]), "+f"(d[9]), "+f"(d[10]), "+f"(d[11]), "+f"(d[12]), "+f"(d[13]), "+f"(d[14]), "+f"(d[15]), "+f"(d[16]), "+f"(d[17]), "+f"(d[18]), "+f"(d[19]), "+f"(d[20]), "+f"(d[21]), "+f"(d[22]), "+f"(d[23]), "+f"(d[24]), "+f"(d[25]), "+f"(d[26]), "+f"(d[27]), "+f"(d[28]), "+f"(d[29]), "+f"(d[30]), "+f"(d[31]), "+f"(d[32]), "+f"(d[33]), "+f"(d[34]), "+f"(d[35]), "+f"(d[36]), "+f"(d[37]), "+f"(d[38]), "+f"(d[39]), "+f"(d[40]), "+f"(d[41]), "+f"(d[42]), "+f"(d[43]), "+f"(d[44]), "+f"(d[45]), "+f"(d[46]), "+f"(d[47]), "+f"(d[48]), "+f"(d[49]), "+f"(d[50]), "+f"(d[51]), "+f"(d[52]), "+f"(d[53]), "+f"(d[54]), "+f"(d[55]), "+f"(d[56]), "+f"(d[57]), "+f"(d[58]), "+f"(d[59]), "+f"(d[60]), "+f"(d[61]), "+f"(d[62]), "+f"(d[63]), "+f"(d[64]), "+f"(d[65]), "+f"(d[66]), "+f"(d[67]), "+f"(d[68]), "+f"(d[69]), "+f"(d[70]), "+f"(d[71]), "+f"(d[72]), "+f"(d[73]), "+f"(d[74]), "+f"(d[75]), "+f"(d[76]), "+f"(d[77]), "+f"(d[78]), "+f"(d[79]), "+f"(d[80]), "+f"(d[81]), "+f"(d[82]), "+f"(d[83]), "+f"(d[84]), "+f"(d[85]), "+f"(d[86]), "+f"(d[87]), "+f"(d[88]), "+f"(d[89]), "+f"(d[90]), "+f"(d[91]), "+f"(d[92]), "+f"(d[93]), "+f"(d[94]), "+f"(d[95]), "+f"(d[96]), "+f"(d[97]), "+f"(d[98]), "+f"(d[99]), "+f"(d[100]), "+f"(d[101]), "+f"(d[102]), "+f"(d[103]), "+f"(d[104]), "+f"(d[105]), "+f"(d[106]), "+f"(d[107]), "+f"(d[108]), "+f"(d[109]), "+f"(d[110]), "+f"(d[111]), "+f"(d[112]), "+f"(d[113]), "+f"(d[114]), "+f"(d[115]), "+f"(d[116]), "+f"(d[117]), "+f"(d[118]), "+f"(d[119]), "+f"(d[120]), "+f"(d[121]), "+f"(d[122]), "+f"(d[123]), "+f"(d[124]), "+f"(d[125]), "+f"(d[126]), "+f"(d[127])
    : "l"(da), "l"(db));
}
__device__ __forceinline__ void wgmma_n256_first(float (&d)[128], uint64_t da, uint64_t db) {
  asm volatile("wgmma.mma_async.sync.aligned.m64n256k16.f32.bf16.bf16 "
    "{%0, %1, %2, %3, %4, %5, %6, %7, %8, %9, %10, %11, %12, %13, %14, %15, %16, %17, %18, %19, %20, %21, %22, %23, %24, %25, %26, %27, %28, %29, %30, %31, %32, %33, %34, %35, %36, %37, %38, %39, %40, %41, %42, %43, %44, %45, %46, %47, %48, %49, %50, %51, %52, %53, %54, %55, %56, %57, %58, %59, %60, %61, %62, %63, %64, %65, %66, %67, %68, %69, %70, %71, %72, %73, %74, %75, %76, %77, %78, %79, %80, %81, %82, %83, %84, %85, %86, %87, %88, %89, %90, %91, %92, %93, %94, %95, %96, %97, %98, %99, %100, %101, %102, %103, %104, %105, %106, %107, %108, %109, %110, %111, %112, %113, %114, %115, %116, %117, %118, %119, %120, %121, %122, %123, %124, %125, %126, %127}, "
    "%128, %129, 0, 1, 1, 0, 1;\n"
    : "=f"(d[0]), "=f"(d[1]), "=f"(d[2]), "=f"(d[3]), "=f"(d[4]), "=f"(d[5]), "=f"(d[6]), "=f"(d[7]), "=f"(d[8]), "=f"(d[9]), "=f"(d[10]), "=f"(d[11]), "=f"(d[12]), "=f"(d[13]), "=f"(d[14]), "=f"(d[15]), "=f"(d[16]), "=f"(d[17]), "=f"(d[18]), "=f"(d[19]), "=f"(d[20]), "=f"(d[21]), "=f"(d[22]), "=f"(d[23]), "=f"(d[24]), "=f"(d[25]), "=f"(d[26]), "=f"(d[27]), "=f"(d[28]), "=f"(d[29]), "=f"(d[30]), "=f"(d[31]), "=f"(d[32]), "=f"(d[33]), "=f"(d[34]), "=f"(d[35]), "=f"(d[36]), "=f"(d[37]), "=f"(d[38]), "=f"(d[39]), "=f"(d[40]), "=f"(d[41]), "=f"(d[42]), "=f"(d[43]), "=f"(d[44]), "=f"(d[45]), "=f"(d[46]), "=f"(d[47]), "=f"(d[48]), "=f"(d[49]), "=f"(d[50]), "=f"(d[51]), "=f"(d[52]), "=f"(d[53]), "=f"(d[54]), "=f"(d[55]), "=f"(d[56]), "=f"(d[57]), "=f"(d[58]), "=f"(d[59]), "=f"(d[60]), "=f"(d[61]), "=f"(d[62]), "=f"(d[63]), "=f"(d[64]), "=f"(d[65]), "=f"(d[66]), "=f"(d[67]), "=f"(d[68]), "=f"(d[69]), "=f"(d[70]), "=f"(d[71]), "=f"(d[72]), "=f"(d[73]), "=f"(d[74]), "=f"(d[75]), "=f"(d[76]), "=f"(d[77]), "=f"(d[78]), "=f"(d[79]), "=f"(d[80]), "=f"(d[81]), "=f"(d[82]), "=f"(d[83]), "=f"(d[84]), "=f"(d[85]), "=f"(d[86]), "=f"(d[87]), "=f"(d[88]), "=f"(d[89]), "=f"(d[90]), "=f"(d[91]), "=f"(d[92]), "=f"(d[93]), "=f"(d[94]), "=f"(d[95]), "=f"(d[96]), "=f"(d[97]), "=f"(d[98]), "=f"(d[99]), "=f"(d[100]), "=f"(d[101]), "=f"(d[102]), "=f"(d[103]), "=f"(d[104]), "=f"(d[105]), "=f"(d[106]), "=f"(d[107]), "=f"(d[108]), "=f"(d[109]), "=f"(d[110]), "=f"(d[111]), "=f"(d[112]), "=f"(d[113]), "=f"(d[114]), "=f"(d[115]), "=f"(d[116]), "=f"(d[117]), "=f"(d[118]), "=f"(d[119]), "=f"(d[120]), "=f"(d[121]), "=f"(d[122]), "=f"(d[123]), "=f"(d[124]), "=f"(d[125]), "=f"(d[126]), "=f"(d[127])
    : "l"(da), "l"(db));
}

template <int N> struct WG;
#define DEF_WG(N) template <> struct WG<N> { \
  static __device__ __forceinline__ void mma(float (&d)[N / 2], uint64_t a, uint64_t b) { wgmma_n##N(d, a, b); } \
  static __device__ __forceinline__ void first(float (&d)[N / 2], uint64_t a, uint64_t b) { wgmma_n##N##_first(d, a, b); } };
DEF_WG(128) DEF_WG(256)

constexpr uint64_t DESC_A = (1ull << 62) | ((uint64_t)(1024 >> 4) << 32) | (1ull << 16);
constexpr uint64_t DESC_B = (1ull << 62) | ((uint64_t)(1024 >> 4) << 32) | ((uint64_t)(8192 >> 4) << 16);

struct Ring { int s; uint32_t ph; int wrap; };
template <int NS> __device__ __forceinline__ void ring_next(Ring& r) { r.s = (r.s + 1 == NS) ? 0 : r.s + 1; if (r.s == r.wrap) r.ph ^= 1; }

__device__ __forceinline__ int own_order(int it, int j) {
  return it < 2 ? 2 * j + it : it < 4 ? 2 * (j ^ 1) + it - 2 : ((j >> 1) * 4 + 2 * it - (it < 10 ? 4 : 15)) & 15;
}

template <int V> struct IC { static constexpr int v = V; };
template <int I, int E, class F> __device__ __forceinline__ void static_for(F&& f) { if constexpr (I < E) { f(IC<I>{}); static_for<I + 1, E>(f); } }

template <int N, int NS, int PRE, int LAG, class Pre, class Mid, class Last>
__device__ __forceinline__ void mainloop(float (&acc)[N / 2], int nkb, bool own, Ring& r, uint32_t sb, int wg, int lane, uint32_t rel_base, uint32_t* step0, Pre pre, Mid mid, Last last) {
  constexpr int SLOT = RING / NS;
  const uint32_t full = sb + MISC + (NS == 4 ? B_FULL4 : B_FULL6);
  const uint32_t rel = rel_base + (NS == 4 ? B_EMPTY4 : B_EMPTY6);
  const uint32_t s0 = (sb & 0x3FFFF) >> 4, a0 = s0 + wg * (HALF >> 4);
  int ps;
  auto issue = [&](int it, bool first) {
    const uint64_t da = DESC_A | (a0 + ((own && it < 2) ? (STG + it * BLK) >> 4 : r.s * (SLOT >> 4))), db = DESC_B | (s0 + r.s * (SLOT >> 4) + (BLK >> 4));
    mbar_wait(full + r.s * 8, r.ph);
    TRS(it);
    wg_arrive();
    if (first) WG<N>::first(acc, da, db); else WG<N>::mma(acc, da, db);
#pragma unroll
    for (int k = 1; k < 4; k++) WG<N>::mma(acc, da + k * 2, db + k * 128);
    wg_commit();
  };
  auto retire = [&](int it) {
    wg_wait<1>();
    if (lane < 2) mbar_arrive_cl(rel + ps * 8);
    ps = r.s;
    ring_next<NS>(r);
  };
  issue(0, true);
  ps = r.s;
  ring_next<NS>(r);
  static_for<1, PRE + 1>([&](auto ic) { issue(ic.v, false); pre(ic); retire(ic.v); });
#pragma unroll 1
  for (int it = PRE + 1; it < nkb; it++) {
    if (LAG && it == nkb - LAG && wg == 1) mbar_wait(sb + MISC + B_LAG, WOLAG && !own);
    issue(it, false); mid(it); retire(it);
  }
  last();
  wg_wait<0>();
  if (lane < 2) mbar_arrive_cl(rel + ps * 8);
}

__device__ __forceinline__ void ln_publish(const float (&v)[64], uint4* st, int j, int row0, int lane, uint32_t ep) {
  float s0 = 0, s1 = 0, s2 = 0, s3 = 0, q0 = 0, q1 = 0, q2 = 0, q3 = 0;
#pragma unroll
  for (int i = 0; i < 16; i++) {
    s0 += v[4 * i]; s1 += v[4 * i + 1]; s2 += v[4 * i + 2]; s3 += v[4 * i + 3];
    q0 = fmaf(v[4 * i], v[4 * i], q0); q1 = fmaf(v[4 * i + 1], v[4 * i + 1], q1); q2 = fmaf(v[4 * i + 2], v[4 * i + 2], q2); q3 = fmaf(v[4 * i + 3], v[4 * i + 3], q3);
  }
  s0 += s1; s2 += s3; q0 += q1; q2 += q3;
  const bool odd = lane & 1;
  float s = (odd ? s2 : s0) + __shfl_xor_sync(~0u, odd ? s0 : s2, 1), q = (odd ? q2 : q0) + __shfl_xor_sync(~0u, odd ? q0 : q2, 1);
  s += __shfl_xor_sync(~0u, s, 2); q += __shfl_xor_sync(~0u, q, 2);
  if ((lane & 3) < 2) st_rlx4(st + j * 128 + row0 + (lane & 1) * 8, __float_as_uint(s), ep, __float_as_uint(q), ep);
}
__device__ __forceinline__ void ln_gather(const uint4* st, int row0, int lane, uint32_t ep, float& n0, float& r0, float& n1, float& r1) {
  const uint4* p = st + (lane & 2) * 256 + row0 + (lane & 1) * 8;
  uint4 a, b, c, d; uint32_t n = 0;
  while (true) {
    a = ld_rlx4(p); b = ld_rlx4(p + 128); c = ld_rlx4(p + 256); d = ld_rlx4(p + 384);
    if (a.y == ep && a.w == ep && b.y == ep && b.w == ep && c.y == ep && c.w == ep && d.y == ep && d.w == ep) break;
    SPIN_GUARD(n);
  }
  __syncwarp();
  float s = (__uint_as_float(a.x) + __uint_as_float(b.x)) + (__uint_as_float(c.x) + __uint_as_float(d.x));
  float q = (__uint_as_float(a.z) + __uint_as_float(b.z)) + (__uint_as_float(c.z) + __uint_as_float(d.z));
  s += __shfl_xor_sync(~0u, s, 2); q += __shfl_xor_sync(~0u, q, 2);
  s *= 1.f / 1024;
  const float r = rsqrtf(fmaxf(fmaf(-s, s, q * (1.f / 1024)), 0.f) + 1e-5f), nn = -s * r;
  const float ro = __shfl_xor_sync(~0u, r, 1), no = __shfl_xor_sync(~0u, nn, 1);
  const bool odd = lane & 1;
  r0 = odd ? ro : r; n0 = odd ? no : nn; r1 = odd ? r : ro; n1 = odd ? nn : no;
}
__device__ __forceinline__ void load_vec(uint32_t* w, uint32_t sb, int sec, int b, int lane) {
#pragma unroll
  for (int q = 0; q < 2; q++) { uint4 t = lds128(sb + MISC + MODV + sec * 256 + (lane & 3) * 64 + b * 32 + q * 16); w[4 * q] = t.x; w[4 * q + 1] = t.y; w[4 * q + 2] = t.z; w[4 * q + 3] = t.w; }
}
__device__ __forceinline__ void stage_done(uint32_t sb, int wg, int b, int lane) {
  fence_async_smem();
  __syncwarp();
  if (lane == 0) mbar_arrive(sb + MISC + B_RDY + b * 8);
}
__device__ __forceinline__ uint32_t hfma2(uint32_t a, uint32_t b, uint32_t c) { uint32_t r; asm("fma.rn.bf16x2 %0, %1, %2, %3;" : "=r"(r) : "r"(a), "r"(b), "r"(c)); return r; }
__device__ __forceinline__ void ln_apply(const float (&v)[64], const uint4* st, int row0, uint32_t ep, uint32_t sb, int sec_shift, int sec_scale, uint32_t stg_row, int wg, int lane, uint32_t* step0) {
  uint32_t sc[16], sh[16];
#pragma unroll
  for (int b = 0; b < 2; b++) { load_vec(sc + 8 * b, sb, sec_scale, b, lane); load_vec(sh + 8 * b, sb, sec_shift, b, lane); }
  float n0, r0, n1, r1;
  TRW(1);
  ln_gather(st, row0, lane, ep, n0, r0, n1, r1);
  TRW(2);
#pragma unroll
  for (int i = 0; i < 16; i += 2) {
    if (i == 8) { const float z = lds32f(sb + MISC + ZERO); n0 += z; n1 += z; }
    uint32_t w[4];
#pragma unroll
    for (int u = 0; u < 2; u++) {
      int q = i + u;
      w[2 * u] = hfma2(pack2(fmaf(v[4 * q], r0, n0), fmaf(v[4 * q + 1], r0, n0)), sc[q], sh[q]);
      w[2 * u + 1] = hfma2(pack2(fmaf(v[4 * q + 2], r1, n1), fmaf(v[4 * q + 3], r1, n1)), sc[q], sh[q]);
    }
    stsm4(stg_row + (i >> 3) * BLK + ((((i & 7) + (lane >> 4)) ^ (lane & 7)) << 4), w[0], w[1], w[2], w[3]);
    if ((i & 7) == 6) { stage_done(sb, wg, i >> 3, lane); TRW(3 + (i >> 3)); }
  }
}
__device__ __forceinline__ uint32_t hmul2(uint32_t a, uint32_t b) { uint32_t r; asm("mul.rn.bf16x2 %0, %1, %2;" : "=r"(r) : "r"(a), "r"(b)); return r; }
__device__ __forceinline__ uint32_t silu_mul2(uint32_t g, uint32_t u) {
  const uint32_t h = hmul2(g, 0x3f003f00u);
  const float h0 = bf_lo(h), h1 = bf_hi(h);
  return hmul2(pack2(fmaf(h0, tanh_fast(h0), h0), fmaf(h1, tanh_fast(h1), h1)), u);
}

__device__ __forceinline__ void gemv_fma(float (&a)[8], uint4 w, float s) {
  a[0] = fmaf(bf_lo(w.x), s, a[0]); a[1] = fmaf(bf_hi(w.x), s, a[1]); a[2] = fmaf(bf_lo(w.y), s, a[2]); a[3] = fmaf(bf_hi(w.y), s, a[3]);
  a[4] = fmaf(bf_lo(w.z), s, a[4]); a[5] = fmaf(bf_hi(w.z), s, a[5]); a[6] = fmaf(bf_lo(w.w), s, a[6]); a[7] = fmaf(bf_hi(w.w), s, a[7]);
}
__device__ __forceinline__ float silu_c(float v) { return bf_round(__fdividef(v, 1.f + __expf(-v))); }
__device__ __forceinline__ float mod_gather(const uint2* p, uint32_t ep) {
  uint2 a, b, c, d; uint32_t n = 0;
  while (true) {
    a = ld_rlx2(p); b = ld_rlx2(p + 128); c = ld_rlx2(p + 256); d = ld_rlx2(p + 384);
    if (a.y == ep && b.y == ep && c.y == ep && d.y == ep) break;
    SPIN_GUARD(n);
  }
  return (__uint_as_float(a.x) + __uint_as_float(b.x)) + (__uint_as_float(c.x) + __uint_as_float(d.x));
}
__device__ __forceinline__ void mod_store(uint32_t sb, int sec, int col, float v) {
  v = bf_round(v);
  if (sec == 1 || sec == 4) v += 1.f;
  sts16(sb + MISC + MODV + sec * 256 + (((col >> 1) & 3) * 16 + (col >> 3)) * 4 + (col & 1) * 2, __float2bfloat16_rn(v));
}

__global__ void __cluster_dims__(2, 1, 1) __launch_bounds__(384, 1)
fused_kernel(const bf16* __restrict__ cvec, const bf16* __restrict__ wmod, Scratch* gs, int by_sm, const __grid_constant__ Maps maps) {
  extern __shared__ __align__(1024) uint8_t smem_raw[];
  const uint32_t sb = smem_u32(smem_raw);
  const int warp = __shfl_sync(~0u, threadIdx.x >> 5, 0), lane = threadIdx.x & 31;
  const int rank = blockIdx.x & 1;
  uint32_t sm; asm("mov.u32 %0, %%smid;" : "=r"(sm));
  const int t = sm >> 1, v = t < 32 ? t : t < 60 ? t + 1 + (((t - 32) * 37) >> 8) : (t - 58) * 8;
  const int cid = !by_sm ? (blockIdx.x >> 1) - 2 : (t & ~1) == 60 ? t - 62 : (v & 1) * 32 + ((v >> 1) & 31);
  const bool extra = cid < 0;
  const int bid = cid * 2 + rank;
  const int m = cid >> 2, j = (cid & 3) * 2 + rank;
  const uint32_t bar = sb + MISC;

  if (warp >= 8) {
    asm volatile("setmaxnreg.dec.sync.aligned.u32 40;");
    if (extra) {
      if (warp == 8) {
        if (lane == 0) { for (int s = 0; s < 6; s++) { mbar_init(bar + B_FULL6 + s * 8, 1); mbar_init(bar + B_EMPTY6 + s * 8, 8); } fence_async_smem(); }
        __syncwarp();
        asm volatile("bar.arrive 2, 288;" ::: "memory");
        __nanosleep(XSLEEP);
#pragma unroll 1
        for (int it = 0, s = 0, par = 1; it < 64; it++) {
          mbar_wait(bar + B_EMPTY6 + s * 8, par);
          if (elect()) { mbar_expect_tx(bar + B_FULL6 + s * 8, 32768); tma_3d(sb + s * 32768, &maps.wmod, bar + B_FULL6 + s * 8, 0, (it & 15) * 64, 12 + (it >> 4) * 4 + bid); }
          if (++s == 6) { s = 0; par ^= 1; }
        }
      }
    } else if (warp < 10) {
      uint32_t s6 = 0, p6 = 1;
      auto next6 = [&]() { if (++s6 == 6) { s6 = 0; p6 ^= 1; } };
      auto drained4 = [&](int q, int late) { if (q < 5) mbar_wait(bar + B_EMPTY4 + (((late ? 0x10332 : 0x32110) >> (4 * q)) & 3) * 8, 1); };
      auto drained6 = [&](int q) { if (q < 3) mbar_wait(bar + B_EMPTY6 + ((0x154 >> (4 * q)) & 7) * 8, q >> 1); };
      auto skip6 = [&]() { mbar_wait(bar + B_EMPTY6 + s6 * 8, p6); if (elect()) mbar_arrive(bar + B_FULL6 + s6 * 8); next6(); };
      if (warp == 8) {
        const uint32_t t_start = clock();
        if (lane == 0) {
          if (sb & 1023) bail();
          for (int b = 0; b < 2; b++) mbar_init(bar + B_X + b * 8, 1);
          for (int s = 0; s < 4; s++) { mbar_init(bar + B_FULL4 + s * 8, 2); mbar_init(bar + B_EMPTY4 + s * 8, 16); }
          for (int s = 0; s < 6; s++) { mbar_init(bar + B_FULL6 + s * 8, 2); mbar_init(bar + B_EMPTY6 + s * 8, 16); }
          for (int b = 0; b < 2; b++) { mbar_init(bar + B_RDY + b * 8, 8); mbar_init(bar + B_FREE + b * 8, 1); mbar_init(bar + B_HH + b * 8, 1); }
          mbar_init(bar + B_MOD, 1); mbar_init(bar + B_LAG, 4); mbar_init(bar + B_HALO, 2); mbar_init(bar + B_ALL, 1); mbar_init(bar + B_HH2, 1);
          asm volatile("st.shared.u32 [%0], 0;" :: "r"(bar + ZERO) : "memory");
          asm volatile("fence.mbarrier_init.release.cluster;" ::: "memory");
          fence_async_smem();
        }
        __syncwarp();
        cl_arrive_relaxed();
        auto wide = [&](int s, int par, const CUtensorMap* m0, int a0, const CUtensorMap* m1, int a1, int kb) {
          const uint32_t full = bar + B_FULL4 + s * 8, d = sb + s * 49152 + BLK;
          mbar_wait(full + 32, par);
          if (elect()) { mbar_expect_tx(full, 2 * BLK); tma_3d(d, m0, full, 0, kb * 64, a0); tma_3d(d + BLK, m1, full, 0, kb * 64, a1); }
        };
        auto narrow = [&](const CUtensorMap* m0, int kb) {
          const uint32_t full = bar + B_FULL6 + s6 * 8;
          mbar_wait(full + 48, p6);
          if (elect()) { mbar_expect_tx(full, BLK); tma_3d(sb + s6 * 32768 + BLK, m0, full, 0, kb * 64, 2 * j); }
          next6();
        };
#pragma unroll 1
        for (int it = 0; it < 16; it++) {
          if (it == 0) {
            while ((uint32_t)clock() - t_start < XDELAY) {}
            if (elect()) for (int b = 0; b < 2; b++) { mbar_expect_tx(bar + B_X + b * 8, BLK); tma_3d(sb + STG + b * BLK, &maps.x, bar + B_X + b * 8, j * 128 + b * 64, m * 64, 0); }
            mbar_wait(bar + B_X + 8, 0);
          }
          wide(it & 3, ~(it >> 2) & 1, &maps.wqkv, 16 + 2 * j, &maps.wqkv, 32 + 2 * j, own_order(it, j));
        }
#pragma unroll 1
        for (int it = 0; it < 16; it++) { drained4(it, 0); narrow(&maps.wqkv, it); }
#pragma unroll 1
        for (int it = 0; it < 16; it++) narrow(&maps.wo, own_order(it, j));
        skip6();
#pragma unroll 1
        for (int it = 0; it < 48; it++) {
          const int s = (it + 2) & 3, par = ~(it >> 2) & 1;
          drained6(it);
          wide(s, par, &maps.w1, (it & 48) + 2 * j, &maps.w3, (it & 48) + 2 * j, it < 16 ? own_order(it, j) : it & 15);
          if (it >= 44) {
            if (it == 44) { mbar_wait(bar + B_FREE, 0); mbar_wait(bar + B_FREE + 8, 0); if (elect()) mbar_expect_tx(bar + B_X, 2 * BLK); }
            if (elect()) bulk_ld(sb + STG + (it - 44) * HALF, gs->x1 + bid * 2048 + (it - 44) * 512, HALF, bar + B_X);
          }
        }
#pragma unroll 1
        for (int it = 0; it < 16; it++) {
          const uint32_t full = bar + B_FULL6 + s6 * 8, d = sb + s6 * 32768 + BLK;
          drained4(it, 1);
          mbar_wait(full + 48, p6);
          if (elect()) { mbar_expect_tx(full, BLK); tma_3d(d, &maps.w1s, full, 0, it * 64, 48 + j); tma_3d(d + HALF, &maps.w3s, full, 0, it * 64, 48 + j); }
          next6();
        }
#pragma unroll 1
        for (int it = 0; it < 56; it++) narrow(&maps.w2, it);
      } else {
        if (lane < 9) prefetch_map(&maps.x + lane);
        const uint32_t ep = gs->epoch[bid + 4] + 1;
        cl_arrive_relaxed(); cl_wait();
        auto plain = [&](uint32_t full, uint32_t empty, int par, uint32_t slot, const uint4* blk) {
          mbar_wait(empty, par);
          if (elect()) { mbar_expect_tx(full, BLK); bulk_ld_mc(slot + rank * HALF, blk + rank * 512, HALF, full); }
        };
        auto plain6 = [&](const uint4* blk) { plain(bar + B_FULL6 + s6 * 8, bar + B_EMPTY6 + s6 * 8, p6, sb + s6 * 32768, blk); next6(); };
        uint32_t ready = 0;
        auto poll = [&](int e) { ready = __ballot_sync(~0u, ld_acquire(gs->flag + m * 128 + e * 16 + (lane & 15)) == ep); };
        auto need = [&](int e, uint32_t mask) {
          if ((ready & mask) != mask) {
            uint32_t n = 0;
            do { poll(e); SPIN_GUARD(n); } while ((ready & mask) != mask);
            fence_async_global();
          }
        };
        auto fresh = [&](int e, int it, uint32_t full, uint32_t empty, int par, uint32_t slot, uint4* src) {
          if (it >= 4) {
            const int kb = own_order(it, j);
            if (it < 10) need(e, 1u << kb); else if (it == 10) mbar_wait(bar + B_ALL, e & 1);
            plain(full, empty, par, slot, src + kb * 1024);
          } else {
            if (it == 0) { poll(e); ready = 0; }
            mbar_wait(empty, par);
            if (it < 2) { if (elect()) mbar_arrive(full); }
            else {
              const int b = it > 2;
              const uint32_t to_peer = mapa(sb, rank ^ 1) - sb;
              if (elect()) mbar_expect_tx(full, BLK);
              const bool push = e != 1;
              mbar_wait(bar + (b ? (push ? B_RDY + 8 : B_FREE + 8) : B_RDY), e & 1);
              if (b == 0) TR(e == 0 ? 24 : e == 2 ? 30 : 44);
              if (elect()) {
                if (b == 0) {
                  bulk_st(src + 2 * j * 1024, sb + STG, BLK);
                  bulk_commit();
                  bulk_wait_all();
                  mbar_arrive(bar + B_FREE);
                }
                if (b && push) bulk_push(slot + to_peer, sb + STG + BLK, BLK, full + to_peer);
                else {
                  fence_async_global();
                  bulk_ld(slot + to_peer, src + (2 * j + b) * 1024, BLK, full + to_peer);
                }
              }
              __syncwarp();
            }
          }
          if (it == 4) TR(e == 0 ? 28 : e == 1 ? 46 : 34);
        };
#pragma unroll 1
        for (int ph = 0; ph < 2; ph++) {
          uint4* h = gs->h + m * 16384;
#pragma unroll 1
          for (int it = 0; it < 16; it++) {
            const int s = (it + 2 * ph) & 3;
            if (ph) drained6(it);
            fresh(2 * ph, it, bar + B_FULL4 + s * 8, bar + B_EMPTY4 + s * 8, ~(it >> 2) & 1, sb + s * 49152, h);
          }
          if (ph) {
#pragma unroll 1
            for (int it = 16; it < 48; it++) {
              const int s = (it + 2) & 3;
              const uint32_t full = bar + B_FULL4 + s * 8;
              plain(full, full + 32, ~(it >> 2) & 1, sb + s * 49152, h + (it & 15) * 1024);
            }
          }
#pragma unroll 1
          for (int it = 0; it < 16; it++) { drained4(it, ph); plain6(h + it * 1024); }
          if (!ph) {
#pragma unroll 1
            for (int it = 0; it < 16; it++) { fresh(1, it, bar + B_FULL6 + s6 * 8, bar + B_EMPTY6 + s6 * 8, p6, sb + s6 * 32768, gs->o + m * 16384); next6(); }
            skip6();
          }
        }
#pragma unroll 1
        for (int it = 0; it < 56; it++) {
          if (it == 0 || it == 32 || it == 48) mbar_wait(bar + (it == 48 ? B_HH2 : B_HH + (it >> 2)), 0);
          plain6(gs->hh + m * 57344 + it * 1024);
        }
      }
    } else {
      const int b = warp - 10;
      const uint32_t ep = gs->epoch[bid + 4] + 1;
      const uint32_t stg = sb + STG + b * BLK;
      cl_arrive_relaxed(); cl_wait();
      auto all_there = [&](int u, uint32_t done) {
        const uint32_t* fl = gs->flag + u;
        uint32_t n = 0;
        while (!__all_sync(~0u, ld_acquire(fl) == ep)) { __nanosleep(100); SPIN_GUARD(n); }
        fence_async_global();
        if (lane == 0) mbar_arrive(done);
      };
      auto fetch_mod = [&](int sec) {
        const uint4* p = (const uint4*)(gs->modv + (sec - 2) * 1024 + j * 128) + lane;
        uint4 v0, v1; uint32_t n = 0;
        while (true) {
          v0 = ld_rlx4(p); v1 = ld_rlx4(p + 32);
          if (v0.y == ep && v0.w == ep && v1.y == ep && v1.w == ep) break;
          SPIN_GUARD(n);
        }
        mod_store(sb, sec, 2 * lane, __uint_as_float(v0.x)); mod_store(sb, sec, 2 * lane + 1, __uint_as_float(v0.z));
        mod_store(sb, sec, 64 + 2 * lane, __uint_as_float(v1.x)); mod_store(sb, sec, 65 + 2 * lane, __uint_as_float(v1.z));
        __syncwarp();
      };
#pragma unroll 1
      for (int e = 0; e < 7 - b; e++) {
        if (lane == 0) {
          if (e < 3) {
            mbar_wait(bar + B_FREE, e & 1);
            if (b) {
              const uint32_t t0 = clock();
              while ((uint32_t)clock() - t0 < (e == 0 ? B1P : e == 2 ? B1P2 : B1D)) {}
              mbar_wait(bar + B_RDY + 8, e & 1);
              bulk_st((e == 1 ? gs->o : gs->h) + m * 16384 + (2 * j + 1) * 1024, stg, BLK);
              bulk_commit();
              bulk_wait_all();
              mbar_arrive(bar + B_FREE + 8);
              TR(53 + e);
            }
            st_release(gs->flag + m * 128 + e * 16 + 2 * j + b, ep);
            TR((e == 0 ? 26 : e == 2 ? 32 : 42) + b);
          } else {
            const int kb = (e < 6 ? 2 * (8 * (e - 3) + j) : 48 + j) + b;
            mbar_wait(bar + B_RDY + b * 8, e & 1);
#pragma unroll 1
            for (int q = 0; q < NPIECE; q++) { if (q) __nanosleep(PSLEEP); bulk_st(gs->hh + m * 57344 + kb * 1024 + q * (1024 / NPIECE), stg + q * (BLK / NPIECE), BLK / NPIECE); }
            bulk_commit();
            bulk_wait_all();
            mbar_arrive(bar + B_FREE + b * 8);
            st_release(gs->flag + m * 128 + U_HH + kb, ep);
          }
        }
        __syncwarp();
        if (e < 3 && b) all_there(m * 128 + e * 16 + (lane & 15), bar + B_ALL);
        if (e == 4 && b) all_there(m * 128 + U_HH + lane, bar + B_HH);
        if (!b && (e == 1 || e == 2)) {
#pragma unroll 1
          for (int sec = e == 1 ? 2 : 5; sec < 4 + e; sec++) fetch_mod(sec);
          if (e == 1) { if (lane == 0) mbar_arrive(bar + B_MOD); TR(50); }
        }
        if (e == 0) {
          mbar_wait(bar + B_EMPTY6 + 24, 0);
          if (HSLEEP) __nanosleep(HSLEEP);
#pragma unroll 1
          for (int w = 0; w < 4; w++) {
            const uint4* hp = gs->halo + ((m * 8 + j) * 2 + (w & 1)) * 512 + b * 256 + (w >> 1) * 128 + lane;
            uint4 q[4] = {}; uint32_t n = 0;
            while (m > 0) {
              bool ok = true;
#pragma unroll
              for (int i = 0; i < 4; i++) q[i] = ld_rlx4(hp + i * 32);
#pragma unroll
              for (int i = 0; i < 4; i++) ok = ok && q[i].y == ep && q[i].w == ep;
              if (ok) break;
              SPIN_GUARD(n);
            }
#pragma unroll
            for (int i = 0; i < 2; i++) sts128(stg + lane * 16 + (w & 1) * HALF + (w >> 1) * 1024 + i * 512, q[2 * i].x, q[2 * i + 1].x, q[2 * i].z, q[2 * i + 1].z);
          }
          __syncwarp();
          if (lane == 0) mbar_arrive(bar + B_HALO);
          if (b == 0) TR(52);
        }
      }
      if (b) { all_there(m * 128 + U_HH + 32 + (lane & 15), bar + B_HH + 8); all_there(m * 128 + U_HH + 48 + (lane & 7), bar + B_HH2); }
    }
  } else {
    const int wg = warp >> 2, wq = warp & 3, tid = threadIdx.x;
    const int g = lane >> 2, c = lane & 3;
    const int sec0 = (m >> 1) & 1, hf0 = m & 1, ks0 = (m >> 2) & 3;
    uint4 wv[8];
    uint32_t ep0; uint16_t cv_;
    asm volatile("ld.global.nc.u16 %0, [%1];" : "=h"(cv_) : "l"(cvec + ks0 * 256 + warp * 32 + lane));
    asm volatile("ld.global.u32 %0, [%1];" : "=r"(ep0) : "l"(gs->epoch + bid + 4));
    if (!extra) {
      const bf16* wp = wmod + (size_t)(ks0 * 256 + warp * 32 + (lane >> 3)) * 6144 + sec0 * 1024 + j * 128 + hf0 * 64 + (lane & 7) * 8;
#pragma unroll
      for (int i = 0; i < 8; i++) wv[i] = ldg_nc(wp + (size_t)i * 4 * 6144);
    }
    asm volatile("setmaxnreg.inc.sync.aligned.u32 232;" ::: "memory");
    if (__builtin_expect(extra, 0)) {
      const uint32_t ep = ep0 + 1;
      float sv[4];
#pragma unroll
      for (int p = 0; p < 4; p++) sv[p] = silu_c(__bfloat162float(cvec[64 * (4 * p + (lane >> 3)) + 8 * warp + (lane & 7)]));
      named_bar(2, 288);
      int s = 0, par = 0;
#pragma unroll 1
      for (int sec = 0; sec < 4; sec++) {
        float a[8] = {0, 0, 0, 0, 0, 0, 0, 0};
#pragma unroll 1
        for (int it = 0; it < 16; it++) {
          const float sc = it < 4 ? sv[0] : it < 8 ? sv[1] : it < 12 ? sv[2] : sv[3];
          mbar_wait(bar + B_FULL6 + s * 8, par);
          uint4 w[8];
#pragma unroll
          for (int i = 0; i < 8; i++) w[i] = lds128(sb + s * 32768 + (warp * 8 + i) * 512 + lane * 16);
#pragma unroll
          for (int i = 0; i < 8; i++) gemv_fma(a, w[i], __shfl_sync(~0u, sc, (it & 3) * 8 + i));
          if (lane == 0) mbar_arrive(bar + B_EMPTY6 + s * 8);
          if (++s == 6) { s = 0; par ^= 1; }
        }
        const uint32_t red = sb + STG + sec * 8192;
        sts128(red + warp * 1024 + lane * 32, __float_as_uint(a[0]), __float_as_uint(a[1]), __float_as_uint(a[2]), __float_as_uint(a[3]));
        sts128(red + warp * 1024 + lane * 32 + 16, __float_as_uint(a[4]), __float_as_uint(a[5]), __float_as_uint(a[6]), __float_as_uint(a[7]));
        named_bar(1, 256);
        float t = 0;
#pragma unroll
        for (int q = 0; q < 8; q++) t += lds32f(red + q * 1024 + tid * 4);
        st_rlx2(gs->modv + sec * 1024 + (bid + 4) * 256 + tid, __float_as_uint(t), ep);
      }
      if (tid == 0) gs->epoch[bid + 4] = ep;
      return;
    }
    if (warp == 0) TR(0);
    const int row0 = wg * 64 + wq * 16 + g;
    if (c < 2) st_rlx4(gs->stat + m * 1024 + j * 128 + row0 + c * 8, 0, 0, 0, 0);
    if (tid < 64) st_rlx2(gs->modp + ((j * 2 + sec0) * 4 + ks0) * 128 + hf0 * 64 + tid, 0, 0);
    cl_arrive_relaxed(); cl_wait();
    uint32_t ep;
    asm volatile("add.u32 %0, %1, 1;" : "=r"(ep) : "r"(ep0) : "memory");
    const float sc_ = silu_c(__uint_as_float((uint32_t)cv_ << 16));
    const uint32_t rel = mapa(bar, (lane & 1) ^ rank);
    const uint32_t stg_row = sb + STG + (wg * 64 + wq * 16 + (lane & 15)) * 128;
    const uint32_t fre = bar + B_FREE;
    Ring r4{0, 0, 0}, r6{0, 0, 0};
    auto none = [](auto) {};
    uint32_t xk[32];
    {
      float a[8] = {0, 0, 0, 0, 0, 0, 0, 0};
#pragma unroll
      for (int i = 0; i < 8; i++) gemv_fma(a, wv[i], __shfl_sync(~0u, sc_, i * 4 + (lane >> 3)));
#pragma unroll
      for (int i = 0; i < 8; i++) { a[i] += __shfl_xor_sync(~0u, a[i], 8); a[i] += __shfl_xor_sync(~0u, a[i], 16); }
      if (lane < 8) {
        sts128(sb + RED_OFF + warp * 256 + lane * 32, __float_as_uint(a[0]), __float_as_uint(a[1]), __float_as_uint(a[2]), __float_as_uint(a[3]));
        sts128(sb + RED_OFF + warp * 256 + lane * 32 + 16, __float_as_uint(a[4]), __float_as_uint(a[5]), __float_as_uint(a[6]), __float_as_uint(a[7]));
      }
      named_bar(1, 256);
      if (tid < 64) {
        float s = 0;
#pragma unroll
        for (int w = 0; w < 8; w++) s += lds32f(sb + RED_OFF + w * 256 + tid * 4);
        st_rlx2(gs->modp + ((j * 2 + sec0) * 4 + ks0) * 128 + hf0 * 64 + tid, __float_as_uint(s), ep);
      }
      if (warp == 0) TR(1);
      float v[64];
      mbar_wait(bar + B_X, 0); mbar_wait(bar + B_X + 8, 0);
#pragma unroll
      for (int i = 0; i < 16; i += 2) {
        uint32_t w0, w1, w2, w3;
        ldsm4(stg_row + (i >> 3) * BLK + ((((i & 7) + (lane >> 4)) ^ (lane & 7)) << 4), w0, w1, w2, w3);
        xk[2 * i] = w0; xk[2 * i + 1] = w1; xk[2 * i + 2] = w2; xk[2 * i + 3] = w3;
        v[4 * i] = bf_lo(w0); v[4 * i + 1] = bf_hi(w0); v[4 * i + 2] = bf_lo(w1); v[4 * i + 3] = bf_hi(w1);
        v[4 * i + 4] = bf_lo(w2); v[4 * i + 5] = bf_hi(w2); v[4 * i + 6] = bf_lo(w3); v[4 * i + 7] = bf_hi(w3);
      }
      ln_publish(v, gs->stat + m * 1024, j, row0, lane, ep);
      if (warp == 0) TR(2);
      { uint32_t* step0 = STEP0 + 168; TRW(0); }
      mod_store(sb, tid >> 7, tid & 127, mod_gather(gs->modp + (j * 2 + (tid >> 7)) * 512 + (tid & 127), ep));
      named_bar(1, 256);
      if (warp == 0) TR(3);
      ln_apply(v, gs->stat + m * 1024, row0, ep, sb, 0, 1, stg_row, wg, lane, STEP0 + 168);
      named_bar(1, 256);
    }
    if (warp == 0) TR(4);
    { uint32_t* step0 = STEP0 + 168; TRW(5); }
    {
      uint32_t kf[32], vf[32], pv[32];
      const bool first = wq == 0 && m == 0;
      const uint32_t xa = sb + STG + wg * HALF + wq * 2048 + lane * 16;
      {
        float acc[128];
        mainloop<256, 4, 0, 0>(acc, 16, true, r4, sb, wg, lane, rel, STEP0 + 0, none, none, [&] {
          mbar_wait(fre + 8, 0);
          if (c < 2) st_rlx4(gs->stat + (16 + m) * 1024 + j * 128 + row0 + c * 8, 0, 0, 0, 0);
        });
        if (warp == 0) TR(5);
#pragma unroll
        for (int i = 0; i < 32; i++) { kf[i] = pack2(acc[2 * i], acc[2 * i + 1]); vf[i] = pack2(acc[64 + 2 * i], acc[65 + 2 * i]); }
      }
      if (warp == 0) TR(6);
      float acc[64];
      constexpr int QP = 2;
      mainloop<128, 6, 8 / QP, 0>(acc, 16, false, r6, sb, wg, lane, rel, STEP0 + 16, [&](auto ic) {
        constexpr int q = (ic.v - 1) * QP;
#pragma unroll
        for (int i = 4 * q; i < 4 * (q + QP); i++) vf[i] = movm(vf[i]);
        if (wq == 3) {
          if (m < 15) {
            uint4* hp = gs->halo + (((m + 1) * 8 + j) * 2 + wg) * 512 + lane;
#pragma unroll
            for (int i = 2 * q; i < 2 * (q + QP); i++) st_rlx4(hp + i * 32, kf[2 * i + 1], ep, vf[2 * i + 1], ep);
          }
        } else {
#pragma unroll
          for (int i = q; i < q + QP; i++) sts128(xa + 2048 + (i >> 2) * BLK + (i & 3) * 512, kf[4 * i + 1], kf[4 * i + 3], vf[4 * i + 1], vf[4 * i + 3]);
        }
      }, none, [&] {
        named_bar(2 + wg, 128);
        if (wq == 0) mbar_wait(bar + B_HALO, 0);
#pragma unroll
        for (int i = 0; i < 8; i++) {
          uint4 q = lds128(xa + (i >> 2) * BLK + (i & 3) * 512);
          pv[4 * i] = q.x; pv[4 * i + 1] = q.y; pv[4 * i + 2] = q.z; pv[4 * i + 3] = q.w;
        }
        __syncwarp();
      });
      if (warp == 0) TR(7);
      { uint32_t* step0 = STEP0 + 184; TRW(0); }
      int gz = g;
#pragma unroll
      for (int b = 0; b < 2; b++) {
        const bool up0 = 2 * c > gz, up1 = 2 * c + 1 > gz;
        const uint32_t mup = (up0 ? 0xffffu : 0u) | (up1 ? 0xffff0000u : 0u);
        float l[2][4], mx[4];
#pragma unroll
        for (int h = 0; h < 2; h++) {
          uint32_t q[8];
          const int k = 16 * b + 8 * h;
#pragma unroll
          for (int i = 0; i < 8; i++) q[i] = pack2(acc[2 * k + 2 * i], acc[2 * k + 2 * i + 1]);
          float s0[4], s1[4], s2[4];
          mma16z(s0, q[0], q[1], q[2], q[3], pv[k], pv[k + 1]); mma16z(s1, q[0], q[1], q[2], q[3], kf[k], kf[k + 2]); mma16z(s2, q[0], q[1], q[2], q[3], kf[k + 1], kf[k + 3]);
          mma16(s0, q[4], q[5], q[6], q[7], pv[k + 4], pv[k + 5]); mma16(s1, q[4], q[5], q[6], q[7], kf[k + 4], kf[k + 6]); mma16(s2, q[4], q[5], q[6], q[7], kf[k + 5], kf[k + 7]);
          if (first) { s0[0] = -INFINITY; s0[1] = -INFINITY; }
          l[h][0] = up0 ? s0[0] : s1[0]; l[h][1] = up1 ? s0[1] : s1[1]; l[h][2] = up0 ? s1[2] : s2[2]; l[h][3] = up1 ? s1[3] : s2[3];
          mx[2 * h] = fmaxf(l[h][0], l[h][1]); mx[2 * h + 1] = fmaxf(l[h][2], l[h][3]);
        }
#pragma unroll
        for (int o = 1; o < 4; o <<= 1) {
#pragma unroll
          for (int h = 0; h < 4; h++) mx[h] = fmaxf(mx[h], __shfl_xor_sync(~0u, mx[h], o));
        }
#pragma unroll
        for (int h = 0; h < 2; h++) {
          const float n0 = -mx[2 * h] * SCL, n1 = -mx[2 * h + 1] * SCL;
          const uint32_t pa = pack2(ex2(fmaf(l[h][0], SCL, n0)), ex2(fmaf(l[h][1], SCL, n0))), pb = pack2(ex2(fmaf(l[h][2], SCL, n1)), ex2(fmaf(l[h][3], SCL, n1)));
          float sm[4];
          mma8z(sm, pa, pb, 0x3f803f80u);
          const float ia = rcp(sm[0]), ib = rcp(sm[2]);
#pragma unroll
          for (int i = 8 * b + 4 * h; i < 8 * b + 4 * h + 4; i += 2) {
            uint32_t of[4];
#pragma unroll
            for (int d = 0; d < 2; d++) {
              float o[4];
              mma16z(o, pa & ~mup, pb & mup, 0u, pb & ~mup, vf[2 * (i + d)], vf[2 * (i + d) + 1]);
              mma8(o, pa & mup, 0u, pv[2 * i + 2 + d]);
              of[2 * d] = pack2(o[0] * ia, o[1] * ia); of[2 * d + 1] = pack2(o[2] * ib, o[3] * ib);
            }
            stsm4(stg_row + b * BLK + ((((i & 7) + (lane >> 4)) ^ (lane & 7)) << 4), of[0], of[1], of[2], of[3]);
          }
        }
        stage_done(sb, wg, b, lane);
        { uint32_t* step0 = STEP0 + 184; TRW(1 + b); }
        if (b == 0) gz += __float_as_uint(lds32f(bar + ZERO));
      }
      named_bar(1, 256);
      if (warp == 0) TR(8);
      { uint32_t* step0 = STEP0 + 184; TRW(3); }
    }
    uint32_t pk[64];
    {
      float acc[64];
      mainloop<128, 6, 0, WOLAG>(acc, 16, true, r6, sb, wg, lane, rel, STEP0 + 32, none, none, [&] {
        if (WOLAG && wg == 0 && lane == 0) mbar_arrive(bar + B_LAG);
        mbar_wait(bar + B_MOD, 0); mbar_wait(fre + 8, 1);
        load_vec(pk + 32, sb, 2, 0, lane); load_vec(pk + 40, sb, 2, 1, lane);
#pragma unroll
        for (int i = 0; i < 32; i++) { pk[i] = xk[i]; asm volatile("" : "+r"(pk[i])); }
      });
      if (warp == 0) TR(9);
      { uint32_t* step0 = STEP0 + 176; TRW(0); }
#pragma unroll
      for (int i = 0; i < 32; i++) {
        acc[2 * i] = fmaf(acc[2 * i], bf_lo(pk[32 + (i >> 1)]), bf_lo(pk[i]));
        acc[2 * i + 1] = fmaf(acc[2 * i + 1], bf_hi(pk[32 + (i >> 1)]), bf_hi(pk[i]));
      }
      ln_publish(acc, gs->stat + (16 + m) * 1024, j, row0, lane, ep);
      if (warp == 0) TR(36);
      mbar_wait(bar + B_FULL6 + 16, 1);
      if (lane < 2) mbar_arrive_cl(rel + B_EMPTY6 + 16);
      ring_next<6>(r6);
#pragma unroll
      for (int i = 0; i < 32; i++) { pk[i] = pack2(acc[2 * i], acc[2 * i + 1]); pk[32 + i] = 0; }
      ln_apply(acc, gs->stat + (16 + m) * 1024, row0, ep, sb, 3, 4, stg_row, wg, lane, STEP0 + 176);
      named_bar(1, 256);
      if (warp == 0) TR(11);
      { uint32_t* step0 = STEP0 + 176; TRW(5); }
    }
    auto swiglu = [&](int q, int uo, int par) {
      if ((q & 3) == 0 && par >= 0) mbar_wait(fre + 2 * q, par);
      uint32_t w[4];
#pragma unroll
      for (int u = 0; u < 4; u++) w[u] = silu_mul2(pk[4 * q + u], pk[uo + 4 * q + u]);
      stsm4(stg_row + (q >> 2) * BLK + ((((2 * q & 7) + (lane >> 4)) ^ (lane & 7)) << 4), w[0], w[1], w[2], w[3]);
    };
    r4.s = r4.wrap = 2;
#pragma unroll 1
    for (int t = 0; t < 3; t++) {
      float acc[128];
      mainloop<256, 4, 5, 0>(acc, 16, t == 0, r4, sb, wg, lane, rel, STEP0 + 48 + 16 * t, [&](auto ic) {
        if (t) {
          if (ic.v == 3 || ic.v == 5) stage_done(sb, wg, ic.v >> 2, lane);
          if (ic.v < 5) { swiglu(2 * ic.v - 2, 32, ~t & 1); swiglu(2 * ic.v - 1, 32, 0); }
        }
      }, [&](int it) {
#pragma unroll
        for (int i = 0; i < 8; i++)
          if (t == 0 && it == 8 + i) gs->x1[bid * 2048 + (i >> 2) * 1024 + warp * 128 + (i & 3) * 32 + lane] = make_uint4(pk[4 * i], pk[4 * i + 1], pk[4 * i + 2], pk[4 * i + 3]);
      }, [&] { if (t == 0) fence_async_global(); else if (t == 2) mbar_wait(bar + B_X, 1); });
      if (warp == 0) TR(12 + 2 * t);
#pragma unroll
      for (int i = 0; i < 64; i++) pk[i] = pack2(acc[2 * i], acc[2 * i + 1]);
      if (warp == 0) TR(13 + 2 * t);
    }
    uint32_t x1[32];
    {
      float acc[64];
      mainloop<128, 6, 12, 0>(acc, 16, false, r6, sb, wg, lane, rel, STEP0 + 96, [&](auto ic) {
        constexpr int b = ic.v > 6, q = ic.v - 6 * b;
        if (q == 1) {
#pragma unroll
          for (int i = 4 * b; i < 4 * b + 4; i++) { const uint4 x = lds128(sb + STG + b * BLK + warp * 2048 + (i & 3) * 512 + lane * 16); x1[4 * i] = x.x; x1[4 * i + 1] = x.y; x1[4 * i + 2] = x.z; x1[4 * i + 3] = x.w; }
          __syncwarp();
        } else if (q < 6) swiglu(4 * b + q - 2, 32, -1);
        else stage_done(sb, wg, b, lane);
      }, none, [] {});
      if (warp == 0) TR(18);
#pragma unroll
      for (int i = 0; i < 32; i++) pk[i] = pack2(acc[2 * i], acc[2 * i + 1]);
      if (warp == 0) TR(19);
    }
    {
      float acc[64];
      mainloop<128, 6, 5, TAILLAG>(acc, 56, false, r6, sb, wg, lane, rel, STEP0 + 112, [&](auto ic) {
        if (ic.v == 5) stage_done(sb, wg, 0, lane); else swiglu(ic.v - 1, 16, 1);
      }, none, [&] {
        if (TAILLAG && wg == 0 && lane == 0) mbar_arrive(bar + B_LAG);
        load_vec(pk + 32, sb, 5, 0, lane); load_vec(pk + 40, sb, 5, 1, lane);
        mbar_wait(fre, 0); mbar_wait(fre + 8, 1);
      });
      __syncwarp();
      cl_arrive_relaxed();
      if (warp == 0) TR(20);
#pragma unroll
      for (int i = 0; i < 16; i += 2) {
        uint32_t w[4];
#pragma unroll
        for (int u = 0; u < 4; u++) {
          const int q = 2 * i + u;
          w[u] = pack2(fmaf(acc[2 * q], bf_lo(pk[32 + (q >> 1)]), bf_lo(x1[q])), fmaf(acc[2 * q + 1], bf_hi(pk[32 + (q >> 1)]), bf_hi(x1[q])));
        }
        stsm4(stg_row + (i >> 3) * BLK + ((((i & 7) + (lane >> 4)) ^ (lane & 7)) << 4), w[0], w[1], w[2], w[3]);
        if ((i & 7) == 6) {
          fence_async_smem();
          named_bar(2 + wg, 128);
          if (wq == 0 && elect()) { tma_store_3d(&maps.out, sb + STG + (i >> 3) * BLK + wg * HALF, j * 128 + (i >> 3) * 64, m * 64, wg); bulk_commit(); }
          if (i < 8) x1[16] |= __float_as_uint(lds32f(bar + ZERO));
        }
      }
      if (wq == 0) bulk_wait_read();
      if (wq == 0) TR(40 + wg);
      if (tid == 0) gs->epoch[bid + 4] = ep;
      if (warp == 0) TR(21);
      cl_wait();
    }
  }
}

typedef CUresult (*EncodeFn)(CUtensorMap*, CUtensorMapDataType, cuuint32_t, void*, const cuuint64_t*, const cuuint64_t*, const cuuint32_t*, const cuuint32_t*,
                             CUtensorMapInterleave, CUtensorMapSwizzle, CUtensorMapL2promotion, CUtensorMapFloatOOBfill);

void make_map(EncodeFn fn, CUtensorMap* mp, const void* base, uint64_t d0, uint64_t d1, uint64_t d2, uint64_t s1, uint64_t s2, uint32_t b2, uint32_t b0 = 64) {
  cuuint64_t d[3] = {d0, d1, d2}, s[2] = {s1, s2};
  cuuint32_t b[3] = {b0, 64, b2}, e[3] = {1, 1, 1};
  fn(mp, CU_TENSOR_MAP_DATA_TYPE_BFLOAT16, 3, (void*)base, d, s, b, e, CU_TENSOR_MAP_INTERLEAVE_NONE, b0 == 64 ? CU_TENSOR_MAP_SWIZZLE_128B : CU_TENSOR_MAP_SWIZZLE_NONE,
     CU_TENSOR_MAP_L2_PROMOTION_L2_128B, CU_TENSOR_MAP_FLOAT_OOB_FILL_NONE);
}

__global__ void probe_kernel() {}
int max_clusters(int size) {
  cudaLaunchConfig_t cfg = {};
  cudaLaunchAttribute at;
  at.id = cudaLaunchAttributeClusterDimension; at.val.clusterDim.x = size; at.val.clusterDim.y = 1; at.val.clusterDim.z = 1;
  cfg.gridDim = dim3(size * 66); cfg.blockDim = dim3(384); cfg.dynamicSmemBytes = SMEM_BYTES; cfg.attrs = &at; cfg.numAttrs = 1;
  int n = 0;
  if (cudaOccupancyMaxActiveClusters(&n, probe_kernel, &cfg) != cudaSuccess) { cudaGetLastError(); return 0; }
  return n;
}

}

extern "C" void kernel_launch(void* const* d_in, const int* in_sizes, int n_in, void* d_out, int out_size) {
  static EncodeFn fn = nullptr;
  static int by_sm = 0;
  static Scratch* gs = nullptr;
  if (!fn) {
    void* p = nullptr; cudaDriverEntryPointQueryResult q;
    cudaGetDriverEntryPoint("cuTensorMapEncodeTiled", &p, cudaEnableDefault, &q);
    fn = (EncodeFn)p;
    cudaFuncSetAttribute(fused_kernel, cudaFuncAttributeMaxDynamicSharedMemorySize, SMEM_BYTES);
    int dev = 0, sms = 0;
    cudaGetSymbolAddress((void**)&gs, g_scratch);
    cudaGetDevice(&dev);
    cudaDeviceGetAttribute(&sms, cudaDevAttrMultiProcessorCount, dev);
    cudaFuncSetAttribute(probe_kernel, cudaFuncAttributeMaxDynamicSharedMemorySize, SMEM_BYTES);
    by_sm = BYSM && sms == 132 && max_clusters(2) == 66 && max_clusters(4) == 30 && max_clusters(6) == 17 && max_clusters(8) == 15;
  }
  Maps mp;
  make_map(fn, &mp.x, d_in[0], D_, S_ / 2, 2, 4096, 2048, 2);
  make_map(fn, &mp.out, d_out, D_, S_ / 2, 2, 4096, 2048, 1);
  make_map(fn, &mp.wqkv, d_in[1], 64, D_, 3 * D_ / 64, 3 * D_ * 2, 128, 2);
  make_map(fn, &mp.wo, d_in[2], 64, D_, D_ / 64, D_ * 2, 128, 2);
  make_map(fn, &mp.w1, d_in[4], 64, D_, F_ / 64, F_ * 2, 128, 2);
  make_map(fn, &mp.w3, d_in[5], 64, D_, F_ / 64, F_ * 2, 128, 2);
  make_map(fn, &mp.w1s, d_in[4], 64, D_, F_ / 64, F_ * 2, 128, 1);
  make_map(fn, &mp.w3s, d_in[5], 64, D_, F_ / 64, F_ * 2, 128, 1);
  make_map(fn, &mp.w2, d_in[6], 64, F_, D_ / 64, D_ * 2, 128, 2);
  make_map(fn, &mp.wmod, d_in[8], 256, D_, 24, 6 * D_ * 2, 512, 1, 256);
  fused_kernel<<<132, 384, SMEM_BYTES>>>((const bf16*)d_in[7], (const bf16*)d_in[8], gs, by_sm, mp);
}
```

```cpp
#include <cuda_runtime.h>
#include <cuda_bf16.h>
#include <cuda.h>
#include <stdint.h>

typedef __nv_bfloat16 bf16;

#define NPIECE 4
#define PSLEEP 300
#define XSLEEP 4000
#define XDELAY 2000
#define TAILLAG 5
#define HSLEEP 400
#define B1D 900
#define B1P 3500
#define WOLAG 2
#define B1P2 3200
#define QPV 2
#define BYSM 1
namespace {

constexpr int S_ = 2048, D_ = 1024, F_ = 3584;
constexpr int BLK = 16384;
constexpr int HALF = 8192;
constexpr int RING = 196608;
constexpr int STG = RING;
constexpr int MISC = RING + 2 * BLK;
constexpr int SMEM_BYTES = MISC + 3072;
constexpr int B_FULL4 = 0, B_EMPTY4 = 32, B_FULL6 = 64, B_EMPTY6 = 112, B_RDY = 160, B_FREE = 176, B_LAG = 192, B_X = 208, B_MOD = 224, B_HALO = 232, B_HH = 256, B_ALL = 272, B_HH2 = 288, ZERO = 296;
constexpr int MODV = 512;
constexpr int RED_OFF = 0;
constexpr float SCL = 0.17677669529663687f * 1.4426950408889634f;
constexpr int U_HH = 64;

struct Maps { CUtensorMap x, out, wqkv, wo, w1, w3, w1s, w3s, w2, wmod; };

struct Scratch {
  uint4 h[16 * 16 * 1024];
  uint4 o[16 * 16 * 1024];
  uint4 hh[16 * 56 * 1024];
  uint4 x1[128 * 8 * 256];
  uint4 stat[2 * 16 * 8 * 128];
  uint4 halo[16 * 8 * 2 * 512];
  uint2 modp[8 * 2 * 4 * 128];
  uint2 modv[4 * 1024];
  uint32_t flag[16 * 128];
  uint32_t epoch[132];
};
__device__ __align__(1024) Scratch g_scratch;
#define TR(i)
#define TRS(i)
#define STEP0 gs->flag
#define TRW(i) (void)step0

__device__ __forceinline__ void bail() { asm volatile("st.global.u32 [%0], %1;" :: "l"(0ull), "r"(0) : "memory"); }
__device__ __forceinline__ uint32_t smem_u32(const void* p) { return (uint32_t)__cvta_generic_to_shared(p); }
__device__ __forceinline__ void mbar_init(uint32_t bar, uint32_t cnt) { asm volatile("mbarrier.init.shared::cta.b64 [%0], %1;" :: "r"(bar), "r"(cnt) : "memory"); }
__device__ __forceinline__ void mbar_expect_tx(uint32_t bar, uint32_t bytes) { asm volatile("mbarrier.arrive.expect_tx.shared::cta.b64 _, [%0], %1;" :: "r"(bar), "r"(bytes) : "memory"); }
__device__ __forceinline__ void mbar_arrive(uint32_t bar) { asm volatile("mbarrier.arrive.shared::cta.b64 _, [%0];" :: "r"(bar) : "memory"); }
__device__ __forceinline__ void mbar_arrive_cl(uint32_t cl_addr) { asm volatile("mbarrier.arrive.shared::cluster.b64 _, [%0];" :: "r"(cl_addr) : "memory"); }
__device__ __forceinline__ uint32_t mapa(uint32_t addr, uint32_t cta) { uint32_t r; asm("mapa.shared::cluster.u32 %0, %1, %2;" : "=r"(r) : "r"(addr), "r"(cta)); return r; }
__device__ __forceinline__ void mbar_wait(uint32_t bar, uint32_t parity) {
  asm volatile("{\n.reg .pred p;\n.reg .b32 n;\n.reg .b64 z;\nmov.b32 n, 0;\nmov.b64 z, 0;\n"
               "W: add.u32 n, n, 1;\nsetp.gt.u32 p, n, 0x400000;\n@p st.global.u32 [z], n;\n"
               "mbarrier.try_wait.parity.shared::cta.b64 p, [%0], %1;\n@!p bra W;\n}" :: "r"(bar), "r"(parity) : "memory");
}
__device__ __forceinline__ void tma_3d(uint32_t dst, const CUtensorMap* m, uint32_t bar, int c0, int c1, int c2) {
  asm volatile("cp.async.bulk.tensor.3d.shared::cluster.global.mbarrier::complete_tx::bytes [%0], [%1, {%3, %4, %5}], [%2];" :: "r"(dst), "l"(m), "r"(bar), "r"(c0), "r"(c1), "r"(c2) : "memory");
}
__device__ __forceinline__ void tma_store_3d(const CUtensorMap* m, uint32_t src, int c0, int c1, int c2) {
  asm volatile("cp.async.bulk.tensor.3d.global.shared::cta.bulk_group [%0, {%2, %3, %4}], [%1];" :: "l"(m), "r"(src), "r"(c0), "r"(c1), "r"(c2) : "memory");
}
__device__ __forceinline__ void bulk_ld(uint32_t dst, const void* src, uint32_t bytes, uint32_t bar) {
  asm volatile("cp.async.bulk.shared::cluster.global.mbarrier::complete_tx::bytes [%0], [%1], %2, [%3];" :: "r"(dst), "l"(src), "r"(bytes), "r"(bar) : "memory");
}
__device__ __forceinline__ void bulk_ld_mc(uint32_t dst, const void* src, uint32_t bytes, uint32_t bar) {
  asm volatile("cp.async.bulk.shared::cluster.global.mbarrier::complete_tx::bytes.multicast::cluster [%0], [%1], %2, [%3], %4;" :: "r"(dst), "l"(src), "r"(bytes), "r"(bar), "h"((uint16_t)3) : "memory");
}
__device__ __forceinline__ void bulk_push(uint32_t dst_cl, uint32_t src, uint32_t bytes, uint32_t bar_cl) {
  asm volatile("cp.async.bulk.shared::cluster.shared::cta.mbarrier::complete_tx::bytes [%0], [%1], %2, [%3];" :: "r"(dst_cl), "r"(src), "r"(bytes), "r"(bar_cl) : "memory");
}
__device__ __forceinline__ void bulk_st(void* dst, uint32_t src, uint32_t bytes) {
  asm volatile("cp.async.bulk.global.shared::cta.bulk_group [%0], [%1], %2;" :: "l"(dst), "r"(src), "r"(bytes) : "memory");
}
__device__ __forceinline__ void bulk_commit() { asm volatile("cp.async.bulk.commit_group;" ::: "memory"); }
__device__ __forceinline__ void bulk_wait_read() { asm volatile("cp.async.bulk.wait_group.read 0;" ::: "memory"); }
__device__ __forceinline__ void bulk_wait_all() { asm volatile("cp.async.bulk.wait_group 0;" ::: "memory"); }
__device__ __forceinline__ void fence_async_global() { asm volatile("fence.proxy.async.global;" ::: "memory"); }
__device__ __forceinline__ void fence_async_smem() { asm volatile("fence.proxy.async.shared::cta;" ::: "memory"); }
__device__ __forceinline__ void wg_arrive() { asm volatile("wgmma.fence.sync.aligned;" ::: "memory"); }
__device__ __forceinline__ void wg_commit() { asm volatile("wgmma.commit_group.sync.aligned;" ::: "memory"); }
template <int N> __device__ __forceinline__ void wg_wait() { asm volatile("wgmma.wait_group.sync.aligned %0;" :: "n"(N) : "memory"); }
__device__ __forceinline__ void cl_arrive_relaxed() { asm volatile("barrier.cluster.arrive.relaxed.aligned;" ::: "memory"); }
__device__ __forceinline__ void cl_wait() { asm volatile("barrier.cluster.wait.acquire.aligned;" ::: "memory"); }
__device__ __forceinline__ bool elect() { uint32_t p; asm volatile("{\n.reg .pred p;\nelect.sync _|p, 0xffffffff;\nselp.u32 %0, 1, 0, p;\n}" : "=r"(p)); return p; }
__device__ __forceinline__ void named_bar(int id, int n) { asm volatile("bar.sync %0, %1;" :: "r"(id), "r"(n) : "memory"); }
__device__ __forceinline__ uint32_t pack2(float lo, float hi) { uint32_t r; asm("cvt.rn.bf16x2.f32 %0, %1, %2;" : "=r"(r) : "f"(hi), "f"(lo)); return r; }
__device__ __forceinline__ float bf_lo(uint32_t w) { return __uint_as_float(w << 16); }
__device__ __forceinline__ float bf_hi(uint32_t w) { return __uint_as_float(w & 0xffff0000u); }
__device__ __forceinline__ float bf_round(float v) { return __bfloat162float(__float2bfloat16_rn(v)); }
__device__ __forceinline__ void stsm4(uint32_t addr, uint32_t a, uint32_t b, uint32_t c, uint32_t d) {
  asm volatile("stmatrix.sync.aligned.m8n8.x4.shared.b16 [%0], {%1, %2, %3, %4};" :: "r"(addr), "r"(a), "r"(b), "r"(c), "r"(d) : "memory");
}
__device__ __forceinline__ void ldsm4(uint32_t addr, uint32_t& a, uint32_t& b, uint32_t& c, uint32_t& d) {
  asm volatile("ldmatrix.sync.aligned.m8n8.x4.shared.b16 {%0, %1, %2, %3}, [%4];" : "=r"(a), "=r"(b), "=r"(c), "=r"(d) : "r"(addr) : "memory");
}
__device__ __forceinline__ uint32_t movm(uint32_t a) { uint32_t r; asm volatile("movmatrix.sync.aligned.m8n8.trans.b16 %0, %1;" : "=r"(r) : "r"(a)); return r; }
__device__ __forceinline__ void mma16(float (&d)[4], uint32_t a0, uint32_t a1, uint32_t a2, uint32_t a3, uint32_t b0, uint32_t b1) {
  asm("mma.sync.aligned.m16n8k16.row.col.f32.bf16.bf16.f32 {%0,%1,%2,%3}, {%4,%5,%6,%7}, {%8,%9}, {%0,%1,%2,%3};"
               : "+f"(d[0]), "+f"(d[1]), "+f"(d[2]), "+f"(d[3]) : "r"(a0), "r"(a1), "r"(a2), "r"(a3), "r"(b0), "r"(b1));
}
__device__ __forceinline__ void mma16z(float (&d)[4], uint32_t a0, uint32_t a1, uint32_t a2, uint32_t a3, uint32_t b0, uint32_t b1) {
  asm("mma.sync.aligned.m16n8k16.row.col.f32.bf16.bf16.f32 {%0,%1,%2,%3}, {%4,%5,%6,%7}, {%8,%9}, {%10,%10,%10,%10};"
      : "=f"(d[0]), "=f"(d[1]), "=f"(d[2]), "=f"(d[3]) : "r"(a0), "r"(a1), "r"(a2), "r"(a3), "r"(b0), "r"(b1), "f"(0.f));
}
__device__ __forceinline__ void mma8z(float (&d)[4], uint32_t a0, uint32_t a1, uint32_t b0) {
  asm("mma.sync.aligned.m16n8k8.row.col.f32.bf16.bf16.f32 {%0,%1,%2,%3}, {%4,%5}, {%6}, {%7,%7,%7,%7};"
      : "=f"(d[0]), "=f"(d[1]), "=f"(d[2]), "=f"(d[3]) : "r"(a0), "r"(a1), "r"(b0), "f"(0.f));
}
__device__ __forceinline__ void mma8(float (&d)[4], uint32_t a0, uint32_t a1, uint32_t b0) {
  asm("mma.sync.aligned.m16n8k8.row.col.f32.bf16.bf16.f32 {%0,%1,%2,%3}, {%4,%5}, {%6}, {%0,%1,%2,%3};"
               : "+f"(d[0]), "+f"(d[1]), "+f"(d[2]), "+f"(d[3]) : "r"(a0), "r"(a1), "r"(b0));
}
__device__ __forceinline__ uint4 lds128(uint32_t a) { uint4 v; asm volatile("ld.shared.v4.u32 {%0,%1,%2,%3}, [%4];" : "=r"(v.x), "=r"(v.y), "=r"(v.z), "=r"(v.w) : "r"(a) : "memory"); return v; }
__device__ __forceinline__ void sts128(uint32_t a, uint32_t x, uint32_t y, uint32_t z, uint32_t w) { asm volatile("st.shared.v4.u32 [%0], {%1,%2,%3,%4};" :: "r"(a), "r"(x), "r"(y), "r"(z), "r"(w) : "memory"); }
__device__ __forceinline__ float lds32f(uint32_t a) { float v; asm volatile("ld.shared.f32 %0, [%1];" : "=f"(v) : "r"(a) : "memory"); return v; }
__device__ __forceinline__ void sts16(uint32_t a, bf16 v) { asm volatile("st.shared.b16 [%0], %1;" :: "r"(a), "h"(__bfloat16_as_ushort(v)) : "memory"); }
__device__ __forceinline__ uint4 ldg_nc(const void* p) { uint4 v; asm volatile("ld.global.nc.L1::no_allocate.v4.u32 {%0,%1,%2,%3}, [%4];" : "=r"(v.x), "=r"(v.y), "=r"(v.z), "=r"(v.w) : "l"(p)); return v; }
__device__ __forceinline__ uint4 ld_rlx4(const uint4* p) {
  unsigned long long a, b; asm volatile("ld.relaxed.gpu.global.v2.b64 {%0,%1}, [%2];" : "=l"(a), "=l"(b) : "l"(p) : "memory");
  return make_uint4((uint32_t)a, (uint32_t)(a >> 32), (uint32_t)b, (uint32_t)(b >> 32));
}
__device__ __forceinline__ uint2 ld_rlx2(const uint2* p) { unsigned long long a; asm volatile("ld.relaxed.gpu.global.b64 %0, [%1];" : "=l"(a) : "l"(p) : "memory"); return make_uint2((uint32_t)a, (uint32_t)(a >> 32)); }
__device__ __forceinline__ void st_rlx4(uint4* p, uint32_t x, uint32_t y, uint32_t z, uint32_t w) {
  asm volatile("st.relaxed.gpu.global.v2.b64 [%0], {%1,%2};" :: "l"(p), "l"((unsigned long long)x | ((unsigned long long)y << 32)), "l"((unsigned long long)z | ((unsigned long long)w << 32)) : "memory");
}
__device__ __forceinline__ void st_rlx2(uint2* p, uint32_t x, uint32_t y) { asm volatile("st.relaxed.gpu.global.b64 [%0], %1;" :: "l"(p), "l"((unsigned long long)x | ((unsigned long long)y << 32)) : "memory"); }
__device__ __forceinline__ void st_release(uint32_t* p, uint32_t v) { asm volatile("st.release.gpu.global.u32 [%0], %1;" :: "l"(p), "r"(v) : "memory"); }
__device__ __forceinline__ uint32_t ld_acquire(const uint32_t* p) { uint32_t v; asm volatile("ld.acquire.gpu.global.u32 %0, [%1];" : "=r"(v) : "l"(p) : "memory"); return v; }
__device__ __forceinline__ void prefetch_map(const CUtensorMap* m) { asm volatile("prefetch.tensormap [%0];" :: "l"(m) : "memory"); }
__device__ __forceinline__ float rcp(float x) { float r; asm("rcp.approx.ftz.f32 %0, %1;" : "=f"(r) : "f"(x)); return r; }
__device__ __forceinline__ float ex2(float x) { float r; asm("ex2.approx.ftz.f32 %0, %1;" : "=f"(r) : "f"(x)); return r; }
__device__ __forceinline__ float tanh_fast(float x) { float r; asm("tanh.approx.f32 %0, %1;" : "=f"(r) : "f"(x)); return r; }
#define SPIN_GUARD(n) if (++(n) > (1u << 24)) bail()

__device__ __forceinline__ void wgmma_n128(float (&d)[64], uint64_t da, uint64_t db) {
  asm volatile("wgmma.mma_async.sync.aligned.m64n128k16.f32.bf16.bf16 "
    "{%0, %1, %2, %3, %4, %5, %6, %7, %8, %9, %10, %11, %12, %13, %14, %15, %16, %17, %18, %19, %20, %21, %22, %23, %24, %25, %26, %27, %28, %29, %30, %31, %32, %33, %34, %35, %36, %37, %38, %39, %40, %41, %42, %43, %44, %45, %46, %47, %48, %49, %50, %51, %52, %53, %54, %55, %56, %57, %58, %59, %60, %61, %62, %63}, "
    "%64, %65, 1, 1, 1, 0, 1;\n"
    : "+f"(d[0]), "+f"(d[1]), "+f"(d[2]), "+f"(d[3]), "+f"(d[4]), "+f"(d[5]), "+f"(d[6]), "+f"(d[7]), "+f"(d[8]), "+f"(d[9]), "+f"(d[10]), "+f"(d[11]), "+f"(d[12]), "+f"(d[13]), "+f"(d[14]), "+f"(d[15]), "+f"(d[16]), "+f"(d[17]), "+f"(d[18]), "+f"(d[19]), "+f"(d[20]), "+f"(d[21]), "+f"(d[22]), "+f"(d[23]), "+f"(d[24]), "+f"(d[25]), "+f"(d[26]), "+f"(d[27]), "+f"(d[28]), "+f"(d[29]), "+f"(d[30]), "+f"(d[31]), "+f"(d[32]), "+f"(d[33]), "+f"(d[34]), "+f"(d[35]), "+f"(d[36]), "+f"(d[37]), "+f"(d[38]), "+f"(d[39]), "+f"(d[40]), "+f"(d[41]), "+f"(d[42]), "+f"(d[43]), "+f"(d[44]), "+f"(d[45]), "+f"(d[46]), "+f"(d[47]), "+f"(d[48]), "+f"(d[49]), "+f"(d[50]), "+f"(d[51]), "+f"(d[52]), "+f"(d[53]), "+f"(d[54]), "+f"(d[55]), "+f"(d[56]), "+f"(d[57]), "+f"(d[58]), "+f"(d[59]), "+f"(d[60]), "+f"(d[61]), "+f"(d[62]), "+f"(d[63])
    : "l"(da), "l"(db));
}
__device__ __forceinline__ void wgmma_n128_first(float (&d)[64], uint64_t da, uint64_t db) {
  asm volatile("wgmma.mma_async.sync.aligned.m64n128k16.f32.bf16.bf16 "
    "{%0, %1, %2, %3, %4, %5, %6, %7, %8, %9, %10, %11, %12, %13, %14, %15, %16, %17, %18, %19, %20, %21, %22, %23, %24, %25, %26, %27, %28, %29, %30, %31, %32, %33, %34, %35, %36, %37, %38, %39, %40, %41, %42, %43, %44, %45, %46, %47, %48, %49, %50, %51, %52, %53, %54, %55, %56, %57, %58, %59, %60, %61, %62, %63}, "
    "%64, %65, 0, 1, 1, 0, 1;\n"
    : "=f"(d[0]), "=f"(d[1]), "=f"(d[2]), "=f"(d[3]), "=f"(d[4]), "=f"(d[5]), "=f"(d[6]), "=f"(d[7]), "=f"(d[8]), "=f"(d[9]), "=f"(d[10]), "=f"(d[11]), "=f"(d[12]), "=f"(d[13]), "=f"(d[14]), "=f"(d[15]), "=f"(d[16]), "=f"(d[17]), "=f"(d[18]), "=f"(d[19]), "=f"(d[20]), "=f"(d[21]), "=f"(d[22]), "=f"(d[23]), "=f"(d[24]), "=f"(d[25]), "=f"(d[26]), "=f"(d[27]), "=f"(d[28]), "=f"(d[29]), "=f"(d[30]), "=f"(d[31]), "=f"(d[32]), "=f"(d[33]), "=f"(d[34]), "=f"(d[35]), "=f"(d[36]), "=f"(d[37]), "=f"(d[38]), "=f"(d[39]), "=f"(d[40]), "=f"(d[41]), "=f"(d[42]), "=f"(d[43]), "=f"(d[44]), "=f"(d[45]), "=f"(d[46]), "=f"(d[47]), "=f"(d[48]), "=f"(d[49]), "=f"(d[50]), "=f"(d[51]), "=f"(d[52]), "=f"(d[53]), "=f"(d[54]), "=f"(d[55]), "=f"(d[56]), "=f"(d[57]), "=f"(d[58]), "=f"(d[59]), "=f"(d[60]), "=f"(d[61]), "=f"(d[62]), "=f"(d[63])
    : "l"(da), "l"(db));
}
__device__ __forceinline__ void wgmma_n256(float (&d)[128], uint64_t da, uint64_t db) {
  asm volatile("wgmma.mma_async.sync.aligned.m64n256k16.f32.bf16.bf16 "
    "{%0, %1, %2, %3, %4, %5, %6, %7, %8, %9, %10, %11, %12, %13, %14, %15, %16, %17, %18, %19, %20, %21, %22, %23, %24, %25, %26, %27, %28, %29, %30, %31, %32, %33, %34, %35, %36, %37, %38, %39, %40, %41, %42, %43, %44, %45, %46, %47, %48, %49, %50, %51, %52, %53, %54, %55, %56, %57, %58, %59, %60, %61, %62, %63, %64, %65, %66, %67, %68, %69, %70, %71, %72, %73, %74, %75, %76, %77, %78, %79, %80, %81, %82, %83, %84, %85, %86, %87, %88, %89, %90, %91, %92, %93, %94, %95, %96, %97, %98, %99, %100, %101, %102, %103, %104, %105, %106, %107, %108, %109, %110, %111, %112, %113, %114, %115, %116, %117, %118, %119, %120, %121, %122, %123, %124, %125, %126, %127}, "
    "%128, %129, 1, 1, 1, 0, 1;\n"
    : "+f"(d[0]), "+f"(d[1]), "+f"(d[2]), "+f"(d[3]), "+f"(d[4]), "+f"(d[5]), "+f"(d[6]), "+f"(d[7]), "+f"(d[8]), "+f"(d[9]), "+f"(d[10]), "+f"(d[11]), "+f"(d[12]), "+f"(d[13]), "+f"(d[14]), "+f"(d[15]), "+f"(d[16]), "+f"(d[17]), "+f"(d[18]), "+f"(d[19]), "+f"(d[20]), "+f"(d[21]), "+f"(d[22]), "+f"(d[23]), "+f"(d[24]), "+f"(d[25]), "+f"(d[26]), "+f"(d[27]), "+f"(d[28]), "+f"(d[29]), "+f"(d[30]), "+f"(d[31]), "+f"(d[32]), "+f"(d[33]), "+f"(d[34]), "+f"(d[35]), "+f"(d[36]), "+f"(d[37]), "+f"(d[38]), "+f"(d[39]), "+f"(d[40]), "+f"(d[41]), "+f"(d[42]), "+f"(d[43]), "+f"(d[44]), "+f"(d[45]), "+f"(d[46]), "+f"(d[47]), "+f"(d[48]), "+f"(d[49]), "+f"(d[50]), "+f"(d[51]), "+f"(d[52]), "+f"(d[53]), "+f"(d[54]), "+f"(d[55]), "+f"(d[56]), "+f"(d[57]), "+f"(d[58]), "+f"(d[59]), "+f"(d[60]), "+f"(d[61]), "+f"(d[62]), "+f"(d[63]), "+f"(d[64]), "+f"(d[65]), "+f"(d[66]), "+f"(d[67]), "+f"(d[68]), "+f"(d[69]), "+f"(d[70]), "+f"(d[71]), "+f"(d[72]), "+f"(d[73]), "+f"(d[74]), "+f"(d[75]), "+f"(d[76]), "+f"(d[77]), "+f"(d[78]), "+f"(d[79]), "+f"(d[80]), "+f"(d[81]), "+f"(d[82]), "+f"(d[83]), "+f"(d[84]), "+f"(d[85]), "+f"(d[86]), "+f"(d[87]), "+f"(d[88]), "+f"(d[89]), "+f"(d[90]), "+f"(d[91]), "+f"(d[92]), "+f"(d[93]), "+f"(d[94]), "+f"(d[95]), "+f"(d[96]), "+f"(d[97]), "+f"(d[98]), "+f"(d[99]), "+f"(d[100]), "+f"(d[101]), "+f"(d[102]), "+f"(d[103]), "+f"(d[104]), "+f"(d[105]), "+f"(d[106]), "+f"(d[107]), "+f"(d[108]), "+f"(d[109]), "+f"(d[110]), "+f"(d[111]), "+f"(d[112]), "+f"(d[113]), "+f"(d[114]), "+f"(d[115]), "+f"(d[116]), "+f"(d[117]), "+f"(d[118]), "+f"(d[119]), "+f"(d[120]), "+f"(d[121]), "+f"(d[122]), "+f"(d[123]), "+f"(d[124]), "+f"(d[125]), "+f"(d[126]), "+f"(d[127])
    : "l"(da), "l"(db));
}
__device__ __forceinline__ void wgmma_n256_first(float (&d)[128], uint64_t da, uint64_t db) {
  asm volatile("wgmma.mma_async.sync.aligned.m64n256k16.f32.bf16.bf16 "
    "{%0, %1, %2, %3, %4, %5, %6, %7, %8, %9, %10, %11, %12, %13, %14, %15, %16, %17, %18, %19, %20, %21, %22, %23, %24, %25, %26, %27, %28, %29, %30, %31, %32, %33, %34, %35, %36, %37, %38, %39, %40, %41, %42, %43, %44, %45, %46, %47, %48, %49, %50, %51, %52, %53, %54, %55, %56, %57, %58, %59, %60, %61, %62, %63, %64, %65, %66, %67, %68, %69, %70, %71, %72, %73, %74, %75, %76, %77, %78, %79, %80, %81, %82, %83, %84, %85, %86, %87, %88, %89, %90, %91, %92, %93, %94, %95, %96, %97, %98, %99, %100, %101, %102, %103, %104, %105, %106, %107, %108, %109, %110, %111, %112, %113, %114, %115, %116, %117, %118, %119, %120, %121, %122, %123, %124, %125, %126, %127}, "
    "%128, %129, 0, 1, 1, 0, 1;\n"
    : "=f"(d[0]), "=f"(d[1]), "=f"(d[2]), "=f"(d[3]), "=f"(d[4]), "=f"(d[5]), "=f"(d[6]), "=f"(d[7]), "=f"(d[8]), "=f"(d[9]), "=f"(d[10]), "=f"(d[11]), "=f"(d[12]), "=f"(d[13]), "=f"(d[14]), "=f"(d[15]), "=f"(d[16]), "=f"(d[17]), "=f"(d[18]), "=f"(d[19]), "=f"(d[20]), "=f"(d[21]), "=f"(d[22]), "=f"(d[23]), "=f"(d[24]), "=f"(d[25]), "=f"(d[26]), "=f"(d[27]), "=f"(d[28]), "=f"(d[29]), "=f"(d[30]), "=f"(d[31]), "=f"(d[32]), "=f"(d[33]), "=f"(d[34]), "=f"(d[35]), "=f"(d[36]), "=f"(d[37]), "=f"(d[38]), "=f"(d[39]), "=f"(d[40]), "=f"(d[41]), "=f"(d[42]), "=f"(d[43]), "=f"(d[44]), "=f"(d[45]), "=f"(d[46]), "=f"(d[47]), "=f"(d[48]), "=f"(d[49]), "=f"(d[50]), "=f"(d[51]), "=f"(d[52]), "=f"(d[53]), "=f"(d[54]), "=f"(d[55]), "=f"(d[56]), "=f"(d[57]), "=f"(d[58]), "=f"(d[59]), "=f"(d[60]), "=f"(d[61]), "=f"(d[62]), "=f"(d[63]), "=f"(d[64]), "=f"(d[65]), "=f"(d[66]), "=f"(d[67]), "=f"(d[68]), "=f"(d[69]), "=f"(d[70]), "=f"(d[71]), "=f"(d[72]), "=f"(d[73]), "=f"(d[74]), "=f"(d[75]), "=f"(d[76]), "=f"(d[77]), "=f"(d[78]), "=f"(d[79]), "=f"(d[80]), "=f"(d[81]), "=f"(d[82]), "=f"(d[83]), "=f"(d[84]), "=f"(d[85]), "=f"(d[86]), "=f"(d[87]), "=f"(d[88]), "=f"(d[89]), "=f"(d[90]), "=f"(d[91]), "=f"(d[92]), "=f"(d[93]), "=f"(d[94]), "=f"(d[95]), "=f"(d[96]), "=f"(d[97]), "=f"(d[98]), "=f"(d[99]), "=f"(d[100]), "=f"(d[101]), "=f"(d[102]), "=f"(d[103]), "=f"(d[104]), "=f"(d[105]), "=f"(d[106]), "=f"(d[107]), "=f"(d[108]), "=f"(d[109]), "=f"(d[110]), "=f"(d[111]), "=f"(d[112]), "=f"(d[113]), "=f"(d[114]), "=f"(d[115]), "=f"(d[116]), "=f"(d[117]), "=f"(d[118]), "=f"(d[119]), "=f"(d[120]), "=f"(d[121]), "=f"(d[122]), "=f"(d[123]), "=f"(d[124]), "=f"(d[125]), "=f"(d[126]), "=f"(d[127])
    : "l"(da), "l"(db));
}

template <int N> struct WG;
#define DEF_WG(N) template <> struct WG<N> { \
  static __device__ __forceinline__ void mma(float (&d)[N / 2], uint64_t a, uint64_t b) { wgmma_n##N(d, a, b); } \
  static __device__ __forceinline__ void first(float (&d)[N / 2], uint64_t a, uint64_t b) { wgmma_n##N##_first(d, a, b); } };
DEF_WG(128) DEF_WG(256)

constexpr uint64_t DESC_A = (1ull << 62) | ((uint64_t)(1024 >> 4) << 32) | (1ull << 16);
constexpr uint64_t DESC_B = (1ull << 62) | ((uint64_t)(1024 >> 4) << 32) | ((uint64_t)(8192 >> 4) << 16);

struct Ring { int s; uint32_t ph; int wrap; };
template <int NS> __device__ __forceinline__ void ring_next(Ring& r) { r.s = (r.s + 1 == NS) ? 0 : r.s + 1; if (r.s == r.wrap) r.ph ^= 1; }

__device__ __forceinline__ int own_order(int it, int j) {
  return it < 2 ? 2 * j + it : it < 4 ? 2 * (j ^ 1) + it - 2 : ((j >> 1) * 4 + 2 * it - (it < 10 ? 4 : 15)) & 15;
}

template <int V> struct IC { static constexpr int v = V; };
template <int I, int E, class F> __device__ __forceinline__ void static_for(F&& f) { if constexpr (I < E) { f(IC<I>{}); static_for<I + 1, E>(f); } }

template <int N, int NS, int PRE, int LAG, class Pre, class Mid, class Last>
__device__ __forceinline__ void mainloop(float (&acc)[N / 2], int nkb, bool own, Ring& r, uint32_t sb, int wg, int lane, uint32_t rel_base, uint32_t* step0, Pre pre, Mid mid, Last last) {
  constexpr int SLOT = RING / NS;
  const uint32_t full = sb + MISC + (NS == 4 ? B_FULL4 : B_FULL6);
  const uint32_t rel = rel_base + (NS == 4 ? B_EMPTY4 : B_EMPTY6);
  const uint32_t s0 = (sb & 0x3FFFF) >> 4, a0 = s0 + wg * (HALF >> 4);
  int ps;
  auto issue = [&](int it, bool first) {
    const uint64_t da = DESC_A | (a0 + ((own && it < 2) ? (STG + it * BLK) >> 4 : r.s * (SLOT >> 4))), db = DESC_B | (s0 + r.s * (SLOT >> 4) + (BLK >> 4));
    mbar_wait(full + r.s * 8, r.ph);
    TRS(it);
    wg_arrive();
    if (first) WG<N>::first(acc, da, db); else WG<N>::mma(acc, da, db);
#pragma unroll
    for (int k = 1; k < 4; k++) WG<N>::mma(acc, da + k * 2, db + k * 128);
    wg_commit();
  };
  auto retire = [&](int it) {
    wg_wait<1>();
    if (lane < 2) mbar_arrive_cl(rel + ps * 8);
    ps = r.s;
    ring_next<NS>(r);
  };
  issue(0, true);
  ps = r.s;
  ring_next<NS>(r);
  static_for<1, PRE + 1>([&](auto ic) { issue(ic.v, false); pre(ic); retire(ic.v); });
#pragma unroll 1
  for (int it = PRE + 1; it < nkb; it++) {
    if (LAG && it == nkb - LAG && wg == 1) mbar_wait(sb + MISC + B_LAG, WOLAG && !own);
    issue(it, false); mid(it); retire(it);
  }
  last();
  wg_wait<0>();
  if (lane < 2) mbar_arrive_cl(rel + ps * 8);
}

__device__ __forceinline__ void ln_publish(const float (&v)[64], uint4* st, int j, int row0, int lane, uint32_t ep) {
  float s0 = 0, s1 = 0, s2 = 0, s3 = 0, q0 = 0, q1 = 0, q2 = 0, q3 = 0;
#pragma unroll
  for (int i = 0; i < 16; i++) {
    s0 += v[4 * i]; s1 += v[4 * i + 1]; s2 += v[4 * i + 2]; s3 += v[4 * i + 3];
    q0 = fmaf(v[4 * i], v[4 * i], q0); q1 = fmaf(v[4 * i + 1], v[4 * i + 1], q1); q2 = fmaf(v[4 * i + 2], v[4 * i + 2], q2); q3 = fmaf(v[4 * i + 3], v[4 * i + 3], q3);
  }
  s0 += s1; s2 += s3; q0 += q1; q2 += q3;
  const bool odd = lane & 1;
  float s = (odd ? s2 : s0) + __shfl_xor_sync(~0u, odd ? s0 : s2, 1), q = (odd ? q2 : q0) + __shfl_xor_sync(~0u, odd ? q0 : q2, 1);
  s += __shfl_xor_sync(~0u, s, 2); q += __shfl_xor_sync(~0u, q, 2);
  if ((lane & 3) < 2) st_rlx4(st + j * 128 + row0 + (lane & 1) * 8, __float_as_uint(s), ep, __float_as_uint(q), ep);
}
__device__ __forceinline__ void ln_gather(const uint4* st, int row0, int lane, uint32_t ep, float& n0, float& r0, float& n1, float& r1) {
  const uint4* p = st + (lane & 2) * 256 + row0 + (lane & 1) * 8;
  uint4 a, b, c, d; uint32_t n = 0;
  while (true) {
    a = ld_rlx4(p); b = ld_rlx4(p + 128); c = ld_rlx4(p + 256); d = ld_rlx4(p + 384);
    if (a.y == ep && a.w == ep && b.y == ep && b.w == ep && c.y == ep && c.w == ep && d.y == ep && d.w == ep) break;
    SPIN_GUARD(n);
  }
  __syncwarp();
  float s = (__uint_as_float(a.x) + __uint_as_float(b.x)) + (__uint_as_float(c.x) + __uint_as_float(d.x));
  float q = (__uint_as_float(a.z) + __uint_as_float(b.z)) + (__uint_as_float(c.z) + __uint_as_float(d.z));
  s += __shfl_xor_sync(~0u, s, 2); q += __shfl_xor_sync(~0u, q, 2);
  s *= 1.f / 1024;
  const float r = rsqrtf(fmaxf(fmaf(-s, s, q * (1.f / 1024)), 0.f) + 1e-5f), nn = -s * r;
  const float ro = __shfl_xor_sync(~0u, r, 1), no = __shfl_xor_sync(~0u, nn, 1);
  const bool odd = lane & 1;
  r0 = odd ? ro : r; n0 = odd ? no : nn; r1 = odd ? r : ro; n1 = odd ? nn : no;
}
__device__ __forceinline__ void load_vec(uint32_t* w, uint32_t sb, int sec, int b, int lane) {
#pragma unroll
  for (int q = 0; q < 2; q++) { uint4 t = lds128(sb + MISC + MODV + sec * 256 + (lane & 3) * 64 + b * 32 + q * 16); w[4 * q] = t.x; w[4 * q + 1] = t.y; w[4 * q + 2] = t.z; w[4 * q + 3] = t.w; }
}
__device__ __forceinline__ void stage_done(uint32_t sb, int wg, int b, int lane) {
  fence_async_smem();
  __syncwarp();
  if (lane == 0) mbar_arrive(sb + MISC + B_RDY + b * 8);
}
__device__ __forceinline__ uint32_t hfma2(uint32_t a, uint32_t b, uint32_t c) { uint32_t r; asm("fma.rn.bf16x2 %0, %1, %2, %3;" : "=r"(r) : "r"(a), "r"(b), "r"(c)); return r; }
__device__ __forceinline__ void ln_apply(const float (&v)[64], const uint4* st, int row0, uint32_t ep, uint32_t sb, int sec_shift, int sec_scale, uint32_t stg_row, int wg, int lane, uint32_t* step0) {
  uint32_t sc[16], sh[16];
#pragma unroll
  for (int b = 0; b < 2; b++) { load_vec(sc + 8 * b, sb, sec_scale, b, lane); load_vec(sh + 8 * b, sb, sec_shift, b, lane); }
  float n0, r0, n1, r1;
  TRW(1);
  ln_gather(st, row0, lane, ep, n0, r0, n1, r1);
  TRW(2);
#pragma unroll
  for (int i = 0; i < 16; i += 2) {
    if (i == 8) { const float z = lds32f(sb + MISC + ZERO); n0 += z; n1 += z; }
    uint32_t w[4];
#pragma unroll
    for (int u = 0; u < 2; u++) {
      int q = i + u;
      w[2 * u] = hfma2(pack2(fmaf(v[4 * q], r0, n0), fmaf(v[4 * q + 1], r0, n0)), sc[q], sh[q]);
      w[2 * u + 1] = hfma2(pack2(fmaf(v[4 * q + 2], r1, n1), fmaf(v[4 * q + 3], r1, n1)), sc[q], sh[q]);
    }
    stsm4(stg_row + (i >> 3) * BLK + ((((i & 7) + (lane >> 4)) ^ (lane & 7)) << 4), w[0], w[1], w[2], w[3]);
    if ((i & 7) == 6) { stage_done(sb, wg, i >> 3, lane); TRW(3 + (i >> 3)); }
  }
}
__device__ __forceinline__ uint32_t hmul2(uint32_t a, uint32_t b) { uint32_t r; asm("mul.rn.bf16x2 %0, %1, %2;" : "=r"(r) : "r"(a), "r"(b)); return r; }
__device__ __forceinline__ uint32_t silu_mul2(uint32_t g, uint32_t u) {
  const uint32_t h = hmul2(g, 0x3f003f00u);
  const float h0 = bf_lo(h), h1 = bf_hi(h);
  return hmul2(pack2(fmaf(h0, tanh_fast(h0), h0), fmaf(h1, tanh_fast(h1), h1)), u);
}

__device__ __forceinline__ void gemv_fma(float (&a)[8], uint4 w, float s) {
  a[0] = fmaf(bf_lo(w.x), s, a[0]); a[1] = fmaf(bf_hi(w.x), s, a[1]); a[2] = fmaf(bf_lo(w.y), s, a[2]); a[3] = fmaf(bf_hi(w.y), s, a[3]);
  a[4] = fmaf(bf_lo(w.z), s, a[4]); a[5] = fmaf(bf_hi(w.z), s, a[5]); a[6] = fmaf(bf_lo(w.w), s, a[6]); a[7] = fmaf(bf_hi(w.w), s, a[7]);
}
__device__ __forceinline__ float silu_c(float v) { return bf_round(__fdividef(v, 1.f + __expf(-v))); }
__device__ __forceinline__ float mod_gather(const uint2* p, uint32_t ep) {
  uint2 a, b, c, d; uint32_t n = 0;
  while (true) {
    a = ld_rlx2(p); b = ld_rlx2(p + 128); c = ld_rlx2(p + 256); d = ld_rlx2(p + 384);
    if (a.y == ep && b.y == ep && c.y == ep && d.y == ep) break;
    SPIN_GUARD(n);
  }
  return (__uint_as_float(a.x) + __uint_as_float(b.x)) + (__uint_as_float(c.x) + __uint_as_float(d.x));
}
__device__ __forceinline__ void mod_store(uint32_t sb, int sec, int col, float v) {
  v = bf_round(v);
  if (sec == 1 || sec == 4) v += 1.f;
  sts16(sb + MISC + MODV + sec * 256 + (((col >> 1) & 3) * 16 + (col >> 3)) * 4 + (col & 1) * 2, __float2bfloat16_rn(v));
}

__global__ void __cluster_dims__(2, 1, 1) __launch_bounds__(384, 1)
fused_kernel(const bf16* __restrict__ cvec, const bf16* __restrict__ wmod, Scratch* gs, int by_sm, const __grid_constant__ Maps maps) {
  extern __shared__ __align__(1024) uint8_t smem_raw[];
  const uint32_t sb = smem_u32(smem_raw);
  const int warp = __shfl_sync(~0u, threadIdx.x >> 5, 0), lane = threadIdx.x & 31;
  const int rank = blockIdx.x & 1;
  uint32_t sm; asm("mov.u32 %0, %%smid;" : "=r"(sm));
  const int t = sm >> 1, v = t < 32 ? t : t < 60 ? t + 1 + (((t - 32) * 37) >> 8) : (t - 58) * 8;
  const int cid = !by_sm ? (blockIdx.x >> 1) - 2 : (t & ~1) == 60 ? t - 62 : (v & 1) * 32 + ((v >> 1) & 31);
  const bool extra = cid < 0;
  const int bid = cid * 2 + rank;
  const int m = cid >> 2, j = (cid & 3) * 2 + rank;
  const uint32_t bar = sb + MISC;

  if (warp >= 8) {
    asm volatile("setmaxnreg.dec.sync.aligned.u32 40;");
    if (extra) {
      if (warp == 8) {
        if (lane == 0) { for (int s = 0; s < 6; s++) { mbar_init(bar + B_FULL6 + s * 8, 1); mbar_init(bar + B_EMPTY6 + s * 8, 8); } fence_async_smem(); }
        __syncwarp();
        asm volatile("bar.arrive 2, 288;" ::: "memory");
        __nanosleep(XSLEEP);
#pragma unroll 1
        for (int it = 0, s = 0, par = 1; it < 64; it++) {
          mbar_wait(bar + B_EMPTY6 + s * 8, par);
          if (elect()) { mbar_expect_tx(bar + B_FULL6 + s * 8, 32768); tma_3d(sb + s * 32768, &maps.wmod, bar + B_FULL6 + s * 8, 0, (it & 15) * 64, 12 + (it >> 4) * 4 + bid); }
          if (++s == 6) { s = 0; par ^= 1; }
        }
      }
    } else if (warp < 10) {
      uint32_t s6 = 0, p6 = 1;
      auto next6 = [&]() { if (++s6 == 6) { s6 = 0; p6 ^= 1; } };
      auto drained4 = [&](int q, int late) { if (q < 5) mbar_wait(bar + B_EMPTY4 + (((late ? 0x10332 : 0x32110) >> (4 * q)) & 3) * 8, 1); };
      auto drained6 = [&](int q) { if (q < 3) mbar_wait(bar + B_EMPTY6 + ((0x154 >> (4 * q)) & 7) * 8, q >> 1); };
      auto skip6 = [&]() { mbar_wait(bar + B_EMPTY6 + s6 * 8, p6); if (elect()) mbar_arrive(bar + B_FULL6 + s6 * 8); next6(); };
      if (warp == 8) {
        const uint32_t t_start = clock();
        if (lane == 0) {
          if (sb & 1023) bail();
          for (int b = 0; b < 2; b++) mbar_init(bar + B_X + b * 8, 1);
          for (int s = 0; s < 4; s++) { mbar_init(bar + B_FULL4 + s * 8, 2); mbar_init(bar + B_EMPTY4 + s * 8, 16); }
          for (int s = 0; s < 6; s++) { mbar_init(bar + B_FULL6 + s * 8, 2); mbar_init(bar + B_EMPTY6 + s * 8, 16); }
          for (int b = 0; b < 2; b++) { mbar_init(bar + B_RDY + b * 8, 8); mbar_init(bar + B_FREE + b * 8, 1); mbar_init(bar + B_HH + b * 8, 1); }
          mbar_init(bar + B_MOD, 1); mbar_init(bar + B_LAG, 4); mbar_init(bar + B_HALO, 2); mbar_init(bar + B_ALL, 1); mbar_init(bar + B_HH2, 1);
          asm volatile("st.shared.u32 [%0], 0;" :: "r"(bar + ZERO) : "memory");
          asm volatile("fence.mbarrier_init.release.cluster;" ::: "memory");
          fence_async_smem();
        }
        __syncwarp();
        cl_arrive_relaxed();
        auto wide = [&](int s, int par, const CUtensorMap* m0, int a0, const CUtensorMap* m1, int a1, int kb, bool spaced) {
          const uint32_t full = bar + B_FULL4 + s * 8, d = sb + s * 49152 + BLK;
          mbar_wait(full + 32, par);
          const uint32_t t0 = clock();
          if (elect()) { mbar_expect_tx(full, 2 * BLK); tma_3d(d, m0, full, 0, kb * 64, a0); }
          if (spaced) while ((uint32_t)clock() - t0 < 300) {}
          if (elect()) tma_3d(d + BLK, m1, full, 0, kb * 64, a1);
          if (spaced) while ((uint32_t)clock() - t0 < 600) {}
        };
        auto narrow = [&](const CUtensorMap* m0, int kb) {
          const uint32_t full = bar + B_FULL6 + s6 * 8;
          mbar_wait(full + 48, p6);
          if (elect()) { mbar_expect_tx(full, BLK); tma_3d(sb + s6 * 32768 + BLK, m0, full, 0, kb * 64, 2 * j); }
          next6();
        };
#pragma unroll 1
        for (int it = 0; it < 16; it++) {
          if (it == 0) {
            while ((uint32_t)clock() - t_start < XDELAY) {}
            if (elect()) for (int b = 0; b < 2; b++) { mbar_expect_tx(bar + B_X + b * 8, BLK); tma_3d(sb + STG + b * BLK, &maps.x, bar + B_X + b * 8, j * 128 + b * 64, m * 64, 0); }
            mbar_wait(bar + B_X + 8, 0);
          }
          wide(it & 3, ~(it >> 2) & 1, &maps.wqkv, 16 + 2 * j, &maps.wqkv, 32 + 2 * j, own_order(it, j), it < 4);
        }
#pragma unroll 1
        for (int it = 0; it < 16; it++) { drained4(it, 0); narrow(&maps.wqkv, it); }
#pragma unroll 1
        for (int it = 0; it < 16; it++) narrow(&maps.wo, own_order(it, j));
        skip6();
#pragma unroll 1
        for (int it = 0; it < 48; it++) {
          const int s = (it + 2) & 3, par = ~(it >> 2) & 1;
          drained6(it);
          wide(s, par, &maps.w1, (it & 48) + 2 * j, &maps.w3, (it & 48) + 2 * j, it < 16 ? own_order(it, j) : it & 15, it < 4);
          if (it >= 44) {
            if (it == 44) { mbar_wait(bar + B_FREE, 0); mbar_wait(bar + B_FREE + 8, 0); if (elect()) mbar_expect_tx(bar + B_X, 2 * BLK); }
            if (elect()) bulk_ld(sb + STG + (it - 44) * HALF, gs->x1 + bid * 2048 + (it - 44) * 512, HALF, bar + B_X);
          }
        }
#pragma unroll 1
        for (int it = 0; it < 16; it++) {
          const uint32_t full = bar + B_FULL6 + s6 * 8, d = sb + s6 * 32768 + BLK;
          drained4(it, 1);
          mbar_wait(full + 48, p6);
          if (elect()) { mbar_expect_tx(full, BLK); tma_3d(d, &maps.w1s, full, 0, it * 64, 48 + j); tma_3d(d + HALF, &maps.w3s, full, 0, it * 64, 48 + j); }
          next6();
        }
#pragma unroll 1
        for (int it = 0; it < 56; it++) narrow(&maps.w2, it);
      } else {
        if (lane < 9) prefetch_map(&maps.x + lane);
        const uint32_t ep = gs->epoch[bid + 4] + 1;
        cl_arrive_relaxed(); cl_wait();
        auto plain = [&](uint32_t full, uint32_t empty, int par, uint32_t slot, const uint4* blk) {
          mbar_wait(empty, par);
          if (elect()) { mbar_expect_tx(full, BLK); bulk_ld_mc(slot + rank * HALF, blk + rank * 512, HALF, full); }
        };
        auto plain6 = [&](const uint4* blk) { plain(bar + B_FULL6 + s6 * 8, bar + B_EMPTY6 + s6 * 8, p6, sb + s6 * 32768, blk); next6(); };
        uint32_t ready = 0;
        auto poll = [&](int e) { ready = __ballot_sync(~0u, ld_acquire(gs->flag + m * 128 + e * 16 + (lane & 15)) == ep); };
        auto need = [&](int e, uint32_t mask) {
          if ((ready & mask) != mask) {
            uint32_t n = 0;
            do { poll(e); SPIN_GUARD(n); } while ((ready & mask) != mask);
            fence_async_global();
          }
        };
        auto fresh = [&](int e, int it, uint32_t full, uint32_t empty, int par, uint32_t slot, uint4* src) {
          if (it >= 4) {
            const int kb = own_order(it, j);
            if (it < 10) need(e, 1u << kb); else if (it == 10) mbar_wait(bar + B_ALL, e & 1);
            plain(full, empty, par, slot, src + kb * 1024);
          } else {
            if (it == 0) ready = 0;
            mbar_wait(empty, par);
            if (it < 2) { if (elect()) mbar_arrive(full); }
            else {
              const int b = it > 2;
              const uint32_t to_peer = mapa(sb, rank ^ 1) - sb;
              if (elect()) mbar_expect_tx(full, BLK);
              const bool push = e != 1;
              mbar_wait(bar + (b ? (push ? B_RDY + 8 : B_FREE + 8) : B_RDY), e & 1);
              if (b == 0) TR(e == 0 ? 24 : e == 2 ? 30 : 44);
              if (elect()) {
                if (b == 0) {
                  bulk_st(src + 2 * j * 1024, sb + STG, BLK);
                  bulk_commit();
                  bulk_wait_all();
                  mbar_arrive(bar + B_FREE);
                }
                if (b && push) bulk_push(slot + to_peer, sb + STG + BLK, BLK, full + to_peer);
                else {
                  fence_async_global();
                  bulk_ld(slot + to_peer, src + (2 * j + b) * 1024, BLK, full + to_peer);
                }
              }
              __syncwarp();
            }
          }
          if (it == 4) TR(e == 0 ? 28 : e == 1 ? 46 : 34);
        };
#pragma unroll 1
        for (int ph = 0; ph < 2; ph++) {
          uint4* h = gs->h + m * 16384;
#pragma unroll 1
          for (int it = 0; it < 16; it++) {
            const int s = (it + 2 * ph) & 3;
            if (ph) drained6(it);
            fresh(2 * ph, it, bar + B_FULL4 + s * 8, bar + B_EMPTY4 + s * 8, ~(it >> 2) & 1, sb + s * 49152, h);
          }
          if (ph) {
#pragma unroll 1
            for (int it = 16; it < 48; it++) {
              const int s = (it + 2) & 3;
              const uint32_t full = bar + B_FULL4 + s * 8;
              plain(full, full + 32, ~(it >> 2) & 1, sb + s * 49152, h + (it & 15) * 1024);
            }
          }
#pragma unroll 1
          for (int it = 0; it < 16; it++) { drained4(it, ph); plain6(h + it * 1024); }
          if (!ph) {
#pragma unroll 1
            for (int it = 0; it < 16; it++) { fresh(1, it, bar + B_FULL6 + s6 * 8, bar + B_EMPTY6 + s6 * 8, p6, sb + s6 * 32768, gs->o + m * 16384); next6(); }
            skip6();
          }
        }
#pragma unroll 1
        for (int it = 0; it < 56; it++) {
          if (it == 0 || it == 32 || it == 48) mbar_wait(bar + (it == 48 ? B_HH2 : B_HH + (it >> 2)), 0);
          plain6(gs->hh + m * 57344 + it * 1024);
        }
      }
    } else {
      const int b = warp - 10;
      const uint32_t ep = gs->epoch[bid + 4] + 1;
      const uint32_t stg = sb + STG + b * BLK;
      cl_arrive_relaxed(); cl_wait();
      auto all_there = [&](int u, uint32_t done) {
        const uint32_t* fl = gs->flag + u;
        uint32_t n = 0;
        while (!__all_sync(~0u, ld_acquire(fl) == ep)) { __nanosleep(100); SPIN_GUARD(n); }
        fence_async_global();
        if (lane == 0) mbar_arrive(done);
      };
      auto fetch_mod = [&](int sec) {
        const uint4* p = (const uint4*)(gs->modv + (sec - 2) * 1024 + j * 128) + lane;
        uint4 v0, v1; uint32_t n = 0;
        while (true) {
          v0 = ld_rlx4(p); v1 = ld_rlx4(p + 32);
          if (v0.y == ep && v0.w == ep && v1.y == ep && v1.w == ep) break;
          SPIN_GUARD(n);
        }
        mod_store(sb, sec, 2 * lane, __uint_as_float(v0.x)); mod_store(sb, sec, 2 * lane + 1, __uint_as_float(v0.z));
        mod_store(sb, sec, 64 + 2 * lane, __uint_as_float(v1.x)); mod_store(sb, sec, 65 + 2 * lane, __uint_as_float(v1.z));
        __syncwarp();
      };
#pragma unroll 1
      for (int e = 0; e < 7 - b; e++) {
        if (lane == 0) {
          if (e < 3) {
            mbar_wait(bar + B_FREE, e & 1);
            if (b) {
              const uint32_t t0 = clock();
              while ((uint32_t)clock() - t0 < (e == 0 ? B1P : e == 2 ? B1P2 : B1D)) {}
              mbar_wait(bar + B_RDY + 8, e & 1);
              bulk_st((e == 1 ? gs->o : gs->h) + m * 16384 + (2 * j + 1) * 1024, stg, BLK);
              bulk_commit();
              bulk_wait_all();
              mbar_arrive(bar + B_FREE + 8);
              TR(53 + e);
            }
            st_release(gs->flag + m * 128 + e * 16 + 2 * j + b, ep);
            TR((e == 0 ? 26 : e == 2 ? 32 : 42) + b);
          } else {
            const int kb = (e < 6 ? 2 * (8 * (e - 3) + j) : 48 + j) + b;
            mbar_wait(bar + B_RDY + b * 8, e & 1);
#pragma unroll 1
            for (int q = 0; q < NPIECE; q++) { if (q) __nanosleep(PSLEEP); bulk_st(gs->hh + m * 57344 + kb * 1024 + q * (1024 / NPIECE), stg + q * (BLK / NPIECE), BLK / NPIECE); }
            bulk_commit();
            bulk_wait_all();
            mbar_arrive(bar + B_FREE + b * 8);
            st_release(gs->flag + m * 128 + U_HH + kb, ep);
          }
        }
        __syncwarp();
        if (e < 3 && b) all_there(m * 128 + e * 16 + (lane & 15), bar + B_ALL);
        if (e == 4 && b) all_there(m * 128 + U_HH + lane, bar + B_HH);
        if (!b && (e == 1 || e == 2)) {
#pragma unroll 1
          for (int sec = e == 1 ? 2 : 5; sec < 4 + e; sec++) fetch_mod(sec);
          if (e == 1) { if (lane == 0) mbar_arrive(bar + B_MOD); TR(50); }
        }
        if (e == 0) {
          mbar_wait(bar + B_EMPTY6 + 24, 0);
          if (HSLEEP) __nanosleep(HSLEEP + (QPV == 1 ? b * 700 : 0));
#pragma unroll 1
          for (int w = 0; w < 4; w++) {
            const uint4* hp = gs->halo + ((m * 8 + j) * 2 + (w & 1)) * 512 + b * 256 + (w >> 1) * 128 + lane;
            uint4 q[4] = {}; uint32_t n = 0;
            while (m > 0) {
              bool ok = true;
#pragma unroll
              for (int i = 0; i < 4; i++) q[i] = ld_rlx4(hp + i * 32);
#pragma unroll
              for (int i = 0; i < 4; i++) ok = ok && q[i].y == ep && q[i].w == ep;
              if (ok) break;
              SPIN_GUARD(n);
            }
#pragma unroll
            for (int i = 0; i < 2; i++) sts128(stg + lane * 16 + (w & 1) * HALF + (w >> 1) * 1024 + i * 512, q[2 * i].x, q[2 * i + 1].x, q[2 * i].z, q[2 * i + 1].z);
          }
          __syncwarp();
          if (lane == 0) mbar_arrive(bar + B_HALO);
          if (b == 0) TR(52);
        }
      }
      if (b) { all_there(m * 128 + U_HH + 32 + (lane & 15), bar + B_HH + 8); all_there(m * 128 + U_HH + 48 + (lane & 7), bar + B_HH2); }
    }
  } else {
    const int wg = warp >> 2, wq = warp & 3, tid = threadIdx.x;
    const int g = lane >> 2, c = lane & 3;
    const int sec0 = (m >> 1) & 1, hf0 = m & 1, ks0 = (m >> 2) & 3;
    uint4 wv[8];
    uint32_t ep0; uint16_t cv_;
    asm volatile("ld.global.nc.u16 %0, [%1];" : "=h"(cv_) : "l"(cvec + ks0 * 256 + warp * 32 + lane));
    asm volatile("ld.global.u32 %0, [%1];" : "=r"(ep0) : "l"(gs->epoch + bid + 4));
    if (!extra) {
      const bf16* wp = wmod + (size_t)(ks0 * 256 + warp * 32 + (lane >> 3)) * 6144 + sec0 * 1024 + j * 128 + hf0 * 64 + (lane & 7) * 8;
#pragma unroll
      for (int i = 0; i < 8; i++) wv[i] = ldg_nc(wp + (size_t)i * 4 * 6144);
    }
    asm volatile("setmaxnreg.inc.sync.aligned.u32 232;" ::: "memory");
    if (__builtin_expect(extra, 0)) {
      const uint32_t ep = ep0 + 1;
      float sv[4];
#pragma unroll
      for (int p = 0; p < 4; p++) sv[p] = silu_c(__bfloat162float(cvec[64 * (4 * p + (lane >> 3)) + 8 * warp + (lane & 7)]));
      named_bar(2, 288);
      int s = 0, par = 0;
#pragma unroll 1
      for (int sec = 0; sec < 4; sec++) {
        float a[8] = {0, 0, 0, 0, 0, 0, 0, 0};
#pragma unroll 1
        for (int it = 0; it < 16; it++) {
          const float sc = it < 4 ? sv[0] : it < 8 ? sv[1] : it < 12 ? sv[2] : sv[3];
          mbar_wait(bar + B_FULL6 + s * 8, par);
          uint4 w[8];
#pragma unroll
          for (int i = 0; i < 8; i++) w[i] = lds128(sb + s * 32768 + (warp * 8 + i) * 512 + lane * 16);
#pragma unroll
          for (int i = 0; i < 8; i++) gemv_fma(a, w[i], __shfl_sync(~0u, sc, (it & 3) * 8 + i));
          if (lane == 0) mbar_arrive(bar + B_EMPTY6 + s * 8);
          if (++s == 6) { s = 0; par ^= 1; }
        }
        const uint32_t red = sb + STG + sec * 8192;
        sts128(red + warp * 1024 + lane * 32, __float_as_uint(a[0]), __float_as_uint(a[1]), __float_as_uint(a[2]), __float_as_uint(a[3]));
        sts128(red + warp * 1024 + lane * 32 + 16, __float_as_uint(a[4]), __float_as_uint(a[5]), __float_as_uint(a[6]), __float_as_uint(a[7]));
        named_bar(1, 256);
        float t = 0;
#pragma unroll
        for (int q = 0; q < 8; q++) t += lds32f(red + q * 1024 + tid * 4);
        st_rlx2(gs->modv + sec * 1024 + (bid + 4) * 256 + tid, __float_as_uint(t), ep);
      }
      if (tid == 0) gs->epoch[bid + 4] = ep;
      return;
    }
    if (warp == 0) TR(0);
    const int row0 = wg * 64 + wq * 16 + g;
    if (c < 2) st_rlx4(gs->stat + m * 1024 + j * 128 + row0 + c * 8, 0, 0, 0, 0);
    if (tid < 64) st_rlx2(gs->modp + ((j * 2 + sec0) * 4 + ks0) * 128 + hf0 * 64 + tid, 0, 0);
    cl_arrive_relaxed(); cl_wait();
    uint32_t ep;
    asm volatile("add.u32 %0, %1, 1;" : "=r"(ep) : "r"(ep0) : "memory");
    const float sc_ = silu_c(__uint_as_float((uint32_t)cv_ << 16));
    const uint32_t rel = mapa(bar, (lane & 1) ^ rank);
    const uint32_t stg_row = sb + STG + (wg * 64 + wq * 16 + (lane & 15)) * 128;
    const uint32_t fre = bar + B_FREE;
    Ring r4{0, 0, 0}, r6{0, 0, 0};
    auto none = [](auto) {};
    uint32_t xk[32];
    {
      float a[8] = {0, 0, 0, 0, 0, 0, 0, 0};
#pragma unroll
      for (int i = 0; i < 8; i++) gemv_fma(a, wv[i], __shfl_sync(~0u, sc_, i * 4 + (lane >> 3)));
#pragma unroll
      for (int i = 0; i < 8; i++) { a[i] += __shfl_xor_sync(~0u, a[i], 8); a[i] += __shfl_xor_sync(~0u, a[i], 16); }
      if (lane < 8) {
        sts128(sb + RED_OFF + warp * 256 + lane * 32, __float_as_uint(a[0]), __float_as_uint(a[1]), __float_as_uint(a[2]), __float_as_uint(a[3]));
        sts128(sb + RED_OFF + warp * 256 + lane * 32 + 16, __float_as_uint(a[4]), __float_as_uint(a[5]), __float_as_uint(a[6]), __float_as_uint(a[7]));
      }
      named_bar(1, 256);
      if (tid < 64) {
        float s = 0;
#pragma unroll
        for (int w = 0; w < 8; w++) s += lds32f(sb + RED_OFF + w * 256 + tid * 4);
        st_rlx2(gs->modp + ((j * 2 + sec0) * 4 + ks0) * 128 + hf0 * 64 + tid, __float_as_uint(s), ep);
      }
      if (warp == 0) TR(1);
      float v[64];
      mbar_wait(bar + B_X, 0); mbar_wait(bar + B_X + 8, 0);
#pragma unroll
      for (int i = 0; i < 16; i += 2) {
        uint32_t w0, w1, w2, w3;
        ldsm4(stg_row + (i >> 3) * BLK + ((((i & 7) + (lane >> 4)) ^ (lane & 7)) << 4), w0, w1, w2, w3);
        xk[2 * i] = w0; xk[2 * i + 1] = w1; xk[2 * i + 2] = w2; xk[2 * i + 3] = w3;
        v[4 * i] = bf_lo(w0); v[4 * i + 1] = bf_hi(w0); v[4 * i + 2] = bf_lo(w1); v[4 * i + 3] = bf_hi(w1);
        v[4 * i + 4] = bf_lo(w2); v[4 * i + 5] = bf_hi(w2); v[4 * i + 6] = bf_lo(w3); v[4 * i + 7] = bf_hi(w3);
      }
      ln_publish(v, gs->stat + m * 1024, j, row0, lane, ep);
      if (warp == 0) TR(2);
      { uint32_t* step0 = STEP0 + 168; TRW(0); }
      mod_store(sb, tid >> 7, tid & 127, mod_gather(gs->modp + (j * 2 + (tid >> 7)) * 512 + (tid & 127), ep));
      named_bar(1, 256);
      if (warp == 0) TR(3);
      ln_apply(v, gs->stat + m * 1024, row0, ep, sb, 0, 1, stg_row, wg, lane, STEP0 + 168);
      named_bar(1, 256);
    }
    if (warp == 0) TR(4);
    { uint32_t* step0 = STEP0 + 168; TRW(5); }
    {
      uint32_t kf[32], vf[32], pv[32];
      const bool first = wq == 0 && m == 0;
      const uint32_t xa = sb + STG + wg * HALF + wq * 2048 + lane * 16;
      {
        float acc[128];
        mainloop<256, 4, 0, 0>(acc, 16, true, r4, sb, wg, lane, rel, STEP0 + 0, none, none, [&] {
          mbar_wait(fre + 8, 0);
          if (c < 2) st_rlx4(gs->stat + (16 + m) * 1024 + j * 128 + row0 + c * 8, 0, 0, 0, 0);
        });
        if (warp == 0) TR(5);
#pragma unroll
        for (int i = 0; i < 32; i++) { kf[i] = pack2(acc[2 * i], acc[2 * i + 1]); vf[i] = pack2(acc[64 + 2 * i], acc[65 + 2 * i]); }
      }
      if (warp == 0) TR(6);
      float acc[64];
      constexpr int QP = QPV;
      mainloop<128, 6, 8 / QP, 0>(acc, 16, false, r6, sb, wg, lane, rel, STEP0 + 16, [&](auto ic) {
        constexpr int q = (ic.v - 1) * QP;
#pragma unroll
        for (int i = 4 * q; i < 4 * (q + QP); i++) vf[i] = movm(vf[i]);
        if (wq == 3) {
          if (m < 15) {
            uint4* hp = gs->halo + (((m + 1) * 8 + j) * 2 + wg) * 512 + lane;
#pragma unroll
            for (int i = 2 * q; i < 2 * (q + QP); i++) st_rlx4(hp + i * 32, kf[2 * i + 1], ep, vf[2 * i + 1], ep);
          }
        } else {
#pragma unroll
          for (int i = q; i < q + QP; i++) sts128(xa + 2048 + (i >> 2) * BLK + (i & 3) * 512, kf[4 * i + 1], kf[4 * i + 3], vf[4 * i + 1], vf[4 * i + 3]);
        }
      }, none, [&] {
        named_bar(2 + wg, 128);
        if (wq == 0) mbar_wait(bar + B_HALO, 0);
#pragma unroll
        for (int i = 0; i < 8; i++) {
          uint4 q = lds128(xa + (i >> 2) * BLK + (i & 3) * 512);
          pv[4 * i] = q.x; pv[4 * i + 1] = q.y; pv[4 * i + 2] = q.z; pv[4 * i + 3] = q.w;
        }
        __syncwarp();
      });
      if (warp == 0) TR(7);
      { uint32_t* step0 = STEP0 + 184; TRW(0); }
      int gz = g;
#pragma unroll
      for (int b = 0; b < 2; b++) {
        const bool up0 = 2 * c > gz, up1 = 2 * c + 1 > gz;
        const uint32_t mup = (up0 ? 0xffffu : 0u) | (up1 ? 0xffff0000u : 0u);
        float l[2][4], mx[4];
#pragma unroll
        for (int h = 0; h < 2; h++) {
          uint32_t q[8];
          const int k = 16 * b + 8 * h;
#pragma unroll
          for (int i = 0; i < 8; i++) q[i] = pack2(acc[2 * k + 2 * i], acc[2 * k + 2 * i + 1]);
          float s0[4], s1[4], s2[4];
          mma16z(s0, q[0], q[1], q[2], q[3], pv[k], pv[k + 1]); mma16z(s1, q[0], q[1], q[2], q[3], kf[k], kf[k + 2]); mma16z(s2, q[0], q[1], q[2], q[3], kf[k + 1], kf[k + 3]);
          mma16(s0, q[4], q[5], q[6], q[7], pv[k + 4], pv[k + 5]); mma16(s1, q[4], q[5], q[6], q[7], kf[k + 4], kf[k + 6]); mma16(s2, q[4], q[5], q[6], q[7], kf[k + 5], kf[k + 7]);
          if (first) { s0[0] = -INFINITY; s0[1] = -INFINITY; }
          l[h][0] = up0 ? s0[0] : s1[0]; l[h][1] = up1 ? s0[1] : s1[1]; l[h][2] = up0 ? s1[2] : s2[2]; l[h][3] = up1 ? s1[3] : s2[3];
          mx[2 * h] = fmaxf(l[h][0], l[h][1]); mx[2 * h + 1] = fmaxf(l[h][2], l[h][3]);
        }
#pragma unroll
        for (int o = 1; o < 4; o <<= 1) {
#pragma unroll
          for (int h = 0; h < 4; h++) mx[h] = fmaxf(mx[h], __shfl_xor_sync(~0u, mx[h], o));
        }
#pragma unroll
        for (int h = 0; h < 2; h++) {
          const float n0 = -mx[2 * h] * SCL, n1 = -mx[2 * h + 1] * SCL;
          const uint32_t pa = pack2(ex2(fmaf(l[h][0], SCL, n0)), ex2(fmaf(l[h][1], SCL, n0))), pb = pack2(ex2(fmaf(l[h][2], SCL, n1)), ex2(fmaf(l[h][3], SCL, n1)));
          float sm[4];
          mma8z(sm, pa, pb, 0x3f803f80u);
          const float ia = rcp(sm[0]), ib = rcp(sm[2]);
#pragma unroll
          for (int i = 8 * b + 4 * h; i < 8 * b + 4 * h + 4; i += 2) {
            uint32_t of[4];
#pragma unroll
            for (int d = 0; d < 2; d++) {
              float o[4];
              mma16z(o, pa & ~mup, pb & mup, 0u, pb & ~mup, vf[2 * (i + d)], vf[2 * (i + d) + 1]);
              mma8(o, pa & mup, 0u, pv[2 * i + 2 + d]);
              of[2 * d] = pack2(o[0] * ia, o[1] * ia); of[2 * d + 1] = pack2(o[2] * ib, o[3] * ib);
            }
            stsm4(stg_row + b * BLK + ((((i & 7) + (lane >> 4)) ^ (lane & 7)) << 4), of[0], of[1], of[2], of[3]);
          }
        }
        stage_done(sb, wg, b, lane);
        { uint32_t* step0 = STEP0 + 184; TRW(1 + b); }
        if (b == 0) gz += __float_as_uint(lds32f(bar + ZERO));
      }
      named_bar(1, 256);
      if (warp == 0) TR(8);
      { uint32_t* step0 = STEP0 + 184; TRW(3); }
    }
    uint32_t pk[64];
    {
      float acc[64];
      mainloop<128, 6, 0, WOLAG>(acc, 16, true, r6, sb, wg, lane, rel, STEP0 + 32, none, none, [&] {
        if (WOLAG && wg == 0 && lane == 0) mbar_arrive(bar + B_LAG);
        mbar_wait(bar + B_MOD, 0); mbar_wait(fre + 8, 1);
        load_vec(pk + 32, sb, 2, 0, lane); load_vec(pk + 40, sb, 2, 1, lane);
#pragma unroll
        for (int i = 0; i < 32; i++) { pk[i] = xk[i]; asm volatile("" : "+r"(pk[i])); }
      });
      if (warp == 0) TR(9);
      { uint32_t* step0 = STEP0 + 176; TRW(0); }
#pragma unroll
      for (int i = 0; i < 32; i++) {
        acc[2 * i] = fmaf(acc[2 * i], bf_lo(pk[32 + (i >> 1)]), bf_lo(pk[i]));
        acc[2 * i + 1] = fmaf(acc[2 * i + 1], bf_hi(pk[32 + (i >> 1)]), bf_hi(pk[i]));
      }
      ln_publish(acc, gs->stat + (16 + m) * 1024, j, row0, lane, ep);
      if (warp == 0) TR(36);
      mbar_wait(bar + B_FULL6 + 16, 1);
      if (lane < 2) mbar_arrive_cl(rel + B_EMPTY6 + 16);
      ring_next<6>(r6);
#pragma unroll
      for (int i = 0; i < 32; i++) { pk[i] = pack2(acc[2 * i], acc[2 * i + 1]); pk[32 + i] = 0; }
      ln_apply(acc, gs->stat + (16 + m) * 1024, row0, ep, sb, 3, 4, stg_row, wg, lane, STEP0 + 176);
      named_bar(1, 256);
      if (warp == 0) TR(11);
      { uint32_t* step0 = STEP0 + 176; TRW(5); }
    }
    auto swiglu = [&](int q, int uo, int par) {
      if ((q & 3) == 0 && par >= 0) mbar_wait(fre + 2 * q, par);
      uint32_t w[4];
#pragma unroll
      for (int u = 0; u < 4; u++) w[u] = silu_mul2(pk[4 * q + u], pk[uo + 4 * q + u]);
      stsm4(stg_row + (q >> 2) * BLK + ((((2 * q & 7) + (lane >> 4)) ^ (lane & 7)) << 4), w[0], w[1], w[2], w[3]);
    };
    r4.s = r4.wrap = 2;
#pragma unroll 1
    for (int t = 0; t < 3; t++) {
      float acc[128];
      mainloop<256, 4, 5, 0>(acc, 16, t == 0, r4, sb, wg, lane, rel, STEP0 + 48 + 16 * t, [&](auto ic) {
        if (t) {
          if (ic.v == 3 || ic.v == 5) stage_done(sb, wg, ic.v >> 2, lane);
          if (ic.v < 5) { swiglu(2 * ic.v - 2, 32, ~t & 1); swiglu(2 * ic.v - 1, 32, 0); }
        }
      }, [&](int it) {
#pragma unroll
        for (int i = 0; i < 8; i++)
          if (t == 0 && it == 8 + i) gs->x1[bid * 2048 + (i >> 2) * 1024 + warp * 128 + (i & 3) * 32 + lane] = make_uint4(pk[4 * i], pk[4 * i + 1], pk[4 * i + 2], pk[4 * i + 3]);
      }, [&] { if (t == 0) fence_async_global(); else if (t == 2) mbar_wait(bar + B_X, 1); });
      if (warp == 0) TR(12 + 2 * t);
#pragma unroll
      for (int i = 0; i < 64; i++) pk[i] = pack2(acc[2 * i], acc[2 * i + 1]);
      if (warp == 0) TR(13 + 2 * t);
    }
    uint32_t x1[32];
    {
      float acc[64];
      mainloop<128, 6, 12, 0>(acc, 16, false, r6, sb, wg, lane, rel, STEP0 + 96, [&](auto ic) {
        constexpr int b = ic.v > 6, q = ic.v - 6 * b;
        if (q == 1) {
#pragma unroll
          for (int i = 4 * b; i < 4 * b + 4; i++) { const uint4 x = lds128(sb + STG + b * BLK + warp * 2048 + (i & 3) * 512 + lane * 16); x1[4 * i] = x.x; x1[4 * i + 1] = x.y; x1[4 * i + 2] = x.z; x1[4 * i + 3] = x.w; }
          __syncwarp();
        } else if (q < 6) swiglu(4 * b + q - 2, 32, -1);
        else stage_done(sb, wg, b, lane);
      }, none, [] {});
      if (warp == 0) TR(18);
#pragma unroll
      for (int i = 0; i < 32; i++) pk[i] = pack2(acc[2 * i], acc[2 * i + 1]);
      if (warp == 0) TR(19);
    }
    {
      float acc[64];
      mainloop<128, 6, 5, TAILLAG>(acc, 56, false, r6, sb, wg, lane, rel, STEP0 + 112, [&](auto ic) {
        if (ic.v == 5) stage_done(sb, wg, 0, lane); else swiglu(ic.v - 1, 16, 1);
      }, none, [&] {
        if (TAILLAG && wg == 0 && lane == 0) mbar_arrive(bar + B_LAG);
        load_vec(pk + 32, sb, 5, 0, lane); load_vec(pk + 40, sb, 5, 1, lane);
        mbar_wait(fre, 0); mbar_wait(fre + 8, 1);
      });
      __syncwarp();
      cl_arrive_relaxed();
      if (warp == 0) TR(20);
#pragma unroll
      for (int i = 0; i < 16; i += 2) {
        uint32_t w[4];
#pragma unroll
        for (int u = 0; u < 4; u++) {
          const int q = 2 * i + u;
          w[u] = pack2(fmaf(acc[2 * q], bf_lo(pk[32 + (q >> 1)]), bf_lo(x1[q])), fmaf(acc[2 * q + 1], bf_hi(pk[32 + (q >> 1)]), bf_hi(x1[q])));
        }
        stsm4(stg_row + (i >> 3) * BLK + ((((i & 7) + (lane >> 4)) ^ (lane & 7)) << 4), w[0], w[1], w[2], w[3]);
        if ((i & 7) == 6) {
          fence_async_smem();
          named_bar(2 + wg, 128);
          if (wq == 0 && elect()) { tma_store_3d(&maps.out, sb + STG + (i >> 3) * BLK + wg * HALF, j * 128 + (i >> 3) * 64, m * 64, wg); bulk_commit(); }
          if (i < 8) x1[16] |= __float_as_uint(lds32f(bar + ZERO));
        }
      }
      if (wq == 0) bulk_wait_read();
      if (wq == 0) TR(40 + wg);
      if (tid == 0) gs->epoch[bid + 4] = ep;
      if (warp == 0) TR(21);
      cl_wait();
    }
  }
}

typedef CUresult (*EncodeFn)(CUtensorMap*, CUtensorMapDataType, cuuint32_t, void*, const cuuint64_t*, const cuuint64_t*, const cuuint32_t*, const cuuint32_t*,
                             CUtensorMapInterleave, CUtensorMapSwizzle, CUtensorMapL2promotion, CUtensorMapFloatOOBfill);

void make_map(EncodeFn fn, CUtensorMap* mp, const void* base, uint64_t d0, uint64_t d1, uint64_t d2, uint64_t s1, uint64_t s2, uint32_t b2, uint32_t b0 = 64) {
  cuuint64_t d[3] = {d0, d1, d2}, s[2] = {s1, s2};
  cuuint32_t b[3] = {b0, 64, b2}, e[3] = {1, 1, 1};
  fn(mp, CU_TENSOR_MAP_DATA_TYPE_BFLOAT16, 3, (void*)base, d, s, b, e, CU_TENSOR_MAP_INTERLEAVE_NONE, b0 == 64 ? CU_TENSOR_MAP_SWIZZLE_128B : CU_TENSOR_MAP_SWIZZLE_NONE,
     CU_TENSOR_MAP_L2_PROMOTION_L2_128B, CU_TENSOR_MAP_FLOAT_OOB_FILL_NONE);
}

__global__ void probe_kernel() {}
int max_clusters(int size) {
  cudaLaunchConfig_t cfg = {};
  cudaLaunchAttribute at;
  at.id = cudaLaunchAttributeClusterDimension; at.val.clusterDim.x = size; at.val.clusterDim.y = 1; at.val.clusterDim.z = 1;
  cfg.gridDim = dim3(size * 66); cfg.blockDim = dim3(384); cfg.dynamicSmemBytes = SMEM_BYTES; cfg.attrs = &at; cfg.numAttrs = 1;
  int n = 0;
  if (cudaOccupancyMaxActiveClusters(&n, probe_kernel, &cfg) != cudaSuccess) { cudaGetLastError(); return 0; }
  return n;
}

}

extern "C" void kernel_launch(void* const* d_in, const int* in_sizes, int n_in, void* d_out, int out_size) {
  static EncodeFn fn = nullptr;
  static int by_sm = 0;
  static Scratch* gs = nullptr;
  if (!fn) {
    void* p = nullptr; cudaDriverEntryPointQueryResult q;
    cudaGetDriverEntryPoint("cuTensorMapEncodeTiled", &p, cudaEnableDefault, &q);
    fn = (EncodeFn)p;
    cudaFuncSetAttribute(fused_kernel, cudaFuncAttributeMaxDynamicSharedMemorySize, SMEM_BYTES);
    int dev = 0, sms = 0;
    cudaGetSymbolAddress((void**)&gs, g_scratch);
    cudaGetDevice(&dev);
    cudaDeviceGetAttribute(&sms, cudaDevAttrMultiProcessorCount, dev);
    cudaFuncSetAttribute(probe_kernel, cudaFuncAttributeMaxDynamicSharedMemorySize, SMEM_BYTES);
    by_sm = BYSM && sms == 132 && max_clusters(2) == 66 && max_clusters(4) == 30 && max_clusters(6) == 17 && max_clusters(8) == 15;
  }
  Maps mp;
  make_map(fn, &mp.x, d_in[0], D_, S_ / 2, 2, 4096, 2048, 2);
  make_map(fn, &mp.out, d_out, D_, S_ / 2, 2, 4096, 2048, 1);
  make_map(fn, &mp.wqkv, d_in[1], 64, D_, 3 * D_ / 64, 3 * D_ * 2, 128, 2);
  make_map(fn, &mp.wo, d_in[2], 64, D_, D_ / 64, D_ * 2, 128, 2);
  make_map(fn, &mp.w1, d_in[4], 64, D_, F_ / 64, F_ * 2, 128, 2);
  make_map(fn, &mp.w3, d_in[5], 64, D_, F_ / 64, F_ * 2, 128, 2);
  make_map(fn, &mp.w1s, d_in[4], 64, D_, F_ / 64, F_ * 2, 128, 1);
  make_map(fn, &mp.w3s, d_in[5], 64, D_, F_ / 64, F_ * 2, 128, 1);
  make_map(fn, &mp.w2, d_in[6], 64, F_, D_ / 64, D_ * 2, 128, 2);
  make_map(fn, &mp.wmod, d_in[8], 256, D_, 24, 6 * D_ * 2, 512, 1, 256);
  fused_kernel<<<132, 384, SMEM_BYTES>>>((const bf16*)d_in[7], (const bf16*)d_in[8], gs, by_sm, mp);
}
```

```cpp
#include <cuda_runtime.h>
#include <cuda_bf16.h>
#include <cuda.h>
#include <stdint.h>

typedef __nv_bfloat16 bf16;

#define NPIECE 4
#define PSLEEP 300
#define XSLEEP 4000
#define XDELAY 2000
#define TAILLAG 5
#define HSLEEP 400
#define B1D 900
#define B1P 3500
#define WOLAG 2
#define B1P2 3200
#define QPV 2
#define BYSM 1
namespace {

constexpr int S_ = 2048, D_ = 1024, F_ = 3584;
constexpr int BLK = 16384;
constexpr int HALF = 8192;
constexpr int RING = 196608;
constexpr int STG = RING;
constexpr int MISC = RING + 2 * BLK;
constexpr int SMEM_BYTES = MISC + 3072;
constexpr int B_FULL4 = 0, B_EMPTY4 = 32, B_FULL6 = 64, B_EMPTY6 = 112, B_RDY = 160, B_FREE = 176, B_LAG = 192, B_X = 208, B_MOD = 224, B_HALO = 232, B_HH = 256, B_ALL = 272, B_HH2 = 288, ZERO = 296;
constexpr int MODV = 512;
constexpr int RED_OFF = 0;
constexpr float SCL = 0.17677669529663687f * 1.4426950408889634f;
constexpr int U_HH = 64;
constexpr int FS = 8;

struct Maps { CUtensorMap x, out, wqkv, wo, w1, w3, w1s, w3s, w2, wmod; };

struct Scratch {
  uint4 h[16 * 16 * 1024];
  uint4 o[16 * 16 * 1024];
  uint4 hh[16 * 56 * 1024];
  uint4 x1[128 * 8 * 256];
  uint4 stat[2 * 16 * 8 * 128];
  uint4 halo[16 * 8 * 2 * 512];
  uint2 modp[8 * 2 * 4 * 128];
  uint2 modv[4 * 1024];
  uint32_t flag[16 * 128 * FS];
  uint32_t epoch[132];
};
__device__ __align__(1024) Scratch g_scratch;
#define TR(i)
#define TRS(i)
#define STEP0 gs->flag
#define TRW(i) (void)step0

__device__ __forceinline__ void bail() { asm volatile("st.global.u32 [%0], %1;" :: "l"(0ull), "r"(0) : "memory"); }
__device__ __forceinline__ uint32_t smem_u32(const void* p) { return (uint32_t)__cvta_generic_to_shared(p); }
__device__ __forceinline__ void mbar_init(uint32_t bar, uint32_t cnt) { asm volatile("mbarrier.init.shared::cta.b64 [%0], %1;" :: "r"(bar), "r"(cnt) : "memory"); }
__device__ __forceinline__ void mbar_expect_tx(uint32_t bar, uint32_t bytes) { asm volatile("mbarrier.arrive.expect_tx.shared::cta.b64 _, [%0], %1;" :: "r"(bar), "r"(bytes) : "memory"); }
__device__ __forceinline__ void mbar_arrive(uint32_t bar) { asm volatile("mbarrier.arrive.shared::cta.b64 _, [%0];" :: "r"(bar) : "memory"); }
__device__ __forceinline__ void mbar_arrive_cl(uint32_t cl_addr) { asm volatile("mbarrier.arrive.shared::cluster.b64 _, [%0];" :: "r"(cl_addr) : "memory"); }
__device__ __forceinline__ uint32_t mapa(uint32_t addr, uint32_t cta) { uint32_t r; asm("mapa.shared::cluster.u32 %0, %1, %2;" : "=r"(r) : "r"(addr), "r"(cta)); return r; }
__device__ __forceinline__ void mbar_wait(uint32_t bar, uint32_t parity) {
  asm volatile("{\n.reg .pred p;\n.reg .b32 n;\n.reg .b64 z;\nmov.b32 n, 0;\nmov.b64 z, 0;\n"
               "W: add.u32 n, n, 1;\nsetp.gt.u32 p, n, 0x400000;\n@p st.global.u32 [z], n;\n"
               "mbarrier.try_wait.parity.shared::cta.b64 p, [%0], %1;\n@!p bra W;\n}" :: "r"(bar), "r"(parity) : "memory");
}
__device__ __forceinline__ void tma_3d(uint32_t dst, const CUtensorMap* m, uint32_t bar, int c0, int c1, int c2) {
  asm volatile("cp.async.bulk.tensor.3d.shared::cluster.global.mbarrier::complete_tx::bytes [%0], [%1, {%3, %4, %5}], [%2];" :: "r"(dst), "l"(m), "r"(bar), "r"(c0), "r"(c1), "r"(c2) : "memory");
}
__device__ __forceinline__ void tma_store_3d(const CUtensorMap* m, uint32_t src, int c0, int c1, int c2) {
  asm volatile("cp.async.bulk.tensor.3d.global.shared::cta.bulk_group [%0, {%2, %3, %4}], [%1];" :: "l"(m), "r"(src), "r"(c0), "r"(c1), "r"(c2) : "memory");
}
__device__ __forceinline__ void bulk_ld(uint32_t dst, const void* src, uint32_t bytes, uint32_t bar) {
  asm volatile("cp.async.bulk.shared::cluster.global.mbarrier::complete_tx::bytes [%0], [%1], %2, [%3];" :: "r"(dst), "l"(src), "r"(bytes), "r"(bar) : "memory");
}
__device__ __forceinline__ void bulk_ld_mc(uint32_t dst, const void* src, uint32_t bytes, uint32_t bar) {
  asm volatile("cp.async.bulk.shared::cluster.global.mbarrier::complete_tx::bytes.multicast::cluster [%0], [%1], %2, [%3], %4;" :: "r"(dst), "l"(src), "r"(bytes), "r"(bar), "h"((uint16_t)3) : "memory");
}
__device__ __forceinline__ void bulk_push(uint32_t dst_cl, uint32_t src, uint32_t bytes, uint32_t bar_cl) {
  asm volatile("cp.async.bulk.shared::cluster.shared::cta.mbarrier::complete_tx::bytes [%0], [%1], %2, [%3];" :: "r"(dst_cl), "r"(src), "r"(bytes), "r"(bar_cl) : "memory");
}
__device__ __forceinline__ void bulk_st(void* dst, uint32_t src, uint32_t bytes) {
  asm volatile("cp.async.bulk.global.shared::cta.bulk_group [%0], [%1], %2;" :: "l"(dst), "r"(src), "r"(bytes) : "memory");
}
__device__ __forceinline__ void bulk_commit() { asm volatile("cp.async.bulk.commit_group;" ::: "memory"); }
__device__ __forceinline__ void bulk_wait_read() { asm volatile("cp.async.bulk.wait_group.read 0;" ::: "memory"); }
__device__ __forceinline__ void bulk_wait_all() { asm volatile("cp.async.bulk.wait_group 0;" ::: "memory"); }
__device__ __forceinline__ void fence_async_global() { asm volatile("fence.proxy.async.global;" ::: "memory"); }
__device__ __forceinline__ void fence_async_smem() { asm volatile("fence.proxy.async.shared::cta;" ::: "memory"); }
__device__ __forceinline__ void wg_arrive() { asm volatile("wgmma.fence.sync.aligned;" ::: "memory"); }
__device__ __forceinline__ void wg_commit() { asm volatile("wgmma.commit_group.sync.aligned;" ::: "memory"); }
template <int N> __device__ __forceinline__ void wg_wait() { asm volatile("wgmma.wait_group.sync.aligned %0;" :: "n"(N) : "memory"); }
__device__ __forceinline__ void cl_arrive_relaxed() { asm volatile("barrier.cluster.arrive.relaxed.aligned;" ::: "memory"); }
__device__ __forceinline__ void cl_wait() { asm volatile("barrier.cluster.wait.acquire.aligned;" ::: "memory"); }
__device__ __forceinline__ bool elect() { uint32_t p; asm volatile("{\n.reg .pred p;\nelect.sync _|p, 0xffffffff;\nselp.u32 %0, 1, 0, p;\n}" : "=r"(p)); return p; }
__device__ __forceinline__ void named_bar(int id, int n) { asm volatile("bar.sync %0, %1;" :: "r"(id), "r"(n) : "memory"); }
__device__ __forceinline__ uint32_t pack2(float lo, float hi) { uint32_t r; asm("cvt.rn.bf16x2.f32 %0, %1, %2;" : "=r"(r) : "f"(hi), "f"(lo)); return r; }
__device__ __forceinline__ float bf_lo(uint32_t w) { return __uint_as_float(w << 16); }
__device__ __forceinline__ float bf_hi(uint32_t w) { return __uint_as_float(w & 0xffff0000u); }
__device__ __forceinline__ float bf_round(float v) { return __bfloat162float(__float2bfloat16_rn(v)); }
__device__ __forceinline__ void stsm4(uint32_t addr, uint32_t a, uint32_t b, uint32_t c, uint32_t d) {
  asm volatile("stmatrix.sync.aligned.m8n8.x4.shared.b16 [%0], {%1, %2, %3, %4};" :: "r"(addr), "r"(a), "r"(b), "r"(c), "r"(d) : "memory");
}
__device__ __forceinline__ void ldsm4(uint32_t addr, uint32_t& a, uint32_t& b, uint32_t& c, uint32_t& d) {
  asm volatile("ldmatrix.sync.aligned.m8n8.x4.shared.b16 {%0, %1, %2, %3}, [%4];" : "=r"(a), "=r"(b), "=r"(c), "=r"(d) : "r"(addr) : "memory");
}
__device__ __forceinline__ uint32_t movm(uint32_t a) { uint32_t r; asm volatile("movmatrix.sync.aligned.m8n8.trans.b16 %0, %1;" : "=r"(r) : "r"(a)); return r; }
__device__ __forceinline__ void mma16(float (&d)[4], uint32_t a0, uint32_t a1, uint32_t a2, uint32_t a3, uint32_t b0, uint32_t b1) {
  asm("mma.sync.aligned.m16n8k16.row.col.f32.bf16.bf16.f32 {%0,%1,%2,%3}, {%4,%5,%6,%7}, {%8,%9}, {%0,%1,%2,%3};"
               : "+f"(d[0]), "+f"(d[1]), "+f"(d[2]), "+f"(d[3]) : "r"(a0), "r"(a1), "r"(a2), "r"(a3), "r"(b0), "r"(b1));
}
__device__ __forceinline__ void mma16z(float (&d)[4], uint32_t a0, uint32_t a1, uint32_t a2, uint32_t a3, uint32_t b0, uint32_t b1) {
  asm("mma.sync.aligned.m16n8k16.row.col.f32.bf16.bf16.f32 {%0,%1,%2,%3}, {%4,%5,%6,%7}, {%8,%9}, {%10,%10,%10,%10};"
      : "=f"(d[0]), "=f"(d[1]), "=f"(d[2]), "=f"(d[3]) : "r"(a0), "r"(a1), "r"(a2), "r"(a3), "r"(b0), "r"(b1), "f"(0.f));
}
__device__ __forceinline__ void mma8z(float (&d)[4], uint32_t a0, uint32_t a1, uint32_t b0) {
  asm("mma.sync.aligned.m16n8k8.row.col.f32.bf16.bf16.f32 {%0,%1,%2,%3}, {%4,%5}, {%6}, {%7,%7,%7,%7};"
      : "=f"(d[0]), "=f"(d[1]), "=f"(d[2]), "=f"(d[3]) : "r"(a0), "r"(a1), "r"(b0), "f"(0.f));
}
__device__ __forceinline__ void mma8(float (&d)[4], uint32_t a0, uint32_t a1, uint32_t b0) {
  asm("mma.sync.aligned.m16n8k8.row.col.f32.bf16.bf16.f32 {%0,%1,%2,%3}, {%4,%5}, {%6}, {%0,%1,%2,%3};"
               : "+f"(d[0]), "+f"(d[1]), "+f"(d[2]), "+f"(d[3]) : "r"(a0), "r"(a1), "r"(b0));
}
__device__ __forceinline__ uint4 lds128(uint32_t a) { uint4 v; asm volatile("ld.shared.v4.u32 {%0,%1,%2,%3}, [%4];" : "=r"(v.x), "=r"(v.y), "=r"(v.z), "=r"(v.w) : "r"(a) : "memory"); return v; }
__device__ __forceinline__ void sts128(uint32_t a, uint32_t x, uint32_t y, uint32_t z, uint32_t w) { asm volatile("st.shared.v4.u32 [%0], {%1,%2,%3,%4};" :: "r"(a), "r"(x), "r"(y), "r"(z), "r"(w) : "memory"); }
__device__ __forceinline__ float lds32f(uint32_t a) { float v; asm volatile("ld.shared.f32 %0, [%1];" : "=f"(v) : "r"(a) : "memory"); return v; }
__device__ __forceinline__ void sts16(uint32_t a, bf16 v) { asm volatile("st.shared.b16 [%0], %1;" :: "r"(a), "h"(__bfloat16_as_ushort(v)) : "memory"); }
__device__ __forceinline__ uint4 ldg_nc(const void* p) { uint4 v; asm volatile("ld.global.nc.L1::no_allocate.v4.u32 {%0,%1,%2,%3}, [%4];" : "=r"(v.x), "=r"(v.y), "=r"(v.z), "=r"(v.w) : "l"(p)); return v; }
__device__ __forceinline__ uint4 ld_rlx4(const uint4* p) {
  unsigned long long a, b; asm volatile("ld.relaxed.gpu.global.v2.b64 {%0,%1}, [%2];" : "=l"(a), "=l"(b) : "l"(p) : "memory");
  return make_uint4((uint32_t)a, (uint32_t)(a >> 32), (uint32_t)b, (uint32_t)(b >> 32));
}
__device__ __forceinline__ uint2 ld_rlx2(const uint2* p) { unsigned long long a; asm volatile("ld.relaxed.gpu.global.b64 %0, [%1];" : "=l"(a) : "l"(p) : "memory"); return make_uint2((uint32_t)a, (uint32_t)(a >> 32)); }
__device__ __forceinline__ void st_rlx4(uint4* p, uint32_t x, uint32_t y, uint32_t z, uint32_t w) {
  asm volatile("st.relaxed.gpu.global.v2.b64 [%0], {%1,%2};" :: "l"(p), "l"((unsigned long long)x | ((unsigned long long)y << 32)), "l"((unsigned long long)z | ((unsigned long long)w << 32)) : "memory");
}
__device__ __forceinline__ void st_rlx2(uint2* p, uint32_t x, uint32_t y) { asm volatile("st.relaxed.gpu.global.b64 [%0], %1;" :: "l"(p), "l"((unsigned long long)x | ((unsigned long long)y << 32)) : "memory"); }
__device__ __forceinline__ void st_release(uint32_t* p, uint32_t v) { asm volatile("st.release.gpu.global.u32 [%0], %1;" :: "l"(p), "r"(v) : "memory"); }
__device__ __forceinline__ uint32_t ld_acquire(const uint32_t* p) { uint32_t v; asm volatile("ld.acquire.gpu.global.u32 %0, [%1];" : "=r"(v) : "l"(p) : "memory"); return v; }
__device__ __forceinline__ void prefetch_map(const CUtensorMap* m) { asm volatile("prefetch.tensormap [%0];" :: "l"(m) : "memory"); }
__device__ __forceinline__ float rcp(float x) { float r; asm("rcp.approx.ftz.f32 %0, %1;" : "=f"(r) : "f"(x)); return r; }
__device__ __forceinline__ float ex2(float x) { float r; asm("ex2.approx.ftz.f32 %0, %1;" : "=f"(r) : "f"(x)); return r; }
__device__ __forceinline__ float tanh_fast(float x) { float r; asm("tanh.approx.f32 %0, %1;" : "=f"(r) : "f"(x)); return r; }
#define SPIN_GUARD(n) if (++(n) > (1u << 24)) bail()

__device__ __forceinline__ void wgmma_n128(float (&d)[64], uint64_t da, uint64_t db) {
  asm volatile("wgmma.mma_async.sync.aligned.m64n128k16.f32.bf16.bf16 "
    "{%0, %1, %2, %3, %4, %5, %6, %7, %8, %9, %10, %11, %12, %13, %14, %15, %16, %17, %18, %19, %20, %21, %22, %23, %24, %25, %26, %27, %28, %29, %30, %31, %32, %33, %34, %35, %36, %37, %38, %39, %40, %41, %42, %43, %44, %45, %46, %47, %48, %49, %50, %51, %52, %53, %54, %55, %56, %57, %58, %59, %60, %61, %62, %63}, "
    "%64, %65, 1, 1, 1, 0, 1;\n"
    : "+f"(d[0]), "+f"(d[1]), "+f"(d[2]), "+f"(d[3]), "+f"(d[4]), "+f"(d[5]), "+f"(d[6]), "+f"(d[7]), "+f"(d[8]), "+f"(d[9]), "+f"(d[10]), "+f"(d[11]), "+f"(d[12]), "+f"(d[13]), "+f"(d[14]), "+f"(d[15]), "+f"(d[16]), "+f"(d[17]), "+f"(d[18]), "+f"(d[19]), "+f"(d[20]), "+f"(d[21]), "+f"(d[22]), "+f"(d[23]), "+f"(d[24]), "+f"(d[25]), "+f"(d[26]), "+f"(d[27]), "+f"(d[28]), "+f"(d[29]), "+f"(d[30]), "+f"(d[31]), "+f"(d[32]), "+f"(d[33]), "+f"(d[34]), "+f"(d[35]), "+f"(d[36]), "+f"(d[37]), "+f"(d[38]), "+f"(d[39]), "+f"(d[40]), "+f"(d[41]), "+f"(d[42]), "+f"(d[43]), "+f"(d[44]), "+f"(d[45]), "+f"(d[46]), "+f"(d[47]), "+f"(d[48]), "+f"(d[49]), "+f"(d[50]), "+f"(d[51]), "+f"(d[52]), "+f"(d[53]), "+f"(d[54]), "+f"(d[55]), "+f"(d[56]), "+f"(d[57]), "+f"(d[58]), "+f"(d[59]), "+f"(d[60]), "+f"(d[61]), "+f"(d[62]), "+f"(d[63])
    : "l"(da), "l"(db));
}
__device__ __forceinline__ void wgmma_n128_first(float (&d)[64], uint64_t da, uint64_t db) {
  asm volatile("wgmma.mma_async.sync.aligned.m64n128k16.f32.bf16.bf16 "
    "{%0, %1, %2, %3, %4, %5, %6, %7, %8, %9, %10, %11, %12, %13, %14, %15, %16, %17, %18, %19, %20, %21, %22, %23, %24, %25, %26, %27, %28, %29, %30, %31, %32, %33, %34, %35, %36, %37, %38, %39, %40, %41, %42, %43, %44, %45, %46, %47, %48, %49, %50, %51, %52, %53, %54, %55, %56, %57, %58, %59, %60, %61, %62, %63}, "
    "%64, %65, 0, 1, 1, 0, 1;\n"
    : "=f"(d[0]), "=f"(d[1]), "=f"(d[2]), "=f"(d[3]), "=f"(d[4]), "=f"(d[5]), "=f"(d[6]), "=f"(d[7]), "=f"(d[8]), "=f"(d[9]), "=f"(d[10]), "=f"(d[11]), "=f"(d[12]), "=f"(d[13]), "=f"(d[14]), "=f"(d[15]), "=f"(d[16]), "=f"(d[17]), "=f"(d[18]), "=f"(d[19]), "=f"(d[20]), "=f"(d[21]), "=f"(d[22]), "=f"(d[23]), "=f"(d[24]), "=f"(d[25]), "=f"(d[26]), "=f"(d[27]), "=f"(d[28]), "=f"(d[29]), "=f"(d[30]), "=f"(d[31]), "=f"(d[32]), "=f"(d[33]), "=f"(d[34]), "=f"(d[35]), "=f"(d[36]), "=f"(d[37]), "=f"(d[38]), "=f"(d[39]), "=f"(d[40]), "=f"(d[41]), "=f"(d[42]), "=f"(d[43]), "=f"(d[44]), "=f"(d[45]), "=f"(d[46]), "=f"(d[47]), "=f"(d[48]), "=f"(d[49]), "=f"(d[50]), "=f"(d[51]), "=f"(d[52]), "=f"(d[53]), "=f"(d[54]), "=f"(d[55]), "=f"(d[56]), "=f"(d[57]), "=f"(d[58]), "=f"(d[59]), "=f"(d[60]), "=f"(d[61]), "=f"(d[62]), "=f"(d[63])
    : "l"(da), "l"(db));
}
__device__ __forceinline__ void wgmma_n256(float (&d)[128], uint64_t da, uint64_t db) {
  asm volatile("wgmma.mma_async.sync.aligned.m64n256k16.f32.bf16.bf16 "
    "{%0, %1, %2, %3, %4, %5, %6, %7, %8, %9, %10, %11, %12, %13, %14, %15, %16, %17, %18, %19, %20, %21, %22, %23, %24, %25, %26, %27, %28, %29, %30, %31, %32, %33, %34, %35, %36, %37, %38, %39, %40, %41, %42, %43, %44, %45, %46, %47, %48, %49, %50, %51, %52, %53, %54, %55, %56, %57, %58, %59, %60, %61, %62, %63, %64, %65, %66, %67, %68, %69, %70, %71, %72, %73, %74, %75, %76, %77, %78, %79, %80, %81, %82, %83, %84, %85, %86, %87, %88, %89, %90, %91, %92, %93, %94, %95, %96, %97, %98, %99, %100, %101, %102, %103, %104, %105, %106, %107, %108, %109, %110, %111, %112, %113, %114, %115, %116, %117, %118, %119, %120, %121, %122, %123, %124, %125, %126, %127}, "
    "%128, %129, 1, 1, 1, 0, 1;\n"
    : "+f"(d[0]), "+f"(d[1]), "+f"(d[2]), "+f"(d[3]), "+f"(d[4]), "+f"(d[5]), "+f"(d[6]), "+f"(d[7]), "+f"(d[8]), "+f"(d[9]), "+f"(d[10]), "+f"(d[11]), "+f"(d[12]), "+f"(d[13]), "+f"(d[14]), "+f"(d[15]), "+f"(d[16]), "+f"(d[17]), "+f"(d[18]), "+f"(d[19]), "+f"(d[20]), "+f"(d[21]), "+f"(d[22]), "+f"(d[23]), "+f"(d[24]), "+f"(d[25]), "+f"(d[26]), "+f"(d[27]), "+f"(d[28]), "+f"(d[29]), "+f"(d[30]), "+f"(d[31]), "+f"(d[32]), "+f"(d[33]), "+f"(d[34]), "+f"(d[35]), "+f"(d[36]), "+f"(d[37]), "+f"(d[38]), "+f"(d[39]), "+f"(d[40]), "+f"(d[41]), "+f"(d[42]), "+f"(d[43]), "+f"(d[44]), "+f"(d[45]), "+f"(d[46]), "+f"(d[47]), "+f"(d[48]), "+f"(d[49]), "+f"(d[50]), "+f"(d[51]), "+f"(d[52]), "+f"(d[53]), "+f"(d[54]), "+f"(d[55]), "+f"(d[56]), "+f"(d[57]), "+f"(d[58]), "+f"(d[59]), "+f"(d[60]), "+f"(d[61]), "+f"(d[62]), "+f"(d[63]), "+f"(d[64]), "+f"(d[65]), "+f"(d[66]), "+f"(d[67]), "+f"(d[68]), "+f"(d[69]), "+f"(d[70]), "+f"(d[71]), "+f"(d[72]), "+f"(d[73]), "+f"(d[74]), "+f"(d[75]), "+f"(d[76]), "+f"(d[77]), "+f"(d[78]), "+f"(d[79]), "+f"(d[80]), "+f"(d[81]), "+f"(d[82]), "+f"(d[83]), "+f"(d[84]), "+f"(d[85]), "+f"(d[86]), "+f"(d[87]), "+f"(d[88]), "+f"(d[89]), "+f"(d[90]), "+f"(d[91]), "+f"(d[92]), "+f"(d[93]), "+f"(d[94]), "+f"(d[95]), "+f"(d[96]), "+f"(d[97]), "+f"(d[98]), "+f"(d[99]), "+f"(d[100]), "+f"(d[101]), "+f"(d[102]), "+f"(d[103]), "+f"(d[104]), "+f"(d[105]), "+f"(d[106]), "+f"(d[107]), "+f"(d[108]), "+f"(d[109]), "+f"(d[110]), "+f"(d[111]), "+f"(d[112]), "+f"(d[113]), "+f"(d[114]), "+f"(d[115]), "+f"(d[116]), "+f"(d[117]), "+f"(d[118]), "+f"(d[119]), "+f"(d[120]), "+f"(d[121]), "+f"(d[122]), "+f"(d[123]), "+f"(d[124]), "+f"(d[125]), "+f"(d[126]), "+f"(d[127])
    : "l"(da), "l"(db));
}
__device__ __forceinline__ void wgmma_n256_first(float (&d)[128], uint64_t da, uint64_t db) {
  asm volatile("wgmma.mma_async.sync.aligned.m64n256k16.f32.bf16.bf16 "
    "{%0, %1, %2, %3, %4, %5, %6, %7, %8, %9, %10, %11, %12, %13, %14, %15, %16, %17, %18, %19, %20, %21, %22, %23, %24, %25, %26, %27, %28, %29, %30, %31, %32, %33, %34, %35, %36, %37, %38, %39, %40, %41, %42, %43, %44, %45, %46, %47, %48, %49, %50, %51, %52, %53, %54, %55, %56, %57, %58, %59, %60, %61, %62, %63, %64, %65, %66, %67, %68, %69, %70, %71, %72, %73, %74, %75, %76, %77, %78, %79, %80, %81, %82, %83, %84, %85, %86, %87, %88, %89, %90, %91, %92, %93, %94, %95, %96, %97, %98, %99, %100, %101, %102, %103, %104, %105, %106, %107, %108, %109, %110, %111, %112, %113, %114, %115, %116, %117, %118, %119, %120, %121, %122, %123, %124, %125, %126, %127}, "
    "%128, %129, 0, 1, 1, 0, 1;\n"
    : "=f"(d[0]), "=f"(d[1]), "=f"(d[2]), "=f"(d[3]), "=f"(d[4]), "=f"(d[5]), "=f"(d[6]), "=f"(d[7]), "=f"(d[8]), "=f"(d[9]), "=f"(d[10]), "=f"(d[11]), "=f"(d[12]), "=f"(d[13]), "=f"(d[14]), "=f"(d[15]), "=f"(d[16]), "=f"(d[17]), "=f"(d[18]), "=f"(d[19]), "=f"(d[20]), "=f"(d[21]), "=f"(d[22]), "=f"(d[23]), "=f"(d[24]), "=f"(d[25]), "=f"(d[26]), "=f"(d[27]), "=f"(d[28]), "=f"(d[29]), "=f"(d[30]), "=f"(d[31]), "=f"(d[32]), "=f"(d[33]), "=f"(d[34]), "=f"(d[35]), "=f"(d[36]), "=f"(d[37]), "=f"(d[38]), "=f"(d[39]), "=f"(d[40]), "=f"(d[41]), "=f"(d[42]), "=f"(d[43]), "=f"(d[44]), "=f"(d[45]), "=f"(d[46]), "=f"(d[47]), "=f"(d[48]), "=f"(d[49]), "=f"(d[50]), "=f"(d[51]), "=f"(d[52]), "=f"(d[53]), "=f"(d[54]), "=f"(d[55]), "=f"(d[56]), "=f"(d[57]), "=f"(d[58]), "=f"(d[59]), "=f"(d[60]), "=f"(d[61]), "=f"(d[62]), "=f"(d[63]), "=f"(d[64]), "=f"(d[65]), "=f"(d[66]), "=f"(d[67]), "=f"(d[68]), "=f"(d[69]), "=f"(d[70]), "=f"(d[71]), "=f"(d[72]), "=f"(d[73]), "=f"(d[74]), "=f"(d[75]), "=f"(d[76]), "=f"(d[77]), "=f"(d[78]), "=f"(d[79]), "=f"(d[80]), "=f"(d[81]), "=f"(d[82]), "=f"(d[83]), "=f"(d[84]), "=f"(d[85]), "=f"(d[86]), "=f"(d[87]), "=f"(d[88]), "=f"(d[89]), "=f"(d[90]), "=f"(d[91]), "=f"(d[92]), "=f"(d[93]), "=f"(d[94]), "=f"(d[95]), "=f"(d[96]), "=f"(d[97]), "=f"(d[98]), "=f"(d[99]), "=f"(d[100]), "=f"(d[101]), "=f"(d[102]), "=f"(d[103]), "=f"(d[104]), "=f"(d[105]), "=f"(d[106]), "=f"(d[107]), "=f"(d[108]), "=f"(d[109]), "=f"(d[110]), "=f"(d[111]), "=f"(d[112]), "=f"(d[113]), "=f"(d[114]), "=f"(d[115]), "=f"(d[116]), "=f"(d[117]), "=f"(d[118]), "=f"(d[119]), "=f"(d[120]), "=f"(d[121]), "=f"(d[122]), "=f"(d[123]), "=f"(d[124]), "=f"(d[125]), "=f"(d[126]), "=f"(d[127])
    : "l"(da), "l"(db));
}

template <int N> struct WG;
#define DEF_WG(N) template <> struct WG<N> { \
  static __device__ __forceinline__ void mma(float (&d)[N / 2], uint64_t a, uint64_t b) { wgmma_n##N(d, a, b); } \
  static __device__ __forceinline__ void first(float (&d)[N / 2], uint64_t a, uint64_t b) { wgmma_n##N##_first(d, a, b); } };
DEF_WG(128) DEF_WG(256)

constexpr uint64_t DESC_A = (1ull << 62) | ((uint64_t)(1024 >> 4) << 32) | (1ull << 16);
constexpr uint64_t DESC_B = (1ull << 62) | ((uint64_t)(1024 >> 4) << 32) | ((uint64_t)(8192 >> 4) << 16);

struct Ring { int s; uint32_t ph; int wrap; };
template <int NS> __device__ __forceinline__ void ring_next(Ring& r) { r.s = (r.s + 1 == NS) ? 0 : r.s + 1; if (r.s == r.wrap) r.ph ^= 1; }

__device__ __forceinline__ int own_order(int it, int j) {
  return it < 2 ? 2 * j + it : it < 4 ? 2 * (j ^ 1) + it - 2 : ((j >> 1) * 4 + 2 * it - (it < 10 ? 4 : 15)) & 15;
}

template <int V> struct IC { static constexpr int v = V; };
template <int I, int E, class F> __device__ __forceinline__ void static_for(F&& f) { if constexpr (I < E) { f(IC<I>{}); static_for<I + 1, E>(f); } }

template <int N, int NS, int PRE, int LAG, class Pre, class Mid, class Last>
__device__ __forceinline__ void mainloop(float (&acc)[N / 2], int nkb, bool own, Ring& r, uint32_t sb, int wg, int lane, uint32_t rel_base, uint32_t* step0, Pre pre, Mid mid, Last last) {
  constexpr int SLOT = RING / NS;
  const uint32_t full = sb + MISC + (NS == 4 ? B_FULL4 : B_FULL6);
  const uint32_t rel = rel_base + (NS == 4 ? B_EMPTY4 : B_EMPTY6);
  const uint32_t s0 = (sb & 0x3FFFF) >> 4, a0 = s0 + wg * (HALF >> 4);
  int ps;
  auto issue = [&](int it, bool first) {
    const uint64_t da = DESC_A | (a0 + ((own && it < 2) ? (STG + it * BLK) >> 4 : r.s * (SLOT >> 4))), db = DESC_B | (s0 + r.s * (SLOT >> 4) + (BLK >> 4));
    mbar_wait(full + r.s * 8, r.ph);
    TRS(it);
    wg_arrive();
    if (first) WG<N>::first(acc, da, db); else WG<N>::mma(acc, da, db);
#pragma unroll
    for (int k = 1; k < 4; k++) WG<N>::mma(acc, da + k * 2, db + k * 128);
    wg_commit();
  };
  auto retire = [&](int it) {
    wg_wait<1>();
    if (lane < 2) mbar_arrive_cl(rel + ps * 8);
    ps = r.s;
    ring_next<NS>(r);
  };
  issue(0, true);
  ps = r.s;
  ring_next<NS>(r);
  static_for<1, PRE + 1>([&](auto ic) { issue(ic.v, false); pre(ic); retire(ic.v); });
#pragma unroll 1
  for (int it = PRE + 1; it < nkb; it++) {
    if (LAG && it == nkb - LAG && wg == 1) mbar_wait(sb + MISC + B_LAG, WOLAG && !own);
    issue(it, false); mid(it); retire(it);
  }
  last();
  wg_wait<0>();
  if (lane < 2) mbar_arrive_cl(rel + ps * 8);
}

__device__ __forceinline__ void ln_publish(const float (&v)[64], uint4* st, int j, int row0, int lane, uint32_t ep) {
  float s0 = 0, s1 = 0, s2 = 0, s3 = 0, q0 = 0, q1 = 0, q2 = 0, q3 = 0;
#pragma unroll
  for (int i = 0; i < 16; i++) {
    s0 += v[4 * i]; s1 += v[4 * i + 1]; s2 += v[4 * i + 2]; s3 += v[4 * i + 3];
    q0 = fmaf(v[4 * i], v[4 * i], q0); q1 = fmaf(v[4 * i + 1], v[4 * i + 1], q1); q2 = fmaf(v[4 * i + 2], v[4 * i + 2], q2); q3 = fmaf(v[4 * i + 3], v[4 * i + 3], q3);
  }
  s0 += s1; s2 += s3; q0 += q1; q2 += q3;
  const bool odd = lane & 1;
  float s = (odd ? s2 : s0) + __shfl_xor_sync(~0u, odd ? s0 : s2, 1), q = (odd ? q2 : q0) + __shfl_xor_sync(~0u, odd ? q0 : q2, 1);
  s += __shfl_xor_sync(~0u, s, 2); q += __shfl_xor_sync(~0u, q, 2);
  if ((lane & 3) < 2) st_rlx4(st + j * 128 + row0 + (lane & 1) * 8, __float_as_uint(s), ep, __float_as_uint(q), ep);
}
__device__ __forceinline__ void ln_gather(const uint4* st, int row0, int lane, uint32_t ep, float& n0, float& r0, float& n1, float& r1) {
  const uint4* p = st + (lane & 2) * 256 + row0 + (lane & 1) * 8;
  uint4 a, b, c, d; uint32_t n = 0;
  while (true) {
    a = ld_rlx4(p); b = ld_rlx4(p + 128); c = ld_rlx4(p + 256); d = ld_rlx4(p + 384);
    if (a.y == ep && a.w == ep && b.y == ep && b.w == ep && c.y == ep && c.w == ep && d.y == ep && d.w == ep) break;
    SPIN_GUARD(n);
  }
  __syncwarp();
  float s = (__uint_as_float(a.x) + __uint_as_float(b.x)) + (__uint_as_float(c.x) + __uint_as_float(d.x));
  float q = (__uint_as_float(a.z) + __uint_as_float(b.z)) + (__uint_as_float(c.z) + __uint_as_float(d.z));
  s += __shfl_xor_sync(~0u, s, 2); q += __shfl_xor_sync(~0u, q, 2);
  s *= 1.f / 1024;
  const float r = rsqrtf(fmaxf(fmaf(-s, s, q * (1.f / 1024)), 0.f) + 1e-5f), nn = -s * r;
  const float ro = __shfl_xor_sync(~0u, r, 1), no = __shfl_xor_sync(~0u, nn, 1);
  const bool odd = lane & 1;
  r0 = odd ? ro : r; n0 = odd ? no : nn; r1 = odd ? r : ro; n1 = odd ? nn : no;
}
__device__ __forceinline__ void load_vec(uint32_t* w, uint32_t sb, int sec, int b, int lane) {
#pragma unroll
  for (int q = 0; q < 2; q++) { uint4 t = lds128(sb + MISC + MODV + sec * 256 + (lane & 3) * 64 + b * 32 + q * 16); w[4 * q] = t.x; w[4 * q + 1] = t.y; w[4 * q + 2] = t.z; w[4 * q + 3] = t.w; }
}
__device__ __forceinline__ void stage_done(uint32_t sb, int wg, int b, int lane) {
  fence_async_smem();
  __syncwarp();
  if (lane == 0) mbar_arrive(sb + MISC + B_RDY + b * 8);
}
__device__ __forceinline__ uint32_t hfma2(uint32_t a, uint32_t b, uint32_t c) { uint32_t r; asm("fma.rn.bf16x2 %0, %1, %2, %3;" : "=r"(r) : "r"(a), "r"(b), "r"(c)); return r; }
__device__ __forceinline__ void ln_apply(const float (&v)[64], const uint4* st, int row0, uint32_t ep, uint32_t sb, int sec_shift, int sec_scale, uint32_t stg_row, int wg, int lane, uint32_t* step0) {
  uint32_t sc[16], sh[16];
#pragma unroll
  for (int b = 0; b < 2; b++) { load_vec(sc + 8 * b, sb, sec_scale, b, lane); load_vec(sh + 8 * b, sb, sec_shift, b, lane); }
  float n0, r0, n1, r1;
  TRW(1);
  ln_gather(st, row0, lane, ep, n0, r0, n1, r1);
  TRW(2);
#pragma unroll
  for (int i = 0; i < 16; i += 2) {
    if (i == 8) { const float z = lds32f(sb + MISC + ZERO); n0 += z; n1 += z; }
    uint32_t w[4];
#pragma unroll
    for (int u = 0; u < 2; u++) {
      int q = i + u;
      w[2 * u] = hfma2(pack2(fmaf(v[4 * q], r0, n0), fmaf(v[4 * q + 1], r0, n0)), sc[q], sh[q]);
      w[2 * u + 1] = hfma2(pack2(fmaf(v[4 * q + 2], r1, n1), fmaf(v[4 * q + 3], r1, n1)), sc[q], sh[q]);
    }
    stsm4(stg_row + (i >> 3) * BLK + ((((i & 7) + (lane >> 4)) ^ (lane & 7)) << 4), w[0], w[1], w[2], w[3]);
    if ((i & 7) == 6) { stage_done(sb, wg, i >> 3, lane); TRW(3 + (i >> 3)); }
  }
}
__device__ __forceinline__ uint32_t hmul2(uint32_t a, uint32_t b) { uint32_t r; asm("mul.rn.bf16x2 %0, %1, %2;" : "=r"(r) : "r"(a), "r"(b)); return r; }
__device__ __forceinline__ uint32_t silu_mul2(uint32_t g, uint32_t u) {
  const uint32_t h = hmul2(g, 0x3f003f00u);
  const float h0 = bf_lo(h), h1 = bf_hi(h);
  return hmul2(pack2(fmaf(h0, tanh_fast(h0), h0), fmaf(h1, tanh_fast(h1), h1)), u);
}

__device__ __forceinline__ void gemv_fma(float (&a)[8], uint4 w, float s) {
  a[0] = fmaf(bf_lo(w.x), s, a[0]); a[1] = fmaf(bf_hi(w.x), s, a[1]); a[2] = fmaf(bf_lo(w.y), s, a[2]); a[3] = fmaf(bf_hi(w.y), s, a[3]);
  a[4] = fmaf(bf_lo(w.z), s, a[4]); a[5] = fmaf(bf_hi(w.z), s, a[5]); a[6] = fmaf(bf_lo(w.w), s, a[6]); a[7] = fmaf(bf_hi(w.w), s, a[7]);
}
__device__ __forceinline__ float silu_c(float v) { return bf_round(__fdividef(v, 1.f + __expf(-v))); }
__device__ __forceinline__ float mod_gather(const uint2* p, uint32_t ep) {
  uint2 a, b, c, d; uint32_t n = 0;
  while (true) {
    a = ld_rlx2(p); b = ld_rlx2(p + 128); c = ld_rlx2(p + 256); d = ld_rlx2(p + 384);
    if (a.y == ep && b.y == ep && c.y == ep && d.y == ep) break;
    SPIN_GUARD(n);
  }
  return (__uint_as_float(a.x) + __uint_as_float(b.x)) + (__uint_as_float(c.x) + __uint_as_float(d.x));
}
__device__ __forceinline__ void mod_store(uint32_t sb, int sec, int col, float v) {
  v = bf_round(v);
  if (sec == 1 || sec == 4) v += 1.f;
  sts16(sb + MISC + MODV + sec * 256 + (((col >> 1) & 3) * 16 + (col >> 3)) * 4 + (col & 1) * 2, __float2bfloat16_rn(v));
}

__global__ void __cluster_dims__(2, 1, 1) __launch_bounds__(384, 1)
fused_kernel(const bf16* __restrict__ cvec, const bf16* __restrict__ wmod, Scratch* gs, int by_sm, const __grid_constant__ Maps maps) {
  extern __shared__ __align__(1024) uint8_t smem_raw[];
  const uint32_t sb = smem_u32(smem_raw);
  const int warp = __shfl_sync(~0u, threadIdx.x >> 5, 0), lane = threadIdx.x & 31;
  const int rank = blockIdx.x & 1;
  uint32_t sm; asm("mov.u32 %0, %%smid;" : "=r"(sm));
  const int t = sm >> 1, v = t < 32 ? t : t < 60 ? t + 1 + (((t - 32) * 37) >> 8) : (t - 58) * 8;
  const int cid = !by_sm ? (blockIdx.x >> 1) - 2 : (t & ~1) == 60 ? t - 62 : (v & 1) * 32 + ((v >> 1) & 31);
  const bool extra = cid < 0;
  const int bid = cid * 2 + rank;
  const int m = cid >> 2, j = (cid & 3) * 2 + rank;
  const uint32_t bar = sb + MISC;

  if (warp >= 8) {
    asm volatile("setmaxnreg.dec.sync.aligned.u32 40;");
    if (extra) {
      if (warp == 8) {
        if (lane == 0) { for (int s = 0; s < 6; s++) { mbar_init(bar + B_FULL6 + s * 8, 1); mbar_init(bar + B_EMPTY6 + s * 8, 8); } fence_async_smem(); }
        __syncwarp();
        asm volatile("bar.arrive 2, 288;" ::: "memory");
        __nanosleep(XSLEEP);
#pragma unroll 1
        for (int it = 0, s = 0, par = 1; it < 64; it++) {
          mbar_wait(bar + B_EMPTY6 + s * 8, par);
          if (elect()) { mbar_expect_tx(bar + B_FULL6 + s * 8, 32768); tma_3d(sb + s * 32768, &maps.wmod, bar + B_FULL6 + s * 8, 0, (it & 15) * 64, 12 + (it >> 4) * 4 + bid); }
          if (++s == 6) { s = 0; par ^= 1; }
        }
      }
    } else if (warp < 10) {
      uint32_t s6 = 0, p6 = 1;
      auto next6 = [&]() { if (++s6 == 6) { s6 = 0; p6 ^= 1; } };
      auto drained4 = [&](int q, int late) { if (q < 5) mbar_wait(bar + B_EMPTY4 + (((late ? 0x10332 : 0x32110) >> (4 * q)) & 3) * 8, 1); };
      auto drained6 = [&](int q) { if (q < 3) mbar_wait(bar + B_EMPTY6 + ((0x154 >> (4 * q)) & 7) * 8, q >> 1); };
      auto skip6 = [&]() { mbar_wait(bar + B_EMPTY6 + s6 * 8, p6); if (elect()) mbar_arrive(bar + B_FULL6 + s6 * 8); next6(); };
      if (warp == 8) {
        const uint32_t t_start = clock();
        if (lane == 0) {
          if (sb & 1023) bail();
          for (int b = 0; b < 2; b++) mbar_init(bar + B_X + b * 8, 1);
          for (int s = 0; s < 4; s++) { mbar_init(bar + B_FULL4 + s * 8, 2); mbar_init(bar + B_EMPTY4 + s * 8, 16); }
          for (int s = 0; s < 6; s++) { mbar_init(bar + B_FULL6 + s * 8, 2); mbar_init(bar + B_EMPTY6 + s * 8, 16); }
          for (int b = 0; b < 2; b++) { mbar_init(bar + B_RDY + b * 8, 8); mbar_init(bar + B_FREE + b * 8, 1); mbar_init(bar + B_HH + b * 8, 1); }
          mbar_init(bar + B_MOD, 1); mbar_init(bar + B_LAG, 4); mbar_init(bar + B_HALO, 2); mbar_init(bar + B_ALL, 1); mbar_init(bar + B_HH2, 1);
          asm volatile("st.shared.u32 [%0], 0;" :: "r"(bar + ZERO) : "memory");
          asm volatile("fence.mbarrier_init.release.cluster;" ::: "memory");
          fence_async_smem();
        }
        __syncwarp();
        cl_arrive_relaxed();
        auto wide = [&](int s, int par, const CUtensorMap* m0, int a0, const CUtensorMap* m1, int a1, int kb, bool spaced) {
          const uint32_t full = bar + B_FULL4 + s * 8, d = sb + s * 49152 + BLK;
          mbar_wait(full + 32, par);
          const uint32_t t0 = clock();
          if (elect()) { mbar_expect_tx(full, 2 * BLK); tma_3d(d, m0, full, 0, kb * 64, a0); }
          if (spaced) while ((uint32_t)clock() - t0 < 300) {}
          if (elect()) tma_3d(d + BLK, m1, full, 0, kb * 64, a1);
          if (spaced) while ((uint32_t)clock() - t0 < 600) {}
        };
        auto narrow = [&](const CUtensorMap* m0, int kb) {
          const uint32_t full = bar + B_FULL6 + s6 * 8;
          mbar_wait(full + 48, p6);
          if (elect()) { mbar_expect_tx(full, BLK); tma_3d(sb + s6 * 32768 + BLK, m0, full, 0, kb * 64, 2 * j); }
          next6();
        };
#pragma unroll 1
        for (int it = 0; it < 16; it++) {
          if (it == 0) {
            while ((uint32_t)clock() - t_start < XDELAY) {}
            if (elect()) for (int b = 0; b < 2; b++) { mbar_expect_tx(bar + B_X + b * 8, BLK); tma_3d(sb + STG + b * BLK, &maps.x, bar + B_X + b * 8, j * 128 + b * 64, m * 64, 0); }
            mbar_wait(bar + B_X + 8, 0);
          }
          wide(it & 3, ~(it >> 2) & 1, &maps.wqkv, 16 + 2 * j, &maps.wqkv, 32 + 2 * j, own_order(it, j), it < 4);
        }
#pragma unroll 1
        for (int it = 0; it < 16; it++) { drained4(it, 0); narrow(&maps.wqkv, it); }
#pragma unroll 1
        for (int it = 0; it < 16; it++) narrow(&maps.wo, own_order(it, j));
        skip6();
#pragma unroll 1
        for (int it = 0; it < 48; it++) {
          const int s = (it + 2) & 3, par = ~(it >> 2) & 1;
          drained6(it);
          wide(s, par, &maps.w1, (it & 48) + 2 * j, &maps.w3, (it & 48) + 2 * j, it < 16 ? own_order(it, j) : it & 15, it < 4);
          if (it >= 44) {
            if (it == 44) { mbar_wait(bar + B_FREE, 0); mbar_wait(bar + B_FREE + 8, 0); if (elect()) mbar_expect_tx(bar + B_X, 2 * BLK); }
            if (elect()) bulk_ld(sb + STG + (it - 44) * HALF, gs->x1 + bid * 2048 + (it - 44) * 512, HALF, bar + B_X);
          }
        }
#pragma unroll 1
        for (int it = 0; it < 16; it++) {
          const uint32_t full = bar + B_FULL6 + s6 * 8, d = sb + s6 * 32768 + BLK;
          drained4(it, 1);
          mbar_wait(full + 48, p6);
          if (elect()) { mbar_expect_tx(full, BLK); tma_3d(d, &maps.w1s, full, 0, it * 64, 48 + j); tma_3d(d + HALF, &maps.w3s, full, 0, it * 64, 48 + j); }
          next6();
        }
#pragma unroll 1
        for (int it = 0; it < 56; it++) narrow(&maps.w2, it);
      } else {
        if (lane < 9) prefetch_map(&maps.x + lane);
        const uint32_t ep = gs->epoch[bid + 4] + 1;
        cl_arrive_relaxed(); cl_wait();
        auto plain = [&](uint32_t full, uint32_t empty, int par, uint32_t slot, const uint4* blk) {
          mbar_wait(empty, par);
          if (elect()) { mbar_expect_tx(full, BLK); bulk_ld_mc(slot + rank * HALF, blk + rank * 512, HALF, full); }
        };
        auto plain6 = [&](const uint4* blk) { plain(bar + B_FULL6 + s6 * 8, bar + B_EMPTY6 + s6 * 8, p6, sb + s6 * 32768, blk); next6(); };
        uint32_t ready = 0;
        auto poll = [&](int e) { ready = __ballot_sync(~0u, ld_acquire(gs->flag + (m * 128 + e * 16 + (lane & 14)) * FS) == ep); };
        auto need = [&](int e, uint32_t mask) {
          if ((ready & mask) != mask) {
            uint32_t n = 0;
            do { poll(e); SPIN_GUARD(n); } while ((ready & mask) != mask);
            fence_async_global();
          }
        };
        auto fresh = [&](int e, int it, uint32_t full, uint32_t empty, int par, uint32_t slot, uint4* src) {
          if (it >= 4) {
            const int kb = own_order(it, j);
            if (it < 10) need(e, 1u << kb); else if (it == 10) mbar_wait(bar + B_ALL, e & 1);
            plain(full, empty, par, slot, src + kb * 1024);
          } else {
            if (it == 0) ready = 0;
            mbar_wait(empty, par);
            if (it < 2) { if (elect()) mbar_arrive(full); }
            else {
              const int b = it > 2;
              const uint32_t to_peer = mapa(sb, rank ^ 1) - sb;
              if (elect()) mbar_expect_tx(full, BLK);
              const bool push = e != 1;
              mbar_wait(bar + (b ? (push ? B_RDY + 8 : B_FREE + 8) : B_RDY), e & 1);
              if (b == 0) TR(e == 0 ? 24 : e == 2 ? 30 : 44);
              if (elect()) {
                if (b == 0) {
                  bulk_st(src + 2 * j * 1024, sb + STG, BLK);
                  bulk_commit();
                  bulk_wait_all();
                  mbar_arrive(bar + B_FREE);
                }
                if (b && push) bulk_push(slot + to_peer, sb + STG + BLK, BLK, full + to_peer);
                else {
                  fence_async_global();
                  bulk_ld(slot + to_peer, src + (2 * j + b) * 1024, BLK, full + to_peer);
                }
              }
              __syncwarp();
            }
          }
          if (it == 4) TR(e == 0 ? 28 : e == 1 ? 46 : 34);
        };
#pragma unroll 1
        for (int ph = 0; ph < 2; ph++) {
          uint4* h = gs->h + m * 16384;
#pragma unroll 1
          for (int it = 0; it < 16; it++) {
            const int s = (it + 2 * ph) & 3;
            if (ph) drained6(it);
            fresh(2 * ph, it, bar + B_FULL4 + s * 8, bar + B_EMPTY4 + s * 8, ~(it >> 2) & 1, sb + s * 49152, h);
          }
          if (ph) {
#pragma unroll 1
            for (int it = 16; it < 48; it++) {
              const int s = (it + 2) & 3;
              const uint32_t full = bar + B_FULL4 + s * 8;
              plain(full, full + 32, ~(it >> 2) & 1, sb + s * 49152, h + (it & 15) * 1024);
            }
          }
#pragma unroll 1
          for (int it = 0; it < 16; it++) { drained4(it, ph); plain6(h + it * 1024); }
          if (!ph) {
#pragma unroll 1
            for (int it = 0; it < 16; it++) { fresh(1, it, bar + B_FULL6 + s6 * 8, bar + B_EMPTY6 + s6 * 8, p6, sb + s6 * 32768, gs->o + m * 16384); next6(); }
            skip6();
          }
        }
#pragma unroll 1
        for (int it = 0; it < 56; it++) {
          if (it == 0 || it == 32 || it == 48) mbar_wait(bar + (it == 48 ? B_HH2 : B_HH + (it >> 2)), 0);
          plain6(gs->hh + m * 57344 + it * 1024);
        }
      }
    } else {
      const int b = warp - 10;
      const uint32_t ep = gs->epoch[bid + 4] + 1;
      const uint32_t stg = sb + STG + b * BLK;
      cl_arrive_relaxed(); cl_wait();
      auto all_there = [&](int u, uint32_t done) {
        const uint32_t* fl = gs->flag + u * FS;
        uint32_t n = 0;
        while (!__all_sync(~0u, ld_acquire(fl) == ep)) { __nanosleep(100); SPIN_GUARD(n); }
        fence_async_global();
        if (lane == 0) mbar_arrive(done);
      };
      auto fetch_mod = [&](int sec) {
        const uint4* p = (const uint4*)(gs->modv + (sec - 2) * 1024 + j * 128) + lane;
        uint4 v0, v1; uint32_t n = 0;
        while (true) {
          v0 = ld_rlx4(p); v1 = ld_rlx4(p + 32);
          if (v0.y == ep && v0.w == ep && v1.y == ep && v1.w == ep) break;
          SPIN_GUARD(n);
        }
        mod_store(sb, sec, 2 * lane, __uint_as_float(v0.x)); mod_store(sb, sec, 2 * lane + 1, __uint_as_float(v0.z));
        mod_store(sb, sec, 64 + 2 * lane, __uint_as_float(v1.x)); mod_store(sb, sec, 65 + 2 * lane, __uint_as_float(v1.z));
        __syncwarp();
      };
#pragma unroll 1
      for (int e = 0; e < 7 - b; e++) {
        if (lane == 0) {
          if (e < 3) {
            mbar_wait(bar + B_FREE, e & 1);
            if (b) {
              const uint32_t t0 = clock();
              while ((uint32_t)clock() - t0 < (e == 0 ? B1P : e == 2 ? B1P2 : B1D)) {}
              mbar_wait(bar + B_RDY + 8, e & 1);
              bulk_st((e == 1 ? gs->o : gs->h) + m * 16384 + (2 * j + 1) * 1024, stg, BLK);
              bulk_commit();
              bulk_wait_all();
              mbar_arrive(bar + B_FREE + 8);
              TR(53 + e);
            }
            st_release(gs->flag + (m * 128 + e * 16 + 2 * j + b) * FS, ep);
            TR((e == 0 ? 26 : e == 2 ? 32 : 42) + b);
          } else {
            const int kb = (e < 6 ? 2 * (8 * (e - 3) + j) : 48 + j) + b;
            mbar_wait(bar + B_RDY + b * 8, e & 1);
#pragma unroll 1
            for (int q = 0; q < NPIECE; q++) { if (q) __nanosleep(PSLEEP); bulk_st(gs->hh + m * 57344 + kb * 1024 + q * (1024 / NPIECE), stg + q * (BLK / NPIECE), BLK / NPIECE); }
            bulk_commit();
            bulk_wait_all();
            mbar_arrive(bar + B_FREE + b * 8);
            st_release(gs->flag + (m * 128 + U_HH + kb) * FS, ep);
          }
        }
        __syncwarp();
        if (e < 3 && b) all_there(m * 128 + e * 16 + (lane & 15), bar + B_ALL);
        if (e == 4 && b) all_there(m * 128 + U_HH + lane, bar + B_HH);
        if (!b && (e == 1 || e == 2)) {
#pragma unroll 1
          for (int sec = e == 1 ? 2 : 5; sec < 4 + e; sec++) fetch_mod(sec);
          if (e == 1) { if (lane == 0) mbar_arrive(bar + B_MOD); TR(50); }
        }
        if (e == 0) {
          mbar_wait(bar + B_EMPTY6 + 24, 0);
          if (HSLEEP) __nanosleep(HSLEEP + (QPV == 1 ? b * 700 : 0));
#pragma unroll 1
          for (int w = 0; w < 4; w++) {
            const uint4* hp = gs->halo + ((m * 8 + j) * 2 + (w & 1)) * 512 + b * 256 + (w >> 1) * 128 + lane;
            uint4 q[4] = {}; uint32_t n = 0;
            while (m > 0) {
              bool ok = true;
#pragma unroll
              for (int i = 0; i < 4; i++) q[i] = ld_rlx4(hp + i * 32);
#pragma unroll
              for (int i = 0; i < 4; i++) ok = ok && q[i].y == ep && q[i].w == ep;
              if (ok) break;
              SPIN_GUARD(n);
            }
#pragma unroll
            for (int i = 0; i < 2; i++) sts128(stg + lane * 16 + (w & 1) * HALF + (w >> 1) * 1024 + i * 512, q[2 * i].x, q[2 * i + 1].x, q[2 * i].z, q[2 * i + 1].z);
          }
          __syncwarp();
          if (lane == 0) mbar_arrive(bar + B_HALO);
          if (b == 0) TR(52);
        }
      }
      if (b) { all_there(m * 128 + U_HH + 32 + (lane & 15), bar + B_HH + 8); all_there(m * 128 + U_HH + 48 + (lane & 7), bar + B_HH2); }
    }
  } else {
    const int wg = warp >> 2, wq = warp & 3, tid = threadIdx.x;
    const int g = lane >> 2, c = lane & 3;
    const int sec0 = (m >> 1) & 1, hf0 = m & 1, ks0 = (m >> 2) & 3;
    uint4 wv[8];
    uint32_t ep0; uint16_t cv_;
    asm volatile("ld.global.nc.u16 %0, [%1];" : "=h"(cv_) : "l"(cvec + ks0 * 256 + warp * 32 + lane));
    asm volatile("ld.global.u32 %0, [%1];" : "=r"(ep0) : "l"(gs->epoch + bid + 4));
    if (!extra) {
      const bf16* wp = wmod + (size_t)(ks0 * 256 + warp * 32 + (lane >> 3)) * 6144 + sec0 * 1024 + j * 128 + hf0 * 64 + (lane & 7) * 8;
#pragma unroll
      for (int i = 0; i < 8; i++) wv[i] = ldg_nc(wp + (size_t)i * 4 * 6144);
    }
    asm volatile("setmaxnreg.inc.sync.aligned.u32 232;" ::: "memory");
    if (__builtin_expect(extra, 0)) {
      const uint32_t ep = ep0 + 1;
      float sv[4];
#pragma unroll
      for (int p = 0; p < 4; p++) sv[p] = silu_c(__bfloat162float(cvec[64 * (4 * p + (lane >> 3)) + 8 * warp + (lane & 7)]));
      named_bar(2, 288);
      int s = 0, par = 0;
#pragma unroll 1
      for (int sec = 0; sec < 4; sec++) {
        float a[8] = {0, 0, 0, 0, 0, 0, 0, 0};
#pragma unroll 1
        for (int it = 0; it < 16; it++) {
          const float sc = it < 4 ? sv[0] : it < 8 ? sv[1] : it < 12 ? sv[2] : sv[3];
          mbar_wait(bar + B_FULL6 + s * 8, par);
          uint4 w[8];
#pragma unroll
          for (int i = 0; i < 8; i++) w[i] = lds128(sb + s * 32768 + (warp * 8 + i) * 512 + lane * 16);
#pragma unroll
          for (int i = 0; i < 8; i++) gemv_fma(a, w[i], __shfl_sync(~0u, sc, (it & 3) * 8 + i));
          if (lane == 0) mbar_arrive(bar + B_EMPTY6 + s * 8);
          if (++s == 6) { s = 0; par ^= 1; }
        }
        const uint32_t red = sb + STG + sec * 8192;
        sts128(red + warp * 1024 + lane * 32, __float_as_uint(a[0]), __float_as_uint(a[1]), __float_as_uint(a[2]), __float_as_uint(a[3]));
        sts128(red + warp * 1024 + lane * 32 + 16, __float_as_uint(a[4]), __float_as_uint(a[5]), __float_as_uint(a[6]), __float_as_uint(a[7]));
        named_bar(1, 256);
        float t = 0;
#pragma unroll
        for (int q = 0; q < 8; q++) t += lds32f(red + q * 1024 + tid * 4);
        st_rlx2(gs->modv + sec * 1024 + (bid + 4) * 256 + tid, __float_as_uint(t), ep);
      }
      if (tid == 0) gs->epoch[bid + 4] = ep;
      return;
    }
    if (warp == 0) TR(0);
    const int row0 = wg * 64 + wq * 16 + g;
    if (c < 2) st_rlx4(gs->stat + m * 1024 + j * 128 + row0 + c * 8, 0, 0, 0, 0);
    if (tid < 64) st_rlx2(gs->modp + ((j * 2 + sec0) * 4 + ks0) * 128 + hf0 * 64 + tid, 0, 0);
    cl_arrive_relaxed(); cl_wait();
    uint32_t ep;
    asm volatile("add.u32 %0, %1, 1;" : "=r"(ep) : "r"(ep0) : "memory");
    const float sc_ = silu_c(__uint_as_float((uint32_t)cv_ << 16));
    const uint32_t rel = mapa(bar, (lane & 1) ^ rank);
    const uint32_t stg_row = sb + STG + (wg * 64 + wq * 16 + (lane & 15)) * 128;
    const uint32_t fre = bar + B_FREE;
    Ring r4{0, 0, 0}, r6{0, 0, 0};
    auto none = [](auto) {};
    uint32_t xk[32];
    {
      float a[8] = {0, 0, 0, 0, 0, 0, 0, 0};
#pragma unroll
      for (int i = 0; i < 8; i++) gemv_fma(a, wv[i], __shfl_sync(~0u, sc_, i * 4 + (lane >> 3)));
#pragma unroll
      for (int i = 0; i < 8; i++) { a[i] += __shfl_xor_sync(~0u, a[i], 8); a[i] += __shfl_xor_sync(~0u, a[i], 16); }
      if (lane < 8) {
        sts128(sb + RED_OFF + warp * 256 + lane * 32, __float_as_uint(a[0]), __float_as_uint(a[1]), __float_as_uint(a[2]), __float_as_uint(a[3]));
        sts128(sb + RED_OFF + warp * 256 + lane * 32 + 16, __float_as_uint(a[4]), __float_as_uint(a[5]), __float_as_uint(a[6]), __float_as_uint(a[7]));
      }
      named_bar(1, 256);
      if (tid < 64) {
        float s = 0;
#pragma unroll
        for (int w = 0; w < 8; w++) s += lds32f(sb + RED_OFF + w * 256 + tid * 4);
        st_rlx2(gs->modp + ((j * 2 + sec0) * 4 + ks0) * 128 + hf0 * 64 + tid, __float_as_uint(s), ep);
      }
      if (warp == 0) TR(1);
      float v[64];
      mbar_wait(bar + B_X, 0); mbar_wait(bar + B_X + 8, 0);
#pragma unroll
      for (int i = 0; i < 16; i += 2) {
        uint32_t w0, w1, w2, w3;
        ldsm4(stg_row + (i >> 3) * BLK + ((((i & 7) + (lane >> 4)) ^ (lane & 7)) << 4), w0, w1, w2, w3);
        xk[2 * i] = w0; xk[2 * i + 1] = w1; xk[2 * i + 2] = w2; xk[2 * i + 3] = w3;
        v[4 * i] = bf_lo(w0); v[4 * i + 1] = bf_hi(w0); v[4 * i + 2] = bf_lo(w1); v[4 * i + 3] = bf_hi(w1);
        v[4 * i + 4] = bf_lo(w2); v[4 * i + 5] = bf_hi(w2); v[4 * i + 6] = bf_lo(w3); v[4 * i + 7] = bf_hi(w3);
      }
      ln_publish(v, gs->stat + m * 1024, j, row0, lane, ep);
      if (warp == 0) TR(2);
      { uint32_t* step0 = STEP0 + 168; TRW(0); }
      mod_store(sb, tid >> 7, tid & 127, mod_gather(gs->modp + (j * 2 + (tid >> 7)) * 512 + (tid & 127), ep));
      named_bar(1, 256);
      if (warp == 0) TR(3);
      ln_apply(v, gs->stat + m * 1024, row0, ep, sb, 0, 1, stg_row, wg, lane, STEP0 + 168);
      named_bar(1, 256);
    }
    if (warp == 0) TR(4);
    { uint32_t* step0 = STEP0 + 168; TRW(5); }
    {
      uint32_t kf[32], vf[32], pv[32];
      const bool first = wq == 0 && m == 0;
      const uint32_t xa = sb + STG + wg * HALF + wq * 2048 + lane * 16;
      {
        float acc[128];
        mainloop<256, 4, 0, 0>(acc, 16, true, r4, sb, wg, lane, rel, STEP0 + 0, none, none, [&] {
          mbar_wait(fre + 8, 0);
          if (c < 2) st_rlx4(gs->stat + (16 + m) * 1024 + j * 128 + row0 + c * 8, 0, 0, 0, 0);
        });
        if (warp == 0) TR(5);
#pragma unroll
        for (int i = 0; i < 32; i++) { kf[i] = pack2(acc[2 * i], acc[2 * i + 1]); vf[i] = pack2(acc[64 + 2 * i], acc[65 + 2 * i]); }
      }
      if (warp == 0) TR(6);
      float acc[64];
      constexpr int QP = QPV;
      mainloop<128, 6, 8 / QP, 0>(acc, 16, false, r6, sb, wg, lane, rel, STEP0 + 16, [&](auto ic) {
        constexpr int q = (ic.v - 1) * QP;
#pragma unroll
        for (int i = 4 * q; i < 4 * (q + QP); i++) vf[i] = movm(vf[i]);
        if (wq == 3) {
          if (m < 15) {
            uint4* hp = gs->halo + (((m + 1) * 8 + j) * 2 + wg) * 512 + lane;
#pragma unroll
            for (int i = 2 * q; i < 2 * (q + QP); i++) st_rlx4(hp + i * 32, kf[2 * i + 1], ep, vf[2 * i + 1], ep);
          }
        } else {
#pragma unroll
          for (int i = q; i < q + QP; i++) sts128(xa + 2048 + (i >> 2) * BLK + (i & 3) * 512, kf[4 * i + 1], kf[4 * i + 3], vf[4 * i + 1], vf[4 * i + 3]);
        }
      }, none, [&] {
        named_bar(2 + wg, 128);
        if (wq == 0) mbar_wait(bar + B_HALO, 0);
#pragma unroll
        for (int i = 0; i < 8; i++) {
          uint4 q = lds128(xa + (i >> 2) * BLK + (i & 3) * 512);
          pv[4 * i] = q.x; pv[4 * i + 1] = q.y; pv[4 * i + 2] = q.z; pv[4 * i + 3] = q.w;
        }
        __syncwarp();
      });
      if (warp == 0) TR(7);
      { uint32_t* step0 = STEP0 + 184; TRW(0); }
      int gz = g;
#pragma unroll
      for (int b = 0; b < 2; b++) {
        const bool up0 = 2 * c > gz, up1 = 2 * c + 1 > gz;
        const uint32_t mup = (up0 ? 0xffffu : 0u) | (up1 ? 0xffff0000u : 0u);
        float l[2][4], mx[4];
#pragma unroll
        for (int h = 0; h < 2; h++) {
          uint32_t q[8];
          const int k = 16 * b + 8 * h;
#pragma unroll
          for (int i = 0; i < 8; i++) q[i] = pack2(acc[2 * k + 2 * i], acc[2 * k + 2 * i + 1]);
          float s0[4], s1[4], s2[4];
          mma16z(s0, q[0], q[1], q[2], q[3], pv[k], pv[k + 1]); mma16z(s1, q[0], q[1], q[2], q[3], kf[k], kf[k + 2]); mma16z(s2, q[0], q[1], q[2], q[3], kf[k + 1], kf[k + 3]);
          mma16(s0, q[4], q[5], q[6], q[7], pv[k + 4], pv[k + 5]); mma16(s1, q[4], q[5], q[6], q[7], kf[k + 4], kf[k + 6]); mma16(s2, q[4], q[5], q[6], q[7], kf[k + 5], kf[k + 7]);
          if (first) { s0[0] = -INFINITY; s0[1] = -INFINITY; }
          l[h][0] = up0 ? s0[0] : s1[0]; l[h][1] = up1 ? s0[1] : s1[1]; l[h][2] = up0 ? s1[2] : s2[2]; l[h][3] = up1 ? s1[3] : s2[3];
          mx[2 * h] = fmaxf(l[h][0], l[h][1]); mx[2 * h + 1] = fmaxf(l[h][2], l[h][3]);
        }
#pragma unroll
        for (int o = 1; o < 4; o <<= 1) {
#pragma unroll
          for (int h = 0; h < 4; h++) mx[h] = fmaxf(mx[h], __shfl_xor_sync(~0u, mx[h], o));
        }
#pragma unroll
        for (int h = 0; h < 2; h++) {
          const float n0 = -mx[2 * h] * SCL, n1 = -mx[2 * h + 1] * SCL;
          const uint32_t pa = pack2(ex2(fmaf(l[h][0], SCL, n0)), ex2(fmaf(l[h][1], SCL, n0))), pb = pack2(ex2(fmaf(l[h][2], SCL, n1)), ex2(fmaf(l[h][3], SCL, n1)));
          float sm[4];
          mma8z(sm, pa, pb, 0x3f803f80u);
          const float ia = rcp(sm[0]), ib = rcp(sm[2]);
#pragma unroll
          for (int i = 8 * b + 4 * h; i < 8 * b + 4 * h + 4; i += 2) {
            uint32_t of[4];
#pragma unroll
            for (int d = 0; d < 2; d++) {
              float o[4];
              mma16z(o, pa & ~mup, pb & mup, 0u, pb & ~mup, vf[2 * (i + d)], vf[2 * (i + d) + 1]);
              mma8(o, pa & mup, 0u, pv[2 * i + 2 + d]);
              of[2 * d] = pack2(o[0] * ia, o[1] * ia); of[2 * d + 1] = pack2(o[2] * ib, o[3] * ib);
            }
            stsm4(stg_row + b * BLK + ((((i & 7) + (lane >> 4)) ^ (lane & 7)) << 4), of[0], of[1], of[2], of[3]);
          }
        }
        stage_done(sb, wg, b, lane);
        { uint32_t* step0 = STEP0 + 184; TRW(1 + b); }
        if (b == 0) gz += __float_as_uint(lds32f(bar + ZERO));
      }
      named_bar(1, 256);
      if (warp == 0) TR(8);
      { uint32_t* step0 = STEP0 + 184; TRW(3); }
    }
    uint32_t pk[64];
    {
      float acc[64];
      mainloop<128, 6, 0, WOLAG>(acc, 16, true, r6, sb, wg, lane, rel, STEP0 + 32, none, none, [&] {
        if (WOLAG && wg == 0 && lane == 0) mbar_arrive(bar + B_LAG);
        mbar_wait(bar + B_MOD, 0); mbar_wait(fre + 8, 1);
        load_vec(pk + 32, sb, 2, 0, lane); load_vec(pk + 40, sb, 2, 1, lane);
#pragma unroll
        for (int i = 0; i < 32; i++) { pk[i] = xk[i]; asm volatile("" : "+r"(pk[i])); }
      });
      if (warp == 0) TR(9);
      { uint32_t* step0 = STEP0 + 176; TRW(0); }
#pragma unroll
      for (int i = 0; i < 32; i++) {
        acc[2 * i] = fmaf(acc[2 * i], bf_lo(pk[32 + (i >> 1)]), bf_lo(pk[i]));
        acc[2 * i + 1] = fmaf(acc[2 * i + 1], bf_hi(pk[32 + (i >> 1)]), bf_hi(pk[i]));
      }
      ln_publish(acc, gs->stat + (16 + m) * 1024, j, row0, lane, ep);
      if (warp == 0) TR(36);
      mbar_wait(bar + B_FULL6 + 16, 1);
      if (lane < 2) mbar_arrive_cl(rel + B_EMPTY6 + 16);
      ring_next<6>(r6);
#pragma unroll
      for (int i = 0; i < 32; i++) { pk[i] = pack2(acc[2 * i], acc[2 * i + 1]); pk[32 + i] = 0; }
      ln_apply(acc, gs->stat + (16 + m) * 1024, row0, ep, sb, 3, 4, stg_row, wg, lane, STEP0 + 176);
      named_bar(1, 256);
      if (warp == 0) TR(11);
      { uint32_t* step0 = STEP0 + 176; TRW(5); }
    }
    auto swiglu = [&](int q, int uo, int par) {
      if ((q & 3) == 0 && par >= 0) mbar_wait(fre + 2 * q, par);
      uint32_t w[4];
#pragma unroll
      for (int u = 0; u < 4; u++) w[u] = silu_mul2(pk[4 * q + u], pk[uo + 4 * q + u]);
      stsm4(stg_row + (q >> 2) * BLK + ((((2 * q & 7) + (lane >> 4)) ^ (lane & 7)) << 4), w[0], w[1], w[2], w[3]);
    };
    r4.s = r4.wrap = 2;
#pragma unroll 1
    for (int t = 0; t < 3; t++) {
      float acc[128];
      mainloop<256, 4, 5, 0>(acc, 16, t == 0, r4, sb, wg, lane, rel, STEP0 + 48 + 16 * t, [&](auto ic) {
        if (t) {
          if (ic.v == 3 || ic.v == 5) stage_done(sb, wg, ic.v >> 2, lane);
          if (ic.v < 5) { swiglu(2 * ic.v - 2, 32, ~t & 1); swiglu(2 * ic.v - 1, 32, 0); }
        }
      }, [&](int it) {
#pragma unroll
        for (int i = 0; i < 8; i++)
          if (t == 0 && it == 8 + i) gs->x1[bid * 2048 + (i >> 2) * 1024 + warp * 128 + (i & 3) * 32 + lane] = make_uint4(pk[4 * i], pk[4 * i + 1], pk[4 * i + 2], pk[4 * i + 3]);
      }, [&] { if (t == 0) fence_async_global(); else if (t == 2) mbar_wait(bar + B_X, 1); });
      if (warp == 0) TR(12 + 2 * t);
#pragma unroll
      for (int i = 0; i < 64; i++) pk[i] = pack2(acc[2 * i], acc[2 * i + 1]);
      if (warp == 0) TR(13 + 2 * t);
    }
    uint32_t x1[32];
    {
      float acc[64];
      mainloop<128, 6, 12, 0>(acc, 16, false, r6, sb, wg, lane, rel, STEP0 + 96, [&](auto ic) {
        constexpr int b = ic.v > 6, q = ic.v - 6 * b;
        if (q == 1) {
#pragma unroll
          for (int i = 4 * b; i < 4 * b + 4; i++) { const uint4 x = lds128(sb + STG + b * BLK + warp * 2048 + (i & 3) * 512 + lane * 16); x1[4 * i] = x.x; x1[4 * i + 1] = x.y; x1[4 * i + 2] = x.z; x1[4 * i + 3] = x.w; }
          __syncwarp();
        } else if (q < 6) swiglu(4 * b + q - 2, 32, -1);
        else stage_done(sb, wg, b, lane);
      }, none, [] {});
      if (warp == 0) TR(18);
#pragma unroll
      for (int i = 0; i < 32; i++) pk[i] = pack2(acc[2 * i], acc[2 * i + 1]);
      if (warp == 0) TR(19);
    }
    {
      float acc[64];
      mainloop<128, 6, 5, TAILLAG>(acc, 56, false, r6, sb, wg, lane, rel, STEP0 + 112, [&](auto ic) {
        if (ic.v == 5) stage_done(sb, wg, 0, lane); else swiglu(ic.v - 1, 16, 1);
      }, none, [&] {
        if (TAILLAG && wg == 0 && lane == 0) mbar_arrive(bar + B_LAG);
        load_vec(pk + 32, sb, 5, 0, lane); load_vec(pk + 40, sb, 5, 1, lane);
        mbar_wait(fre, 0); mbar_wait(fre + 8, 1);
      });
      __syncwarp();
      cl_arrive_relaxed();
      if (warp == 0) TR(20);
#pragma unroll
      for (int i = 0; i < 16; i += 2) {
        uint32_t w[4];
#pragma unroll
        for (int u = 0; u < 4; u++) {
          const int q = 2 * i + u;
          w[u] = pack2(fmaf(acc[2 * q], bf_lo(pk[32 + (q >> 1)]), bf_lo(x1[q])), fmaf(acc[2 * q + 1], bf_hi(pk[32 + (q >> 1)]), bf_hi(x1[q])));
        }
        stsm4(stg_row + (i >> 3) * BLK + ((((i & 7) + (lane >> 4)) ^ (lane & 7)) << 4), w[0], w[1], w[2], w[3]);
        if ((i & 7) == 6) {
          fence_async_smem();
          named_bar(2 + wg, 128);
          if (wq == 0 && elect()) { tma_store_3d(&maps.out, sb + STG + (i >> 3) * BLK + wg * HALF, j * 128 + (i >> 3) * 64, m * 64, wg); bulk_commit(); }
          if (i < 8) x1[16] |= __float_as_uint(lds32f(bar + ZERO));
        }
      }
      if (wq == 0) bulk_wait_read();
      if (wq == 0) TR(40 + wg);
      if (tid == 0) gs->epoch[bid + 4] = ep;
      if (warp == 0) TR(21);
      cl_wait();
    }
  }
}

typedef CUresult (*EncodeFn)(CUtensorMap*, CUtensorMapDataType, cuuint32_t, void*, const cuuint64_t*, const cuuint64_t*, const cuuint32_t*, const cuuint32_t*,
                             CUtensorMapInterleave, CUtensorMapSwizzle, CUtensorMapL2promotion, CUtensorMapFloatOOBfill);

void make_map(EncodeFn fn, CUtensorMap* mp, const void* base, uint64_t d0, uint64_t d1, uint64_t d2, uint64_t s1, uint64_t s2, uint32_t b2, uint32_t b0 = 64) {
  cuuint64_t d[3] = {d0, d1, d2}, s[2] = {s1, s2};
  cuuint32_t b[3] = {b0, 64, b2}, e[3] = {1, 1, 1};
  fn(mp, CU_TENSOR_MAP_DATA_TYPE_BFLOAT16, 3, (void*)base, d, s, b, e, CU_TENSOR_MAP_INTERLEAVE_NONE, b0 == 64 ? CU_TENSOR_MAP_SWIZZLE_128B : CU_TENSOR_MAP_SWIZZLE_NONE,
     CU_TENSOR_MAP_L2_PROMOTION_L2_128B, CU_TENSOR_MAP_FLOAT_OOB_FILL_NONE);
}

__global__ void probe_kernel() {}
int max_clusters(int size) {
  cudaLaunchConfig_t cfg = {};
  cudaLaunchAttribute at;
  at.id = cudaLaunchAttributeClusterDimension; at.val.clusterDim.x = size; at.val.clusterDim.y = 1; at.val.clusterDim.z = 1;
  cfg.gridDim = dim3(size * 66); cfg.blockDim = dim3(384); cfg.dynamicSmemBytes = SMEM_BYTES; cfg.attrs = &at; cfg.numAttrs = 1;
  int n = 0;
  if (cudaOccupancyMaxActiveClusters(&n, probe_kernel, &cfg) != cudaSuccess) { cudaGetLastError(); return 0; }
  return n;
}

}

extern "C" void kernel_launch(void* const* d_in, const int* in_sizes, int n_in, void* d_out, int out_size) {
  static EncodeFn fn = nullptr;
  static int by_sm = 0;
  static Scratch* gs = nullptr;
  if (!fn) {
    void* p = nullptr; cudaDriverEntryPointQueryResult q;
    cudaGetDriverEntryPoint("cuTensorMapEncodeTiled", &p, cudaEnableDefault, &q);
    fn = (EncodeFn)p;
    cudaFuncSetAttribute(fused_kernel, cudaFuncAttributeMaxDynamicSharedMemorySize, SMEM_BYTES);
    int dev = 0, sms = 0;
    cudaGetSymbolAddress((void**)&gs, g_scratch);
    cudaGetDevice(&dev);
    cudaDeviceGetAttribute(&sms, cudaDevAttrMultiProcessorCount, dev);
    cudaFuncSetAttribute(probe_kernel, cudaFuncAttributeMaxDynamicSharedMemorySize, SMEM_BYTES);
    by_sm = BYSM && sms == 132 && max_clusters(2) == 66 && max_clusters(4) == 30 && max_clusters(6) == 17 && max_clusters(8) == 15;
  }
  Maps mp;
  make_map(fn, &mp.x, d_in[0], D_, S_ / 2, 2, 4096, 2048, 2);
  make_map(fn, &mp.out, d_out, D_, S_ / 2, 2, 4096, 2048, 1);
  make_map(fn, &mp.wqkv, d_in[1], 64, D_, 3 * D_ / 64, 3 * D_ * 2, 128, 2);
  make_map(fn, &mp.wo, d_in[2], 64, D_, D_ / 64, D_ * 2, 128, 2);
  make_map(fn, &mp.w1, d_in[4], 64, D_, F_ / 64, F_ * 2, 128, 2);
  make_map(fn, &mp.w3, d_in[5], 64, D_, F_ / 64, F_ * 2, 128, 2);
  make_map(fn, &mp.w1s, d_in[4], 64, D_, F_ / 64, F_ * 2, 128, 1);
  make_map(fn, &mp.w3s, d_in[5], 64, D_, F_ / 64, F_ * 2, 128, 1);
  make_map(fn, &mp.w2, d_in[6], 64, F_, D_ / 64, D_ * 2, 128, 2);
  make_map(fn, &mp.wmod, d_in[8], 256, D_, 24, 6 * D_ * 2, 512, 1, 256);
  fused_kernel<<<132, 384, SMEM_BYTES>>>((const bf16*)d_in[7], (const bf16*)d_in[8], gs, by_sm, mp);
}
```

```cpp
#include <cuda_runtime.h>
#include <cuda_bf16.h>
#include <cuda.h>
#include <stdint.h>

typedef __nv_bfloat16 bf16;

namespace {

constexpr int S_ = 2048, D_ = 1024, F_ = 3584;
constexpr int BLK = 16384;
constexpr int HALF = 8192;
constexpr int RING = 196608;
constexpr int STG = RING;
constexpr int MISC = RING + 2 * BLK;
constexpr int SMEM_BYTES = MISC + 3072;
constexpr int B_FULL4 = 0, B_EMPTY4 = 32, B_FULL6 = 64, B_EMPTY6 = 112, B_RDY = 160, B_FREE = 176, B_LAG = 192, B_X = 208, B_MOD = 224, B_HALO = 232, B_HH = 256, B_ALL = 272, B_HH2 = 288, ZERO = 296;
constexpr int MODV = 512;
constexpr int RED_OFF = 0;
constexpr float SCL = 0.17677669529663687f * 1.4426950408889634f;
constexpr int U_HH = 64;
constexpr int FS = 8;
constexpr int NPIECE = 4, PSLEEP = 300;
constexpr int XSLEEP = 4000, HSLEEP = 400;
constexpr uint32_t XDELAY = 2000;
constexpr uint32_t B1P = 3500, B1D = 900, B1P2 = 3200;
constexpr int WOLAG = 2, TAILLAG = 5;

struct Maps { CUtensorMap x, out, wqkv, wo, w1, w3, w1s, w3s, w2, wmod; };

struct Scratch {
  uint4 h[16 * 16 * 1024];
  uint4 o[16 * 16 * 1024];
  uint4 hh[16 * 56 * 1024];
  uint4 x1[128 * 8 * 256];
  uint4 stat[2 * 16 * 8 * 128];
  uint4 halo[16 * 8 * 2 * 512];
  uint2 modp[8 * 2 * 4 * 128];
  uint2 modv[4 * 1024];
  uint32_t flag[16 * 128 * FS];
  uint32_t epoch[132];
};
__device__ __align__(1024) Scratch g_scratch;

__device__ __forceinline__ void bail() { asm volatile("st.global.u32 [%0], %1;" :: "l"(0ull), "r"(0) : "memory"); }
__device__ __forceinline__ uint32_t smem_u32(const void* p) { return (uint32_t)__cvta_generic_to_shared(p); }
__device__ __forceinline__ void mbar_init(uint32_t bar, uint32_t cnt) { asm volatile("mbarrier.init.shared::cta.b64 [%0], %1;" :: "r"(bar), "r"(cnt) : "memory"); }
__device__ __forceinline__ void mbar_expect_tx(uint32_t bar, uint32_t bytes) { asm volatile("mbarrier.arrive.expect_tx.shared::cta.b64 _, [%0], %1;" :: "r"(bar), "r"(bytes) : "memory"); }
__device__ __forceinline__ void mbar_arrive(uint32_t bar) { asm volatile("mbarrier.arrive.shared::cta.b64 _, [%0];" :: "r"(bar) : "memory"); }
__device__ __forceinline__ void mbar_arrive_cl(uint32_t cl_addr) { asm volatile("mbarrier.arrive.shared::cluster.b64 _, [%0];" :: "r"(cl_addr) : "memory"); }
__device__ __forceinline__ uint32_t mapa(uint32_t addr, uint32_t cta) { uint32_t r; asm("mapa.shared::cluster.u32 %0, %1, %2;" : "=r"(r) : "r"(addr), "r"(cta)); return r; }
__device__ __forceinline__ void mbar_wait(uint32_t bar, uint32_t parity) {
  asm volatile("{\n.reg .pred p;\n.reg .b32 n;\n.reg .b64 z;\nmov.b32 n, 0;\nmov.b64 z, 0;\n"
               "W: add.u32 n, n, 1;\nsetp.gt.u32 p, n, 0x400000;\n@p st.global.u32 [z], n;\n"
               "mbarrier.try_wait.parity.shared::cta.b64 p, [%0], %1;\n@!p bra W;\n}" :: "r"(bar), "r"(parity) : "memory");
}
__device__ __forceinline__ void tma_3d(uint32_t dst, const CUtensorMap* m, uint32_t bar, int c0, int c1, int c2) {
  asm volatile("cp.async.bulk.tensor.3d.shared::cluster.global.mbarrier::complete_tx::bytes [%0], [%1, {%3, %4, %5}], [%2];" :: "r"(dst), "l"(m), "r"(bar), "r"(c0), "r"(c1), "r"(c2) : "memory");
}
__device__ __forceinline__ void tma_store_3d(const CUtensorMap* m, uint32_t src, int c0, int c1, int c2) {
  asm volatile("cp.async.bulk.tensor.3d.global.shared::cta.bulk_group [%0, {%2, %3, %4}], [%1];" :: "l"(m), "r"(src), "r"(c0), "r"(c1), "r"(c2) : "memory");
}
__device__ __forceinline__ void bulk_ld(uint32_t dst, const void* src, uint32_t bytes, uint32_t bar) {
  asm volatile("cp.async.bulk.shared::cluster.global.mbarrier::complete_tx::bytes [%0], [%1], %2, [%3];" :: "r"(dst), "l"(src), "r"(bytes), "r"(bar) : "memory");
}
__device__ __forceinline__ void bulk_ld_mc(uint32_t dst, const void* src, uint32_t bytes, uint32_t bar) {
  asm volatile("cp.async.bulk.shared::cluster.global.mbarrier::complete_tx::bytes.multicast::cluster [%0], [%1], %2, [%3], %4;" :: "r"(dst), "l"(src), "r"(bytes), "r"(bar), "h"((uint16_t)3) : "memory");
}
__device__ __forceinline__ void bulk_push(uint32_t dst_cl, uint32_t src, uint32_t bytes, uint32_t bar_cl) {
  asm volatile("cp.async.bulk.shared::cluster.shared::cta.mbarrier::complete_tx::bytes [%0], [%1], %2, [%3];" :: "r"(dst_cl), "r"(src), "r"(bytes), "r"(bar_cl) : "memory");
}
__device__ __forceinline__ void bulk_st(void* dst, uint32_t src, uint32_t bytes) {
  asm volatile("cp.async.bulk.global.shared::cta.bulk_group [%0], [%1], %2;" :: "l"(dst), "r"(src), "r"(bytes) : "memory");
}
__device__ __forceinline__ void bulk_commit() { asm volatile("cp.async.bulk.commit_group;" ::: "memory"); }
__device__ __forceinline__ void bulk_wait_read() { asm volatile("cp.async.bulk.wait_group.read 0;" ::: "memory"); }
__device__ __forceinline__ void bulk_wait_all() { asm volatile("cp.async.bulk.wait_group 0;" ::: "memory"); }
__device__ __forceinline__ void fence_async_global() { asm volatile("fence.proxy.async.global;" ::: "memory"); }
__device__ __forceinline__ void fence_async_smem() { asm volatile("fence.proxy.async.shared::cta;" ::: "memory"); }
__device__ __forceinline__ void wg_arrive() { asm volatile("wgmma.fence.sync.aligned;" ::: "memory"); }
__device__ __forceinline__ void wg_commit() { asm volatile("wgmma.commit_group.sync.aligned;" ::: "memory"); }
template <int N> __device__ __forceinline__ void wg_wait() { asm volatile("wgmma.wait_group.sync.aligned %0;" :: "n"(N) : "memory"); }
__device__ __forceinline__ void cl_arrive_relaxed() { asm volatile("barrier.cluster.arrive.relaxed.aligned;" ::: "memory"); }
__device__ __forceinline__ void cl_wait() { asm volatile("barrier.cluster.wait.acquire.aligned;" ::: "memory"); }
__device__ __forceinline__ bool elect() { uint32_t p; asm volatile("{\n.reg .pred p;\nelect.sync _|p, 0xffffffff;\nselp.u32 %0, 1, 0, p;\n}" : "=r"(p)); return p; }
__device__ __forceinline__ void named_bar(int id, int n) { asm volatile("bar.sync %0, %1;" :: "r"(id), "r"(n) : "memory"); }
__device__ __forceinline__ uint32_t pack2(float lo, float hi) { uint32_t r; asm("cvt.rn.bf16x2.f32 %0, %1, %2;" : "=r"(r) : "f"(hi), "f"(lo)); return r; }
__device__ __forceinline__ float bf_lo(uint32_t w) { return __uint_as_float(w << 16); }
__device__ __forceinline__ float bf_hi(uint32_t w) { return __uint_as_float(w & 0xffff0000u); }
__device__ __forceinline__ float bf_round(float v) { return __bfloat162float(__float2bfloat16_rn(v)); }
__device__ __forceinline__ void stsm4(uint32_t addr, uint32_t a, uint32_t b, uint32_t c, uint32_t d) {
  asm volatile("stmatrix.sync.aligned.m8n8.x4.shared.b16 [%0], {%1, %2, %3, %4};" :: "r"(addr), "r"(a), "r"(b), "r"(c), "r"(d) : "memory");
}
__device__ __forceinline__ void ldsm4(uint32_t addr, uint32_t& a, uint32_t& b, uint32_t& c, uint32_t& d) {
  asm volatile("ldmatrix.sync.aligned.m8n8.x4.shared.b16 {%0, %1, %2, %3}, [%4];" : "=r"(a), "=r"(b), "=r"(c), "=r"(d) : "r"(addr) : "memory");
}
__device__ __forceinline__ uint32_t movm(uint32_t a) { uint32_t r; asm volatile("movmatrix.sync.aligned.m8n8.trans.b16 %0, %1;" : "=r"(r) : "r"(a)); return r; }
__device__ __forceinline__ void mma16(float (&d)[4], uint32_t a0, uint32_t a1, uint32_t a2, uint32_t a3, uint32_t b0, uint32_t b1) {
  asm("mma.sync.aligned.m16n8k16.row.col.f32.bf16.bf16.f32 {%0,%1,%2,%3}, {%4,%5,%6,%7}, {%8,%9}, {%0,%1,%2,%3};"
               : "+f"(d[0]), "+f"(d[1]), "+f"(d[2]), "+f"(d[3]) : "r"(a0), "r"(a1), "r"(a2), "r"(a3), "r"(b0), "r"(b1));
}
__device__ __forceinline__ void mma16z(float (&d)[4], uint32_t a0, uint32_t a1, uint32_t a2, uint32_t a3, uint32_t b0, uint32_t b1) {
  asm("mma.sync.aligned.m16n8k16.row.col.f32.bf16.bf16.f32 {%0,%1,%2,%3}, {%4,%5,%6,%7}, {%8,%9}, {%10,%10,%10,%10};"
      : "=f"(d[0]), "=f"(d[1]), "=f"(d[2]), "=f"(d[3]) : "r"(a0), "r"(a1), "r"(a2), "r"(a3), "r"(b0), "r"(b1), "f"(0.f));
}
__device__ __forceinline__ void mma8z(float (&d)[4], uint32_t a0, uint32_t a1, uint32_t b0) {
  asm("mma.sync.aligned.m16n8k8.row.col.f32.bf16.bf16.f32 {%0,%1,%2,%3}, {%4,%5}, {%6}, {%7,%7,%7,%7};"
      : "=f"(d[0]), "=f"(d[1]), "=f"(d[2]), "=f"(d[3]) : "r"(a0), "r"(a1), "r"(b0), "f"(0.f));
}
__device__ __forceinline__ void mma8(float (&d)[4], uint32_t a0, uint32_t a1, uint32_t b0) {
  asm("mma.sync.aligned.m16n8k8.row.col.f32.bf16.bf16.f32 {%0,%1,%2,%3}, {%4,%5}, {%6}, {%0,%1,%2,%3};"
               : "+f"(d[0]), "+f"(d[1]), "+f"(d[2]), "+f"(d[3]) : "r"(a0), "r"(a1), "r"(b0));
}
__device__ __forceinline__ uint4 lds128(uint32_t a) { uint4 v; asm volatile("ld.shared.v4.u32 {%0,%1,%2,%3}, [%4];" : "=r"(v.x), "=r"(v.y), "=r"(v.z), "=r"(v.w) : "r"(a) : "memory"); return v; }
__device__ __forceinline__ void sts128(uint32_t a, uint32_t x, uint32_t y, uint32_t z, uint32_t w) { asm volatile("st.shared.v4.u32 [%0], {%1,%2,%3,%4};" :: "r"(a), "r"(x), "r"(y), "r"(z), "r"(w) : "memory"); }
__device__ __forceinline__ float lds32f(uint32_t a) { float v; asm volatile("ld.shared.f32 %0, [%1];" : "=f"(v) : "r"(a) : "memory"); return v; }
__device__ __forceinline__ void sts16(uint32_t a, bf16 v) { asm volatile("st.shared.b16 [%0], %1;" :: "r"(a), "h"(__bfloat16_as_ushort(v)) : "memory"); }
__device__ __forceinline__ uint4 ldg_nc(const void* p) { uint4 v; asm volatile("ld.global.nc.L1::no_allocate.v4.u32 {%0,%1,%2,%3}, [%4];" : "=r"(v.x), "=r"(v.y), "=r"(v.z), "=r"(v.w) : "l"(p)); return v; }
__device__ __forceinline__ uint4 ld_rlx4(const uint4* p) {
  unsigned long long a, b; asm volatile("ld.relaxed.gpu.global.v2.b64 {%0,%1}, [%2];" : "=l"(a), "=l"(b) : "l"(p) : "memory");
  return make_uint4((uint32_t)a, (uint32_t)(a >> 32), (uint32_t)b, (uint32_t)(b >> 32));
}
__device__ __forceinline__ uint2 ld_rlx2(const uint2* p) { unsigned long long a; asm volatile("ld.relaxed.gpu.global.b64 %0, [%1];" : "=l"(a) : "l"(p) : "memory"); return make_uint2((uint32_t)a, (uint32_t)(a >> 32)); }
__device__ __forceinline__ void st_rlx4(uint4* p, uint32_t x, uint32_t y, uint32_t z, uint32_t w) {
  asm volatile("st.relaxed.gpu.global.v2.b64 [%0], {%1,%2};" :: "l"(p), "l"((unsigned long long)x | ((unsigned long long)y << 32)), "l"((unsigned long long)z | ((unsigned long long)w << 32)) : "memory");
}
__device__ __forceinline__ void st_rlx2(uint2* p, uint32_t x, uint32_t y) { asm volatile("st.relaxed.gpu.global.b64 [%0], %1;" :: "l"(p), "l"((unsigned long long)x | ((unsigned long long)y << 32)) : "memory"); }
__device__ __forceinline__ void st_release(uint32_t* p, uint32_t v) { asm volatile("st.release.gpu.global.u32 [%0], %1;" :: "l"(p), "r"(v) : "memory"); }
__device__ __forceinline__ uint32_t ld_acquire(const uint32_t* p) { uint32_t v; asm volatile("ld.acquire.gpu.global.u32 %0, [%1];" : "=r"(v) : "l"(p) : "memory"); return v; }
__device__ __forceinline__ void prefetch_map(const CUtensorMap* m) { asm volatile("prefetch.tensormap [%0];" :: "l"(m) : "memory"); }
__device__ __forceinline__ float rcp(float x) { float r; asm("rcp.approx.ftz.f32 %0, %1;" : "=f"(r) : "f"(x)); return r; }
__device__ __forceinline__ float ex2(float x) { float r; asm("ex2.approx.ftz.f32 %0, %1;" : "=f"(r) : "f"(x)); return r; }
__device__ __forceinline__ float tanh_fast(float x) { float r; asm("tanh.approx.f32 %0, %1;" : "=f"(r) : "f"(x)); return r; }
#define SPIN_GUARD(n) if (++(n) > (1u << 24)) bail()

__device__ __forceinline__ void wgmma_n128(float (&d)[64], uint64_t da, uint64_t db) {
  asm volatile("wgmma.mma_async.sync.aligned.m64n128k16.f32.bf16.bf16 "
    "{%0, %1, %2, %3, %4, %5, %6, %7, %8, %9, %10, %11, %12, %13, %14, %15, %16, %17, %18, %19, %20, %21, %22, %23, %24, %25, %26, %27, %28, %29, %30, %31, %32, %33, %34, %35, %36, %37, %38, %39, %40, %41, %42, %43, %44, %45, %46, %47, %48, %49, %50, %51, %52, %53, %54, %55, %56, %57, %58, %59, %60, %61, %62, %63}, "
    "%64, %65, 1, 1, 1, 0, 1;\n"
    : "+f"(d[0]), "+f"(d[1]), "+f"(d[2]), "+f"(d[3]), "+f"(d[4]), "+f"(d[5]), "+f"(d[6]), "+f"(d[7]), "+f"(d[8]), "+f"(d[9]), "+f"(d[10]), "+f"(d[11]), "+f"(d[12]), "+f"(d[13]), "+f"(d[14]), "+f"(d[15]), "+f"(d[16]), "+f"(d[17]), "+f"(d[18]), "+f"(d[19]), "+f"(d[20]), "+f"(d[21]), "+f"(d[22]), "+f"(d[23]), "+f"(d[24]), "+f"(d[25]), "+f"(d[26]), "+f"(d[27]), "+f"(d[28]), "+f"(d[29]), "+f"(d[30]), "+f"(d[31]), "+f"(d[32]), "+f"(d[33]), "+f"(d[34]), "+f"(d[35]), "+f"(d[36]), "+f"(d[37]), "+f"(d[38]), "+f"(d[39]), "+f"(d[40]), "+f"(d[41]), "+f"(d[42]), "+f"(d[43]), "+f"(d[44]), "+f"(d[45]), "+f"(d[46]), "+f"(d[47]), "+f"(d[48]), "+f"(d[49]), "+f"(d[50]), "+f"(d[51]), "+f"(d[52]), "+f"(d[53]), "+f"(d[54]), "+f"(d[55]), "+f"(d[56]), "+f"(d[57]), "+f"(d[58]), "+f"(d[59]), "+f"(d[60]), "+f"(d[61]), "+f"(d[62]), "+f"(d[63])
    : "l"(da), "l"(db));
}
__device__ __forceinline__ void wgmma_n128_first(float (&d)[64], uint64_t da, uint64_t db) {
  asm volatile("wgmma.mma_async.sync.aligned.m64n128k16.f32.bf16.bf16 "
    "{%0, %1, %2, %3, %4, %5, %6, %7, %8, %9, %10, %11, %12, %13, %14, %15, %16, %17, %18, %19, %20, %21, %22, %23, %24, %25, %26, %27, %28, %29, %30, %31, %32, %33, %34, %35, %36, %37, %38, %39, %40, %41, %42, %43, %44, %45, %46, %47, %48, %49, %50, %51, %52, %53, %54, %55, %56, %57, %58, %59, %60, %61, %62, %63}, "
    "%64, %65, 0, 1, 1, 0, 1;\n"
    : "=f"(d[0]), "=f"(d[1]), "=f"(d[2]), "=f"(d[3]), "=f"(d[4]), "=f"(d[5]), "=f"(d[6]), "=f"(d[7]), "=f"(d[8]), "=f"(d[9]), "=f"(d[10]), "=f"(d[11]), "=f"(d[12]), "=f"(d[13]), "=f"(d[14]), "=f"(d[15]), "=f"(d[16]), "=f"(d[17]), "=f"(d[18]), "=f"(d[19]), "=f"(d[20]), "=f"(d[21]), "=f"(d[22]), "=f"(d[23]), "=f"(d[24]), "=f"(d[25]), "=f"(d[26]), "=f"(d[27]), "=f"(d[28]), "=f"(d[29]), "=f"(d[30]), "=f"(d[31]), "=f"(d[32]), "=f"(d[33]), "=f"(d[34]), "=f"(d[35]), "=f"(d[36]), "=f"(d[37]), "=f"(d[38]), "=f"(d[39]), "=f"(d[40]), "=f"(d[41]), "=f"(d[42]), "=f"(d[43]), "=f"(d[44]), "=f"(d[45]), "=f"(d[46]), "=f"(d[47]), "=f"(d[48]), "=f"(d[49]), "=f"(d[50]), "=f"(d[51]), "=f"(d[52]), "=f"(d[53]), "=f"(d[54]), "=f"(d[55]), "=f"(d[56]), "=f"(d[57]), "=f"(d[58]), "=f"(d[59]), "=f"(d[60]), "=f"(d[61]), "=f"(d[62]), "=f"(d[63])
    : "l"(da), "l"(db));
}
__device__ __forceinline__ void wgmma_n256(float (&d)[128], uint64_t da, uint64_t db) {
  asm volatile("wgmma.mma_async.sync.aligned.m64n256k16.f32.bf16.bf16 "
    "{%0, %1, %2, %3, %4, %5, %6, %7, %8, %9, %10, %11, %12, %13, %14, %15, %16, %17, %18, %19, %20, %21, %22, %23, %24, %25, %26, %27, %28, %29, %30, %31, %32, %33, %34, %35, %36, %37, %38, %39, %40, %41, %42, %43, %44, %45, %46, %47, %48, %49, %50, %51, %52, %53, %54, %55, %56, %57, %58, %59, %60, %61, %62, %63, %64, %65, %66, %67, %68, %69, %70, %71, %72, %73, %74, %75, %76, %77, %78, %79, %80, %81, %82, %83, %84, %85, %86, %87, %88, %89, %90, %91, %92, %93, %94, %95, %96, %97, %98, %99, %100, %101, %102, %103, %104, %105, %106, %107, %108, %109, %110, %111, %112, %113, %114, %115, %116, %117, %118, %119, %120, %121, %122, %123, %124, %125, %126, %127}, "
    "%128, %129, 1, 1, 1, 0, 1;\n"
    : "+f"(d[0]), "+f"(d[1]), "+f"(d[2]), "+f"(d[3]), "+f"(d[4]), "+f"(d[5]), "+f"(d[6]), "+f"(d[7]), "+f"(d[8]), "+f"(d[9]), "+f"(d[10]), "+f"(d[11]), "+f"(d[12]), "+f"(d[13]), "+f"(d[14]), "+f"(d[15]), "+f"(d[16]), "+f"(d[17]), "+f"(d[18]), "+f"(d[19]), "+f"(d[20]), "+f"(d[21]), "+f"(d[22]), "+f"(d[23]), "+f"(d[24]), "+f"(d[25]), "+f"(d[26]), "+f"(d[27]), "+f"(d[28]), "+f"(d[29]), "+f"(d[30]), "+f"(d[31]), "+f"(d[32]), "+f"(d[33]), "+f"(d[34]), "+f"(d[35]), "+f"(d[36]), "+f"(d[37]), "+f"(d[38]), "+f"(d[39]), "+f"(d[40]), "+f"(d[41]), "+f"(d[42]), "+f"(d[43]), "+f"(d[44]), "+f"(d[45]), "+f"(d[46]), "+f"(d[47]), "+f"(d[48]), "+f"(d[49]), "+f"(d[50]), "+f"(d[51]), "+f"(d[52]), "+f"(d[53]), "+f"(d[54]), "+f"(d[55]), "+f"(d[56]), "+f"(d[57]), "+f"(d[58]), "+f"(d[59]), "+f"(d[60]), "+f"(d[61]), "+f"(d[62]), "+f"(d[63]), "+f"(d[64]), "+f"(d[65]), "+f"(d[66]), "+f"(d[67]), "+f"(d[68]), "+f"(d[69]), "+f"(d[70]), "+f"(d[71]), "+f"(d[72]), "+f"(d[73]), "+f"(d[74]), "+f"(d[75]), "+f"(d[76]), "+f"(d[77]), "+f"(d[78]), "+f"(d[79]), "+f"(d[80]), "+f"(d[81]), "+f"(d[82]), "+f"(d[83]), "+f"(d[84]), "+f"(d[85]), "+f"(d[86]), "+f"(d[87]), "+f"(d[88]), "+f"(d[89]), "+f"(d[90]), "+f"(d[91]), "+f"(d[92]), "+f"(d[93]), "+f"(d[94]), "+f"(d[95]), "+f"(d[96]), "+f"(d[97]), "+f"(d[98]), "+f"(d[99]), "+f"(d[100]), "+f"(d[101]), "+f"(d[102]), "+f"(d[103]), "+f"(d[104]), "+f"(d[105]), "+f"(d[106]), "+f"(d[107]), "+f"(d[108]), "+f"(d[109]), "+f"(d[110]), "+f"(d[111]), "+f"(d[112]), "+f"(d[113]), "+f"(d[114]), "+f"(d[115]), "+f"(d[116]), "+f"(d[117]), "+f"(d[118]), "+f"(d[119]), "+f"(d[120]), "+f"(d[121]), "+f"(d[122]), "+f"(d[123]), "+f"(d[124]), "+f"(d[125]), "+f"(d[126]), "+f"(d[127])
    : "l"(da), "l"(db));
}
__device__ __forceinline__ void wgmma_n256_first(float (&d)[128], uint64_t da, uint64_t db) {
  asm volatile("wgmma.mma_async.sync.aligned.m64n256k16.f32.bf16.bf16 "
    "{%0, %1, %2, %3, %4, %5, %6, %7, %8, %9, %10, %11, %12, %13, %14, %15, %16, %17, %18, %19, %20, %21, %22, %23, %24, %25, %26, %27, %28, %29, %30, %31, %32, %33, %34, %35, %36, %37, %38, %39, %40, %41, %42, %43, %44, %45, %46, %47, %48, %49, %50, %51, %52, %53, %54, %55, %56, %57, %58, %59, %60, %61, %62, %63, %64, %65, %66, %67, %68, %69, %70, %71, %72, %73, %74, %75, %76, %77, %78, %79, %80, %81, %82, %83, %84, %85, %86, %87, %88, %89, %90, %91, %92, %93, %94, %95, %96, %97, %98, %99, %100, %101, %102, %103, %104, %105, %106, %107, %108, %109, %110, %111, %112, %113, %114, %115, %116, %117, %118, %119, %120, %121, %122, %123, %124, %125, %126, %127}, "
    "%128, %129, 0, 1, 1, 0, 1;\n"
    : "=f"(d[0]), "=f"(d[1]), "=f"(d[2]), "=f"(d[3]), "=f"(d[4]), "=f"(d[5]), "=f"(d[6]), "=f"(d[7]), "=f"(d[8]), "=f"(d[9]), "=f"(d[10]), "=f"(d[11]), "=f"(d[12]), "=f"(d[13]), "=f"(d[14]), "=f"(d[15]), "=f"(d[16]), "=f"(d[17]), "=f"(d[18]), "=f"(d[19]), "=f"(d[20]), "=f"(d[21]), "=f"(d[22]), "=f"(d[23]), "=f"(d[24]), "=f"(d[25]), "=f"(d[26]), "=f"(d[27]), "=f"(d[28]), "=f"(d[29]), "=f"(d[30]), "=f"(d[31]), "=f"(d[32]), "=f"(d[33]), "=f"(d[34]), "=f"(d[35]), "=f"(d[36]), "=f"(d[37]), "=f"(d[38]), "=f"(d[39]), "=f"(d[40]), "=f"(d[41]), "=f"(d[42]), "=f"(d[43]), "=f"(d[44]), "=f"(d[45]), "=f"(d[46]), "=f"(d[47]), "=f"(d[48]), "=f"(d[49]), "=f"(d[50]), "=f"(d[51]), "=f"(d[52]), "=f"(d[53]), "=f"(d[54]), "=f"(d[55]), "=f"(d[56]), "=f"(d[57]), "=f"(d[58]), "=f"(d[59]), "=f"(d[60]), "=f"(d[61]), "=f"(d[62]), "=f"(d[63]), "=f"(d[64]), "=f"(d[65]), "=f"(d[66]), "=f"(d[67]), "=f"(d[68]), "=f"(d[69]), "=f"(d[70]), "=f"(d[71]), "=f"(d[72]), "=f"(d[73]), "=f"(d[74]), "=f"(d[75]), "=f"(d[76]), "=f"(d[77]), "=f"(d[78]), "=f"(d[79]), "=f"(d[80]), "=f"(d[81]), "=f"(d[82]), "=f"(d[83]), "=f"(d[84]), "=f"(d[85]), "=f"(d[86]), "=f"(d[87]), "=f"(d[88]), "=f"(d[89]), "=f"(d[90]), "=f"(d[91]), "=f"(d[92]), "=f"(d[93]), "=f"(d[94]), "=f"(d[95]), "=f"(d[96]), "=f"(d[97]), "=f"(d[98]), "=f"(d[99]), "=f"(d[100]), "=f"(d[101]), "=f"(d[102]), "=f"(d[103]), "=f"(d[104]), "=f"(d[105]), "=f"(d[106]), "=f"(d[107]), "=f"(d[108]), "=f"(d[109]), "=f"(d[110]), "=f"(d[111]), "=f"(d[112]), "=f"(d[113]), "=f"(d[114]), "=f"(d[115]), "=f"(d[116]), "=f"(d[117]), "=f"(d[118]), "=f"(d[119]), "=f"(d[120]), "=f"(d[121]), "=f"(d[122]), "=f"(d[123]), "=f"(d[124]), "=f"(d[125]), "=f"(d[126]), "=f"(d[127])
    : "l"(da), "l"(db));
}

template <int N> struct WG;
#define DEF_WG(N) template <> struct WG<N> { \
  static __device__ __forceinline__ void mma(float (&d)[N / 2], uint64_t a, uint64_t b) { wgmma_n##N(d, a, b); } \
  static __device__ __forceinline__ void first(float (&d)[N / 2], uint64_t a, uint64_t b) { wgmma_n##N##_first(d, a, b); } };
DEF_WG(128) DEF_WG(256)

constexpr uint64_t DESC_A = (1ull << 62) | ((uint64_t)(1024 >> 4) << 32) | (1ull << 16);
constexpr uint64_t DESC_B = (1ull << 62) | ((uint64_t)(1024 >> 4) << 32) | ((uint64_t)(8192 >> 4) << 16);

struct Ring { int s; uint32_t ph; int wrap; };
template <int NS> __device__ __forceinline__ void ring_next(Ring& r) { r.s = (r.s + 1 == NS) ? 0 : r.s + 1; if (r.s == r.wrap) r.ph ^= 1; }

__device__ __forceinline__ int own_order(int it, int j) {
  return it < 2 ? 2 * j + it : it < 4 ? 2 * (j ^ 1) + it - 2 : ((j >> 1) * 4 + 2 * it - (it < 10 ? 4 : 15)) & 15;
}

template <int V> struct IC { static constexpr int v = V; };
template <int I, int E, class F> __device__ __forceinline__ void static_for(F&& f) { if constexpr (I < E) { f(IC<I>{}); static_for<I + 1, E>(f); } }

template <int N, int NS, int PRE, int LAG, class Pre, class Mid, class Last>
__device__ __forceinline__ void mainloop(float (&acc)[N / 2], int nkb, bool own, Ring& r, uint32_t sb, int wg, int lane, uint32_t rel_base, Pre pre, Mid mid, Last last) {
  constexpr int SLOT = RING / NS;
  const uint32_t full = sb + MISC + (NS == 4 ? B_FULL4 : B_FULL6);
  const uint32_t rel = rel_base + (NS == 4 ? B_EMPTY4 : B_EMPTY6);
  const uint32_t s0 = (sb & 0x3FFFF) >> 4, a0 = s0 + wg * (HALF >> 4);
  int ps;
  auto issue = [&](int it, bool first) {
    const uint64_t da = DESC_A | (a0 + ((own && it < 2) ? (STG + it * BLK) >> 4 : r.s * (SLOT >> 4))), db = DESC_B | (s0 + r.s * (SLOT >> 4) + (BLK >> 4));
    mbar_wait(full + r.s * 8, r.ph);
    wg_arrive();
    if (first) WG<N>::first(acc, da, db); else WG<N>::mma(acc, da, db);
#pragma unroll
    for (int k = 1; k < 4; k++) WG<N>::mma(acc, da + k * 2, db + k * 128);
    wg_commit();
  };
  auto retire = [&](int it) {
    wg_wait<1>();
    if (lane < 2) mbar_arrive_cl(rel + ps * 8);
    ps = r.s;
    ring_next<NS>(r);
  };
  issue(0, true);
  ps = r.s;
  ring_next<NS>(r);
  static_for<1, PRE + 1>([&](auto ic) { issue(ic.v, false); pre(ic); retire(ic.v); });
#pragma unroll 1
  for (int it = PRE + 1; it < nkb; it++) {
    if (LAG && it == nkb - LAG && wg == 1) mbar_wait(sb + MISC + B_LAG, WOLAG && !own);
    issue(it, false); mid(it); retire(it);
  }
  last();
  wg_wait<0>();
  if (lane < 2) mbar_arrive_cl(rel + ps * 8);
}

__device__ __forceinline__ void ln_publish(const float (&v)[64], uint4* st, int j, int row0, int lane, uint32_t ep) {
  float s0 = 0, s1 = 0, s2 = 0, s3 = 0, q0 = 0, q1 = 0, q2 = 0, q3 = 0;
#pragma unroll
  for (int i = 0; i < 16; i++) {
    s0 += v[4 * i]; s1 += v[4 * i + 1]; s2 += v[4 * i + 2]; s3 += v[4 * i + 3];
    q0 = fmaf(v[4 * i], v[4 * i], q0); q1 = fmaf(v[4 * i + 1], v[4 * i + 1], q1); q2 = fmaf(v[4 * i + 2], v[4 * i + 2], q2); q3 = fmaf(v[4 * i + 3], v[4 * i + 3], q3);
  }
  s0 += s1; s2 += s3; q0 += q1; q2 += q3;
  const bool odd = lane & 1;
  float s = (odd ? s2 : s0) + __shfl_xor_sync(~0u, odd ? s0 : s2, 1), q = (odd ? q2 : q0) + __shfl_xor_sync(~0u, odd ? q0 : q2, 1);
  s += __shfl_xor_sync(~0u, s, 2); q += __shfl_xor_sync(~0u, q, 2);
  if ((lane & 3) < 2) st_rlx4(st + j * 128 + row0 + (lane & 1) * 8, __float_as_uint(s), ep, __float_as_uint(q), ep);
}
__device__ __forceinline__ void ln_gather(const uint4* st, int row0, int lane, uint32_t ep, float& n0, float& r0, float& n1, float& r1) {
  const uint4* p = st + (lane & 2) * 256 + row0 + (lane & 1) * 8;
  uint4 a, b, c, d; uint32_t n = 0;
  while (true) {
    a = ld_rlx4(p); b = ld_rlx4(p + 128); c = ld_rlx4(p + 256); d = ld_rlx4(p + 384);
    if (a.y == ep && a.w == ep && b.y == ep && b.w == ep && c.y == ep && c.w == ep && d.y == ep && d.w == ep) break;
    SPIN_GUARD(n);
  }
  __syncwarp();
  float s = (__uint_as_float(a.x) + __uint_as_float(b.x)) + (__uint_as_float(c.x) + __uint_as_float(d.x));
  float q = (__uint_as_float(a.z) + __uint_as_float(b.z)) + (__uint_as_float(c.z) + __uint_as_float(d.z));
  s += __shfl_xor_sync(~0u, s, 2); q += __shfl_xor_sync(~0u, q, 2);
  s *= 1.f / 1024;
  const float r = rsqrtf(fmaxf(fmaf(-s, s, q * (1.f / 1024)), 0.f) + 1e-5f), nn = -s * r;
  const float ro = __shfl_xor_sync(~0u, r, 1), no = __shfl_xor_sync(~0u, nn, 1);
  const bool odd = lane & 1;
  r0 = odd ? ro : r; n0 = odd ? no : nn; r1 = odd ? r : ro; n1 = odd ? nn : no;
}
__device__ __forceinline__ void load_vec(uint32_t* w, uint32_t sb, int sec, int b, int lane) {
#pragma unroll
  for (int q = 0; q < 2; q++) { uint4 t = lds128(sb + MISC + MODV + sec * 256 + (lane & 3) * 64 + b * 32 + q * 16); w[4 * q] = t.x; w[4 * q + 1] = t.y; w[4 * q + 2] = t.z; w[4 * q + 3] = t.w; }
}
__device__ __forceinline__ void stage_done(uint32_t sb, int wg, int b, int lane) {
  fence_async_smem();
  __syncwarp();
  if (lane == 0) mbar_arrive(sb + MISC + B_RDY + b * 8);
}
__device__ __forceinline__ uint32_t hfma2(uint32_t a, uint32_t b, uint32_t c) { uint32_t r; asm("fma.rn.bf16x2 %0, %1, %2, %3;" : "=r"(r) : "r"(a), "r"(b), "r"(c)); return r; }
__device__ __forceinline__ void ln_apply(const float (&v)[64], const uint4* st, int row0, uint32_t ep, uint32_t sb, int sec_shift, int sec_scale, uint32_t stg_row, int wg, int lane) {
  uint32_t sc[16], sh[16];
#pragma unroll
  for (int b = 0; b < 2; b++) { load_vec(sc + 8 * b, sb, sec_scale, b, lane); load_vec(sh + 8 * b, sb, sec_shift, b, lane); }
  float n0, r0, n1, r1;
  ln_gather(st, row0, lane, ep, n0, r0, n1, r1);
#pragma unroll
  for (int i = 0; i < 16; i += 2) {
    if (i == 8) { const float z = lds32f(sb + MISC + ZERO); n0 += z; n1 += z; }
    uint32_t w[4];
#pragma unroll
    for (int u = 0; u < 2; u++) {
      int q = i + u;
      w[2 * u] = hfma2(pack2(fmaf(v[4 * q], r0, n0), fmaf(v[4 * q + 1], r0, n0)), sc[q], sh[q]);
      w[2 * u + 1] = hfma2(pack2(fmaf(v[4 * q + 2], r1, n1), fmaf(v[4 * q + 3], r1, n1)), sc[q], sh[q]);
    }
    stsm4(stg_row + (i >> 3) * BLK + ((((i & 7) + (lane >> 4)) ^ (lane & 7)) << 4), w[0], w[1], w[2], w[3]);
    if ((i & 7) == 6) { stage_done(sb, wg, i >> 3, lane); }
  }
}
__device__ __forceinline__ uint32_t hmul2(uint32_t a, uint32_t b) { uint32_t r; asm("mul.rn.bf16x2 %0, %1, %2;" : "=r"(r) : "r"(a), "r"(b)); return r; }
__device__ __forceinline__ uint32_t silu_mul2(uint32_t g, uint32_t u) {
  const uint32_t h = hmul2(g, 0x3f003f00u);
  const float h0 = bf_lo(h), h1 = bf_hi(h);
  return hmul2(pack2(fmaf(h0, tanh_fast(h0), h0), fmaf(h1, tanh_fast(h1), h1)), u);
}

__device__ __forceinline__ void gemv_fma(float (&a)[8], uint4 w, float s) {
  a[0] = fmaf(bf_lo(w.x), s, a[0]); a[1] = fmaf(bf_hi(w.x), s, a[1]); a[2] = fmaf(bf_lo(w.y), s, a[2]); a[3] = fmaf(bf_hi(w.y), s, a[3]);
  a[4] = fmaf(bf_lo(w.z), s, a[4]); a[5] = fmaf(bf_hi(w.z), s, a[5]); a[6] = fmaf(bf_lo(w.w), s, a[6]); a[7] = fmaf(bf_hi(w.w), s, a[7]);
}
__device__ __forceinline__ float silu_c(float v) { return bf_round(__fdividef(v, 1.f + __expf(-v))); }
__device__ __forceinline__ float mod_gather(const uint2* p, uint32_t ep) {
  uint2 a, b, c, d; uint32_t n = 0;
  while (true) {
    a = ld_rlx2(p); b = ld_rlx2(p + 128); c = ld_rlx2(p + 256); d = ld_rlx2(p + 384);
    if (a.y == ep && b.y == ep && c.y == ep && d.y == ep) break;
    SPIN_GUARD(n);
  }
  return (__uint_as_float(a.x) + __uint_as_float(b.x)) + (__uint_as_float(c.x) + __uint_as_float(d.x));
}
__device__ __forceinline__ void mod_store(uint32_t sb, int sec, int col, float v) {
  v = bf_round(v);
  if (sec == 1 || sec == 4) v += 1.f;
  sts16(sb + MISC + MODV + sec * 256 + (((col >> 1) & 3) * 16 + (col >> 3)) * 4 + (col & 1) * 2, __float2bfloat16_rn(v));
}

__global__ void __cluster_dims__(2, 1, 1) __launch_bounds__(384, 1)
fused_kernel(const bf16* __restrict__ cvec, const bf16* __restrict__ wmod, Scratch* gs, int by_sm, const __grid_constant__ Maps maps) {
  extern __shared__ __align__(1024) uint8_t smem_raw[];
  const uint32_t sb = smem_u32(smem_raw);
  const int warp = __shfl_sync(~0u, threadIdx.x >> 5, 0), lane = threadIdx.x & 31;
  const int rank = blockIdx.x & 1;
  uint32_t sm; asm volatile("mov.u32 %0, %%smid;" : "=r"(sm));
  const int t = sm >> 1, v = t < 32 ? t : t < 60 ? t + 1 + (((t - 32) * 37) >> 8) : (t - 58) * 8;
  const int cid = !by_sm ? (blockIdx.x >> 1) - 2 : (t & ~1) == 60 ? t - 62 : (v & 1) * 32 + ((v >> 1) & 31);
  const bool extra = cid < 0;
  const int bid = cid * 2 + rank;
  const int m = cid >> 2, j = (cid & 3) * 2 + rank;
  const uint32_t bar = sb + MISC;

  if (warp >= 8) {
    asm volatile("setmaxnreg.dec.sync.aligned.u32 40;");
    if (extra) {
      if (warp == 8) {
        if (lane == 0) { for (int s = 0; s < 6; s++) { mbar_init(bar + B_FULL6 + s * 8, 1); mbar_init(bar + B_EMPTY6 + s * 8, 8); } fence_async_smem(); }
        __syncwarp();
        asm volatile("bar.arrive 2, 288;" ::: "memory");
        __nanosleep(XSLEEP);
#pragma unroll 1
        for (int it = 0, s = 0, par = 1; it < 64; it++) {
          mbar_wait(bar + B_EMPTY6 + s * 8, par);
          if (elect()) { mbar_expect_tx(bar + B_FULL6 + s * 8, 32768); tma_3d(sb + s * 32768, &maps.wmod, bar + B_FULL6 + s * 8, 0, (it & 15) * 64, 12 + (it >> 4) * 4 + bid); }
          if (++s == 6) { s = 0; par ^= 1; }
        }
      }
    } else if (warp < 10) {
      uint32_t s6 = 0, p6 = 1;
      auto next6 = [&]() { if (++s6 == 6) { s6 = 0; p6 ^= 1; } };
      auto drained4 = [&](int q, int late) { if (q < 5) mbar_wait(bar + B_EMPTY4 + (((late ? 0x10332 : 0x32110) >> (4 * q)) & 3) * 8, 1); };
      auto drained6 = [&](int q) { if (q < 3) mbar_wait(bar + B_EMPTY6 + ((0x154 >> (4 * q)) & 7) * 8, q >> 1); };
      auto skip6 = [&]() { mbar_wait(bar + B_EMPTY6 + s6 * 8, p6); if (elect()) mbar_arrive(bar + B_FULL6 + s6 * 8); next6(); };
      if (warp == 8) {
        const uint32_t t_start = clock();
        if (lane == 0) {
          if (sb & 1023) bail();
          for (int b = 0; b < 2; b++) mbar_init(bar + B_X + b * 8, 1);
          for (int s = 0; s < 4; s++) { mbar_init(bar + B_FULL4 + s * 8, 2); mbar_init(bar + B_EMPTY4 + s * 8, 16); }
          for (int s = 0; s < 6; s++) { mbar_init(bar + B_FULL6 + s * 8, 2); mbar_init(bar + B_EMPTY6 + s * 8, 16); }
          for (int b = 0; b < 2; b++) { mbar_init(bar + B_RDY + b * 8, 8); mbar_init(bar + B_FREE + b * 8, 1); mbar_init(bar + B_HH + b * 8, 1); }
          mbar_init(bar + B_MOD, 1); mbar_init(bar + B_LAG, 4); mbar_init(bar + B_HALO, 2); mbar_init(bar + B_ALL, 1); mbar_init(bar + B_HH2, 1);
          asm volatile("st.shared.u32 [%0], 0;" :: "r"(bar + ZERO) : "memory");
          asm volatile("fence.mbarrier_init.release.cluster;" ::: "memory");
          fence_async_smem();
        }
        __syncwarp();
        cl_arrive_relaxed();
        auto wide = [&](int s, int par, const CUtensorMap* m0, int a0, const CUtensorMap* m1, int a1, int kb, bool spaced) {
          const uint32_t full = bar + B_FULL4 + s * 8, d = sb + s * 49152 + BLK;
          mbar_wait(full + 32, par);
          const uint32_t t0 = clock();
          if (elect()) { mbar_expect_tx(full, 2 * BLK); tma_3d(d, m0, full, 0, kb * 64, a0); }
          if (spaced) while ((uint32_t)clock() - t0 < 300) {}
          if (elect()) tma_3d(d + BLK, m1, full, 0, kb * 64, a1);
          if (spaced) while ((uint32_t)clock() - t0 < 600) {}
        };
        auto narrow = [&](const CUtensorMap* m0, int kb) {
          const uint32_t full = bar + B_FULL6 + s6 * 8;
          mbar_wait(full + 48, p6);
          if (elect()) { mbar_expect_tx(full, BLK); tma_3d(sb + s6 * 32768 + BLK, m0, full, 0, kb * 64, 2 * j); }
          next6();
        };
#pragma unroll 1
        for (int it = 0; it < 16; it++) {
          if (it == 0) {
            while ((uint32_t)clock() - t_start < XDELAY) {}
            if (elect()) for (int b = 0; b < 2; b++) { mbar_expect_tx(bar + B_X + b * 8, BLK); tma_3d(sb + STG + b * BLK, &maps.x, bar + B_X + b * 8, j * 128 + b * 64, m * 64, 0); }
            mbar_wait(bar + B_X + 8, 0);
          }
          wide(it & 3, ~(it >> 2) & 1, &maps.wqkv, 16 + 2 * j, &maps.wqkv, 32 + 2 * j, own_order(it, j), it < 4);
        }
#pragma unroll 1
        for (int it = 0; it < 16; it++) { drained4(it, 0); narrow(&maps.wqkv, it); }
#pragma unroll 1
        for (int it = 0; it < 16; it++) narrow(&maps.wo, own_order(it, j));
        skip6();
#pragma unroll 1
        for (int it = 0; it < 48; it++) {
          const int s = (it + 2) & 3, par = ~(it >> 2) & 1;
          drained6(it);
          wide(s, par, &maps.w1, (it & 48) + 2 * j, &maps.w3, (it & 48) + 2 * j, it < 16 ? own_order(it, j) : it & 15, it < 4);
          if (it >= 44) {
            if (it == 44) { mbar_wait(bar + B_FREE, 0); mbar_wait(bar + B_FREE + 8, 0); if (elect()) mbar_expect_tx(bar + B_X, 2 * BLK); }
            if (elect()) bulk_ld(sb + STG + (it - 44) * HALF, gs->x1 + bid * 2048 + (it - 44) * 512, HALF, bar + B_X);
          }
        }
#pragma unroll 1
        for (int it = 0; it < 16; it++) {
          const uint32_t full = bar + B_FULL6 + s6 * 8, d = sb + s6 * 32768 + BLK;
          drained4(it, 1);
          mbar_wait(full + 48, p6);
          if (elect()) { mbar_expect_tx(full, BLK); tma_3d(d, &maps.w1s, full, 0, it * 64, 48 + j); tma_3d(d + HALF, &maps.w3s, full, 0, it * 64, 48 + j); }
          next6();
        }
#pragma unroll 1
        for (int it = 0; it < 56; it++) narrow(&maps.w2, it);
      } else {
        if (lane < 9) prefetch_map(&maps.x + lane);
        const uint32_t ep = gs->epoch[bid + 4] + 1;
        cl_arrive_relaxed(); cl_wait();
        auto plain = [&](uint32_t full, uint32_t empty, int par, uint32_t slot, const uint4* blk) {
          mbar_wait(empty, par);
          if (elect()) { mbar_expect_tx(full, BLK); bulk_ld_mc(slot + rank * HALF, blk + rank * 512, HALF, full); }
        };
        auto plain6 = [&](const uint4* blk) { plain(bar + B_FULL6 + s6 * 8, bar + B_EMPTY6 + s6 * 8, p6, sb + s6 * 32768, blk); next6(); };
        uint32_t ready = 0;
        auto poll = [&](int e) { ready = __ballot_sync(~0u, ld_acquire(gs->flag + (m * 128 + e * 16 + (lane & 14)) * FS) == ep); };
        auto need = [&](int e, uint32_t mask) {
          if ((ready & mask) != mask) {
            uint32_t n = 0;
            do { poll(e); SPIN_GUARD(n); } while ((ready & mask) != mask);
            fence_async_global();
          }
        };
        auto fresh = [&](int e, int it, uint32_t full, uint32_t empty, int par, uint32_t slot, uint4* src) {
          if (it >= 4) {
            const int kb = own_order(it, j);
            if (it < 10) need(e, 1u << kb); else if (it == 10) mbar_wait(bar + B_ALL, e & 1);
            plain(full, empty, par, slot, src + kb * 1024);
          } else {
            if (it == 0) ready = 0;
            mbar_wait(empty, par);
            if (it < 2) { if (elect()) mbar_arrive(full); }
            else {
              const int b = it > 2;
              const uint32_t to_peer = mapa(sb, rank ^ 1) - sb;
              if (elect()) mbar_expect_tx(full, BLK);
              const bool push = e != 1;
              mbar_wait(bar + (b ? (push ? B_RDY + 8 : B_FREE + 8) : B_RDY), e & 1);
              if (elect()) {
                if (b == 0) {
                  bulk_st(src + 2 * j * 1024, sb + STG, BLK);
                  bulk_commit();
                  bulk_wait_all();
                  mbar_arrive(bar + B_FREE);
                }
                if (b && push) bulk_push(slot + to_peer, sb + STG + BLK, BLK, full + to_peer);
                else {
                  fence_async_global();
                  bulk_ld(slot + to_peer, src + (2 * j + b) * 1024, BLK, full + to_peer);
                }
              }
              __syncwarp();
            }
          }
        };
#pragma unroll 1
        for (int ph = 0; ph < 2; ph++) {
          uint4* h = gs->h + m * 16384;
#pragma unroll 1
          for (int it = 0; it < 16; it++) {
            const int s = (it + 2 * ph) & 3;
            if (ph) drained6(it);
            fresh(2 * ph, it, bar + B_FULL4 + s * 8, bar + B_EMPTY4 + s * 8, ~(it >> 2) & 1, sb + s * 49152, h);
          }
          if (ph) {
#pragma unroll 1
            for (int it = 16; it < 48; it++) {
              const int s = (it + 2) & 3;
              const uint32_t full = bar + B_FULL4 + s * 8;
              plain(full, full + 32, ~(it >> 2) & 1, sb + s * 49152, h + (it & 15) * 1024);
            }
          }
#pragma unroll 1
          for (int it = 0; it < 16; it++) { drained4(it, ph); plain6(h + it * 1024); }
          if (!ph) {
#pragma unroll 1
            for (int it = 0; it < 16; it++) { fresh(1, it, bar + B_FULL6 + s6 * 8, bar + B_EMPTY6 + s6 * 8, p6, sb + s6 * 32768, gs->o + m * 16384); next6(); }
            skip6();
          }
        }
#pragma unroll 1
        for (int it = 0; it < 56; it++) {
          if (it == 0 || it == 32 || it == 48) mbar_wait(bar + (it == 48 ? B_HH2 : B_HH + (it >> 2)), 0);
          plain6(gs->hh + m * 57344 + it * 1024);
        }
      }
    } else {
      const int b = warp - 10;
      const uint32_t ep = gs->epoch[bid + 4] + 1;
      const uint32_t stg = sb + STG + b * BLK;
      cl_arrive_relaxed(); cl_wait();
      auto all_there = [&](int u, uint32_t done) {
        const uint32_t* fl = gs->flag + u * FS;
        uint32_t n = 0;
        while (!__all_sync(~0u, ld_acquire(fl) == ep)) { __nanosleep(100); SPIN_GUARD(n); }
        fence_async_global();
        if (lane == 0) mbar_arrive(done);
      };
      auto fetch_mod = [&](int sec) {
        const uint4* p = (const uint4*)(gs->modv + (sec - 2) * 1024 + j * 128) + lane;
        uint4 v0, v1; uint32_t n = 0;
        while (true) {
          v0 = ld_rlx4(p); v1 = ld_rlx4(p + 32);
          if (v0.y == ep && v0.w == ep && v1.y == ep && v1.w == ep) break;
          SPIN_GUARD(n);
        }
        mod_store(sb, sec, 2 * lane, __uint_as_float(v0.x)); mod_store(sb, sec, 2 * lane + 1, __uint_as_float(v0.z));
        mod_store(sb, sec, 64 + 2 * lane, __uint_as_float(v1.x)); mod_store(sb, sec, 65 + 2 * lane, __uint_as_float(v1.z));
        __syncwarp();
      };
#pragma unroll 1
      for (int e = 0; e < 7 - b; e++) {
        if (lane == 0) {
          if (e < 3) {
            mbar_wait(bar + B_FREE, e & 1);
            if (b) {
              const uint32_t t0 = clock();
              while ((uint32_t)clock() - t0 < (e == 0 ? B1P : e == 2 ? B1P2 : B1D)) {}
              mbar_wait(bar + B_RDY + 8, e & 1);
              bulk_st((e == 1 ? gs->o : gs->h) + m * 16384 + (2 * j + 1) * 1024, stg, BLK);
              bulk_commit();
              bulk_wait_all();
              mbar_arrive(bar + B_FREE + 8);
            }
            st_release(gs->flag + (m * 128 + e * 16 + 2 * j + b) * FS, ep);
          } else {
            const int kb = (e < 6 ? 2 * (8 * (e - 3) + j) : 48 + j) + b;
            mbar_wait(bar + B_RDY + b * 8, e & 1);
#pragma unroll 1
            for (int q = 0; q < NPIECE; q++) { if (q) __nanosleep(PSLEEP); bulk_st(gs->hh + m * 57344 + kb * 1024 + q * (1024 / NPIECE), stg + q * (BLK / NPIECE), BLK / NPIECE); }
            bulk_commit();
            bulk_wait_all();
            mbar_arrive(bar + B_FREE + b * 8);
            st_release(gs->flag + (m * 128 + U_HH + kb) * FS, ep);
          }
        }
        __syncwarp();
        if (e < 3 && b) all_there(m * 128 + e * 16 + (lane & 15), bar + B_ALL);
        if (e == 4 && b) all_there(m * 128 + U_HH + lane, bar + B_HH);
        if (!b && (e == 1 || e == 2)) {
#pragma unroll 1
          for (int sec = e == 1 ? 2 : 5; sec < 4 + e; sec++) fetch_mod(sec);
          if (e == 1) { if (lane == 0) mbar_arrive(bar + B_MOD); }
        }
        if (e == 0) {
          mbar_wait(bar + B_EMPTY6 + 24, 0);
          __nanosleep(HSLEEP);
#pragma unroll 1
          for (int w = 0; w < 4; w++) {
            const uint4* hp = gs->halo + ((m * 8 + j) * 2 + (w & 1)) * 512 + b * 256 + (w >> 1) * 128 + lane;
            uint4 q[4] = {}; uint32_t n = 0;
            while (m > 0) {
              bool ok = true;
#pragma unroll
              for (int i = 0; i < 4; i++) q[i] = ld_rlx4(hp + i * 32);
#pragma unroll
              for (int i = 0; i < 4; i++) ok = ok && q[i].y == ep && q[i].w == ep;
              if (ok) break;
              SPIN_GUARD(n);
            }
#pragma unroll
            for (int i = 0; i < 2; i++) sts128(stg + lane * 16 + (w & 1) * HALF + (w >> 1) * 1024 + i * 512, q[2 * i].x, q[2 * i + 1].x, q[2 * i].z, q[2 * i + 1].z);
          }
          __syncwarp();
          if (lane == 0) mbar_arrive(bar + B_HALO);
        }
      }
      if (b) { all_there(m * 128 + U_HH + 32 + (lane & 15), bar + B_HH + 8); all_there(m * 128 + U_HH + 48 + (lane & 7), bar + B_HH2); }
    }
  } else {
    const int wg = warp >> 2, wq = warp & 3, tid = threadIdx.x;
    const int g = lane >> 2, c = lane & 3;
    const int sec0 = (m >> 1) & 1, hf0 = m & 1, ks0 = (m >> 2) & 3;
    uint4 wv[8];
    uint32_t ep0; uint16_t cv_;
    asm volatile("ld.global.nc.u16 %0, [%1];" : "=h"(cv_) : "l"(cvec + ks0 * 256 + warp * 32 + lane));
    asm volatile("ld.global.u32 %0, [%1];" : "=r"(ep0) : "l"(gs->epoch + bid + 4));
    if (!extra) {
      const bf16* wp = wmod + (size_t)(ks0 * 256 + warp * 32 + (lane >> 3)) * 6144 + sec0 * 1024 + j * 128 + hf0 * 64 + (lane & 7) * 8;
#pragma unroll
      for (int i = 0; i < 8; i++) wv[i] = ldg_nc(wp + (size_t)i * 4 * 6144);
    }
    asm volatile("setmaxnreg.inc.sync.aligned.u32 232;" ::: "memory");
    if (__builtin_expect(extra, 0)) {
      const uint32_t ep = ep0 + 1;
      float sv[4];
#pragma unroll
      for (int p = 0; p < 4; p++) sv[p] = silu_c(__bfloat162float(cvec[64 * (4 * p + (lane >> 3)) + 8 * warp + (lane & 7)]));
      named_bar(2, 288);
      int s = 0, par = 0;
#pragma unroll 1
      for (int sec = 0; sec < 4; sec++) {
        float a[8] = {0, 0, 0, 0, 0, 0, 0, 0};
#pragma unroll 1
        for (int it = 0; it < 16; it++) {
          const float sc = it < 4 ? sv[0] : it < 8 ? sv[1] : it < 12 ? sv[2] : sv[3];
          mbar_wait(bar + B_FULL6 + s * 8, par);
          uint4 w[8];
#pragma unroll
          for (int i = 0; i < 8; i++) w[i] = lds128(sb + s * 32768 + (warp * 8 + i) * 512 + lane * 16);
#pragma unroll
          for (int i = 0; i < 8; i++) gemv_fma(a, w[i], __shfl_sync(~0u, sc, (it & 3) * 8 + i));
          if (lane == 0) mbar_arrive(bar + B_EMPTY6 + s * 8);
          if (++s == 6) { s = 0; par ^= 1; }
        }
        const uint32_t red = sb + STG + sec * 8192;
        sts128(red + warp * 1024 + lane * 32, __float_as_uint(a[0]), __float_as_uint(a[1]), __float_as_uint(a[2]), __float_as_uint(a[3]));
        sts128(red + warp * 1024 + lane * 32 + 16, __float_as_uint(a[4]), __float_as_uint(a[5]), __float_as_uint(a[6]), __float_as_uint(a[7]));
        named_bar(1, 256);
        float t = 0;
#pragma unroll
        for (int q = 0; q < 8; q++) t += lds32f(red + q * 1024 + tid * 4);
        st_rlx2(gs->modv + sec * 1024 + (bid + 4) * 256 + tid, __float_as_uint(t), ep);
      }
      if (tid == 0) gs->epoch[bid + 4] = ep;
      return;
    }
    const int row0 = wg * 64 + wq * 16 + g;
    if (c < 2) st_rlx4(gs->stat + m * 1024 + j * 128 + row0 + c * 8, 0, 0, 0, 0);
    if (tid < 64) st_rlx2(gs->modp + ((j * 2 + sec0) * 4 + ks0) * 128 + hf0 * 64 + tid, 0, 0);
    cl_arrive_relaxed(); cl_wait();
    uint32_t ep;
    asm volatile("add.u32 %0, %1, 1;" : "=r"(ep) : "r"(ep0) : "memory");
    const float sc_ = silu_c(__uint_as_float((uint32_t)cv_ << 16));
    const uint32_t rel = mapa(bar, (lane & 1) ^ rank);
    const uint32_t stg_row = sb + STG + (wg * 64 + wq * 16 + (lane & 15)) * 128;
    const uint32_t fre = bar + B_FREE;
    Ring r4{0, 0, 0}, r6{0, 0, 0};
    auto none = [](auto) {};
    uint32_t xk[32];
    {
      float a[8] = {0, 0, 0, 0, 0, 0, 0, 0};
#pragma unroll
      for (int i = 0; i < 8; i++) gemv_fma(a, wv[i], __shfl_sync(~0u, sc_, i * 4 + (lane >> 3)));
#pragma unroll
      for (int i = 0; i < 8; i++) { a[i] += __shfl_xor_sync(~0u, a[i], 8); a[i] += __shfl_xor_sync(~0u, a[i], 16); }
      if (lane < 8) {
        sts128(sb + RED_OFF + warp * 256 + lane * 32, __float_as_uint(a[0]), __float_as_uint(a[1]), __float_as_uint(a[2]), __float_as_uint(a[3]));
        sts128(sb + RED_OFF + warp * 256 + lane * 32 + 16, __float_as_uint(a[4]), __float_as_uint(a[5]), __float_as_uint(a[6]), __float_as_uint(a[7]));
      }
      named_bar(1, 256);
      if (tid < 64) {
        float s = 0;
#pragma unroll
        for (int w = 0; w < 8; w++) s += lds32f(sb + RED_OFF + w * 256 + tid * 4);
        st_rlx2(gs->modp + ((j * 2 + sec0) * 4 + ks0) * 128 + hf0 * 64 + tid, __float_as_uint(s), ep);
      }
      float v[64];
      mbar_wait(bar + B_X, 0); mbar_wait(bar + B_X + 8, 0);
#pragma unroll
      for (int i = 0; i < 16; i += 2) {
        uint32_t w0, w1, w2, w3;
        ldsm4(stg_row + (i >> 3) * BLK + ((((i & 7) + (lane >> 4)) ^ (lane & 7)) << 4), w0, w1, w2, w3);
        xk[2 * i] = w0; xk[2 * i + 1] = w1; xk[2 * i + 2] = w2; xk[2 * i + 3] = w3;
        v[4 * i] = bf_lo(w0); v[4 * i + 1] = bf_hi(w0); v[4 * i + 2] = bf_lo(w1); v[4 * i + 3] = bf_hi(w1);
        v[4 * i + 4] = bf_lo(w2); v[4 * i + 5] = bf_hi(w2); v[4 * i + 6] = bf_lo(w3); v[4 * i + 7] = bf_hi(w3);
      }
      ln_publish(v, gs->stat + m * 1024, j, row0, lane, ep);
      mod_store(sb, tid >> 7, tid & 127, mod_gather(gs->modp + (j * 2 + (tid >> 7)) * 512 + (tid & 127), ep));
      named_bar(1, 256);
      ln_apply(v, gs->stat + m * 1024, row0, ep, sb, 0, 1, stg_row, wg, lane);
      named_bar(1, 256);
    }
    {
      uint32_t kf[32], vf[32], pv[32];
      const bool first = wq == 0 && m == 0;
      const uint32_t xa = sb + STG + wg * HALF + wq * 2048 + lane * 16;
      {
        float acc[128];
        mainloop<256, 4, 0, 0>(acc, 16, true, r4, sb, wg, lane, rel, none, none, [&] {
          mbar_wait(fre + 8, 0);
          if (c < 2) st_rlx4(gs->stat + (16 + m) * 1024 + j * 128 + row0 + c * 8, 0, 0, 0, 0);
        });
#pragma unroll
        for (int i = 0; i < 32; i++) { kf[i] = pack2(acc[2 * i], acc[2 * i + 1]); vf[i] = pack2(acc[64 + 2 * i], acc[65 + 2 * i]); }
      }
      float acc[64];
      constexpr int QP = 2;
      mainloop<128, 6, 8 / QP, 0>(acc, 16, false, r6, sb, wg, lane, rel, [&](auto ic) {
        constexpr int q = (ic.v - 1) * QP;
#pragma unroll
        for (int i = 4 * q; i < 4 * (q + QP); i++) vf[i] = movm(vf[i]);
        if (wq == 3) {
          if (m < 15) {
            uint4* hp = gs->halo + (((m + 1) * 8 + j) * 2 + wg) * 512 + lane;
#pragma unroll
            for (int i = 2 * q; i < 2 * (q + QP); i++) st_rlx4(hp + i * 32, kf[2 * i + 1], ep, vf[2 * i + 1], ep);
          }
        } else {
#pragma unroll
          for (int i = q; i < q + QP; i++) sts128(xa + 2048 + (i >> 2) * BLK + (i & 3) * 512, kf[4 * i + 1], kf[4 * i + 3], vf[4 * i + 1], vf[4 * i + 3]);
        }
      }, none, [&] {
        named_bar(2 + wg, 128);
        if (wq == 0) mbar_wait(bar + B_HALO, 0);
#pragma unroll
        for (int i = 0; i < 8; i++) {
          uint4 q = lds128(xa + (i >> 2) * BLK + (i & 3) * 512);
          pv[4 * i] = q.x; pv[4 * i + 1] = q.y; pv[4 * i + 2] = q.z; pv[4 * i + 3] = q.w;
        }
        __syncwarp();
      });
      int gz = g;
#pragma unroll
      for (int b = 0; b < 2; b++) {
        const bool up0 = 2 * c > gz, up1 = 2 * c + 1 > gz;
        const uint32_t mup = (up0 ? 0xffffu : 0u) | (up1 ? 0xffff0000u : 0u);
        float l[2][4], mx[4];
#pragma unroll
        for (int h = 0; h < 2; h++) {
          uint32_t q[8];
          const int k = 16 * b + 8 * h;
#pragma unroll
          for (int i = 0; i < 8; i++) q[i] = pack2(acc[2 * k + 2 * i], acc[2 * k + 2 * i + 1]);
          float s0[4], s1[4], s2[4];
          mma16z(s0, q[0], q[1], q[2], q[3], pv[k], pv[k + 1]); mma16z(s1, q[0], q[1], q[2], q[3], kf[k], kf[k + 2]); mma16z(s2, q[0], q[1], q[2], q[3], kf[k + 1], kf[k + 3]);
          mma16(s0, q[4], q[5], q[6], q[7], pv[k + 4], pv[k + 5]); mma16(s1, q[4], q[5], q[6], q[7], kf[k + 4], kf[k + 6]); mma16(s2, q[4], q[5], q[6], q[7], kf[k + 5], kf[k + 7]);
          if (first) { s0[0] = -INFINITY; s0[1] = -INFINITY; }
          l[h][0] = up0 ? s0[0] : s1[0]; l[h][1] = up1 ? s0[1] : s1[1]; l[h][2] = up0 ? s1[2] : s2[2]; l[h][3] = up1 ? s1[3] : s2[3];
          mx[2 * h] = fmaxf(l[h][0], l[h][1]); mx[2 * h + 1] = fmaxf(l[h][2], l[h][3]);
        }
#pragma unroll
        for (int o = 1; o < 4; o <<= 1) {
#pragma unroll
          for (int h = 0; h < 4; h++) mx[h] = fmaxf(mx[h], __shfl_xor_sync(~0u, mx[h], o));
        }
#pragma unroll
        for (int h = 0; h < 2; h++) {
          const float n0 = -mx[2 * h] * SCL, n1 = -mx[2 * h + 1] * SCL;
          const uint32_t pa = pack2(ex2(fmaf(l[h][0], SCL, n0)), ex2(fmaf(l[h][1], SCL, n0))), pb = pack2(ex2(fmaf(l[h][2], SCL, n1)), ex2(fmaf(l[h][3], SCL, n1)));
          float sm[4];
          mma8z(sm, pa, pb, 0x3f803f80u);
          const float ia = rcp(sm[0]), ib = rcp(sm[2]);
#pragma unroll
          for (int i = 8 * b + 4 * h; i < 8 * b + 4 * h + 4; i += 2) {
            uint32_t of[4];
#pragma unroll
            for (int d = 0; d < 2; d++) {
              float o[4];
              mma16z(o, pa & ~mup, pb & mup, 0u, pb & ~mup, vf[2 * (i + d)], vf[2 * (i + d) + 1]);
              mma8(o, pa & mup, 0u, pv[2 * i + 2 + d]);
              of[2 * d] = pack2(o[0] * ia, o[1] * ia); of[2 * d + 1] = pack2(o[2] * ib, o[3] * ib);
            }
            stsm4(stg_row + b * BLK + ((((i & 7) + (lane >> 4)) ^ (lane & 7)) << 4), of[0], of[1], of[2], of[3]);
          }
        }
        stage_done(sb, wg, b, lane);
        if (b == 0) gz += __float_as_uint(lds32f(bar + ZERO));
      }
      named_bar(1, 256);
    }
    uint32_t pk[64];
    {
      float acc[64];
      mainloop<128, 6, 0, WOLAG>(acc, 16, true, r6, sb, wg, lane, rel, none, none, [&] {
        if (WOLAG && wg == 0 && lane == 0) mbar_arrive(bar + B_LAG);
        mbar_wait(bar + B_MOD, 0); mbar_wait(fre + 8, 1);
        load_vec(pk + 32, sb, 2, 0, lane); load_vec(pk + 40, sb, 2, 1, lane);
#pragma unroll
        for (int i = 0; i < 32; i++) { pk[i] = xk[i]; asm volatile("" : "+r"(pk[i])); }
      });
#pragma unroll
      for (int i = 0; i < 32; i++) {
        acc[2 * i] = fmaf(acc[2 * i], bf_lo(pk[32 + (i >> 1)]), bf_lo(pk[i]));
        acc[2 * i + 1] = fmaf(acc[2 * i + 1], bf_hi(pk[32 + (i >> 1)]), bf_hi(pk[i]));
      }
      ln_publish(acc, gs->stat + (16 + m) * 1024, j, row0, lane, ep);
      mbar_wait(bar + B_FULL6 + 16, 1);
      if (lane < 2) mbar_arrive_cl(rel + B_EMPTY6 + 16);
      ring_next<6>(r6);
#pragma unroll
      for (int i = 0; i < 32; i++) { pk[i] = pack2(acc[2 * i], acc[2 * i + 1]); pk[32 + i] = 0; }
      ln_apply(acc, gs->stat + (16 + m) * 1024, row0, ep, sb, 3, 4, stg_row, wg, lane);
      named_bar(1, 256);
    }
    auto swiglu = [&](int q, int uo, int par) {
      if ((q & 3) == 0 && par >= 0) mbar_wait(fre + 2 * q, par);
      uint32_t w[4];
#pragma unroll
      for (int u = 0; u < 4; u++) w[u] = silu_mul2(pk[4 * q + u], pk[uo + 4 * q + u]);
      stsm4(stg_row + (q >> 2) * BLK + ((((2 * q & 7) + (lane >> 4)) ^ (lane & 7)) << 4), w[0], w[1], w[2], w[3]);
    };
    r4.s = r4.wrap = 2;
#pragma unroll 1
    for (int t = 0; t < 3; t++) {
      float acc[128];
      mainloop<256, 4, 5, 0>(acc, 16, t == 0, r4, sb, wg, lane, rel, [&](auto ic) {
        if (t) {
          if (ic.v == 3 || ic.v == 5) stage_done(sb, wg, ic.v >> 2, lane);
          if (ic.v < 5) { swiglu(2 * ic.v - 2, 32, ~t & 1); swiglu(2 * ic.v - 1, 32, 0); }
        }
      }, [&](int it) {
#pragma unroll
        for (int i = 0; i < 8; i++)
          if (t == 0 && it == 8 + i) gs->x1[bid * 2048 + (i >> 2) * 1024 + warp * 128 + (i & 3) * 32 + lane] = make_uint4(pk[4 * i], pk[4 * i + 1], pk[4 * i + 2], pk[4 * i + 3]);
      }, [&] { if (t == 0) fence_async_global(); else if (t == 2) mbar_wait(bar + B_X, 1); });
#pragma unroll
      for (int i = 0; i < 64; i++) pk[i] = pack2(acc[2 * i], acc[2 * i + 1]);
    }
    uint32_t x1[32];
    {
      float acc[64];
      mainloop<128, 6, 12, 0>(acc, 16, false, r6, sb, wg, lane, rel, [&](auto ic) {
        constexpr int b = ic.v > 6, q = ic.v - 6 * b;
        if (q == 1) {
#pragma unroll
          for (int i = 4 * b; i < 4 * b + 4; i++) { const uint4 x = lds128(sb + STG + b * BLK + warp * 2048 + (i & 3) * 512 + lane * 16); x1[4 * i] = x.x; x1[4 * i + 1] = x.y; x1[4 * i + 2] = x.z; x1[4 * i + 3] = x.w; }
          __syncwarp();
        } else if (q < 6) swiglu(4 * b + q - 2, 32, -1);
        else stage_done(sb, wg, b, lane);
      }, none, [] {});
#pragma unroll
      for (int i = 0; i < 32; i++) pk[i] = pack2(acc[2 * i], acc[2 * i + 1]);
    }
    {
      float acc[64];
      mainloop<128, 6, 5, TAILLAG>(acc, 56, false, r6, sb, wg, lane, rel, [&](auto ic) {
        if (ic.v == 5) stage_done(sb, wg, 0, lane); else swiglu(ic.v - 1, 16, 1);
      }, none, [&] {
        if (TAILLAG && wg == 0 && lane == 0) mbar_arrive(bar + B_LAG);
        load_vec(pk + 32, sb, 5, 0, lane); load_vec(pk + 40, sb, 5, 1, lane);
        mbar_wait(fre, 0); mbar_wait(fre + 8, 1);
      });
      __syncwarp();
      cl_arrive_relaxed();
#pragma unroll
      for (int i = 0; i < 16; i += 2) {
        uint32_t w[4];
#pragma unroll
        for (int u = 0; u < 4; u++) {
          const int q = 2 * i + u;
          w[u] = pack2(fmaf(acc[2 * q], bf_lo(pk[32 + (q >> 1)]), bf_lo(x1[q])), fmaf(acc[2 * q + 1], bf_hi(pk[32 + (q >> 1)]), bf_hi(x1[q])));
        }
        stsm4(stg_row + (i >> 3) * BLK + ((((i & 7) + (lane >> 4)) ^ (lane & 7)) << 4), w[0], w[1], w[2], w[3]);
        if ((i & 7) == 6) {
          fence_async_smem();
          named_bar(2 + wg, 128);
          if (wq == 0 && elect()) { tma_store_3d(&maps.out, sb + STG + (i >> 3) * BLK + wg * HALF, j * 128 + (i >> 3) * 64, m * 64, wg); bulk_commit(); }
          if (i < 8) x1[16] |= __float_as_uint(lds32f(bar + ZERO));
        }
      }
      if (wq == 0) bulk_wait_read();
      if (tid == 0) gs->epoch[bid + 4] = ep;
      cl_wait();
    }
  }
}

typedef CUresult (*EncodeFn)(CUtensorMap*, CUtensorMapDataType, cuuint32_t, void*, const cuuint64_t*, const cuuint64_t*, const cuuint32_t*, const cuuint32_t*,
                             CUtensorMapInterleave, CUtensorMapSwizzle, CUtensorMapL2promotion, CUtensorMapFloatOOBfill);

void make_map(EncodeFn fn, CUtensorMap* mp, const void* base, uint64_t d0, uint64_t d1, uint64_t d2, uint64_t s1, uint64_t s2, uint32_t b2, uint32_t b0 = 64) {
  cuuint64_t d[3] = {d0, d1, d2}, s[2] = {s1, s2};
  cuuint32_t b[3] = {b0, 64, b2}, e[3] = {1, 1, 1};
  fn(mp, CU_TENSOR_MAP_DATA_TYPE_BFLOAT16, 3, (void*)base, d, s, b, e, CU_TENSOR_MAP_INTERLEAVE_NONE, b0 == 64 ? CU_TENSOR_MAP_SWIZZLE_128B : CU_TENSOR_MAP_SWIZZLE_NONE,
     CU_TENSOR_MAP_L2_PROMOTION_L2_128B, CU_TENSOR_MAP_FLOAT_OOB_FILL_NONE);
}

__global__ void probe_kernel() {}
int max_clusters(int size) {
  cudaLaunchConfig_t cfg = {};
  cudaLaunchAttribute at;
  at.id = cudaLaunchAttributeClusterDimension; at.val.clusterDim.x = size; at.val.clusterDim.y = 1; at.val.clusterDim.z = 1;
  cfg.gridDim = dim3(size * 66); cfg.blockDim = dim3(384); cfg.dynamicSmemBytes = SMEM_BYTES; cfg.attrs = &at; cfg.numAttrs = 1;
  int n = 0;
  if (cudaOccupancyMaxActiveClusters(&n, probe_kernel, &cfg) != cudaSuccess) { cudaGetLastError(); return 0; }
  return n;
}

}

extern "C" void kernel_launch(void* const* d_in, const int* in_sizes, int n_in, void* d_out, int out_size) {
  static EncodeFn fn = nullptr;
  static int by_sm = 0;
  static Scratch* gs = nullptr;
  if (!fn) {
    void* p = nullptr; cudaDriverEntryPointQueryResult q;
    cudaGetDriverEntryPoint("cuTensorMapEncodeTiled", &p, cudaEnableDefault, &q);
    fn = (EncodeFn)p;
    cudaFuncSetAttribute(fused_kernel, cudaFuncAttributeMaxDynamicSharedMemorySize, SMEM_BYTES);
    int dev = 0, sms = 0;
    cudaGetSymbolAddress((void**)&gs, g_scratch);
    cudaGetDevice(&dev);
    cudaDeviceGetAttribute(&sms, cudaDevAttrMultiProcessorCount, dev);
    cudaFuncSetAttribute(probe_kernel, cudaFuncAttributeMaxDynamicSharedMemorySize, SMEM_BYTES);
    by_sm = sms == 132 && max_clusters(2) == 66 && max_clusters(4) == 30 && max_clusters(6) == 17 && max_clusters(8) == 15;
  }
  Maps mp;
  make_map(fn, &mp.x, d_in[0], D_, S_ / 2, 2, 4096, 2048, 2);
  make_map(fn, &mp.out, d_out, D_, S_ / 2, 2, 4096, 2048, 1);
  make_map(fn, &mp.wqkv, d_in[1], 64, D_, 3 * D_ / 64, 3 * D_ * 2, 128, 2);
  make_map(fn, &mp.wo, d_in[2], 64, D_, D_ / 64, D_ * 2, 128, 2);
  make_map(fn, &mp.w1, d_in[4], 64, D_, F_ / 64, F_ * 2, 128, 2);
  make_map(fn, &mp.w3, d_in[5], 64, D_, F_ / 64, F_ * 2, 128, 2);
  make_map(fn, &mp.w1s, d_in[4], 64, D_, F_ / 64, F_ * 2, 128, 1);
  make_map(fn, &mp.w3s, d_in[5], 64, D_, F_ / 64, F_ * 2, 128, 1);
  make_map(fn, &mp.w2, d_in[6], 64, F_, D_ / 64, D_ * 2, 128, 2);
  make_map(fn, &mp.wmod, d_in[8], 256, D_, 24, 6 * D_ * 2, 512, 1, 256);
  fused_kernel<<<132, 384, SMEM_BYTES>>>((const bf16*)d_in[7], (const bf16*)d_in[8], gs, by_sm, mp);
}
```

```cpp
#include <cuda_runtime.h>
#include <cuda_bf16.h>
#include <cuda.h>
#include <stdint.h>

typedef __nv_bfloat16 bf16;

namespace {

constexpr int S_ = 2048, D_ = 1024, F_ = 3584;
constexpr int BLK = 16384;
constexpr int HALF = 8192;
constexpr int RING = 196608;
constexpr int STG = RING;
constexpr int MISC = RING + 2 * BLK;
constexpr int SMEM_BYTES = MISC + 3072;
constexpr int B_FULL4 = 0, B_EMPTY4 = 32, B_FULL6 = 64, B_EMPTY6 = 112, B_RDY = 160, B_FREE = 176, B_LAG = 192, B_X = 208, B_MOD = 224, B_HALO = 232, B_HH = 256, B_ALL = 272, B_HH2 = 288, ZERO = 296;
constexpr int MODV = 512;
constexpr int RED_OFF = 0;
constexpr float SCL = 0.17677669529663687f * 1.4426950408889634f;
constexpr int U_HH = 64;
constexpr int FS = 8;
constexpr int NPIECE = 4, PSLEEP = 300;
constexpr int XSLEEP = 4000, HSLEEP = 400;
constexpr uint32_t XDELAY = 2000;
constexpr uint32_t B1P = 3500, B1D = 900, B1P2 = 3200;
constexpr int WOLAG = 2, TAILLAG = 5;

struct Maps { CUtensorMap x, out, wqkv, wo, w1, w3, w1s, w3s, w2, wmod; };

struct Scratch {
  uint4 h[16 * 16 * 1024];
  uint4 o[16 * 16 * 1024];
  uint4 hh[16 * 56 * 1024];
  uint4 x1[128 * 8 * 256];
  uint4 stat[2 * 16 * 8 * 128];
  uint4 halo[16 * 8 * 2 * 512];
  uint2 modp[8 * 2 * 4 * 128];
  uint2 modv[4 * 1024];
  uint32_t flag[16 * 128 * FS];
  uint32_t epoch[132];
};
__device__ __align__(1024) Scratch g_scratch;

__device__ __forceinline__ void bail() { asm volatile("st.global.u32 [%0], %1;" :: "l"(0ull), "r"(0) : "memory"); }
__device__ __forceinline__ uint32_t smem_u32(const void* p) { return (uint32_t)__cvta_generic_to_shared(p); }
__device__ __forceinline__ void mbar_init(uint32_t bar, uint32_t cnt) { asm volatile("mbarrier.init.shared::cta.b64 [%0], %1;" :: "r"(bar), "r"(cnt) : "memory"); }
__device__ __forceinline__ void mbar_expect_tx(uint32_t bar, uint32_t bytes) { asm volatile("mbarrier.arrive.expect_tx.shared::cta.b64 _, [%0], %1;" :: "r"(bar), "r"(bytes) : "memory"); }
__device__ __forceinline__ void mbar_arrive(uint32_t bar) { asm volatile("mbarrier.arrive.shared::cta.b64 _, [%0];" :: "r"(bar) : "memory"); }
__device__ __forceinline__ void mbar_arrive_cl(uint32_t cl_addr) { asm volatile("mbarrier.arrive.shared::cluster.b64 _, [%0];" :: "r"(cl_addr) : "memory"); }
__device__ __forceinline__ uint32_t mapa(uint32_t addr, uint32_t cta) { uint32_t r; asm("mapa.shared::cluster.u32 %0, %1, %2;" : "=r"(r) : "r"(addr), "r"(cta)); return r; }
__device__ __forceinline__ void mbar_wait(uint32_t bar, uint32_t parity) {
  asm volatile("{\n.reg .pred p;\n.reg .b32 n;\n.reg .b64 z;\nmov.b32 n, 0;\nmov.b64 z, 0;\n"
               "W: add.u32 n, n, 1;\nsetp.gt.u32 p, n, 0x400000;\n@p st.global.u32 [z], n;\n"
               "mbarrier.try_wait.parity.shared::cta.b64 p, [%0], %1;\n@!p bra W;\n}" :: "r"(bar), "r"(parity) : "memory");
}
__device__ __forceinline__ void tma_3d(uint32_t dst, const CUtensorMap* m, uint32_t bar, int c0, int c1, int c2) {
  asm volatile("cp.async.bulk.tensor.3d.shared::cluster.global.mbarrier::complete_tx::bytes [%0], [%1, {%3, %4, %5}], [%2];" :: "r"(dst), "l"(m), "r"(bar), "r"(c0), "r"(c1), "r"(c2) : "memory");
}
__device__ __forceinline__ void tma_store_3d(const CUtensorMap* m, uint32_t src, int c0, int c1, int c2) {
  asm volatile("cp.async.bulk.tensor.3d.global.shared::cta.bulk_group [%0, {%2, %3, %4}], [%1];" :: "l"(m), "r"(src), "r"(c0), "r"(c1), "r"(c2) : "memory");
}
__device__ __forceinline__ void bulk_ld(uint32_t dst, const void* src, uint32_t bytes, uint32_t bar) {
  asm volatile("cp.async.bulk.shared::cluster.global.mbarrier::complete_tx::bytes [%0], [%1], %2, [%3];" :: "r"(dst), "l"(src), "r"(bytes), "r"(bar) : "memory");
}
__device__ __forceinline__ void bulk_ld_mc(uint32_t dst, const void* src, uint32_t bytes, uint32_t bar) {
  asm volatile("cp.async.bulk.shared::cluster.global.mbarrier::complete_tx::bytes.multicast::cluster [%0], [%1], %2, [%3], %4;" :: "r"(dst), "l"(src), "r"(bytes), "r"(bar), "h"((uint16_t)3) : "memory");
}
__device__ __forceinline__ void bulk_push(uint32_t dst_cl, uint32_t src, uint32_t bytes, uint32_t bar_cl) {
  asm volatile("cp.async.bulk.shared::cluster.shared::cta.mbarrier::complete_tx::bytes [%0], [%1], %2, [%3];" :: "r"(dst_cl), "r"(src), "r"(bytes), "r"(bar_cl) : "memory");
}
__device__ __forceinline__ void bulk_st(void* dst, uint32_t src, uint32_t bytes) {
  asm volatile("cp.async.bulk.global.shared::cta.bulk_group [%0], [%1], %2;" :: "l"(dst), "r"(src), "r"(bytes) : "memory");
}
__device__ __forceinline__ void bulk_commit() { asm volatile("cp.async.bulk.commit_group;" ::: "memory"); }
__device__ __forceinline__ void bulk_wait_read() { asm volatile("cp.async.bulk.wait_group.read 0;" ::: "memory"); }
__device__ __forceinline__ void bulk_wait_all() { asm volatile("cp.async.bulk.wait_group 0;" ::: "memory"); }
__device__ __forceinline__ void fence_async_global() { asm volatile("fence.proxy.async.global;" ::: "memory"); }
__device__ __forceinline__ void fence_async_smem() { asm volatile("fence.proxy.async.shared::cta;" ::: "memory"); }
__device__ __forceinline__ void wg_arrive() { asm volatile("wgmma.fence.sync.aligned;" ::: "memory"); }
__device__ __forceinline__ void wg_commit() { asm volatile("wgmma.commit_group.sync.aligned;" ::: "memory"); }
template <int N> __device__ __forceinline__ void wg_wait() { asm volatile("wgmma.wait_group.sync.aligned %0;" :: "n"(N) : "memory"); }
__device__ __forceinline__ void cl_arrive_relaxed() { asm volatile("barrier.cluster.arrive.relaxed.aligned;" ::: "memory"); }
__device__ __forceinline__ void cl_wait() { asm volatile("barrier.cluster.wait.acquire.aligned;" ::: "memory"); }
__device__ __forceinline__ bool elect() { uint32_t p; asm volatile("{\n.reg .pred p;\nelect.sync _|p, 0xffffffff;\nselp.u32 %0, 1, 0, p;\n}" : "=r"(p)); return p; }
__device__ __forceinline__ void named_bar(int id, int n) { asm volatile("bar.sync %0, %1;" :: "r"(id), "r"(n) : "memory"); }
__device__ __forceinline__ uint32_t pack2(float lo, float hi) { uint32_t r; asm("cvt.rn.bf16x2.f32 %0, %1, %2;" : "=r"(r) : "f"(hi), "f"(lo)); return r; }
__device__ __forceinline__ float bf_lo(uint32_t w) { return __uint_as_float(w << 16); }
__device__ __forceinline__ float bf_hi(uint32_t w) { return __uint_as_float(w & 0xffff0000u); }
__device__ __forceinline__ float bf_round(float v) { return __bfloat162float(__float2bfloat16_rn(v)); }
__device__ __forceinline__ void stsm4(uint32_t addr, uint32_t a, uint32_t b, uint32_t c, uint32_t d) {
  asm volatile("stmatrix.sync.aligned.m8n8.x4.shared.b16 [%0], {%1, %2, %3, %4};" :: "r"(addr), "r"(a), "r"(b), "r"(c), "r"(d) : "memory");
}
__device__ __forceinline__ void ldsm4(uint32_t addr, uint32_t& a, uint32_t& b, uint32_t& c, uint32_t& d) {
  asm volatile("ldmatrix.sync.aligned.m8n8.x4.shared.b16 {%0, %1, %2, %3}, [%4];" : "=r"(a), "=r"(b), "=r"(c), "=r"(d) : "r"(addr) : "memory");
}
__device__ __forceinline__ uint32_t movm(uint32_t a) { uint32_t r; asm volatile("movmatrix.sync.aligned.m8n8.trans.b16 %0, %1;" : "=r"(r) : "r"(a)); return r; }
__device__ __forceinline__ void mma16(float (&d)[4], uint32_t a0, uint32_t a1, uint32_t a2, uint32_t a3, uint32_t b0, uint32_t b1) {
  asm("mma.sync.aligned.m16n8k16.row.col.f32.bf16.bf16.f32 {%0,%1,%2,%3}, {%4,%5,%6,%7}, {%8,%9}, {%0,%1,%2,%3};"
               : "+f"(d[0]), "+f"(d[1]), "+f"(d[2]), "+f"(d[3]) : "r"(a0), "r"(a1), "r"(a2), "r"(a3), "r"(b0), "r"(b1));
}
__device__ __forceinline__ void mma16z(float (&d)[4], uint32_t a0, uint32_t a1, uint32_t a2, uint32_t a3, uint32_t b0, uint32_t b1) {
  asm("mma.sync.aligned.m16n8k16.row.col.f32.bf16.bf16.f32 {%0,%1,%2,%3}, {%4,%5,%6,%7}, {%8,%9}, {%10,%10,%10,%10};"
      : "=f"(d[0]), "=f"(d[1]), "=f"(d[2]), "=f"(d[3]) : "r"(a0), "r"(a1), "r"(a2), "r"(a3), "r"(b0), "r"(b1), "f"(0.f));
}
__device__ __forceinline__ void mma8z(float (&d)[4], uint32_t a0, uint32_t a1, uint32_t b0) {
  asm("mma.sync.aligned.m16n8k8.row.col.f32.bf16.bf16.f32 {%0,%1,%2,%3}, {%4,%5}, {%6}, {%7,%7,%7,%7};"
      : "=f"(d[0]), "=f"(d[1]), "=f"(d[2]), "=f"(d[3]) : "r"(a0), "r"(a1), "r"(b0), "f"(0.f));
}
__device__ __forceinline__ void mma8(float (&d)[4], uint32_t a0, uint32_t a1, uint32_t b0) {
  asm("mma.sync.aligned.m16n8k8.row.col.f32.bf16.bf16.f32 {%0,%1,%2,%3}, {%4,%5}, {%6}, {%0,%1,%2,%3};"
               : "+f"(d[0]), "+f"(d[1]), "+f"(d[2]), "+f"(d[3]) : "r"(a0), "r"(a1), "r"(b0));
}
__device__ __forceinline__ uint4 lds128(uint32_t a) { uint4 v; asm volatile("ld.shared.v4.u32 {%0,%1,%2,%3}, [%4];" : "=r"(v.x), "=r"(v.y), "=r"(v.z), "=r"(v.w) : "r"(a) : "memory"); return v; }
__device__ __forceinline__ void sts128(uint32_t a, uint32_t x, uint32_t y, uint32_t z, uint32_t w) { asm volatile("st.shared.v4.u32 [%0], {%1,%2,%3,%4};" :: "r"(a), "r"(x), "r"(y), "r"(z), "r"(w) : "memory"); }
__device__ __forceinline__ float lds32f(uint32_t a) { float v; asm volatile("ld.shared.f32 %0, [%1];" : "=f"(v) : "r"(a) : "memory"); return v; }
__device__ __forceinline__ void sts16(uint32_t a, bf16 v) { asm volatile("st.shared.b16 [%0], %1;" :: "r"(a), "h"(__bfloat16_as_ushort(v)) : "memory"); }
__device__ __forceinline__ uint4 ldg_nc(const void* p) { uint4 v; asm volatile("ld.global.nc.L1::no_allocate.v4.u32 {%0,%1,%2,%3}, [%4];" : "=r"(v.x), "=r"(v.y), "=r"(v.z), "=r"(v.w) : "l"(p)); return v; }
__device__ __forceinline__ uint4 ld_rlx4(const uint4* p) {
  unsigned long long a, b; asm volatile("ld.relaxed.gpu.global.v2.b64 {%0,%1}, [%2];" : "=l"(a), "=l"(b) : "l"(p) : "memory");
  return make_uint4((uint32_t)a, (uint32_t)(a >> 32), (uint32_t)b, (uint32_t)(b >> 32));
}
__device__ __forceinline__ uint2 ld_rlx2(const uint2* p) { unsigned long long a; asm volatile("ld.relaxed.gpu.global.b64 %0, [%1];" : "=l"(a) : "l"(p) : "memory"); return make_uint2((uint32_t)a, (uint32_t)(a >> 32)); }
__device__ __forceinline__ void st_rlx4(uint4* p, uint32_t x, uint32_t y, uint32_t z, uint32_t w) {
  asm volatile("st.relaxed.gpu.global.v2.b64 [%0], {%1,%2};" :: "l"(p), "l"((unsigned long long)x | ((unsigned long long)y << 32)), "l"((unsigned long long)z | ((unsigned long long)w << 32)) : "memory");
}
__device__ __forceinline__ void st_rlx2(uint2* p, uint32_t x, uint32_t y) { asm volatile("st.relaxed.gpu.global.b64 [%0], %1;" :: "l"(p), "l"((unsigned long long)x | ((unsigned long long)y << 32)) : "memory"); }
__device__ __forceinline__ void st_release(uint32_t* p, uint32_t v) { asm volatile("st.release.gpu.global.u32 [%0], %1;" :: "l"(p), "r"(v) : "memory"); }
__device__ __forceinline__ uint32_t ld_acquire(const uint32_t* p) { uint32_t v; asm volatile("ld.acquire.gpu.global.u32 %0, [%1];" : "=r"(v) : "l"(p) : "memory"); return v; }
__device__ __forceinline__ void prefetch_map(const CUtensorMap* m) { asm volatile("prefetch.tensormap [%0];" :: "l"(m) : "memory"); }
__device__ __forceinline__ float rcp(float x) { float r; asm("rcp.approx.ftz.f32 %0, %1;" : "=f"(r) : "f"(x)); return r; }
__device__ __forceinline__ float ex2(float x) { float r; asm("ex2.approx.ftz.f32 %0, %1;" : "=f"(r) : "f"(x)); return r; }
__device__ __forceinline__ float tanh_fast(float x) { float r; asm("tanh.approx.f32 %0, %1;" : "=f"(r) : "f"(x)); return r; }
#define SPIN_GUARD(n) if (++(n) > (1u << 24)) bail()

__device__ __forceinline__ void wgmma_n128(float (&d)[64], uint64_t da, uint64_t db) {
  asm volatile("wgmma.mma_async.sync.aligned.m64n128k16.f32.bf16.bf16 "
    "{%0, %1, %2, %3, %4, %5, %6, %7, %8, %9, %10, %11, %12, %13, %14, %15, %16, %17, %18, %19, %20, %21, %22, %23, %24, %25, %26, %27, %28, %29, %30, %31, %32, %33, %34, %35, %36, %37, %38, %39, %40, %41, %42, %43, %44, %45, %46, %47, %48, %49, %50, %51, %52, %53, %54, %55, %56, %57, %58, %59, %60, %61, %62, %63}, "
    "%64, %65, 1, 1, 1, 0, 1;\n"
    : "+f"(d[0]), "+f"(d[1]), "+f"(d[2]), "+f"(d[3]), "+f"(d[4]), "+f"(d[5]), "+f"(d[6]), "+f"(d[7]), "+f"(d[8]), "+f"(d[9]), "+f"(d[10]), "+f"(d[11]), "+f"(d[12]), "+f"(d[13]), "+f"(d[14]), "+f"(d[15]), "+f"(d[16]), "+f"(d[17]), "+f"(d[18]), "+f"(d[19]), "+f"(d[20]), "+f"(d[21]), "+f"(d[22]), "+f"(d[23]), "+f"(d[24]), "+f"(d[25]), "+f"(d[26]), "+f"(d[27]), "+f"(d[28]), "+f"(d[29]), "+f"(d[30]), "+f"(d[31]), "+f"(d[32]), "+f"(d[33]), "+f"(d[34]), "+f"(d[35]), "+f"(d[36]), "+f"(d[37]), "+f"(d[38]), "+f"(d[39]), "+f"(d[40]), "+f"(d[41]), "+f"(d[42]), "+f"(d[43]), "+f"(d[44]), "+f"(d[45]), "+f"(d[46]), "+f"(d[47]), "+f"(d[48]), "+f"(d[49]), "+f"(d[50]), "+f"(d[51]), "+f"(d[52]), "+f"(d[53]), "+f"(d[54]), "+f"(d[55]), "+f"(d[56]), "+f"(d[57]), "+f"(d[58]), "+f"(d[59]), "+f"(d[60]), "+f"(d[61]), "+f"(d[62]), "+f"(d[63])
    : "l"(da), "l"(db));
}
__device__ __forceinline__ void wgmma_n128_first(float (&d)[64], uint64_t da, uint64_t db) {
  asm volatile("wgmma.mma_async.sync.aligned.m64n128k16.f32.bf16.bf16 "
    "{%0, %1, %2, %3, %4, %5, %6, %7, %8, %9, %10, %11, %12, %13, %14, %15, %16, %17, %18, %19, %20, %21, %22, %23, %24, %25, %26, %27, %28, %29, %30, %31, %32, %33, %34, %35, %36, %37, %38, %39, %40, %41, %42, %43, %44, %45, %46, %47, %48, %49, %50, %51, %52, %53, %54, %55, %56, %57, %58, %59, %60, %61, %62, %63}, "
    "%64, %65, 0, 1, 1, 0, 1;\n"
    : "=f"(d[0]), "=f"(d[1]), "=f"(d[2]), "=f"(d[3]), "=f"(d[4]), "=f"(d[5]), "=f"(d[6]), "=f"(d[7]), "=f"(d[8]), "=f"(d[9]), "=f"(d[10]), "=f"(d[11]), "=f"(d[12]), "=f"(d[13]), "=f"(d[14]), "=f"(d[15]), "=f"(d[16]), "=f"(d[17]), "=f"(d[18]), "=f"(d[19]), "=f"(d[20]), "=f"(d[21]), "=f"(d[22]), "=f"(d[23]), "=f"(d[24]), "=f"(d[25]), "=f"(d[26]), "=f"(d[27]), "=f"(d[28]), "=f"(d[29]), "=f"(d[30]), "=f"(d[31]), "=f"(d[32]), "=f"(d[33]), "=f"(d[34]), "=f"(d[35]), "=f"(d[36]), "=f"(d[37]), "=f"(d[38]), "=f"(d[39]), "=f"(d[40]), "=f"(d[41]), "=f"(d[42]), "=f"(d[43]), "=f"(d[44]), "=f"(d[45]), "=f"(d[46]), "=f"(d[47]), "=f"(d[48]), "=f"(d[49]), "=f"(d[50]), "=f"(d[51]), "=f"(d[52]), "=f"(d[53]), "=f"(d[54]), "=f"(d[55]), "=f"(d[56]), "=f"(d[57]), "=f"(d[58]), "=f"(d[59]), "=f"(d[60]), "=f"(d[61]), "=f"(d[62]), "=f"(d[63])
    : "l"(da), "l"(db));
}
__device__ __forceinline__ void wgmma_n256(float (&d)[128], uint64_t da, uint64_t db) {
  asm volatile("wgmma.mma_async.sync.aligned.m64n256k16.f32.bf16.bf16 "
    "{%0, %1, %2, %3, %4, %5, %6, %7, %8, %9, %10, %11, %12, %13, %14, %15, %16, %17, %18, %19, %20, %21, %22, %23, %24, %25, %26, %27, %28, %29, %30, %31, %32, %33, %34, %35, %36, %37, %38, %39, %40, %41, %42, %43, %44, %45, %46, %47, %48, %49, %50, %51, %52, %53, %54, %55, %56, %57, %58, %59, %60, %61, %62, %63, %64, %65, %66, %67, %68, %69, %70, %71, %72, %73, %74, %75, %76, %77, %78, %79, %80, %81, %82, %83, %84, %85, %86, %87, %88, %89, %90, %91, %92, %93, %94, %95, %96, %97, %98, %99, %100, %101, %102, %103, %104, %105, %106, %107, %108, %109, %110, %111, %112, %113, %114, %115, %116, %117, %118, %119, %120, %121, %122, %123, %124, %125, %126, %127}, "
    "%128, %129, 1, 1, 1, 0, 1;\n"
    : "+f"(d[0]), "+f"(d[1]), "+f"(d[2]), "+f"(d[3]), "+f"(d[4]), "+f"(d[5]), "+f"(d[6]), "+f"(d[7]), "+f"(d[8]), "+f"(d[9]), "+f"(d[10]), "+f"(d[11]), "+f"(d[12]), "+f"(d[13]), "+f"(d[14]), "+f"(d[15]), "+f"(d[16]), "+f"(d[17]), "+f"(d[18]), "+f"(d[19]), "+f"(d[20]), "+f"(d[21]), "+f"(d[22]), "+f"(d[23]), "+f"(d[24]), "+f"(d[25]), "+f"(d[26]), "+f"(d[27]), "+f"(d[28]), "+f"(d[29]), "+f"(d[30]), "+f"(d[31]), "+f"(d[32]), "+f"(d[33]), "+f"(d[34]), "+f"(d[35]), "+f"(d[36]), "+f"(d[37]), "+f"(d[38]), "+f"(d[39]), "+f"(d[40]), "+f"(d[41]), "+f"(d[42]), "+f"(d[43]), "+f"(d[44]), "+f"(d[45]), "+f"(d[46]), "+f"(d[47]), "+f"(d[48]), "+f"(d[49]), "+f"(d[50]), "+f"(d[51]), "+f"(d[52]), "+f"(d[53]), "+f"(d[54]), "+f"(d[55]), "+f"(d[56]), "+f"(d[57]), "+f"(d[58]), "+f"(d[59]), "+f"(d[60]), "+f"(d[61]), "+f"(d[62]), "+f"(d[63]), "+f"(d[64]), "+f"(d[65]), "+f"(d[66]), "+f"(d[67]), "+f"(d[68]), "+f"(d[69]), "+f"(d[70]), "+f"(d[71]), "+f"(d[72]), "+f"(d[73]), "+f"(d[74]), "+f"(d[75]), "+f"(d[76]), "+f"(d[77]), "+f"(d[78]), "+f"(d[79]), "+f"(d[80]), "+f"(d[81]), "+f"(d[82]), "+f"(d[83]), "+f"(d[84]), "+f"(d[85]), "+f"(d[86]), "+f"(d[87]), "+f"(d[88]), "+f"(d[89]), "+f"(d[90]), "+f"(d[91]), "+f"(d[92]), "+f"(d[93]), "+f"(d[94]), "+f"(d[95]), "+f"(d[96]), "+f"(d[97]), "+f"(d[98]), "+f"(d[99]), "+f"(d[100]), "+f"(d[101]), "+f"(d[102]), "+f"(d[103]), "+f"(d[104]), "+f"(d[105]), "+f"(d[106]), "+f"(d[107]), "+f"(d[108]), "+f"(d[109]), "+f"(d[110]), "+f"(d[111]), "+f"(d[112]), "+f"(d[113]), "+f"(d[114]), "+f"(d[115]), "+f"(d[116]), "+f"(d[117]), "+f"(d[118]), "+f"(d[119]), "+f"(d[120]), "+f"(d[121]), "+f"(d[122]), "+f"(d[123]), "+f"(d[124]), "+f"(d[125]), "+f"(d[126]), "+f"(d[127])
    : "l"(da), "l"(db));
}
__device__ __forceinline__ void wgmma_n256_first(float (&d)[128], uint64_t da, uint64_t db) {
  asm volatile("wgmma.mma_async.sync.aligned.m64n256k16.f32.bf16.bf16 "
    "{%0, %1, %2, %3, %4, %5, %6, %7, %8, %9, %10, %11, %12, %13, %14, %15, %16, %17, %18, %19, %20, %21, %22, %23, %24, %25, %26, %27, %28, %29, %30, %31, %32, %33, %34, %35, %36, %37, %38, %39, %40, %41, %42, %43, %44, %45, %46, %47, %48, %49, %50, %51, %52, %53, %54, %55, %56, %57, %58, %59, %60, %61, %62, %63, %64, %65, %66, %67, %68, %69, %70, %71, %72, %73, %74, %75, %76, %77, %78, %79, %80, %81, %82, %83, %84, %85, %86, %87, %88, %89, %90, %91, %92, %93, %94, %95, %96, %97, %98, %99, %100, %101, %102, %103, %104, %105, %106, %107, %108, %109, %110, %111, %112, %113, %114, %115, %116, %117, %118, %119, %120, %121, %122, %123, %124, %125, %126, %127}, "
    "%128, %129, 0, 1, 1, 0, 1;\n"
    : "=f"(d[0]), "=f"(d[1]), "=f"(d[2]), "=f"(d[3]), "=f"(d[4]), "=f"(d[5]), "=f"(d[6]), "=f"(d[7]), "=f"(d[8]), "=f"(d[9]), "=f"(d[10]), "=f"(d[11]), "=f"(d[12]), "=f"(d[13]), "=f"(d[14]), "=f"(d[15]), "=f"(d[16]), "=f"(d[17]), "=f"(d[18]), "=f"(d[19]), "=f"(d[20]), "=f"(d[21]), "=f"(d[22]), "=f"(d[23]), "=f"(d[24]), "=f"(d[25]), "=f"(d[26]), "=f"(d[27]), "=f"(d[28]), "=f"(d[29]), "=f"(d[30]), "=f"(d[31]), "=f"(d[32]), "=f"(d[33]), "=f"(d[34]), "=f"(d[35]), "=f"(d[36]), "=f"(d[37]), "=f"(d[38]), "=f"(d[39]), "=f"(d[40]), "=f"(d[41]), "=f"(d[42]), "=f"(d[43]), "=f"(d[44]), "=f"(d[45]), "=f"(d[46]), "=f"(d[47]), "=f"(d[48]), "=f"(d[49]), "=f"(d[50]), "=f"(d[51]), "=f"(d[52]), "=f"(d[53]), "=f"(d[54]), "=f"(d[55]), "=f"(d[56]), "=f"(d[57]), "=f"(d[58]), "=f"(d[59]), "=f"(d[60]), "=f"(d[61]), "=f"(d[62]), "=f"(d[63]), "=f"(d[64]), "=f"(d[65]), "=f"(d[66]), "=f"(d[67]), "=f"(d[68]), "=f"(d[69]), "=f"(d[70]), "=f"(d[71]), "=f"(d[72]), "=f"(d[73]), "=f"(d[74]), "=f"(d[75]), "=f"(d[76]), "=f"(d[77]), "=f"(d[78]), "=f"(d[79]), "=f"(d[80]), "=f"(d[81]), "=f"(d[82]), "=f"(d[83]), "=f"(d[84]), "=f"(d[85]), "=f"(d[86]), "=f"(d[87]), "=f"(d[88]), "=f"(d[89]), "=f"(d[90]), "=f"(d[91]), "=f"(d[92]), "=f"(d[93]), "=f"(d[94]), "=f"(d[95]), "=f"(d[96]), "=f"(d[97]), "=f"(d[98]), "=f"(d[99]), "=f"(d[100]), "=f"(d[101]), "=f"(d[102]), "=f"(d[103]), "=f"(d[104]), "=f"(d[105]), "=f"(d[106]), "=f"(d[107]), "=f"(d[108]), "=f"(d[109]), "=f"(d[110]), "=f"(d[111]), "=f"(d[112]), "=f"(d[113]), "=f"(d[114]), "=f"(d[115]), "=f"(d[116]), "=f"(d[117]), "=f"(d[118]), "=f"(d[119]), "=f"(d[120]), "=f"(d[121]), "=f"(d[122]), "=f"(d[123]), "=f"(d[124]), "=f"(d[125]), "=f"(d[126]), "=f"(d[127])
    : "l"(da), "l"(db));
}

template <int N> struct WG;
#define DEF_WG(N) template <> struct WG<N> { \
  static __device__ __forceinline__ void mma(float (&d)[N / 2], uint64_t a, uint64_t b) { wgmma_n##N(d, a, b); } \
  static __device__ __forceinline__ void first(float (&d)[N / 2], uint64_t a, uint64_t b) { wgmma_n##N##_first(d, a, b); } };
DEF_WG(128) DEF_WG(256)

constexpr uint64_t DESC_A = (1ull << 62) | ((uint64_t)(1024 >> 4) << 32) | (1ull << 16);
constexpr uint64_t DESC_B = (1ull << 62) | ((uint64_t)(1024 >> 4) << 32) | ((uint64_t)(8192 >> 4) << 16);

struct Ring { int s; uint32_t ph; int wrap; };
template <int NS> __device__ __forceinline__ void ring_next(Ring& r) { r.s = (r.s + 1 == NS) ? 0 : r.s + 1; if (r.s == r.wrap) r.ph ^= 1; }

__device__ __forceinline__ int own_order(int it, int j) {
  return it < 2 ? 2 * j + it : it < 4 ? 2 * (j ^ 1) + it - 2 : ((j >> 1) * 4 + 2 * it - (it < 10 ? 4 : 15)) & 15;
}

template <int V> struct IC { static constexpr int v = V; };
template <int I, int E, class F> __device__ __forceinline__ void static_for(F&& f) { if constexpr (I < E) { f(IC<I>{}); static_for<I + 1, E>(f); } }

template <int N, int NS, int PRE, int LAG, class Pre, class Mid, class Last>
__device__ __forceinline__ void mainloop(float (&acc)[N / 2], int nkb, bool own, Ring& r, uint32_t sb, int wg, int lane, uint32_t rel_base, Pre pre, Mid mid, Last last) {
  constexpr int SLOT = RING / NS;
  const uint32_t full = sb + MISC + (NS == 4 ? B_FULL4 : B_FULL6);
  const uint32_t rel = rel_base + (NS == 4 ? B_EMPTY4 : B_EMPTY6);
  const uint32_t s0 = (sb & 0x3FFFF) >> 4, a0 = s0 + wg * (HALF >> 4);
  int ps;
  auto issue = [&](int it, bool first) {
    const uint64_t da = DESC_A | (a0 + ((own && it < 2) ? (STG + it * BLK) >> 4 : r.s * (SLOT >> 4))), db = DESC_B | (s0 + r.s * (SLOT >> 4) + (BLK >> 4));
    mbar_wait(full + r.s * 8, r.ph);
    wg_arrive();
    if (first) WG<N>::first(acc, da, db); else WG<N>::mma(acc, da, db);
#pragma unroll
    for (int k = 1; k < 4; k++) WG<N>::mma(acc, da + k * 2, db + k * 128);
    wg_commit();
  };
  auto retire = [&](int it) {
    wg_wait<1>();
    if (lane < 2) mbar_arrive_cl(rel + ps * 8);
    ps = r.s;
    ring_next<NS>(r);
  };
  issue(0, true);
  ps = r.s;
  ring_next<NS>(r);
  static_for<1, PRE + 1>([&](auto ic) { issue(ic.v, false); pre(ic); retire(ic.v); });
#pragma unroll 1
  for (int it = PRE + 1; it < nkb; it++) {
    if (LAG && it == nkb - LAG && wg == 1) mbar_wait(sb + MISC + B_LAG, WOLAG && !own);
    issue(it, false); mid(it); retire(it);
  }
  last();
  wg_wait<0>();
  if (lane < 2) mbar_arrive_cl(rel + ps * 8);
}

__device__ __forceinline__ void ln_publish(const float (&v)[64], uint4* st, int j, int row0, int lane, uint32_t ep) {
  float s0 = 0, s1 = 0, s2 = 0, s3 = 0, q0 = 0, q1 = 0, q2 = 0, q3 = 0;
#pragma unroll
  for (int i = 0; i < 16; i++) {
    s0 += v[4 * i]; s1 += v[4 * i + 1]; s2 += v[4 * i + 2]; s3 += v[4 * i + 3];
    q0 = fmaf(v[4 * i], v[4 * i], q0); q1 = fmaf(v[4 * i + 1], v[4 * i + 1], q1); q2 = fmaf(v[4 * i + 2], v[4 * i + 2], q2); q3 = fmaf(v[4 * i + 3], v[4 * i + 3], q3);
  }
  s0 += s1; s2 += s3; q0 += q1; q2 += q3;
  const bool odd = lane & 1;
  float s = (odd ? s2 : s0) + __shfl_xor_sync(~0u, odd ? s0 : s2, 1), q = (odd ? q2 : q0) + __shfl_xor_sync(~0u, odd ? q0 : q2, 1);
  s += __shfl_xor_sync(~0u, s, 2); q += __shfl_xor_sync(~0u, q, 2);
  if ((lane & 3) < 2) st_rlx4(st + j * 128 + row0 + (lane & 1) * 8, __float_as_uint(s), ep, __float_as_uint(q), ep);
}
__device__ __forceinline__ void ln_gather(const uint4* st, int row0, int lane, uint32_t ep, float& n0, float& r0, float& n1, float& r1, bool rnd) {
  const uint4* p = st + (lane & 2) * 256 + row0 + (lane & 1) * 8;
  uint4 a, b, c, d; uint32_t n = 0;
  while (true) {
    a = ld_rlx4(p); b = ld_rlx4(p + 128); c = ld_rlx4(p + 256); d = ld_rlx4(p + 384);
    if (a.y == ep && a.w == ep && b.y == ep && b.w == ep && c.y == ep && c.w == ep && d.y == ep && d.w == ep) break;
    SPIN_GUARD(n);
  }
  __syncwarp();
  float s = (__uint_as_float(a.x) + __uint_as_float(b.x)) + (__uint_as_float(c.x) + __uint_as_float(d.x));
  float q = (__uint_as_float(a.z) + __uint_as_float(b.z)) + (__uint_as_float(c.z) + __uint_as_float(d.z));
  s += __shfl_xor_sync(~0u, s, 2); q += __shfl_xor_sync(~0u, q, 2);
  s *= 1.f / 1024;
  const float var = fmaxf(fmaf(-s, s, q * (1.f / 1024)), 0.f);
  float r;
  if (rnd) {
    float sd; asm("sqrt.approx.f32 %0, %1;" : "=f"(sd) : "f"(bf_round(bf_round(var) + 1e-5f)));
    r = rcp(bf_round(sd)); s = bf_round(s);
  } else r = rsqrtf(var + 1e-5f);
  const float nn = -s * r;
  const float ro = __shfl_xor_sync(~0u, r, 1), no = __shfl_xor_sync(~0u, nn, 1);
  const bool odd = lane & 1;
  r0 = odd ? ro : r; n0 = odd ? no : nn; r1 = odd ? r : ro; n1 = odd ? nn : no;
}
__device__ __forceinline__ void load_vec(uint32_t* w, uint32_t sb, int sec, int b, int lane) {
#pragma unroll
  for (int q = 0; q < 2; q++) { uint4 t = lds128(sb + MISC + MODV + sec * 256 + (lane & 3) * 64 + b * 32 + q * 16); w[4 * q] = t.x; w[4 * q + 1] = t.y; w[4 * q + 2] = t.z; w[4 * q + 3] = t.w; }
}
__device__ __forceinline__ void stage_done(uint32_t sb, int wg, int b, int lane) {
  fence_async_smem();
  __syncwarp();
  if (lane == 0) mbar_arrive(sb + MISC + B_RDY + b * 8);
}
__device__ __forceinline__ uint32_t hfma2(uint32_t a, uint32_t b, uint32_t c) { uint32_t r; asm("fma.rn.bf16x2 %0, %1, %2, %3;" : "=r"(r) : "r"(a), "r"(b), "r"(c)); return r; }
__device__ __forceinline__ void ln_apply(const float (&v)[64], const uint4* st, int row0, uint32_t ep, uint32_t sb, int sec_shift, int sec_scale, uint32_t stg_row, int wg, int lane) {
  uint32_t sc[16], sh[16];
#pragma unroll
  for (int b = 0; b < 2; b++) { load_vec(sc + 8 * b, sb, sec_scale, b, lane); load_vec(sh + 8 * b, sb, sec_shift, b, lane); }
  float n0, r0, n1, r1;
  ln_gather(st, row0, lane, ep, n0, r0, n1, r1, sec_shift == 0);
#pragma unroll
  for (int i = 0; i < 16; i += 2) {
    if (i == 8) { const float z = lds32f(sb + MISC + ZERO); n0 += z; n1 += z; }
    uint32_t w[4];
#pragma unroll
    for (int u = 0; u < 2; u++) {
      int q = i + u;
      w[2 * u] = hfma2(pack2(fmaf(v[4 * q], r0, n0), fmaf(v[4 * q + 1], r0, n0)), sc[q], sh[q]);
      w[2 * u + 1] = hfma2(pack2(fmaf(v[4 * q + 2], r1, n1), fmaf(v[4 * q + 3], r1, n1)), sc[q], sh[q]);
    }
    stsm4(stg_row + (i >> 3) * BLK + ((((i & 7) + (lane >> 4)) ^ (lane & 7)) << 4), w[0], w[1], w[2], w[3]);
    if ((i & 7) == 6) { stage_done(sb, wg, i >> 3, lane); }
  }
}
__device__ __forceinline__ uint32_t hmul2(uint32_t a, uint32_t b) { uint32_t r; asm("mul.rn.bf16x2 %0, %1, %2;" : "=r"(r) : "r"(a), "r"(b)); return r; }
__device__ __forceinline__ uint32_t silu_mul2(uint32_t g, uint32_t u) {
  const uint32_t h = hmul2(g, 0x3f003f00u);
  const float h0 = bf_lo(h), h1 = bf_hi(h);
  return hmul2(pack2(fmaf(h0, tanh_fast(h0), h0), fmaf(h1, tanh_fast(h1), h1)), u);
}

__device__ __forceinline__ void gemv_fma(float (&a)[8], uint4 w, float s) {
  a[0] = fmaf(bf_lo(w.x), s, a[0]); a[1] = fmaf(bf_hi(w.x), s, a[1]); a[2] = fmaf(bf_lo(w.y), s, a[2]); a[3] = fmaf(bf_hi(w.y), s, a[3]);
  a[4] = fmaf(bf_lo(w.z), s, a[4]); a[5] = fmaf(bf_hi(w.z), s, a[5]); a[6] = fmaf(bf_lo(w.w), s, a[6]); a[7] = fmaf(bf_hi(w.w), s, a[7]);
}
__device__ __forceinline__ float silu_c(float v) { return bf_round(__fdividef(v, 1.f + __expf(-v))); }
__device__ __forceinline__ float mod_gather(const uint2* p, uint32_t ep) {
  uint2 a, b, c, d; uint32_t n = 0;
  while (true) {
    a = ld_rlx2(p); b = ld_rlx2(p + 128); c = ld_rlx2(p + 256); d = ld_rlx2(p + 384);
    if (a.y == ep && b.y == ep && c.y == ep && d.y == ep) break;
    SPIN_GUARD(n);
  }
  return (__uint_as_float(a.x) + __uint_as_float(b.x)) + (__uint_as_float(c.x) + __uint_as_float(d.x));
}
__device__ __forceinline__ void mod_store(uint32_t sb, int sec, int col, float v) {
  v = bf_round(v);
  if (sec == 1 || sec == 4) v += 1.f;
  sts16(sb + MISC + MODV + sec * 256 + (((col >> 1) & 3) * 16 + (col >> 3)) * 4 + (col & 1) * 2, __float2bfloat16_rn(v));
}

__global__ void __cluster_dims__(2, 1, 1) __launch_bounds__(384, 1)
fused_kernel(const bf16* __restrict__ cvec, const bf16* __restrict__ wmod, Scratch* gs, int by_sm, const __grid_constant__ Maps maps) {
  extern __shared__ __align__(1024) uint8_t smem_raw[];
  const uint32_t sb = smem_u32(smem_raw);
  const int warp = __shfl_sync(~0u, threadIdx.x >> 5, 0), lane = threadIdx.x & 31;
  const int rank = blockIdx.x & 1;
  uint32_t sm; asm volatile("mov.u32 %0, %%smid;" : "=r"(sm));
  const int t = sm >> 1, v = t < 32 ? t : t < 60 ? t + 1 + (((t - 32) * 37) >> 8) : (t - 58) * 8;
  const int cid = !by_sm ? (blockIdx.x >> 1) - 2 : (t & ~1) == 60 ? t - 62 : (v & 1) * 32 + ((v >> 1) & 31);
  const bool extra = cid < 0;
  const int bid = cid * 2 + rank;
  const int m = cid >> 2, j = (cid & 3) * 2 + rank;
  const uint32_t bar = sb + MISC;

  if (warp >= 8) {
    asm volatile("setmaxnreg.dec.sync.aligned.u32 40;");
    if (extra) {
      if (warp == 8) {
        if (lane == 0) { for (int s = 0; s < 6; s++) { mbar_init(bar + B_FULL6 + s * 8, 1); mbar_init(bar + B_EMPTY6 + s * 8, 8); } fence_async_smem(); }
        __syncwarp();
        asm volatile("bar.arrive 2, 288;" ::: "memory");
        __nanosleep(XSLEEP);
#pragma unroll 1
        for (int it = 0, s = 0, par = 1; it < 64; it++) {
          mbar_wait(bar + B_EMPTY6 + s * 8, par);
          if (elect()) { mbar_expect_tx(bar + B_FULL6 + s * 8, 32768); tma_3d(sb + s * 32768, &maps.wmod, bar + B_FULL6 + s * 8, 0, (it & 15) * 64, 12 + (it >> 4) * 4 + bid); }
          if (++s == 6) { s = 0; par ^= 1; }
        }
      }
    } else if (warp < 10) {
      uint32_t s6 = 0, p6 = 1;
      auto next6 = [&]() { if (++s6 == 6) { s6 = 0; p6 ^= 1; } };
      auto drained4 = [&](int q, int late) { if (q < 5) mbar_wait(bar + B_EMPTY4 + (((late ? 0x10332 : 0x32110) >> (4 * q)) & 3) * 8, 1); };
      auto drained6 = [&](int q) { if (q < 3) mbar_wait(bar + B_EMPTY6 + ((0x154 >> (4 * q)) & 7) * 8, q >> 1); };
      auto skip6 = [&]() { mbar_wait(bar + B_EMPTY6 + s6 * 8, p6); if (elect()) mbar_arrive(bar + B_FULL6 + s6 * 8); next6(); };
      if (warp == 8) {
        const uint32_t t_start = clock();
        if (lane == 0) {
          if (sb & 1023) bail();
          for (int b = 0; b < 2; b++) mbar_init(bar + B_X + b * 8, 1);
          for (int s = 0; s < 4; s++) { mbar_init(bar + B_FULL4 + s * 8, 2); mbar_init(bar + B_EMPTY4 + s * 8, 16); }
          for (int s = 0; s < 6; s++) { mbar_init(bar + B_FULL6 + s * 8, 2); mbar_init(bar + B_EMPTY6 + s * 8, 16); }
          for (int b = 0; b < 2; b++) { mbar_init(bar + B_RDY + b * 8, 8); mbar_init(bar + B_FREE + b * 8, 1); mbar_init(bar + B_HH + b * 8, 1); }
          mbar_init(bar + B_MOD, 1); mbar_init(bar + B_LAG, 4); mbar_init(bar + B_HALO, 2); mbar_init(bar + B_ALL, 1); mbar_init(bar + B_HH2, 1);
          asm volatile("st.shared.u32 [%0], 0;" :: "r"(bar + ZERO) : "memory");
          asm volatile("fence.mbarrier_init.release.cluster;" ::: "memory");
          fence_async_smem();
        }
        __syncwarp();
        cl_arrive_relaxed();
        auto wide = [&](int s, int par, const CUtensorMap* m0, int a0, const CUtensorMap* m1, int a1, int kb, bool spaced) {
          const uint32_t full = bar + B_FULL4 + s * 8, d = sb + s * 49152 + BLK;
          mbar_wait(full + 32, par);
          const uint32_t t0 = clock();
          if (elect()) { mbar_expect_tx(full, 2 * BLK); tma_3d(d, m0, full, 0, kb * 64, a0); }
          if (spaced) while ((uint32_t)clock() - t0 < 300) {}
          if (elect()) tma_3d(d + BLK, m1, full, 0, kb * 64, a1);
          if (spaced) while ((uint32_t)clock() - t0 < 600) {}
        };
        auto narrow = [&](const CUtensorMap* m0, int kb) {
          const uint32_t full = bar + B_FULL6 + s6 * 8;
          mbar_wait(full + 48, p6);
          if (elect()) { mbar_expect_tx(full, BLK); tma_3d(sb + s6 * 32768 + BLK, m0, full, 0, kb * 64, 2 * j); }
          next6();
        };
#pragma unroll 1
        for (int it = 0; it < 16; it++) {
          if (it == 0) {
            while ((uint32_t)clock() - t_start < XDELAY) {}
            if (elect()) for (int b = 0; b < 2; b++) { mbar_expect_tx(bar + B_X + b * 8, BLK); tma_3d(sb + STG + b * BLK, &maps.x, bar + B_X + b * 8, j * 128 + b * 64, m * 64, 0); }
            mbar_wait(bar + B_X + 8, 0);
          }
          wide(it & 3, ~(it >> 2) & 1, &maps.wqkv, 16 + 2 * j, &maps.wqkv, 32 + 2 * j, own_order(it, j), it < 4);
        }
#pragma unroll 1
        for (int it = 0; it < 16; it++) { drained4(it, 0); narrow(&maps.wqkv, it); }
#pragma unroll 1
        for (int it = 0; it < 16; it++) narrow(&maps.wo, own_order(it, j));
        skip6();
#pragma unroll 1
        for (int it = 0; it < 48; it++) {
          const int s = (it + 2) & 3, par = ~(it >> 2) & 1;
          drained6(it);
          wide(s, par, &maps.w1, (it & 48) + 2 * j, &maps.w3, (it & 48) + 2 * j, it < 16 ? own_order(it, j) : it & 15, it < 4);
          if (it >= 44) {
            if (it == 44) { mbar_wait(bar + B_FREE, 0); mbar_wait(bar + B_FREE + 8, 0); if (elect()) mbar_expect_tx(bar + B_X, 2 * BLK); }
            if (elect()) bulk_ld(sb + STG + (it - 44) * HALF, gs->x1 + bid * 2048 + (it - 44) * 512, HALF, bar + B_X);
          }
        }
#pragma unroll 1
        for (int it = 0; it < 16; it++) {
          const uint32_t full = bar + B_FULL6 + s6 * 8, d = sb + s6 * 32768 + BLK;
          drained4(it, 1);
          mbar_wait(full + 48, p6);
          if (elect()) { mbar_expect_tx(full, BLK); tma_3d(d, &maps.w1s, full, 0, it * 64, 48 + j); tma_3d(d + HALF, &maps.w3s, full, 0, it * 64, 48 + j); }
          next6();
        }
#pragma unroll 1
        for (int it = 0; it < 56; it++) narrow(&maps.w2, it);
      } else {
        if (lane < 9) prefetch_map(&maps.x + lane);
        const uint32_t ep = gs->epoch[bid + 4] + 1;
        cl_arrive_relaxed(); cl_wait();
        auto plain = [&](uint32_t full, uint32_t empty, int par, uint32_t slot, const uint4* blk) {
          mbar_wait(empty, par);
          if (elect()) { mbar_expect_tx(full, BLK); bulk_ld_mc(slot + rank * HALF, blk + rank * 512, HALF, full); }
        };
        auto plain6 = [&](const uint4* blk) { plain(bar + B_FULL6 + s6 * 8, bar + B_EMPTY6 + s6 * 8, p6, sb + s6 * 32768, blk); next6(); };
        uint32_t ready = 0;
        auto poll = [&](int e) { ready = __ballot_sync(~0u, ld_acquire(gs->flag + (m * 128 + e * 16 + (lane & 14)) * FS) == ep); };
        auto need = [&](int e, uint32_t mask) {
          if ((ready & mask) != mask) {
            uint32_t n = 0;
            do { poll(e); SPIN_GUARD(n); } while ((ready & mask) != mask);
            fence_async_global();
          }
        };
        auto fresh = [&](int e, int it, uint32_t full, uint32_t empty, int par, uint32_t slot, uint4* src) {
          if (it >= 4) {
            const int kb = own_order(it, j);
            if (it < 10) need(e, 1u << kb); else if (it == 10) mbar_wait(bar + B_ALL, e & 1);
            plain(full, empty, par, slot, src + kb * 1024);
          } else {
            if (it == 0) ready = 0;
            mbar_wait(empty, par);
            if (it < 2) { if (elect()) mbar_arrive(full); }
            else {
              const int b = it > 2;
              const uint32_t to_peer = mapa(sb, rank ^ 1) - sb;
              if (elect()) mbar_expect_tx(full, BLK);
              const bool push = e != 1;
              mbar_wait(bar + (b ? (push ? B_RDY + 8 : B_FREE + 8) : B_RDY), e & 1);
              if (elect()) {
                if (b == 0) {
                  bulk_st(src + 2 * j * 1024, sb + STG, BLK);
                  bulk_commit();
                  bulk_wait_all();
                  mbar_arrive(bar + B_FREE);
                }
                if (b && push) bulk_push(slot + to_peer, sb + STG + BLK, BLK, full + to_peer);
                else {
                  fence_async_global();
                  bulk_ld(slot + to_peer, src + (2 * j + b) * 1024, BLK, full + to_peer);
                }
              }
              __syncwarp();
            }
          }
        };
#pragma unroll 1
        for (int ph = 0; ph < 2; ph++) {
          uint4* h = gs->h + m * 16384;
#pragma unroll 1
          for (int it = 0; it < 16; it++) {
            const int s = (it + 2 * ph) & 3;
            if (ph) drained6(it);
            fresh(2 * ph, it, bar + B_FULL4 + s * 8, bar + B_EMPTY4 + s * 8, ~(it >> 2) & 1, sb + s * 49152, h);
          }
          if (ph) {
#pragma unroll 1
            for (int it = 16; it < 48; it++) {
              const int s = (it + 2) & 3;
              const uint32_t full = bar + B_FULL4 + s * 8;
              plain(full, full + 32, ~(it >> 2) & 1, sb + s * 49152, h + (it & 15) * 1024);
            }
          }
#pragma unroll 1
          for (int it = 0; it < 16; it++) { drained4(it, ph); plain6(h + it * 1024); }
          if (!ph) {
#pragma unroll 1
            for (int it = 0; it < 16; it++) { fresh(1, it, bar + B_FULL6 + s6 * 8, bar + B_EMPTY6 + s6 * 8, p6, sb + s6 * 32768, gs->o + m * 16384); next6(); }
            skip6();
          }
        }
#pragma unroll 1
        for (int it = 0; it < 56; it++) {
          if (it == 0 || it == 32 || it == 48) mbar_wait(bar + (it == 48 ? B_HH2 : B_HH + (it >> 2)), 0);
          plain6(gs->hh + m * 57344 + it * 1024);
        }
      }
    } else {
      const int b = warp - 10;
      const uint32_t ep = gs->epoch[bid + 4] + 1;
      const uint32_t stg = sb + STG + b * BLK;
      cl_arrive_relaxed(); cl_wait();
      auto all_there = [&](int u, uint32_t done) {
        const uint32_t* fl = gs->flag + u * FS;
        uint32_t n = 0;
        while (!__all_sync(~0u, ld_acquire(fl) == ep)) { __nanosleep(100); SPIN_GUARD(n); }
        fence_async_global();
        if (lane == 0) mbar_arrive(done);
      };
      auto fetch_mod = [&](int sec) {
        const uint4* p = (const uint4*)(gs->modv + (sec - 2) * 1024 + j * 128) + lane;
        uint4 v0, v1; uint32_t n = 0;
        while (true) {
          v0 = ld_rlx4(p); v1 = ld_rlx4(p + 32);
          if (v0.y == ep && v0.w == ep && v1.y == ep && v1.w == ep) break;
          SPIN_GUARD(n);
        }
        mod_store(sb, sec, 2 * lane, __uint_as_float(v0.x)); mod_store(sb, sec, 2 * lane + 1, __uint_as_float(v0.z));
        mod_store(sb, sec, 64 + 2 * lane, __uint_as_float(v1.x)); mod_store(sb, sec, 65 + 2 * lane, __uint_as_float(v1.z));
        __syncwarp();
      };
#pragma unroll 1
      for (int e = 0; e < 7 - b; e++) {
        if (lane == 0) {
          if (e < 3) {
            mbar_wait(bar + B_FREE, e & 1);
            if (b) {
              const uint32_t t0 = clock();
              while ((uint32_t)clock() - t0 < (e == 0 ? B1P : e == 2 ? B1P2 : B1D)) {}
              mbar_wait(bar + B_RDY + 8, e & 1);
              bulk_st((e == 1 ? gs->o : gs->h) + m * 16384 + (2 * j + 1) * 1024, stg, BLK);
              bulk_commit();
              bulk_wait_all();
              mbar_arrive(bar + B_FREE + 8);
            }
            st_release(gs->flag + (m * 128 + e * 16 + 2 * j + b) * FS, ep);
          } else {
            const int kb = (e < 6 ? 2 * (8 * (e - 3) + j) : 48 + j) + b;
            mbar_wait(bar + B_RDY + b * 8, e & 1);
#pragma unroll 1
            for (int q = 0; q < NPIECE; q++) { if (q) __nanosleep(PSLEEP); bulk_st(gs->hh + m * 57344 + kb * 1024 + q * (1024 / NPIECE), stg + q * (BLK / NPIECE), BLK / NPIECE); }
            bulk_commit();
            bulk_wait_all();
            mbar_arrive(bar + B_FREE + b * 8);
            st_release(gs->flag + (m * 128 + U_HH + kb) * FS, ep);
          }
        }
        __syncwarp();
        if (e < 3 && b) all_there(m * 128 + e * 16 + (lane & 15), bar + B_ALL);
        if (e == 4 && b) all_there(m * 128 + U_HH + lane, bar + B_HH);
        if (!b && (e == 1 || e == 2)) {
#pragma unroll 1
          for (int sec = e == 1 ? 2 : 5; sec < 4 + e; sec++) fetch_mod(sec);
          if (e == 1) { if (lane == 0) mbar_arrive(bar + B_MOD); }
        }
        if (e == 0) {
          mbar_wait(bar + B_EMPTY6 + 24, 0);
          __nanosleep(HSLEEP);
#pragma unroll 1
          for (int w = 0; w < 4; w++) {
            const uint4* hp = gs->halo + ((m * 8 + j) * 2 + (w & 1)) * 512 + b * 256 + (w >> 1) * 128 + lane;
            uint4 q[4] = {}; uint32_t n = 0;
            while (m > 0) {
              bool ok = true;
#pragma unroll
              for (int i = 0; i < 4; i++) q[i] = ld_rlx4(hp + i * 32);
#pragma unroll
              for (int i = 0; i < 4; i++) ok = ok && q[i].y == ep && q[i].w == ep;
              if (ok) break;
              SPIN_GUARD(n);
            }
#pragma unroll
            for (int i = 0; i < 2; i++) sts128(stg + lane * 16 + (w & 1) * HALF + (w >> 1) * 1024 + i * 512, q[2 * i].x, q[2 * i + 1].x, q[2 * i].z, q[2 * i + 1].z);
          }
          __syncwarp();
          if (lane == 0) mbar_arrive(bar + B_HALO);
        }
      }
      if (b) { all_there(m * 128 + U_HH + 32 + (lane & 15), bar + B_HH + 8); all_there(m * 128 + U_HH + 48 + (lane & 7), bar + B_HH2); }
    }
  } else {
    const int wg = warp >> 2, wq = warp & 3, tid = threadIdx.x;
    const int g = lane >> 2, c = lane & 3;
    const int sec0 = (m >> 1) & 1, hf0 = m & 1, ks0 = (m >> 2) & 3;
    uint4 wv[8];
    uint32_t ep0; uint16_t cv_;
    asm volatile("ld.global.nc.u16 %0, [%1];" : "=h"(cv_) : "l"(cvec + ks0 * 256 + warp * 32 + lane));
    asm volatile("ld.global.u32 %0, [%1];" : "=r"(ep0) : "l"(gs->epoch + bid + 4));
    if (!extra) {
      const bf16* wp = wmod + (size_t)(ks0 * 256 + warp * 32 + (lane >> 3)) * 6144 + sec0 * 1024 + j * 128 + hf0 * 64 + (lane & 7) * 8;
#pragma unroll
      for (int i = 0; i < 8; i++) wv[i] = ldg_nc(wp + (size_t)i * 4 * 6144);
    }
    asm volatile("setmaxnreg.inc.sync.aligned.u32 232;" ::: "memory");
    if (__builtin_expect(extra, 0)) {
      const uint32_t ep = ep0 + 1;
      float sv[4];
#pragma unroll
      for (int p = 0; p < 4; p++) sv[p] = silu_c(__bfloat162float(cvec[64 * (4 * p + (lane >> 3)) + 8 * warp + (lane & 7)]));
      named_bar(2, 288);
      int s = 0, par = 0;
#pragma unroll 1
      for (int sec = 0; sec < 4; sec++) {
        float a[8] = {0, 0, 0, 0, 0, 0, 0, 0};
#pragma unroll 1
        for (int it = 0; it < 16; it++) {
          const float sc = it < 4 ? sv[0] : it < 8 ? sv[1] : it < 12 ? sv[2] : sv[3];
          mbar_wait(bar + B_FULL6 + s * 8, par);
          uint4 w[8];
#pragma unroll
          for (int i = 0; i < 8; i++) w[i] = lds128(sb + s * 32768 + (warp * 8 + i) * 512 + lane * 16);
#pragma unroll
          for (int i = 0; i < 8; i++) gemv_fma(a, w[i], __shfl_sync(~0u, sc, (it & 3) * 8 + i));
          if (lane == 0) mbar_arrive(bar + B_EMPTY6 + s * 8);
          if (++s == 6) { s = 0; par ^= 1; }
        }
        const uint32_t red = sb + STG + sec * 8192;
        sts128(red + warp * 1024 + lane * 32, __float_as_uint(a[0]), __float_as_uint(a[1]), __float_as_uint(a[2]), __float_as_uint(a[3]));
        sts128(red + warp * 1024 + lane * 32 + 16, __float_as_uint(a[4]), __float_as_uint(a[5]), __float_as_uint(a[6]), __float_as_uint(a[7]));
        named_bar(1, 256);
        float t = 0;
#pragma unroll
        for (int q = 0; q < 8; q++) t += lds32f(red + q * 1024 + tid * 4);
        st_rlx2(gs->modv + sec * 1024 + (bid + 4) * 256 + tid, __float_as_uint(t), ep);
      }
      if (tid == 0) gs->epoch[bid + 4] = ep;
      return;
    }
    const int row0 = wg * 64 + wq * 16 + g;
    if (c < 2) st_rlx4(gs->stat + m * 1024 + j * 128 + row0 + c * 8, 0, 0, 0, 0);
    if (tid < 64) st_rlx2(gs->modp + ((j * 2 + sec0) * 4 + ks0) * 128 + hf0 * 64 + tid, 0, 0);
    cl_arrive_relaxed(); cl_wait();
    uint32_t ep;
    asm volatile("add.u32 %0, %1, 1;" : "=r"(ep) : "r"(ep0) : "memory");
    const float sc_ = silu_c(__uint_as_float((uint32_t)cv_ << 16));
    const uint32_t rel = mapa(bar, (lane & 1) ^ rank);
    const uint32_t stg_row = sb + STG + (wg * 64 + wq * 16 + (lane & 15)) * 128;
    const uint32_t fre = bar + B_FREE;
    Ring r4{0, 0, 0}, r6{0, 0, 0};
    auto none = [](auto) {};
    uint32_t xk[32];
    {
      float a[8] = {0, 0, 0, 0, 0, 0, 0, 0};
#pragma unroll
      for (int i = 0; i < 8; i++) gemv_fma(a, wv[i], __shfl_sync(~0u, sc_, i * 4 + (lane >> 3)));
#pragma unroll
      for (int i = 0; i < 8; i++) { a[i] += __shfl_xor_sync(~0u, a[i], 8); a[i] += __shfl_xor_sync(~0u, a[i], 16); }
      if (lane < 8) {
        sts128(sb + RED_OFF + warp * 256 + lane * 32, __float_as_uint(a[0]), __float_as_uint(a[1]), __float_as_uint(a[2]), __float_as_uint(a[3]));
        sts128(sb + RED_OFF + warp * 256 + lane * 32 + 16, __float_as_uint(a[4]), __float_as_uint(a[5]), __float_as_uint(a[6]), __float_as_uint(a[7]));
      }
      named_bar(1, 256);
      if (tid < 64) {
        float s = 0;
#pragma unroll
        for (int w = 0; w < 8; w++) s += lds32f(sb + RED_OFF + w * 256 + tid * 4);
        st_rlx2(gs->modp + ((j * 2 + sec0) * 4 + ks0) * 128 + hf0 * 64 + tid, __float_as_uint(s), ep);
      }
      float v[64];
      mbar_wait(bar + B_X, 0); mbar_wait(bar + B_X + 8, 0);
#pragma unroll
      for (int i = 0; i < 16; i += 2) {
        uint32_t w0, w1, w2, w3;
        ldsm4(stg_row + (i >> 3) * BLK + ((((i & 7) + (lane >> 4)) ^ (lane & 7)) << 4), w0, w1, w2, w3);
        xk[2 * i] = w0; xk[2 * i + 1] = w1; xk[2 * i + 2] = w2; xk[2 * i + 3] = w3;
        v[4 * i] = bf_lo(w0); v[4 * i + 1] = bf_hi(w0); v[4 * i + 2] = bf_lo(w1); v[4 * i + 3] = bf_hi(w1);
        v[4 * i + 4] = bf_lo(w2); v[4 * i + 5] = bf_hi(w2); v[4 * i + 6] = bf_lo(w3); v[4 * i + 7] = bf_hi(w3);
      }
      ln_publish(v, gs->stat + m * 1024, j, row0, lane, ep);
      mod_store(sb, tid >> 7, tid & 127, mod_gather(gs->modp + (j * 2 + (tid >> 7)) * 512 + (tid & 127), ep));
      named_bar(1, 256);
      ln_apply(v, gs->stat + m * 1024, row0, ep, sb, 0, 1, stg_row, wg, lane);
      named_bar(1, 256);
    }
    {
      uint32_t kf[32], vf[32], pv[32];
      const bool first = wq == 0 && m == 0;
      const uint32_t xa = sb + STG + wg * HALF + wq * 2048 + lane * 16;
      {
        float acc[128];
        mainloop<256, 4, 0, 0>(acc, 16, true, r4, sb, wg, lane, rel, none, none, [&] {
          mbar_wait(fre + 8, 0);
          if (c < 2) st_rlx4(gs->stat + (16 + m) * 1024 + j * 128 + row0 + c * 8, 0, 0, 0, 0);
        });
#pragma unroll
        for (int i = 0; i < 32; i++) { kf[i] = pack2(acc[2 * i], acc[2 * i + 1]); vf[i] = pack2(acc[64 + 2 * i], acc[65 + 2 * i]); }
      }
      float acc[64];
      constexpr int QP = 2;
      mainloop<128, 6, 8 / QP, 0>(acc, 16, false, r6, sb, wg, lane, rel, [&](auto ic) {
        constexpr int q = (ic.v - 1) * QP;
#pragma unroll
        for (int i = 4 * q; i < 4 * (q + QP); i++) vf[i] = movm(vf[i]);
        if (wq == 3) {
          if (m < 15) {
            uint4* hp = gs->halo + (((m + 1) * 8 + j) * 2 + wg) * 512 + lane;
#pragma unroll
            for (int i = 2 * q; i < 2 * (q + QP); i++) st_rlx4(hp + i * 32, kf[2 * i + 1], ep, vf[2 * i + 1], ep);
          }
        } else {
#pragma unroll
          for (int i = q; i < q + QP; i++) sts128(xa + 2048 + (i >> 2) * BLK + (i & 3) * 512, kf[4 * i + 1], kf[4 * i + 3], vf[4 * i + 1], vf[4 * i + 3]);
        }
      }, none, [&] {
        named_bar(2 + wg, 128);
        if (wq == 0) mbar_wait(bar + B_HALO, 0);
#pragma unroll
        for (int i = 0; i < 8; i++) {
          uint4 q = lds128(xa + (i >> 2) * BLK + (i & 3) * 512);
          pv[4 * i] = q.x; pv[4 * i + 1] = q.y; pv[4 * i + 2] = q.z; pv[4 * i + 3] = q.w;
        }
        __syncwarp();
      });
      int gz = g;
#pragma unroll
      for (int b = 0; b < 2; b++) {
        const bool up0 = 2 * c > gz, up1 = 2 * c + 1 > gz;
        const uint32_t mup = (up0 ? 0xffffu : 0u) | (up1 ? 0xffff0000u : 0u);
        float l[2][4], mx[4];
#pragma unroll
        for (int h = 0; h < 2; h++) {
          uint32_t q[8];
          const int k = 16 * b + 8 * h;
#pragma unroll
          for (int i = 0; i < 8; i++) q[i] = pack2(acc[2 * k + 2 * i], acc[2 * k + 2 * i + 1]);
          float s0[4], s1[4], s2[4];
          mma16z(s0, q[0], q[1], q[2], q[3], pv[k], pv[k + 1]); mma16z(s1, q[0], q[1], q[2], q[3], kf[k], kf[k + 2]); mma16z(s2, q[0], q[1], q[2], q[3], kf[k + 1], kf[k + 3]);
          mma16(s0, q[4], q[5], q[6], q[7], pv[k + 4], pv[k + 5]); mma16(s1, q[4], q[5], q[6], q[7], kf[k + 4], kf[k + 6]); mma16(s2, q[4], q[5], q[6], q[7], kf[k + 5], kf[k + 7]);
          if (first) { s0[0] = -INFINITY; s0[1] = -INFINITY; }
          l[h][0] = up0 ? s0[0] : s1[0]; l[h][1] = up1 ? s0[1] : s1[1]; l[h][2] = up0 ? s1[2] : s2[2]; l[h][3] = up1 ? s1[3] : s2[3];
          mx[2 * h] = fmaxf(l[h][0], l[h][1]); mx[2 * h + 1] = fmaxf(l[h][2], l[h][3]);
        }
#pragma unroll
        for (int o = 1; o < 4; o <<= 1) {
#pragma unroll
          for (int h = 0; h < 4; h++) mx[h] = fmaxf(mx[h], __shfl_xor_sync(~0u, mx[h], o));
        }
#pragma unroll
        for (int h = 0; h < 2; h++) {
          const float n0 = -mx[2 * h] * SCL, n1 = -mx[2 * h + 1] * SCL;
          const uint32_t pa = pack2(ex2(fmaf(l[h][0], SCL, n0)), ex2(fmaf(l[h][1], SCL, n0))), pb = pack2(ex2(fmaf(l[h][2], SCL, n1)), ex2(fmaf(l[h][3], SCL, n1)));
          float sm[4];
          mma8z(sm, pa, pb, 0x3f803f80u);
          const float ia = rcp(sm[0]), ib = rcp(sm[2]);
#pragma unroll
          for (int i = 8 * b + 4 * h; i < 8 * b + 4 * h + 4; i += 2) {
            uint32_t of[4];
#pragma unroll
            for (int d = 0; d < 2; d++) {
              float o[4];
              mma16z(o, pa & ~mup, pb & mup, 0u, pb & ~mup, vf[2 * (i + d)], vf[2 * (i + d) + 1]);
              mma8(o, pa & mup, 0u, pv[2 * i + 2 + d]);
              of[2 * d] = pack2(o[0] * ia, o[1] * ia); of[2 * d + 1] = pack2(o[2] * ib, o[3] * ib);
            }
            stsm4(stg_row + b * BLK + ((((i & 7) + (lane >> 4)) ^ (lane & 7)) << 4), of[0], of[1], of[2], of[3]);
          }
        }
        stage_done(sb, wg, b, lane);
        if (b == 0) gz += __float_as_uint(lds32f(bar + ZERO));
      }
      named_bar(1, 256);
    }
    uint32_t pk[64];
    {
      float acc[64];
      mainloop<128, 6, 0, WOLAG>(acc, 16, true, r6, sb, wg, lane, rel, none, none, [&] {
        if (WOLAG && wg == 0 && lane == 0) mbar_arrive(bar + B_LAG);
        mbar_wait(bar + B_MOD, 0); mbar_wait(fre + 8, 1);
        load_vec(pk + 32, sb, 2, 0, lane); load_vec(pk + 40, sb, 2, 1, lane);
#pragma unroll
        for (int i = 0; i < 32; i++) { pk[i] = xk[i]; asm volatile("" : "+r"(pk[i])); }
      });
#pragma unroll
      for (int i = 0; i < 32; i++) {
        acc[2 * i] = fmaf(acc[2 * i], bf_lo(pk[32 + (i >> 1)]), bf_lo(pk[i]));
        acc[2 * i + 1] = fmaf(acc[2 * i + 1], bf_hi(pk[32 + (i >> 1)]), bf_hi(pk[i]));
      }
      ln_publish(acc, gs->stat + (16 + m) * 1024, j, row0, lane, ep);
      mbar_wait(bar + B_FULL6 + 16, 1);
      if (lane < 2) mbar_arrive_cl(rel + B_EMPTY6 + 16);
      ring_next<6>(r6);
#pragma unroll
      for (int i = 0; i < 32; i++) { pk[i] = pack2(acc[2 * i], acc[2 * i + 1]); pk[32 + i] = 0; }
      ln_apply(acc, gs->stat + (16 + m) * 1024, row0, ep, sb, 3, 4, stg_row, wg, lane);
      named_bar(1, 256);
    }
    auto swiglu = [&](int q, int uo, int par) {
      if ((q & 3) == 0 && par >= 0) mbar_wait(fre + 2 * q, par);
      uint32_t w[4];
#pragma unroll
      for (int u = 0; u < 4; u++) w[u] = silu_mul2(pk[4 * q + u], pk[uo + 4 * q + u]);
      stsm4(stg_row + (q >> 2) * BLK + ((((2 * q & 7) + (lane >> 4)) ^ (lane & 7)) << 4), w[0], w[1], w[2], w[3]);
    };
    r4.s = r4.wrap = 2;
#pragma unroll 1
    for (int t = 0; t < 3; t++) {
      float acc[128];
      mainloop<256, 4, 5, 0>(acc, 16, t == 0, r4, sb, wg, lane, rel, [&](auto ic) {
        if (t) {
          if (ic.v == 3 || ic.v == 5) stage_done(sb, wg, ic.v >> 2, lane);
          if (ic.v < 5) { swiglu(2 * ic.v - 2, 32, ~t & 1); swiglu(2 * ic.v - 1, 32, 0); }
        }
      }, [&](int it) {
#pragma unroll
        for (int i = 0; i < 8; i++)
          if (t == 0 && it == 8 + i) gs->x1[bid * 2048 + (i >> 2) * 1024 + warp * 128 + (i & 3) * 32 + lane] = make_uint4(pk[4 * i], pk[4 * i + 1], pk[4 * i + 2], pk[4 * i + 3]);
      }, [&] { if (t == 0) fence_async_global(); else if (t == 2) mbar_wait(bar + B_X, 1); });
#pragma unroll
      for (int i = 0; i < 64; i++) pk[i] = pack2(acc[2 * i], acc[2 * i + 1]);
    }
    uint32_t x1[32];
    {
      float acc[64];
      mainloop<128, 6, 12, 0>(acc, 16, false, r6, sb, wg, lane, rel, [&](auto ic) {
        constexpr int b = ic.v > 6, q = ic.v - 6 * b;
        if (q == 1) {
#pragma unroll
          for (int i = 4 * b; i < 4 * b + 4; i++) { const uint4 x = lds128(sb + STG + b * BLK + warp * 2048 + (i & 3) * 512 + lane * 16); x1[4 * i] = x.x; x1[4 * i + 1] = x.y; x1[4 * i + 2] = x.z; x1[4 * i + 3] = x.w; }
          __syncwarp();
        } else if (q < 6) swiglu(4 * b + q - 2, 32, -1);
        else stage_done(sb, wg, b, lane);
      }, none, [] {});
#pragma unroll
      for (int i = 0; i < 32; i++) pk[i] = pack2(acc[2 * i], acc[2 * i + 1]);
    }
    {
      float acc[64];
      mainloop<128, 6, 5, TAILLAG>(acc, 56, false, r6, sb, wg, lane, rel, [&](auto ic) {
        if (ic.v == 5) stage_done(sb, wg, 0, lane); else swiglu(ic.v - 1, 16, 1);
      }, none, [&] {
        if (TAILLAG && wg == 0 && lane == 0) mbar_arrive(bar + B_LAG);
        load_vec(pk + 32, sb, 5, 0, lane); load_vec(pk + 40, sb, 5, 1, lane);
        mbar_wait(fre, 0); mbar_wait(fre + 8, 1);
      });
      __syncwarp();
      cl_arrive_relaxed();
#pragma unroll
      for (int i = 0; i < 16; i += 2) {
        uint32_t w[4];
#pragma unroll
        for (int u = 0; u < 4; u++) {
          const int q = 2 * i + u;
          w[u] = pack2(fmaf(acc[2 * q], bf_lo(pk[32 + (q >> 1)]), bf_lo(x1[q])), fmaf(acc[2 * q + 1], bf_hi(pk[32 + (q >> 1)]), bf_hi(x1[q])));
        }
        stsm4(stg_row + (i >> 3) * BLK + ((((i & 7) + (lane >> 4)) ^ (lane & 7)) << 4), w[0], w[1], w[2], w[3]);
        if ((i & 7) == 6) {
          fence_async_smem();
          named_bar(2 + wg, 128);
          if (wq == 0 && elect()) { tma_store_3d(&maps.out, sb + STG + (i >> 3) * BLK + wg * HALF, j * 128 + (i >> 3) * 64, m * 64, wg); bulk_commit(); }
          if (i < 8) x1[16] |= __float_as_uint(lds32f(bar + ZERO));
        }
      }
      if (wq == 0) bulk_wait_read();
      if (tid == 0) gs->epoch[bid + 4] = ep;
      cl_wait();
    }
  }
}

typedef CUresult (*EncodeFn)(CUtensorMap*, CUtensorMapDataType, cuuint32_t, void*, const cuuint64_t*, const cuuint64_t*, const cuuint32_t*, const cuuint32_t*,
                             CUtensorMapInterleave, CUtensorMapSwizzle, CUtensorMapL2promotion, CUtensorMapFloatOOBfill);

void make_map(EncodeFn fn, CUtensorMap* mp, const void* base, uint64_t d0, uint64_t d1, uint64_t d2, uint64_t s1, uint64_t s2, uint32_t b2, uint32_t b0 = 64) {
  cuuint64_t d[3] = {d0, d1, d2}, s[2] = {s1, s2};
  cuuint32_t b[3] = {b0, 64, b2}, e[3] = {1, 1, 1};
  fn(mp, CU_TENSOR_MAP_DATA_TYPE_BFLOAT16, 3, (void*)base, d, s, b, e, CU_TENSOR_MAP_INTERLEAVE_NONE, b0 == 64 ? CU_TENSOR_MAP_SWIZZLE_128B : CU_TENSOR_MAP_SWIZZLE_NONE,
     CU_TENSOR_MAP_L2_PROMOTION_L2_128B, CU_TENSOR_MAP_FLOAT_OOB_FILL_NONE);
}

__global__ void probe_kernel() {}
int max_clusters(int size) {
  cudaLaunchConfig_t cfg = {};
  cudaLaunchAttribute at;
  at.id = cudaLaunchAttributeClusterDimension; at.val.clusterDim.x = size; at.val.clusterDim.y = 1; at.val.clusterDim.z = 1;
  cfg.gridDim = dim3(size * 66); cfg.blockDim = dim3(384); cfg.dynamicSmemBytes = SMEM_BYTES; cfg.attrs = &at; cfg.numAttrs = 1;
  int n = 0;
  if (cudaOccupancyMaxActiveClusters(&n, probe_kernel, &cfg) != cudaSuccess) { cudaGetLastError(); return 0; }
  return n;
}

}

extern "C" void kernel_launch(void* const* d_in, const int* in_sizes, int n_in, void* d_out, int out_size) {
  static EncodeFn fn = nullptr;
  static int by_sm = 0;
  static Scratch* gs = nullptr;
  if (!fn) {
    void* p = nullptr; cudaDriverEntryPointQueryResult q;
    cudaGetDriverEntryPoint("cuTensorMapEncodeTiled", &p, cudaEnableDefault, &q);
    fn = (EncodeFn)p;
    cudaFuncSetAttribute(fused_kernel, cudaFuncAttributeMaxDynamicSharedMemorySize, SMEM_BYTES);
    int dev = 0, sms = 0;
    cudaGetSymbolAddress((void**)&gs, g_scratch);
    cudaGetDevice(&dev);
    cudaDeviceGetAttribute(&sms, cudaDevAttrMultiProcessorCount, dev);
    cudaFuncSetAttribute(probe_kernel, cudaFuncAttributeMaxDynamicSharedMemorySize, SMEM_BYTES);
    by_sm = sms == 132 && max_clusters(2) == 66 && max_clusters(4) == 30 && max_clusters(6) == 17 && max_clusters(8) == 15;
  }
  Maps mp;
  make_map(fn, &mp.x, d_in[0], D_, S_ / 2, 2, 4096, 2048, 2);
  make_map(fn, &mp.out, d_out, D_, S_ / 2, 2, 4096, 2048, 1);
  make_map(fn, &mp.wqkv, d_in[1], 64, D_, 3 * D_ / 64, 3 * D_ * 2, 128, 2);
  make_map(fn, &mp.wo, d_in[2], 64, D_, D_ / 64, D_ * 2, 128, 2);
  make_map(fn, &mp.w1, d_in[4], 64, D_, F_ / 64, F_ * 2, 128, 2);
  make_map(fn, &mp.w3, d_in[5], 64, D_, F_ / 64, F_ * 2, 128, 2);
  make_map(fn, &mp.w1s, d_in[4], 64, D_, F_ / 64, F_ * 2, 128, 1);
  make_map(fn, &mp.w3s, d_in[5], 64, D_, F_ / 64, F_ * 2, 128, 1);
  make_map(fn, &mp.w2, d_in[6], 64, F_, D_ / 64, D_ * 2, 128, 2);
  make_map(fn, &mp.wmod, d_in[8], 256, D_, 24, 6 * D_ * 2, 512, 1, 256);
  fused_kernel<<<132, 384, SMEM_BYTES>>>((const bf16*)d_in[7], (const bf16*)d_in[8], gs, by_sm, mp);
}
```

```cpp
#include <cuda_runtime.h>
#include <cuda_bf16.h>
#include <cuda.h>
#include <stdint.h>

typedef __nv_bfloat16 bf16;

namespace {

constexpr int S_ = 2048, D_ = 1024, F_ = 3584;
constexpr int BLK = 16384;
constexpr int HALF = 8192;
constexpr int RING = 196608;
constexpr int STG = RING;
constexpr int MISC = RING + 2 * BLK;
constexpr int SMEM_BYTES = MISC + 3072;
constexpr int B_FULL4 = 0, B_EMPTY4 = 32, B_FULL6 = 64, B_EMPTY6 = 112, B_RDY = 160, B_FREE = 176, B_LAG = 192, B_X = 208, B_MOD = 224, B_HALO = 232, B_HH = 256, B_ALL = 272, B_HH2 = 288, ZERO = 296;
constexpr int MODV = 512;
constexpr int RED_OFF = 0;
constexpr float SCL = 0.17677669529663687f * 1.4426950408889634f;
constexpr int U_HH = 64;
constexpr int FS = 8;
constexpr int NPIECE = 4, PSLEEP = 300;
constexpr int XSLEEP = 4000, HSLEEP = 400;
constexpr uint32_t XDELAY = 2000;
constexpr uint32_t B1P = 3500, B1D = 900, B1P2 = 3200;
constexpr int WOLAG = 2, TAILLAG = 5;

struct Maps { CUtensorMap x, out, wqkv, wo, w1, w3, w1s, w3s, w2, wmod; };

struct Scratch {
  uint4 h[16 * 16 * 1024];
  uint4 o[16 * 16 * 1024];
  uint4 hh[16 * 56 * 1024];
  uint4 x1[128 * 8 * 256];
  uint2 stat[2 * 16 * 8 * 128];
  uint4 halo[16 * 8 * 2 * 512];
  uint2 modp[8 * 2 * 4 * 128];
  uint2 modv[4 * 1024];
  uint32_t flag[16 * 128 * FS];
  uint32_t epoch[132];
};
__device__ __align__(1024) Scratch g_scratch;

__device__ __forceinline__ void bail() { asm volatile("st.global.u32 [%0], %1;" :: "l"(0ull), "r"(0) : "memory"); }
__device__ __forceinline__ uint32_t smem_u32(const void* p) { return (uint32_t)__cvta_generic_to_shared(p); }
__device__ __forceinline__ void mbar_init(uint32_t bar, uint32_t cnt) { asm volatile("mbarrier.init.shared::cta.b64 [%0], %1;" :: "r"(bar), "r"(cnt) : "memory"); }
__device__ __forceinline__ void mbar_expect_tx(uint32_t bar, uint32_t bytes) { asm volatile("mbarrier.arrive.expect_tx.shared::cta.b64 _, [%0], %1;" :: "r"(bar), "r"(bytes) : "memory"); }
__device__ __forceinline__ void mbar_arrive(uint32_t bar) { asm volatile("mbarrier.arrive.shared::cta.b64 _, [%0];" :: "r"(bar) : "memory"); }
__device__ __forceinline__ void mbar_arrive_cl(uint32_t cl_addr) { asm volatile("mbarrier.arrive.shared::cluster.b64 _, [%0];" :: "r"(cl_addr) : "memory"); }
__device__ __forceinline__ uint32_t mapa(uint32_t addr, uint32_t cta) { uint32_t r; asm("mapa.shared::cluster.u32 %0, %1, %2;" : "=r"(r) : "r"(addr), "r"(cta)); return r; }
__device__ __forceinline__ void mbar_wait(uint32_t bar, uint32_t parity) {
  asm volatile("{\n.reg .pred p;\n.reg .b32 n;\n.reg .b64 z;\nmov.b32 n, 0;\nmov.b64 z, 0;\n"
               "W: add.u32 n, n, 1;\nsetp.gt.u32 p, n, 0x400000;\n@p st.global.u32 [z], n;\n"
               "mbarrier.try_wait.parity.shared::cta.b64 p, [%0], %1;\n@!p bra W;\n}" :: "r"(bar), "r"(parity) : "memory");
}
__device__ __forceinline__ void tma_3d(uint32_t dst, const CUtensorMap* m, uint32_t bar, int c0, int c1, int c2) {
  asm volatile("cp.async.bulk.tensor.3d.shared::cluster.global.mbarrier::complete_tx::bytes [%0], [%1, {%3, %4, %5}], [%2];" :: "r"(dst), "l"(m), "r"(bar), "r"(c0), "r"(c1), "r"(c2) : "memory");
}
__device__ __forceinline__ void tma_store_3d(const CUtensorMap* m, uint32_t src, int c0, int c1, int c2) {
  asm volatile("cp.async.bulk.tensor.3d.global.shared::cta.bulk_group [%0, {%2, %3, %4}], [%1];" :: "l"(m), "r"(src), "r"(c0), "r"(c1), "r"(c2) : "memory");
}
__device__ __forceinline__ void bulk_ld(uint32_t dst, const void* src, uint32_t bytes, uint32_t bar) {
  asm volatile("cp.async.bulk.shared::cluster.global.mbarrier::complete_tx::bytes [%0], [%1], %2, [%3];" :: "r"(dst), "l"(src), "r"(bytes), "r"(bar) : "memory");
}
__device__ __forceinline__ void bulk_ld_mc(uint32_t dst, const void* src, uint32_t bytes, uint32_t bar) {
  asm volatile("cp.async.bulk.shared::cluster.global.mbarrier::complete_tx::bytes.multicast::cluster [%0], [%1], %2, [%3], %4;" :: "r"(dst), "l"(src), "r"(bytes), "r"(bar), "h"((uint16_t)3) : "memory");
}
__device__ __forceinline__ void bulk_push(uint32_t dst_cl, uint32_t src, uint32_t bytes, uint32_t bar_cl) {
  asm volatile("cp.async.bulk.shared::cluster.shared::cta.mbarrier::complete_tx::bytes [%0], [%1], %2, [%3];" :: "r"(dst_cl), "r"(src), "r"(bytes), "r"(bar_cl) : "memory");
}
__device__ __forceinline__ void bulk_st(void* dst, uint32_t src, uint32_t bytes) {
  asm volatile("cp.async.bulk.global.shared::cta.bulk_group [%0], [%1], %2;" :: "l"(dst), "r"(src), "r"(bytes) : "memory");
}
__device__ __forceinline__ void bulk_commit() { asm volatile("cp.async.bulk.commit_group;" ::: "memory"); }
__device__ __forceinline__ void bulk_wait_read() { asm volatile("cp.async.bulk.wait_group.read 0;" ::: "memory"); }
__device__ __forceinline__ void bulk_wait_all() { asm volatile("cp.async.bulk.wait_group 0;" ::: "memory"); }
__device__ __forceinline__ void fence_async_global() { asm volatile("fence.proxy.async.global;" ::: "memory"); }
__device__ __forceinline__ void fence_async_smem() { asm volatile("fence.proxy.async.shared::cta;" ::: "memory"); }
__device__ __forceinline__ void wg_arrive() { asm volatile("wgmma.fence.sync.aligned;" ::: "memory"); }
__device__ __forceinline__ void wg_commit() { asm volatile("wgmma.commit_group.sync.aligned;" ::: "memory"); }
template <int N> __device__ __forceinline__ void wg_wait() { asm volatile("wgmma.wait_group.sync.aligned %0;" :: "n"(N) : "memory"); }
__device__ __forceinline__ void cl_arrive_relaxed() { asm volatile("barrier.cluster.arrive.relaxed.aligned;" ::: "memory"); }
__device__ __forceinline__ void cl_wait() { asm volatile("barrier.cluster.wait.acquire.aligned;" ::: "memory"); }
__device__ __forceinline__ bool elect() { uint32_t p; asm volatile("{\n.reg .pred p;\nelect.sync _|p, 0xffffffff;\nselp.u32 %0, 1, 0, p;\n}" : "=r"(p)); return p; }
__device__ __forceinline__ void named_bar(int id, int n) { asm volatile("bar.sync %0, %1;" :: "r"(id), "r"(n) : "memory"); }
__device__ __forceinline__ uint32_t pack2(float lo, float hi) { uint32_t r; asm("cvt.rn.bf16x2.f32 %0, %1, %2;" : "=r"(r) : "f"(hi), "f"(lo)); return r; }
__device__ __forceinline__ float bf_lo(uint32_t w) { return __uint_as_float(w << 16); }
__device__ __forceinline__ float bf_hi(uint32_t w) { return __uint_as_float(w & 0xffff0000u); }
__device__ __forceinline__ float bf_round(float v) { return __bfloat162float(__float2bfloat16_rn(v)); }
__device__ __forceinline__ void stsm4(uint32_t addr, uint32_t a, uint32_t b, uint32_t c, uint32_t d) {
  asm volatile("stmatrix.sync.aligned.m8n8.x4.shared.b16 [%0], {%1, %2, %3, %4};" :: "r"(addr), "r"(a), "r"(b), "r"(c), "r"(d) : "memory");
}
__device__ __forceinline__ void ldsm4(uint32_t addr, uint32_t& a, uint32_t& b, uint32_t& c, uint32_t& d) {
  asm volatile("ldmatrix.sync.aligned.m8n8.x4.shared.b16 {%0, %1, %2, %3}, [%4];" : "=r"(a), "=r"(b), "=r"(c), "=r"(d) : "r"(addr) : "memory");
}
__device__ __forceinline__ uint32_t movm(uint32_t a) { uint32_t r; asm volatile("movmatrix.sync.aligned.m8n8.trans.b16 %0, %1;" : "=r"(r) : "r"(a)); return r; }
__device__ __forceinline__ void mma16(float (&d)[4], uint32_t a0, uint32_t a1, uint32_t a2, uint32_t a3, uint32_t b0, uint32_t b1) {
  asm("mma.sync.aligned.m16n8k16.row.col.f32.bf16.bf16.f32 {%0,%1,%2,%3}, {%4,%5,%6,%7}, {%8,%9}, {%0,%1,%2,%3};"
               : "+f"(d[0]), "+f"(d[1]), "+f"(d[2]), "+f"(d[3]) : "r"(a0), "r"(a1), "r"(a2), "r"(a3), "r"(b0), "r"(b1));
}
__device__ __forceinline__ void mma16z(float (&d)[4], uint32_t a0, uint32_t a1, uint32_t a2, uint32_t a3, uint32_t b0, uint32_t b1) {
  asm("mma.sync.aligned.m16n8k16.row.col.f32.bf16.bf16.f32 {%0,%1,%2,%3}, {%4,%5,%6,%7}, {%8,%9}, {%10,%10,%10,%10};"
      : "=f"(d[0]), "=f"(d[1]), "=f"(d[2]), "=f"(d[3]) : "r"(a0), "r"(a1), "r"(a2), "r"(a3), "r"(b0), "r"(b1), "f"(0.f));
}
__device__ __forceinline__ void mma8z(float (&d)[4], uint32_t a0, uint32_t a1, uint32_t b0) {
  asm("mma.sync.aligned.m16n8k8.row.col.f32.bf16.bf16.f32 {%0,%1,%2,%3}, {%4,%5}, {%6}, {%7,%7,%7,%7};"
      : "=f"(d[0]), "=f"(d[1]), "=f"(d[2]), "=f"(d[3]) : "r"(a0), "r"(a1), "r"(b0), "f"(0.f));
}
__device__ __forceinline__ void mma8(float (&d)[4], uint32_t a0, uint32_t a1, uint32_t b0) {
  asm("mma.sync.aligned.m16n8k8.row.col.f32.bf16.bf16.f32 {%0,%1,%2,%3}, {%4,%5}, {%6}, {%0,%1,%2,%3};"
               : "+f"(d[0]), "+f"(d[1]), "+f"(d[2]), "+f"(d[3]) : "r"(a0), "r"(a1), "r"(b0));
}
__device__ __forceinline__ uint4 lds128(uint32_t a) { uint4 v; asm volatile("ld.shared.v4.u32 {%0,%1,%2,%3}, [%4];" : "=r"(v.x), "=r"(v.y), "=r"(v.z), "=r"(v.w) : "r"(a) : "memory"); return v; }
__device__ __forceinline__ void sts128(uint32_t a, uint32_t x, uint32_t y, uint32_t z, uint32_t w) { asm volatile("st.shared.v4.u32 [%0], {%1,%2,%3,%4};" :: "r"(a), "r"(x), "r"(y), "r"(z), "r"(w) : "memory"); }
__device__ __forceinline__ float lds32f(uint32_t a) { float v; asm volatile("ld.shared.f32 %0, [%1];" : "=f"(v) : "r"(a) : "memory"); return v; }
__device__ __forceinline__ void sts16(uint32_t a, bf16 v) { asm volatile("st.shared.b16 [%0], %1;" :: "r"(a), "h"(__bfloat16_as_ushort(v)) : "memory"); }
__device__ __forceinline__ uint4 ldg_nc(const void* p) { uint4 v; asm volatile("ld.global.nc.L1::no_allocate.v4.u32 {%0,%1,%2,%3}, [%4];" : "=r"(v.x), "=r"(v.y), "=r"(v.z), "=r"(v.w) : "l"(p)); return v; }
__device__ __forceinline__ uint4 ld_rlx4(const uint4* p) {
  unsigned long long a, b; asm volatile("ld.relaxed.gpu.global.v2.b64 {%0,%1}, [%2];" : "=l"(a), "=l"(b) : "l"(p) : "memory");
  return make_uint4((uint32_t)a, (uint32_t)(a >> 32), (uint32_t)b, (uint32_t)(b >> 32));
}
__device__ __forceinline__ uint2 ld_rlx2(const uint2* p) { unsigned long long a; asm volatile("ld.relaxed.gpu.global.b64 %0, [%1];" : "=l"(a) : "l"(p) : "memory"); return make_uint2((uint32_t)a, (uint32_t)(a >> 32)); }
__device__ __forceinline__ void st_rlx4(uint4* p, uint32_t x, uint32_t y, uint32_t z, uint32_t w) {
  asm volatile("st.relaxed.gpu.global.v2.b64 [%0], {%1,%2};" :: "l"(p), "l"((unsigned long long)x | ((unsigned long long)y << 32)), "l"((unsigned long long)z | ((unsigned long long)w << 32)) : "memory");
}
__device__ __forceinline__ void st_rlx2(uint2* p, uint32_t x, uint32_t y) { asm volatile("st.relaxed.gpu.global.b64 [%0], %1;" :: "l"(p), "l"((unsigned long long)x | ((unsigned long long)y << 32)) : "memory"); }
__device__ __forceinline__ void st_release(uint32_t* p, uint32_t v) { asm volatile("st.release.gpu.global.u32 [%0], %1;" :: "l"(p), "r"(v) : "memory"); }
__device__ __forceinline__ uint32_t ld_acquire(const uint32_t* p) { uint32_t v; asm volatile("ld.acquire.gpu.global.u32 %0, [%1];" : "=r"(v) : "l"(p) : "memory"); return v; }
__device__ __forceinline__ void prefetch_map(const CUtensorMap* m) { asm volatile("prefetch.tensormap [%0];" :: "l"(m) : "memory"); }
__device__ __forceinline__ float rcp(float x) { float r; asm("rcp.approx.ftz.f32 %0, %1;" : "=f"(r) : "f"(x)); return r; }
__device__ __forceinline__ float ex2(float x) { float r; asm("ex2.approx.ftz.f32 %0, %1;" : "=f"(r) : "f"(x)); return r; }
__device__ __forceinline__ float tanh_fast(float x) { float r; asm("tanh.approx.f32 %0, %1;" : "=f"(r) : "f"(x)); return r; }
#define SPIN_GUARD(n) if (++(n) > (1u << 24)) bail()

__device__ __forceinline__ void wgmma_n128(float (&d)[64], uint64_t da, uint64_t db) {
  asm volatile("wgmma.mma_async.sync.aligned.m64n128k16.f32.bf16.bf16 "
    "{%0, %1, %2, %3, %4, %5, %6, %7, %8, %9, %10, %11, %12, %13, %14, %15, %16, %17, %18, %19, %20, %21, %22, %23, %24, %25, %26, %27, %28, %29, %30, %31, %32, %33, %34, %35, %36, %37, %38, %39, %40, %41, %42, %43, %44, %45, %46, %47, %48, %49, %50, %51, %52, %53, %54, %55, %56, %57, %58, %59, %60, %61, %62, %63}, "
    "%64, %65, 1, 1, 1, 0, 1;\n"
    : "+f"(d[0]), "+f"(d[1]), "+f"(d[2]), "+f"(d[3]), "+f"(d[4]), "+f"(d[5]), "+f"(d[6]), "+f"(d[7]), "+f"(d[8]), "+f"(d[9]), "+f"(d[10]), "+f"(d[11]), "+f"(d[12]), "+f"(d[13]), "+f"(d[14]), "+f"(d[15]), "+f"(d[16]), "+f"(d[17]), "+f"(d[18]), "+f"(d[19]), "+f"(d[20]), "+f"(d[21]), "+f"(d[22]), "+f"(d[23]), "+f"(d[24]), "+f"(d[25]), "+f"(d[26]), "+f"(d[27]), "+f"(d[28]), "+f"(d[29]), "+f"(d[30]), "+f"(d[31]), "+f"(d[32]), "+f"(d[33]), "+f"(d[34]), "+f"(d[35]), "+f"(d[36]), "+f"(d[37]), "+f"(d[38]), "+f"(d[39]), "+f"(d[40]), "+f"(d[41]), "+f"(d[42]), "+f"(d[43]), "+f"(d[44]), "+f"(d[45]), "+f"(d[46]), "+f"(d[47]), "+f"(d[48]), "+f"(d[49]), "+f"(d[50]), "+f"(d[51]), "+f"(d[52]), "+f"(d[53]), "+f"(d[54]), "+f"(d[55]), "+f"(d[56]), "+f"(d[57]), "+f"(d[58]), "+f"(d[59]), "+f"(d[60]), "+f"(d[61]), "+f"(d[62]), "+f"(d[63])
    : "l"(da), "l"(db));
}
__device__ __forceinline__ void wgmma_n128_first(float (&d)[64], uint64_t da, uint64_t db) {
  asm volatile("wgmma.mma_async.sync.aligned.m64n128k16.f32.bf16.bf16 "
    "{%0, %1, %2, %3, %4, %5, %6, %7, %8, %9, %10, %11, %12, %13, %14, %15, %16, %17, %18, %19, %20, %21, %22, %23, %24, %25, %26, %27, %28, %29, %30, %31, %32, %33, %34, %35, %36, %37, %38, %39, %40, %41, %42, %43, %44, %45, %46, %47, %48, %49, %50, %51, %52, %53, %54, %55, %56, %57, %58, %59, %60, %61, %62, %63}, "
    "%64, %65, 0, 1, 1, 0, 1;\n"
    : "=f"(d[0]), "=f"(d[1]), "=f"(d[2]), "=f"(d[3]), "=f"(d[4]), "=f"(d[5]), "=f"(d[6]), "=f"(d[7]), "=f"(d[8]), "=f"(d[9]), "=f"(d[10]), "=f"(d[11]), "=f"(d[12]), "=f"(d[13]), "=f"(d[14]), "=f"(d[15]), "=f"(d[16]), "=f"(d[17]), "=f"(d[18]), "=f"(d[19]), "=f"(d[20]), "=f"(d[21]), "=f"(d[22]), "=f"(d[23]), "=f"(d[24]), "=f"(d[25]), "=f"(d[26]), "=f"(d[27]), "=f"(d[28]), "=f"(d[29]), "=f"(d[30]), "=f"(d[31]), "=f"(d[32]), "=f"(d[33]), "=f"(d[34]), "=f"(d[35]), "=f"(d[36]), "=f"(d[37]), "=f"(d[38]), "=f"(d[39]), "=f"(d[40]), "=f"(d[41]), "=f"(d[42]), "=f"(d[43]), "=f"(d[44]), "=f"(d[45]), "=f"(d[46]), "=f"(d[47]), "=f"(d[48]), "=f"(d[49]), "=f"(d[50]), "=f"(d[51]), "=f"(d[52]), "=f"(d[53]), "=f"(d[54]), "=f"(d[55]), "=f"(d[56]), "=f"(d[57]), "=f"(d[58]), "=f"(d[59]), "=f"(d[60]), "=f"(d[61]), "=f"(d[62]), "=f"(d[63])
    : "l"(da), "l"(db));
}
__device__ __forceinline__ void wgmma_n256(float (&d)[128], uint64_t da, uint64_t db) {
  asm volatile("wgmma.mma_async.sync.aligned.m64n256k16.f32.bf16.bf16 "
    "{%0, %1, %2, %3, %4, %5, %6, %7, %8, %9, %10, %11, %12, %13, %14, %15, %16, %17, %18, %19, %20, %21, %22, %23, %24, %25, %26, %27, %28, %29, %30, %31, %32, %33, %34, %35, %36, %37, %38, %39, %40, %41, %42, %43, %44, %45, %46, %47, %48, %49, %50, %51, %52, %53, %54, %55, %56, %57, %58, %59, %60, %61, %62, %63, %64, %65, %66, %67, %68, %69, %70, %71, %72, %73, %74, %75, %76, %77, %78, %79, %80, %81, %82, %83, %84, %85, %86, %87, %88, %89, %90, %91, %92, %93, %94, %95, %96, %97, %98, %99, %100, %101, %102, %103, %104, %105, %106, %107, %108, %109, %110, %111, %112, %113, %114, %115, %116, %117, %118, %119, %120, %121, %122, %123, %124, %125, %126, %127}, "
    "%128, %129, 1, 1, 1, 0, 1;\n"
    : "+f"(d[0]), "+f"(d[1]), "+f"(d[2]), "+f"(d[3]), "+f"(d[4]), "+f"(d[5]), "+f"(d[6]), "+f"(d[7]), "+f"(d[8]), "+f"(d[9]), "+f"(d[10]), "+f"(d[11]), "+f"(d[12]), "+f"(d[13]), "+f"(d[14]), "+f"(d[15]), "+f"(d[16]), "+f"(d[17]), "+f"(d[18]), "+f"(d[19]), "+f"(d[20]), "+f"(d[21]), "+f"(d[22]), "+f"(d[23]), "+f"(d[24]), "+f"(d[25]), "+f"(d[26]), "+f"(d[27]), "+f"(d[28]), "+f"(d[29]), "+f"(d[30]), "+f"(d[31]), "+f"(d[32]), "+f"(d[33]), "+f"(d[34]), "+f"(d[35]), "+f"(d[36]), "+f"(d[37]), "+f"(d[38]), "+f"(d[39]), "+f"(d[40]), "+f"(d[41]), "+f"(d[42]), "+f"(d[43]), "+f"(d[44]), "+f"(d[45]), "+f"(d[46]), "+f"(d[47]), "+f"(d[48]), "+f"(d[49]), "+f"(d[50]), "+f"(d[51]), "+f"(d[52]), "+f"(d[53]), "+f"(d[54]), "+f"(d[55]), "+f"(d[56]), "+f"(d[57]), "+f"(d[58]), "+f"(d[59]), "+f"(d[60]), "+f"(d[61]), "+f"(d[62]), "+f"(d[63]), "+f"(d[64]), "+f"(d[65]), "+f"(d[66]), "+f"(d[67]), "+f"(d[68]), "+f"(d[69]), "+f"(d[70]), "+f"(d[71]), "+f"(d[72]), "+f"(d[73]), "+f"(d[74]), "+f"(d[75]), "+f"(d[76]), "+f"(d[77]), "+f"(d[78]), "+f"(d[79]), "+f"(d[80]), "+f"(d[81]), "+f"(d[82]), "+f"(d[83]), "+f"(d[84]), "+f"(d[85]), "+f"(d[86]), "+f"(d[87]), "+f"(d[88]), "+f"(d[89]), "+f"(d[90]), "+f"(d[91]), "+f"(d[92]), "+f"(d[93]), "+f"(d[94]), "+f"(d[95]), "+f"(d[96]), "+f"(d[97]), "+f"(d[98]), "+f"(d[99]), "+f"(d[100]), "+f"(d[101]), "+f"(d[102]), "+f"(d[103]), "+f"(d[104]), "+f"(d[105]), "+f"(d[106]), "+f"(d[107]), "+f"(d[108]), "+f"(d[109]), "+f"(d[110]), "+f"(d[111]), "+f"(d[112]), "+f"(d[113]), "+f"(d[114]), "+f"(d[115]), "+f"(d[116]), "+f"(d[117]), "+f"(d[118]), "+f"(d[119]), "+f"(d[120]), "+f"(d[121]), "+f"(d[122]), "+f"(d[123]), "+f"(d[124]), "+f"(d[125]), "+f"(d[126]), "+f"(d[127])
    : "l"(da), "l"(db));
}
__device__ __forceinline__ void wgmma_n256_first(float (&d)[128], uint64_t da, uint64_t db) {
  asm volatile("wgmma.mma_async.sync.aligned.m64n256k16.f32.bf16.bf16 "
    "{%0, %1, %2, %3, %4, %5, %6, %7, %8, %9, %10, %11, %12, %13, %14, %15, %16, %17, %18, %19, %20, %21, %22, %23, %24, %25, %26, %27, %28, %29, %30, %31, %32, %33, %34, %35, %36, %37, %38, %39, %40, %41, %42, %43, %44, %45, %46, %47, %48, %49, %50, %51, %52, %53, %54, %55, %56, %57, %58, %59, %60, %61, %62, %63, %64, %65, %66, %67, %68, %69, %70, %71, %72, %73, %74, %75, %76, %77, %78, %79, %80, %81, %82, %83, %84, %85, %86, %87, %88, %89, %90, %91, %92, %93, %94, %95, %96, %97, %98, %99, %100, %101, %102, %103, %104, %105, %106, %107, %108, %109, %110, %111, %112, %113, %114, %115, %116, %117, %118, %119, %120, %121, %122, %123, %124, %125, %126, %127}, "
    "%128, %129, 0, 1, 1, 0, 1;\n"
    : "=f"(d[0]), "=f"(d[1]), "=f"(d[2]), "=f"(d[3]), "=f"(d[4]), "=f"(d[5]), "=f"(d[6]), "=f"(d[7]), "=f"(d[8]), "=f"(d[9]), "=f"(d[10]), "=f"(d[11]), "=f"(d[12]), "=f"(d[13]), "=f"(d[14]), "=f"(d[15]), "=f"(d[16]), "=f"(d[17]), "=f"(d[18]), "=f"(d[19]), "=f"(d[20]), "=f"(d[21]), "=f"(d[22]), "=f"(d[23]), "=f"(d[24]), "=f"(d[25]), "=f"(d[26]), "=f"(d[27]), "=f"(d[28]), "=f"(d[29]), "=f"(d[30]), "=f"(d[31]), "=f"(d[32]), "=f"(d[33]), "=f"(d[34]), "=f"(d[35]), "=f"(d[36]), "=f"(d[37]), "=f"(d[38]), "=f"(d[39]), "=f"(d[40]), "=f"(d[41]), "=f"(d[42]), "=f"(d[43]), "=f"(d[44]), "=f"(d[45]), "=f"(d[46]), "=f"(d[47]), "=f"(d[48]), "=f"(d[49]), "=f"(d[50]), "=f"(d[51]), "=f"(d[52]), "=f"(d[53]), "=f"(d[54]), "=f"(d[55]), "=f"(d[56]), "=f"(d[57]), "=f"(d[58]), "=f"(d[59]), "=f"(d[60]), "=f"(d[61]), "=f"(d[62]), "=f"(d[63]), "=f"(d[64]), "=f"(d[65]), "=f"(d[66]), "=f"(d[67]), "=f"(d[68]), "=f"(d[69]), "=f"(d[70]), "=f"(d[71]), "=f"(d[72]), "=f"(d[73]), "=f"(d[74]), "=f"(d[75]), "=f"(d[76]), "=f"(d[77]), "=f"(d[78]), "=f"(d[79]), "=f"(d[80]), "=f"(d[81]), "=f"(d[82]), "=f"(d[83]), "=f"(d[84]), "=f"(d[85]), "=f"(d[86]), "=f"(d[87]), "=f"(d[88]), "=f"(d[89]), "=f"(d[90]), "=f"(d[91]), "=f"(d[92]), "=f"(d[93]), "=f"(d[94]), "=f"(d[95]), "=f"(d[96]), "=f"(d[97]), "=f"(d[98]), "=f"(d[99]), "=f"(d[100]), "=f"(d[101]), "=f"(d[102]), "=f"(d[103]), "=f"(d[104]), "=f"(d[105]), "=f"(d[106]), "=f"(d[107]), "=f"(d[108]), "=f"(d[109]), "=f"(d[110]), "=f"(d[111]), "=f"(d[112]), "=f"(d[113]), "=f"(d[114]), "=f"(d[115]), "=f"(d[116]), "=f"(d[117]), "=f"(d[118]), "=f"(d[119]), "=f"(d[120]), "=f"(d[121]), "=f"(d[122]), "=f"(d[123]), "=f"(d[124]), "=f"(d[125]), "=f"(d[126]), "=f"(d[127])
    : "l"(da), "l"(db));
}

template <int N> struct WG;
#define DEF_WG(N) template <> struct WG<N> { \
  static __device__ __forceinline__ void mma(float (&d)[N / 2], uint64_t a, uint64_t b) { wgmma_n##N(d, a, b); } \
  static __device__ __forceinline__ void first(float (&d)[N / 2], uint64_t a, uint64_t b) { wgmma_n##N##_first(d, a, b); } };
DEF_WG(128) DEF_WG(256)

constexpr uint64_t DESC_A = (1ull << 62) | ((uint64_t)(1024 >> 4) << 32) | (1ull << 16);
constexpr uint64_t DESC_B = (1ull << 62) | ((uint64_t)(1024 >> 4) << 32) | ((uint64_t)(8192 >> 4) << 16);

struct Ring { int s; uint32_t ph; int wrap; };
template <int NS> __device__ __forceinline__ void ring_next(Ring& r) { r.s = (r.s + 1 == NS) ? 0 : r.s + 1; if (r.s == r.wrap) r.ph ^= 1; }

__device__ __forceinline__ int own_order(int it, int j) {
  return it < 2 ? 2 * j + it : it < 4 ? 2 * (j ^ 1) + it - 2 : ((j >> 1) * 4 + 2 * it - (it < 10 ? 4 : 15)) & 15;
}

template <int V> struct IC { static constexpr int v = V; };
template <int I, int E, class F> __device__ __forceinline__ void static_for(F&& f) { if constexpr (I < E) { f(IC<I>{}); static_for<I + 1, E>(f); } }

template <int N, int NS, int PRE, int LAG, class Pre, class Mid, class Last>
__device__ __forceinline__ void mainloop(float (&acc)[N / 2], int nkb, bool own, Ring& r, uint32_t sb, int wg, int lane, uint32_t rel_base, Pre pre, Mid mid, Last last) {
  constexpr int SLOT = RING / NS;
  const uint32_t full = sb + MISC + (NS == 4 ? B_FULL4 : B_FULL6);
  const uint32_t rel = rel_base + (NS == 4 ? B_EMPTY4 : B_EMPTY6);
  const uint32_t s0 = (sb & 0x3FFFF) >> 4, a0 = s0 + wg * (HALF >> 4);
  int ps;
  auto issue = [&](int it, bool first) {
    const uint64_t da = DESC_A | (a0 + ((own && it < 2) ? (STG + it * BLK) >> 4 : r.s * (SLOT >> 4))), db = DESC_B | (s0 + r.s * (SLOT >> 4) + (BLK >> 4));
    mbar_wait(full + r.s * 8, r.ph);
    wg_arrive();
    if (first) WG<N>::first(acc, da, db); else WG<N>::mma(acc, da, db);
#pragma unroll
    for (int k = 1; k < 4; k++) WG<N>::mma(acc, da + k * 2, db + k * 128);
    wg_commit();
  };
  auto retire = [&](int it) {
    wg_wait<1>();
    if (lane < 2) mbar_arrive_cl(rel + ps * 8);
    ps = r.s;
    ring_next<NS>(r);
  };
  issue(0, true);
  ps = r.s;
  ring_next<NS>(r);
  static_for<1, PRE + 1>([&](auto ic) { issue(ic.v, false); pre(ic); retire(ic.v); });
#pragma unroll 1
  for (int it = PRE + 1; it < nkb; it++) {
    if (LAG && it == nkb - LAG && wg == 1) mbar_wait(sb + MISC + B_LAG, WOLAG && !own);
    issue(it, false); mid(it); retire(it);
  }
  last();
  wg_wait<0>();
  if (lane < 2) mbar_arrive_cl(rel + ps * 8);
}

__device__ __forceinline__ uint32_t tag_of(uint32_t ep) { return ep % 255u + 1u; }
__device__ __forceinline__ void ln_publish(const float (&v)[64], uint2* st, int j, int row0, int lane, uint32_t ep) {
  float s0 = 0, s1 = 0, s2 = 0, s3 = 0, q0 = 0, q1 = 0, q2 = 0, q3 = 0;
#pragma unroll
  for (int i = 0; i < 16; i++) {
    s0 += v[4 * i]; s1 += v[4 * i + 1]; s2 += v[4 * i + 2]; s3 += v[4 * i + 3];
    q0 = fmaf(v[4 * i], v[4 * i], q0); q1 = fmaf(v[4 * i + 1], v[4 * i + 1], q1); q2 = fmaf(v[4 * i + 2], v[4 * i + 2], q2); q3 = fmaf(v[4 * i + 3], v[4 * i + 3], q3);
  }
  s0 += s1; s2 += s3; q0 += q1; q2 += q3;
  const bool odd = lane & 1;
  float s = (odd ? s2 : s0) + __shfl_xor_sync(~0u, odd ? s0 : s2, 1), q = (odd ? q2 : q0) + __shfl_xor_sync(~0u, odd ? q0 : q2, 1);
  s += __shfl_xor_sync(~0u, s, 2); q += __shfl_xor_sync(~0u, q, 2);
  if ((lane & 3) < 2) st_rlx2(st + j * 128 + row0 + (lane & 1) * 8, __float_as_uint(s), (__float_as_uint(fmaf(s * (-1.f / 128), s, q)) & ~255u) | tag_of(ep));
}
__device__ __forceinline__ void ln_gather(const uint2* st, int row0, int lane, uint32_t ep, float& n0, float& r0, float& n1, float& r1, bool rnd) {
  const uint2* p = st + (lane & 2) * 256 + row0 + (lane & 1) * 8;
  const uint32_t tag = tag_of(ep);
  uint2 a, b, c, d; uint32_t n = 0;
  while (true) {
    a = ld_rlx2(p); b = ld_rlx2(p + 128); c = ld_rlx2(p + 256); d = ld_rlx2(p + 384);
    if ((((a.y ^ tag) | (b.y ^ tag) | (c.y ^ tag) | (d.y ^ tag)) & 255u) == 0) break;
    SPIN_GUARD(n);
  }
  __syncwarp();
  const uint32_t fix = tag ^ 128u;
  float s = (__uint_as_float(a.x) + __uint_as_float(b.x)) + (__uint_as_float(c.x) + __uint_as_float(d.x));
  float q = (__uint_as_float(a.y ^ fix) + __uint_as_float(b.y ^ fix)) + (__uint_as_float(c.y ^ fix) + __uint_as_float(d.y ^ fix));
  q = fmaf(fmaf(__uint_as_float(a.x), __uint_as_float(a.x), __uint_as_float(b.x) * __uint_as_float(b.x)) +
           fmaf(__uint_as_float(c.x), __uint_as_float(c.x), __uint_as_float(d.x) * __uint_as_float(d.x)), 1.f / 128, q);
  s += __shfl_xor_sync(~0u, s, 2); q += __shfl_xor_sync(~0u, q, 2);
  s *= 1.f / 1024;
  const float var = fmaxf(fmaf(-s, s, q * (1.f / 1024)), 0.f);
  float r;
  if (rnd) {
    float sd; asm("sqrt.approx.f32 %0, %1;" : "=f"(sd) : "f"(bf_round(bf_round(var) + 1e-5f)));
    r = rcp(bf_round(sd)); s = bf_round(s);
  } else r = rsqrtf(var + 1e-5f);
  const float nn = -s * r;
  const float ro = __shfl_xor_sync(~0u, r, 1), no = __shfl_xor_sync(~0u, nn, 1);
  const bool odd = lane & 1;
  r0 = odd ? ro : r; n0 = odd ? no : nn; r1 = odd ? r : ro; n1 = odd ? nn : no;
}
__device__ __forceinline__ void load_vec(uint32_t* w, uint32_t sb, int sec, int b, int lane) {
#pragma unroll
  for (int q = 0; q < 2; q++) { uint4 t = lds128(sb + MISC + MODV + sec * 256 + (lane & 3) * 64 + b * 32 + q * 16); w[4 * q] = t.x; w[4 * q + 1] = t.y; w[4 * q + 2] = t.z; w[4 * q + 3] = t.w; }
}
__device__ __forceinline__ void stage_done(uint32_t sb, int wg, int b, int lane) {
  fence_async_smem();
  __syncwarp();
  if (lane == 0) mbar_arrive(sb + MISC + B_RDY + b * 8);
}
__device__ __forceinline__ uint32_t hfma2(uint32_t a, uint32_t b, uint32_t c) { uint32_t r; asm("fma.rn.bf16x2 %0, %1, %2, %3;" : "=r"(r) : "r"(a), "r"(b), "r"(c)); return r; }
__device__ __forceinline__ void ln_apply(const float (&v)[64], const uint2* st, int row0, uint32_t ep, uint32_t sb, int sec_shift, int sec_scale, uint32_t stg_row, int wg, int lane) {
  uint32_t sc[16], sh[16];
#pragma unroll
  for (int b = 0; b < 2; b++) { load_vec(sc + 8 * b, sb, sec_scale, b, lane); load_vec(sh + 8 * b, sb, sec_shift, b, lane); }
  float n0, r0, n1, r1;
  ln_gather(st, row0, lane, ep, n0, r0, n1, r1, sec_shift == 0);
#pragma unroll
  for (int i = 0; i < 16; i += 2) {
    if (i == 8) { const float z = lds32f(sb + MISC + ZERO); n0 += z; n1 += z; }
    uint32_t w[4];
#pragma unroll
    for (int u = 0; u < 2; u++) {
      int q = i + u;
      w[2 * u] = hfma2(pack2(fmaf(v[4 * q], r0, n0), fmaf(v[4 * q + 1], r0, n0)), sc[q], sh[q]);
      w[2 * u + 1] = hfma2(pack2(fmaf(v[4 * q + 2], r1, n1), fmaf(v[4 * q + 3], r1, n1)), sc[q], sh[q]);
    }
    stsm4(stg_row + (i >> 3) * BLK + ((((i & 7) + (lane >> 4)) ^ (lane & 7)) << 4), w[0], w[1], w[2], w[3]);
    if ((i & 7) == 6) { stage_done(sb, wg, i >> 3, lane); }
  }
}
__device__ __forceinline__ uint32_t hmul2(uint32_t a, uint32_t b) { uint32_t r; asm("mul.rn.bf16x2 %0, %1, %2;" : "=r"(r) : "r"(a), "r"(b)); return r; }
__device__ __forceinline__ uint32_t silu_mul2(uint32_t g, uint32_t u) {
  const uint32_t h = hmul2(g, 0x3f003f00u);
  const float h0 = bf_lo(h), h1 = bf_hi(h);
  return hmul2(pack2(fmaf(h0, tanh_fast(h0), h0), fmaf(h1, tanh_fast(h1), h1)), u);
}

__device__ __forceinline__ void gemv_fma(float (&a)[8], uint4 w, float s) {
  a[0] = fmaf(bf_lo(w.x), s, a[0]); a[1] = fmaf(bf_hi(w.x), s, a[1]); a[2] = fmaf(bf_lo(w.y), s, a[2]); a[3] = fmaf(bf_hi(w.y), s, a[3]);
  a[4] = fmaf(bf_lo(w.z), s, a[4]); a[5] = fmaf(bf_hi(w.z), s, a[5]); a[6] = fmaf(bf_lo(w.w), s, a[6]); a[7] = fmaf(bf_hi(w.w), s, a[7]);
}
__device__ __forceinline__ float silu_c(float v) { return bf_round(__fdividef(v, 1.f + __expf(-v))); }
__device__ __forceinline__ float mod_gather(const uint2* p, uint32_t ep) {
  uint2 a, b, c, d; uint32_t n = 0;
  while (true) {
    a = ld_rlx2(p); b = ld_rlx2(p + 128); c = ld_rlx2(p + 256); d = ld_rlx2(p + 384);
    if (a.y == ep && b.y == ep && c.y == ep && d.y == ep) break;
    SPIN_GUARD(n);
  }
  return (__uint_as_float(a.x) + __uint_as_float(b.x)) + (__uint_as_float(c.x) + __uint_as_float(d.x));
}
__device__ __forceinline__ void mod_store(uint32_t sb, int sec, int col, float v) {
  v = bf_round(v);
  if (sec == 1 || sec == 4) v += 1.f;
  sts16(sb + MISC + MODV + sec * 256 + (((col >> 1) & 3) * 16 + (col >> 3)) * 4 + (col & 1) * 2, __float2bfloat16_rn(v));
}

__global__ void __cluster_dims__(2, 1, 1) __launch_bounds__(384, 1)
fused_kernel(const bf16* __restrict__ cvec, const bf16* __restrict__ wmod, Scratch* gs, int by_sm, const __grid_constant__ Maps maps) {
  extern __shared__ __align__(1024) uint8_t smem_raw[];
  const uint32_t sb = smem_u32(smem_raw);
  const int warp = __shfl_sync(~0u, threadIdx.x >> 5, 0), lane = threadIdx.x & 31;
  const int rank = blockIdx.x & 1;
  uint32_t sm; asm volatile("mov.u32 %0, %%smid;" : "=r"(sm));
  const int t = sm >> 1, v = t < 32 ? t : t < 60 ? t + 1 + (((t - 32) * 37) >> 8) : (t - 58) * 8;
  const int cid = !by_sm ? (blockIdx.x >> 1) - 2 : (t & ~1) == 60 ? t - 62 : (v & 1) * 32 + ((v >> 1) & 31);
  const bool extra = cid < 0;
  const int bid = cid * 2 + rank;
  const int m = cid >> 2, j = (cid & 3) * 2 + rank;
  const uint32_t bar = sb + MISC;

  if (warp >= 8) {
    asm volatile("setmaxnreg.dec.sync.aligned.u32 40;");
    if (extra) {
      if (warp == 8) {
        if (lane == 0) { for (int s = 0; s < 6; s++) { mbar_init(bar + B_FULL6 + s * 8, 1); mbar_init(bar + B_EMPTY6 + s * 8, 8); } fence_async_smem(); }
        __syncwarp();
        asm volatile("bar.arrive 2, 288;" ::: "memory");
        __nanosleep(XSLEEP);
#pragma unroll 1
        for (int it = 0, s = 0, par = 1; it < 64; it++) {
          mbar_wait(bar + B_EMPTY6 + s * 8, par);
          if (elect()) { mbar_expect_tx(bar + B_FULL6 + s * 8, 32768); tma_3d(sb + s * 32768, &maps.wmod, bar + B_FULL6 + s * 8, 0, (it & 15) * 64, 12 + (it >> 4) * 4 + bid); }
          if (++s == 6) { s = 0; par ^= 1; }
        }
      }
    } else if (warp < 10) {
      uint32_t s6 = 0, p6 = 1;
      auto next6 = [&]() { if (++s6 == 6) { s6 = 0; p6 ^= 1; } };
      auto drained4 = [&](int q, int late) { if (q < 5) mbar_wait(bar + B_EMPTY4 + (((late ? 0x10332 : 0x32110) >> (4 * q)) & 3) * 8, 1); };
      auto drained6 = [&](int q) { if (q < 3) mbar_wait(bar + B_EMPTY6 + ((0x154 >> (4 * q)) & 7) * 8, q >> 1); };
      auto skip6 = [&]() { mbar_wait(bar + B_EMPTY6 + s6 * 8, p6); if (elect()) mbar_arrive(bar + B_FULL6 + s6 * 8); next6(); };
      if (warp == 8) {
        const uint32_t t_start = clock();
        if (lane == 0) {
          if (sb & 1023) bail();
          for (int b = 0; b < 2; b++) mbar_init(bar + B_X + b * 8, 1);
          for (int s = 0; s < 4; s++) { mbar_init(bar + B_FULL4 + s * 8, 2); mbar_init(bar + B_EMPTY4 + s * 8, 16); }
          for (int s = 0; s < 6; s++) { mbar_init(bar + B_FULL6 + s * 8, 2); mbar_init(bar + B_EMPTY6 + s * 8, 16); }
          for (int b = 0; b < 2; b++) { mbar_init(bar + B_RDY + b * 8, 8); mbar_init(bar + B_FREE + b * 8, 1); mbar_init(bar + B_HH + b * 8, 1); }
          mbar_init(bar + B_MOD, 1); mbar_init(bar + B_LAG, 4); mbar_init(bar + B_HALO, 2); mbar_init(bar + B_ALL, 1); mbar_init(bar + B_HH2, 1);
          asm volatile("st.shared.u32 [%0], 0;" :: "r"(bar + ZERO) : "memory");
          asm volatile("fence.mbarrier_init.release.cluster;" ::: "memory");
          fence_async_smem();
        }
        __syncwarp();
        cl_arrive_relaxed();
        auto wide = [&](int s, int par, const CUtensorMap* m0, int a0, const CUtensorMap* m1, int a1, int kb, bool spaced) {
          const uint32_t full = bar + B_FULL4 + s * 8, d = sb + s * 49152 + BLK;
          mbar_wait(full + 32, par);
          const uint32_t t0 = clock();
          if (elect()) { mbar_expect_tx(full, 2 * BLK); tma_3d(d, m0, full, 0, kb * 64, a0); }
          if (spaced) while ((uint32_t)clock() - t0 < 300) {}
          if (elect()) tma_3d(d + BLK, m1, full, 0, kb * 64, a1);
          if (spaced) while ((uint32_t)clock() - t0 < 600) {}
        };
        auto narrow = [&](const CUtensorMap* m0, int kb) {
          const uint32_t full = bar + B_FULL6 + s6 * 8;
          mbar_wait(full + 48, p6);
          if (elect()) { mbar_expect_tx(full, BLK); tma_3d(sb + s6 * 32768 + BLK, m0, full, 0, kb * 64, 2 * j); }
          next6();
        };
#pragma unroll 1
        for (int it = 0; it < 16; it++) {
          if (it == 0) {
            while ((uint32_t)clock() - t_start < XDELAY) {}
            if (elect()) for (int b = 0; b < 2; b++) { mbar_expect_tx(bar + B_X + b * 8, BLK); tma_3d(sb + STG + b * BLK, &maps.x, bar + B_X + b * 8, j * 128 + b * 64, m * 64, 0); }
            mbar_wait(bar + B_X + 8, 0);
          }
          wide(it & 3, ~(it >> 2) & 1, &maps.wqkv, 16 + 2 * j, &maps.wqkv, 32 + 2 * j, own_order(it, j), it < 4);
        }
#pragma unroll 1
        for (int it = 0; it < 16; it++) { drained4(it, 0); narrow(&maps.wqkv, it); }
#pragma unroll 1
        for (int it = 0; it < 16; it++) narrow(&maps.wo, own_order(it, j));
        skip6();
#pragma unroll 1
        for (int it = 0; it < 48; it++) {
          const int s = (it + 2) & 3, par = ~(it >> 2) & 1;
          drained6(it);
          wide(s, par, &maps.w1, (it & 48) + 2 * j, &maps.w3, (it & 48) + 2 * j, it < 16 ? own_order(it, j) : it & 15, it < 4);
          if (it >= 44) {
            if (it == 44) { mbar_wait(bar + B_FREE, 0); mbar_wait(bar + B_FREE + 8, 0); if (elect()) mbar_expect_tx(bar + B_X, 2 * BLK); }
            if (elect()) bulk_ld(sb + STG + (it - 44) * HALF, gs->x1 + bid * 2048 + (it - 44) * 512, HALF, bar + B_X);
          }
        }
#pragma unroll 1
        for (int it = 0; it < 16; it++) {
          const uint32_t full = bar + B_FULL6 + s6 * 8, d = sb + s6 * 32768 + BLK;
          drained4(it, 1);
          mbar_wait(full + 48, p6);
          if (elect()) { mbar_expect_tx(full, BLK); tma_3d(d, &maps.w1s, full, 0, it * 64, 48 + j); tma_3d(d + HALF, &maps.w3s, full, 0, it * 64, 48 + j); }
          next6();
        }
#pragma unroll 1
        for (int it = 0; it < 56; it++) narrow(&maps.w2, it);
      } else {
        if (lane < 9) prefetch_map(&maps.x + lane);
        const uint32_t ep = gs->epoch[bid + 4] + 1;
        cl_arrive_relaxed(); cl_wait();
        auto plain = [&](uint32_t full, uint32_t empty, int par, uint32_t slot, const uint4* blk) {
          mbar_wait(empty, par);
          if (elect()) { mbar_expect_tx(full, BLK); bulk_ld_mc(slot + rank * HALF, blk + rank * 512, HALF, full); }
        };
        auto plain6 = [&](const uint4* blk) { plain(bar + B_FULL6 + s6 * 8, bar + B_EMPTY6 + s6 * 8, p6, sb + s6 * 32768, blk); next6(); };
        uint32_t ready = 0;
        auto poll = [&](int e) { ready = __ballot_sync(~0u, ld_acquire(gs->flag + (m * 128 + e * 16 + (lane & 14)) * FS) == ep); };
        auto need = [&](int e, uint32_t mask) {
          if ((ready & mask) != mask) {
            uint32_t n = 0;
            do { poll(e); SPIN_GUARD(n); } while ((ready & mask) != mask);
            fence_async_global();
          }
        };
        auto fresh = [&](int e, int it, uint32_t full, uint32_t empty, int par, uint32_t slot, uint4* src) {
          if (it >= 4) {
            const int kb = own_order(it, j);
            if (it < 10) need(e, 1u << kb); else if (it == 10) mbar_wait(bar + B_ALL, e & 1);
            plain(full, empty, par, slot, src + kb * 1024);
          } else {
            if (it == 0) ready = 0;
            mbar_wait(empty, par);
            if (it < 2) { if (elect()) mbar_arrive(full); }
            else {
              const int b = it > 2;
              const uint32_t to_peer = mapa(sb, rank ^ 1) - sb;
              if (elect()) mbar_expect_tx(full, BLK);
              const bool push = e != 1;
              mbar_wait(bar + (b ? (push ? B_RDY + 8 : B_FREE + 8) : B_RDY), e & 1);
              if (elect()) {
                if (b == 0) {
                  bulk_st(src + 2 * j * 1024, sb + STG, BLK);
                  bulk_commit();
                  bulk_wait_all();
                  mbar_arrive(bar + B_FREE);
                }
                if (b && push) bulk_push(slot + to_peer, sb + STG + BLK, BLK, full + to_peer);
                else {
                  fence_async_global();
                  bulk_ld(slot + to_peer, src + (2 * j + b) * 1024, BLK, full + to_peer);
                }
              }
              __syncwarp();
            }
          }
        };
#pragma unroll 1
        for (int ph = 0; ph < 2; ph++) {
          uint4* h = gs->h + m * 16384;
#pragma unroll 1
          for (int it = 0; it < 16; it++) {
            const int s = (it + 2 * ph) & 3;
            if (ph) drained6(it);
            fresh(2 * ph, it, bar + B_FULL4 + s * 8, bar + B_EMPTY4 + s * 8, ~(it >> 2) & 1, sb + s * 49152, h);
          }
          if (ph) {
#pragma unroll 1
            for (int it = 16; it < 48; it++) {
              const int s = (it + 2) & 3;
              const uint32_t full = bar + B_FULL4 + s * 8;
              plain(full, full + 32, ~(it >> 2) & 1, sb + s * 49152, h + (it & 15) * 1024);
            }
          }
#pragma unroll 1
          for (int it = 0; it < 16; it++) { drained4(it, ph); plain6(h + it * 1024); }
          if (!ph) {
#pragma unroll 1
            for (int it = 0; it < 16; it++) { fresh(1, it, bar + B_FULL6 + s6 * 8, bar + B_EMPTY6 + s6 * 8, p6, sb + s6 * 32768, gs->o + m * 16384); next6(); }
            skip6();
          }
        }
#pragma unroll 1
        for (int it = 0; it < 56; it++) {
          if (it == 0 || it == 32 || it == 48) mbar_wait(bar + (it == 48 ? B_HH2 : B_HH + (it >> 2)), 0);
          plain6(gs->hh + m * 57344 + it * 1024);
        }
      }
    } else {
      const int b = warp - 10;
      const uint32_t ep = gs->epoch[bid + 4] + 1;
      const uint32_t stg = sb + STG + b * BLK;
      cl_arrive_relaxed(); cl_wait();
      auto all_there = [&](int u, uint32_t done) {
        const uint32_t* fl = gs->flag + u * FS;
        uint32_t n = 0;
        while (!__all_sync(~0u, ld_acquire(fl) == ep)) { __nanosleep(100); SPIN_GUARD(n); }
        fence_async_global();
        if (lane == 0) mbar_arrive(done);
      };
      auto fetch_mod = [&](int sec) {
        const uint4* p = (const uint4*)(gs->modv + (sec - 2) * 1024 + j * 128) + lane;
        uint4 v0, v1; uint32_t n = 0;
        while (true) {
          v0 = ld_rlx4(p); v1 = ld_rlx4(p + 32);
          if (v0.y == ep && v0.w == ep && v1.y == ep && v1.w == ep) break;
          SPIN_GUARD(n);
        }
        mod_store(sb, sec, 2 * lane, __uint_as_float(v0.x)); mod_store(sb, sec, 2 * lane + 1, __uint_as_float(v0.z));
        mod_store(sb, sec, 64 + 2 * lane, __uint_as_float(v1.x)); mod_store(sb, sec, 65 + 2 * lane, __uint_as_float(v1.z));
        __syncwarp();
      };
#pragma unroll 1
      for (int e = 0; e < 7 - b; e++) {
        if (lane == 0) {
          if (e < 3) {
            mbar_wait(bar + B_FREE, e & 1);
            if (b) {
              const uint32_t t0 = clock();
              while ((uint32_t)clock() - t0 < (e == 0 ? B1P : e == 2 ? B1P2 : B1D)) {}
              mbar_wait(bar + B_RDY + 8, e & 1);
              bulk_st((e == 1 ? gs->o : gs->h) + m * 16384 + (2 * j + 1) * 1024, stg, BLK);
              bulk_commit();
              bulk_wait_all();
              mbar_arrive(bar + B_FREE + 8);
            }
            st_release(gs->flag + (m * 128 + e * 16 + 2 * j + b) * FS, ep);
          } else {
            const int kb = (e < 6 ? 2 * (8 * (e - 3) + j) : 48 + j) + b;
            mbar_wait(bar + B_RDY + b * 8, e & 1);
#pragma unroll 1
            for (int q = 0; q < NPIECE; q++) { if (q) __nanosleep(PSLEEP); bulk_st(gs->hh + m * 57344 + kb * 1024 + q * (1024 / NPIECE), stg + q * (BLK / NPIECE), BLK / NPIECE); }
            bulk_commit();
            bulk_wait_all();
            mbar_arrive(bar + B_FREE + b * 8);
            st_release(gs->flag + (m * 128 + U_HH + kb) * FS, ep);
          }
        }
        __syncwarp();
        if (e < 3 && b) all_there(m * 128 + e * 16 + (lane & 15), bar + B_ALL);
        if (e == 4 && b) all_there(m * 128 + U_HH + lane, bar + B_HH);
        if (!b && (e == 1 || e == 2)) {
#pragma unroll 1
          for (int sec = e == 1 ? 2 : 5; sec < 4 + e; sec++) fetch_mod(sec);
          if (e == 1) { if (lane == 0) mbar_arrive(bar + B_MOD); }
        }
        if (e == 0) {
          mbar_wait(bar + B_EMPTY6 + 24, 0);
          __nanosleep(HSLEEP);
#pragma unroll 1
          for (int w = 0; w < 4; w++) {
            const uint4* hp = gs->halo + ((m * 8 + j) * 2 + (w & 1)) * 512 + b * 256 + (w >> 1) * 128 + lane;
            uint4 q[4] = {}; uint32_t n = 0;
            while (m > 0) {
              bool ok = true;
#pragma unroll
              for (int i = 0; i < 4; i++) q[i] = ld_rlx4(hp + i * 32);
#pragma unroll
              for (int i = 0; i < 4; i++) ok = ok && q[i].y == ep && q[i].w == ep;
              if (ok) break;
              SPIN_GUARD(n);
            }
#pragma unroll
            for (int i = 0; i < 2; i++) sts128(stg + lane * 16 + (w & 1) * HALF + (w >> 1) * 1024 + i * 512, q[2 * i].x, q[2 * i + 1].x, q[2 * i].z, q[2 * i + 1].z);
          }
          __syncwarp();
          if (lane == 0) mbar_arrive(bar + B_HALO);
        }
      }
      if (b) { all_there(m * 128 + U_HH + 32 + (lane & 15), bar + B_HH + 8); all_there(m * 128 + U_HH + 48 + (lane & 7), bar + B_HH2); }
    }
  } else {
    const int wg = warp >> 2, wq = warp & 3, tid = threadIdx.x;
    const int g = lane >> 2, c = lane & 3;
    const int sec0 = (m >> 1) & 1, hf0 = m & 1, ks0 = (m >> 2) & 3;
    uint4 wv[8];
    uint32_t ep0; uint16_t cv_;
    asm volatile("ld.global.nc.u16 %0, [%1];" : "=h"(cv_) : "l"(cvec + ks0 * 256 + warp * 32 + lane));
    asm volatile("ld.global.u32 %0, [%1];" : "=r"(ep0) : "l"(gs->epoch + bid + 4));
    if (!extra) {
      const bf16* wp = wmod + (size_t)(ks0 * 256 + warp * 32 + (lane >> 3)) * 6144 + sec0 * 1024 + j * 128 + hf0 * 64 + (lane & 7) * 8;
#pragma unroll
      for (int i = 0; i < 8; i++) wv[i] = ldg_nc(wp + (size_t)i * 4 * 6144);
    }
    asm volatile("setmaxnreg.inc.sync.aligned.u32 232;" ::: "memory");
    if (__builtin_expect(extra, 0)) {
      const uint32_t ep = ep0 + 1;
      float sv[4];
#pragma unroll
      for (int p = 0; p < 4; p++) sv[p] = silu_c(__bfloat162float(cvec[64 * (4 * p + (lane >> 3)) + 8 * warp + (lane & 7)]));
      named_bar(2, 288);
      int s = 0, par = 0;
#pragma unroll 1
      for (int sec = 0; sec < 4; sec++) {
        float a[8] = {0, 0, 0, 0, 0, 0, 0, 0};
#pragma unroll 1
        for (int it = 0; it < 16; it++) {
          const float sc = it < 4 ? sv[0] : it < 8 ? sv[1] : it < 12 ? sv[2] : sv[3];
          mbar_wait(bar + B_FULL6 + s * 8, par);
          uint4 w[8];
#pragma unroll
          for (int i = 0; i < 8; i++) w[i] = lds128(sb + s * 32768 + (warp * 8 + i) * 512 + lane * 16);
#pragma unroll
          for (int i = 0; i < 8; i++) gemv_fma(a, w[i], __shfl_sync(~0u, sc, (it & 3) * 8 + i));
          if (lane == 0) mbar_arrive(bar + B_EMPTY6 + s * 8);
          if (++s == 6) { s = 0; par ^= 1; }
        }
        const uint32_t red = sb + STG + sec * 8192;
        sts128(red + warp * 1024 + lane * 32, __float_as_uint(a[0]), __float_as_uint(a[1]), __float_as_uint(a[2]), __float_as_uint(a[3]));
        sts128(red + warp * 1024 + lane * 32 + 16, __float_as_uint(a[4]), __float_as_uint(a[5]), __float_as_uint(a[6]), __float_as_uint(a[7]));
        named_bar(1, 256);
        float t = 0;
#pragma unroll
        for (int q = 0; q < 8; q++) t += lds32f(red + q * 1024 + tid * 4);
        st_rlx2(gs->modv + sec * 1024 + (bid + 4) * 256 + tid, __float_as_uint(t), ep);
      }
      if (tid == 0) gs->epoch[bid + 4] = ep;
      return;
    }
    const int row0 = wg * 64 + wq * 16 + g;
    if (c < 2) st_rlx2(gs->stat + m * 1024 + j * 128 + row0 + c * 8, 0, 0);
    if (tid < 64) st_rlx2(gs->modp + ((j * 2 + sec0) * 4 + ks0) * 128 + hf0 * 64 + tid, 0, 0);
    cl_arrive_relaxed(); cl_wait();
    uint32_t ep;
    asm volatile("add.u32 %0, %1, 1;" : "=r"(ep) : "r"(ep0) : "memory");
    const float sc_ = silu_c(__uint_as_float((uint32_t)cv_ << 16));
    const uint32_t rel = mapa(bar, (lane & 1) ^ rank);
    const uint32_t stg_row = sb + STG + (wg * 64 + wq * 16 + (lane & 15)) * 128;
    const uint32_t fre = bar + B_FREE;
    Ring r4{0, 0, 0}, r6{0, 0, 0};
    auto none = [](auto) {};
    uint32_t xk[32];
    {
      float a[8] = {0, 0, 0, 0, 0, 0, 0, 0};
#pragma unroll
      for (int i = 0; i < 8; i++) gemv_fma(a, wv[i], __shfl_sync(~0u, sc_, i * 4 + (lane >> 3)));
#pragma unroll
      for (int i = 0; i < 8; i++) { a[i] += __shfl_xor_sync(~0u, a[i], 8); a[i] += __shfl_xor_sync(~0u, a[i], 16); }
      if (lane < 8) {
        sts128(sb + RED_OFF + warp * 256 + lane * 32, __float_as_uint(a[0]), __float_as_uint(a[1]), __float_as_uint(a[2]), __float_as_uint(a[3]));
        sts128(sb + RED_OFF + warp * 256 + lane * 32 + 16, __float_as_uint(a[4]), __float_as_uint(a[5]), __float_as_uint(a[6]), __float_as_uint(a[7]));
      }
      named_bar(1, 256);
      if (tid < 64) {
        float s = 0;
#pragma unroll
        for (int w = 0; w < 8; w++) s += lds32f(sb + RED_OFF + w * 256 + tid * 4);
        st_rlx2(gs->modp + ((j * 2 + sec0) * 4 + ks0) * 128 + hf0 * 64 + tid, __float_as_uint(s), ep);
      }
      float v[64];
      mbar_wait(bar + B_X, 0); mbar_wait(bar + B_X + 8, 0);
#pragma unroll
      for (int i = 0; i < 16; i += 2) {
        uint32_t w0, w1, w2, w3;
        ldsm4(stg_row + (i >> 3) * BLK + ((((i & 7) + (lane >> 4)) ^ (lane & 7)) << 4), w0, w1, w2, w3);
        xk[2 * i] = w0; xk[2 * i + 1] = w1; xk[2 * i + 2] = w2; xk[2 * i + 3] = w3;
        v[4 * i] = bf_lo(w0); v[4 * i + 1] = bf_hi(w0); v[4 * i + 2] = bf_lo(w1); v[4 * i + 3] = bf_hi(w1);
        v[4 * i + 4] = bf_lo(w2); v[4 * i + 5] = bf_hi(w2); v[4 * i + 6] = bf_lo(w3); v[4 * i + 7] = bf_hi(w3);
      }
      ln_publish(v, gs->stat + m * 1024, j, row0, lane, ep);
      mod_store(sb, tid >> 7, tid & 127, mod_gather(gs->modp + (j * 2 + (tid >> 7)) * 512 + (tid & 127), ep));
      named_bar(1, 256);
      ln_apply(v, gs->stat + m * 1024, row0, ep, sb, 0, 1, stg_row, wg, lane);
      named_bar(1, 256);
    }
    {
      uint32_t kf[32], vf[32], pv[32];
      const bool first = wq == 0 && m == 0;
      const uint32_t xa = sb + STG + wg * HALF + wq * 2048 + lane * 16;
      {
        float acc[128];
        mainloop<256, 4, 0, 0>(acc, 16, true, r4, sb, wg, lane, rel, none, none, [&] {
          mbar_wait(fre + 8, 0);
          if (c < 2) st_rlx2(gs->stat + (16 + m) * 1024 + j * 128 + row0 + c * 8, 0, 0);
        });
#pragma unroll
        for (int i = 0; i < 32; i++) { kf[i] = pack2(acc[2 * i], acc[2 * i + 1]); vf[i] = pack2(acc[64 + 2 * i], acc[65 + 2 * i]); }
      }
      float acc[64];
      constexpr int QP = 2;
      mainloop<128, 6, 8 / QP, 0>(acc, 16, false, r6, sb, wg, lane, rel, [&](auto ic) {
        constexpr int q = (ic.v - 1) * QP;
#pragma unroll
        for (int i = 4 * q; i < 4 * (q + QP); i++) vf[i] = movm(vf[i]);
        if (wq == 3) {
          if (m < 15) {
            uint4* hp = gs->halo + (((m + 1) * 8 + j) * 2 + wg) * 512 + lane;
#pragma unroll
            for (int i = 2 * q; i < 2 * (q + QP); i++) st_rlx4(hp + i * 32, kf[2 * i + 1], ep, vf[2 * i + 1], ep);
          }
        } else {
#pragma unroll
          for (int i = q; i < q + QP; i++) sts128(xa + 2048 + (i >> 2) * BLK + (i & 3) * 512, kf[4 * i + 1], kf[4 * i + 3], vf[4 * i + 1], vf[4 * i + 3]);
        }
      }, none, [&] {
        named_bar(2 + wg, 128);
        if (wq == 0) mbar_wait(bar + B_HALO, 0);
#pragma unroll
        for (int i = 0; i < 8; i++) {
          uint4 q = lds128(xa + (i >> 2) * BLK + (i & 3) * 512);
          pv[4 * i] = q.x; pv[4 * i + 1] = q.y; pv[4 * i + 2] = q.z; pv[4 * i + 3] = q.w;
        }
        __syncwarp();
      });
      int gz = g;
#pragma unroll
      for (int b = 0; b < 2; b++) {
        const bool up0 = 2 * c > gz, up1 = 2 * c + 1 > gz;
        const uint32_t mup = (up0 ? 0xffffu : 0u) | (up1 ? 0xffff0000u : 0u);
        float l[2][4], mx[4];
#pragma unroll
        for (int h = 0; h < 2; h++) {
          uint32_t q[8];
          const int k = 16 * b + 8 * h;
#pragma unroll
          for (int i = 0; i < 8; i++) q[i] = pack2(acc[2 * k + 2 * i], acc[2 * k + 2 * i + 1]);
          float s0[4], s1[4], s2[4];
          mma16z(s0, q[0], q[1], q[2], q[3], pv[k], pv[k + 1]); mma16z(s1, q[0], q[1], q[2], q[3], kf[k], kf[k + 2]); mma16z(s2, q[0], q[1], q[2], q[3], kf[k + 1], kf[k + 3]);
          mma16(s0, q[4], q[5], q[6], q[7], pv[k + 4], pv[k + 5]); mma16(s1, q[4], q[5], q[6], q[7], kf[k + 4], kf[k + 6]); mma16(s2, q[4], q[5], q[6], q[7], kf[k + 5], kf[k + 7]);
          if (first) { s0[0] = -INFINITY; s0[1] = -INFINITY; }
          l[h][0] = up0 ? s0[0] : s1[0]; l[h][1] = up1 ? s0[1] : s1[1]; l[h][2] = up0 ? s1[2] : s2[2]; l[h][3] = up1 ? s1[3] : s2[3];
          mx[2 * h] = fmaxf(l[h][0], l[h][1]); mx[2 * h + 1] = fmaxf(l[h][2], l[h][3]);
        }
#pragma unroll
        for (int o = 1; o < 4; o <<= 1) {
#pragma unroll
          for (int h = 0; h < 4; h++) mx[h] = fmaxf(mx[h], __shfl_xor_sync(~0u, mx[h], o));
        }
#pragma unroll
        for (int h = 0; h < 2; h++) {
          const float n0 = -mx[2 * h] * SCL, n1 = -mx[2 * h + 1] * SCL;
          const uint32_t pa = pack2(ex2(fmaf(l[h][0], SCL, n0)), ex2(fmaf(l[h][1], SCL, n0))), pb = pack2(ex2(fmaf(l[h][2], SCL, n1)), ex2(fmaf(l[h][3], SCL, n1)));
          float sm[4];
          mma8z(sm, pa, pb, 0x3f803f80u);
          const float ia = rcp(sm[0]), ib = rcp(sm[2]);
#pragma unroll
          for (int i = 8 * b + 4 * h; i < 8 * b + 4 * h + 4; i += 2) {
            uint32_t of[4];
#pragma unroll
            for (int d = 0; d < 2; d++) {
              float o[4];
              mma16z(o, pa & ~mup, pb & mup, 0u, pb & ~mup, vf[2 * (i + d)], vf[2 * (i + d) + 1]);
              mma8(o, pa & mup, 0u, pv[2 * i + 2 + d]);
              of[2 * d] = pack2(o[0] * ia, o[1] * ia); of[2 * d + 1] = pack2(o[2] * ib, o[3] * ib);
            }
            stsm4(stg_row + b * BLK + ((((i & 7) + (lane >> 4)) ^ (lane & 7)) << 4), of[0], of[1], of[2], of[3]);
          }
        }
        stage_done(sb, wg, b, lane);
        if (b == 0) gz += __float_as_uint(lds32f(bar + ZERO));
      }
      named_bar(1, 256);
    }
    uint32_t pk[64];
    {
      float acc[64];
      mainloop<128, 6, 0, WOLAG>(acc, 16, true, r6, sb, wg, lane, rel, none, none, [&] {
        if (WOLAG && wg == 0 && lane == 0) mbar_arrive(bar + B_LAG);
        mbar_wait(bar + B_MOD, 0); mbar_wait(fre + 8, 1);
        load_vec(pk + 32, sb, 2, 0, lane); load_vec(pk + 40, sb, 2, 1, lane);
#pragma unroll
        for (int i = 0; i < 32; i++) { pk[i] = xk[i]; asm volatile("" : "+r"(pk[i])); }
      });
#pragma unroll
      for (int i = 0; i < 32; i++) {
        acc[2 * i] = fmaf(acc[2 * i], bf_lo(pk[32 + (i >> 1)]), bf_lo(pk[i]));
        acc[2 * i + 1] = fmaf(acc[2 * i + 1], bf_hi(pk[32 + (i >> 1)]), bf_hi(pk[i]));
      }
      ln_publish(acc, gs->stat + (16 + m) * 1024, j, row0, lane, ep);
      mbar_wait(bar + B_FULL6 + 16, 1);
      if (lane < 2) mbar_arrive_cl(rel + B_EMPTY6 + 16);
      ring_next<6>(r6);
#pragma unroll
      for (int i = 0; i < 32; i++) { pk[i] = pack2(acc[2 * i], acc[2 * i + 1]); pk[32 + i] = 0; }
      ln_apply(acc, gs->stat + (16 + m) * 1024, row0, ep, sb, 3, 4, stg_row, wg, lane);
      named_bar(1, 256);
    }
    auto swiglu = [&](int q, int uo, int par) {
      if ((q & 3) == 0 && par >= 0) mbar_wait(fre + 2 * q, par);
      uint32_t w[4];
#pragma unroll
      for (int u = 0; u < 4; u++) w[u] = silu_mul2(pk[4 * q + u], pk[uo + 4 * q + u]);
      stsm4(stg_row + (q >> 2) * BLK + ((((2 * q & 7) + (lane >> 4)) ^ (lane & 7)) << 4), w[0], w[1], w[2], w[3]);
    };
    r4.s = r4.wrap = 2;
#pragma unroll 1
    for (int t = 0; t < 3; t++) {
      float acc[128];
      mainloop<256, 4, 5, 0>(acc, 16, t == 0, r4, sb, wg, lane, rel, [&](auto ic) {
        if (t) {
          if (ic.v == 3 || ic.v == 5) stage_done(sb, wg, ic.v >> 2, lane);
          if (ic.v < 5) { swiglu(2 * ic.v - 2, 32, ~t & 1); swiglu(2 * ic.v - 1, 32, 0); }
        }
      }, [&](int it) {
#pragma unroll
        for (int i = 0; i < 8; i++)
          if (t == 0 && it == 8 + i) gs->x1[bid * 2048 + (i >> 2) * 1024 + warp * 128 + (i & 3) * 32 + lane] = make_uint4(pk[4 * i], pk[4 * i + 1], pk[4 * i + 2], pk[4 * i + 3]);
      }, [&] { if (t == 0) fence_async_global(); else if (t == 2) mbar_wait(bar + B_X, 1); });
#pragma unroll
      for (int i = 0; i < 64; i++) pk[i] = pack2(acc[2 * i], acc[2 * i + 1]);
    }
    uint32_t x1[32];
    {
      float acc[64];
      mainloop<128, 6, 12, 0>(acc, 16, false, r6, sb, wg, lane, rel, [&](auto ic) {
        constexpr int b = ic.v > 6, q = ic.v - 6 * b;
        if (q == 1) {
#pragma unroll
          for (int i = 4 * b; i < 4 * b + 4; i++) { const uint4 x = lds128(sb + STG + b * BLK + warp * 2048 + (i & 3) * 512 + lane * 16); x1[4 * i] = x.x; x1[4 * i + 1] = x.y; x1[4 * i + 2] = x.z; x1[4 * i + 3] = x.w; }
          __syncwarp();
        } else if (q < 6) swiglu(4 * b + q - 2, 32, -1);
        else stage_done(sb, wg, b, lane);
      }, none, [] {});
#pragma unroll
      for (int i = 0; i < 32; i++) pk[i] = pack2(acc[2 * i], acc[2 * i + 1]);
    }
    {
      float acc[64];
      mainloop<128, 6, 5, TAILLAG>(acc, 56, false, r6, sb, wg, lane, rel, [&](auto ic) {
        if (ic.v == 5) stage_done(sb, wg, 0, lane); else swiglu(ic.v - 1, 16, 1);
      }, none, [&] {
        if (TAILLAG && wg == 0 && lane == 0) mbar_arrive(bar + B_LAG);
        load_vec(pk + 32, sb, 5, 0, lane); load_vec(pk + 40, sb, 5, 1, lane);
        mbar_wait(fre, 0); mbar_wait(fre + 8, 1);
      });
      __syncwarp();
      cl_arrive_relaxed();
#pragma unroll
      for (int i = 0; i < 16; i += 2) {
        uint32_t w[4];
#pragma unroll
        for (int u = 0; u < 4; u++) {
          const int q = 2 * i + u;
          w[u] = pack2(fmaf(acc[2 * q], bf_lo(pk[32 + (q >> 1)]), bf_lo(x1[q])), fmaf(acc[2 * q + 1], bf_hi(pk[32 + (q >> 1)]), bf_hi(x1[q])));
        }
        stsm4(stg_row + (i >> 3) * BLK + ((((i & 7) + (lane >> 4)) ^ (lane & 7)) << 4), w[0], w[1], w[2], w[3]);
        if ((i & 7) == 6) {
          fence_async_smem();
          named_bar(2 + wg, 128);
          if (wq == 0 && elect()) { tma_store_3d(&maps.out, sb + STG + (i >> 3) * BLK + wg * HALF, j * 128 + (i >> 3) * 64, m * 64, wg); bulk_commit(); }
          if (i < 8) x1[16] |= __float_as_uint(lds32f(bar + ZERO));
        }
      }
      if (wq == 0) bulk_wait_read();
      if (tid == 0) gs->epoch[bid + 4] = ep;
      cl_wait();
    }
  }
}

typedef CUresult (*EncodeFn)(CUtensorMap*, CUtensorMapDataType, cuuint32_t, void*, const cuuint64_t*, const cuuint64_t*, const cuuint32_t*, const cuuint32_t*,
                             CUtensorMapInterleave, CUtensorMapSwizzle, CUtensorMapL2promotion, CUtensorMapFloatOOBfill);

void make_map(EncodeFn fn, CUtensorMap* mp, const void* base, uint64_t d0, uint64_t d1, uint64_t d2, uint64_t s1, uint64_t s2, uint32_t b2, uint32_t b0 = 64) {
  cuuint64_t d[3] = {d0, d1, d2}, s[2] = {s1, s2};
  cuuint32_t b[3] = {b0, 64, b2}, e[3] = {1, 1, 1};
  fn(mp, CU_TENSOR_MAP_DATA_TYPE_BFLOAT16, 3, (void*)base, d, s, b, e, CU_TENSOR_MAP_INTERLEAVE_NONE, b0 == 64 ? CU_TENSOR_MAP_SWIZZLE_128B : CU_TENSOR_MAP_SWIZZLE_NONE,
     CU_TENSOR_MAP_L2_PROMOTION_L2_128B, CU_TENSOR_MAP_FLOAT_OOB_FILL_NONE);
}

__global__ void probe_kernel() {}
int max_clusters(int size) {
  cudaLaunchConfig_t cfg = {};
  cudaLaunchAttribute at;
  at.id = cudaLaunchAttributeClusterDimension; at.val.clusterDim.x = size; at.val.clusterDim.y = 1; at.val.clusterDim.z = 1;
  cfg.gridDim = dim3(size * 66); cfg.blockDim = dim3(384); cfg.dynamicSmemBytes = SMEM_BYTES; cfg.attrs = &at; cfg.numAttrs = 1;
  int n = 0;
  if (cudaOccupancyMaxActiveClusters(&n, probe_kernel, &cfg) != cudaSuccess) { cudaGetLastError(); return 0; }
  return n;
}

}

extern "C" void kernel_launch(void* const* d_in, const int* in_sizes, int n_in, void* d_out, int out_size) {
  static EncodeFn fn = nullptr;
  static int by_sm = 0;
  static Scratch* gs = nullptr;
  if (!fn) {
    void* p = nullptr; cudaDriverEntryPointQueryResult q;
    cudaGetDriverEntryPoint("cuTensorMapEncodeTiled", &p, cudaEnableDefault, &q);
    fn = (EncodeFn)p;
    cudaFuncSetAttribute(fused_kernel, cudaFuncAttributeMaxDynamicSharedMemorySize, SMEM_BYTES);
    int dev = 0, sms = 0;
    cudaGetSymbolAddress((void**)&gs, g_scratch);
    cudaGetDevice(&dev);
    cudaDeviceGetAttribute(&sms, cudaDevAttrMultiProcessorCount, dev);
    cudaFuncSetAttribute(probe_kernel, cudaFuncAttributeMaxDynamicSharedMemorySize, SMEM_BYTES);
    by_sm = sms == 132 && max_clusters(2) == 66 && max_clusters(4) == 30 && max_clusters(6) == 17 && max_clusters(8) == 15;
  }
  Maps mp;
  make_map(fn, &mp.x, d_in[0], D_, S_ / 2, 2, 4096, 2048, 2);
  make_map(fn, &mp.out, d_out, D_, S_ / 2, 2, 4096, 2048, 1);
  make_map(fn, &mp.wqkv, d_in[1], 64, D_, 3 * D_ / 64, 3 * D_ * 2, 128, 2);
  make_map(fn, &mp.wo, d_in[2], 64, D_, D_ / 64, D_ * 2, 128, 2);
  make_map(fn, &mp.w1, d_in[4], 64, D_, F_ / 64, F_ * 2, 128, 2);
  make_map(fn, &mp.w3, d_in[5], 64, D_, F_ / 64, F_ * 2, 128, 2);
  make_map(fn, &mp.w1s, d_in[4], 64, D_, F_ / 64, F_ * 2, 128, 1);
  make_map(fn, &mp.w3s, d_in[5], 64, D_, F_ / 64, F_ * 2, 128, 1);
  make_map(fn, &mp.w2, d_in[6], 64, F_, D_ / 64, D_ * 2, 128, 2);
  make_map(fn, &mp.wmod, d_in[8], 256, D_, 24, 6 * D_ * 2, 512, 1, 256);
  fused_kernel<<<132, 384, SMEM_BYTES>>>((const bf16*)d_in[7], (const bf16*)d_in[8], gs, by_sm, mp);
}
```

```cpp
#include <cuda_runtime.h>
#include <cuda_bf16.h>
#include <cuda.h>
#include <stdint.h>

typedef __nv_bfloat16 bf16;

namespace {

constexpr int S_ = 2048, D_ = 1024, F_ = 3584;
constexpr int BLK = 16384;
constexpr int HALF = 8192;
constexpr int RING = 196608;
constexpr int STG = RING;
constexpr int MISC = RING + 2 * BLK;
constexpr int SMEM_BYTES = MISC + 3072;
constexpr int B_FULL4 = 0, B_EMPTY4 = 32, B_FULL6 = 64, B_EMPTY6 = 112, B_RDY = 160, B_FREE = 176, B_LAG = 192, B_X = 208, B_MOD = 224, B_HALO = 232, B_HH = 256, B_ALL = 272, B_HH2 = 288, ZERO = 296;
constexpr int MODV = 512;
constexpr int RED_OFF = 0;
constexpr float SCL = 0.17677669529663687f * 1.4426950408889634f;
constexpr int U_HH = 64;
constexpr int FS = 8;
constexpr int NPIECE = 4, PSLEEP = 300;
constexpr int XSLEEP = 4000, HSLEEP = 400;
constexpr uint32_t XDELAY = 2000;
constexpr uint32_t B1P = 3500, B1D = 900, B1P2 = 3200;
constexpr int WOLAG = 2, TAILLAG = 5;

struct Maps { CUtensorMap x, out, wqkv, wo, w1, w3, w1s, w3s, w2, wmod; };

struct Scratch {
  uint4 h[16 * 16 * 1024];
  uint4 o[16 * 16 * 1024];
  uint4 hh[16 * 56 * 1024];
  uint4 x1[128 * 8 * 256];
  uint2 stat[2 * 16 * 8 * 128];
  uint4 halo[16 * 8 * 2 * 512];
  uint32_t modp[8 * 2 * 4 * 128];
  uint2 modv[4 * 1024];
  uint32_t flag[16 * 128 * FS];
  uint32_t epoch[132];
};
__device__ __align__(1024) Scratch g_scratch;

__device__ __forceinline__ void bail() { asm volatile("st.global.u32 [%0], %1;" :: "l"(0ull), "r"(0) : "memory"); }
__device__ __forceinline__ uint32_t smem_u32(const void* p) { return (uint32_t)__cvta_generic_to_shared(p); }
__device__ __forceinline__ void mbar_init(uint32_t bar, uint32_t cnt) { asm volatile("mbarrier.init.shared::cta.b64 [%0], %1;" :: "r"(bar), "r"(cnt) : "memory"); }
__device__ __forceinline__ void mbar_expect_tx(uint32_t bar, uint32_t bytes) { asm volatile("mbarrier.arrive.expect_tx.shared::cta.b64 _, [%0], %1;" :: "r"(bar), "r"(bytes) : "memory"); }
__device__ __forceinline__ void mbar_arrive(uint32_t bar) { asm volatile("mbarrier.arrive.shared::cta.b64 _, [%0];" :: "r"(bar) : "memory"); }
__device__ __forceinline__ void mbar_arrive_cl(uint32_t cl_addr) { asm volatile("mbarrier.arrive.shared::cluster.b64 _, [%0];" :: "r"(cl_addr) : "memory"); }
__device__ __forceinline__ uint32_t mapa(uint32_t addr, uint32_t cta) { uint32_t r; asm("mapa.shared::cluster.u32 %0, %1, %2;" : "=r"(r) : "r"(addr), "r"(cta)); return r; }
__device__ __forceinline__ void mbar_wait(uint32_t bar, uint32_t parity) {
  asm volatile("{\n.reg .pred p;\n.reg .b32 n;\n.reg .b64 z;\nmov.b32 n, 0;\nmov.b64 z, 0;\n"
               "W: add.u32 n, n, 1;\nsetp.gt.u32 p, n, 0x400000;\n@p st.global.u32 [z], n;\n"
               "mbarrier.try_wait.parity.shared::cta.b64 p, [%0], %1;\n@!p bra W;\n}" :: "r"(bar), "r"(parity) : "memory");
}
__device__ __forceinline__ void tma_3d(uint32_t dst, const CUtensorMap* m, uint32_t bar, int c0, int c1, int c2) {
  asm volatile("cp.async.bulk.tensor.3d.shared::cluster.global.mbarrier::complete_tx::bytes [%0], [%1, {%3, %4, %5}], [%2];" :: "r"(dst), "l"(m), "r"(bar), "r"(c0), "r"(c1), "r"(c2) : "memory");
}
__device__ __forceinline__ void tma_store_3d(const CUtensorMap* m, uint32_t src, int c0, int c1, int c2) {
  asm volatile("cp.async.bulk.tensor.3d.global.shared::cta.bulk_group [%0, {%2, %3, %4}], [%1];" :: "l"(m), "r"(src), "r"(c0), "r"(c1), "r"(c2) : "memory");
}
__device__ __forceinline__ void bulk_ld(uint32_t dst, const void* src, uint32_t bytes, uint32_t bar) {
  asm volatile("cp.async.bulk.shared::cluster.global.mbarrier::complete_tx::bytes [%0], [%1], %2, [%3];" :: "r"(dst), "l"(src), "r"(bytes), "r"(bar) : "memory");
}
__device__ __forceinline__ void bulk_ld_mc(uint32_t dst, const void* src, uint32_t bytes, uint32_t bar) {
  asm volatile("cp.async.bulk.shared::cluster.global.mbarrier::complete_tx::bytes.multicast::cluster [%0], [%1], %2, [%3], %4;" :: "r"(dst), "l"(src), "r"(bytes), "r"(bar), "h"((uint16_t)3) : "memory");
}
__device__ __forceinline__ void bulk_push(uint32_t dst_cl, uint32_t src, uint32_t bytes, uint32_t bar_cl) {
  asm volatile("cp.async.bulk.shared::cluster.shared::cta.mbarrier::complete_tx::bytes [%0], [%1], %2, [%3];" :: "r"(dst_cl), "r"(src), "r"(bytes), "r"(bar_cl) : "memory");
}
__device__ __forceinline__ void bulk_st(void* dst, uint32_t src, uint32_t bytes) {
  asm volatile("cp.async.bulk.global.shared::cta.bulk_group [%0], [%1], %2;" :: "l"(dst), "r"(src), "r"(bytes) : "memory");
}
__device__ __forceinline__ void bulk_commit() { asm volatile("cp.async.bulk.commit_group;" ::: "memory"); }
__device__ __forceinline__ void bulk_wait_read() { asm volatile("cp.async.bulk.wait_group.read 0;" ::: "memory"); }
__device__ __forceinline__ void bulk_wait_all() { asm volatile("cp.async.bulk.wait_group 0;" ::: "memory"); }
__device__ __forceinline__ void fence_async_global() { asm volatile("fence.proxy.async.global;" ::: "memory"); }
__device__ __forceinline__ void fence_async_smem() { asm volatile("fence.proxy.async.shared::cta;" ::: "memory"); }
__device__ __forceinline__ void wg_arrive() { asm volatile("wgmma.fence.sync.aligned;" ::: "memory"); }
__device__ __forceinline__ void wg_commit() { asm volatile("wgmma.commit_group.sync.aligned;" ::: "memory"); }
template <int N> __device__ __forceinline__ void wg_wait() { asm volatile("wgmma.wait_group.sync.aligned %0;" :: "n"(N) : "memory"); }
__device__ __forceinline__ void cl_arrive_relaxed() { asm volatile("barrier.cluster.arrive.relaxed.aligned;" ::: "memory"); }
__device__ __forceinline__ void cl_wait() { asm volatile("barrier.cluster.wait.acquire.aligned;" ::: "memory"); }
__device__ __forceinline__ bool elect() { uint32_t p; asm volatile("{\n.reg .pred p;\nelect.sync _|p, 0xffffffff;\nselp.u32 %0, 1, 0, p;\n}" : "=r"(p)); return p; }
__device__ __forceinline__ void named_bar(int id, int n) { asm volatile("bar.sync %0, %1;" :: "r"(id), "r"(n) : "memory"); }
__device__ __forceinline__ uint32_t pack2(float lo, float hi) { uint32_t r; asm("cvt.rn.bf16x2.f32 %0, %1, %2;" : "=r"(r) : "f"(hi), "f"(lo)); return r; }
__device__ __forceinline__ float bf_lo(uint32_t w) { return __uint_as_float(w << 16); }
__device__ __forceinline__ float bf_hi(uint32_t w) { return __uint_as_float(w & 0xffff0000u); }
__device__ __forceinline__ float bf_round(float v) { return __bfloat162float(__float2bfloat16_rn(v)); }
__device__ __forceinline__ void stsm4(uint32_t addr, uint32_t a, uint32_t b, uint32_t c, uint32_t d) {
  asm volatile("stmatrix.sync.aligned.m8n8.x4.shared.b16 [%0], {%1, %2, %3, %4};" :: "r"(addr), "r"(a), "r"(b), "r"(c), "r"(d) : "memory");
}
__device__ __forceinline__ void ldsm4(uint32_t addr, uint32_t& a, uint32_t& b, uint32_t& c, uint32_t& d) {
  asm volatile("ldmatrix.sync.aligned.m8n8.x4.shared.b16 {%0, %1, %2, %3}, [%4];" : "=r"(a), "=r"(b), "=r"(c), "=r"(d) : "r"(addr) : "memory");
}
__device__ __forceinline__ uint32_t movm(uint32_t a) { uint32_t r; asm volatile("movmatrix.sync.aligned.m8n8.trans.b16 %0, %1;" : "=r"(r) : "r"(a)); return r; }
__device__ __forceinline__ void mma16(float (&d)[4], uint32_t a0, uint32_t a1, uint32_t a2, uint32_t a3, uint32_t b0, uint32_t b1) {
  asm("mma.sync.aligned.m16n8k16.row.col.f32.bf16.bf16.f32 {%0,%1,%2,%3}, {%4,%5,%6,%7}, {%8,%9}, {%0,%1,%2,%3};"
               : "+f"(d[0]), "+f"(d[1]), "+f"(d[2]), "+f"(d[3]) : "r"(a0), "r"(a1), "r"(a2), "r"(a3), "r"(b0), "r"(b1));
}
__device__ __forceinline__ void mma16z(float (&d)[4], uint32_t a0, uint32_t a1, uint32_t a2, uint32_t a3, uint32_t b0, uint32_t b1) {
  asm("mma.sync.aligned.m16n8k16.row.col.f32.bf16.bf16.f32 {%0,%1,%2,%3}, {%4,%5,%6,%7}, {%8,%9}, {%10,%10,%10,%10};"
      : "=f"(d[0]), "=f"(d[1]), "=f"(d[2]), "=f"(d[3]) : "r"(a0), "r"(a1), "r"(a2), "r"(a3), "r"(b0), "r"(b1), "f"(0.f));
}
__device__ __forceinline__ void mma8z(float (&d)[4], uint32_t a0, uint32_t a1, uint32_t b0) {
  asm("mma.sync.aligned.m16n8k8.row.col.f32.bf16.bf16.f32 {%0,%1,%2,%3}, {%4,%5}, {%6}, {%7,%7,%7,%7};"
      : "=f"(d[0]), "=f"(d[1]), "=f"(d[2]), "=f"(d[3]) : "r"(a0), "r"(a1), "r"(b0), "f"(0.f));
}
__device__ __forceinline__ void mma8(float (&d)[4], uint32_t a0, uint32_t a1, uint32_t b0) {
  asm("mma.sync.aligned.m16n8k8.row.col.f32.bf16.bf16.f32 {%0,%1,%2,%3}, {%4,%5}, {%6}, {%0,%1,%2,%3};"
               : "+f"(d[0]), "+f"(d[1]), "+f"(d[2]), "+f"(d[3]) : "r"(a0), "r"(a1), "r"(b0));
}
__device__ __forceinline__ uint4 lds128(uint32_t a) { uint4 v; asm volatile("ld.shared.v4.u32 {%0,%1,%2,%3}, [%4];" : "=r"(v.x), "=r"(v.y), "=r"(v.z), "=r"(v.w) : "r"(a) : "memory"); return v; }
__device__ __forceinline__ void sts128(uint32_t a, uint32_t x, uint32_t y, uint32_t z, uint32_t w) { asm volatile("st.shared.v4.u32 [%0], {%1,%2,%3,%4};" :: "r"(a), "r"(x), "r"(y), "r"(z), "r"(w) : "memory"); }
__device__ __forceinline__ float lds32f(uint32_t a) { float v; asm volatile("ld.shared.f32 %0, [%1];" : "=f"(v) : "r"(a) : "memory"); return v; }
__device__ __forceinline__ void sts16(uint32_t a, bf16 v) { asm volatile("st.shared.b16 [%0], %1;" :: "r"(a), "h"(__bfloat16_as_ushort(v)) : "memory"); }
__device__ __forceinline__ uint4 ldg_nc(const void* p) { uint4 v; asm volatile("ld.global.nc.L1::no_allocate.v4.u32 {%0,%1,%2,%3}, [%4];" : "=r"(v.x), "=r"(v.y), "=r"(v.z), "=r"(v.w) : "l"(p)); return v; }
__device__ __forceinline__ uint4 ld_rlx4(const uint4* p) {
  unsigned long long a, b; asm volatile("ld.relaxed.gpu.global.v2.b64 {%0,%1}, [%2];" : "=l"(a), "=l"(b) : "l"(p) : "memory");
  return make_uint4((uint32_t)a, (uint32_t)(a >> 32), (uint32_t)b, (uint32_t)(b >> 32));
}
__device__ __forceinline__ uint2 ld_rlx2(const uint2* p) { unsigned long long a; asm volatile("ld.relaxed.gpu.global.b64 %0, [%1];" : "=l"(a) : "l"(p) : "memory"); return make_uint2((uint32_t)a, (uint32_t)(a >> 32)); }
__device__ __forceinline__ void st_rlx4(uint4* p, uint32_t x, uint32_t y, uint32_t z, uint32_t w) {
  asm volatile("st.relaxed.gpu.global.v2.b64 [%0], {%1,%2};" :: "l"(p), "l"((unsigned long long)x | ((unsigned long long)y << 32)), "l"((unsigned long long)z | ((unsigned long long)w << 32)) : "memory");
}
__device__ __forceinline__ void st_rlx2(uint2* p, uint32_t x, uint32_t y) { asm volatile("st.relaxed.gpu.global.b64 [%0], %1;" :: "l"(p), "l"((unsigned long long)x | ((unsigned long long)y << 32)) : "memory"); }
__device__ __forceinline__ void st_rlx1(uint32_t* p, uint32_t v) { asm volatile("st.relaxed.gpu.global.u32 [%0], %1;" :: "l"(p), "r"(v) : "memory"); }
__device__ __forceinline__ uint32_t ld_rlx1(const uint32_t* p) { uint32_t v; asm volatile("ld.relaxed.gpu.global.u32 %0, [%1];" : "=r"(v) : "l"(p) : "memory"); return v; }
__device__ __forceinline__ void st_release(uint32_t* p, uint32_t v) { asm volatile("st.release.gpu.global.u32 [%0], %1;" :: "l"(p), "r"(v) : "memory"); }
__device__ __forceinline__ uint32_t ld_acquire(const uint32_t* p) { uint32_t v; asm volatile("ld.acquire.gpu.global.u32 %0, [%1];" : "=r"(v) : "l"(p) : "memory"); return v; }
__device__ __forceinline__ void prefetch_map(const CUtensorMap* m) { asm volatile("prefetch.tensormap [%0];" :: "l"(m) : "memory"); }
__device__ __forceinline__ float rcp(float x) { float r; asm("rcp.approx.ftz.f32 %0, %1;" : "=f"(r) : "f"(x)); return r; }
__device__ __forceinline__ float ex2(float x) { float r; asm("ex2.approx.ftz.f32 %0, %1;" : "=f"(r) : "f"(x)); return r; }
__device__ __forceinline__ float tanh_fast(float x) { float r; asm("tanh.approx.f32 %0, %1;" : "=f"(r) : "f"(x)); return r; }
#define SPIN_GUARD(n) if (++(n) > (1u << 24)) bail()

__device__ __forceinline__ void wgmma_n128(float (&d)[64], uint64_t da, uint64_t db) {
  asm volatile("wgmma.mma_async.sync.aligned.m64n128k16.f32.bf16.bf16 "
    "{%0, %1, %2, %3, %4, %5, %6, %7, %8, %9, %10, %11, %12, %13, %14, %15, %16, %17, %18, %19, %20, %21, %22, %23, %24, %25, %26, %27, %28, %29, %30, %31, %32, %33, %34, %35, %36, %37, %38, %39, %40, %41, %42, %43, %44, %45, %46, %47, %48, %49, %50, %51, %52, %53, %54, %55, %56, %57, %58, %59, %60, %61, %62, %63}, "
    "%64, %65, 1, 1, 1, 0, 1;\n"
    : "+f"(d[0]), "+f"(d[1]), "+f"(d[2]), "+f"(d[3]), "+f"(d[4]), "+f"(d[5]), "+f"(d[6]), "+f"(d[7]), "+f"(d[8]), "+f"(d[9]), "+f"(d[10]), "+f"(d[11]), "+f"(d[12]), "+f"(d[13]), "+f"(d[14]), "+f"(d[15]), "+f"(d[16]), "+f"(d[17]), "+f"(d[18]), "+f"(d[19]), "+f"(d[20]), "+f"(d[21]), "+f"(d[22]), "+f"(d[23]), "+f"(d[24]), "+f"(d[25]), "+f"(d[26]), "+f"(d[27]), "+f"(d[28]), "+f"(d[29]), "+f"(d[30]), "+f"(d[31]), "+f"(d[32]), "+f"(d[33]), "+f"(d[34]), "+f"(d[35]), "+f"(d[36]), "+f"(d[37]), "+f"(d[38]), "+f"(d[39]), "+f"(d[40]), "+f"(d[41]), "+f"(d[42]), "+f"(d[43]), "+f"(d[44]), "+f"(d[45]), "+f"(d[46]), "+f"(d[47]), "+f"(d[48]), "+f"(d[49]), "+f"(d[50]), "+f"(d[51]), "+f"(d[52]), "+f"(d[53]), "+f"(d[54]), "+f"(d[55]), "+f"(d[56]), "+f"(d[57]), "+f"(d[58]), "+f"(d[59]), "+f"(d[60]), "+f"(d[61]), "+f"(d[62]), "+f"(d[63])
    : "l"(da), "l"(db));
}
__device__ __forceinline__ void wgmma_n128_first(float (&d)[64], uint64_t da, uint64_t db) {
  asm volatile("wgmma.mma_async.sync.aligned.m64n128k16.f32.bf16.bf16 "
    "{%0, %1, %2, %3, %4, %5, %6, %7, %8, %9, %10, %11, %12, %13, %14, %15, %16, %17, %18, %19, %20, %21, %22, %23, %24, %25, %26, %27, %28, %29, %30, %31, %32, %33, %34, %35, %36, %37, %38, %39, %40, %41, %42, %43, %44, %45, %46, %47, %48, %49, %50, %51, %52, %53, %54, %55, %56, %57, %58, %59, %60, %61, %62, %63}, "
    "%64, %65, 0, 1, 1, 0, 1;\n"
    : "=f"(d[0]), "=f"(d[1]), "=f"(d[2]), "=f"(d[3]), "=f"(d[4]), "=f"(d[5]), "=f"(d[6]), "=f"(d[7]), "=f"(d[8]), "=f"(d[9]), "=f"(d[10]), "=f"(d[11]), "=f"(d[12]), "=f"(d[13]), "=f"(d[14]), "=f"(d[15]), "=f"(d[16]), "=f"(d[17]), "=f"(d[18]), "=f"(d[19]), "=f"(d[20]), "=f"(d[21]), "=f"(d[22]), "=f"(d[23]), "=f"(d[24]), "=f"(d[25]), "=f"(d[26]), "=f"(d[27]), "=f"(d[28]), "=f"(d[29]), "=f"(d[30]), "=f"(d[31]), "=f"(d[32]), "=f"(d[33]), "=f"(d[34]), "=f"(d[35]), "=f"(d[36]), "=f"(d[37]), "=f"(d[38]), "=f"(d[39]), "=f"(d[40]), "=f"(d[41]), "=f"(d[42]), "=f"(d[43]), "=f"(d[44]), "=f"(d[45]), "=f"(d[46]), "=f"(d[47]), "=f"(d[48]), "=f"(d[49]), "=f"(d[50]), "=f"(d[51]), "=f"(d[52]), "=f"(d[53]), "=f"(d[54]), "=f"(d[55]), "=f"(d[56]), "=f"(d[57]), "=f"(d[58]), "=f"(d[59]), "=f"(d[60]), "=f"(d[61]), "=f"(d[62]), "=f"(d[63])
    : "l"(da), "l"(db));
}
__device__ __forceinline__ void wgmma_n256(float (&d)[128], uint64_t da, uint64_t db) {
  asm volatile("wgmma.mma_async.sync.aligned.m64n256k16.f32.bf16.bf16 "
    "{%0, %1, %2, %3, %4, %5, %6, %7, %8, %9, %10, %11, %12, %13, %14, %15, %16, %17, %18, %19, %20, %21, %22, %23, %24, %25, %26, %27, %28, %29, %30, %31, %32, %33, %34, %35, %36, %37, %38, %39, %40, %41, %42, %43, %44, %45, %46, %47, %48, %49, %50, %51, %52, %53, %54, %55, %56, %57, %58, %59, %60, %61, %62, %63, %64, %65, %66, %67, %68, %69, %70, %71, %72, %73, %74, %75, %76, %77, %78, %79, %80, %81, %82, %83, %84, %85, %86, %87, %88, %89, %90, %91, %92, %93, %94, %95, %96, %97, %98, %99, %100, %101, %102, %103, %104, %105, %106, %107, %108, %109, %110, %111, %112, %113, %114, %115, %116, %117, %118, %119, %120, %121, %122, %123, %124, %125, %126, %127}, "
    "%128, %129, 1, 1, 1, 0, 1;\n"
    : "+f"(d[0]), "+f"(d[1]), "+f"(d[2]), "+f"(d[3]), "+f"(d[4]), "+f"(d[5]), "+f"(d[6]), "+f"(d[7]), "+f"(d[8]), "+f"(d[9]), "+f"(d[10]), "+f"(d[11]), "+f"(d[12]), "+f"(d[13]), "+f"(d[14]), "+f"(d[15]), "+f"(d[16]), "+f"(d[17]), "+f"(d[18]), "+f"(d[19]), "+f"(d[20]), "+f"(d[21]), "+f"(d[22]), "+f"(d[23]), "+f"(d[24]), "+f"(d[25]), "+f"(d[26]), "+f"(d[27]), "+f"(d[28]), "+f"(d[29]), "+f"(d[30]), "+f"(d[31]), "+f"(d[32]), "+f"(d[33]), "+f"(d[34]), "+f"(d[35]), "+f"(d[36]), "+f"(d[37]), "+f"(d[38]), "+f"(d[39]), "+f"(d[40]), "+f"(d[41]), "+f"(d[42]), "+f"(d[43]), "+f"(d[44]), "+f"(d[45]), "+f"(d[46]), "+f"(d[47]), "+f"(d[48]), "+f"(d[49]), "+f"(d[50]), "+f"(d[51]), "+f"(d[52]), "+f"(d[53]), "+f"(d[54]), "+f"(d[55]), "+f"(d[56]), "+f"(d[57]), "+f"(d[58]), "+f"(d[59]), "+f"(d[60]), "+f"(d[61]), "+f"(d[62]), "+f"(d[63]), "+f"(d[64]), "+f"(d[65]), "+f"(d[66]), "+f"(d[67]), "+f"(d[68]), "+f"(d[69]), "+f"(d[70]), "+f"(d[71]), "+f"(d[72]), "+f"(d[73]), "+f"(d[74]), "+f"(d[75]), "+f"(d[76]), "+f"(d[77]), "+f"(d[78]), "+f"(d[79]), "+f"(d[80]), "+f"(d[81]), "+f"(d[82]), "+f"(d[83]), "+f"(d[84]), "+f"(d[85]), "+f"(d[86]), "+f"(d[87]), "+f"(d[88]), "+f"(d[89]), "+f"(d[90]), "+f"(d[91]), "+f"(d[92]), "+f"(d[93]), "+f"(d[94]), "+f"(d[95]), "+f"(d[96]), "+f"(d[97]), "+f"(d[98]), "+f"(d[99]), "+f"(d[100]), "+f"(d[101]), "+f"(d[102]), "+f"(d[103]), "+f"(d[104]), "+f"(d[105]), "+f"(d[106]), "+f"(d[107]), "+f"(d[108]), "+f"(d[109]), "+f"(d[110]), "+f"(d[111]), "+f"(d[112]), "+f"(d[113]), "+f"(d[114]), "+f"(d[115]), "+f"(d[116]), "+f"(d[117]), "+f"(d[118]), "+f"(d[119]), "+f"(d[120]), "+f"(d[121]), "+f"(d[122]), "+f"(d[123]), "+f"(d[124]), "+f"(d[125]), "+f"(d[126]), "+f"(d[127])
    : "l"(da), "l"(db));
}
__device__ __forceinline__ void wgmma_n256_first(float (&d)[128], uint64_t da, uint64_t db) {
  asm volatile("wgmma.mma_async.sync.aligned.m64n256k16.f32.bf16.bf16 "
    "{%0, %1, %2, %3, %4, %5, %6, %7, %8, %9, %10, %11, %12, %13, %14, %15, %16, %17, %18, %19, %20, %21, %22, %23, %24, %25, %26, %27, %28, %29, %30, %31, %32, %33, %34, %35, %36, %37, %38, %39, %40, %41, %42, %43, %44, %45, %46, %47, %48, %49, %50, %51, %52, %53, %54, %55, %56, %57, %58, %59, %60, %61, %62, %63, %64, %65, %66, %67, %68, %69, %70, %71, %72, %73, %74, %75, %76, %77, %78, %79, %80, %81, %82, %83, %84, %85, %86, %87, %88, %89, %90, %91, %92, %93, %94, %95, %96, %97, %98, %99, %100, %101, %102, %103, %104, %105, %106, %107, %108, %109, %110, %111, %112, %113, %114, %115, %116, %117, %118, %119, %120, %121, %122, %123, %124, %125, %126, %127}, "
    "%128, %129, 0, 1, 1, 0, 1;\n"
    : "=f"(d[0]), "=f"(d[1]), "=f"(d[2]), "=f"(d[3]), "=f"(d[4]), "=f"(d[5]), "=f"(d[6]), "=f"(d[7]), "=f"(d[8]), "=f"(d[9]), "=f"(d[10]), "=f"(d[11]), "=f"(d[12]), "=f"(d[13]), "=f"(d[14]), "=f"(d[15]), "=f"(d[16]), "=f"(d[17]), "=f"(d[18]), "=f"(d[19]), "=f"(d[20]), "=f"(d[21]), "=f"(d[22]), "=f"(d[23]), "=f"(d[24]), "=f"(d[25]), "=f"(d[26]), "=f"(d[27]), "=f"(d[28]), "=f"(d[29]), "=f"(d[30]), "=f"(d[31]), "=f"(d[32]), "=f"(d[33]), "=f"(d[34]), "=f"(d[35]), "=f"(d[36]), "=f"(d[37]), "=f"(d[38]), "=f"(d[39]), "=f"(d[40]), "=f"(d[41]), "=f"(d[42]), "=f"(d[43]), "=f"(d[44]), "=f"(d[45]), "=f"(d[46]), "=f"(d[47]), "=f"(d[48]), "=f"(d[49]), "=f"(d[50]), "=f"(d[51]), "=f"(d[52]), "=f"(d[53]), "=f"(d[54]), "=f"(d[55]), "=f"(d[56]), "=f"(d[57]), "=f"(d[58]), "=f"(d[59]), "=f"(d[60]), "=f"(d[61]), "=f"(d[62]), "=f"(d[63]), "=f"(d[64]), "=f"(d[65]), "=f"(d[66]), "=f"(d[67]), "=f"(d[68]), "=f"(d[69]), "=f"(d[70]), "=f"(d[71]), "=f"(d[72]), "=f"(d[73]), "=f"(d[74]), "=f"(d[75]), "=f"(d[76]), "=f"(d[77]), "=f"(d[78]), "=f"(d[79]), "=f"(d[80]), "=f"(d[81]), "=f"(d[82]), "=f"(d[83]), "=f"(d[84]), "=f"(d[85]), "=f"(d[86]), "=f"(d[87]), "=f"(d[88]), "=f"(d[89]), "=f"(d[90]), "=f"(d[91]), "=f"(d[92]), "=f"(d[93]), "=f"(d[94]), "=f"(d[95]), "=f"(d[96]), "=f"(d[97]), "=f"(d[98]), "=f"(d[99]), "=f"(d[100]), "=f"(d[101]), "=f"(d[102]), "=f"(d[103]), "=f"(d[104]), "=f"(d[105]), "=f"(d[106]), "=f"(d[107]), "=f"(d[108]), "=f"(d[109]), "=f"(d[110]), "=f"(d[111]), "=f"(d[112]), "=f"(d[113]), "=f"(d[114]), "=f"(d[115]), "=f"(d[116]), "=f"(d[117]), "=f"(d[118]), "=f"(d[119]), "=f"(d[120]), "=f"(d[121]), "=f"(d[122]), "=f"(d[123]), "=f"(d[124]), "=f"(d[125]), "=f"(d[126]), "=f"(d[127])
    : "l"(da), "l"(db));
}

template <int N> struct WG;
#define DEF_WG(N) template <> struct WG<N> { \
  static __device__ __forceinline__ void mma(float (&d)[N / 2], uint64_t a, uint64_t b) { wgmma_n##N(d, a, b); } \
  static __device__ __forceinline__ void first(float (&d)[N / 2], uint64_t a, uint64_t b) { wgmma_n##N##_first(d, a, b); } };
DEF_WG(128) DEF_WG(256)

constexpr uint64_t DESC_A = (1ull << 62) | ((uint64_t)(1024 >> 4) << 32) | (1ull << 16);
constexpr uint64_t DESC_B = (1ull << 62) | ((uint64_t)(1024 >> 4) << 32) | ((uint64_t)(8192 >> 4) << 16);

struct Ring { int s; uint32_t ph; int wrap; };
template <int NS> __device__ __forceinline__ void ring_next(Ring& r) { r.s = (r.s + 1 == NS) ? 0 : r.s + 1; if (r.s == r.wrap) r.ph ^= 1; }

__device__ __forceinline__ int own_order(int it, int j) {
  return it < 2 ? 2 * j + it : it < 4 ? 2 * (j ^ 1) + it - 2 : ((j >> 1) * 4 + 2 * it - (it < 10 ? 4 : 15)) & 15;
}

template <int V> struct IC { static constexpr int v = V; };
template <int I, int E, class F> __device__ __forceinline__ void static_for(F&& f) { if constexpr (I < E) { f(IC<I>{}); static_for<I + 1, E>(f); } }

template <int N, int NS, int PRE, int LAG, class Pre, class Mid, class Last>
__device__ __forceinline__ void mainloop(float (&acc)[N / 2], int nkb, bool own, Ring& r, uint32_t sb, int wg, int lane, uint32_t rel_base, Pre pre, Mid mid, Last last) {
  constexpr int SLOT = RING / NS;
  const uint32_t full = sb + MISC + (NS == 4 ? B_FULL4 : B_FULL6);
  const uint32_t rel = rel_base + (NS == 4 ? B_EMPTY4 : B_EMPTY6);
  const uint32_t s0 = (sb & 0x3FFFF) >> 4, a0 = s0 + wg * (HALF >> 4);
  int ps;
  auto issue = [&](int it, bool first) {
    const uint64_t da = DESC_A | (a0 + ((own && it < 2) ? (STG + it * BLK) >> 4 : r.s * (SLOT >> 4))), db = DESC_B | (s0 + r.s * (SLOT >> 4) + (BLK >> 4));
    mbar_wait(full + r.s * 8, r.ph);
    wg_arrive();
    if (first) WG<N>::first(acc, da, db); else WG<N>::mma(acc, da, db);
#pragma unroll
    for (int k = 1; k < 4; k++) WG<N>::mma(acc, da + k * 2, db + k * 128);
    wg_commit();
  };
  auto retire = [&](int it) {
    wg_wait<1>();
    if (lane < 2) mbar_arrive_cl(rel + ps * 8);
    ps = r.s;
    ring_next<NS>(r);
  };
  issue(0, true);
  ps = r.s;
  ring_next<NS>(r);
  static_for<1, PRE + 1>([&](auto ic) { issue(ic.v, false); pre(ic); retire(ic.v); });
#pragma unroll 1
  for (int it = PRE + 1; it < nkb; it++) {
    if (LAG && it == nkb - LAG && wg == 1) mbar_wait(sb + MISC + B_LAG, WOLAG && !own);
    issue(it, false); mid(it); retire(it);
  }
  last();
  wg_wait<0>();
  if (lane < 2) mbar_arrive_cl(rel + ps * 8);
}

__device__ __forceinline__ uint32_t tag_of(uint32_t ep) { return ep % 255u + 1u; }
__device__ __forceinline__ void ln_publish(const float (&v)[64], uint2* st, int j, int row0, int lane, uint32_t ep) {
  float s0 = 0, s1 = 0, s2 = 0, s3 = 0, q0 = 0, q1 = 0, q2 = 0, q3 = 0;
#pragma unroll
  for (int i = 0; i < 16; i++) {
    s0 += v[4 * i]; s1 += v[4 * i + 1]; s2 += v[4 * i + 2]; s3 += v[4 * i + 3];
    q0 = fmaf(v[4 * i], v[4 * i], q0); q1 = fmaf(v[4 * i + 1], v[4 * i + 1], q1); q2 = fmaf(v[4 * i + 2], v[4 * i + 2], q2); q3 = fmaf(v[4 * i + 3], v[4 * i + 3], q3);
  }
  s0 += s1; s2 += s3; q0 += q1; q2 += q3;
  const bool odd = lane & 1;
  float s = (odd ? s2 : s0) + __shfl_xor_sync(~0u, odd ? s0 : s2, 1), q = (odd ? q2 : q0) + __shfl_xor_sync(~0u, odd ? q0 : q2, 1);
  s += __shfl_xor_sync(~0u, s, 2); q += __shfl_xor_sync(~0u, q, 2);
  if ((lane & 3) < 2) st_rlx2(st + j * 128 + row0 + (lane & 1) * 8, __float_as_uint(s), (__float_as_uint(fmaf(s * (-1.f / 128), s, q)) & ~255u) | tag_of(ep));
}
__device__ __forceinline__ void ln_gather(const uint2* st, int row0, int lane, uint32_t ep, float& n0, float& r0, float& n1, float& r1, bool rnd) {
  const uint2* p = st + (lane & 2) * 256 + row0 + (lane & 1) * 8;
  const uint32_t tag = tag_of(ep);
  uint2 a, b, c, d; uint32_t n = 0;
  while (true) {
    a = ld_rlx2(p); b = ld_rlx2(p + 128); c = ld_rlx2(p + 256); d = ld_rlx2(p + 384);
    if ((((a.y ^ tag) | (b.y ^ tag) | (c.y ^ tag) | (d.y ^ tag)) & 255u) == 0) break;
    SPIN_GUARD(n);
  }
  __syncwarp();
  const uint32_t fix = tag ^ 128u;
  float s = (__uint_as_float(a.x) + __uint_as_float(b.x)) + (__uint_as_float(c.x) + __uint_as_float(d.x));
  float q = (__uint_as_float(a.y ^ fix) + __uint_as_float(b.y ^ fix)) + (__uint_as_float(c.y ^ fix) + __uint_as_float(d.y ^ fix));
  q = fmaf(fmaf(__uint_as_float(a.x), __uint_as_float(a.x), __uint_as_float(b.x) * __uint_as_float(b.x)) +
           fmaf(__uint_as_float(c.x), __uint_as_float(c.x), __uint_as_float(d.x) * __uint_as_float(d.x)), 1.f / 128, q);
  s += __shfl_xor_sync(~0u, s, 2); q += __shfl_xor_sync(~0u, q, 2);
  s *= 1.f / 1024;
  const float var = fmaxf(fmaf(-s, s, q * (1.f / 1024)), 0.f);
  float r;
  if (rnd) {
    float sd; asm("sqrt.approx.f32 %0, %1;" : "=f"(sd) : "f"(bf_round(bf_round(var) + 1e-5f)));
    r = rcp(bf_round(sd)); s = bf_round(s);
  } else r = rsqrtf(var + 1e-5f);
  const float nn = -s * r;
  const float ro = __shfl_xor_sync(~0u, r, 1), no = __shfl_xor_sync(~0u, nn, 1);
  const bool odd = lane & 1;
  r0 = odd ? ro : r; n0 = odd ? no : nn; r1 = odd ? r : ro; n1 = odd ? nn : no;
}
__device__ __forceinline__ void load_vec(uint32_t* w, uint32_t sb, int sec, int b, int lane) {
#pragma unroll
  for (int q = 0; q < 2; q++) { uint4 t = lds128(sb + MISC + MODV + sec * 256 + (lane & 3) * 64 + b * 32 + q * 16); w[4 * q] = t.x; w[4 * q + 1] = t.y; w[4 * q + 2] = t.z; w[4 * q + 3] = t.w; }
}
__device__ __forceinline__ void stage_done(uint32_t sb, int wg, int b, int lane) {
  fence_async_smem();
  __syncwarp();
  if (lane == 0) mbar_arrive(sb + MISC + B_RDY + b * 8);
}
__device__ __forceinline__ uint32_t hfma2(uint32_t a, uint32_t b, uint32_t c) { uint32_t r; asm("fma.rn.bf16x2 %0, %1, %2, %3;" : "=r"(r) : "r"(a), "r"(b), "r"(c)); return r; }
__device__ __forceinline__ void ln_apply(const float (&v)[64], const uint2* st, int row0, uint32_t ep, uint32_t sb, int sec_shift, int sec_scale, uint32_t stg_row, int wg, int lane) {
  uint32_t sc[16], sh[16];
#pragma unroll
  for (int b = 0; b < 2; b++) { load_vec(sc + 8 * b, sb, sec_scale, b, lane); load_vec(sh + 8 * b, sb, sec_shift, b, lane); }
  float n0, r0, n1, r1;
  ln_gather(st, row0, lane, ep, n0, r0, n1, r1, sec_shift == 0);
#pragma unroll
  for (int i = 0; i < 16; i += 2) {
    if (i == 8) { const float z = lds32f(sb + MISC + ZERO); n0 += z; n1 += z; }
    uint32_t w[4];
#pragma unroll
    for (int u = 0; u < 2; u++) {
      int q = i + u;
      w[2 * u] = hfma2(pack2(fmaf(v[4 * q], r0, n0), fmaf(v[4 * q + 1], r0, n0)), sc[q], sh[q]);
      w[2 * u + 1] = hfma2(pack2(fmaf(v[4 * q + 2], r1, n1), fmaf(v[4 * q + 3], r1, n1)), sc[q], sh[q]);
    }
    stsm4(stg_row + (i >> 3) * BLK + ((((i & 7) + (lane >> 4)) ^ (lane & 7)) << 4), w[0], w[1], w[2], w[3]);
    if ((i & 7) == 6) { stage_done(sb, wg, i >> 3, lane); }
  }
}
__device__ __forceinline__ uint32_t hmul2(uint32_t a, uint32_t b) { uint32_t r; asm("mul.rn.bf16x2 %0, %1, %2;" : "=r"(r) : "r"(a), "r"(b)); return r; }
__device__ __forceinline__ uint32_t silu_mul2(uint32_t g, uint32_t u) {
  const uint32_t h = hmul2(g, 0x3f003f00u);
  const float h0 = bf_lo(h), h1 = bf_hi(h);
  return hmul2(pack2(fmaf(h0, tanh_fast(h0), h0), fmaf(h1, tanh_fast(h1), h1)), u);
}

__device__ __forceinline__ void gemv_fma(float (&a)[8], uint4 w, float s) {
  a[0] = fmaf(bf_lo(w.x), s, a[0]); a[1] = fmaf(bf_hi(w.x), s, a[1]); a[2] = fmaf(bf_lo(w.y), s, a[2]); a[3] = fmaf(bf_hi(w.y), s, a[3]);
  a[4] = fmaf(bf_lo(w.z), s, a[4]); a[5] = fmaf(bf_hi(w.z), s, a[5]); a[6] = fmaf(bf_lo(w.w), s, a[6]); a[7] = fmaf(bf_hi(w.w), s, a[7]);
}
__device__ __forceinline__ float silu_c(float v) { return bf_round(__fdividef(v, 1.f + __expf(-v))); }
__device__ __forceinline__ float mod_gather(const uint32_t* p, uint32_t ep) {
  const uint32_t tag = tag_of(ep), fix = tag ^ 128u;
  uint32_t a, b, c, d, n = 0;
  while (true) {
    a = ld_rlx1(p); b = ld_rlx1(p + 128); c = ld_rlx1(p + 256); d = ld_rlx1(p + 384);
    if ((((a ^ tag) | (b ^ tag) | (c ^ tag) | (d ^ tag)) & 255u) == 0) break;
    SPIN_GUARD(n);
  }
  return (__uint_as_float(a ^ fix) + __uint_as_float(b ^ fix)) + (__uint_as_float(c ^ fix) + __uint_as_float(d ^ fix));
}
__device__ __forceinline__ void mod_store(uint32_t sb, int sec, int col, float v) {
  v = bf_round(v);
  if (sec == 1 || sec == 4) v += 1.f;
  sts16(sb + MISC + MODV + sec * 256 + (((col >> 1) & 3) * 16 + (col >> 3)) * 4 + (col & 1) * 2, __float2bfloat16_rn(v));
}

__global__ void __cluster_dims__(2, 1, 1) __launch_bounds__(384, 1)
fused_kernel(const bf16* __restrict__ cvec, const bf16* __restrict__ wmod, Scratch* gs, int by_sm, const __grid_constant__ Maps maps) {
  extern __shared__ __align__(1024) uint8_t smem_raw[];
  const uint32_t sb = smem_u32(smem_raw);
  const int warp = __shfl_sync(~0u, threadIdx.x >> 5, 0), lane = threadIdx.x & 31;
  const int rank = blockIdx.x & 1;
  uint32_t sm; asm volatile("mov.u32 %0, %%smid;" : "=r"(sm));
  const int t = sm >> 1, v = t < 32 ? t : t < 60 ? t + 1 + (((t - 32) * 37) >> 8) : (t - 58) * 8;
  const int cid = !by_sm ? (blockIdx.x >> 1) - 2 : (t & ~1) == 60 ? t - 62 : (v & 1) * 32 + ((v >> 1) & 31);
  const bool extra = cid < 0;
  const int bid = cid * 2 + rank;
  const int m = cid >> 2, j = (cid & 3) * 2 + rank;
  const uint32_t bar = sb + MISC;

  if (warp >= 8) {
    asm volatile("setmaxnreg.dec.sync.aligned.u32 40;");
    if (extra) {
      if (warp == 8) {
        if (lane == 0) { for (int s = 0; s < 6; s++) { mbar_init(bar + B_FULL6 + s * 8, 1); mbar_init(bar + B_EMPTY6 + s * 8, 8); } fence_async_smem(); }
        __syncwarp();
        asm volatile("bar.arrive 2, 288;" ::: "memory");
        __nanosleep(XSLEEP);
#pragma unroll 1
        for (int it = 0, s = 0, par = 1; it < 64; it++) {
          mbar_wait(bar + B_EMPTY6 + s * 8, par);
          if (elect()) { mbar_expect_tx(bar + B_FULL6 + s * 8, 32768); tma_3d(sb + s * 32768, &maps.wmod, bar + B_FULL6 + s * 8, 0, (it & 15) * 64, 12 + (it >> 4) * 4 + bid); }
          if (++s == 6) { s = 0; par ^= 1; }
        }
      }
    } else if (warp < 10) {
      uint32_t s6 = 0, p6 = 1;
      auto next6 = [&]() { if (++s6 == 6) { s6 = 0; p6 ^= 1; } };
      auto drained4 = [&](int q, int late) { if (q < 5) mbar_wait(bar + B_EMPTY4 + (((late ? 0x10332 : 0x32110) >> (4 * q)) & 3) * 8, 1); };
      auto drained6 = [&](int q) { if (q < 3) mbar_wait(bar + B_EMPTY6 + ((0x154 >> (4 * q)) & 7) * 8, q >> 1); };
      auto skip6 = [&]() { mbar_wait(bar + B_EMPTY6 + s6 * 8, p6); if (elect()) mbar_arrive(bar + B_FULL6 + s6 * 8); next6(); };
      if (warp == 8) {
        const uint32_t t_start = clock();
        if (lane == 0) {
          if (sb & 1023) bail();
          for (int b = 0; b < 2; b++) mbar_init(bar + B_X + b * 8, 1);
          for (int s = 0; s < 4; s++) { mbar_init(bar + B_FULL4 + s * 8, 2); mbar_init(bar + B_EMPTY4 + s * 8, 16); }
          for (int s = 0; s < 6; s++) { mbar_init(bar + B_FULL6 + s * 8, 2); mbar_init(bar + B_EMPTY6 + s * 8, 16); }
          for (int b = 0; b < 2; b++) { mbar_init(bar + B_RDY + b * 8, 8); mbar_init(bar + B_FREE + b * 8, 1); mbar_init(bar + B_HH + b * 8, 1); }
          mbar_init(bar + B_MOD, 1); mbar_init(bar + B_LAG, 4); mbar_init(bar + B_HALO, 2); mbar_init(bar + B_ALL, 1); mbar_init(bar + B_HH2, 1);
          asm volatile("st.shared.u32 [%0], 0;" :: "r"(bar + ZERO) : "memory");
          asm volatile("fence.mbarrier_init.release.cluster;" ::: "memory");
          fence_async_smem();
        }
        __syncwarp();
        cl_arrive_relaxed();
        auto wide = [&](int s, int par, const CUtensorMap* m0, int a0, const CUtensorMap* m1, int a1, int kb, bool spaced) {
          const uint32_t full = bar + B_FULL4 + s * 8, d = sb + s * 49152 + BLK;
          mbar_wait(full + 32, par);
          const uint32_t t0 = clock();
          if (elect()) { mbar_expect_tx(full, 2 * BLK); tma_3d(d, m0, full, 0, kb * 64, a0); }
          if (spaced) while ((uint32_t)clock() - t0 < 300) {}
          if (elect()) tma_3d(d + BLK, m1, full, 0, kb * 64, a1);
          if (spaced) while ((uint32_t)clock() - t0 < 600) {}
        };
        auto narrow = [&](const CUtensorMap* m0, int kb) {
          const uint32_t full = bar + B_FULL6 + s6 * 8;
          mbar_wait(full + 48, p6);
          if (elect()) { mbar_expect_tx(full, BLK); tma_3d(sb + s6 * 32768 + BLK, m0, full, 0, kb * 64, 2 * j); }
          next6();
        };
#pragma unroll 1
        for (int it = 0; it < 16; it++) {
          if (it == 0) {
            while ((uint32_t)clock() - t_start < XDELAY) {}
            if (elect()) for (int b = 0; b < 2; b++) { mbar_expect_tx(bar + B_X + b * 8, BLK); tma_3d(sb + STG + b * BLK, &maps.x, bar + B_X + b * 8, j * 128 + b * 64, m * 64, 0); }
            mbar_wait(bar + B_X + 8, 0);
          }
          wide(it & 3, ~(it >> 2) & 1, &maps.wqkv, 16 + 2 * j, &maps.wqkv, 32 + 2 * j, own_order(it, j), it < 4);
        }
#pragma unroll 1
        for (int it = 0; it < 16; it++) { drained4(it, 0); narrow(&maps.wqkv, it); }
#pragma unroll 1
        for (int it = 0; it < 16; it++) narrow(&maps.wo, own_order(it, j));
        skip6();
#pragma unroll 1
        for (int it = 0; it < 48; it++) {
          const int s = (it + 2) & 3, par = ~(it >> 2) & 1;
          drained6(it);
          wide(s, par, &maps.w1, (it & 48) + 2 * j, &maps.w3, (it & 48) + 2 * j, it < 16 ? own_order(it, j) : it & 15, it < 4);
          if (it >= 44) {
            if (it == 44) { mbar_wait(bar + B_FREE, 0); mbar_wait(bar + B_FREE + 8, 0); if (elect()) mbar_expect_tx(bar + B_X, 2 * BLK); }
            if (elect()) bulk_ld(sb + STG + (it - 44) * HALF, gs->x1 + bid * 2048 + (it - 44) * 512, HALF, bar + B_X);
          }
        }
#pragma unroll 1
        for (int it = 0; it < 16; it++) {
          const uint32_t full = bar + B_FULL6 + s6 * 8, d = sb + s6 * 32768 + BLK;
          drained4(it, 1);
          mbar_wait(full + 48, p6);
          if (elect()) { mbar_expect_tx(full, BLK); tma_3d(d, &maps.w1s, full, 0, it * 64, 48 + j); tma_3d(d + HALF, &maps.w3s, full, 0, it * 64, 48 + j); }
          next6();
        }
#pragma unroll 1
        for (int it = 0; it < 56; it++) narrow(&maps.w2, it);
      } else {
        if (lane < 9) prefetch_map(&maps.x + lane);
        const uint32_t ep = gs->epoch[bid + 4] + 1;
        cl_arrive_relaxed(); cl_wait();
        auto plain = [&](uint32_t full, uint32_t empty, int par, uint32_t slot, const uint4* blk) {
          mbar_wait(empty, par);
          if (elect()) { mbar_expect_tx(full, BLK); bulk_ld_mc(slot + rank * HALF, blk + rank * 512, HALF, full); }
        };
        auto plain6 = [&](const uint4* blk) { plain(bar + B_FULL6 + s6 * 8, bar + B_EMPTY6 + s6 * 8, p6, sb + s6 * 32768, blk); next6(); };
        uint32_t ready = 0;
        auto poll = [&](int e) { ready = __ballot_sync(~0u, ld_acquire(gs->flag + (m * 128 + e * 16 + (lane & 14)) * FS) == ep); };
        auto need = [&](int e, uint32_t mask) {
          if ((ready & mask) != mask) {
            uint32_t n = 0;
            do { poll(e); SPIN_GUARD(n); } while ((ready & mask) != mask);
            fence_async_global();
          }
        };
        auto fresh = [&](int e, int it, uint32_t full, uint32_t empty, int par, uint32_t slot, uint4* src) {
          if (it >= 4) {
            const int kb = own_order(it, j);
            if (it < 10) need(e, 1u << kb); else if (it == 10) mbar_wait(bar + B_ALL, e & 1);
            plain(full, empty, par, slot, src + kb * 1024);
          } else {
            if (it == 0) ready = 0;
            mbar_wait(empty, par);
            if (it < 2) { if (elect()) mbar_arrive(full); }
            else {
              const int b = it > 2;
              const uint32_t to_peer = mapa(sb, rank ^ 1) - sb;
              if (elect()) mbar_expect_tx(full, BLK);
              const bool push = e != 1;
              mbar_wait(bar + (b ? (push ? B_RDY + 8 : B_FREE + 8) : B_RDY), e & 1);
              if (elect()) {
                if (b == 0) {
                  bulk_st(src + 2 * j * 1024, sb + STG, BLK);
                  bulk_commit();
                  bulk_wait_all();
                  mbar_arrive(bar + B_FREE);
                }
                if (b && push) bulk_push(slot + to_peer, sb + STG + BLK, BLK, full + to_peer);
                else {
                  fence_async_global();
                  bulk_ld(slot + to_peer, src + (2 * j + b) * 1024, BLK, full + to_peer);
                }
              }
              __syncwarp();
            }
          }
        };
#pragma unroll 1
        for (int ph = 0; ph < 2; ph++) {
          uint4* h = gs->h + m * 16384;
#pragma unroll 1
          for (int it = 0; it < 16; it++) {
            const int s = (it + 2 * ph) & 3;
            if (ph) drained6(it);
            fresh(2 * ph, it, bar + B_FULL4 + s * 8, bar + B_EMPTY4 + s * 8, ~(it >> 2) & 1, sb + s * 49152, h);
          }
          if (ph) {
#pragma unroll 1
            for (int it = 16; it < 48; it++) {
              const int s = (it + 2) & 3;
              const uint32_t full = bar + B_FULL4 + s * 8;
              plain(full, full + 32, ~(it >> 2) & 1, sb + s * 49152, h + (it & 15) * 1024);
            }
          }
#pragma unroll 1
          for (int it = 0; it < 16; it++) { drained4(it, ph); plain6(h + it * 1024); }
          if (!ph) {
#pragma unroll 1
            for (int it = 0; it < 16; it++) { fresh(1, it, bar + B_FULL6 + s6 * 8, bar + B_EMPTY6 + s6 * 8, p6, sb + s6 * 32768, gs->o + m * 16384); next6(); }
            skip6();
          }
        }
#pragma unroll 1
        for (int it = 0; it < 56; it++) {
          if (it == 0 || it == 32 || it == 48) mbar_wait(bar + (it == 48 ? B_HH2 : B_HH + (it >> 2)), 0);
          plain6(gs->hh + m * 57344 + it * 1024);
        }
      }
    } else {
      const int b = warp - 10;
      const uint32_t ep = gs->epoch[bid + 4] + 1;
      const uint32_t stg = sb + STG + b * BLK;
      cl_arrive_relaxed(); cl_wait();
      auto all_there = [&](int u, uint32_t done) {
        const uint32_t* fl = gs->flag + u * FS;
        uint32_t n = 0;
        while (!__all_sync(~0u, ld_acquire(fl) == ep)) { __nanosleep(100); SPIN_GUARD(n); }
        fence_async_global();
        if (lane == 0) mbar_arrive(done);
      };
      auto fetch_mod = [&](int sec) {
        const uint4* p = (const uint4*)(gs->modv + (sec - 2) * 1024 + j * 128) + lane;
        uint4 v0, v1; uint32_t n = 0;
        while (true) {
          v0 = ld_rlx4(p); v1 = ld_rlx4(p + 32);
          if (v0.y == ep && v0.w == ep && v1.y == ep && v1.w == ep) break;
          SPIN_GUARD(n);
        }
        mod_store(sb, sec, 2 * lane, __uint_as_float(v0.x)); mod_store(sb, sec, 2 * lane + 1, __uint_as_float(v0.z));
        mod_store(sb, sec, 64 + 2 * lane, __uint_as_float(v1.x)); mod_store(sb, sec, 65 + 2 * lane, __uint_as_float(v1.z));
        __syncwarp();
      };
#pragma unroll 1
      for (int e = 0; e < 7 - b; e++) {
        if (lane == 0) {
          if (e < 3) {
            mbar_wait(bar + B_FREE, e & 1);
            if (b) {
              const uint32_t t0 = clock();
              while ((uint32_t)clock() - t0 < (e == 0 ? B1P : e == 2 ? B1P2 : B1D)) {}
              mbar_wait(bar + B_RDY + 8, e & 1);
              bulk_st((e == 1 ? gs->o : gs->h) + m * 16384 + (2 * j + 1) * 1024, stg, BLK);
              bulk_commit();
              bulk_wait_all();
              mbar_arrive(bar + B_FREE + 8);
            }
            st_release(gs->flag + (m * 128 + e * 16 + 2 * j + b) * FS, ep);
          } else {
            const int kb = (e < 6 ? 2 * (8 * (e - 3) + j) : 48 + j) + b;
            mbar_wait(bar + B_RDY + b * 8, e & 1);
#pragma unroll 1
            for (int q = 0; q < NPIECE; q++) { if (q) __nanosleep(PSLEEP); bulk_st(gs->hh + m * 57344 + kb * 1024 + q * (1024 / NPIECE), stg + q * (BLK / NPIECE), BLK / NPIECE); }
            bulk_commit();
            bulk_wait_all();
            mbar_arrive(bar + B_FREE + b * 8);
            st_release(gs->flag + (m * 128 + U_HH + kb) * FS, ep);
          }
        }
        __syncwarp();
        if (e < 3 && b) all_there(m * 128 + e * 16 + (lane & 15), bar + B_ALL);
        if (e == 4 && b) all_there(m * 128 + U_HH + lane, bar + B_HH);
        if (!b && (e == 1 || e == 2)) {
#pragma unroll 1
          for (int sec = e == 1 ? 2 : 5; sec < 4 + e; sec++) fetch_mod(sec);
          if (e == 1) { if (lane == 0) mbar_arrive(bar + B_MOD); }
        }
        if (e == 0) {
          mbar_wait(bar + B_EMPTY6 + 24, 0);
          __nanosleep(HSLEEP);
#pragma unroll 1
          for (int w = 0; w < 4; w++) {
            const uint4* hp = gs->halo + ((m * 8 + j) * 2 + (w & 1)) * 512 + b * 256 + (w >> 1) * 128 + lane;
            uint4 q[4] = {}; uint32_t n = 0;
            while (m > 0) {
              bool ok = true;
#pragma unroll
              for (int i = 0; i < 4; i++) q[i] = ld_rlx4(hp + i * 32);
#pragma unroll
              for (int i = 0; i < 4; i++) ok = ok && q[i].y == ep && q[i].w == ep;
              if (ok) break;
              SPIN_GUARD(n);
            }
#pragma unroll
            for (int i = 0; i < 2; i++) sts128(stg + lane * 16 + (w & 1) * HALF + (w >> 1) * 1024 + i * 512, q[2 * i].x, q[2 * i + 1].x, q[2 * i].z, q[2 * i + 1].z);
          }
          __syncwarp();
          if (lane == 0) mbar_arrive(bar + B_HALO);
        }
      }
      if (b) { all_there(m * 128 + U_HH + 32 + (lane & 15), bar + B_HH + 8); all_there(m * 128 + U_HH + 48 + (lane & 7), bar + B_HH2); }
    }
  } else {
    const int wg = warp >> 2, wq = warp & 3, tid = threadIdx.x;
    const int g = lane >> 2, c = lane & 3;
    const int sec0 = (m >> 1) & 1, hf0 = m & 1, ks0 = (m >> 2) & 3;
    uint4 wv[8];
    uint32_t ep0; uint16_t cv_;
    asm volatile("ld.global.nc.u16 %0, [%1];" : "=h"(cv_) : "l"(cvec + ks0 * 256 + warp * 32 + lane));
    asm volatile("ld.global.u32 %0, [%1];" : "=r"(ep0) : "l"(gs->epoch + bid + 4));
    if (!extra) {
      const bf16* wp = wmod + (size_t)(ks0 * 256 + warp * 32 + (lane >> 3)) * 6144 + sec0 * 1024 + j * 128 + hf0 * 64 + (lane & 7) * 8;
#pragma unroll
      for (int i = 0; i < 8; i++) wv[i] = ldg_nc(wp + (size_t)i * 4 * 6144);
    }
    asm volatile("setmaxnreg.inc.sync.aligned.u32 232;" ::: "memory");
    if (__builtin_expect(extra, 0)) {
      const uint32_t ep = ep0 + 1;
      float sv[4];
#pragma unroll
      for (int p = 0; p < 4; p++) sv[p] = silu_c(__bfloat162float(cvec[64 * (4 * p + (lane >> 3)) + 8 * warp + (lane & 7)]));
      named_bar(2, 288);
      int s = 0, par = 0;
#pragma unroll 1
      for (int sec = 0; sec < 4; sec++) {
        float a[8] = {0, 0, 0, 0, 0, 0, 0, 0};
#pragma unroll 1
        for (int it = 0; it < 16; it++) {
          const float sc = it < 4 ? sv[0] : it < 8 ? sv[1] : it < 12 ? sv[2] : sv[3];
          mbar_wait(bar + B_FULL6 + s * 8, par);
          uint4 w[8];
#pragma unroll
          for (int i = 0; i < 8; i++) w[i] = lds128(sb + s * 32768 + (warp * 8 + i) * 512 + lane * 16);
#pragma unroll
          for (int i = 0; i < 8; i++) gemv_fma(a, w[i], __shfl_sync(~0u, sc, (it & 3) * 8 + i));
          if (lane == 0) mbar_arrive(bar + B_EMPTY6 + s * 8);
          if (++s == 6) { s = 0; par ^= 1; }
        }
        const uint32_t red = sb + STG + sec * 8192;
        sts128(red + warp * 1024 + lane * 32, __float_as_uint(a[0]), __float_as_uint(a[1]), __float_as_uint(a[2]), __float_as_uint(a[3]));
        sts128(red + warp * 1024 + lane * 32 + 16, __float_as_uint(a[4]), __float_as_uint(a[5]), __float_as_uint(a[6]), __float_as_uint(a[7]));
        named_bar(1, 256);
        float t = 0;
#pragma unroll
        for (int q = 0; q < 8; q++) t += lds32f(red + q * 1024 + tid * 4);
        st_rlx2(gs->modv + sec * 1024 + (bid + 4) * 256 + tid, __float_as_uint(t), ep);
      }
      if (tid == 0) gs->epoch[bid + 4] = ep;
      return;
    }
    const int row0 = wg * 64 + wq * 16 + g;
    if (c < 2) st_rlx2(gs->stat + m * 1024 + j * 128 + row0 + c * 8, 0, 0);
    if (tid < 64) st_rlx1(gs->modp + ((j * 2 + sec0) * 4 + ks0) * 128 + hf0 * 64 + tid, 0);
    cl_arrive_relaxed(); cl_wait();
    uint32_t ep;
    asm volatile("add.u32 %0, %1, 1;" : "=r"(ep) : "r"(ep0) : "memory");
    const float sc_ = silu_c(__uint_as_float((uint32_t)cv_ << 16));
    const uint32_t rel = mapa(bar, (lane & 1) ^ rank);
    const uint32_t stg_row = sb + STG + (wg * 64 + wq * 16 + (lane & 15)) * 128;
    const uint32_t fre = bar + B_FREE;
    Ring r4{0, 0, 0}, r6{0, 0, 0};
    auto none = [](auto) {};
    uint32_t xk[32];
    {
      float a[8] = {0, 0, 0, 0, 0, 0, 0, 0};
#pragma unroll
      for (int i = 0; i < 8; i++) gemv_fma(a, wv[i], __shfl_sync(~0u, sc_, i * 4 + (lane >> 3)));
#pragma unroll
      for (int i = 0; i < 8; i++) { a[i] += __shfl_xor_sync(~0u, a[i], 8); a[i] += __shfl_xor_sync(~0u, a[i], 16); }
      if (lane < 8) {
        sts128(sb + RED_OFF + warp * 256 + lane * 32, __float_as_uint(a[0]), __float_as_uint(a[1]), __float_as_uint(a[2]), __float_as_uint(a[3]));
        sts128(sb + RED_OFF + warp * 256 + lane * 32 + 16, __float_as_uint(a[4]), __float_as_uint(a[5]), __float_as_uint(a[6]), __float_as_uint(a[7]));
      }
      named_bar(1, 256);
      if (tid < 64) {
        float s = 0;
#pragma unroll
        for (int w = 0; w < 8; w++) s += lds32f(sb + RED_OFF + w * 256 + tid * 4);
        st_rlx1(gs->modp + ((j * 2 + sec0) * 4 + ks0) * 128 + hf0 * 64 + tid, (__float_as_uint(s) & ~255u) | tag_of(ep));
      }
      float v[64];
      mbar_wait(bar + B_X, 0); mbar_wait(bar + B_X + 8, 0);
#pragma unroll
      for (int i = 0; i < 16; i += 2) {
        uint32_t w0, w1, w2, w3;
        ldsm4(stg_row + (i >> 3) * BLK + ((((i & 7) + (lane >> 4)) ^ (lane & 7)) << 4), w0, w1, w2, w3);
        xk[2 * i] = w0; xk[2 * i + 1] = w1; xk[2 * i + 2] = w2; xk[2 * i + 3] = w3;
        v[4 * i] = bf_lo(w0); v[4 * i + 1] = bf_hi(w0); v[4 * i + 2] = bf_lo(w1); v[4 * i + 3] = bf_hi(w1);
        v[4 * i + 4] = bf_lo(w2); v[4 * i + 5] = bf_hi(w2); v[4 * i + 6] = bf_lo(w3); v[4 * i + 7] = bf_hi(w3);
      }
      ln_publish(v, gs->stat + m * 1024, j, row0, lane, ep);
      mod_store(sb, tid >> 7, tid & 127, mod_gather(gs->modp + (j * 2 + (tid >> 7)) * 512 + (tid & 127), ep));
      named_bar(1, 256);
      ln_apply(v, gs->stat + m * 1024, row0, ep, sb, 0, 1, stg_row, wg, lane);
      named_bar(1, 256);
    }
    {
      uint32_t kf[32], vf[32], pv[32];
      const bool first = wq == 0 && m == 0;
      const uint32_t xa = sb + STG + wg * HALF + wq * 2048 + lane * 16;
      {
        float acc[128];
        mainloop<256, 4, 0, 0>(acc, 16, true, r4, sb, wg, lane, rel, none, none, [&] {
          mbar_wait(fre + 8, 0);
          if (c < 2) st_rlx2(gs->stat + (16 + m) * 1024 + j * 128 + row0 + c * 8, 0, 0);
        });
#pragma unroll
        for (int i = 0; i < 32; i++) { kf[i] = pack2(acc[2 * i], acc[2 * i + 1]); vf[i] = pack2(acc[64 + 2 * i], acc[65 + 2 * i]); }
      }
      float acc[64];
      constexpr int QP = 2;
      mainloop<128, 6, 8 / QP, 0>(acc, 16, false, r6, sb, wg, lane, rel, [&](auto ic) {
        constexpr int q = (ic.v - 1) * QP;
#pragma unroll
        for (int i = 4 * q; i < 4 * (q + QP); i++) vf[i] = movm(vf[i]);
        if (wq == 3) {
          if (m < 15) {
            uint4* hp = gs->halo + (((m + 1) * 8 + j) * 2 + wg) * 512 + lane;
#pragma unroll
            for (int i = 2 * q; i < 2 * (q + QP); i++) st_rlx4(hp + i * 32, kf[2 * i + 1], ep, vf[2 * i + 1], ep);
          }
        } else {
#pragma unroll
          for (int i = q; i < q + QP; i++) sts128(xa + 2048 + (i >> 2) * BLK + (i & 3) * 512, kf[4 * i + 1], kf[4 * i + 3], vf[4 * i + 1], vf[4 * i + 3]);
        }
      }, none, [&] {
        named_bar(2 + wg, 128);
        if (wq == 0) mbar_wait(bar + B_HALO, 0);
#pragma unroll
        for (int i = 0; i < 8; i++) {
          uint4 q = lds128(xa + (i >> 2) * BLK + (i & 3) * 512);
          pv[4 * i] = q.x; pv[4 * i + 1] = q.y; pv[4 * i + 2] = q.z; pv[4 * i + 3] = q.w;
        }
        __syncwarp();
      });
      int gz = g;
#pragma unroll
      for (int b = 0; b < 2; b++) {
        const bool up0 = 2 * c > gz, up1 = 2 * c + 1 > gz;
        const uint32_t mup = (up0 ? 0xffffu : 0u) | (up1 ? 0xffff0000u : 0u);
        float l[2][4], mx[4];
#pragma unroll
        for (int h = 0; h < 2; h++) {
          uint32_t q[8];
          const int k = 16 * b + 8 * h;
#pragma unroll
          for (int i = 0; i < 8; i++) q[i] = pack2(acc[2 * k + 2 * i], acc[2 * k + 2 * i + 1]);
          float s0[4], s1[4], s2[4];
          mma16z(s0, q[0], q[1], q[2], q[3], pv[k], pv[k + 1]); mma16z(s1, q[0], q[1], q[2], q[3], kf[k], kf[k + 2]); mma16z(s2, q[0], q[1], q[2], q[3], kf[k + 1], kf[k + 3]);
          mma16(s0, q[4], q[5], q[6], q[7], pv[k + 4], pv[k + 5]); mma16(s1, q[4], q[5], q[6], q[7], kf[k + 4], kf[k + 6]); mma16(s2, q[4], q[5], q[6], q[7], kf[k + 5], kf[k + 7]);
          if (first) { s0[0] = -INFINITY; s0[1] = -INFINITY; }
          l[h][0] = up0 ? s0[0] : s1[0]; l[h][1] = up1 ? s0[1] : s1[1]; l[h][2] = up0 ? s1[2] : s2[2]; l[h][3] = up1 ? s1[3] : s2[3];
          mx[2 * h] = fmaxf(l[h][0], l[h][1]); mx[2 * h + 1] = fmaxf(l[h][2], l[h][3]);
        }
#pragma unroll
        for (int o = 1; o < 4; o <<= 1) {
#pragma unroll
          for (int h = 0; h < 4; h++) mx[h] = fmaxf(mx[h], __shfl_xor_sync(~0u, mx[h], o));
        }
#pragma unroll
        for (int h = 0; h < 2; h++) {
          const float n0 = -mx[2 * h] * SCL, n1 = -mx[2 * h + 1] * SCL;
          const uint32_t pa = pack2(ex2(fmaf(l[h][0], SCL, n0)), ex2(fmaf(l[h][1], SCL, n0))), pb = pack2(ex2(fmaf(l[h][2], SCL, n1)), ex2(fmaf(l[h][3], SCL, n1)));
          float sm[4];
          mma8z(sm, pa, pb, 0x3f803f80u);
          const float ia = rcp(sm[0]), ib = rcp(sm[2]);
#pragma unroll
          for (int i = 8 * b + 4 * h; i < 8 * b + 4 * h + 4; i += 2) {
            uint32_t of[4];
#pragma unroll
            for (int d = 0; d < 2; d++) {
              float o[4];
              mma16z(o, pa & ~mup, pb & mup, 0u, pb & ~mup, vf[2 * (i + d)], vf[2 * (i + d) + 1]);
              mma8(o, pa & mup, 0u, pv[2 * i + 2 + d]);
              of[2 * d] = pack2(o[0] * ia, o[1] * ia); of[2 * d + 1] = pack2(o[2] * ib, o[3] * ib);
            }
            stsm4(stg_row + b * BLK + ((((i & 7) + (lane >> 4)) ^ (lane & 7)) << 4), of[0], of[1], of[2], of[3]);
          }
        }
        stage_done(sb, wg, b, lane);
        if (b == 0) gz += __float_as_uint(lds32f(bar + ZERO));
      }
      named_bar(1, 256);
    }
    uint32_t pk[64];
    {
      float acc[64];
      mainloop<128, 6, 0, WOLAG>(acc, 16, true, r6, sb, wg, lane, rel, none, none, [&] {
        if (WOLAG && wg == 0 && lane == 0) mbar_arrive(bar + B_LAG);
        mbar_wait(bar + B_MOD, 0); mbar_wait(fre + 8, 1);
        load_vec(pk + 32, sb, 2, 0, lane); load_vec(pk + 40, sb, 2, 1, lane);
#pragma unroll
        for (int i = 0; i < 32; i++) { pk[i] = xk[i]; asm volatile("" : "+r"(pk[i])); }
      });
#pragma unroll
      for (int i = 0; i < 32; i++) {
        acc[2 * i] = fmaf(acc[2 * i], bf_lo(pk[32 + (i >> 1)]), bf_lo(pk[i]));
        acc[2 * i + 1] = fmaf(acc[2 * i + 1], bf_hi(pk[32 + (i >> 1)]), bf_hi(pk[i]));
      }
      ln_publish(acc, gs->stat + (16 + m) * 1024, j, row0, lane, ep);
      mbar_wait(bar + B_FULL6 + 16, 1);
      if (lane < 2) mbar_arrive_cl(rel + B_EMPTY6 + 16);
      ring_next<6>(r6);
#pragma unroll
      for (int i = 0; i < 32; i++) { pk[i] = pack2(acc[2 * i], acc[2 * i + 1]); pk[32 + i] = 0; }
      ln_apply(acc, gs->stat + (16 + m) * 1024, row0, ep, sb, 3, 4, stg_row, wg, lane);
      named_bar(1, 256);
    }
    auto swiglu = [&](int q, int uo, int par) {
      if ((q & 3) == 0 && par >= 0) mbar_wait(fre + 2 * q, par);
      uint32_t w[4];
#pragma unroll
      for (int u = 0; u < 4; u++) w[u] = silu_mul2(pk[4 * q + u], pk[uo + 4 * q + u]);
      stsm4(stg_row + (q >> 2) * BLK + ((((2 * q & 7) + (lane >> 4)) ^ (lane & 7)) << 4), w[0], w[1], w[2], w[3]);
    };
    r4.s = r4.wrap = 2;
#pragma unroll 1
    for (int t = 0; t < 3; t++) {
      float acc[128];
      mainloop<256, 4, 5, 0>(acc, 16, t == 0, r4, sb, wg, lane, rel, [&](auto ic) {
        if (t) {
          if (ic.v == 3 || ic.v == 5) stage_done(sb, wg, ic.v >> 2, lane);
          if (ic.v < 5) { swiglu(2 * ic.v - 2, 32, ~t & 1); swiglu(2 * ic.v - 1, 32, 0); }
        }
      }, [&](int it) {
#pragma unroll
        for (int i = 0; i < 8; i++)
          if (t == 0 && it == 8 + i) gs->x1[bid * 2048 + (i >> 2) * 1024 + warp * 128 + (i & 3) * 32 + lane] = make_uint4(pk[4 * i], pk[4 * i + 1], pk[4 * i + 2], pk[4 * i + 3]);
      }, [&] { if (t == 0) fence_async_global(); else if (t == 2) mbar_wait(bar + B_X, 1); });
#pragma unroll
      for (int i = 0; i < 64; i++) pk[i] = pack2(acc[2 * i], acc[2 * i + 1]);
    }
    uint32_t x1[32];
    {
      float acc[64];
      mainloop<128, 6, 12, 0>(acc, 16, false, r6, sb, wg, lane, rel, [&](auto ic) {
        constexpr int b = ic.v > 6, q = ic.v - 6 * b;
        if (q == 1) {
#pragma unroll
          for (int i = 4 * b; i < 4 * b + 4; i++) { const uint4 x = lds128(sb + STG + b * BLK + warp * 2048 + (i & 3) * 512 + lane * 16); x1[4 * i] = x.x; x1[4 * i + 1] = x.y; x1[4 * i + 2] = x.z; x1[4 * i + 3] = x.w; }
          __syncwarp();
        } else if (q < 6) swiglu(4 * b + q - 2, 32, -1);
        else stage_done(sb, wg, b, lane);
      }, none, [] {});
#pragma unroll
      for (int i = 0; i < 32; i++) pk[i] = pack2(acc[2 * i], acc[2 * i + 1]);
    }
    {
      float acc[64];
      mainloop<128, 6, 5, TAILLAG>(acc, 56, false, r6, sb, wg, lane, rel, [&](auto ic) {
        if (ic.v == 5) stage_done(sb, wg, 0, lane); else swiglu(ic.v - 1, 16, 1);
      }, none, [&] {
        if (TAILLAG && wg == 0 && lane == 0) mbar_arrive(bar + B_LAG);
        load_vec(pk + 32, sb, 5, 0, lane); load_vec(pk + 40, sb, 5, 1, lane);
        mbar_wait(fre, 0); mbar_wait(fre + 8, 1);
      });
      __syncwarp();
      cl_arrive_relaxed();
#pragma unroll
      for (int i = 0; i < 16; i += 2) {
        uint32_t w[4];
#pragma unroll
        for (int u = 0; u < 4; u++) {
          const int q = 2 * i + u;
          w[u] = pack2(fmaf(acc[2 * q], bf_lo(pk[32 + (q >> 1)]), bf_lo(x1[q])), fmaf(acc[2 * q + 1], bf_hi(pk[32 + (q >> 1)]), bf_hi(x1[q])));
        }
        stsm4(stg_row + (i >> 3) * BLK + ((((i & 7) + (lane >> 4)) ^ (lane & 7)) << 4), w[0], w[1], w[2], w[3]);
        if ((i & 7) == 6) {
          fence_async_smem();
          named_bar(2 + wg, 128);
          if (wq == 0 && elect()) { tma_store_3d(&maps.out, sb + STG + (i >> 3) * BLK + wg * HALF, j * 128 + (i >> 3) * 64, m * 64, wg); bulk_commit(); }
          if (i < 8) x1[16] |= __float_as_uint(lds32f(bar + ZERO));
        }
      }
      if (wq == 0) bulk_wait_read();
      if (tid == 0) gs->epoch[bid + 4] = ep;
      cl_wait();
    }
  }
}

typedef CUresult (*EncodeFn)(CUtensorMap*, CUtensorMapDataType, cuuint32_t, void*, const cuuint64_t*, const cuuint64_t*, const cuuint32_t*, const cuuint32_t*,
                             CUtensorMapInterleave, CUtensorMapSwizzle, CUtensorMapL2promotion, CUtensorMapFloatOOBfill);

void make_map(EncodeFn fn, CUtensorMap* mp, const void* base, uint64_t d0, uint64_t d1, uint64_t d2, uint64_t s1, uint64_t s2, uint32_t b2, uint32_t b0 = 64) {
  cuuint64_t d[3] = {d0, d1, d2}, s[2] = {s1, s2};
  cuuint32_t b[3] = {b0, 64, b2}, e[3] = {1, 1, 1};
  fn(mp, CU_TENSOR_MAP_DATA_TYPE_BFLOAT16, 3, (void*)base, d, s, b, e, CU_TENSOR_MAP_INTERLEAVE_NONE, b0 == 64 ? CU_TENSOR_MAP_SWIZZLE_128B : CU_TENSOR_MAP_SWIZZLE_NONE,
     CU_TENSOR_MAP_L2_PROMOTION_L2_128B, CU_TENSOR_MAP_FLOAT_OOB_FILL_NONE);
}

__global__ void probe_kernel() {}
int max_clusters(int size) {
  cudaLaunchConfig_t cfg = {};
  cudaLaunchAttribute at;
  at.id = cudaLaunchAttributeClusterDimension; at.val.clusterDim.x = size; at.val.clusterDim.y = 1; at.val.clusterDim.z = 1;
  cfg.gridDim = dim3(size * 66); cfg.blockDim = dim3(384); cfg.dynamicSmemBytes = SMEM_BYTES; cfg.attrs = &at; cfg.numAttrs = 1;
  int n = 0;
  if (cudaOccupancyMaxActiveClusters(&n, probe_kernel, &cfg) != cudaSuccess) { cudaGetLastError(); return 0; }
  return n;
}

}

extern "C" void kernel_launch(void* const* d_in, const int* in_sizes, int n_in, void* d_out, int out_size) {
  static EncodeFn fn = nullptr;
  static int by_sm = 0;
  static Scratch* gs = nullptr;
  if (!fn) {
    void* p = nullptr; cudaDriverEntryPointQueryResult q;
    cudaGetDriverEntryPoint("cuTensorMapEncodeTiled", &p, cudaEnableDefault, &q);
    fn = (EncodeFn)p;
    cudaFuncSetAttribute(fused_kernel, cudaFuncAttributeMaxDynamicSharedMemorySize, SMEM_BYTES);
    int dev = 0, sms = 0;
    cudaGetSymbolAddress((void**)&gs, g_scratch);
    cudaGetDevice(&dev);
    cudaDeviceGetAttribute(&sms, cudaDevAttrMultiProcessorCount, dev);
    cudaFuncSetAttribute(probe_kernel, cudaFuncAttributeMaxDynamicSharedMemorySize, SMEM_BYTES);
    by_sm = sms == 132 && max_clusters(2) == 66 && max_clusters(4) == 30 && max_clusters(6) == 17 && max_clusters(8) == 15;
  }
  Maps mp;
  make_map(fn, &mp.x, d_in[0], D_, S_ / 2, 2, 4096, 2048, 2);
  make_map(fn, &mp.out, d_out, D_, S_ / 2, 2, 4096, 2048, 1);
  make_map(fn, &mp.wqkv, d_in[1], 64, D_, 3 * D_ / 64, 3 * D_ * 2, 128, 2);
  make_map(fn, &mp.wo, d_in[2], 64, D_, D_ / 64, D_ * 2, 128, 2);
  make_map(fn, &mp.w1, d_in[4], 64, D_, F_ / 64, F_ * 2, 128, 2);
  make_map(fn, &mp.w3, d_in[5], 64, D_, F_ / 64, F_ * 2, 128, 2);
  make_map(fn, &mp.w1s, d_in[4], 64, D_, F_ / 64, F_ * 2, 128, 1);
  make_map(fn, &mp.w3s, d_in[5], 64, D_, F_ / 64, F_ * 2, 128, 1);
  make_map(fn, &mp.w2, d_in[6], 64, F_, D_ / 64, D_ * 2, 128, 2);
  make_map(fn, &mp.wmod, d_in[8], 256, D_, 24, 6 * D_ * 2, 512, 1, 256);
  fused_kernel<<<132, 384, SMEM_BYTES>>>((const bf16*)d_in[7], (const bf16*)d_in[8], gs, by_sm, mp);
}
```

```cpp
#include <cuda_runtime.h>
#include <cuda_bf16.h>
#include <cuda.h>
#include <stdint.h>

typedef __nv_bfloat16 bf16;

namespace {

constexpr int S_ = 2048, D_ = 1024, F_ = 3584;
constexpr int BLK = 16384;
constexpr int HALF = 8192;
constexpr int RING = 196608;
constexpr int STG = RING;
constexpr int MISC = RING + 2 * BLK;
constexpr int SMEM_BYTES = MISC + 3072;
constexpr int B_FULL4 = 0, B_EMPTY4 = 32, B_FULL6 = 64, B_EMPTY6 = 112, B_RDY = 160, B_FREE = 176, B_LAG = 192, B_X = 208, B_MOD = 224, B_HALO = 232, B_HH = 256, B_ALL = 272, B_HH2 = 288, ZERO = 296;
constexpr int MODV = 512;
constexpr int RED_OFF = 0;
constexpr float SCL = 0.17677669529663687f * 1.4426950408889634f;
constexpr int U_HH = 64;
constexpr int FS = 8;
constexpr int NPIECE = 4, PSLEEP = 300;
constexpr int XSLEEP = 4000, HSLEEP = 400;
constexpr uint32_t XDELAY = 2000;
constexpr uint32_t B1P = 3500, B1D = 900, B1P2 = 3200;
constexpr int WOLAG = 2, TAILLAG = 5;

struct Maps { CUtensorMap x, out, wqkv, wo, w1, w3, w1s, w3s, w2, wmod; };

struct Scratch {
  uint4 h[16 * 16 * 1024];
  uint4 o[16 * 16 * 1024];
  uint4 hh[16 * 56 * 1024];
  uint4 x1[128 * 8 * 256];
  uint2 stat[2 * 16 * 8 * 128];
  uint4 halo[16 * 8 * 2 * 512];
  uint32_t modp[8 * 2 * 4 * 128];
  uint2 modv[4 * 1024];
  uint32_t flag[16 * 128 * FS];
  uint32_t epoch[132];
};
__device__ __align__(1024) Scratch g_scratch;

__device__ __forceinline__ void bail() { asm volatile("st.global.u32 [%0], %1;" :: "l"(0ull), "r"(0) : "memory"); }
__device__ __forceinline__ uint32_t smem_u32(const void* p) { return (uint32_t)__cvta_generic_to_shared(p); }
__device__ __forceinline__ void mbar_init(uint32_t bar, uint32_t cnt) { asm volatile("mbarrier.init.shared::cta.b64 [%0], %1;" :: "r"(bar), "r"(cnt) : "memory"); }
__device__ __forceinline__ void mbar_expect_tx(uint32_t bar, uint32_t bytes) { asm volatile("mbarrier.arrive.expect_tx.shared::cta.b64 _, [%0], %1;" :: "r"(bar), "r"(bytes) : "memory"); }
__device__ __forceinline__ void mbar_arrive(uint32_t bar) { asm volatile("mbarrier.arrive.shared::cta.b64 _, [%0];" :: "r"(bar) : "memory"); }
__device__ __forceinline__ void mbar_arrive_cl(uint32_t cl_addr) { asm volatile("mbarrier.arrive.shared::cluster.b64 _, [%0];" :: "r"(cl_addr) : "memory"); }
__device__ __forceinline__ uint32_t mapa(uint32_t addr, uint32_t cta) { uint32_t r; asm("mapa.shared::cluster.u32 %0, %1, %2;" : "=r"(r) : "r"(addr), "r"(cta)); return r; }
__device__ __forceinline__ void mbar_wait(uint32_t bar, uint32_t parity) {
  asm volatile("{\n.reg .pred p;\n.reg .b32 n;\n.reg .b64 z;\nmov.b32 n, 0;\nmov.b64 z, 0;\n"
               "W: add.u32 n, n, 1;\nsetp.gt.u32 p, n, 0x400000;\n@p st.global.u32 [z], n;\n"
               "mbarrier.try_wait.parity.shared::cta.b64 p, [%0], %1;\n@!p bra W;\n}" :: "r"(bar), "r"(parity) : "memory");
}
__device__ __forceinline__ void tma_3d(uint32_t dst, const CUtensorMap* m, uint32_t bar, int c0, int c1, int c2) {
  asm volatile("cp.async.bulk.tensor.3d.shared::cluster.global.mbarrier::complete_tx::bytes [%0], [%1, {%3, %4, %5}], [%2];" :: "r"(dst), "l"(m), "r"(bar), "r"(c0), "r"(c1), "r"(c2) : "memory");
}
__device__ __forceinline__ void tma_store_3d(const CUtensorMap* m, uint32_t src, int c0, int c1, int c2) {
  asm volatile("cp.async.bulk.tensor.3d.global.shared::cta.bulk_group [%0, {%2, %3, %4}], [%1];" :: "l"(m), "r"(src), "r"(c0), "r"(c1), "r"(c2) : "memory");
}
__device__ __forceinline__ void bulk_ld(uint32_t dst, const void* src, uint32_t bytes, uint32_t bar) {
  asm volatile("cp.async.bulk.shared::cluster.global.mbarrier::complete_tx::bytes [%0], [%1], %2, [%3];" :: "r"(dst), "l"(src), "r"(bytes), "r"(bar) : "memory");
}
__device__ __forceinline__ void bulk_ld_mc(uint32_t dst, const void* src, uint32_t bytes, uint32_t bar) {
  asm volatile("cp.async.bulk.shared::cluster.global.mbarrier::complete_tx::bytes.multicast::cluster [%0], [%1], %2, [%3], %4;" :: "r"(dst), "l"(src), "r"(bytes), "r"(bar), "h"((uint16_t)3) : "memory");
}
__device__ __forceinline__ void bulk_push(uint32_t dst_cl, uint32_t src, uint32_t bytes, uint32_t bar_cl) {
  asm volatile("cp.async.bulk.shared::cluster.shared::cta.mbarrier::complete_tx::bytes [%0], [%1], %2, [%3];" :: "r"(dst_cl), "r"(src), "r"(bytes), "r"(bar_cl) : "memory");
}
__device__ __forceinline__ void bulk_st(void* dst, uint32_t src, uint32_t bytes) {
  asm volatile("cp.async.bulk.global.shared::cta.bulk_group [%0], [%1], %2;" :: "l"(dst), "r"(src), "r"(bytes) : "memory");
}
__device__ __forceinline__ void bulk_commit() { asm volatile("cp.async.bulk.commit_group;" ::: "memory"); }
__device__ __forceinline__ void bulk_wait_read() { asm volatile("cp.async.bulk.wait_group.read 0;" ::: "memory"); }
__device__ __forceinline__ void bulk_wait_all() { asm volatile("cp.async.bulk.wait_group 0;" ::: "memory"); }
__device__ __forceinline__ void fence_async_global() { asm volatile("fence.proxy.async.global;" ::: "memory"); }
__device__ __forceinline__ void fence_async_smem() { asm volatile("fence.proxy.async.shared::cta;" ::: "memory"); }
__device__ __forceinline__ void wg_arrive() { asm volatile("wgmma.fence.sync.aligned;" ::: "memory"); }
__device__ __forceinline__ void wg_commit() { asm volatile("wgmma.commit_group.sync.aligned;" ::: "memory"); }
template <int N> __device__ __forceinline__ void wg_wait() { asm volatile("wgmma.wait_group.sync.aligned %0;" :: "n"(N) : "memory"); }
__device__ __forceinline__ void cl_arrive_relaxed() { asm volatile("barrier.cluster.arrive.relaxed.aligned;" ::: "memory"); }
__device__ __forceinline__ void cl_wait() { asm volatile("barrier.cluster.wait.acquire.aligned;" ::: "memory"); }
__device__ __forceinline__ bool elect() { uint32_t p; asm volatile("{\n.reg .pred p;\nelect.sync _|p, 0xffffffff;\nselp.u32 %0, 1, 0, p;\n}" : "=r"(p)); return p; }
__device__ __forceinline__ void named_bar(int id, int n) { asm volatile("bar.sync %0, %1;" :: "r"(id), "r"(n) : "memory"); }
__device__ __forceinline__ uint32_t pack2(float lo, float hi) { uint32_t r; asm("cvt.rn.bf16x2.f32 %0, %1, %2;" : "=r"(r) : "f"(hi), "f"(lo)); return r; }
__device__ __forceinline__ float bf_lo(uint32_t w) { return __uint_as_float(w << 16); }
__device__ __forceinline__ float bf_hi(uint32_t w) { return __uint_as_float(w & 0xffff0000u); }
__device__ __forceinline__ float bf_round(float v) { return __bfloat162float(__float2bfloat16_rn(v)); }
__device__ __forceinline__ void stsm4(uint32_t addr, uint32_t a, uint32_t b, uint32_t c, uint32_t d) {
  asm volatile("stmatrix.sync.aligned.m8n8.x4.shared.b16 [%0], {%1, %2, %3, %4};" :: "r"(addr), "r"(a), "r"(b), "r"(c), "r"(d) : "memory");
}
__device__ __forceinline__ void ldsm4(uint32_t addr, uint32_t& a, uint32_t& b, uint32_t& c, uint32_t& d) {
  asm volatile("ldmatrix.sync.aligned.m8n8.x4.shared.b16 {%0, %1, %2, %3}, [%4];" : "=r"(a), "=r"(b), "=r"(c), "=r"(d) : "r"(addr) : "memory");
}
__device__ __forceinline__ uint32_t movm(uint32_t a) { uint32_t r; asm volatile("movmatrix.sync.aligned.m8n8.trans.b16 %0, %1;" : "=r"(r) : "r"(a)); return r; }
__device__ __forceinline__ void mma16(float (&d)[4], uint32_t a0, uint32_t a1, uint32_t a2, uint32_t a3, uint32_t b0, uint32_t b1) {
  asm("mma.sync.aligned.m16n8k16.row.col.f32.bf16.bf16.f32 {%0,%1,%2,%3}, {%4,%5,%6,%7}, {%8,%9}, {%0,%1,%2,%3};"
               : "+f"(d[0]), "+f"(d[1]), "+f"(d[2]), "+f"(d[3]) : "r"(a0), "r"(a1), "r"(a2), "r"(a3), "r"(b0), "r"(b1));
}
__device__ __forceinline__ void mma16z(float (&d)[4], uint32_t a0, uint32_t a1, uint32_t a2, uint32_t a3, uint32_t b0, uint32_t b1) {
  asm("mma.sync.aligned.m16n8k16.row.col.f32.bf16.bf16.f32 {%0,%1,%2,%3}, {%4,%5,%6,%7}, {%8,%9}, {%10,%10,%10,%10};"
      : "=f"(d[0]), "=f"(d[1]), "=f"(d[2]), "=f"(d[3]) : "r"(a0), "r"(a1), "r"(a2), "r"(a3), "r"(b0), "r"(b1), "f"(0.f));
}
__device__ __forceinline__ void mma8z(float (&d)[4], uint32_t a0, uint32_t a1, uint32_t b0) {
  asm("mma.sync.aligned.m16n8k8.row.col.f32.bf16.bf16.f32 {%0,%1,%2,%3}, {%4,%5}, {%6}, {%7,%7,%7,%7};"
      : "=f"(d[0]), "=f"(d[1]), "=f"(d[2]), "=f"(d[3]) : "r"(a0), "r"(a1), "r"(b0), "f"(0.f));
}
__device__ __forceinline__ void mma8(float (&d)[4], uint32_t a0, uint32_t a1, uint32_t b0) {
  asm("mma.sync.aligned.m16n8k8.row.col.f32.bf16.bf16.f32 {%0,%1,%2,%3}, {%4,%5}, {%6}, {%0,%1,%2,%3};"
               : "+f"(d[0]), "+f"(d[1]), "+f"(d[2]), "+f"(d[3]) : "r"(a0), "r"(a1), "r"(b0));
}
__device__ __forceinline__ uint4 lds128(uint32_t a) { uint4 v; asm volatile("ld.shared.v4.u32 {%0,%1,%2,%3}, [%4];" : "=r"(v.x), "=r"(v.y), "=r"(v.z), "=r"(v.w) : "r"(a) : "memory"); return v; }
__device__ __forceinline__ void sts128(uint32_t a, uint32_t x, uint32_t y, uint32_t z, uint32_t w) { asm volatile("st.shared.v4.u32 [%0], {%1,%2,%3,%4};" :: "r"(a), "r"(x), "r"(y), "r"(z), "r"(w) : "memory"); }
__device__ __forceinline__ float lds32f(uint32_t a) { float v; asm volatile("ld.shared.f32 %0, [%1];" : "=f"(v) : "r"(a) : "memory"); return v; }
__device__ __forceinline__ void sts16(uint32_t a, bf16 v) { asm volatile("st.shared.b16 [%0], %1;" :: "r"(a), "h"(__bfloat16_as_ushort(v)) : "memory"); }
__device__ __forceinline__ uint4 ldg_nc(const void* p) { uint4 v; asm volatile("ld.global.nc.L1::no_allocate.v4.u32 {%0,%1,%2,%3}, [%4];" : "=r"(v.x), "=r"(v.y), "=r"(v.z), "=r"(v.w) : "l"(p)); return v; }
__device__ __forceinline__ uint4 ld_rlx4(const uint4* p) {
  unsigned long long a, b; asm volatile("ld.relaxed.gpu.global.v2.b64 {%0,%1}, [%2];" : "=l"(a), "=l"(b) : "l"(p) : "memory");
  return make_uint4((uint32_t)a, (uint32_t)(a >> 32), (uint32_t)b, (uint32_t)(b >> 32));
}
__device__ __forceinline__ uint2 ld_rlx2(const uint2* p) { unsigned long long a; asm volatile("ld.relaxed.gpu.global.b64 %0, [%1];" : "=l"(a) : "l"(p) : "memory"); return make_uint2((uint32_t)a, (uint32_t)(a >> 32)); }
__device__ __forceinline__ void st_rlx4(uint4* p, uint32_t x, uint32_t y, uint32_t z, uint32_t w) {
  asm volatile("st.relaxed.gpu.global.v2.b64 [%0], {%1,%2};" :: "l"(p), "l"((unsigned long long)x | ((unsigned long long)y << 32)), "l"((unsigned long long)z | ((unsigned long long)w << 32)) : "memory");
}
__device__ __forceinline__ void st_rlx2(uint2* p, uint32_t x, uint32_t y) { asm volatile("st.relaxed.gpu.global.b64 [%0], %1;" :: "l"(p), "l"((unsigned long long)x | ((unsigned long long)y << 32)) : "memory"); }
__device__ __forceinline__ void st_rlx1(uint32_t* p, uint32_t v) { asm volatile("st.relaxed.gpu.global.u32 [%0], %1;" :: "l"(p), "r"(v) : "memory"); }
__device__ __forceinline__ uint32_t ld_rlx1(const uint32_t* p) { uint32_t v; asm volatile("ld.relaxed.gpu.global.u32 %0, [%1];" : "=r"(v) : "l"(p) : "memory"); return v; }
__device__ __forceinline__ void st_release(uint32_t* p, uint32_t v) { asm volatile("st.release.gpu.global.u32 [%0], %1;" :: "l"(p), "r"(v) : "memory"); }
__device__ __forceinline__ uint32_t ld_acquire(const uint32_t* p) { uint32_t v; asm volatile("ld.acquire.gpu.global.u32 %0, [%1];" : "=r"(v) : "l"(p) : "memory"); return v; }
__device__ __forceinline__ void prefetch_map(const CUtensorMap* m) { asm volatile("prefetch.tensormap [%0];" :: "l"(m) : "memory"); }
__device__ __forceinline__ float rcp(float x) { float r; asm("rcp.approx.ftz.f32 %0, %1;" : "=f"(r) : "f"(x)); return r; }
__device__ __forceinline__ float ex2(float x) { float r; asm("ex2.approx.ftz.f32 %0, %1;" : "=f"(r) : "f"(x)); return r; }
__device__ __forceinline__ float tanh_fast(float x) { float r; asm("tanh.approx.f32 %0, %1;" : "=f"(r) : "f"(x)); return r; }
#define SPIN_GUARD(n) if (++(n) > (1u << 24)) bail()

__device__ __forceinline__ void wgmma_n128(float (&d)[64], uint64_t da, uint64_t db) {
  asm volatile("wgmma.mma_async.sync.aligned.m64n128k16.f32.bf16.bf16 "
    "{%0, %1, %2, %3, %4, %5, %6, %7, %8, %9, %10, %11, %12, %13, %14, %15, %16, %17, %18, %19, %20, %21, %22, %23, %24, %25, %26, %27, %28, %29, %30, %31, %32, %33, %34, %35, %36, %37, %38, %39, %40, %41, %42, %43, %44, %45, %46, %47, %48, %49, %50, %51, %52, %53, %54, %55, %56, %57, %58, %59, %60, %61, %62, %63}, "
    "%64, %65, 1, 1, 1, 0, 1;\n"
    : "+f"(d[0]), "+f"(d[1]), "+f"(d[2]), "+f"(d[3]), "+f"(d[4]), "+f"(d[5]), "+f"(d[6]), "+f"(d[7]), "+f"(d[8]), "+f"(d[9]), "+f"(d[10]), "+f"(d[11]), "+f"(d[12]), "+f"(d[13]), "+f"(d[14]), "+f"(d[15]), "+f"(d[16]), "+f"(d[17]), "+f"(d[18]), "+f"(d[19]), "+f"(d[20]), "+f"(d[21]), "+f"(d[22]), "+f"(d[23]), "+f"(d[24]), "+f"(d[25]), "+f"(d[26]), "+f"(d[27]), "+f"(d[28]), "+f"(d[29]), "+f"(d[30]), "+f"(d[31]), "+f"(d[32]), "+f"(d[33]), "+f"(d[34]), "+f"(d[35]), "+f"(d[36]), "+f"(d[37]), "+f"(d[38]), "+f"(d[39]), "+f"(d[40]), "+f"(d[41]), "+f"(d[42]), "+f"(d[43]), "+f"(d[44]), "+f"(d[45]), "+f"(d[46]), "+f"(d[47]), "+f"(d[48]), "+f"(d[49]), "+f"(d[50]), "+f"(d[51]), "+f"(d[52]), "+f"(d[53]), "+f"(d[54]), "+f"(d[55]), "+f"(d[56]), "+f"(d[57]), "+f"(d[58]), "+f"(d[59]), "+f"(d[60]), "+f"(d[61]), "+f"(d[62]), "+f"(d[63])
    : "l"(da), "l"(db));
}
__device__ __forceinline__ void wgmma_n128_first(float (&d)[64], uint64_t da, uint64_t db) {
  asm volatile("wgmma.mma_async.sync.aligned.m64n128k16.f32.bf16.bf16 "
    "{%0, %1, %2, %3, %4, %5, %6, %7, %8, %9, %10, %11, %12, %13, %14, %15, %16, %17, %18, %19, %20, %21, %22, %23, %24, %25, %26, %27, %28, %29, %30, %31, %32, %33, %34, %35, %36, %37, %38, %39, %40, %41, %42, %43, %44, %45, %46, %47, %48, %49, %50, %51, %52, %53, %54, %55, %56, %57, %58, %59, %60, %61, %62, %63}, "
    "%64, %65, 0, 1, 1, 0, 1;\n"
    : "=f"(d[0]), "=f"(d[1]), "=f"(d[2]), "=f"(d[3]), "=f"(d[4]), "=f"(d[5]), "=f"(d[6]), "=f"(d[7]), "=f"(d[8]), "=f"(d[9]), "=f"(d[10]), "=f"(d[11]), "=f"(d[12]), "=f"(d[13]), "=f"(d[14]), "=f"(d[15]), "=f"(d[16]), "=f"(d[17]), "=f"(d[18]), "=f"(d[19]), "=f"(d[20]), "=f"(d[21]), "=f"(d[22]), "=f"(d[23]), "=f"(d[24]), "=f"(d[25]), "=f"(d[26]), "=f"(d[27]), "=f"(d[28]), "=f"(d[29]), "=f"(d[30]), "=f"(d[31]), "=f"(d[32]), "=f"(d[33]), "=f"(d[34]), "=f"(d[35]), "=f"(d[36]), "=f"(d[37]), "=f"(d[38]), "=f"(d[39]), "=f"(d[40]), "=f"(d[41]), "=f"(d[42]), "=f"(d[43]), "=f"(d[44]), "=f"(d[45]), "=f"(d[46]), "=f"(d[47]), "=f"(d[48]), "=f"(d[49]), "=f"(d[50]), "=f"(d[51]), "=f"(d[52]), "=f"(d[53]), "=f"(d[54]), "=f"(d[55]), "=f"(d[56]), "=f"(d[57]), "=f"(d[58]), "=f"(d[59]), "=f"(d[60]), "=f"(d[61]), "=f"(d[62]), "=f"(d[63])
    : "l"(da), "l"(db));
}
__device__ __forceinline__ void wgmma_n256(float (&d)[128], uint64_t da, uint64_t db) {
  asm volatile("wgmma.mma_async.sync.aligned.m64n256k16.f32.bf16.bf16 "
    "{%0, %1, %2, %3, %4, %5, %6, %7, %8, %9, %10, %11, %12, %13, %14, %15, %16, %17, %18, %19, %20, %21, %22, %23, %24, %25, %26, %27, %28, %29, %30, %31, %32, %33, %34, %35, %36, %37, %38, %39, %40, %41, %42, %43, %44, %45, %46, %47, %48, %49, %50, %51, %52, %53, %54, %55, %56, %57, %58, %59, %60, %61, %62, %63, %64, %65, %66, %67, %68, %69, %70, %71, %72, %73, %74, %75, %76, %77, %78, %79, %80, %81, %82, %83, %84, %85, %86, %87, %88, %89, %90, %91, %92, %93, %94, %95, %96, %97, %98, %99, %100, %101, %102, %103, %104, %105, %106, %107, %108, %109, %110, %111, %112, %113, %114, %115, %116, %117, %118, %119, %120, %121, %122, %123, %124, %125, %126, %127}, "
    "%128, %129, 1, 1, 1, 0, 1;\n"
    : "+f"(d[0]), "+f"(d[1]), "+f"(d[2]), "+f"(d[3]), "+f"(d[4]), "+f"(d[5]), "+f"(d[6]), "+f"(d[7]), "+f"(d[8]), "+f"(d[9]), "+f"(d[10]), "+f"(d[11]), "+f"(d[12]), "+f"(d[13]), "+f"(d[14]), "+f"(d[15]), "+f"(d[16]), "+f"(d[17]), "+f"(d[18]), "+f"(d[19]), "+f"(d[20]), "+f"(d[21]), "+f"(d[22]), "+f"(d[23]), "+f"(d[24]), "+f"(d[25]), "+f"(d[26]), "+f"(d[27]), "+f"(d[28]), "+f"(d[29]), "+f"(d[30]), "+f"(d[31]), "+f"(d[32]), "+f"(d[33]), "+f"(d[34]), "+f"(d[35]), "+f"(d[36]), "+f"(d[37]), "+f"(d[38]), "+f"(d[39]), "+f"(d[40]), "+f"(d[41]), "+f"(d[42]), "+f"(d[43]), "+f"(d[44]), "+f"(d[45]), "+f"(d[46]), "+f"(d[47]), "+f"(d[48]), "+f"(d[49]), "+f"(d[50]), "+f"(d[51]), "+f"(d[52]), "+f"(d[53]), "+f"(d[54]), "+f"(d[55]), "+f"(d[56]), "+f"(d[57]), "+f"(d[58]), "+f"(d[59]), "+f"(d[60]), "+f"(d[61]), "+f"(d[62]), "+f"(d[63]), "+f"(d[64]), "+f"(d[65]), "+f"(d[66]), "+f"(d[67]), "+f"(d[68]), "+f"(d[69]), "+f"(d[70]), "+f"(d[71]), "+f"(d[72]), "+f"(d[73]), "+f"(d[74]), "+f"(d[75]), "+f"(d[76]), "+f"(d[77]), "+f"(d[78]), "+f"(d[79]), "+f"(d[80]), "+f"(d[81]), "+f"(d[82]), "+f"(d[83]), "+f"(d[84]), "+f"(d[85]), "+f"(d[86]), "+f"(d[87]), "+f"(d[88]), "+f"(d[89]), "+f"(d[90]), "+f"(d[91]), "+f"(d[92]), "+f"(d[93]), "+f"(d[94]), "+f"(d[95]), "+f"(d[96]), "+f"(d[97]), "+f"(d[98]), "+f"(d[99]), "+f"(d[100]), "+f"(d[101]), "+f"(d[102]), "+f"(d[103]), "+f"(d[104]), "+f"(d[105]), "+f"(d[106]), "+f"(d[107]), "+f"(d[108]), "+f"(d[109]), "+f"(d[110]), "+f"(d[111]), "+f"(d[112]), "+f"(d[113]), "+f"(d[114]), "+f"(d[115]), "+f"(d[116]), "+f"(d[117]), "+f"(d[118]), "+f"(d[119]), "+f"(d[120]), "+f"(d[121]), "+f"(d[122]), "+f"(d[123]), "+f"(d[124]), "+f"(d[125]), "+f"(d[126]), "+f"(d[127])
    : "l"(da), "l"(db));
}
__device__ __forceinline__ void wgmma_n256_first(float (&d)[128], uint64_t da, uint64_t db) {
  asm volatile("wgmma.mma_async.sync.aligned.m64n256k16.f32.bf16.bf16 "
    "{%0, %1, %2, %3, %4, %5, %6, %7, %8, %9, %10, %11, %12, %13, %14, %15, %16, %17, %18, %19, %20, %21, %22, %23, %24, %25, %26, %27, %28, %29, %30, %31, %32, %33, %34, %35, %36, %37, %38, %39, %40, %41, %42, %43, %44, %45, %46, %47, %48, %49, %50, %51, %52, %53, %54, %55, %56, %57, %58, %59, %60, %61, %62, %63, %64, %65, %66, %67, %68, %69, %70, %71, %72, %73, %74, %75, %76, %77, %78, %79, %80, %81, %82, %83, %84, %85, %86, %87, %88, %89, %90, %91, %92, %93, %94, %95, %96, %97, %98, %99, %100, %101, %102, %103, %104, %105, %106, %107, %108, %109, %110, %111, %112, %113, %114, %115, %116, %117, %118, %119, %120, %121, %122, %123, %124, %125, %126, %127}, "
    "%128, %129, 0, 1, 1, 0, 1;\n"
    : "=f"(d[0]), "=f"(d[1]), "=f"(d[2]), "=f"(d[3]), "=f"(d[4]), "=f"(d[5]), "=f"(d[6]), "=f"(d[7]), "=f"(d[8]), "=f"(d[9]), "=f"(d[10]), "=f"(d[11]), "=f"(d[12]), "=f"(d[13]), "=f"(d[14]), "=f"(d[15]), "=f"(d[16]), "=f"(d[17]), "=f"(d[18]), "=f"(d[19]), "=f"(d[20]), "=f"(d[21]), "=f"(d[22]), "=f"(d[23]), "=f"(d[24]), "=f"(d[25]), "=f"(d[26]), "=f"(d[27]), "=f"(d[28]), "=f"(d[29]), "=f"(d[30]), "=f"(d[31]), "=f"(d[32]), "=f"(d[33]), "=f"(d[34]), "=f"(d[35]), "=f"(d[36]), "=f"(d[37]), "=f"(d[38]), "=f"(d[39]), "=f"(d[40]), "=f"(d[41]), "=f"(d[42]), "=f"(d[43]), "=f"(d[44]), "=f"(d[45]), "=f"(d[46]), "=f"(d[47]), "=f"(d[48]), "=f"(d[49]), "=f"(d[50]), "=f"(d[51]), "=f"(d[52]), "=f"(d[53]), "=f"(d[54]), "=f"(d[55]), "=f"(d[56]), "=f"(d[57]), "=f"(d[58]), "=f"(d[59]), "=f"(d[60]), "=f"(d[61]), "=f"(d[62]), "=f"(d[63]), "=f"(d[64]), "=f"(d[65]), "=f"(d[66]), "=f"(d[67]), "=f"(d[68]), "=f"(d[69]), "=f"(d[70]), "=f"(d[71]), "=f"(d[72]), "=f"(d[73]), "=f"(d[74]), "=f"(d[75]), "=f"(d[76]), "=f"(d[77]), "=f"(d[78]), "=f"(d[79]), "=f"(d[80]), "=f"(d[81]), "=f"(d[82]), "=f"(d[83]), "=f"(d[84]), "=f"(d[85]), "=f"(d[86]), "=f"(d[87]), "=f"(d[88]), "=f"(d[89]), "=f"(d[90]), "=f"(d[91]), "=f"(d[92]), "=f"(d[93]), "=f"(d[94]), "=f"(d[95]), "=f"(d[96]), "=f"(d[97]), "=f"(d[98]), "=f"(d[99]), "=f"(d[100]), "=f"(d[101]), "=f"(d[102]), "=f"(d[103]), "=f"(d[104]), "=f"(d[105]), "=f"(d[106]), "=f"(d[107]), "=f"(d[108]), "=f"(d[109]), "=f"(d[110]), "=f"(d[111]), "=f"(d[112]), "=f"(d[113]), "=f"(d[114]), "=f"(d[115]), "=f"(d[116]), "=f"(d[117]), "=f"(d[118]), "=f"(d[119]), "=f"(d[120]), "=f"(d[121]), "=f"(d[122]), "=f"(d[123]), "=f"(d[124]), "=f"(d[125]), "=f"(d[126]), "=f"(d[127])
    : "l"(da), "l"(db));
}

template <int N> struct WG;
#define DEF_WG(N) template <> struct WG<N> { \
  static __device__ __forceinline__ void mma(float (&d)[N / 2], uint64_t a, uint64_t b) { wgmma_n##N(d, a, b); } \
  static __device__ __forceinline__ void first(float (&d)[N / 2], uint64_t a, uint64_t b) { wgmma_n##N##_first(d, a, b); } };
DEF_WG(128) DEF_WG(256)

constexpr uint64_t DESC_A = (1ull << 62) | ((uint64_t)(1024 >> 4) << 32) | (1ull << 16);
constexpr uint64_t DESC_B = (1ull << 62) | ((uint64_t)(1024 >> 4) << 32) | ((uint64_t)(8192 >> 4) << 16);

struct Ring { int s; uint32_t ph; int wrap; };
template <int NS> __device__ __forceinline__ void ring_next(Ring& r) { r.s = (r.s + 1 == NS) ? 0 : r.s + 1; if (r.s == r.wrap) r.ph ^= 1; }

__device__ __forceinline__ int own_order(int it, int j) {
  return it < 2 ? 2 * j + it : it < 4 ? 2 * (j ^ 1) + it - 2 : ((j >> 1) * 4 + 2 * it - (it < 10 ? 4 : 15)) & 15;
}

template <int V> struct IC { static constexpr int v = V; };
template <int I, int E, class F> __device__ __forceinline__ void static_for(F&& f) { if constexpr (I < E) { f(IC<I>{}); static_for<I + 1, E>(f); } }

template <int N, int NS, int PRE, int LAG, class Pre, class Mid, class Last>
__device__ __forceinline__ void mainloop(float (&acc)[N / 2], int nkb, bool own, Ring& r, uint32_t sb, int wg, int lane, uint32_t rel_base, Pre pre, Mid mid, Last last) {
  constexpr int SLOT = RING / NS;
  const uint32_t full = sb + MISC + (NS == 4 ? B_FULL4 : B_FULL6);
  const uint32_t rel = rel_base + (NS == 4 ? B_EMPTY4 : B_EMPTY6);
  const uint32_t s0 = (sb & 0x3FFFF) >> 4, a0 = s0 + wg * (HALF >> 4);
  int ps;
  auto issue = [&](int it, bool first) {
    const uint64_t da = DESC_A | (a0 + ((own && it < 2) ? (STG + it * BLK) >> 4 : r.s * (SLOT >> 4))), db = DESC_B | (s0 + r.s * (SLOT >> 4) + (BLK >> 4));
    mbar_wait(full + r.s * 8, r.ph);
    wg_arrive();
    if (first) WG<N>::first(acc, da, db); else WG<N>::mma(acc, da, db);
#pragma unroll
    for (int k = 1; k < 4; k++) WG<N>::mma(acc, da + k * 2, db + k * 128);
    wg_commit();
  };
  auto retire = [&](int it) {
    wg_wait<1>();
    if (lane < 2) mbar_arrive_cl(rel + ps * 8);
    ps = r.s;
    ring_next<NS>(r);
  };
  issue(0, true);
  ps = r.s;
  ring_next<NS>(r);
  static_for<1, PRE + 1>([&](auto ic) { issue(ic.v, false); pre(ic); retire(ic.v); });
#pragma unroll 1
  for (int it = PRE + 1; it < nkb; it++) {
    if (LAG && it == nkb - LAG && wg == 1) mbar_wait(sb + MISC + B_LAG, WOLAG && !own);
    issue(it, false); mid(it); retire(it);
  }
  last();
  wg_wait<0>();
  if (lane < 2) mbar_arrive_cl(rel + ps * 8);
}

__device__ __forceinline__ uint32_t tag_of(uint32_t ep) { return (ep & 127u) + 1u; }
__device__ __forceinline__ void ln_publish(const float (&v)[64], uint2* st, int j, int row0, int lane, uint32_t ep) {
  float s0 = 0, s1 = 0, s2 = 0, s3 = 0, q0 = 0, q1 = 0, q2 = 0, q3 = 0;
#pragma unroll
  for (int i = 0; i < 16; i++) {
    s0 += v[4 * i]; s1 += v[4 * i + 1]; s2 += v[4 * i + 2]; s3 += v[4 * i + 3];
    q0 = fmaf(v[4 * i], v[4 * i], q0); q1 = fmaf(v[4 * i + 1], v[4 * i + 1], q1); q2 = fmaf(v[4 * i + 2], v[4 * i + 2], q2); q3 = fmaf(v[4 * i + 3], v[4 * i + 3], q3);
  }
  s0 += s1; s2 += s3; q0 += q1; q2 += q3;
  const bool odd = lane & 1;
  float s = (odd ? s2 : s0) + __shfl_xor_sync(~0u, odd ? s0 : s2, 1), q = (odd ? q2 : q0) + __shfl_xor_sync(~0u, odd ? q0 : q2, 1);
  s += __shfl_xor_sync(~0u, s, 2); q += __shfl_xor_sync(~0u, q, 2);
  if ((lane & 3) < 2) st_rlx2(st + j * 128 + row0 + (lane & 1) * 8, __float_as_uint(s), (__float_as_uint(fmaf(s * (-1.f / 128), s, q)) & ~255u) | tag_of(ep));
}
__device__ __forceinline__ void ln_gather(const uint2* st, int row0, int lane, uint32_t ep, float& n0, float& r0, float& n1, float& r1, bool rnd) {
  const uint2* p = st + (lane & 2) * 256 + row0 + (lane & 1) * 8;
  const uint32_t tag = tag_of(ep);
  uint2 a, b, c, d; uint32_t n = 0;
  while (true) {
    a = ld_rlx2(p); b = ld_rlx2(p + 128); c = ld_rlx2(p + 256); d = ld_rlx2(p + 384);
    if ((((a.y ^ tag) | (b.y ^ tag) | (c.y ^ tag) | (d.y ^ tag)) & 255u) == 0) break;
    SPIN_GUARD(n);
  }
  __syncwarp();
  const uint32_t fix = tag ^ 128u;
  float s = (__uint_as_float(a.x) + __uint_as_float(b.x)) + (__uint_as_float(c.x) + __uint_as_float(d.x));
  float q = (__uint_as_float(a.y ^ fix) + __uint_as_float(b.y ^ fix)) + (__uint_as_float(c.y ^ fix) + __uint_as_float(d.y ^ fix));
  q = fmaf(fmaf(__uint_as_float(a.x), __uint_as_float(a.x), __uint_as_float(b.x) * __uint_as_float(b.x)) +
           fmaf(__uint_as_float(c.x), __uint_as_float(c.x), __uint_as_float(d.x) * __uint_as_float(d.x)), 1.f / 128, q);
  s += __shfl_xor_sync(~0u, s, 2); q += __shfl_xor_sync(~0u, q, 2);
  s *= 1.f / 1024;
  const float var = fmaxf(fmaf(-s, s, q * (1.f / 1024)), 0.f);
  float r;
  if (rnd) {
    float sd; asm("sqrt.approx.f32 %0, %1;" : "=f"(sd) : "f"(bf_round(bf_round(var) + 1e-5f)));
    r = rcp(bf_round(sd)); s = bf_round(s);
  } else r = rsqrtf(var + 1e-5f);
  const float nn = -s * r;
  const float ro = __shfl_xor_sync(~0u, r, 1), no = __shfl_xor_sync(~0u, nn, 1);
  const bool odd = lane & 1;
  r0 = odd ? ro : r; n0 = odd ? no : nn; r1 = odd ? r : ro; n1 = odd ? nn : no;
}
__device__ __forceinline__ void load_vec(uint32_t* w, uint32_t sb, int sec, int b, int lane) {
#pragma unroll
  for (int q = 0; q < 2; q++) { uint4 t = lds128(sb + MISC + MODV + sec * 256 + (lane & 3) * 64 + b * 32 + q * 16); w[4 * q] = t.x; w[4 * q + 1] = t.y; w[4 * q + 2] = t.z; w[4 * q + 3] = t.w; }
}
__device__ __forceinline__ void stage_done(uint32_t sb, int wg, int b, int lane) {
  fence_async_smem();
  __syncwarp();
  if (lane == 0) mbar_arrive(sb + MISC + B_RDY + b * 8);
}
__device__ __forceinline__ uint32_t hfma2(uint32_t a, uint32_t b, uint32_t c) { uint32_t r; asm("fma.rn.bf16x2 %0, %1, %2, %3;" : "=r"(r) : "r"(a), "r"(b), "r"(c)); return r; }
__device__ __forceinline__ void ln_apply(const float (&v)[64], const uint2* st, int row0, uint32_t ep, uint32_t sb, int sec_shift, int sec_scale, uint32_t stg_row, int wg, int lane) {
  uint32_t sc[16], sh[16];
#pragma unroll
  for (int b = 0; b < 2; b++) { load_vec(sc + 8 * b, sb, sec_scale, b, lane); load_vec(sh + 8 * b, sb, sec_shift, b, lane); }
  float n0, r0, n1, r1;
  ln_gather(st, row0, lane, ep, n0, r0, n1, r1, sec_shift == 0);
#pragma unroll
  for (int i = 0; i < 16; i += 2) {
    if (i == 8) { const float z = lds32f(sb + MISC + ZERO); n0 += z; n1 += z; }
    uint32_t w[4];
#pragma unroll
    for (int u = 0; u < 2; u++) {
      int q = i + u;
      w[2 * u] = hfma2(pack2(fmaf(v[4 * q], r0, n0), fmaf(v[4 * q + 1], r0, n0)), sc[q], sh[q]);
      w[2 * u + 1] = hfma2(pack2(fmaf(v[4 * q + 2], r1, n1), fmaf(v[4 * q + 3], r1, n1)), sc[q], sh[q]);
    }
    stsm4(stg_row + (i >> 3) * BLK + ((((i & 7) + (lane >> 4)) ^ (lane & 7)) << 4), w[0], w[1], w[2], w[3]);
    if ((i & 7) == 6) { stage_done(sb, wg, i >> 3, lane); }
  }
}
__device__ __forceinline__ uint32_t hmul2(uint32_t a, uint32_t b) { uint32_t r; asm("mul.rn.bf16x2 %0, %1, %2;" : "=r"(r) : "r"(a), "r"(b)); return r; }
__device__ __forceinline__ uint32_t silu_mul2(uint32_t g, uint32_t u) {
  const uint32_t h = hmul2(g, 0x3f003f00u);
  const float h0 = bf_lo(h), h1 = bf_hi(h);
  return hmul2(pack2(fmaf(h0, tanh_fast(h0), h0), fmaf(h1, tanh_fast(h1), h1)), u);
}

__device__ __forceinline__ void gemv_fma(float (&a)[8], uint4 w, float s) {
  a[0] = fmaf(bf_lo(w.x), s, a[0]); a[1] = fmaf(bf_hi(w.x), s, a[1]); a[2] = fmaf(bf_lo(w.y), s, a[2]); a[3] = fmaf(bf_hi(w.y), s, a[3]);
  a[4] = fmaf(bf_lo(w.z), s, a[4]); a[5] = fmaf(bf_hi(w.z), s, a[5]); a[6] = fmaf(bf_lo(w.w), s, a[6]); a[7] = fmaf(bf_hi(w.w), s, a[7]);
}
__device__ __forceinline__ float silu_c(float v) { return bf_round(__fdividef(v, 1.f + __expf(-v))); }
__device__ __forceinline__ float mod_gather(const uint32_t* p, uint32_t ep) {
  const uint32_t tag = tag_of(ep), fix = tag ^ 128u;
  uint32_t a, b, c, d, n = 0;
  while (true) {
    a = ld_rlx1(p); b = ld_rlx1(p + 128); c = ld_rlx1(p + 256); d = ld_rlx1(p + 384);
    if ((((a ^ tag) | (b ^ tag) | (c ^ tag) | (d ^ tag)) & 255u) == 0) break;
    SPIN_GUARD(n);
  }
  return (__uint_as_float(a ^ fix) + __uint_as_float(b ^ fix)) + (__uint_as_float(c ^ fix) + __uint_as_float(d ^ fix));
}
__device__ __forceinline__ void mod_store(uint32_t sb, int sec, int col, float v) {
  v = bf_round(v);
  if (sec == 1) v += 1.f;
  sts16(sb + MISC + MODV + sec * 256 + (((col >> 1) & 3) * 16 + (col >> 3)) * 4 + (col & 1) * 2, __float2bfloat16_rn(v));
}

__global__ void __cluster_dims__(2, 1, 1) __launch_bounds__(384, 1)
fused_kernel(const bf16* __restrict__ cvec, const bf16* __restrict__ wmod, Scratch* gs, int by_sm, const __grid_constant__ Maps maps) {
  extern __shared__ __align__(1024) uint8_t smem_raw[];
  const uint32_t sb = smem_u32(smem_raw);
  const int warp = __shfl_sync(~0u, threadIdx.x >> 5, 0), lane = threadIdx.x & 31;
  const int rank = blockIdx.x & 1;
  uint32_t sm; asm volatile("mov.u32 %0, %%smid;" : "=r"(sm));
  const int t = sm >> 1, v = t < 32 ? t : t < 60 ? t + 1 + (((t - 32) * 37) >> 8) : (t - 58) * 8;
  const int cid = !by_sm ? (blockIdx.x >> 1) - 2 : (t & ~1) == 60 ? t - 62 : (v & 1) * 32 + ((v >> 1) & 31);
  const bool extra = cid < 0;
  const int bid = cid * 2 + rank;
  const int m = cid >> 2, j = (cid & 3) * 2 + rank;
  const uint32_t bar = sb + MISC;

  if (warp >= 8) {
    asm volatile("setmaxnreg.dec.sync.aligned.u32 40;");
    if (extra) {
      if (warp == 8) {
        if (lane == 0) { for (int s = 0; s < 6; s++) { mbar_init(bar + B_FULL6 + s * 8, 1); mbar_init(bar + B_EMPTY6 + s * 8, 8); } fence_async_smem(); }
        __syncwarp();
        asm volatile("bar.arrive 2, 288;" ::: "memory");
        __nanosleep(XSLEEP);
#pragma unroll 1
        for (int it = 0, s = 0, par = 1; it < 64; it++) {
          mbar_wait(bar + B_EMPTY6 + s * 8, par);
          if (elect()) { mbar_expect_tx(bar + B_FULL6 + s * 8, 32768); tma_3d(sb + s * 32768, &maps.wmod, bar + B_FULL6 + s * 8, 0, (it & 15) * 64, 12 + (it >> 4) * 4 + bid); }
          if (++s == 6) { s = 0; par ^= 1; }
        }
      }
    } else if (warp < 10) {
      uint32_t s6 = 0, p6 = 1;
      auto next6 = [&]() { if (++s6 == 6) { s6 = 0; p6 ^= 1; } };
      auto drained4 = [&](int q, int late) { if (q < 5) mbar_wait(bar + B_EMPTY4 + (((late ? 0x10332 : 0x32110) >> (4 * q)) & 3) * 8, 1); };
      auto drained6 = [&](int q) { if (q < 3) mbar_wait(bar + B_EMPTY6 + ((0x154 >> (4 * q)) & 7) * 8, q >> 1); };
      auto skip6 = [&]() { mbar_wait(bar + B_EMPTY6 + s6 * 8, p6); if (elect()) mbar_arrive(bar + B_FULL6 + s6 * 8); next6(); };
      if (warp == 8) {
        const uint32_t t_start = clock();
        if (lane == 0) {
          if (sb & 1023) bail();
          for (int b = 0; b < 2; b++) mbar_init(bar + B_X + b * 8, 1);
          for (int s = 0; s < 4; s++) { mbar_init(bar + B_FULL4 + s * 8, 2); mbar_init(bar + B_EMPTY4 + s * 8, 16); }
          for (int s = 0; s < 6; s++) { mbar_init(bar + B_FULL6 + s * 8, 2); mbar_init(bar + B_EMPTY6 + s * 8, 16); }
          for (int b = 0; b < 2; b++) { mbar_init(bar + B_RDY + b * 8, 8); mbar_init(bar + B_FREE + b * 8, 1); mbar_init(bar + B_HH + b * 8, 1); }
          mbar_init(bar + B_MOD, 1); mbar_init(bar + B_LAG, 4); mbar_init(bar + B_HALO, 2); mbar_init(bar + B_ALL, 1); mbar_init(bar + B_HH2, 1);
          asm volatile("st.shared.u32 [%0], 0;" :: "r"(bar + ZERO) : "memory");
          asm volatile("fence.mbarrier_init.release.cluster;" ::: "memory");
          fence_async_smem();
        }
        __syncwarp();
        cl_arrive_relaxed();
        auto wide = [&](int s, int par, const CUtensorMap* m0, int a0, const CUtensorMap* m1, int a1, int kb, bool spaced) {
          const uint32_t full = bar + B_FULL4 + s * 8, d = sb + s * 49152 + BLK;
          mbar_wait(full + 32, par);
          const uint32_t t0 = clock();
          if (elect()) { mbar_expect_tx(full, 2 * BLK); tma_3d(d, m0, full, 0, kb * 64, a0); }
          if (spaced) while ((uint32_t)clock() - t0 < 300) {}
          if (elect()) tma_3d(d + BLK, m1, full, 0, kb * 64, a1);
          if (spaced) while ((uint32_t)clock() - t0 < 600) {}
        };
        while ((uint32_t)clock() - t_start < XDELAY) {}
        if (elect()) for (int b = 0; b < 2; b++) { mbar_expect_tx(bar + B_X + b * 8, BLK); tma_3d(sb + STG + b * BLK, &maps.x, bar + B_X + b * 8, j * 128 + b * 64, m * 64, 0); }
        mbar_wait(bar + B_X + 8, 0);
#pragma unroll 1
        for (int ph = 0; ph < 2; ph++) {
          const CUtensorMap* const m0 = ph ? &maps.w1 : &maps.wqkv;
#pragma unroll 1
          for (int it = 0; it < (ph ? 48 : 16); it++) {
            const int a = (ph ? it & 48 : 16) + 2 * j;
            if (ph) drained6(it);
            wide((it + 2 * ph) & 3, ~(it >> 2) & 1, m0, a, m0 + ph, ph ? a : a + 16, it < 16 ? own_order(it, j) : it & 15, it < 4);
            if (it >= 44) {
              if (it == 44) { mbar_wait(bar + B_FREE, 0); mbar_wait(bar + B_FREE + 8, 0); if (elect()) mbar_expect_tx(bar + B_X, 2 * BLK); }
              if (elect()) bulk_ld(sb + STG + (it - 44) * HALF, gs->x1 + bid * 2048 + (it - 44) * 512, HALF, bar + B_X);
            }
          }
#pragma unroll 1
          for (int it = 0; it < 16; it++) {
            const uint32_t full = bar + B_FULL6 + s6 * 8, d = sb + s6 * 32768 + BLK;
            drained4(it, ph);
            mbar_wait(full + 48, p6);
            if (elect()) {
              mbar_expect_tx(full, BLK);
              tma_3d(d, ph ? &maps.w1s : &maps.wqkv, full, 0, it * 64, ph ? 48 + j : 2 * j);
              if (ph) tma_3d(d + HALF, &maps.w3s, full, 0, it * 64, 48 + j);
            }
            next6();
          }
          const CUtensorMap* const m2 = ph ? &maps.w2 : &maps.wo;
#pragma unroll 1
          for (int it = 0; it < (ph ? 56 : 16); it++) {
            const uint32_t full = bar + B_FULL6 + s6 * 8;
            const int kb = ph ? it : own_order(it, j);
            mbar_wait(full + 48, p6);
            if (elect()) { mbar_expect_tx(full, BLK); tma_3d(sb + s6 * 32768 + BLK, m2, full, 0, kb * 64, 2 * j); }
            next6();
          }
          if (!ph) skip6();
        }
      } else {
        if (lane < 9) prefetch_map(&maps.x + lane);
        const uint32_t ep = gs->epoch[bid + 4] + 1;
        cl_arrive_relaxed(); cl_wait();
        auto plain = [&](uint32_t full, uint32_t empty, int par, uint32_t slot, const uint4* blk) {
          mbar_wait(empty, par);
          if (elect()) { mbar_expect_tx(full, BLK); bulk_ld_mc(slot + rank * HALF, blk + rank * 512, HALF, full); }
        };
        auto plain6 = [&](const uint4* blk) { plain(bar + B_FULL6 + s6 * 8, bar + B_EMPTY6 + s6 * 8, p6, sb + s6 * 32768, blk); next6(); };
        uint32_t ready = 0;
        auto poll = [&](int e) { ready = __ballot_sync(~0u, ld_acquire(gs->flag + (m * 128 + e * 16 + (lane & 14)) * FS) == ep); };
        auto need = [&](int e, uint32_t mask) {
          if ((ready & mask) != mask) {
            uint32_t n = 0;
            do { poll(e); SPIN_GUARD(n); } while ((ready & mask) != mask);
            fence_async_global();
          }
        };
        auto fresh = [&](int e, int it, uint32_t full, uint32_t empty, int par, uint32_t slot, uint4* src) {
          if (it >= 4) {
            const int kb = own_order(it, j);
            if (it < 10) need(e, 1u << kb); else if (it == 10) mbar_wait(bar + B_ALL, e & 1);
            plain(full, empty, par, slot, src + kb * 1024);
          } else {
            if (it == 0) ready = 0;
            mbar_wait(empty, par);
            if (it < 2) { if (elect()) mbar_arrive(full); }
            else {
              const int b = it > 2;
              const uint32_t to_peer = mapa(sb, rank ^ 1) - sb;
              if (elect()) mbar_expect_tx(full, BLK);
              const bool push = e != 1;
              mbar_wait(bar + (b ? (push ? B_RDY + 8 : B_FREE + 8) : B_RDY), e & 1);
              if (elect()) {
                if (b == 0) {
                  bulk_st(src + 2 * j * 1024, sb + STG, BLK);
                  bulk_commit();
                  bulk_wait_all();
                  mbar_arrive(bar + B_FREE);
                }
                if (b && push) bulk_push(slot + to_peer, sb + STG + BLK, BLK, full + to_peer);
                else {
                  fence_async_global();
                  bulk_ld(slot + to_peer, src + (2 * j + b) * 1024, BLK, full + to_peer);
                }
              }
              __syncwarp();
            }
          }
        };
        uint4* const h = gs->h + m * 16384;
#pragma unroll 1
        for (int e = 0; e < 3; e++) {
#pragma unroll 1
          for (int it = 0; it < 16; it++) {
            const int s = e == 1 ? s6 : (it + e) & 3;
            const uint32_t full = bar + (e == 1 ? B_FULL6 : B_FULL4) + s * 8;
            if (e == 2) drained6(it);
            fresh(e, it, full, full + (e == 1 ? 48 : 32), e == 1 ? p6 : ~(it >> 2) & 1, sb + s * (e == 1 ? 32768 : 49152), e == 1 ? gs->o + m * 16384 : h);
            if (e == 1) next6();
          }
          if (e == 1) { skip6(); continue; }
#pragma unroll 1
          for (int it = 16; it < 16 + 16 * e; it++) {
            const int s = (it + 2) & 3;
            const uint32_t full = bar + B_FULL4 + s * 8;
            plain(full, full + 32, ~(it >> 2) & 1, sb + s * 49152, h + (it & 15) * 1024);
          }
#pragma unroll 1
          for (int it = 0; it < 16; it++) { drained4(it, e); plain6(h + it * 1024); }
        }
#pragma unroll 1
        for (int it = 0; it < 56; it++) {
          if (it == 0 || it == 32 || it == 48) mbar_wait(bar + (it == 48 ? B_HH2 : B_HH + (it >> 2)), 0);
          plain6(gs->hh + m * 57344 + it * 1024);
        }
      }
    } else {
      const int b = warp - 10;
      const uint32_t ep = gs->epoch[bid + 4] + 1;
      const uint32_t stg = sb + STG + b * BLK;
      cl_arrive_relaxed(); cl_wait();
      auto all_there = [&](int u, uint32_t done) {
        const uint32_t* fl = gs->flag + u * FS;
        uint32_t n = 0;
        while (!__all_sync(~0u, ld_acquire(fl) == ep)) { __nanosleep(100); SPIN_GUARD(n); }
        fence_async_global();
        if (lane == 0) mbar_arrive(done);
      };
      auto fetch_mod = [&](int sec) {
        const uint4* p = (const uint4*)(gs->modv + (sec - 2) * 1024 + j * 128) + lane;
        uint4 v0, v1; uint32_t n = 0;
        while (true) {
          v0 = ld_rlx4(p); v1 = ld_rlx4(p + 32);
          if (v0.y == ep && v0.w == ep && v1.y == ep && v1.w == ep) break;
          SPIN_GUARD(n);
        }
        const uint32_t d = sb + MISC + MODV + sec * 256 + ((lane & 3) * 16 + (lane >> 2)) * 4;
        asm volatile("st.shared.u32 [%0], %1;" :: "r"(d), "r"(__byte_perm(v0.x, v0.z, 0x7632)) : "memory");
        asm volatile("st.shared.u32 [%0], %1;" :: "r"(d + 32), "r"(__byte_perm(v1.x, v1.z, 0x7632)) : "memory");
        __syncwarp();
      };
#pragma unroll 1
      for (int e = 0; e < 7 - b; e++) {
        if (lane == 0) {
          if (e < 3) {
            mbar_wait(bar + B_FREE, e & 1);
            if (b) {
              const uint32_t t0 = clock();
              while ((uint32_t)clock() - t0 < (e == 0 ? B1P : e == 2 ? B1P2 : B1D)) {}
              mbar_wait(bar + B_RDY + 8, e & 1);
              bulk_st((e == 1 ? gs->o : gs->h) + m * 16384 + (2 * j + 1) * 1024, stg, BLK);
              bulk_commit();
              bulk_wait_all();
              mbar_arrive(bar + B_FREE + 8);
            }
            st_release(gs->flag + (m * 128 + e * 16 + 2 * j + b) * FS, ep);
          } else {
            const int kb = (e < 6 ? 2 * (8 * (e - 3) + j) : 48 + j) + b;
            mbar_wait(bar + B_RDY + b * 8, e & 1);
#pragma unroll 1
            for (int q = 0; q < NPIECE; q++) { if (q) __nanosleep(PSLEEP); bulk_st(gs->hh + m * 57344 + kb * 1024 + q * (1024 / NPIECE), stg + q * (BLK / NPIECE), BLK / NPIECE); }
            bulk_commit();
            bulk_wait_all();
            mbar_arrive(bar + B_FREE + b * 8);
            st_release(gs->flag + (m * 128 + U_HH + kb) * FS, ep);
          }
        }
        __syncwarp();
        if (e < 3 && b) all_there(m * 128 + e * 16 + (lane & 15), bar + B_ALL);
        if (e == 4 && b) all_there(m * 128 + U_HH + lane, bar + B_HH);
        if (!b && (e == 1 || e == 2)) {
#pragma unroll 1
          for (int sec = e == 1 ? 2 : 5; sec < 4 + e; sec++) fetch_mod(sec);
          if (e == 1) { if (lane == 0) mbar_arrive(bar + B_MOD); }
        }
        if (e == 0) {
          mbar_wait(bar + B_EMPTY6 + 24, 0);
          __nanosleep(HSLEEP);
#pragma unroll 1
          for (int w = 0; w < 4; w++) {
            const uint4* hp = gs->halo + ((m * 8 + j) * 2 + (w & 1)) * 512 + b * 256 + (w >> 1) * 128 + lane;
            uint4 q[4] = {}; uint32_t n = 0;
            while (m > 0) {
              bool ok = true;
#pragma unroll
              for (int i = 0; i < 4; i++) q[i] = ld_rlx4(hp + i * 32);
#pragma unroll
              for (int i = 0; i < 4; i++) ok = ok && q[i].y == ep && q[i].w == ep;
              if (ok) break;
              SPIN_GUARD(n);
            }
#pragma unroll
            for (int i = 0; i < 2; i++) sts128(stg + lane * 16 + (w & 1) * HALF + (w >> 1) * 1024 + i * 512, q[2 * i].x, q[2 * i + 1].x, q[2 * i].z, q[2 * i + 1].z);
          }
          __syncwarp();
          if (lane == 0) mbar_arrive(bar + B_HALO);
        }
      }
      if (b) { all_there(m * 128 + U_HH + 32 + (lane & 15), bar + B_HH + 8); all_there(m * 128 + U_HH + 48 + (lane & 7), bar + B_HH2); }
    }
  } else {
    const int wg = warp >> 2, wq = warp & 3, tid = threadIdx.x;
    const int g = lane >> 2, c = lane & 3;
    const int sec0 = (m >> 1) & 1, hf0 = m & 1, ks0 = (m >> 2) & 3;
    uint4 wv[8];
    uint32_t ep0; uint16_t cv_;
    asm volatile("ld.global.nc.u16 %0, [%1];" : "=h"(cv_) : "l"(cvec + ks0 * 256 + warp * 32 + lane));
    asm volatile("ld.global.u32 %0, [%1];" : "=r"(ep0) : "l"(gs->epoch + bid + 4));
    if (!extra) {
      const bf16* wp = wmod + (size_t)(ks0 * 256 + warp * 32 + (lane >> 3)) * 6144 + sec0 * 1024 + j * 128 + hf0 * 64 + (lane & 7) * 8;
#pragma unroll
      for (int i = 0; i < 8; i++) wv[i] = ldg_nc(wp + (size_t)i * 4 * 6144);
    }
    asm volatile("setmaxnreg.inc.sync.aligned.u32 232;" ::: "memory");
    if (__builtin_expect(extra, 0)) {
      const uint32_t ep = ep0 + 1;
      float sv[4];
#pragma unroll
      for (int p = 0; p < 4; p++) sv[p] = silu_c(__bfloat162float(cvec[64 * (4 * p + (lane >> 3)) + 8 * warp + (lane & 7)]));
      named_bar(2, 288);
      int s = 0, par = 0;
#pragma unroll 1
      for (int sec = 0; sec < 4; sec++) {
        float a[8] = {0, 0, 0, 0, 0, 0, 0, 0};
#pragma unroll 1
        for (int it = 0; it < 16; it++) {
          const float sc = it < 4 ? sv[0] : it < 8 ? sv[1] : it < 12 ? sv[2] : sv[3];
          mbar_wait(bar + B_FULL6 + s * 8, par);
          uint4 w[8];
#pragma unroll
          for (int i = 0; i < 8; i++) w[i] = lds128(sb + s * 32768 + (warp * 8 + i) * 512 + lane * 16);
#pragma unroll
          for (int i = 0; i < 8; i++) gemv_fma(a, w[i], __shfl_sync(~0u, sc, (it & 3) * 8 + i));
          if (lane == 0) mbar_arrive(bar + B_EMPTY6 + s * 8);
          if (++s == 6) { s = 0; par ^= 1; }
        }
        const uint32_t red = sb + STG + sec * 8192;
        sts128(red + warp * 1024 + lane * 32, __float_as_uint(a[0]), __float_as_uint(a[1]), __float_as_uint(a[2]), __float_as_uint(a[3]));
        sts128(red + warp * 1024 + lane * 32 + 16, __float_as_uint(a[4]), __float_as_uint(a[5]), __float_as_uint(a[6]), __float_as_uint(a[7]));
        named_bar(1, 256);
        float t = 0;
#pragma unroll
        for (int q = 0; q < 8; q++) t += lds32f(red + q * 1024 + tid * 4);
        t = bf_round(t);
        if (sec == 2) t = bf_round(t + 1.f);
        st_rlx2(gs->modv + sec * 1024 + (bid + 4) * 256 + tid, __float_as_uint(t), ep);
      }
      if (tid == 0) gs->epoch[bid + 4] = ep;
      return;
    }
    const int row0 = wg * 64 + wq * 16 + g;
    if (c < 2) st_rlx2(gs->stat + m * 1024 + j * 128 + row0 + c * 8, 0, 0);
    if (tid < 64) st_rlx1(gs->modp + ((j * 2 + sec0) * 4 + ks0) * 128 + hf0 * 64 + tid, 0);
    cl_arrive_relaxed(); cl_wait();
    uint32_t ep;
    asm volatile("add.u32 %0, %1, 1;" : "=r"(ep) : "r"(ep0) : "memory");
    const float sc_ = silu_c(__uint_as_float((uint32_t)cv_ << 16));
    const uint32_t rel = mapa(bar, (lane & 1) ^ rank);
    const uint32_t stg_row = sb + STG + (wg * 64 + wq * 16 + (lane & 15)) * 128;
    const uint32_t fre = bar + B_FREE;
    Ring r4{0, 0, 0}, r6{0, 0, 0};
    auto none = [](auto) {};
    uint32_t xk[32];
    {
      float a[8] = {0, 0, 0, 0, 0, 0, 0, 0};
#pragma unroll
      for (int i = 0; i < 8; i++) gemv_fma(a, wv[i], __shfl_sync(~0u, sc_, i * 4 + (lane >> 3)));
#pragma unroll
      for (int i = 0; i < 8; i++) { a[i] += __shfl_xor_sync(~0u, a[i], 8); a[i] += __shfl_xor_sync(~0u, a[i], 16); }
      if (lane < 8) {
        sts128(sb + RED_OFF + warp * 256 + lane * 32, __float_as_uint(a[0]), __float_as_uint(a[1]), __float_as_uint(a[2]), __float_as_uint(a[3]));
        sts128(sb + RED_OFF + warp * 256 + lane * 32 + 16, __float_as_uint(a[4]), __float_as_uint(a[5]), __float_as_uint(a[6]), __float_as_uint(a[7]));
      }
      named_bar(1, 256);
      if (tid < 64) {
        float s = 0;
#pragma unroll
        for (int w = 0; w < 8; w++) s += lds32f(sb + RED_OFF + w * 256 + tid * 4);
        st_rlx1(gs->modp + ((j * 2 + sec0) * 4 + ks0) * 128 + hf0 * 64 + tid, (__float_as_uint(s) & ~255u) | tag_of(ep));
      }
      float v[64];
      mbar_wait(bar + B_X, 0); mbar_wait(bar + B_X + 8, 0);
#pragma unroll
      for (int i = 0; i < 16; i += 2) {
        uint32_t w0, w1, w2, w3;
        ldsm4(stg_row + (i >> 3) * BLK + ((((i & 7) + (lane >> 4)) ^ (lane & 7)) << 4), w0, w1, w2, w3);
        xk[2 * i] = w0; xk[2 * i + 1] = w1; xk[2 * i + 2] = w2; xk[2 * i + 3] = w3;
        v[4 * i] = bf_lo(w0); v[4 * i + 1] = bf_hi(w0); v[4 * i + 2] = bf_lo(w1); v[4 * i + 3] = bf_hi(w1);
        v[4 * i + 4] = bf_lo(w2); v[4 * i + 5] = bf_hi(w2); v[4 * i + 6] = bf_lo(w3); v[4 * i + 7] = bf_hi(w3);
      }
      ln_publish(v, gs->stat + m * 1024, j, row0, lane, ep);
      mod_store(sb, tid >> 7, tid & 127, mod_gather(gs->modp + (j * 2 + (tid >> 7)) * 512 + (tid & 127), ep));
      named_bar(1, 256);
      ln_apply(v, gs->stat + m * 1024, row0, ep, sb, 0, 1, stg_row, wg, lane);
      named_bar(1, 256);
    }
    {
      uint32_t kf[32], vf[32], pv[32];
      const bool first = wq == 0 && m == 0;
      const uint32_t xa = sb + STG + wg * HALF + wq * 2048 + lane * 16;
      {
        float acc[128];
        mainloop<256, 4, 0, 0>(acc, 16, true, r4, sb, wg, lane, rel, none, none, [&] {
          mbar_wait(fre + 8, 0);
          if (c < 2) st_rlx2(gs->stat + (16 + m) * 1024 + j * 128 + row0 + c * 8, 0, 0);
        });
#pragma unroll
        for (int i = 0; i < 32; i++) { kf[i] = pack2(acc[2 * i], acc[2 * i + 1]); vf[i] = pack2(acc[64 + 2 * i], acc[65 + 2 * i]); }
      }
      float acc[64];
      constexpr int QP = 2;
      mainloop<128, 6, 8 / QP, 0>(acc, 16, false, r6, sb, wg, lane, rel, [&](auto ic) {
        constexpr int q = (ic.v - 1) * QP;
#pragma unroll
        for (int i = 4 * q; i < 4 * (q + QP); i++) vf[i] = movm(vf[i]);
        if (wq == 3) {
          if (m < 15) {
            uint4* hp = gs->halo + (((m + 1) * 8 + j) * 2 + wg) * 512 + lane;
#pragma unroll
            for (int i = 2 * q; i < 2 * (q + QP); i++) st_rlx4(hp + i * 32, kf[2 * i + 1], ep, vf[2 * i + 1], ep);
          }
        } else {
#pragma unroll
          for (int i = q; i < q + QP; i++) sts128(xa + 2048 + (i >> 2) * BLK + (i & 3) * 512, kf[4 * i + 1], kf[4 * i + 3], vf[4 * i + 1], vf[4 * i + 3]);
        }
      }, none, [&] {
        named_bar(2 + wg, 128);
        if (wq == 0) mbar_wait(bar + B_HALO, 0);
#pragma unroll
        for (int i = 0; i < 8; i++) {
          uint4 q = lds128(xa + (i >> 2) * BLK + (i & 3) * 512);
          pv[4 * i] = q.x; pv[4 * i + 1] = q.y; pv[4 * i + 2] = q.z; pv[4 * i + 3] = q.w;
        }
        __syncwarp();
      });
      int gz = g;
#pragma unroll
      for (int b = 0; b < 2; b++) {
        const bool up0 = 2 * c > gz, up1 = 2 * c + 1 > gz;
        const uint32_t mup = (up0 ? 0xffffu : 0u) | (up1 ? 0xffff0000u : 0u);
        float l[2][4], mx[4];
#pragma unroll
        for (int h = 0; h < 2; h++) {
          uint32_t q[8];
          const int k = 16 * b + 8 * h;
#pragma unroll
          for (int i = 0; i < 8; i++) q[i] = pack2(acc[2 * k + 2 * i], acc[2 * k + 2 * i + 1]);
          float s0[4], s1[4], s2[4];
          mma16z(s0, q[0], q[1], q[2], q[3], pv[k], pv[k + 1]); mma16z(s1, q[0], q[1], q[2], q[3], kf[k], kf[k + 2]); mma16z(s2, q[0], q[1], q[2], q[3], kf[k + 1], kf[k + 3]);
          mma16(s0, q[4], q[5], q[6], q[7], pv[k + 4], pv[k + 5]); mma16(s1, q[4], q[5], q[6], q[7], kf[k + 4], kf[k + 6]); mma16(s2, q[4], q[5], q[6], q[7], kf[k + 5], kf[k + 7]);
          if (first) { s0[0] = -INFINITY; s0[1] = -INFINITY; }
          l[h][0] = up0 ? s0[0] : s1[0]; l[h][1] = up1 ? s0[1] : s1[1]; l[h][2] = up0 ? s1[2] : s2[2]; l[h][3] = up1 ? s1[3] : s2[3];
          mx[2 * h] = fmaxf(l[h][0], l[h][1]); mx[2 * h + 1] = fmaxf(l[h][2], l[h][3]);
        }
#pragma unroll
        for (int o = 1; o < 4; o <<= 1) {
#pragma unroll
          for (int h = 0; h < 4; h++) mx[h] = fmaxf(mx[h], __shfl_xor_sync(~0u, mx[h], o));
        }
#pragma unroll
        for (int h = 0; h < 2; h++) {
          const float n0 = -mx[2 * h] * SCL, n1 = -mx[2 * h + 1] * SCL;
          const uint32_t pa = pack2(ex2(fmaf(l[h][0], SCL, n0)), ex2(fmaf(l[h][1], SCL, n0))), pb = pack2(ex2(fmaf(l[h][2], SCL, n1)), ex2(fmaf(l[h][3], SCL, n1)));
          float sm[4];
          mma8z(sm, pa, pb, 0x3f803f80u);
          const float ia = rcp(sm[0]), ib = rcp(sm[2]);
#pragma unroll
          for (int i = 8 * b + 4 * h; i < 8 * b + 4 * h + 4; i += 2) {
            uint32_t of[4];
#pragma unroll
            for (int d = 0; d < 2; d++) {
              float o[4];
              mma16z(o, pa & ~mup, pb & mup, 0u, pb & ~mup, vf[2 * (i + d)], vf[2 * (i + d) + 1]);
              mma8(o, pa & mup, 0u, pv[2 * i + 2 + d]);
              of[2 * d] = pack2(o[0] * ia, o[1] * ia); of[2 * d + 1] = pack2(o[2] * ib, o[3] * ib);
            }
            stsm4(stg_row + b * BLK + ((((i & 7) + (lane >> 4)) ^ (lane & 7)) << 4), of[0], of[1], of[2], of[3]);
          }
        }
        stage_done(sb, wg, b, lane);
        if (b == 0) gz += __float_as_uint(lds32f(bar + ZERO));
      }
      named_bar(1, 256);
    }
    uint32_t pk[64];
    {
      float acc[64];
      mainloop<128, 6, 0, WOLAG>(acc, 16, true, r6, sb, wg, lane, rel, none, none, [&] {
        if (WOLAG && wg == 0 && lane == 0) mbar_arrive(bar + B_LAG);
        mbar_wait(bar + B_MOD, 0); mbar_wait(fre + 8, 1);
        load_vec(pk + 32, sb, 2, 0, lane); load_vec(pk + 40, sb, 2, 1, lane);
#pragma unroll
        for (int i = 0; i < 32; i++) { pk[i] = xk[i]; asm volatile("" : "+r"(pk[i])); }
      });
#pragma unroll
      for (int i = 0; i < 32; i++) {
        acc[2 * i] = fmaf(acc[2 * i], bf_lo(pk[32 + (i >> 1)]), bf_lo(pk[i]));
        acc[2 * i + 1] = fmaf(acc[2 * i + 1], bf_hi(pk[32 + (i >> 1)]), bf_hi(pk[i]));
      }
      ln_publish(acc, gs->stat + (16 + m) * 1024, j, row0, lane, ep);
      mbar_wait(bar + B_FULL6 + 16, 1);
      if (lane < 2) mbar_arrive_cl(rel + B_EMPTY6 + 16);
      ring_next<6>(r6);
#pragma unroll
      for (int i = 0; i < 32; i++) { pk[i] = pack2(acc[2 * i], acc[2 * i + 1]); pk[32 + i] = 0; }
      ln_apply(acc, gs->stat + (16 + m) * 1024, row0, ep, sb, 3, 4, stg_row, wg, lane);
      named_bar(1, 256);
    }
    auto swiglu = [&](int q, int uo, int par) {
      if ((q & 3) == 0 && par >= 0) mbar_wait(fre + 2 * q, par);
      uint32_t w[4];
#pragma unroll
      for (int u = 0; u < 4; u++) w[u] = silu_mul2(pk[4 * q + u], pk[uo + 4 * q + u]);
      stsm4(stg_row + (q >> 2) * BLK + ((((2 * q & 7) + (lane >> 4)) ^ (lane & 7)) << 4), w[0], w[1], w[2], w[3]);
    };
    r4.s = r4.wrap = 2;
#pragma unroll 1
    for (int t = 0; t < 3; t++) {
      float acc[128];
      mainloop<256, 4, 5, 0>(acc, 16, t == 0, r4, sb, wg, lane, rel, [&](auto ic) {
        if (t) {
          if (ic.v == 3 || ic.v == 5) stage_done(sb, wg, ic.v >> 2, lane);
          if (ic.v < 5) { swiglu(2 * ic.v - 2, 32, ~t & 1); swiglu(2 * ic.v - 1, 32, 0); }
        }
      }, [&](int it) {
#pragma unroll
        for (int i = 0; i < 8; i++)
          if (t == 0 && it == 8 + i) gs->x1[bid * 2048 + (i >> 2) * 1024 + warp * 128 + (i & 3) * 32 + lane] = make_uint4(pk[4 * i], pk[4 * i + 1], pk[4 * i + 2], pk[4 * i + 3]);
      }, [&] { if (t == 0) fence_async_global(); else if (t == 2) mbar_wait(bar + B_X, 1); });
#pragma unroll
      for (int i = 0; i < 64; i++) pk[i] = pack2(acc[2 * i], acc[2 * i + 1]);
    }
    uint32_t x1[32];
    {
      float acc[64];
      mainloop<128, 6, 12, 0>(acc, 16, false, r6, sb, wg, lane, rel, [&](auto ic) {
        constexpr int b = ic.v > 6, q = ic.v - 6 * b;
        if (q == 1) {
#pragma unroll
          for (int i = 4 * b; i < 4 * b + 4; i++) { const uint4 x = lds128(sb + STG + b * BLK + warp * 2048 + (i & 3) * 512 + lane * 16); x1[4 * i] = x.x; x1[4 * i + 1] = x.y; x1[4 * i + 2] = x.z; x1[4 * i + 3] = x.w; }
          __syncwarp();
        } else if (q < 6) swiglu(4 * b + q - 2, 32, -1);
        else stage_done(sb, wg, b, lane);
      }, none, [] {});
#pragma unroll
      for (int i = 0; i < 32; i++) pk[i] = pack2(acc[2 * i], acc[2 * i + 1]);
    }
    {
      float acc[64];
      mainloop<128, 6, 5, TAILLAG>(acc, 56, false, r6, sb, wg, lane, rel, [&](auto ic) {
        if (ic.v == 5) stage_done(sb, wg, 0, lane); else swiglu(ic.v - 1, 16, 1);
      }, none, [&] {
        if (TAILLAG && wg == 0 && lane == 0) mbar_arrive(bar + B_LAG);
        load_vec(pk + 32, sb, 5, 0, lane); load_vec(pk + 40, sb, 5, 1, lane);
        mbar_wait(fre, 0); mbar_wait(fre + 8, 1);
      });
      __syncwarp();
      cl_arrive_relaxed();
#pragma unroll
      for (int i = 0; i < 16; i += 2) {
        uint32_t w[4];
#pragma unroll
        for (int u = 0; u < 4; u++) {
          const int q = 2 * i + u;
          w[u] = pack2(fmaf(acc[2 * q], bf_lo(pk[32 + (q >> 1)]), bf_lo(x1[q])), fmaf(acc[2 * q + 1], bf_hi(pk[32 + (q >> 1)]), bf_hi(x1[q])));
        }
        stsm4(stg_row + (i >> 3) * BLK + ((((i & 7) + (lane >> 4)) ^ (lane & 7)) << 4), w[0], w[1], w[2], w[3]);
        if ((i & 7) == 6) {
          fence_async_smem();
          named_bar(2 + wg, 128);
          if (wq == 0 && elect()) { tma_store_3d(&maps.out, sb + STG + (i >> 3) * BLK + wg * HALF, j * 128 + (i >> 3) * 64, m * 64, wg); bulk_commit(); }
          if (i < 8) x1[16] |= __float_as_uint(lds32f(bar + ZERO));
        }
      }
      if (wq == 0) bulk_wait_read();
      if (tid == 0) gs->epoch[bid + 4] = ep;
      cl_wait();
    }
  }
}

typedef CUresult (*EncodeFn)(CUtensorMap*, CUtensorMapDataType, cuuint32_t, void*, const cuuint64_t*, const cuuint64_t*, const cuuint32_t*, const cuuint32_t*,
                             CUtensorMapInterleave, CUtensorMapSwizzle, CUtensorMapL2promotion, CUtensorMapFloatOOBfill);

void make_map(EncodeFn fn, CUtensorMap* mp, const void* base, uint64_t d0, uint64_t d1, uint64_t d2, uint64_t s1, uint64_t s2, uint32_t b2, uint32_t b0 = 64) {
  cuuint64_t d[3] = {d0, d1, d2}, s[2] = {s1, s2};
  cuuint32_t b[3] = {b0, 64, b2}, e[3] = {1, 1, 1};
  fn(mp, CU_TENSOR_MAP_DATA_TYPE_BFLOAT16, 3, (void*)base, d, s, b, e, CU_TENSOR_MAP_INTERLEAVE_NONE, b0 == 64 ? CU_TENSOR_MAP_SWIZZLE_128B : CU_TENSOR_MAP_SWIZZLE_NONE,
     CU_TENSOR_MAP_L2_PROMOTION_L2_128B, CU_TENSOR_MAP_FLOAT_OOB_FILL_NONE);
}

__global__ void probe_kernel() {}
int max_clusters(int size) {
  cudaLaunchConfig_t cfg = {};
  cudaLaunchAttribute at;
  at.id = cudaLaunchAttributeClusterDimension; at.val.clusterDim.x = size; at.val.clusterDim.y = 1; at.val.clusterDim.z = 1;
  cfg.gridDim = dim3(size * 66); cfg.blockDim = dim3(384); cfg.dynamicSmemBytes = SMEM_BYTES; cfg.attrs = &at; cfg.numAttrs = 1;
  int n = 0;
  if (cudaOccupancyMaxActiveClusters(&n, probe_kernel, &cfg) != cudaSuccess) { cudaGetLastError(); return 0; }
  return n;
}

}

extern "C" void kernel_launch(void* const* d_in, const int* in_sizes, int n_in, void* d_out, int out_size) {
  static EncodeFn fn = nullptr;
  static int by_sm = 0;
  static Scratch* gs = nullptr;
  if (!fn) {
    void* p = nullptr; cudaDriverEntryPointQueryResult q;
    cudaGetDriverEntryPoint("cuTensorMapEncodeTiled", &p, cudaEnableDefault, &q);
    fn = (EncodeFn)p;
    cudaFuncSetAttribute(fused_kernel, cudaFuncAttributeMaxDynamicSharedMemorySize, SMEM_BYTES);
    int dev = 0, sms = 0;
    cudaGetSymbolAddress((void**)&gs, g_scratch);
    cudaGetDevice(&dev);
    cudaDeviceGetAttribute(&sms, cudaDevAttrMultiProcessorCount, dev);
    cudaFuncSetAttribute(probe_kernel, cudaFuncAttributeMaxDynamicSharedMemorySize, SMEM_BYTES);
    by_sm = sms == 132 && max_clusters(2) == 66 && max_clusters(4) == 30 && max_clusters(6) == 17 && max_clusters(8) == 15;
  }
  Maps mp;
  make_map(fn, &mp.x, d_in[0], D_, S_ / 2, 2, 4096, 2048, 2);
  make_map(fn, &mp.out, d_out, D_, S_ / 2, 2, 4096, 2048, 1);
  make_map(fn, &mp.wqkv, d_in[1], 64, D_, 3 * D_ / 64, 3 * D_ * 2, 128, 2);
  make_map(fn, &mp.wo, d_in[2], 64, D_, D_ / 64, D_ * 2, 128, 2);
  make_map(fn, &mp.w1, d_in[4], 64, D_, F_ / 64, F_ * 2, 128, 2);
  make_map(fn, &mp.w3, d_in[5], 64, D_, F_ / 64, F_ * 2, 128, 2);
  make_map(fn, &mp.w1s, d_in[4], 64, D_, F_ / 64, F_ * 2, 128, 1);
  make_map(fn, &mp.w3s, d_in[5], 64, D_, F_ / 64, F_ * 2, 128, 1);
  make_map(fn, &mp.w2, d_in[6], 64, F_, D_ / 64, D_ * 2, 128, 2);
  make_map(fn, &mp.wmod, d_in[8], 256, D_, 24, 6 * D_ * 2, 512, 1, 256);
  fused_kernel<<<132, 384, SMEM_BYTES>>>((const bf16*)d_in[7], (const bf16*)d_in[8], gs, by_sm, mp);
}
```

```cpp
#include <cuda_runtime.h>
#include <cuda_bf16.h>
#include <cuda.h>
#include <stdint.h>

typedef __nv_bfloat16 bf16;

namespace {

constexpr int S_ = 2048, D_ = 1024, F_ = 3584;
constexpr int BLK = 16384;
constexpr int HALF = 8192;
constexpr int RING = 196608;
constexpr int STG = RING;
constexpr int MISC = RING + 2 * BLK;
constexpr int SMEM_BYTES = MISC + 3072;
constexpr int B_FULL4 = 0, B_EMPTY4 = 32, B_FULL6 = 64, B_EMPTY6 = 112, B_RDY = 160, B_FREE = 176, B_LAG = 192, B_X = 208, B_MOD = 224, B_HALO = 232, B_HH = 256, B_ALL = 272, B_HH2 = 288, ZERO = 296;
constexpr int MODV = 512;
constexpr int RED_OFF = 0;
constexpr float SCL = 0.17677669529663687f * 1.4426950408889634f;
constexpr int U_HH = 64;
constexpr int FS = 8;
constexpr int NPIECE = 4, PSLEEP = 300;
constexpr int XSLEEP = 4000, HSLEEP = 400;
constexpr uint32_t XDELAY = 2000;
constexpr uint32_t B1P = 3500, B1D = 900, B1P2 = 3200;
constexpr int WOLAG = 2, TAILLAG = 5;

struct Maps { CUtensorMap x, out, wqkv, wo, w1, w3, w1s, w3s, w2, wmod; };

struct Scratch {
  uint4 h[16 * 16 * 1024];
  uint4 o[16 * 16 * 1024];
  uint4 hh[16 * 56 * 1024];
  uint4 x1[128 * 8 * 256];
  uint2 stat[2 * 16 * 8 * 128];
  uint4 halo[16 * 8 * 2 * 512];
  uint32_t modp[8 * 2 * 4 * 128];
  uint2 modv[4 * 1024];
  uint32_t flag[16 * 128 * FS];
  uint32_t epoch[132];
};
__device__ __align__(1024) Scratch g_scratch;

__device__ __forceinline__ void bail() { asm volatile("st.global.u32 [%0], %1;" :: "l"(0ull), "r"(0) : "memory"); }
__device__ __forceinline__ uint32_t smem_u32(const void* p) { return (uint32_t)__cvta_generic_to_shared(p); }
__device__ __forceinline__ void mbar_init(uint32_t bar, uint32_t cnt) { asm volatile("mbarrier.init.shared::cta.b64 [%0], %1;" :: "r"(bar), "r"(cnt) : "memory"); }
__device__ __forceinline__ void mbar_expect_tx(uint32_t bar, uint32_t bytes) { asm volatile("mbarrier.arrive.expect_tx.shared::cta.b64 _, [%0], %1;" :: "r"(bar), "r"(bytes) : "memory"); }
__device__ __forceinline__ void mbar_arrive(uint32_t bar) { asm volatile("mbarrier.arrive.shared::cta.b64 _, [%0];" :: "r"(bar) : "memory"); }
__device__ __forceinline__ void mbar_arrive_cl(uint32_t cl_addr) { asm volatile("mbarrier.arrive.shared::cluster.b64 _, [%0];" :: "r"(cl_addr) : "memory"); }
__device__ __forceinline__ uint32_t mapa(uint32_t addr, uint32_t cta) { uint32_t r; asm("mapa.shared::cluster.u32 %0, %1, %2;" : "=r"(r) : "r"(addr), "r"(cta)); return r; }
__device__ __forceinline__ void mbar_wait(uint32_t bar, uint32_t parity) {
  asm volatile("{\n.reg .pred p;\n.reg .b32 n;\n.reg .b64 z;\nmov.b32 n, 0;\nmov.b64 z, 0;\n"
               "W: add.u32 n, n, 1;\nsetp.gt.u32 p, n, 0x400000;\n@p st.global.u32 [z], n;\n"
               "mbarrier.try_wait.parity.shared::cta.b64 p, [%0], %1;\n@!p bra W;\n}" :: "r"(bar), "r"(parity) : "memory");
}
__device__ __forceinline__ void tma_3d(uint32_t dst, const CUtensorMap* m, uint32_t bar, int c0, int c1, int c2) {
  asm volatile("cp.async.bulk.tensor.3d.shared::cluster.global.mbarrier::complete_tx::bytes [%0], [%1, {%3, %4, %5}], [%2];" :: "r"(dst), "l"(m), "r"(bar), "r"(c0), "r"(c1), "r"(c2) : "memory");
}
__device__ __forceinline__ void tma_store_3d(const CUtensorMap* m, uint32_t src, int c0, int c1, int c2) {
  asm volatile("cp.async.bulk.tensor.3d.global.shared::cta.bulk_group [%0, {%2, %3, %4}], [%1];" :: "l"(m), "r"(src), "r"(c0), "r"(c1), "r"(c2) : "memory");
}
__device__ __forceinline__ void bulk_ld(uint32_t dst, const void* src, uint32_t bytes, uint32_t bar) {
  asm volatile("cp.async.bulk.shared::cluster.global.mbarrier::complete_tx::bytes [%0], [%1], %2, [%3];" :: "r"(dst), "l"(src), "r"(bytes), "r"(bar) : "memory");
}
__device__ __forceinline__ void bulk_ld_mc(uint32_t dst, const void* src, uint32_t bytes, uint32_t bar) {
  asm volatile("cp.async.bulk.shared::cluster.global.mbarrier::complete_tx::bytes.multicast::cluster [%0], [%1], %2, [%3], %4;" :: "r"(dst), "l"(src), "r"(bytes), "r"(bar), "h"((uint16_t)3) : "memory");
}
__device__ __forceinline__ void bulk_push(uint32_t dst_cl, uint32_t src, uint32_t bytes, uint32_t bar_cl) {
  asm volatile("cp.async.bulk.shared::cluster.shared::cta.mbarrier::complete_tx::bytes [%0], [%1], %2, [%3];" :: "r"(dst_cl), "r"(src), "r"(bytes), "r"(bar_cl) : "memory");
}
__device__ __forceinline__ void bulk_st(void* dst, uint32_t src, uint32_t bytes) {
  asm volatile("cp.async.bulk.global.shared::cta.bulk_group [%0], [%1], %2;" :: "l"(dst), "r"(src), "r"(bytes) : "memory");
}
__device__ __forceinline__ void bulk_commit() { asm volatile("cp.async.bulk.commit_group;" ::: "memory"); }
__device__ __forceinline__ void bulk_wait_read() { asm volatile("cp.async.bulk.wait_group.read 0;" ::: "memory"); }
__device__ __forceinline__ void bulk_wait_all() { asm volatile("cp.async.bulk.wait_group 0;" ::: "memory"); }
__device__ __forceinline__ void fence_async_global() { asm volatile("fence.proxy.async.global;" ::: "memory"); }
__device__ __forceinline__ void fence_async_smem() { asm volatile("fence.proxy.async.shared::cta;" ::: "memory"); }
__device__ __forceinline__ void wg_arrive() { asm volatile("wgmma.fence.sync.aligned;" ::: "memory"); }
__device__ __forceinline__ void wg_commit() { asm volatile("wgmma.commit_group.sync.aligned;" ::: "memory"); }
template <int N> __device__ __forceinline__ void wg_wait() { asm volatile("wgmma.wait_group.sync.aligned %0;" :: "n"(N) : "memory"); }
__device__ __forceinline__ void cl_arrive_relaxed() { asm volatile("barrier.cluster.arrive.relaxed.aligned;" ::: "memory"); }
__device__ __forceinline__ void cl_wait() { asm volatile("barrier.cluster.wait.acquire.aligned;" ::: "memory"); }
__device__ __forceinline__ bool elect() { uint32_t p; asm volatile("{\n.reg .pred p;\nelect.sync _|p, 0xffffffff;\nselp.u32 %0, 1, 0, p;\n}" : "=r"(p)); return p; }
__device__ __forceinline__ void named_bar(int id, int n) { asm volatile("bar.sync %0, %1;" :: "r"(id), "r"(n) : "memory"); }
__device__ __forceinline__ uint32_t pack2(float lo, float hi) { uint32_t r; asm("cvt.rn.bf16x2.f32 %0, %1, %2;" : "=r"(r) : "f"(hi), "f"(lo)); return r; }
__device__ __forceinline__ float bf_lo(uint32_t w) { return __uint_as_float(w << 16); }
__device__ __forceinline__ float bf_hi(uint32_t w) { return __uint_as_float(w & 0xffff0000u); }
__device__ __forceinline__ float bf_round(float v) { return __bfloat162float(__float2bfloat16_rn(v)); }
__device__ __forceinline__ void stsm4(uint32_t addr, uint32_t a, uint32_t b, uint32_t c, uint32_t d) {
  asm volatile("stmatrix.sync.aligned.m8n8.x4.shared.b16 [%0], {%1, %2, %3, %4};" :: "r"(addr), "r"(a), "r"(b), "r"(c), "r"(d) : "memory");
}
__device__ __forceinline__ void ldsm4(uint32_t addr, uint32_t& a, uint32_t& b, uint32_t& c, uint32_t& d) {
  asm volatile("ldmatrix.sync.aligned.m8n8.x4.shared.b16 {%0, %1, %2, %3}, [%4];" : "=r"(a), "=r"(b), "=r"(c), "=r"(d) : "r"(addr) : "memory");
}
__device__ __forceinline__ uint32_t movm(uint32_t a) { uint32_t r; asm volatile("movmatrix.sync.aligned.m8n8.trans.b16 %0, %1;" : "=r"(r) : "r"(a)); return r; }
__device__ __forceinline__ void mma16(float (&d)[4], uint32_t a0, uint32_t a1, uint32_t a2, uint32_t a3, uint32_t b0, uint32_t b1) {
  asm("mma.sync.aligned.m16n8k16.row.col.f32.bf16.bf16.f32 {%0,%1,%2,%3}, {%4,%5,%6,%7}, {%8,%9}, {%0,%1,%2,%3};"
               : "+f"(d[0]), "+f"(d[1]), "+f"(d[2]), "+f"(d[3]) : "r"(a0), "r"(a1), "r"(a2), "r"(a3), "r"(b0), "r"(b1));
}
__device__ __forceinline__ void mma16z(float (&d)[4], uint32_t a0, uint32_t a1, uint32_t a2, uint32_t a3, uint32_t b0, uint32_t b1) {
  asm("mma.sync.aligned.m16n8k16.row.col.f32.bf16.bf16.f32 {%0,%1,%2,%3}, {%4,%5,%6,%7}, {%8,%9}, {%10,%10,%10,%10};"
      : "=f"(d[0]), "=f"(d[1]), "=f"(d[2]), "=f"(d[3]) : "r"(a0), "r"(a1), "r"(a2), "r"(a3), "r"(b0), "r"(b1), "f"(0.f));
}
__device__ __forceinline__ void mma8z(float (&d)[4], uint32_t a0, uint32_t a1, uint32_t b0) {
  asm("mma.sync.aligned.m16n8k8.row.col.f32.bf16.bf16.f32 {%0,%1,%2,%3}, {%4,%5}, {%6}, {%7,%7,%7,%7};"
      : "=f"(d[0]), "=f"(d[1]), "=f"(d[2]), "=f"(d[3]) : "r"(a0), "r"(a1), "r"(b0), "f"(0.f));
}
__device__ __forceinline__ void mma8(float (&d)[4], uint32_t a0, uint32_t a1, uint32_t b0) {
  asm("mma.sync.aligned.m16n8k8.row.col.f32.bf16.bf16.f32 {%0,%1,%2,%3}, {%4,%5}, {%6}, {%0,%1,%2,%3};"
               : "+f"(d[0]), "+f"(d[1]), "+f"(d[2]), "+f"(d[3]) : "r"(a0), "r"(a1), "r"(b0));
}
__device__ __forceinline__ uint4 lds128(uint32_t a) { uint4 v; asm volatile("ld.shared.v4.u32 {%0,%1,%2,%3}, [%4];" : "=r"(v.x), "=r"(v.y), "=r"(v.z), "=r"(v.w) : "r"(a) : "memory"); return v; }
__device__ __forceinline__ void sts128(uint32_t a, uint32_t x, uint32_t y, uint32_t z, uint32_t w) { asm volatile("st.shared.v4.u32 [%0], {%1,%2,%3,%4};" :: "r"(a), "r"(x), "r"(y), "r"(z), "r"(w) : "memory"); }
__device__ __forceinline__ float lds32f(uint32_t a) { float v; asm volatile("ld.shared.f32 %0, [%1];" : "=f"(v) : "r"(a) : "memory"); return v; }
__device__ __forceinline__ void sts16(uint32_t a, bf16 v) { asm volatile("st.shared.b16 [%0], %1;" :: "r"(a), "h"(__bfloat16_as_ushort(v)) : "memory"); }
__device__ __forceinline__ uint4 ldg_nc(const void* p) { uint4 v; asm volatile("ld.global.nc.L1::no_allocate.v4.u32 {%0,%1,%2,%3}, [%4];" : "=r"(v.x), "=r"(v.y), "=r"(v.z), "=r"(v.w) : "l"(p)); return v; }
__device__ __forceinline__ uint4 ld_rlx4(const uint4* p) {
  unsigned long long a, b; asm volatile("ld.relaxed.gpu.global.v2.b64 {%0,%1}, [%2];" : "=l"(a), "=l"(b) : "l"(p) : "memory");
  return make_uint4((uint32_t)a, (uint32_t)(a >> 32), (uint32_t)b, (uint32_t)(b >> 32));
}
__device__ __forceinline__ uint2 ld_rlx2(const uint2* p) { unsigned long long a; asm volatile("ld.relaxed.gpu.global.b64 %0, [%1];" : "=l"(a) : "l"(p) : "memory"); return make_uint2((uint32_t)a, (uint32_t)(a >> 32)); }
__device__ __forceinline__ void st_rlx4(uint4* p, uint32_t x, uint32_t y, uint32_t z, uint32_t w) {
  asm volatile("st.relaxed.gpu.global.v2.b64 [%0], {%1,%2};" :: "l"(p), "l"((unsigned long long)x | ((unsigned long long)y << 32)), "l"((unsigned long long)z | ((unsigned long long)w << 32)) : "memory");
}
__device__ __forceinline__ void st_rlx2(uint2* p, uint32_t x, uint32_t y) { asm volatile("st.relaxed.gpu.global.b64 [%0], %1;" :: "l"(p), "l"((unsigned long long)x | ((unsigned long long)y << 32)) : "memory"); }
__device__ __forceinline__ void st_rlx1(uint32_t* p, uint32_t v) { asm volatile("st.relaxed.gpu.global.u32 [%0], %1;" :: "l"(p), "r"(v) : "memory"); }
__device__ __forceinline__ uint32_t ld_rlx1(const uint32_t* p) { uint32_t v; asm volatile("ld.relaxed.gpu.global.u32 %0, [%1];" : "=r"(v) : "l"(p) : "memory"); return v; }
__device__ __forceinline__ void st_release(uint32_t* p, uint32_t v) { asm volatile("st.release.gpu.global.u32 [%0], %1;" :: "l"(p), "r"(v) : "memory"); }
__device__ __forceinline__ uint32_t ld_acquire(const uint32_t* p) { uint32_t v; asm volatile("ld.acquire.gpu.global.u32 %0, [%1];" : "=r"(v) : "l"(p) : "memory"); return v; }
__device__ __forceinline__ void prefetch_map(const CUtensorMap* m) { asm volatile("prefetch.tensormap [%0];" :: "l"(m) : "memory"); }
__device__ __forceinline__ float rcp(float x) { float r; asm("rcp.approx.ftz.f32 %0, %1;" : "=f"(r) : "f"(x)); return r; }
__device__ __forceinline__ float ex2(float x) { float r; asm("ex2.approx.ftz.f32 %0, %1;" : "=f"(r) : "f"(x)); return r; }
__device__ __forceinline__ float tanh_fast(float x) { float r; asm("tanh.approx.f32 %0, %1;" : "=f"(r) : "f"(x)); return r; }
#define SPIN_GUARD(n) if (++(n) > (1u << 24)) bail()

__device__ __forceinline__ void wgmma_n128(float (&d)[64], uint64_t da, uint64_t db) {
  asm volatile("wgmma.mma_async.sync.aligned.m64n128k16.f32.bf16.bf16 "
    "{%0, %1, %2, %3, %4, %5, %6, %7, %8, %9, %10, %11, %12, %13, %14, %15, %16, %17, %18, %19, %20, %21, %22, %23, %24, %25, %26, %27, %28, %29, %30, %31, %32, %33, %34, %35, %36, %37, %38, %39, %40, %41, %42, %43, %44, %45, %46, %47, %48, %49, %50, %51, %52, %53, %54, %55, %56, %57, %58, %59, %60, %61, %62, %63}, "
    "%64, %65, 1, 1, 1, 0, 1;\n"
    : "+f"(d[0]), "+f"(d[1]), "+f"(d[2]), "+f"(d[3]), "+f"(d[4]), "+f"(d[5]), "+f"(d[6]), "+f"(d[7]), "+f"(d[8]), "+f"(d[9]), "+f"(d[10]), "+f"(d[11]), "+f"(d[12]), "+f"(d[13]), "+f"(d[14]), "+f"(d[15]), "+f"(d[16]), "+f"(d[17]), "+f"(d[18]), "+f"(d[19]), "+f"(d[20]), "+f"(d[21]), "+f"(d[22]), "+f"(d[23]), "+f"(d[24]), "+f"(d[25]), "+f"(d[26]), "+f"(d[27]), "+f"(d[28]), "+f"(d[29]), "+f"(d[30]), "+f"(d[31]), "+f"(d[32]), "+f"(d[33]), "+f"(d[34]), "+f"(d[35]), "+f"(d[36]), "+f"(d[37]), "+f"(d[38]), "+f"(d[39]), "+f"(d[40]), "+f"(d[41]), "+f"(d[42]), "+f"(d[43]), "+f"(d[44]), "+f"(d[45]), "+f"(d[46]), "+f"(d[47]), "+f"(d[48]), "+f"(d[49]), "+f"(d[50]), "+f"(d[51]), "+f"(d[52]), "+f"(d[53]), "+f"(d[54]), "+f"(d[55]), "+f"(d[56]), "+f"(d[57]), "+f"(d[58]), "+f"(d[59]), "+f"(d[60]), "+f"(d[61]), "+f"(d[62]), "+f"(d[63])
    : "l"(da), "l"(db));
}
__device__ __forceinline__ void wgmma_n128_first(float (&d)[64], uint64_t da, uint64_t db) {
  asm volatile("wgmma.mma_async.sync.aligned.m64n128k16.f32.bf16.bf16 "
    "{%0, %1, %2, %3, %4, %5, %6, %7, %8, %9, %10, %11, %12, %13, %14, %15, %16, %17, %18, %19, %20, %21, %22, %23, %24, %25, %26, %27, %28, %29, %30, %31, %32, %33, %34, %35, %36, %37, %38, %39, %40, %41, %42, %43, %44, %45, %46, %47, %48, %49, %50, %51, %52, %53, %54, %55, %56, %57, %58, %59, %60, %61, %62, %63}, "
    "%64, %65, 0, 1, 1, 0, 1;\n"
    : "=f"(d[0]), "=f"(d[1]), "=f"(d[2]), "=f"(d[3]), "=f"(d[4]), "=f"(d[5]), "=f"(d[6]), "=f"(d[7]), "=f"(d[8]), "=f"(d[9]), "=f"(d[10]), "=f"(d[11]), "=f"(d[12]), "=f"(d[13]), "=f"(d[14]), "=f"(d[15]), "=f"(d[16]), "=f"(d[17]), "=f"(d[18]), "=f"(d[19]), "=f"(d[20]), "=f"(d[21]), "=f"(d[22]), "=f"(d[23]), "=f"(d[24]), "=f"(d[25]), "=f"(d[26]), "=f"(d[27]), "=f"(d[28]), "=f"(d[29]), "=f"(d[30]), "=f"(d[31]), "=f"(d[32]), "=f"(d[33]), "=f"(d[34]), "=f"(d[35]), "=f"(d[36]), "=f"(d[37]), "=f"(d[38]), "=f"(d[39]), "=f"(d[40]), "=f"(d[41]), "=f"(d[42]), "=f"(d[43]), "=f"(d[44]), "=f"(d[45]), "=f"(d[46]), "=f"(d[47]), "=f"(d[48]), "=f"(d[49]), "=f"(d[50]), "=f"(d[51]), "=f"(d[52]), "=f"(d[53]), "=f"(d[54]), "=f"(d[55]), "=f"(d[56]), "=f"(d[57]), "=f"(d[58]), "=f"(d[59]), "=f"(d[60]), "=f"(d[61]), "=f"(d[62]), "=f"(d[63])
    : "l"(da), "l"(db));
}
__device__ __forceinline__ void wgmma_n256(float (&d)[128], uint64_t da, uint64_t db) {
  asm volatile("wgmma.mma_async.sync.aligned.m64n256k16.f32.bf16.bf16 "
    "{%0, %1, %2, %3, %4, %5, %6, %7, %8, %9, %10, %11, %12, %13, %14, %15, %16, %17, %18, %19, %20, %21, %22, %23, %24, %25, %26, %27, %28, %29, %30, %31, %32, %33, %34, %35, %36, %37, %38, %39, %40, %41, %42, %43, %44, %45, %46, %47, %48, %49, %50, %51, %52, %53, %54, %55, %56, %57, %58, %59, %60, %61, %62, %63, %64, %65, %66, %67, %68, %69, %70, %71, %72, %73, %74, %75, %76, %77, %78, %79, %80, %81, %82, %83, %84, %85, %86, %87, %88, %89, %90, %91, %92, %93, %94, %95, %96, %97, %98, %99, %100, %101, %102, %103, %104, %105, %106, %107, %108, %109, %110, %111, %112, %113, %114, %115, %116, %117, %118, %119, %120, %121, %122, %123, %124, %125, %126, %127}, "
    "%128, %129, 1, 1, 1, 0, 1;\n"
    : "+f"(d[0]), "+f"(d[1]), "+f"(d[2]), "+f"(d[3]), "+f"(d[4]), "+f"(d[5]), "+f"(d[6]), "+f"(d[7]), "+f"(d[8]), "+f"(d[9]), "+f"(d[10]), "+f"(d[11]), "+f"(d[12]), "+f"(d[13]), "+f"(d[14]), "+f"(d[15]), "+f"(d[16]), "+f"(d[17]), "+f"(d[18]), "+f"(d[19]), "+f"(d[20]), "+f"(d[21]), "+f"(d[22]), "+f"(d[23]), "+f"(d[24]), "+f"(d[25]), "+f"(d[26]), "+f"(d[27]), "+f"(d[28]), "+f"(d[29]), "+f"(d[30]), "+f"(d[31]), "+f"(d[32]), "+f"(d[33]), "+f"(d[34]), "+f"(d[35]), "+f"(d[36]), "+f"(d[37]), "+f"(d[38]), "+f"(d[39]), "+f"(d[40]), "+f"(d[41]), "+f"(d[42]), "+f"(d[43]), "+f"(d[44]), "+f"(d[45]), "+f"(d[46]), "+f"(d[47]), "+f"(d[48]), "+f"(d[49]), "+f"(d[50]), "+f"(d[51]), "+f"(d[52]), "+f"(d[53]), "+f"(d[54]), "+f"(d[55]), "+f"(d[56]), "+f"(d[57]), "+f"(d[58]), "+f"(d[59]), "+f"(d[60]), "+f"(d[61]), "+f"(d[62]), "+f"(d[63]), "+f"(d[64]), "+f"(d[65]), "+f"(d[66]), "+f"(d[67]), "+f"(d[68]), "+f"(d[69]), "+f"(d[70]), "+f"(d[71]), "+f"(d[72]), "+f"(d[73]), "+f"(d[74]), "+f"(d[75]), "+f"(d[76]), "+f"(d[77]), "+f"(d[78]), "+f"(d[79]), "+f"(d[80]), "+f"(d[81]), "+f"(d[82]), "+f"(d[83]), "+f"(d[84]), "+f"(d[85]), "+f"(d[86]), "+f"(d[87]), "+f"(d[88]), "+f"(d[89]), "+f"(d[90]), "+f"(d[91]), "+f"(d[92]), "+f"(d[93]), "+f"(d[94]), "+f"(d[95]), "+f"(d[96]), "+f"(d[97]), "+f"(d[98]), "+f"(d[99]), "+f"(d[100]), "+f"(d[101]), "+f"(d[102]), "+f"(d[103]), "+f"(d[104]), "+f"(d[105]), "+f"(d[106]), "+f"(d[107]), "+f"(d[108]), "+f"(d[109]), "+f"(d[110]), "+f"(d[111]), "+f"(d[112]), "+f"(d[113]), "+f"(d[114]), "+f"(d[115]), "+f"(d[116]), "+f"(d[117]), "+f"(d[118]), "+f"(d[119]), "+f"(d[120]), "+f"(d[121]), "+f"(d[122]), "+f"(d[123]), "+f"(d[124]), "+f"(d[125]), "+f"(d[126]), "+f"(d[127])
    : "l"(da), "l"(db));
}
__device__ __forceinline__ void wgmma_n256_first(float (&d)[128], uint64_t da, uint64_t db) {
  asm volatile("wgmma.mma_async.sync.aligned.m64n256k16.f32.bf16.bf16 "
    "{%0, %1, %2, %3, %4, %5, %6, %7, %8, %9, %10, %11, %12, %13, %14, %15, %16, %17, %18, %19, %20, %21, %22, %23, %24, %25, %26, %27, %28, %29, %30, %31, %32, %33, %34, %35, %36, %37, %38, %39, %40, %41, %42, %43, %44, %45, %46, %47, %48, %49, %50, %51, %52, %53, %54, %55, %56, %57, %58, %59, %60, %61, %62, %63, %64, %65, %66, %67, %68, %69, %70, %71, %72, %73, %74, %75, %76, %77, %78, %79, %80, %81, %82, %83, %84, %85, %86, %87, %88, %89, %90, %91, %92, %93, %94, %95, %96, %97, %98, %99, %100, %101, %102, %103, %104, %105, %106, %107, %108, %109, %110, %111, %112, %113, %114, %115, %116, %117, %118, %119, %120, %121, %122, %123, %124, %125, %126, %127}, "
    "%128, %129, 0, 1, 1, 0, 1;\n"
    : "=f"(d[0]), "=f"(d[1]), "=f"(d[2]), "=f"(d[3]), "=f"(d[4]), "=f"(d[5]), "=f"(d[6]), "=f"(d[7]), "=f"(d[8]), "=f"(d[9]), "=f"(d[10]), "=f"(d[11]), "=f"(d[12]), "=f"(d[13]), "=f"(d[14]), "=f"(d[15]), "=f"(d[16]), "=f"(d[17]), "=f"(d[18]), "=f"(d[19]), "=f"(d[20]), "=f"(d[21]), "=f"(d[22]), "=f"(d[23]), "=f"(d[24]), "=f"(d[25]), "=f"(d[26]), "=f"(d[27]), "=f"(d[28]), "=f"(d[29]), "=f"(d[30]), "=f"(d[31]), "=f"(d[32]), "=f"(d[33]), "=f"(d[34]), "=f"(d[35]), "=f"(d[36]), "=f"(d[37]), "=f"(d[38]), "=f"(d[39]), "=f"(d[40]), "=f"(d[41]), "=f"(d[42]), "=f"(d[43]), "=f"(d[44]), "=f"(d[45]), "=f"(d[46]), "=f"(d[47]), "=f"(d[48]), "=f"(d[49]), "=f"(d[50]), "=f"(d[51]), "=f"(d[52]), "=f"(d[53]), "=f"(d[54]), "=f"(d[55]), "=f"(d[56]), "=f"(d[57]), "=f"(d[58]), "=f"(d[59]), "=f"(d[60]), "=f"(d[61]), "=f"(d[62]), "=f"(d[63]), "=f"(d[64]), "=f"(d[65]), "=f"(d[66]), "=f"(d[67]), "=f"(d[68]), "=f"(d[69]), "=f"(d[70]), "=f"(d[71]), "=f"(d[72]), "=f"(d[73]), "=f"(d[74]), "=f"(d[75]), "=f"(d[76]), "=f"(d[77]), "=f"(d[78]), "=f"(d[79]), "=f"(d[80]), "=f"(d[81]), "=f"(d[82]), "=f"(d[83]), "=f"(d[84]), "=f"(d[85]), "=f"(d[86]), "=f"(d[87]), "=f"(d[88]), "=f"(d[89]), "=f"(d[90]), "=f"(d[91]), "=f"(d[92]), "=f"(d[93]), "=f"(d[94]), "=f"(d[95]), "=f"(d[96]), "=f"(d[97]), "=f"(d[98]), "=f"(d[99]), "=f"(d[100]), "=f"(d[101]), "=f"(d[102]), "=f"(d[103]), "=f"(d[104]), "=f"(d[105]), "=f"(d[106]), "=f"(d[107]), "=f"(d[108]), "=f"(d[109]), "=f"(d[110]), "=f"(d[111]), "=f"(d[112]), "=f"(d[113]), "=f"(d[114]), "=f"(d[115]), "=f"(d[116]), "=f"(d[117]), "=f"(d[118]), "=f"(d[119]), "=f"(d[120]), "=f"(d[121]), "=f"(d[122]), "=f"(d[123]), "=f"(d[124]), "=f"(d[125]), "=f"(d[126]), "=f"(d[127])
    : "l"(da), "l"(db));
}

template <int N> struct WG;
#define DEF_WG(N) template <> struct WG<N> { \
  static __device__ __forceinline__ void mma(float (&d)[N / 2], uint64_t a, uint64_t b) { wgmma_n##N(d, a, b); } \
  static __device__ __forceinline__ void first(float (&d)[N / 2], uint64_t a, uint64_t b) { wgmma_n##N##_first(d, a, b); } };
DEF_WG(128) DEF_WG(256)

constexpr uint64_t DESC_A = (1ull << 62) | ((uint64_t)(1024 >> 4) << 32) | (1ull << 16);
constexpr uint64_t DESC_B = (1ull << 62) | ((uint64_t)(1024 >> 4) << 32) | ((uint64_t)(8192 >> 4) << 16);

struct Ring { int s; uint32_t ph; int wrap; };
template <int NS> __device__ __forceinline__ void ring_next(Ring& r) { r.s = (r.s + 1 == NS) ? 0 : r.s + 1; if (r.s == r.wrap) r.ph ^= 1; }

__device__ __forceinline__ int own_order(int it, int j) {
  return it < 2 ? 2 * j + it : it < 4 ? 2 * (j ^ 1) + it - 2 : ((j >> 1) * 4 + 2 * it - (it < 10 ? 4 : 15)) & 15;
}

template <int V> struct IC { static constexpr int v = V; };
template <int I, int E, class F> __device__ __forceinline__ void static_for(F&& f) { if constexpr (I < E) { f(IC<I>{}); static_for<I + 1, E>(f); } }

template <int N, int NS, int PRE, int LAG, class Pre, class Mid, class Last>
__device__ __forceinline__ void mainloop(float (&acc)[N / 2], int nkb, bool own, Ring& r, uint32_t sb, int wg, int lane, uint32_t rel_base, Pre pre, Mid mid, Last last) {
  constexpr int SLOT = RING / NS;
  const uint32_t full = sb + MISC + (NS == 4 ? B_FULL4 : B_FULL6);
  const uint32_t rel = rel_base + (NS == 4 ? B_EMPTY4 : B_EMPTY6);
  const uint32_t s0 = (sb & 0x3FFFF) >> 4, a0 = s0 + wg * (HALF >> 4);
  int ps;
  auto issue = [&](int it, bool first) {
    const uint64_t da = DESC_A | (a0 + ((own && it < 2) ? (STG + it * BLK) >> 4 : r.s * (SLOT >> 4))), db = DESC_B | (s0 + r.s * (SLOT >> 4) + (BLK >> 4));
    mbar_wait(full + r.s * 8, r.ph);
    wg_arrive();
    if (first) WG<N>::first(acc, da, db); else WG<N>::mma(acc, da, db);
#pragma unroll
    for (int k = 1; k < 4; k++) WG<N>::mma(acc, da + k * 2, db + k * 128);
    wg_commit();
  };
  auto retire = [&](int it) {
    wg_wait<1>();
    if (lane < 2) mbar_arrive_cl(rel + ps * 8);
    ps = r.s;
    ring_next<NS>(r);
  };
  issue(0, true);
  ps = r.s;
  ring_next<NS>(r);
  static_for<1, PRE + 1>([&](auto ic) { issue(ic.v, false); pre(ic); retire(ic.v); });
#pragma unroll 1
  for (int it = PRE + 1; it < nkb; it++) {
    if (LAG && it == nkb - LAG && wg == 1) mbar_wait(sb + MISC + B_LAG, WOLAG && !own);
    issue(it, false); mid(it); retire(it);
  }
  last();
  wg_wait<0>();
  if (lane < 2) mbar_arrive_cl(rel + ps * 8);
}

__device__ __forceinline__ uint32_t tag_of(uint32_t ep) { return (ep & 127u) + 1u; }
__device__ __forceinline__ void ln_publish(const float (&v)[64], uint2* st, int j, int row0, int lane, uint32_t ep) {
  float s0 = 0, s1 = 0, s2 = 0, s3 = 0, q0 = 0, q1 = 0, q2 = 0, q3 = 0;
#pragma unroll
  for (int i = 0; i < 16; i++) {
    s0 += v[4 * i]; s1 += v[4 * i + 1]; s2 += v[4 * i + 2]; s3 += v[4 * i + 3];
    q0 = fmaf(v[4 * i], v[4 * i], q0); q1 = fmaf(v[4 * i + 1], v[4 * i + 1], q1); q2 = fmaf(v[4 * i + 2], v[4 * i + 2], q2); q3 = fmaf(v[4 * i + 3], v[4 * i + 3], q3);
  }
  s0 += s1; s2 += s3; q0 += q1; q2 += q3;
  const bool odd = lane & 1;
  float s = (odd ? s2 : s0) + __shfl_xor_sync(~0u, odd ? s0 : s2, 1), q = (odd ? q2 : q0) + __shfl_xor_sync(~0u, odd ? q0 : q2, 1);
  s += __shfl_xor_sync(~0u, s, 2); q += __shfl_xor_sync(~0u, q, 2);
  if ((lane & 3) < 2) st_rlx2(st + j * 128 + row0 + (lane & 1) * 8, __float_as_uint(s), (__float_as_uint(fmaf(s * (-1.f / 128), s, q)) & ~255u) | tag_of(ep));
}
__device__ __forceinline__ void ln_gather(const uint2* st, int row0, int lane, uint32_t ep, float& n0, float& r0, float& n1, float& r1, bool rnd) {
  const uint2* p = st + (lane & 2) * 256 + row0 + (lane & 1) * 8;
  const uint32_t tag = tag_of(ep);
  uint2 a, b, c, d; uint32_t n = 0;
  while (true) {
    a = ld_rlx2(p); b = ld_rlx2(p + 128); c = ld_rlx2(p + 256); d = ld_rlx2(p + 384);
    if ((((a.y ^ tag) | (b.y ^ tag) | (c.y ^ tag) | (d.y ^ tag)) & 255u) == 0) break;
    SPIN_GUARD(n);
  }
  __syncwarp();
  const uint32_t fix = tag ^ 128u;
  float s = (__uint_as_float(a.x) + __uint_as_float(b.x)) + (__uint_as_float(c.x) + __uint_as_float(d.x));
  float q = (__uint_as_float(a.y ^ fix) + __uint_as_float(b.y ^ fix)) + (__uint_as_float(c.y ^ fix) + __uint_as_float(d.y ^ fix));
  q = fmaf(fmaf(__uint_as_float(a.x), __uint_as_float(a.x), __uint_as_float(b.x) * __uint_as_float(b.x)) +
           fmaf(__uint_as_float(c.x), __uint_as_float(c.x), __uint_as_float(d.x) * __uint_as_float(d.x)), 1.f / 128, q);
  s += __shfl_xor_sync(~0u, s, 2); q += __shfl_xor_sync(~0u, q, 2);
  s *= 1.f / 1024;
  const float var = fmaxf(fmaf(-s, s, q * (1.f / 1024)), 0.f);
  float r;
  if (rnd) {
    float sd; asm("sqrt.approx.f32 %0, %1;" : "=f"(sd) : "f"(bf_round(bf_round(var) + 1e-5f)));
    r = rcp(bf_round(sd)); s = bf_round(s);
  } else r = rsqrtf(var + 1e-5f);
  const float nn = -s * r;
  const float ro = __shfl_xor_sync(~0u, r, 1), no = __shfl_xor_sync(~0u, nn, 1);
  const bool odd = lane & 1;
  r0 = odd ? ro : r; n0 = odd ? no : nn; r1 = odd ? r : ro; n1 = odd ? nn : no;
}
__device__ __forceinline__ void load_vec(uint32_t* w, uint32_t sb, int sec, int b, int lane) {
#pragma unroll
  for (int q = 0; q < 2; q++) { uint4 t = lds128(sb + MISC + MODV + sec * 256 + (lane & 3) * 64 + b * 32 + q * 16); w[4 * q] = t.x; w[4 * q + 1] = t.y; w[4 * q + 2] = t.z; w[4 * q + 3] = t.w; }
}
__device__ __forceinline__ void stage_done(uint32_t sb, int wg, int b, int lane) {
  fence_async_smem();
  __syncwarp();
  if (lane == 0) mbar_arrive(sb + MISC + B_RDY + b * 8);
}
__device__ __forceinline__ uint32_t hfma2(uint32_t a, uint32_t b, uint32_t c) { uint32_t r; asm("fma.rn.bf16x2 %0, %1, %2, %3;" : "=r"(r) : "r"(a), "r"(b), "r"(c)); return r; }
__device__ __forceinline__ void ln_apply(const float (&v)[64], const uint2* st, int row0, uint32_t ep, uint32_t sb, int sec_shift, int sec_scale, uint32_t stg_row, int wg, int lane) {
  uint32_t sc[16], sh[16];
#pragma unroll
  for (int b = 0; b < 2; b++) { load_vec(sc + 8 * b, sb, sec_scale, b, lane); load_vec(sh + 8 * b, sb, sec_shift, b, lane); }
  float n0, r0, n1, r1;
  ln_gather(st, row0, lane, ep, n0, r0, n1, r1, sec_shift == 0);
#pragma unroll
  for (int i = 0; i < 16; i += 2) {
    if (i == 8) { const float z = lds32f(sb + MISC + ZERO); n0 += z; n1 += z; }
    uint32_t w[4];
#pragma unroll
    for (int u = 0; u < 2; u++) {
      int q = i + u;
      w[2 * u] = hfma2(pack2(fmaf(v[4 * q], r0, n0), fmaf(v[4 * q + 1], r0, n0)), sc[q], sh[q]);
      w[2 * u + 1] = hfma2(pack2(fmaf(v[4 * q + 2], r1, n1), fmaf(v[4 * q + 3], r1, n1)), sc[q], sh[q]);
    }
    stsm4(stg_row + (i >> 3) * BLK + ((((i & 7) + (lane >> 4)) ^ (lane & 7)) << 4), w[0], w[1], w[2], w[3]);
    if ((i & 7) == 6) { stage_done(sb, wg, i >> 3, lane); }
  }
}
__device__ __forceinline__ uint32_t hmul2(uint32_t a, uint32_t b) { uint32_t r; asm("mul.rn.bf16x2 %0, %1, %2;" : "=r"(r) : "r"(a), "r"(b)); return r; }
__device__ __forceinline__ uint32_t silu_mul2(uint32_t g, uint32_t u) {
  const uint32_t h = hmul2(g, 0x3f003f00u);
  const float h0 = bf_lo(h), h1 = bf_hi(h);
  return hmul2(pack2(fmaf(h0, tanh_fast(h0), h0), fmaf(h1, tanh_fast(h1), h1)), u);
}

__device__ __forceinline__ void gemv_fma(float (&a)[8], uint4 w, float s) {
  a[0] = fmaf(bf_lo(w.x), s, a[0]); a[1] = fmaf(bf_hi(w.x), s, a[1]); a[2] = fmaf(bf_lo(w.y), s, a[2]); a[3] = fmaf(bf_hi(w.y), s, a[3]);
  a[4] = fmaf(bf_lo(w.z), s, a[4]); a[5] = fmaf(bf_hi(w.z), s, a[5]); a[6] = fmaf(bf_lo(w.w), s, a[6]); a[7] = fmaf(bf_hi(w.w), s, a[7]);
}
__device__ __forceinline__ float silu_c(float v) { return bf_round(__fdividef(v, 1.f + __expf(-v))); }
__device__ __forceinline__ float mod_gather(const uint32_t* p, uint32_t ep) {
  const uint32_t tag = tag_of(ep), fix = tag ^ 128u;
  uint32_t a, b, c, d, n = 0;
  while (true) {
    a = ld_rlx1(p); b = ld_rlx1(p + 128); c = ld_rlx1(p + 256); d = ld_rlx1(p + 384);
    if ((((a ^ tag) | (b ^ tag) | (c ^ tag) | (d ^ tag)) & 255u) == 0) break;
    SPIN_GUARD(n);
  }
  return (__uint_as_float(a ^ fix) + __uint_as_float(b ^ fix)) + (__uint_as_float(c ^ fix) + __uint_as_float(d ^ fix));
}
__device__ __forceinline__ void mod_store(uint32_t sb, int sec, int col, float v) {
  v = bf_round(v);
  if (sec == 1) v += 1.f;
  sts16(sb + MISC + MODV + sec * 256 + (((col >> 1) & 3) * 16 + (col >> 3)) * 4 + (col & 1) * 2, __float2bfloat16_rn(v));
}

__global__ void __cluster_dims__(2, 1, 1) __launch_bounds__(384, 1)
fused_kernel(const bf16* __restrict__ cvec, const bf16* __restrict__ wmod, Scratch* gs, int by_sm, const __grid_constant__ Maps maps) {
  extern __shared__ __align__(1024) uint8_t smem_raw[];
  const uint32_t sb = smem_u32(smem_raw);
  const int warp = __shfl_sync(~0u, threadIdx.x >> 5, 0), lane = threadIdx.x & 31;
  const int rank = blockIdx.x & 1;
  uint32_t sm; asm volatile("mov.u32 %0, %%smid;" : "=r"(sm));
  const int t = sm >> 1, v = t < 32 ? t : t < 60 ? t + 1 + (((t - 32) * 37) >> 8) : (t - 58) * 8;
  const int cid = !by_sm ? (blockIdx.x >> 1) - 2 : (t & ~1) == 60 ? t - 62 : (v & 1) * 32 + ((v >> 1) & 31);
  const bool extra = cid < 0;
  const int bid = cid * 2 + rank;
  const int m = cid >> 2, j = (cid & 3) * 2 + rank;
  const uint32_t bar = sb + MISC;

  if (warp >= 8) {
    asm volatile("setmaxnreg.dec.sync.aligned.u32 40;");
    if (extra) {
      if (warp == 8) {
        if (lane == 0) { for (int s = 0; s < 6; s++) { mbar_init(bar + B_FULL6 + s * 8, 1); mbar_init(bar + B_EMPTY6 + s * 8, 8); } fence_async_smem(); }
        __syncwarp();
        asm volatile("bar.arrive 2, 288;" ::: "memory");
        __nanosleep(XSLEEP);
#pragma unroll 1
        for (int it = 0, s = 0, par = 1; it < 64; it++) {
          mbar_wait(bar + B_EMPTY6 + s * 8, par);
          if (elect()) { mbar_expect_tx(bar + B_FULL6 + s * 8, 32768); tma_3d(sb + s * 32768, &maps.wmod, bar + B_FULL6 + s * 8, 0, (it & 15) * 64, 12 + (it >> 4) * 4 + bid); }
          if (++s == 6) { s = 0; par ^= 1; }
        }
      }
    } else if (warp < 10) {
      uint32_t s6 = 0, p6 = 1;
      auto next6 = [&]() { if (++s6 == 6) { s6 = 0; p6 ^= 1; } };
      auto drained4 = [&](int q, int late) { if (q < 5) mbar_wait(bar + B_EMPTY4 + (((late ? 0x10332 : 0x32110) >> (4 * q)) & 3) * 8, 1); };
      auto drained6 = [&](int q) { if (q < 3) mbar_wait(bar + B_EMPTY6 + ((0x154 >> (4 * q)) & 7) * 8, q >> 1); };
      auto skip6 = [&]() { mbar_wait(bar + B_EMPTY6 + s6 * 8, p6); if (elect()) mbar_arrive(bar + B_FULL6 + s6 * 8); next6(); };
      if (warp == 8) {
        const uint32_t t_start = clock();
        if (lane == 0) {
          if (sb & 1023) bail();
          for (int b = 0; b < 2; b++) mbar_init(bar + B_X + b * 8, 1);
          for (int s = 0; s < 4; s++) { mbar_init(bar + B_FULL4 + s * 8, 2); mbar_init(bar + B_EMPTY4 + s * 8, 16); }
          for (int s = 0; s < 6; s++) { mbar_init(bar + B_FULL6 + s * 8, 2); mbar_init(bar + B_EMPTY6 + s * 8, 16); }
          for (int b = 0; b < 2; b++) { mbar_init(bar + B_RDY + b * 8, 8); mbar_init(bar + B_FREE + b * 8, 1); mbar_init(bar + B_HH + b * 8, 1); }
          mbar_init(bar + B_MOD, 1); mbar_init(bar + B_LAG, 4); mbar_init(bar + B_HALO, 2); mbar_init(bar + B_ALL, 1); mbar_init(bar + B_HH2, 1);
          asm volatile("st.shared.u32 [%0], 0;" :: "r"(bar + ZERO) : "memory");
          asm volatile("fence.mbarrier_init.release.cluster;" ::: "memory");
          fence_async_smem();
        }
        __syncwarp();
        cl_arrive_relaxed();
        auto wide = [&](int s, int par, const CUtensorMap* m0, int a0, const CUtensorMap* m1, int a1, int kb, bool spaced) {
          const uint32_t full = bar + B_FULL4 + s * 8, d = sb + s * 49152 + BLK;
          mbar_wait(full + 32, par);
          const uint32_t t0 = clock();
          if (elect()) { mbar_expect_tx(full, 2 * BLK); tma_3d(d, m0, full, 0, kb * 64, a0); }
          if (spaced) while ((uint32_t)clock() - t0 < 300) {}
          if (elect()) tma_3d(d + BLK, m1, full, 0, kb * 64, a1);
          if (spaced) while ((uint32_t)clock() - t0 < 600) {}
        };
        while ((uint32_t)clock() - t_start < XDELAY) {}
        if (elect()) for (int b = 0; b < 2; b++) { mbar_expect_tx(bar + B_X + b * 8, BLK); tma_3d(sb + STG + b * BLK, &maps.x, bar + B_X + b * 8, j * 128 + b * 64, m * 64, 0); }
        mbar_wait(bar + B_X + 8, 0);
#pragma unroll 1
        for (int ph = 0; ph < 2; ph++) {
          const CUtensorMap* const m0 = ph ? &maps.w1 : &maps.wqkv;
#pragma unroll 1
          for (int it = 0; it < (ph ? 48 : 16); it++) {
            const int a = (ph ? it & 48 : 16) + 2 * j;
            if (ph) drained6(it);
            wide((it + 2 * ph) & 3, ~(it >> 2) & 1, m0, a, m0 + ph, ph ? a : a + 16, it < 16 ? own_order(it, j) : it & 15, it < 4);
            if (it >= 44) {
              if (it == 44) { mbar_wait(bar + B_FREE, 0); mbar_wait(bar + B_FREE + 8, 0); if (elect()) mbar_expect_tx(bar + B_X, 2 * BLK); }
              if (elect()) bulk_ld(sb + STG + (it - 44) * HALF, gs->x1 + bid * 2048 + (it - 44) * 512, HALF, bar + B_X);
            }
          }
#pragma unroll 1
          for (int it = 0; it < 16; it++) {
            const uint32_t full = bar + B_FULL6 + s6 * 8, d = sb + s6 * 32768 + BLK;
            drained4(it, ph);
            mbar_wait(full + 48, p6);
            if (elect()) {
              mbar_expect_tx(full, BLK);
              tma_3d(d, ph ? &maps.w1s : &maps.wqkv, full, 0, it * 64, ph ? 48 + j : 2 * j);
              if (ph) tma_3d(d + HALF, &maps.w3s, full, 0, it * 64, 48 + j);
            }
            next6();
          }
          const CUtensorMap* const m2 = ph ? &maps.w2 : &maps.wo;
#pragma unroll 1
          for (int it = 0; it < (ph ? 56 : 16); it++) {
            const uint32_t full = bar + B_FULL6 + s6 * 8;
            const int kb = ph ? it : own_order(it, j);
            mbar_wait(full + 48, p6);
            if (elect()) { mbar_expect_tx(full, BLK); tma_3d(sb + s6 * 32768 + BLK, m2, full, 0, kb * 64, 2 * j); }
            next6();
          }
          if (!ph) skip6();
        }
      } else {
        if (lane < 9) prefetch_map(&maps.x + lane);
        const uint32_t ep = gs->epoch[bid + 4] + 1;
        cl_arrive_relaxed(); cl_wait();
        auto plain = [&](uint32_t full, uint32_t empty, int par, uint32_t slot, const uint4* blk) {
          mbar_wait(empty, par);
          if (elect()) { mbar_expect_tx(full, BLK); bulk_ld_mc(slot + rank * HALF, blk + rank * 512, HALF, full); }
        };
        auto plain6 = [&](const uint4* blk) { plain(bar + B_FULL6 + s6 * 8, bar + B_EMPTY6 + s6 * 8, p6, sb + s6 * 32768, blk); next6(); };
        uint32_t ready = 0;
        auto poll = [&](int e) { ready = __ballot_sync(~0u, ld_acquire(gs->flag + (m * 128 + e * 16 + (lane & 14)) * FS) == ep); };
        auto need = [&](int e, uint32_t mask) {
          if ((ready & mask) != mask) {
            uint32_t n = 0;
            do { poll(e); SPIN_GUARD(n); } while ((ready & mask) != mask);
            fence_async_global();
          }
        };
        auto fresh = [&](int e, int it, uint32_t full, uint32_t empty, int par, uint32_t slot, uint4* src) {
          if (it >= 4) {
            const int kb = own_order(it, j);
            if (it < 10) need(e, 1u << kb); else if (it == 10) mbar_wait(bar + B_ALL, e & 1);
            plain(full, empty, par, slot, src + kb * 1024);
          } else {
            if (it == 0) ready = 0;
            mbar_wait(empty, par);
            if (it < 2) { if (elect()) mbar_arrive(full); }
            else {
              const int b = it > 2;
              const uint32_t to_peer = mapa(sb, rank ^ 1) - sb;
              if (elect()) mbar_expect_tx(full, BLK);
              const bool push = e != 1;
              mbar_wait(bar + (b ? (push ? B_RDY + 8 : B_FREE + 8) : B_RDY), e & 1);
              if (elect()) {
                if (b == 0) {
                  bulk_st(src + 2 * j * 1024, sb + STG, BLK);
                  bulk_commit();
                  bulk_wait_all();
                  mbar_arrive(bar + B_FREE);
                }
                if (b && push) bulk_push(slot + to_peer, sb + STG + BLK, BLK, full + to_peer);
                else {
                  fence_async_global();
                  bulk_ld(slot + to_peer, src + (2 * j + b) * 1024, BLK, full + to_peer);
                }
              }
              __syncwarp();
            }
          }
        };
        uint4* const h = gs->h + m * 16384;
#pragma unroll 1
        for (int e = 0; e < 3; e++) {
#pragma unroll 1
          for (int it = 0; it < 16; it++) {
            const int s = e == 1 ? s6 : (it + e) & 3;
            const uint32_t full = bar + (e == 1 ? B_FULL6 : B_FULL4) + s * 8;
            if (e == 2) drained6(it);
            fresh(e, it, full, full + (e == 1 ? 48 : 32), e == 1 ? p6 : ~(it >> 2) & 1, sb + s * (e == 1 ? 32768 : 49152), e == 1 ? gs->o + m * 16384 : h);
            if (e == 1) next6();
          }
          if (e == 1) { skip6(); continue; }
#pragma unroll 1
          for (int it = 16; it < 16 + 16 * e; it++) {
            const int s = (it + 2) & 3;
            const uint32_t full = bar + B_FULL4 + s * 8;
            plain(full, full + 32, ~(it >> 2) & 1, sb + s * 49152, h + (it & 15) * 1024);
          }
#pragma unroll 1
          for (int it = 0; it < 16; it++) { drained4(it, e); plain6(h + it * 1024); }
        }
#pragma unroll 1
        for (int it = 0; it < 56; it++) {
          if (it == 0 || it == 32 || it == 48) mbar_wait(bar + (it == 48 ? B_HH2 : B_HH + (it >> 2)), 0);
          plain6(gs->hh + m * 57344 + it * 1024);
        }
      }
    } else {
      const int b = warp - 10;
      const uint32_t ep = gs->epoch[bid + 4] + 1;
      const uint32_t stg = sb + STG + b * BLK;
      cl_arrive_relaxed(); cl_wait();
      auto all_there = [&](int u, uint32_t done) {
        const uint32_t* fl = gs->flag + u * FS;
        uint32_t n = 0;
        while (!__all_sync(~0u, ld_acquire(fl) == ep)) { __nanosleep(100); SPIN_GUARD(n); }
        fence_async_global();
        if (lane == 0) mbar_arrive(done);
      };
      auto fetch_mod = [&](int sec) {
        const uint4* p = (const uint4*)(gs->modv + (sec - 2) * 1024 + j * 128) + lane;
        uint4 v0, v1; uint32_t n = 0;
        while (true) {
          v0 = ld_rlx4(p); v1 = ld_rlx4(p + 32);
          if (v0.y == ep && v0.w == ep && v1.y == ep && v1.w == ep) break;
          SPIN_GUARD(n);
        }
        const uint32_t d = sb + MISC + MODV + sec * 256 + ((lane & 3) * 16 + (lane >> 2)) * 4;
        asm volatile("st.shared.u32 [%0], %1;" :: "r"(d), "r"(__byte_perm(v0.x, v0.z, 0x7632)) : "memory");
        asm volatile("st.shared.u32 [%0], %1;" :: "r"(d + 32), "r"(__byte_perm(v1.x, v1.z, 0x7632)) : "memory");
        __syncwarp();
      };
#pragma unroll 1
      for (int e = 0; e < 7 - b; e++) {
        if (lane == 0) {
          if (e < 3) {
            mbar_wait(bar + B_FREE, e & 1);
            if (b) {
              const uint32_t t0 = clock();
              while ((uint32_t)clock() - t0 < (e == 0 ? B1P : e == 2 ? B1P2 : B1D)) {}
              mbar_wait(bar + B_RDY + 8, e & 1);
              bulk_st((e == 1 ? gs->o : gs->h) + m * 16384 + (2 * j + 1) * 1024, stg, BLK);
              bulk_commit();
              bulk_wait_all();
              mbar_arrive(bar + B_FREE + 8);
            }
            st_release(gs->flag + (m * 128 + e * 16 + 2 * j + b) * FS, ep);
          } else {
            const int kb = (e < 6 ? 2 * (8 * (e - 3) + j) : 48 + j) + b;
            mbar_wait(bar + B_RDY + b * 8, e & 1);
#pragma unroll 1
            for (int q = 0; q < NPIECE; q++) { if (q) __nanosleep(PSLEEP); bulk_st(gs->hh + m * 57344 + kb * 1024 + q * (1024 / NPIECE), stg + q * (BLK / NPIECE), BLK / NPIECE); }
            bulk_commit();
            bulk_wait_all();
            mbar_arrive(bar + B_FREE + b * 8);
            st_release(gs->flag + (m * 128 + U_HH + kb) * FS, ep);
          }
        }
        __syncwarp();
        if (e < 3 && b) all_there(m * 128 + e * 16 + (lane & 15), bar + B_ALL);
        if (e == 4 && b) all_there(m * 128 + U_HH + lane, bar + B_HH);
        if (!b && (e == 1 || e == 2)) {
#pragma unroll 1
          for (int sec = e == 1 ? 2 : 5; sec < 4 + e; sec++) fetch_mod(sec);
          if (e == 1) { if (lane == 0) mbar_arrive(bar + B_MOD); }
        }
        if (e == 0) {
          mbar_wait(bar + B_EMPTY6 + 24, 0);
          __nanosleep(HSLEEP);
#pragma unroll 1
          for (int w = 0; w < 4; w++) {
            const uint4* hp = gs->halo + ((m * 8 + j) * 2 + (w & 1)) * 512 + b * 256 + (w >> 1) * 128 + lane;
            uint4 q[4] = {}; uint32_t n = 0;
            while (m > 0) {
              bool ok = true;
#pragma unroll
              for (int i = 0; i < 4; i++) q[i] = ld_rlx4(hp + i * 32);
#pragma unroll
              for (int i = 0; i < 4; i++) ok = ok && q[i].y == ep && q[i].w == ep;
              if (ok) break;
              SPIN_GUARD(n);
            }
#pragma unroll
            for (int i = 0; i < 2; i++) sts128(stg + lane * 16 + (w & 1) * HALF + (w >> 1) * 1024 + i * 512, q[2 * i].x, q[2 * i + 1].x, q[2 * i].z, q[2 * i + 1].z);
          }
          __syncwarp();
          if (lane == 0) mbar_arrive(bar + B_HALO);
        }
      }
      if (b) { all_there(m * 128 + U_HH + 32 + (lane & 15), bar + B_HH + 8); all_there(m * 128 + U_HH + 48 + (lane & 7), bar + B_HH2); }
    }
  } else {
    const int wg = warp >> 2, wq = warp & 3, tid = threadIdx.x;
    const int g = lane >> 2, c = lane & 3;
    const int sec0 = (m >> 1) & 1, hf0 = m & 1, ks0 = (m >> 2) & 3;
    uint4 wv[8];
    uint32_t ep0; uint16_t cv_;
    asm volatile("ld.global.nc.u16 %0, [%1];" : "=h"(cv_) : "l"(cvec + ks0 * 256 + warp * 32 + lane));
    asm volatile("ld.global.u32 %0, [%1];" : "=r"(ep0) : "l"(gs->epoch + bid + 4));
    if (!extra) {
      const bf16* wp = wmod + (size_t)(ks0 * 256 + warp * 32 + (lane >> 3)) * 6144 + sec0 * 1024 + j * 128 + hf0 * 64 + (lane & 7) * 8;
#pragma unroll
      for (int i = 0; i < 8; i++) wv[i] = ldg_nc(wp + (size_t)i * 4 * 6144);
    }
    asm volatile("setmaxnreg.inc.sync.aligned.u32 232;" ::: "memory");
    if (__builtin_expect(extra, 0)) {
      const uint32_t ep = ep0 + 1;
      float sv[4];
#pragma unroll
      for (int p = 0; p < 4; p++) sv[p] = silu_c(__bfloat162float(cvec[64 * (4 * p + (lane >> 3)) + 8 * warp + (lane & 7)]));
      named_bar(2, 288);
      int s = 0, par = 0;
#pragma unroll 1
      for (int sec = 0; sec < 4; sec++) {
        float a[8] = {0, 0, 0, 0, 0, 0, 0, 0};
#pragma unroll 1
        for (int it = 0; it < 16; it++) {
          const float sc = it < 4 ? sv[0] : it < 8 ? sv[1] : it < 12 ? sv[2] : sv[3];
          mbar_wait(bar + B_FULL6 + s * 8, par);
          uint4 w[8];
#pragma unroll
          for (int i = 0; i < 8; i++) w[i] = lds128(sb + s * 32768 + (warp * 8 + i) * 512 + lane * 16);
#pragma unroll
          for (int i = 0; i < 8; i++) gemv_fma(a, w[i], __shfl_sync(~0u, sc, (it & 3) * 8 + i));
          if (lane == 0) mbar_arrive(bar + B_EMPTY6 + s * 8);
          if (++s == 6) { s = 0; par ^= 1; }
        }
        const uint32_t red = sb + STG + sec * 8192;
        sts128(red + warp * 1024 + lane * 32, __float_as_uint(a[0]), __float_as_uint(a[1]), __float_as_uint(a[2]), __float_as_uint(a[3]));
        sts128(red + warp * 1024 + lane * 32 + 16, __float_as_uint(a[4]), __float_as_uint(a[5]), __float_as_uint(a[6]), __float_as_uint(a[7]));
        named_bar(1, 256);
        float t = 0;
#pragma unroll
        for (int q = 0; q < 8; q++) t += lds32f(red + q * 1024 + tid * 4);
        t = bf_round(t);
        if (sec == 2) t = bf_round(t + 1.f);
        st_rlx2(gs->modv + sec * 1024 + (bid + 4) * 256 + tid, __float_as_uint(t), ep);
      }
      if (tid == 0) gs->epoch[bid + 4] = ep;
      return;
    }
    const int row0 = wg * 64 + wq * 16 + g;
    if (c < 2) st_rlx2(gs->stat + m * 1024 + j * 128 + row0 + c * 8, 0, 0);
    if (tid < 64) st_rlx1(gs->modp + ((j * 2 + sec0) * 4 + ks0) * 128 + hf0 * 64 + tid, 0);
    cl_arrive_relaxed(); cl_wait();
    uint32_t ep;
    asm volatile("add.u32 %0, %1, 1;" : "=r"(ep) : "r"(ep0) : "memory");
    const float sc_ = silu_c(__uint_as_float((uint32_t)cv_ << 16));
    const uint32_t rel = mapa(bar, (lane & 1) ^ rank);
    const uint32_t stg_row = sb + STG + (wg * 64 + wq * 16 + (lane & 15)) * 128;
    const uint32_t fre = bar + B_FREE;
    Ring r4{0, 0, 0}, r6{0, 0, 0};
    auto none = [](auto) {};
    uint32_t xk[32];
    {
      float a[8] = {0, 0, 0, 0, 0, 0, 0, 0};
#pragma unroll
      for (int i = 0; i < 8; i++) gemv_fma(a, wv[i], __shfl_sync(~0u, sc_, i * 4 + (lane >> 3)));
#pragma unroll
      for (int i = 0; i < 8; i++) { a[i] += __shfl_xor_sync(~0u, a[i], 8); a[i] += __shfl_xor_sync(~0u, a[i], 16); }
      if (lane < 8) {
        sts128(sb + RED_OFF + warp * 256 + lane * 32, __float_as_uint(a[0]), __float_as_uint(a[1]), __float_as_uint(a[2]), __float_as_uint(a[3]));
        sts128(sb + RED_OFF + warp * 256 + lane * 32 + 16, __float_as_uint(a[4]), __float_as_uint(a[5]), __float_as_uint(a[6]), __float_as_uint(a[7]));
      }
      named_bar(1, 256);
      if (tid < 64) {
        float s = 0;
#pragma unroll
        for (int w = 0; w < 8; w++) s += lds32f(sb + RED_OFF + w * 256 + tid * 4);
        st_rlx1(gs->modp + ((j * 2 + sec0) * 4 + ks0) * 128 + hf0 * 64 + tid, (__float_as_uint(s) & ~255u) | tag_of(ep));
      }
      float v[64];
      mbar_wait(bar + B_X, 0); mbar_wait(bar + B_X + 8, 0);
#pragma unroll
      for (int i = 0; i < 16; i += 2) {
        uint32_t w0, w1, w2, w3;
        ldsm4(stg_row + (i >> 3) * BLK + ((((i & 7) + (lane >> 4)) ^ (lane & 7)) << 4), w0, w1, w2, w3);
        xk[2 * i] = w0; xk[2 * i + 1] = w1; xk[2 * i + 2] = w2; xk[2 * i + 3] = w3;
        v[4 * i] = bf_lo(w0); v[4 * i + 1] = bf_hi(w0); v[4 * i + 2] = bf_lo(w1); v[4 * i + 3] = bf_hi(w1);
        v[4 * i + 4] = bf_lo(w2); v[4 * i + 5] = bf_hi(w2); v[4 * i + 6] = bf_lo(w3); v[4 * i + 7] = bf_hi(w3);
      }
      ln_publish(v, gs->stat + m * 1024, j, row0, lane, ep);
      mod_store(sb, tid >> 7, tid & 127, mod_gather(gs->modp + (j * 2 + (tid >> 7)) * 512 + (tid & 127), ep));
      named_bar(1, 256);
      ln_apply(v, gs->stat + m * 1024, row0, ep, sb, 0, 1, stg_row, wg, lane);
      named_bar(1, 256);
    }
    {
      uint32_t kf[32], vf[32], pv[32];
      const bool first = wq == 0 && m == 0;
      const uint32_t xa = sb + STG + wg * HALF + wq * 2048 + lane * 16;
      {
        float acc[128];
        mainloop<256, 4, 0, 0>(acc, 16, true, r4, sb, wg, lane, rel, none, none, [&] {
          mbar_wait(fre + 8, 0);
          if (c < 2) st_rlx2(gs->stat + (16 + m) * 1024 + j * 128 + row0 + c * 8, 0, 0);
        });
#pragma unroll
        for (int i = 0; i < 32; i++) { kf[i] = pack2(acc[2 * i], acc[2 * i + 1]); vf[i] = pack2(acc[64 + 2 * i], acc[65 + 2 * i]); }
      }
      float acc[64];
      constexpr int QP = 2;
      mainloop<128, 6, 8 / QP, 0>(acc, 16, false, r6, sb, wg, lane, rel, [&](auto ic) {
        constexpr int q = (ic.v - 1) * QP;
#pragma unroll
        for (int i = 4 * q; i < 4 * (q + QP); i++) vf[i] = movm(vf[i]);
        if (wq == 3) {
          if (m < 15) {
            uint4* hp = gs->halo + (((m + 1) * 8 + j) * 2 + wg) * 512 + lane;
#pragma unroll
            for (int i = 2 * q; i < 2 * (q + QP); i++) st_rlx4(hp + i * 32, kf[2 * i + 1], ep, vf[2 * i + 1], ep);
          }
        } else {
#pragma unroll
          for (int i = q; i < q + QP; i++) sts128(xa + 2048 + (i >> 2) * BLK + (i & 3) * 512, kf[4 * i + 1], kf[4 * i + 3], vf[4 * i + 1], vf[4 * i + 3]);
        }
      }, none, [&] {
        named_bar(2 + wg, 128);
        if (wq == 0) mbar_wait(bar + B_HALO, 0);
#pragma unroll
        for (int i = 0; i < 8; i++) {
          uint4 q = lds128(xa + (i >> 2) * BLK + (i & 3) * 512);
          pv[4 * i] = q.x; pv[4 * i + 1] = q.y; pv[4 * i + 2] = q.z; pv[4 * i + 3] = q.w;
        }
        __syncwarp();
      });
      int gz = g;
#pragma unroll
      for (int b = 0; b < 2; b++) {
        const bool up0 = 2 * c > gz, up1 = 2 * c + 1 > gz;
        const uint32_t mup = (up0 ? 0xffffu : 0u) | (up1 ? 0xffff0000u : 0u);
        float l[2][4], mx[4];
#pragma unroll
        for (int h = 0; h < 2; h++) {
          uint32_t q[8];
          const int k = 16 * b + 8 * h;
#pragma unroll
          for (int i = 0; i < 8; i++) q[i] = pack2(acc[2 * k + 2 * i], acc[2 * k + 2 * i + 1]);
          float s0[4], s1[4], s2[4];
          mma16z(s0, q[0], q[1], q[2], q[3], pv[k], pv[k + 1]); mma16z(s1, q[0], q[1], q[2], q[3], kf[k], kf[k + 2]); mma16z(s2, q[0], q[1], q[2], q[3], kf[k + 1], kf[k + 3]);
          mma16(s0, q[4], q[5], q[6], q[7], pv[k + 4], pv[k + 5]); mma16(s1, q[4], q[5], q[6], q[7], kf[k + 4], kf[k + 6]); mma16(s2, q[4], q[5], q[6], q[7], kf[k + 5], kf[k + 7]);
          if (first) { s0[0] = -INFINITY; s0[1] = -INFINITY; }
          l[h][0] = up0 ? s0[0] : s1[0]; l[h][1] = up1 ? s0[1] : s1[1]; l[h][2] = up0 ? s1[2] : s2[2]; l[h][3] = up1 ? s1[3] : s2[3];
          mx[2 * h] = fmaxf(l[h][0], l[h][1]); mx[2 * h + 1] = fmaxf(l[h][2], l[h][3]);
        }
#pragma unroll
        for (int o = 1; o < 4; o <<= 1) {
#pragma unroll
          for (int h = 0; h < 4; h++) mx[h] = fmaxf(mx[h], __shfl_xor_sync(~0u, mx[h], o));
        }
#pragma unroll
        for (int h = 0; h < 2; h++) {
          const float n0 = -mx[2 * h] * SCL, n1 = -mx[2 * h + 1] * SCL;
          const uint32_t pa = pack2(ex2(fmaf(l[h][0], SCL, n0)), ex2(fmaf(l[h][1], SCL, n0))), pb = pack2(ex2(fmaf(l[h][2], SCL, n1)), ex2(fmaf(l[h][3], SCL, n1)));
          float sm[4];
          mma8z(sm, pa, pb, 0x3f803f80u);
          const float ia = rcp(sm[0]), ib = rcp(sm[2]);
#pragma unroll
          for (int i = 8 * b + 4 * h; i < 8 * b + 4 * h + 4; i += 2) {
            uint32_t of[4];
#pragma unroll
            for (int d = 0; d < 2; d++) {
              float o[4];
              mma16z(o, pa & ~mup, pb & mup, 0u, pb & ~mup, vf[2 * (i + d)], vf[2 * (i + d) + 1]);
              mma8(o, pa & mup, 0u, pv[2 * i + 2 + d]);
              of[2 * d] = pack2(o[0] * ia, o[1] * ia); of[2 * d + 1] = pack2(o[2] * ib, o[3] * ib);
            }
            stsm4(stg_row + b * BLK + ((((i & 7) + (lane >> 4)) ^ (lane & 7)) << 4), of[0], of[1], of[2], of[3]);
          }
        }
        stage_done(sb, wg, b, lane);
        if (b == 0) gz += __float_as_uint(lds32f(bar + ZERO));
      }
      named_bar(1, 256);
    }
    uint32_t pk[64];
    {
      float acc[64];
      mainloop<128, 6, 0, WOLAG>(acc, 16, true, r6, sb, wg, lane, rel, none, none, [&] {
        if (WOLAG && wg == 0 && lane == 0) mbar_arrive(bar + B_LAG);
        mbar_wait(bar + B_MOD, 0); mbar_wait(fre + 8, 1);
        load_vec(pk + 32, sb, 2, 0, lane); load_vec(pk + 40, sb, 2, 1, lane);
#pragma unroll
        for (int i = 0; i < 32; i++) { pk[i] = xk[i]; asm volatile("" : "+r"(pk[i])); }
      });
#pragma unroll
      for (int i = 0; i < 32; i++) {
        acc[2 * i] = fmaf(acc[2 * i], bf_lo(pk[32 + (i >> 1)]), bf_lo(pk[i]));
        acc[2 * i + 1] = fmaf(acc[2 * i + 1], bf_hi(pk[32 + (i >> 1)]), bf_hi(pk[i]));
      }
      ln_publish(acc, gs->stat + (16 + m) * 1024, j, row0, lane, ep);
      mbar_wait(bar + B_FULL6 + 16, 1);
      if (lane < 2) mbar_arrive_cl(rel + B_EMPTY6 + 16);
      ring_next<6>(r6);
#pragma unroll
      for (int i = 0; i < 32; i++) { pk[i] = pack2(acc[2 * i], acc[2 * i + 1]); pk[32 + i] = 0; }
      ln_apply(acc, gs->stat + (16 + m) * 1024, row0, ep, sb, 3, 4, stg_row, wg, lane);
      named_bar(1, 256);
    }
    auto swiglu = [&](int q, int uo, int par) {
      if ((q & 3) == 0 && par >= 0) mbar_wait(fre + 2 * q, par);
      uint32_t w[4];
#pragma unroll
      for (int u = 0; u < 4; u++) w[u] = silu_mul2(pk[4 * q + u], pk[uo + 4 * q + u]);
      stsm4(stg_row + (q >> 2) * BLK + ((((2 * q & 7) + (lane >> 4)) ^ (lane & 7)) << 4), w[0], w[1], w[2], w[3]);
    };
    r4.s = r4.wrap = 2;
#pragma unroll 1
    for (int t = 0; t < 3; t++) {
      float acc[128];
      mainloop<256, 4, 4, 0>(acc, 16, t == 0, r4, sb, wg, lane, rel, [&](auto ic) {
        if (t) {
          if (ic.v == 3) stage_done(sb, wg, 0, lane);
          swiglu(2 * ic.v - 2, 32, ~t & 1); swiglu(2 * ic.v - 1, 32, 0);
        }
      }, [&](int it) {
        if (t && it == 5) stage_done(sb, wg, 1, lane);
#pragma unroll
        for (int i = 0; i < 8; i++)
          if (t == 0 && it == 8 + i) gs->x1[bid * 2048 + (i >> 2) * 1024 + warp * 128 + (i & 3) * 32 + lane] = make_uint4(pk[4 * i], pk[4 * i + 1], pk[4 * i + 2], pk[4 * i + 3]);
      }, [&] { if (t == 0) fence_async_global(); else if (t == 2) mbar_wait(bar + B_X, 1); });
#pragma unroll
      for (int i = 0; i < 64; i++) pk[i] = pack2(acc[2 * i], acc[2 * i + 1]);
    }
    uint32_t x1[32];
    {
      float acc[64];
      mainloop<128, 6, 10, 0>(acc, 16, false, r6, sb, wg, lane, rel, [&](auto ic) {
        constexpr int b = ic.v > 5, q = ic.v - 5 * b;
        if (q == 1) {
          if (b) stage_done(sb, wg, 0, lane);
#pragma unroll
          for (int i = 4 * b; i < 4 * b + 4; i++) { const uint4 x = lds128(sb + STG + b * BLK + warp * 2048 + (i & 3) * 512 + lane * 16); x1[4 * i] = x.x; x1[4 * i + 1] = x.y; x1[4 * i + 2] = x.z; x1[4 * i + 3] = x.w; }
          __syncwarp();
        } else swiglu(4 * b + q - 2, 32, -1);
      }, [&](int it) { if (it == 11) stage_done(sb, wg, 1, lane); }, [] {});
#pragma unroll
      for (int i = 0; i < 32; i++) pk[i] = pack2(acc[2 * i], acc[2 * i + 1]);
    }
    {
      float acc[64];
      mainloop<128, 6, 4, TAILLAG>(acc, 56, false, r6, sb, wg, lane, rel, [&](auto ic) { swiglu(ic.v - 1, 16, 1); },
                                   [&](int it) { if (it == 5) stage_done(sb, wg, 0, lane); }, [&] {
        if (TAILLAG && wg == 0 && lane == 0) mbar_arrive(bar + B_LAG);
        load_vec(pk + 32, sb, 5, 0, lane); load_vec(pk + 40, sb, 5, 1, lane);
        mbar_wait(fre, 0); mbar_wait(fre + 8, 1);
      });
      __syncwarp();
      cl_arrive_relaxed();
#pragma unroll
      for (int i = 0; i < 16; i += 2) {
        uint32_t w[4];
#pragma unroll
        for (int u = 0; u < 4; u++) {
          const int q = 2 * i + u;
          w[u] = pack2(fmaf(acc[2 * q], bf_lo(pk[32 + (q >> 1)]), bf_lo(x1[q])), fmaf(acc[2 * q + 1], bf_hi(pk[32 + (q >> 1)]), bf_hi(x1[q])));
        }
        stsm4(stg_row + (i >> 3) * BLK + ((((i & 7) + (lane >> 4)) ^ (lane & 7)) << 4), w[0], w[1], w[2], w[3]);
        if ((i & 7) == 6) {
          fence_async_smem();
          named_bar(2 + wg, 128);
          if (wq == 0 && elect()) { tma_store_3d(&maps.out, sb + STG + (i >> 3) * BLK + wg * HALF, j * 128 + (i >> 3) * 64, m * 64, wg); bulk_commit(); }
          if (i < 8) x1[16] |= __float_as_uint(lds32f(bar + ZERO));
        }
      }
      if (wq == 0) bulk_wait_read();
      if (tid == 0) gs->epoch[bid + 4] = ep;
      cl_wait();
    }
  }
}

typedef CUresult (*EncodeFn)(CUtensorMap*, CUtensorMapDataType, cuuint32_t, void*, const cuuint64_t*, const cuuint64_t*, const cuuint32_t*, const cuuint32_t*,
                             CUtensorMapInterleave, CUtensorMapSwizzle, CUtensorMapL2promotion, CUtensorMapFloatOOBfill);

void make_map(EncodeFn fn, CUtensorMap* mp, const void* base, uint64_t d0, uint64_t d1, uint64_t d2, uint64_t s1, uint64_t s2, uint32_t b2, uint32_t b0 = 64) {
  cuuint64_t d[3] = {d0, d1, d2}, s[2] = {s1, s2};
  cuuint32_t b[3] = {b0, 64, b2}, e[3] = {1, 1, 1};
  fn(mp, CU_TENSOR_MAP_DATA_TYPE_BFLOAT16, 3, (void*)base, d, s, b, e, CU_TENSOR_MAP_INTERLEAVE_NONE, b0 == 64 ? CU_TENSOR_MAP_SWIZZLE_128B : CU_TENSOR_MAP_SWIZZLE_NONE,
     CU_TENSOR_MAP_L2_PROMOTION_L2_128B, CU_TENSOR_MAP_FLOAT_OOB_FILL_NONE);
}

__global__ void probe_kernel() {}
int max_clusters(int size) {
  cudaLaunchConfig_t cfg = {};
  cudaLaunchAttribute at;
  at.id = cudaLaunchAttributeClusterDimension; at.val.clusterDim.x = size; at.val.clusterDim.y = 1; at.val.clusterDim.z = 1;
  cfg.gridDim = dim3(size * 66); cfg.blockDim = dim3(384); cfg.dynamicSmemBytes = SMEM_BYTES; cfg.attrs = &at; cfg.numAttrs = 1;
  int n = 0;
  if (cudaOccupancyMaxActiveClusters(&n, probe_kernel, &cfg) != cudaSuccess) { cudaGetLastError(); return 0; }
  return n;
}

}

extern "C" void kernel_launch(void* const* d_in, const int* in_sizes, int n_in, void* d_out, int out_size) {
  static EncodeFn fn = nullptr;
  static int by_sm = 0;
  static Scratch* gs = nullptr;
  if (!fn) {
    void* p = nullptr; cudaDriverEntryPointQueryResult q;
    cudaGetDriverEntryPoint("cuTensorMapEncodeTiled", &p, cudaEnableDefault, &q);
    fn = (EncodeFn)p;
    cudaFuncSetAttribute(fused_kernel, cudaFuncAttributeMaxDynamicSharedMemorySize, SMEM_BYTES);
    int dev = 0, sms = 0;
    cudaGetSymbolAddress((void**)&gs, g_scratch);
    cudaGetDevice(&dev);
    cudaDeviceGetAttribute(&sms, cudaDevAttrMultiProcessorCount, dev);
    cudaFuncSetAttribute(probe_kernel, cudaFuncAttributeMaxDynamicSharedMemorySize, SMEM_BYTES);
    by_sm = sms == 132 && max_clusters(2) == 66 && max_clusters(4) == 30 && max_clusters(6) == 17 && max_clusters(8) == 15;
  }
  Maps mp;
  make_map(fn, &mp.x, d_in[0], D_, S_ / 2, 2, 4096, 2048, 2);
  make_map(fn, &mp.out, d_out, D_, S_ / 2, 2, 4096, 2048, 1);
  make_map(fn, &mp.wqkv, d_in[1], 64, D_, 3 * D_ / 64, 3 * D_ * 2, 128, 2);
  make_map(fn, &mp.wo, d_in[2], 64, D_, D_ / 64, D_ * 2, 128, 2);
  make_map(fn, &mp.w1, d_in[4], 64, D_, F_ / 64, F_ * 2, 128, 2);
  make_map(fn, &mp.w3, d_in[5], 64, D_, F_ / 64, F_ * 2, 128, 2);
  make_map(fn, &mp.w1s, d_in[4], 64, D_, F_ / 64, F_ * 2, 128, 1);
  make_map(fn, &mp.w3s, d_in[5], 64, D_, F_ / 64, F_ * 2, 128, 1);
  make_map(fn, &mp.w2, d_in[6], 64, F_, D_ / 64, D_ * 2, 128, 2);
  make_map(fn, &mp.wmod, d_in[8], 256, D_, 24, 6 * D_ * 2, 512, 1, 256);
  fused_kernel<<<132, 384, SMEM_BYTES>>>((const bf16*)d_in[7], (const bf16*)d_in[8], gs, by_sm, mp);
}
```

```cpp
#include <cuda_runtime.h>
#include <cuda_bf16.h>
#include <cuda.h>
#include <stdint.h>

typedef __nv_bfloat16 bf16;

namespace {

constexpr int S_ = 2048, D_ = 1024, F_ = 3584;
constexpr int BLK = 16384;
constexpr int HALF = 8192;
constexpr int RING = 196608;
constexpr int STG = RING;
constexpr int MISC = RING + 2 * BLK;
constexpr int SMEM_BYTES = MISC + 3072;
constexpr int B_FULL4 = 0, B_EMPTY4 = 32, B_FULL6 = 64, B_EMPTY6 = 112, B_RDY = 160, B_FREE = 176, B_LAG = 192, B_X = 208, B_MOD = 224, B_HALO = 232, B_HH = 256, B_ALL = 272, B_HH2 = 288, ZERO = 296;
constexpr int MODV = 512;
constexpr int RED_OFF = 0;
constexpr float SCL = 0.17677669529663687f * 1.4426950408889634f;
constexpr int U_HH = 64;
constexpr int FS = 8;
constexpr int NPIECE = 4, PSLEEP = 300;
constexpr int XSLEEP = 4000, HSLEEP = 400;
constexpr uint32_t XDELAY = 2000;
constexpr uint32_t B1P = 3500, B1D = 900, B1P2 = 3200;
constexpr int WOLAG = 2, TAILLAG = 5;

struct Maps { CUtensorMap x, out, wqkv, wo, w1, w3, w1s, w3s, w2, wmod; };

struct Scratch {
  uint4 h[16 * 16 * 1024];
  uint4 o[16 * 16 * 1024];
  uint4 hh[16 * 56 * 1024];
  uint4 x1[128 * 8 * 256];
  uint2 stat[2 * 16 * 8 * 128];
  uint4 halo[16 * 8 * 2 * 512];
  uint32_t modp[8 * 2 * 4 * 128];
  uint2 modv[4 * 1024];
  uint32_t flag[16 * 128 * FS];
  uint32_t epoch[132];
};
__device__ __align__(1024) Scratch g_scratch;

__device__ __forceinline__ void bail() { asm volatile("st.global.u32 [%0], %1;" :: "l"(0ull), "r"(0) : "memory"); }
__device__ __forceinline__ uint32_t smem_u32(const void* p) { return (uint32_t)__cvta_generic_to_shared(p); }
__device__ __forceinline__ void mbar_init(uint32_t bar, uint32_t cnt) { asm volatile("mbarrier.init.shared::cta.b64 [%0], %1;" :: "r"(bar), "r"(cnt) : "memory"); }
__device__ __forceinline__ void mbar_expect_tx(uint32_t bar, uint32_t bytes) { asm volatile("mbarrier.arrive.expect_tx.shared::cta.b64 _, [%0], %1;" :: "r"(bar), "r"(bytes) : "memory"); }
__device__ __forceinline__ void mbar_arrive(uint32_t bar) { asm volatile("mbarrier.arrive.shared::cta.b64 _, [%0];" :: "r"(bar) : "memory"); }
__device__ __forceinline__ void mbar_arrive_cl(uint32_t cl_addr) { asm volatile("mbarrier.arrive.shared::cluster.b64 _, [%0];" :: "r"(cl_addr) : "memory"); }
__device__ __forceinline__ uint32_t mapa(uint32_t addr, uint32_t cta) { uint32_t r; asm("mapa.shared::cluster.u32 %0, %1, %2;" : "=r"(r) : "r"(addr), "r"(cta)); return r; }
__device__ __forceinline__ void mbar_wait(uint32_t bar, uint32_t parity) {
  asm volatile("{\n.reg .pred p;\n.reg .b32 n;\n.reg .b64 z;\nmov.b32 n, 0;\nmov.b64 z, 0;\n"
               "W: add.u32 n, n, 1;\nsetp.gt.u32 p, n, 0x400000;\n@p st.global.u32 [z], n;\n"
               "mbarrier.try_wait.parity.shared::cta.b64 p, [%0], %1;\n@!p bra W;\n}" :: "r"(bar), "r"(parity) : "memory");
}
__device__ __forceinline__ void tma_3d(uint32_t dst, const CUtensorMap* m, uint32_t bar, int c0, int c1, int c2) {
  asm volatile("cp.async.bulk.tensor.3d.shared::cluster.global.mbarrier::complete_tx::bytes [%0], [%1, {%3, %4, %5}], [%2];" :: "r"(dst), "l"(m), "r"(bar), "r"(c0), "r"(c1), "r"(c2) : "memory");
}
__device__ __forceinline__ void tma_store_3d(const CUtensorMap* m, uint32_t src, int c0, int c1, int c2) {
  asm volatile("cp.async.bulk.tensor.3d.global.shared::cta.bulk_group [%0, {%2, %3, %4}], [%1];" :: "l"(m), "r"(src), "r"(c0), "r"(c1), "r"(c2) : "memory");
}
__device__ __forceinline__ void bulk_ld(uint32_t dst, const void* src, uint32_t bytes, uint32_t bar) {
  asm volatile("cp.async.bulk.shared::cluster.global.mbarrier::complete_tx::bytes [%0], [%1], %2, [%3];" :: "r"(dst), "l"(src), "r"(bytes), "r"(bar) : "memory");
}
__device__ __forceinline__ void bulk_ld_mc(uint32_t dst, const void* src, uint32_t bytes, uint32_t bar) {
  asm volatile("cp.async.bulk.shared::cluster.global.mbarrier::complete_tx::bytes.multicast::cluster [%0], [%1], %2, [%3], %4;" :: "r"(dst), "l"(src), "r"(bytes), "r"(bar), "h"((uint16_t)3) : "memory");
}
__device__ __forceinline__ void bulk_push(uint32_t dst_cl, uint32_t src, uint32_t bytes, uint32_t bar_cl) {
  asm volatile("cp.async.bulk.shared::cluster.shared::cta.mbarrier::complete_tx::bytes [%0], [%1], %2, [%3];" :: "r"(dst_cl), "r"(src), "r"(bytes), "r"(bar_cl) : "memory");
}
__device__ __forceinline__ void bulk_st(void* dst, uint32_t src, uint32_t bytes) {
  asm volatile("cp.async.bulk.global.shared::cta.bulk_group [%0], [%1], %2;" :: "l"(dst), "r"(src), "r"(bytes) : "memory");
}
__device__ __forceinline__ void bulk_commit() { asm volatile("cp.async.bulk.commit_group;" ::: "memory"); }
__device__ __forceinline__ void bulk_wait_read() { asm volatile("cp.async.bulk.wait_group.read 0;" ::: "memory"); }
__device__ __forceinline__ void bulk_wait_all() { asm volatile("cp.async.bulk.wait_group 0;" ::: "memory"); }
__device__ __forceinline__ void fence_async_global() { asm volatile("fence.proxy.async.global;" ::: "memory"); }
__device__ __forceinline__ void fence_async_smem() { asm volatile("fence.proxy.async.shared::cta;" ::: "memory"); }
__device__ __forceinline__ void wg_arrive() { asm volatile("wgmma.fence.sync.aligned;" ::: "memory"); }
__device__ __forceinline__ void wg_commit() { asm volatile("wgmma.commit_group.sync.aligned;" ::: "memory"); }
template <int N> __device__ __forceinline__ void wg_wait() { asm volatile("wgmma.wait_group.sync.aligned %0;" :: "n"(N) : "memory"); }
__device__ __forceinline__ void cl_arrive_relaxed() { asm volatile("barrier.cluster.arrive.relaxed.aligned;" ::: "memory"); }
__device__ __forceinline__ void cl_wait() { asm volatile("barrier.cluster.wait.acquire.aligned;" ::: "memory"); }
__device__ __forceinline__ bool elect() { uint32_t p; asm volatile("{\n.reg .pred p;\nelect.sync _|p, 0xffffffff;\nselp.u32 %0, 1, 0, p;\n}" : "=r"(p)); return p; }
__device__ __forceinline__ void named_bar(int id, int n) { asm volatile("bar.sync %0, %1;" :: "r"(id), "r"(n) : "memory"); }
__device__ __forceinline__ uint32_t pack2(float lo, float hi) { uint32_t r; asm("cvt.rn.bf16x2.f32 %0, %1, %2;" : "=r"(r) : "f"(hi), "f"(lo)); return r; }
__device__ __forceinline__ float bf_lo(uint32_t w) { return __uint_as_float(w << 16); }
__device__ __forceinline__ float bf_hi(uint32_t w) { return __uint_as_float(w & 0xffff0000u); }
__device__ __forceinline__ float bf_round(float v) { return __bfloat162float(__float2bfloat16_rn(v)); }
__device__ __forceinline__ void stsm4(uint32_t addr, uint32_t a, uint32_t b, uint32_t c, uint32_t d) {
  asm volatile("stmatrix.sync.aligned.m8n8.x4.shared.b16 [%0], {%1, %2, %3, %4};" :: "r"(addr), "r"(a), "r"(b), "r"(c), "r"(d) : "memory");
}
__device__ __forceinline__ void ldsm4(uint32_t addr, uint32_t& a, uint32_t& b, uint32_t& c, uint32_t& d) {
  asm volatile("ldmatrix.sync.aligned.m8n8.x4.shared.b16 {%0, %1, %2, %3}, [%4];" : "=r"(a), "=r"(b), "=r"(c), "=r"(d) : "r"(addr) : "memory");
}
__device__ __forceinline__ uint32_t movm(uint32_t a) { uint32_t r; asm volatile("movmatrix.sync.aligned.m8n8.trans.b16 %0, %1;" : "=r"(r) : "r"(a)); return r; }
__device__ __forceinline__ void mma16(float (&d)[4], uint32_t a0, uint32_t a1, uint32_t a2, uint32_t a3, uint32_t b0, uint32_t b1) {
  asm("mma.sync.aligned.m16n8k16.row.col.f32.bf16.bf16.f32 {%0,%1,%2,%3}, {%4,%5,%6,%7}, {%8,%9}, {%0,%1,%2,%3};"
               : "+f"(d[0]), "+f"(d[1]), "+f"(d[2]), "+f"(d[3]) : "r"(a0), "r"(a1), "r"(a2), "r"(a3), "r"(b0), "r"(b1));
}
__device__ __forceinline__ void mma16z(float (&d)[4], uint32_t a0, uint32_t a1, uint32_t a2, uint32_t a3, uint32_t b0, uint32_t b1) {
  asm("mma.sync.aligned.m16n8k16.row.col.f32.bf16.bf16.f32 {%0,%1,%2,%3}, {%4,%5,%6,%7}, {%8,%9}, {%10,%10,%10,%10};"
      : "=f"(d[0]), "=f"(d[1]), "=f"(d[2]), "=f"(d[3]) : "r"(a0), "r"(a1), "r"(a2), "r"(a3), "r"(b0), "r"(b1), "f"(0.f));
}
__device__ __forceinline__ void mma8z(float (&d)[4], uint32_t a0, uint32_t a1, uint32_t b0) {
  asm("mma.sync.aligned.m16n8k8.row.col.f32.bf16.bf16.f32 {%0,%1,%2,%3}, {%4,%5}, {%6}, {%7,%7,%7,%7};"
      : "=f"(d[0]), "=f"(d[1]), "=f"(d[2]), "=f"(d[3]) : "r"(a0), "r"(a1), "r"(b0), "f"(0.f));
}
__device__ __forceinline__ void mma8(float (&d)[4], uint32_t a0, uint32_t a1, uint32_t b0) {
  asm("mma.sync.aligned.m16n8k8.row.col.f32.bf16.bf16.f32 {%0,%1,%2,%3}, {%4,%5}, {%6}, {%0,%1,%2,%3};"
               : "+f"(d[0]), "+f"(d[1]), "+f"(d[2]), "+f"(d[3]) : "r"(a0), "r"(a1), "r"(b0));
}
__device__ __forceinline__ uint4 lds128(uint32_t a) { uint4 v; asm volatile("ld.shared.v4.u32 {%0,%1,%2,%3}, [%4];" : "=r"(v.x), "=r"(v.y), "=r"(v.z), "=r"(v.w) : "r"(a) : "memory"); return v; }
__device__ __forceinline__ void sts128(uint32_t a, uint32_t x, uint32_t y, uint32_t z, uint32_t w) { asm volatile("st.shared.v4.u32 [%0], {%1,%2,%3,%4};" :: "r"(a), "r"(x), "r"(y), "r"(z), "r"(w) : "memory"); }
__device__ __forceinline__ float lds32f(uint32_t a) { float v; asm volatile("ld.shared.f32 %0, [%1];" : "=f"(v) : "r"(a) : "memory"); return v; }
__device__ __forceinline__ void sts16(uint32_t a, bf16 v) { asm volatile("st.shared.b16 [%0], %1;" :: "r"(a), "h"(__bfloat16_as_ushort(v)) : "memory"); }
__device__ __forceinline__ uint4 ldg_nc(const void* p) { uint4 v; asm volatile("ld.global.nc.L1::no_allocate.v4.u32 {%0,%1,%2,%3}, [%4];" : "=r"(v.x), "=r"(v.y), "=r"(v.z), "=r"(v.w) : "l"(p)); return v; }
__device__ __forceinline__ uint4 ld_rlx4(const uint4* p) {
  unsigned long long a, b; asm volatile("ld.relaxed.gpu.global.v2.b64 {%0,%1}, [%2];" : "=l"(a), "=l"(b) : "l"(p) : "memory");
  return make_uint4((uint32_t)a, (uint32_t)(a >> 32), (uint32_t)b, (uint32_t)(b >> 32));
}
__device__ __forceinline__ uint2 ld_rlx2(const uint2* p) { unsigned long long a; asm volatile("ld.relaxed.gpu.global.b64 %0, [%1];" : "=l"(a) : "l"(p) : "memory"); return make_uint2((uint32_t)a, (uint32_t)(a >> 32)); }
__device__ __forceinline__ void st_rlx4(uint4* p, uint32_t x, uint32_t y, uint32_t z, uint32_t w) {
  asm volatile("st.relaxed.gpu.global.v2.b64 [%0], {%1,%2};" :: "l"(p), "l"((unsigned long long)x | ((unsigned long long)y << 32)), "l"((unsigned long long)z | ((unsigned long long)w << 32)) : "memory");
}
__device__ __forceinline__ void st_rlx2(uint2* p, uint32_t x, uint32_t y) { asm volatile("st.relaxed.gpu.global.b64 [%0], %1;" :: "l"(p), "l"((unsigned long long)x | ((unsigned long long)y << 32)) : "memory"); }
__device__ __forceinline__ void st_rlx1(uint32_t* p, uint32_t v) { asm volatile("st.relaxed.gpu.global.u32 [%0], %1;" :: "l"(p), "r"(v) : "memory"); }
__device__ __forceinline__ uint32_t ld_rlx1(const uint32_t* p) { uint32_t v; asm volatile("ld.relaxed.gpu.global.u32 %0, [%1];" : "=r"(v) : "l"(p) : "memory"); return v; }
__device__ __forceinline__ void st_release(uint32_t* p, uint32_t v) { asm volatile("st.release.gpu.global.u32 [%0], %1;" :: "l"(p), "r"(v) : "memory"); }
__device__ __forceinline__ uint32_t ld_acquire(const uint32_t* p) { uint32_t v; asm volatile("ld.acquire.gpu.global.u32 %0, [%1];" : "=r"(v) : "l"(p) : "memory"); return v; }
__device__ __forceinline__ void prefetch_map(const CUtensorMap* m) { asm volatile("prefetch.tensormap [%0];" :: "l"(m) : "memory"); }
__device__ __forceinline__ float rcp(float x) { float r; asm("rcp.approx.ftz.f32 %0, %1;" : "=f"(r) : "f"(x)); return r; }
__device__ __forceinline__ float ex2(float x) { float r; asm("ex2.approx.ftz.f32 %0, %1;" : "=f"(r) : "f"(x)); return r; }
__device__ __forceinline__ float tanh_fast(float x) { float r; asm("tanh.approx.f32 %0, %1;" : "=f"(r) : "f"(x)); return r; }
#define SPIN_GUARD(n) if (++(n) > (1u << 24)) bail()

__device__ __forceinline__ void wgmma_n128(float (&d)[64], uint64_t da, uint64_t db) {
  asm volatile("wgmma.mma_async.sync.aligned.m64n128k16.f32.bf16.bf16 "
    "{%0, %1, %2, %3, %4, %5, %6, %7, %8, %9, %10, %11, %12, %13, %14, %15, %16, %17, %18, %19, %20, %21, %22, %23, %24, %25, %26, %27, %28, %29, %30, %31, %32, %33, %34, %35, %36, %37, %38, %39, %40, %41, %42, %43, %44, %45, %46, %47, %48, %49, %50, %51, %52, %53, %54, %55, %56, %57, %58, %59, %60, %61, %62, %63}, "
    "%64, %65, 1, 1, 1, 0, 1;\n"
    : "+f"(d[0]), "+f"(d[1]), "+f"(d[2]), "+f"(d[3]), "+f"(d[4]), "+f"(d[5]), "+f"(d[6]), "+f"(d[7]), "+f"(d[8]), "+f"(d[9]), "+f"(d[10]), "+f"(d[11]), "+f"(d[12]), "+f"(d[13]), "+f"(d[14]), "+f"(d[15]), "+f"(d[16]), "+f"(d[17]), "+f"(d[18]), "+f"(d[19]), "+f"(d[20]), "+f"(d[21]), "+f"(d[22]), "+f"(d[23]), "+f"(d[24]), "+f"(d[25]), "+f"(d[26]), "+f"(d[27]), "+f"(d[28]), "+f"(d[29]), "+f"(d[30]), "+f"(d[31]), "+f"(d[32]), "+f"(d[33]), "+f"(d[34]), "+f"(d[35]), "+f"(d[36]), "+f"(d[37]), "+f"(d[38]), "+f"(d[39]), "+f"(d[40]), "+f"(d[41]), "+f"(d[42]), "+f"(d[43]), "+f"(d[44]), "+f"(d[45]), "+f"(d[46]), "+f"(d[47]), "+f"(d[48]), "+f"(d[49]), "+f"(d[50]), "+f"(d[51]), "+f"(d[52]), "+f"(d[53]), "+f"(d[54]), "+f"(d[55]), "+f"(d[56]), "+f"(d[57]), "+f"(d[58]), "+f"(d[59]), "+f"(d[60]), "+f"(d[61]), "+f"(d[62]), "+f"(d[63])
    : "l"(da), "l"(db));
}
__device__ __forceinline__ void wgmma_n128_first(float (&d)[64], uint64_t da, uint64_t db) {
  asm volatile("wgmma.mma_async.sync.aligned.m64n128k16.f32.bf16.bf16 "
    "{%0, %1, %2, %3, %4, %5, %6, %7, %8, %9, %10, %11, %12, %13, %14, %15, %16, %17, %18, %19, %20, %21, %22, %23, %24, %25, %26, %27, %28, %29, %30, %31, %32, %33, %34, %35, %36, %37, %38, %39, %40, %41, %42, %43, %44, %45, %46, %47, %48, %49, %50, %51, %52, %53, %54, %55, %56, %57, %58, %59, %60, %61, %62, %63}, "
    "%64, %65, 0, 1, 1, 0, 1;\n"
    : "=f"(d[0]), "=f"(d[1]), "=f"(d[2]), "=f"(d[3]), "=f"(d[4]), "=f"(d[5]), "=f"(d[6]), "=f"(d[7]), "=f"(d[8]), "=f"(d[9]), "=f"(d[10]), "=f"(d[11]), "=f"(d[12]), "=f"(d[13]), "=f"(d[14]), "=f"(d[15]), "=f"(d[16]), "=f"(d[17]), "=f"(d[18]), "=f"(d[19]), "=f"(d[20]), "=f"(d[21]), "=f"(d[22]), "=f"(d[23]), "=f"(d[24]), "=f"(d[25]), "=f"(d[26]), "=f"(d[27]), "=f"(d[28]), "=f"(d[29]), "=f"(d[30]), "=f"(d[31]), "=f"(d[32]), "=f"(d[33]), "=f"(d[34]), "=f"(d[35]), "=f"(d[36]), "=f"(d[37]), "=f"(d[38]), "=f"(d[39]), "=f"(d[40]), "=f"(d[41]), "=f"(d[42]), "=f"(d[43]), "=f"(d[44]), "=f"(d[45]), "=f"(d[46]), "=f"(d[47]), "=f"(d[48]), "=f"(d[49]), "=f"(d[50]), "=f"(d[51]), "=f"(d[52]), "=f"(d[53]), "=f"(d[54]), "=f"(d[55]), "=f"(d[56]), "=f"(d[57]), "=f"(d[58]), "=f"(d[59]), "=f"(d[60]), "=f"(d[61]), "=f"(d[62]), "=f"(d[63])
    : "l"(da), "l"(db));
}
__device__ __forceinline__ void wgmma_n256(float (&d)[128], uint64_t da, uint64_t db) {
  asm volatile("wgmma.mma_async.sync.aligned.m64n256k16.f32.bf16.bf16 "
    "{%0, %1, %2, %3, %4, %5, %6, %7, %8, %9, %10, %11, %12, %13, %14, %15, %16, %17, %18, %19, %20, %21, %22, %23, %24, %25, %26, %27, %28, %29, %30, %31, %32, %33, %34, %35, %36, %37, %38, %39, %40, %41, %42, %43, %44, %45, %46, %47, %48, %49, %50, %51, %52, %53, %54, %55, %56, %57, %58, %59, %60, %61, %62, %63, %64, %65, %66, %67, %68, %69, %70, %71, %72, %73, %74, %75, %76, %77, %78, %79, %80, %81, %82, %83, %84, %85, %86, %87, %88, %89, %90, %91, %92, %93, %94, %95, %96, %97, %98, %99, %100, %101, %102, %103, %104, %105, %106, %107, %108, %109, %110, %111, %112, %113, %114, %115, %116, %117, %118, %119, %120, %121, %122, %123, %124, %125, %126, %127}, "
    "%128, %129, 1, 1, 1, 0, 1;\n"
    : "+f"(d[0]), "+f"(d[1]), "+f"(d[2]), "+f"(d[3]), "+f"(d[4]), "+f"(d[5]), "+f"(d[6]), "+f"(d[7]), "+f"(d[8]), "+f"(d[9]), "+f"(d[10]), "+f"(d[11]), "+f"(d[12]), "+f"(d[13]), "+f"(d[14]), "+f"(d[15]), "+f"(d[16]), "+f"(d[17]), "+f"(d[18]), "+f"(d[19]), "+f"(d[20]), "+f"(d[21]), "+f"(d[22]), "+f"(d[23]), "+f"(d[24]), "+f"(d[25]), "+f"(d[26]), "+f"(d[27]), "+f"(d[28]), "+f"(d[29]), "+f"(d[30]), "+f"(d[31]), "+f"(d[32]), "+f"(d[33]), "+f"(d[34]), "+f"(d[35]), "+f"(d[36]), "+f"(d[37]), "+f"(d[38]), "+f"(d[39]), "+f"(d[40]), "+f"(d[41]), "+f"(d[42]), "+f"(d[43]), "+f"(d[44]), "+f"(d[45]), "+f"(d[46]), "+f"(d[47]), "+f"(d[48]), "+f"(d[49]), "+f"(d[50]), "+f"(d[51]), "+f"(d[52]), "+f"(d[53]), "+f"(d[54]), "+f"(d[55]), "+f"(d[56]), "+f"(d[57]), "+f"(d[58]), "+f"(d[59]), "+f"(d[60]), "+f"(d[61]), "+f"(d[62]), "+f"(d[63]), "+f"(d[64]), "+f"(d[65]), "+f"(d[66]), "+f"(d[67]), "+f"(d[68]), "+f"(d[69]), "+f"(d[70]), "+f"(d[71]), "+f"(d[72]), "+f"(d[73]), "+f"(d[74]), "+f"(d[75]), "+f"(d[76]), "+f"(d[77]), "+f"(d[78]), "+f"(d[79]), "+f"(d[80]), "+f"(d[81]), "+f"(d[82]), "+f"(d[83]), "+f"(d[84]), "+f"(d[85]), "+f"(d[86]), "+f"(d[87]), "+f"(d[88]), "+f"(d[89]), "+f"(d[90]), "+f"(d[91]), "+f"(d[92]), "+f"(d[93]), "+f"(d[94]), "+f"(d[95]), "+f"(d[96]), "+f"(d[97]), "+f"(d[98]), "+f"(d[99]), "+f"(d[100]), "+f"(d[101]), "+f"(d[102]), "+f"(d[103]), "+f"(d[104]), "+f"(d[105]), "+f"(d[106]), "+f"(d[107]), "+f"(d[108]), "+f"(d[109]), "+f"(d[110]), "+f"(d[111]), "+f"(d[112]), "+f"(d[113]), "+f"(d[114]), "+f"(d[115]), "+f"(d[116]), "+f"(d[117]), "+f"(d[118]), "+f"(d[119]), "+f"(d[120]), "+f"(d[121]), "+f"(d[122]), "+f"(d[123]), "+f"(d[124]), "+f"(d[125]), "+f"(d[126]), "+f"(d[127])
    : "l"(da), "l"(db));
}
__device__ __forceinline__ void wgmma_n256_first(float (&d)[128], uint64_t da, uint64_t db) {
  asm volatile("wgmma.mma_async.sync.aligned.m64n256k16.f32.bf16.bf16 "
    "{%0, %1, %2, %3, %4, %5, %6, %7, %8, %9, %10, %11, %12, %13, %14, %15, %16, %17, %18, %19, %20, %21, %22, %23, %24, %25, %26, %27, %28, %29, %30, %31, %32, %33, %34, %35, %36, %37, %38, %39, %40, %41, %42, %43, %44, %45, %46, %47, %48, %49, %50, %51, %52, %53, %54, %55, %56, %57, %58, %59, %60, %61, %62, %63, %64, %65, %66, %67, %68, %69, %70, %71, %72, %73, %74, %75, %76, %77, %78, %79, %80, %81, %82, %83, %84, %85, %86, %87, %88, %89, %90, %91, %92, %93, %94, %95, %96, %97, %98, %99, %100, %101, %102, %103, %104, %105, %106, %107, %108, %109, %110, %111, %112, %113, %114, %115, %116, %117, %118, %119, %120, %121, %122, %123, %124, %125, %126, %127}, "
    "%128, %129, 0, 1, 1, 0, 1;\n"
    : "=f"(d[0]), "=f"(d[1]), "=f"(d[2]), "=f"(d[3]), "=f"(d[4]), "=f"(d[5]), "=f"(d[6]), "=f"(d[7]), "=f"(d[8]), "=f"(d[9]), "=f"(d[10]), "=f"(d[11]), "=f"(d[12]), "=f"(d[13]), "=f"(d[14]), "=f"(d[15]), "=f"(d[16]), "=f"(d[17]), "=f"(d[18]), "=f"(d[19]), "=f"(d[20]), "=f"(d[21]), "=f"(d[22]), "=f"(d[23]), "=f"(d[24]), "=f"(d[25]), "=f"(d[26]), "=f"(d[27]), "=f"(d[28]), "=f"(d[29]), "=f"(d[30]), "=f"(d[31]), "=f"(d[32]), "=f"(d[33]), "=f"(d[34]), "=f"(d[35]), "=f"(d[36]), "=f"(d[37]), "=f"(d[38]), "=f"(d[39]), "=f"(d[40]), "=f"(d[41]), "=f"(d[42]), "=f"(d[43]), "=f"(d[44]), "=f"(d[45]), "=f"(d[46]), "=f"(d[47]), "=f"(d[48]), "=f"(d[49]), "=f"(d[50]), "=f"(d[51]), "=f"(d[52]), "=f"(d[53]), "=f"(d[54]), "=f"(d[55]), "=f"(d[56]), "=f"(d[57]), "=f"(d[58]), "=f"(d[59]), "=f"(d[60]), "=f"(d[61]), "=f"(d[62]), "=f"(d[63]), "=f"(d[64]), "=f"(d[65]), "=f"(d[66]), "=f"(d[67]), "=f"(d[68]), "=f"(d[69]), "=f"(d[70]), "=f"(d[71]), "=f"(d[72]), "=f"(d[73]), "=f"(d[74]), "=f"(d[75]), "=f"(d[76]), "=f"(d[77]), "=f"(d[78]), "=f"(d[79]), "=f"(d[80]), "=f"(d[81]), "=f"(d[82]), "=f"(d[83]), "=f"(d[84]), "=f"(d[85]), "=f"(d[86]), "=f"(d[87]), "=f"(d[88]), "=f"(d[89]), "=f"(d[90]), "=f"(d[91]), "=f"(d[92]), "=f"(d[93]), "=f"(d[94]), "=f"(d[95]), "=f"(d[96]), "=f"(d[97]), "=f"(d[98]), "=f"(d[99]), "=f"(d[100]), "=f"(d[101]), "=f"(d[102]), "=f"(d[103]), "=f"(d[104]), "=f"(d[105]), "=f"(d[106]), "=f"(d[107]), "=f"(d[108]), "=f"(d[109]), "=f"(d[110]), "=f"(d[111]), "=f"(d[112]), "=f"(d[113]), "=f"(d[114]), "=f"(d[115]), "=f"(d[116]), "=f"(d[117]), "=f"(d[118]), "=f"(d[119]), "=f"(d[120]), "=f"(d[121]), "=f"(d[122]), "=f"(d[123]), "=f"(d[124]), "=f"(d[125]), "=f"(d[126]), "=f"(d[127])
    : "l"(da), "l"(db));
}

template <int N> struct WG;
#define DEF_WG(N) template <> struct WG<N> { \
  static __device__ __forceinline__ void mma(float (&d)[N / 2], uint64_t a, uint64_t b) { wgmma_n##N(d, a, b); } \
  static __device__ __forceinline__ void first(float (&d)[N / 2], uint64_t a, uint64_t b) { wgmma_n##N##_first(d, a, b); } };
DEF_WG(128) DEF_WG(256)

constexpr uint64_t DESC_A = (1ull << 62) | ((uint64_t)(1024 >> 4) << 32) | (1ull << 16);
constexpr uint64_t DESC_B = (1ull << 62) | ((uint64_t)(1024 >> 4) << 32) | ((uint64_t)(8192 >> 4) << 16);

struct Ring { int s; uint32_t ph; int wrap; };
template <int NS> __device__ __forceinline__ void ring_next(Ring& r) { r.s = (r.s + 1 == NS) ? 0 : r.s + 1; if (r.s == r.wrap) r.ph ^= 1; }

__device__ __forceinline__ int own_order(int it, int j) {
  return it < 2 ? 2 * j + it : it < 4 ? 2 * (j ^ 1) + it - 2 : ((j >> 1) * 4 + 2 * it - (it < 10 ? 4 : 15)) & 15;
}

template <int V> struct IC { static constexpr int v = V; };
template <int I, int E, class F> __device__ __forceinline__ void static_for(F&& f) { if constexpr (I < E) { f(IC<I>{}); static_for<I + 1, E>(f); } }

template <int N, int NS, int PRE, int LAG, class Pre, class Mid, class Last>
__device__ __forceinline__ void mainloop(float (&acc)[N / 2], int nkb, bool own, Ring& r, uint32_t sb, int wg, int lane, uint32_t rel_base, Pre pre, Mid mid, Last last) {
  constexpr int SLOT = RING / NS;
  const uint32_t full = sb + MISC + (NS == 4 ? B_FULL4 : B_FULL6);
  const uint32_t rel = rel_base + (NS == 4 ? B_EMPTY4 : B_EMPTY6);
  const uint32_t s0 = (sb & 0x3FFFF) >> 4, a0 = s0 + wg * (HALF >> 4);
  int ps;
  auto issue = [&](int it, bool first) {
    const uint64_t da = DESC_A | (a0 + ((own && it < 2) ? (STG + it * BLK) >> 4 : r.s * (SLOT >> 4))), db = DESC_B | (s0 + r.s * (SLOT >> 4) + (BLK >> 4));
    mbar_wait(full + r.s * 8, r.ph);
    wg_arrive();
    if (first) WG<N>::first(acc, da, db); else WG<N>::mma(acc, da, db);
#pragma unroll
    for (int k = 1; k < 4; k++) WG<N>::mma(acc, da + k * 2, db + k * 128);
    wg_commit();
  };
  auto retire = [&](int it) {
    wg_wait<1>();
    if (lane < 2) mbar_arrive_cl(rel + ps * 8);
    ps = r.s;
    ring_next<NS>(r);
  };
  issue(0, true);
  ps = r.s;
  ring_next<NS>(r);
  static_for<1, PRE + 1>([&](auto ic) { issue(ic.v, false); pre(ic); retire(ic.v); });
#pragma unroll 1
  for (int it = PRE + 1; it < nkb; it++) {
    if (LAG && it == nkb - LAG && wg == 1) mbar_wait(sb + MISC + B_LAG, WOLAG && !own);
    issue(it, false); mid(it); retire(it);
  }
  last();
  wg_wait<0>();
  if (lane < 2) mbar_arrive_cl(rel + ps * 8);
}

__device__ __forceinline__ uint32_t tag_of(uint32_t ep) { return (ep & 127u) + 1u; }
__device__ __forceinline__ void ln_publish(const float (&v)[64], uint2* st, int j, int row0, int lane, uint32_t ep) {
  float s0 = 0, s1 = 0, s2 = 0, s3 = 0, q0 = 0, q1 = 0, q2 = 0, q3 = 0;
#pragma unroll
  for (int i = 0; i < 16; i++) {
    s0 += v[4 * i]; s1 += v[4 * i + 1]; s2 += v[4 * i + 2]; s3 += v[4 * i + 3];
    q0 = fmaf(v[4 * i], v[4 * i], q0); q1 = fmaf(v[4 * i + 1], v[4 * i + 1], q1); q2 = fmaf(v[4 * i + 2], v[4 * i + 2], q2); q3 = fmaf(v[4 * i + 3], v[4 * i + 3], q3);
  }
  s0 += s1; s2 += s3; q0 += q1; q2 += q3;
  const bool odd = lane & 1;
  float s = (odd ? s2 : s0) + __shfl_xor_sync(~0u, odd ? s0 : s2, 1), q = (odd ? q2 : q0) + __shfl_xor_sync(~0u, odd ? q0 : q2, 1);
  s += __shfl_xor_sync(~0u, s, 2); q += __shfl_xor_sync(~0u, q, 2);
  if ((lane & 3) < 2) st_rlx2(st + j * 128 + row0 + (lane & 1) * 8, __float_as_uint(s), (__float_as_uint(fmaf(s * (-1.f / 128), s, q)) & ~255u) | tag_of(ep));
}
__device__ __forceinline__ void ln_gather(const uint2* st, int row0, int lane, uint32_t ep, float& n0, float& r0, float& n1, float& r1, bool rnd) {
  const uint2* p = st + (lane & 2) * 256 + row0 + (lane & 1) * 8;
  const uint32_t tag = tag_of(ep);
  uint2 a, b, c, d; uint32_t n = 0;
  while (true) {
    a = ld_rlx2(p); b = ld_rlx2(p + 128); c = ld_rlx2(p + 256); d = ld_rlx2(p + 384);
    if ((((a.y ^ tag) | (b.y ^ tag) | (c.y ^ tag) | (d.y ^ tag)) & 255u) == 0) break;
    SPIN_GUARD(n);
  }
  __syncwarp();
  const uint32_t fix = tag ^ 128u;
  float s = (__uint_as_float(a.x) + __uint_as_float(b.x)) + (__uint_as_float(c.x) + __uint_as_float(d.x));
  float q = (__uint_as_float(a.y ^ fix) + __uint_as_float(b.y ^ fix)) + (__uint_as_float(c.y ^ fix) + __uint_as_float(d.y ^ fix));
  q = fmaf(fmaf(__uint_as_float(a.x), __uint_as_float(a.x), __uint_as_float(b.x) * __uint_as_float(b.x)) +
           fmaf(__uint_as_float(c.x), __uint_as_float(c.x), __uint_as_float(d.x) * __uint_as_float(d.x)), 1.f / 128, q);
  s += __shfl_xor_sync(~0u, s, 2); q += __shfl_xor_sync(~0u, q, 2);
  s *= 1.f / 1024;
  const float var = fmaxf(fmaf(-s, s, q * (1.f / 1024)), 0.f);
  float r;
  if (rnd) {
    float sd; asm("sqrt.approx.f32 %0, %1;" : "=f"(sd) : "f"(bf_round(bf_round(var) + 1e-5f)));
    r = rcp(bf_round(sd)); s = bf_round(s);
  } else r = rsqrtf(var + 1e-5f);
  const float nn = -s * r;
  const float ro = __shfl_xor_sync(~0u, r, 1), no = __shfl_xor_sync(~0u, nn, 1);
  const bool odd = lane & 1;
  r0 = odd ? ro : r; n0 = odd ? no : nn; r1 = odd ? r : ro; n1 = odd ? nn : no;
}
__device__ __forceinline__ void load_vec(uint32_t* w, uint32_t sb, int sec, int b, int lane) {
#pragma unroll
  for (int q = 0; q < 2; q++) { uint4 t = lds128(sb + MISC + MODV + sec * 256 + (lane & 3) * 64 + b * 32 + q * 16); w[4 * q] = t.x; w[4 * q + 1] = t.y; w[4 * q + 2] = t.z; w[4 * q + 3] = t.w; }
}
__device__ __forceinline__ void stage_done(uint32_t sb, int wg, int b, int lane) {
  fence_async_smem();
  __syncwarp();
  if (lane == 0) mbar_arrive(sb + MISC + B_RDY + b * 8);
}
__device__ __forceinline__ uint32_t hfma2(uint32_t a, uint32_t b, uint32_t c) { uint32_t r; asm("fma.rn.bf16x2 %0, %1, %2, %3;" : "=r"(r) : "r"(a), "r"(b), "r"(c)); return r; }
__device__ __forceinline__ void ln_apply(const float (&v)[64], const uint2* st, int row0, uint32_t ep, uint32_t sb, int sec_shift, int sec_scale, uint32_t stg_row, int wg, int lane) {
  uint32_t sc[16], sh[16];
#pragma unroll
  for (int b = 0; b < 2; b++) { load_vec(sc + 8 * b, sb, sec_scale, b, lane); load_vec(sh + 8 * b, sb, sec_shift, b, lane); }
  float n0, r0, n1, r1;
  ln_gather(st, row0, lane, ep, n0, r0, n1, r1, sec_shift == 0);
#pragma unroll
  for (int i = 0; i < 16; i += 2) {
    if (i == 8) { const float z = lds32f(sb + MISC + ZERO); n0 += z; n1 += z; }
    uint32_t w[4];
#pragma unroll
    for (int u = 0; u < 2; u++) {
      int q = i + u;
      w[2 * u] = hfma2(pack2(fmaf(v[4 * q], r0, n0), fmaf(v[4 * q + 1], r0, n0)), sc[q], sh[q]);
      w[2 * u + 1] = hfma2(pack2(fmaf(v[4 * q + 2], r1, n1), fmaf(v[4 * q + 3], r1, n1)), sc[q], sh[q]);
    }
    stsm4(stg_row + (i >> 3) * BLK + ((((i & 7) + (lane >> 4)) ^ (lane & 7)) << 4), w[0], w[1], w[2], w[3]);
    if ((i & 7) == 6) { stage_done(sb, wg, i >> 3, lane); }
  }
}
__device__ __forceinline__ uint32_t hmul2(uint32_t a, uint32_t b) { uint32_t r; asm("mul.rn.bf16x2 %0, %1, %2;" : "=r"(r) : "r"(a), "r"(b)); return r; }
__device__ __forceinline__ uint32_t silu_mul2(uint32_t g, uint32_t u) {
  const uint32_t h = hmul2(g, 0x3f003f00u);
  const float h0 = bf_lo(h), h1 = bf_hi(h);
  return hmul2(pack2(fmaf(h0, tanh_fast(h0), h0), fmaf(h1, tanh_fast(h1), h1)), u);
}

__device__ __forceinline__ void gemv_fma(float (&a)[8], uint4 w, float s) {
  a[0] = fmaf(bf_lo(w.x), s, a[0]); a[1] = fmaf(bf_hi(w.x), s, a[1]); a[2] = fmaf(bf_lo(w.y), s, a[2]); a[3] = fmaf(bf_hi(w.y), s, a[3]);
  a[4] = fmaf(bf_lo(w.z), s, a[4]); a[5] = fmaf(bf_hi(w.z), s, a[5]); a[6] = fmaf(bf_lo(w.w), s, a[6]); a[7] = fmaf(bf_hi(w.w), s, a[7]);
}
__device__ __forceinline__ float silu_c(float v) { return bf_round(__fdividef(v, 1.f + __expf(-v))); }
__device__ __forceinline__ float mod_gather(const uint32_t* p, uint32_t ep) {
  const uint32_t tag = tag_of(ep), fix = tag ^ 128u;
  uint32_t a, b, c, d, n = 0;
  while (true) {
    a = ld_rlx1(p); b = ld_rlx1(p + 128); c = ld_rlx1(p + 256); d = ld_rlx1(p + 384);
    if ((((a ^ tag) | (b ^ tag) | (c ^ tag) | (d ^ tag)) & 255u) == 0) break;
    SPIN_GUARD(n);
  }
  return (__uint_as_float(a ^ fix) + __uint_as_float(b ^ fix)) + (__uint_as_float(c ^ fix) + __uint_as_float(d ^ fix));
}
__device__ __forceinline__ void mod_store(uint32_t sb, int sec, int col, float v) {
  v = bf_round(v);
  if (sec == 1) v += 1.f;
  sts16(sb + MISC + MODV + sec * 256 + (((col >> 1) & 3) * 16 + (col >> 3)) * 4 + (col & 1) * 2, __float2bfloat16_rn(v));
}

__global__ void __cluster_dims__(2, 1, 1) __launch_bounds__(384, 1)
fused_kernel(const bf16* __restrict__ cvec, const bf16* __restrict__ wmod, Scratch* gs, int by_sm, const __grid_constant__ Maps maps) {
  extern __shared__ __align__(1024) uint8_t smem_raw[];
  const uint32_t sb = smem_u32(smem_raw);
  const int warp = __shfl_sync(~0u, threadIdx.x >> 5, 0), lane = threadIdx.x & 31;
  const int rank = blockIdx.x & 1;
  uint32_t sm; asm volatile("mov.u32 %0, %%smid;" : "=r"(sm));
  const int t = sm >> 1, v = t < 32 ? t : t < 60 ? t + 1 + (((t - 32) * 37) >> 8) : (t - 58) * 8;
  const int cid = !by_sm ? (blockIdx.x >> 1) - 2 : (t & ~1) == 60 ? t - 62 : (v & 1) * 32 + ((v >> 1) & 31);
  const bool extra = cid < 0;
  const int bid = cid * 2 + rank;
  const int m = cid >> 2, j = (cid & 3) * 2 + rank;
  const uint32_t bar = sb + MISC;

  if (warp >= 8) {
    asm volatile("setmaxnreg.dec.sync.aligned.u32 40;");
    if (extra) {
      if (warp == 8) {
        if (lane == 0) { for (int s = 0; s < 6; s++) { mbar_init(bar + B_FULL6 + s * 8, 1); mbar_init(bar + B_EMPTY6 + s * 8, 8); } fence_async_smem(); }
        __syncwarp();
        asm volatile("bar.arrive 2, 288;" ::: "memory");
        __nanosleep(XSLEEP);
#pragma unroll 1
        for (int it = 0, s = 0, par = 1; it < 64; it++) {
          mbar_wait(bar + B_EMPTY6 + s * 8, par);
          if (elect()) { mbar_expect_tx(bar + B_FULL6 + s * 8, 32768); tma_3d(sb + s * 32768, &maps.wmod, bar + B_FULL6 + s * 8, 0, (it & 15) * 64, 12 + (it >> 4) * 4 + bid); }
          if (++s == 6) { s = 0; par ^= 1; }
        }
      }
    } else if (warp < 10) {
      uint32_t s6 = 0, p6 = 1;
      auto next6 = [&]() { if (++s6 == 6) { s6 = 0; p6 ^= 1; } };
      auto drained4 = [&](int q, int late) { if (q < 5) mbar_wait(bar + B_EMPTY4 + (((late ? 0x10332 : 0x32110) >> (4 * q)) & 3) * 8, 1); };
      auto drained6 = [&](int q) { if (q < 3) mbar_wait(bar + B_EMPTY6 + ((0x154 >> (4 * q)) & 7) * 8, q >> 1); };
      auto skip6 = [&]() { mbar_wait(bar + B_EMPTY6 + s6 * 8, p6); if (elect()) mbar_arrive(bar + B_FULL6 + s6 * 8); next6(); };
      if (warp == 8) {
        const uint32_t t_start = clock();
        if (lane == 0) {
          if (sb & 1023) bail();
          for (int b = 0; b < 2; b++) mbar_init(bar + B_X + b * 8, 1);
          for (int s = 0; s < 4; s++) { mbar_init(bar + B_FULL4 + s * 8, 2); mbar_init(bar + B_EMPTY4 + s * 8, 16); }
          for (int s = 0; s < 6; s++) { mbar_init(bar + B_FULL6 + s * 8, 2); mbar_init(bar + B_EMPTY6 + s * 8, 16); }
          for (int b = 0; b < 2; b++) { mbar_init(bar + B_RDY + b * 8, 8); mbar_init(bar + B_FREE + b * 8, 1); mbar_init(bar + B_HH + b * 8, 1); }
          mbar_init(bar + B_MOD, 1); mbar_init(bar + B_LAG, 4); mbar_init(bar + B_HALO, 2); mbar_init(bar + B_ALL, 1); mbar_init(bar + B_HH2, 1);
          asm volatile("st.shared.u32 [%0], 0;" :: "r"(bar + ZERO) : "memory");
          asm volatile("fence.mbarrier_init.release.cluster;" ::: "memory");
          fence_async_smem();
        }
        __syncwarp();
        cl_arrive_relaxed();
        auto wide = [&](int s, int par, const CUtensorMap* m0, int a0, const CUtensorMap* m1, int a1, int kb, bool spaced) {
          const uint32_t full = bar + B_FULL4 + s * 8, d = sb + s * 49152 + BLK;
          mbar_wait(full + 32, par);
          const uint32_t t0 = clock();
          if (elect()) { mbar_expect_tx(full, 2 * BLK); tma_3d(d, m0, full, 0, kb * 64, a0); }
          if (spaced) while ((uint32_t)clock() - t0 < 300) {}
          if (elect()) tma_3d(d + BLK, m1, full, 0, kb * 64, a1);
          if (spaced) while ((uint32_t)clock() - t0 < 600) {}
        };
        while ((uint32_t)clock() - t_start < XDELAY) {}
        if (elect()) for (int b = 0; b < 2; b++) { mbar_expect_tx(bar + B_X + b * 8, BLK); tma_3d(sb + STG + b * BLK, &maps.x, bar + B_X + b * 8, j * 128 + b * 64, m * 64, 0); }
        mbar_wait(bar + B_X + 8, 0);
#pragma unroll 1
        for (int ph = 0; ph < 2; ph++) {
          const CUtensorMap* const m0 = ph ? &maps.w1 : &maps.wqkv;
#pragma unroll 1
          for (int it = 0; it < (ph ? 48 : 16); it++) {
            const int a = (ph ? it & 48 : 16) + 2 * j;
            if (ph) drained6(it);
            wide((it + 2 * ph) & 3, ~(it >> 2) & 1, m0, a, m0 + ph, ph ? a : a + 16, it < 16 ? own_order(it, j) : it & 15, it < 4);
            if (it >= 44) {
              if (it == 44) { mbar_wait(bar + B_FREE, 0); mbar_wait(bar + B_FREE + 8, 0); if (elect()) mbar_expect_tx(bar + B_X, 2 * BLK); }
              if (elect()) bulk_ld(sb + STG + (it - 44) * HALF, gs->x1 + bid * 2048 + (it - 44) * 512, HALF, bar + B_X);
            }
          }
#pragma unroll 1
          for (int it = 0; it < 16; it++) {
            const uint32_t full = bar + B_FULL6 + s6 * 8, d = sb + s6 * 32768 + BLK;
            drained4(it, ph);
            mbar_wait(full + 48, p6);
            if (elect()) {
              mbar_expect_tx(full, BLK);
              tma_3d(d, ph ? &maps.w1s : &maps.wqkv, full, 0, it * 64, ph ? 48 + j : 2 * j);
              if (ph) tma_3d(d + HALF, &maps.w3s, full, 0, it * 64, 48 + j);
            }
            next6();
          }
          const CUtensorMap* const m2 = ph ? &maps.w2 : &maps.wo;
#pragma unroll 1
          for (int it = 0; it < (ph ? 56 : 16); it++) {
            const uint32_t full = bar + B_FULL6 + s6 * 8;
            const int kb = ph ? it : own_order(it, j);
            mbar_wait(full + 48, p6);
            if (elect()) { mbar_expect_tx(full, BLK); tma_3d(sb + s6 * 32768 + BLK, m2, full, 0, kb * 64, 2 * j); }
            next6();
          }
          if (!ph) skip6();
        }
      } else {
        if (lane < 9) prefetch_map(&maps.x + lane);
        const uint32_t ep = gs->epoch[blockIdx.x] + 1;
        cl_arrive_relaxed(); cl_wait();
        auto plain = [&](uint32_t full, uint32_t empty, int par, uint32_t slot, const uint4* blk) {
          mbar_wait(empty, par);
          if (elect()) { mbar_expect_tx(full, BLK); bulk_ld_mc(slot + rank * HALF, blk + rank * 512, HALF, full); }
        };
        auto plain6 = [&](const uint4* blk) { plain(bar + B_FULL6 + s6 * 8, bar + B_EMPTY6 + s6 * 8, p6, sb + s6 * 32768, blk); next6(); };
        uint32_t ready = 0;
        auto poll = [&](int e) { ready = __ballot_sync(~0u, ld_acquire(gs->flag + (m * 128 + e * 16 + (lane & 14)) * FS) == ep); };
        auto need = [&](int e, uint32_t mask) {
          if ((ready & mask) != mask) {
            uint32_t n = 0;
            do { poll(e); SPIN_GUARD(n); } while ((ready & mask) != mask);
            fence_async_global();
          }
        };
        auto fresh = [&](int e, int it, uint32_t full, uint32_t empty, int par, uint32_t slot, uint4* src) {
          if (it >= 4) {
            const int kb = own_order(it, j);
            if (it < 10) need(e, 1u << kb); else if (it == 10) mbar_wait(bar + B_ALL, e & 1);
            plain(full, empty, par, slot, src + kb * 1024);
          } else {
            if (it == 0) ready = 0;
            mbar_wait(empty, par);
            if (it < 2) { if (elect()) mbar_arrive(full); }
            else {
              const int b = it > 2;
              const uint32_t to_peer = mapa(sb, rank ^ 1) - sb;
              if (elect()) mbar_expect_tx(full, BLK);
              const bool push = e != 1;
              mbar_wait(bar + (b ? (push ? B_RDY + 8 : B_FREE + 8) : B_RDY), e & 1);
              if (elect()) {
                if (b == 0) {
                  bulk_st(src + 2 * j * 1024, sb + STG, BLK);
                  bulk_commit();
                  bulk_wait_all();
                  mbar_arrive(bar + B_FREE);
                }
                if (b && push) bulk_push(slot + to_peer, sb + STG + BLK, BLK, full + to_peer);
                else {
                  fence_async_global();
                  bulk_ld(slot + to_peer, src + (2 * j + b) * 1024, BLK, full + to_peer);
                }
              }
              __syncwarp();
            }
          }
        };
        uint4* const h = gs->h + m * 16384;
#pragma unroll 1
        for (int e = 0; e < 3; e++) {
#pragma unroll 1
          for (int it = 0; it < 16; it++) {
            const int s = e == 1 ? s6 : (it + e) & 3;
            const uint32_t full = bar + (e == 1 ? B_FULL6 : B_FULL4) + s * 8;
            if (e == 2) drained6(it);
            fresh(e, it, full, full + (e == 1 ? 48 : 32), e == 1 ? p6 : ~(it >> 2) & 1, sb + s * (e == 1 ? 32768 : 49152), e == 1 ? gs->o + m * 16384 : h);
            if (e == 1) next6();
          }
          if (e == 1) { skip6(); continue; }
#pragma unroll 1
          for (int it = 16; it < 16 + 16 * e; it++) {
            const int s = (it + 2) & 3;
            const uint32_t full = bar + B_FULL4 + s * 8;
            plain(full, full + 32, ~(it >> 2) & 1, sb + s * 49152, h + (it & 15) * 1024);
          }
#pragma unroll 1
          for (int it = 0; it < 16; it++) { drained4(it, e); plain6(h + it * 1024); }
        }
#pragma unroll 1
        for (int it = 0; it < 56; it++) {
          if (it == 0 || it == 32 || it == 48) mbar_wait(bar + (it == 48 ? B_HH2 : B_HH + (it >> 2)), 0);
          plain6(gs->hh + m * 57344 + it * 1024);
        }
      }
    } else {
      const int b = warp - 10;
      const uint32_t ep = gs->epoch[blockIdx.x] + 1;
      const uint32_t stg = sb + STG + b * BLK;
      cl_arrive_relaxed(); cl_wait();
      auto all_there = [&](int u, uint32_t done) {
        const uint32_t* fl = gs->flag + u * FS;
        uint32_t n = 0;
        while (!__all_sync(~0u, ld_acquire(fl) == ep)) { __nanosleep(100); SPIN_GUARD(n); }
        fence_async_global();
        if (lane == 0) mbar_arrive(done);
      };
      auto fetch_mod = [&](int sec) {
        const uint4* p = (const uint4*)(gs->modv + (sec - 2) * 1024 + j * 128) + lane;
        uint4 v0, v1; uint32_t n = 0;
        while (true) {
          v0 = ld_rlx4(p); v1 = ld_rlx4(p + 32);
          if (v0.y == ep && v0.w == ep && v1.y == ep && v1.w == ep) break;
          SPIN_GUARD(n);
        }
        const uint32_t d = sb + MISC + MODV + sec * 256 + ((lane & 3) * 16 + (lane >> 2)) * 4;
        asm volatile("st.shared.u32 [%0], %1;" :: "r"(d), "r"(__byte_perm(v0.x, v0.z, 0x7632)) : "memory");
        asm volatile("st.shared.u32 [%0], %1;" :: "r"(d + 32), "r"(__byte_perm(v1.x, v1.z, 0x7632)) : "memory");
        __syncwarp();
      };
#pragma unroll 1
      for (int e = 0; e < 7 - b; e++) {
        if (lane == 0) {
          if (e < 3) {
            mbar_wait(bar + B_FREE, e & 1);
            if (b) {
              const uint32_t t0 = clock();
              while ((uint32_t)clock() - t0 < (e == 0 ? B1P : e == 2 ? B1P2 : B1D)) {}
              mbar_wait(bar + B_RDY + 8, e & 1);
              bulk_st((e == 1 ? gs->o : gs->h) + m * 16384 + (2 * j + 1) * 1024, stg, BLK);
              bulk_commit();
              bulk_wait_all();
              mbar_arrive(bar + B_FREE + 8);
            }
            st_release(gs->flag + (m * 128 + e * 16 + 2 * j + b) * FS, ep);
          } else {
            const int kb = (e < 6 ? 2 * (8 * (e - 3) + j) : 48 + j) + b;
            mbar_wait(bar + B_RDY + b * 8, e & 1);
#pragma unroll 1
            for (int q = 0; q < NPIECE; q++) { if (q) __nanosleep(PSLEEP); bulk_st(gs->hh + m * 57344 + kb * 1024 + q * (1024 / NPIECE), stg + q * (BLK / NPIECE), BLK / NPIECE); }
            bulk_commit();
            bulk_wait_all();
            mbar_arrive(bar + B_FREE + b * 8);
            st_release(gs->flag + (m * 128 + U_HH + kb) * FS, ep);
          }
        }
        __syncwarp();
        if (e < 3 && b) all_there(m * 128 + e * 16 + (lane & 15), bar + B_ALL);
        if (e == 4 && b) all_there(m * 128 + U_HH + lane, bar + B_HH);
        if (!b && (e == 1 || e == 2)) {
#pragma unroll 1
          for (int sec = e == 1 ? 2 : 5; sec < 4 + e; sec++) fetch_mod(sec);
          if (e == 1) { if (lane == 0) mbar_arrive(bar + B_MOD); }
        }
        if (e == 0) {
          mbar_wait(bar + B_EMPTY6 + 24, 0);
          __nanosleep(HSLEEP);
#pragma unroll 1
          for (int w = 0; w < 4; w++) {
            const uint4* hp = gs->halo + ((m * 8 + j) * 2 + (w & 1)) * 512 + b * 256 + (w >> 1) * 128 + lane;
            uint4 q[4] = {}; uint32_t n = 0;
            while (m > 0) {
              bool ok = true;
#pragma unroll
              for (int i = 0; i < 4; i++) q[i] = ld_rlx4(hp + i * 32);
#pragma unroll
              for (int i = 0; i < 4; i++) ok = ok && q[i].y == ep && q[i].w == ep;
              if (ok) break;
              SPIN_GUARD(n);
            }
#pragma unroll
            for (int i = 0; i < 2; i++) sts128(stg + lane * 16 + (w & 1) * HALF + (w >> 1) * 1024 + i * 512, q[2 * i].x, q[2 * i + 1].x, q[2 * i].z, q[2 * i + 1].z);
          }
          __syncwarp();
          if (lane == 0) mbar_arrive(bar + B_HALO);
        }
      }
      if (b) { all_there(m * 128 + U_HH + 32 + (lane & 15), bar + B_HH + 8); all_there(m * 128 + U_HH + 48 + (lane & 7), bar + B_HH2); }
    }
  } else {
    const int wg = warp >> 2, wq = warp & 3, tid = threadIdx.x;
    const int g = lane >> 2, c = lane & 3;
    const int sec0 = (m >> 1) & 1, hf0 = m & 1, ks0 = (m >> 2) & 3;
    uint4 wv[8];
    uint32_t ep0; uint16_t cv_;
    asm volatile("ld.global.nc.u16 %0, [%1];" : "=h"(cv_) : "l"(cvec + ks0 * 256 + warp * 32 + lane));
    asm volatile("ld.global.u32 %0, [%1];" : "=r"(ep0) : "l"(gs->epoch + (blockIdx.x | (lane & by_sm & 2))));
    if (!extra) {
      const bf16* wp = wmod + (size_t)(ks0 * 256 + warp * 32 + (lane >> 3)) * 6144 + sec0 * 1024 + j * 128 + hf0 * 64 + (lane & 7) * 8;
#pragma unroll
      for (int i = 0; i < 8; i++) wv[i] = ldg_nc(wp + (size_t)i * 4 * 6144);
    }
    asm volatile("setmaxnreg.inc.sync.aligned.u32 232;" ::: "memory");
    if (__builtin_expect(extra, 0)) {
      const uint32_t ep = ep0 + 1;
      float sv[4];
#pragma unroll
      for (int p = 0; p < 4; p++) sv[p] = silu_c(__bfloat162float(cvec[64 * (4 * p + (lane >> 3)) + 8 * warp + (lane & 7)]));
      named_bar(2, 288);
      int s = 0, par = 0;
#pragma unroll 1
      for (int sec = 0; sec < 4; sec++) {
        float a[8] = {0, 0, 0, 0, 0, 0, 0, 0};
#pragma unroll 1
        for (int it = 0; it < 16; it++) {
          const float sc = it < 4 ? sv[0] : it < 8 ? sv[1] : it < 12 ? sv[2] : sv[3];
          mbar_wait(bar + B_FULL6 + s * 8, par);
          uint4 w[8];
#pragma unroll
          for (int i = 0; i < 8; i++) w[i] = lds128(sb + s * 32768 + (warp * 8 + i) * 512 + lane * 16);
#pragma unroll
          for (int i = 0; i < 8; i++) gemv_fma(a, w[i], __shfl_sync(~0u, sc, (it & 3) * 8 + i));
          if (lane == 0) mbar_arrive(bar + B_EMPTY6 + s * 8);
          if (++s == 6) { s = 0; par ^= 1; }
        }
        const uint32_t red = sb + STG + sec * 8192;
        sts128(red + warp * 1024 + lane * 32, __float_as_uint(a[0]), __float_as_uint(a[1]), __float_as_uint(a[2]), __float_as_uint(a[3]));
        sts128(red + warp * 1024 + lane * 32 + 16, __float_as_uint(a[4]), __float_as_uint(a[5]), __float_as_uint(a[6]), __float_as_uint(a[7]));
        named_bar(1, 256);
        float t = 0;
#pragma unroll
        for (int q = 0; q < 8; q++) t += lds32f(red + q * 1024 + tid * 4);
        t = bf_round(t);
        if (sec == 2) t = bf_round(t + 1.f);
        st_rlx2(gs->modv + sec * 1024 + (bid + 4) * 256 + tid, __float_as_uint(t), ep);
      }
      if (tid == 0) gs->epoch[blockIdx.x] = ep;
      return;
    }
    const int row0 = wg * 64 + wq * 16 + g;
    if (c < 2) st_rlx2(gs->stat + m * 1024 + j * 128 + row0 + c * 8, 0, 0);
    if (tid < 64) st_rlx1(gs->modp + ((j * 2 + sec0) * 4 + ks0) * 128 + hf0 * 64 + tid, 0);
    cl_arrive_relaxed(); cl_wait();
    uint32_t ep;
    asm volatile("add.u32 %0, %1, 1;" : "=r"(ep) : "r"(ep0) : "memory");
    const float sc_ = silu_c(__uint_as_float((uint32_t)cv_ << 16));
    const uint32_t rel = mapa(bar, (lane & 1) ^ rank);
    const uint32_t stg_row = sb + STG + (wg * 64 + wq * 16 + (lane & 15)) * 128;
    const uint32_t fre = bar + B_FREE;
    Ring r4{0, 0, 0}, r6{0, 0, 0};
    auto none = [](auto) {};
    uint32_t xk[32];
    {
      float a[8] = {0, 0, 0, 0, 0, 0, 0, 0};
#pragma unroll
      for (int i = 0; i < 8; i++) gemv_fma(a, wv[i], __shfl_sync(~0u, sc_, i * 4 + (lane >> 3)));
#pragma unroll
      for (int i = 0; i < 8; i++) { a[i] += __shfl_xor_sync(~0u, a[i], 8); a[i] += __shfl_xor_sync(~0u, a[i], 16); }
      if (lane < 8) {
        sts128(sb + RED_OFF + warp * 256 + lane * 32, __float_as_uint(a[0]), __float_as_uint(a[1]), __float_as_uint(a[2]), __float_as_uint(a[3]));
        sts128(sb + RED_OFF + warp * 256 + lane * 32 + 16, __float_as_uint(a[4]), __float_as_uint(a[5]), __float_as_uint(a[6]), __float_as_uint(a[7]));
      }
      named_bar(1, 256);
      if (tid < 64) {
        float s = 0;
#pragma unroll
        for (int w = 0; w < 8; w++) s += lds32f(sb + RED_OFF + w * 256 + tid * 4);
        st_rlx1(gs->modp + ((j * 2 + sec0) * 4 + ks0) * 128 + hf0 * 64 + tid, (__float_as_uint(s) & ~255u) | tag_of(ep));
      }
      float v[64];
      mbar_wait(bar + B_X, 0); mbar_wait(bar + B_X + 8, 0);
#pragma unroll
      for (int i = 0; i < 16; i += 2) {
        uint32_t w0, w1, w2, w3;
        ldsm4(stg_row + (i >> 3) * BLK + ((((i & 7) + (lane >> 4)) ^ (lane & 7)) << 4), w0, w1, w2, w3);
        xk[2 * i] = w0; xk[2 * i + 1] = w1; xk[2 * i + 2] = w2; xk[2 * i + 3] = w3;
        v[4 * i] = bf_lo(w0); v[4 * i + 1] = bf_hi(w0); v[4 * i + 2] = bf_lo(w1); v[4 * i + 3] = bf_hi(w1);
        v[4 * i + 4] = bf_lo(w2); v[4 * i + 5] = bf_hi(w2); v[4 * i + 6] = bf_lo(w3); v[4 * i + 7] = bf_hi(w3);
      }
      ln_publish(v, gs->stat + m * 1024, j, row0, lane, ep);
      mod_store(sb, tid >> 7, tid & 127, mod_gather(gs->modp + (j * 2 + (tid >> 7)) * 512 + (tid & 127), ep));
      named_bar(1, 256);
      ln_apply(v, gs->stat + m * 1024, row0, ep, sb, 0, 1, stg_row, wg, lane);
      named_bar(1, 256);
    }
    {
      uint32_t kf[32], vf[32], pv[32];
      const bool first = wq == 0 && m == 0;
      const uint32_t xa = sb + STG + wg * HALF + wq * 2048 + lane * 16;
      {
        float acc[128];
        mainloop<256, 4, 0, 0>(acc, 16, true, r4, sb, wg, lane, rel, none, none, [&] {
          mbar_wait(fre + 8, 0);
          if (c < 2) st_rlx2(gs->stat + (16 + m) * 1024 + j * 128 + row0 + c * 8, 0, 0);
        });
#pragma unroll
        for (int i = 0; i < 32; i++) { kf[i] = pack2(acc[2 * i], acc[2 * i + 1]); vf[i] = pack2(acc[64 + 2 * i], acc[65 + 2 * i]); }
      }
      float acc[64];
      constexpr int QP = 2;
      mainloop<128, 6, 8 / QP, 0>(acc, 16, false, r6, sb, wg, lane, rel, [&](auto ic) {
        constexpr int q = (ic.v - 1) * QP;
#pragma unroll
        for (int i = 4 * q; i < 4 * (q + QP); i++) vf[i] = movm(vf[i]);
        if (wq == 3) {
          if (m < 15) {
            uint4* hp = gs->halo + (((m + 1) * 8 + j) * 2 + wg) * 512 + lane;
#pragma unroll
            for (int i = 2 * q; i < 2 * (q + QP); i++) st_rlx4(hp + i * 32, kf[2 * i + 1], ep, vf[2 * i + 1], ep);
          }
        } else {
#pragma unroll
          for (int i = q; i < q + QP; i++) sts128(xa + 2048 + (i >> 2) * BLK + (i & 3) * 512, kf[4 * i + 1], kf[4 * i + 3], vf[4 * i + 1], vf[4 * i + 3]);
        }
      }, none, [&] {
        named_bar(2 + wg, 128);
        if (wq == 0) mbar_wait(bar + B_HALO, 0);
#pragma unroll
        for (int i = 0; i < 8; i++) {
          uint4 q = lds128(xa + (i >> 2) * BLK + (i & 3) * 512);
          pv[4 * i] = q.x; pv[4 * i + 1] = q.y; pv[4 * i + 2] = q.z; pv[4 * i + 3] = q.w;
        }
        __syncwarp();
      });
      int gz = g;
#pragma unroll
      for (int b = 0; b < 2; b++) {
        const bool up0 = 2 * c > gz, up1 = 2 * c + 1 > gz;
        const uint32_t mup = (up0 ? 0xffffu : 0u) | (up1 ? 0xffff0000u : 0u);
        float l[2][4], mx[4];
#pragma unroll
        for (int h = 0; h < 2; h++) {
          uint32_t q[8];
          const int k = 16 * b + 8 * h;
#pragma unroll
          for (int i = 0; i < 8; i++) q[i] = pack2(acc[2 * k + 2 * i], acc[2 * k + 2 * i + 1]);
          float s0[4], s1[4], s2[4];
          mma16z(s0, q[0], q[1], q[2], q[3], pv[k], pv[k + 1]); mma16z(s1, q[0], q[1], q[2], q[3], kf[k], kf[k + 2]); mma16z(s2, q[0], q[1], q[2], q[3], kf[k + 1], kf[k + 3]);
          mma16(s0, q[4], q[5], q[6], q[7], pv[k + 4], pv[k + 5]); mma16(s1, q[4], q[5], q[6], q[7], kf[k + 4], kf[k + 6]); mma16(s2, q[4], q[5], q[6], q[7], kf[k + 5], kf[k + 7]);
          if (first) { s0[0] = -INFINITY; s0[1] = -INFINITY; }
          l[h][0] = up0 ? s0[0] : s1[0]; l[h][1] = up1 ? s0[1] : s1[1]; l[h][2] = up0 ? s1[2] : s2[2]; l[h][3] = up1 ? s1[3] : s2[3];
          mx[2 * h] = fmaxf(l[h][0], l[h][1]); mx[2 * h + 1] = fmaxf(l[h][2], l[h][3]);
        }
#pragma unroll
        for (int o = 1; o < 4; o <<= 1) {
#pragma unroll
          for (int h = 0; h < 4; h++) mx[h] = fmaxf(mx[h], __shfl_xor_sync(~0u, mx[h], o));
        }
#pragma unroll
        for (int h = 0; h < 2; h++) {
          const float n0 = -mx[2 * h] * SCL, n1 = -mx[2 * h + 1] * SCL;
          const uint32_t pa = pack2(ex2(fmaf(l[h][0], SCL, n0)), ex2(fmaf(l[h][1], SCL, n0))), pb = pack2(ex2(fmaf(l[h][2], SCL, n1)), ex2(fmaf(l[h][3], SCL, n1)));
          float sm[4];
          mma8z(sm, pa, pb, 0x3f803f80u);
          const float ia = rcp(sm[0]), ib = rcp(sm[2]);
#pragma unroll
          for (int i = 8 * b + 4 * h; i < 8 * b + 4 * h + 4; i += 2) {
            uint32_t of[4];
#pragma unroll
            for (int d = 0; d < 2; d++) {
              float o[4];
              mma16z(o, pa & ~mup, pb & mup, 0u, pb & ~mup, vf[2 * (i + d)], vf[2 * (i + d) + 1]);
              mma8(o, pa & mup, 0u, pv[2 * i + 2 + d]);
              of[2 * d] = pack2(o[0] * ia, o[1] * ia); of[2 * d + 1] = pack2(o[2] * ib, o[3] * ib);
            }
            stsm4(stg_row + b * BLK + ((((i & 7) + (lane >> 4)) ^ (lane & 7)) << 4), of[0], of[1], of[2], of[3]);
          }
        }
        stage_done(sb, wg, b, lane);
        if (b == 0) gz += __float_as_uint(lds32f(bar + ZERO));
      }
      named_bar(1, 256);
    }
    uint32_t pk[64];
    {
      float acc[64];
      mainloop<128, 6, 0, WOLAG>(acc, 16, true, r6, sb, wg, lane, rel, none, none, [&] {
        if (WOLAG && wg == 0 && lane == 0) mbar_arrive(bar + B_LAG);
        mbar_wait(bar + B_MOD, 0); mbar_wait(fre + 8, 1);
        load_vec(pk + 32, sb, 2, 0, lane); load_vec(pk + 40, sb, 2, 1, lane);
#pragma unroll
        for (int i = 0; i < 32; i++) { pk[i] = xk[i]; asm volatile("" : "+r"(pk[i])); }
      });
#pragma unroll
      for (int i = 0; i < 32; i++) {
        acc[2 * i] = fmaf(acc[2 * i], bf_lo(pk[32 + (i >> 1)]), bf_lo(pk[i]));
        acc[2 * i + 1] = fmaf(acc[2 * i + 1], bf_hi(pk[32 + (i >> 1)]), bf_hi(pk[i]));
      }
      ln_publish(acc, gs->stat + (16 + m) * 1024, j, row0, lane, ep);
      mbar_wait(bar + B_FULL6 + 16, 1);
      if (lane < 2) mbar_arrive_cl(rel + B_EMPTY6 + 16);
      ring_next<6>(r6);
#pragma unroll
      for (int i = 0; i < 32; i++) { pk[i] = pack2(acc[2 * i], acc[2 * i + 1]); pk[32 + i] = 0; }
      ln_apply(acc, gs->stat + (16 + m) * 1024, row0, ep, sb, 3, 4, stg_row, wg, lane);
      named_bar(1, 256);
    }
    auto swiglu = [&](int q, int uo, int par) {
      if ((q & 3) == 0 && par >= 0) mbar_wait(fre + 2 * q, par);
      uint32_t w[4];
#pragma unroll
      for (int u = 0; u < 4; u++) w[u] = silu_mul2(pk[4 * q + u], pk[uo + 4 * q + u]);
      stsm4(stg_row + (q >> 2) * BLK + ((((2 * q & 7) + (lane >> 4)) ^ (lane & 7)) << 4), w[0], w[1], w[2], w[3]);
    };
    r4.s = r4.wrap = 2;
#pragma unroll 1
    for (int t = 0; t < 3; t++) {
      float acc[128];
      mainloop<256, 4, 4, 0>(acc, 16, t == 0, r4, sb, wg, lane, rel, [&](auto ic) {
        if (t) {
          if (ic.v == 3) stage_done(sb, wg, 0, lane);
          swiglu(2 * ic.v - 2, 32, ~t & 1); swiglu(2 * ic.v - 1, 32, 0);
        }
      }, [&](int it) {
        if (t && it == 5) stage_done(sb, wg, 1, lane);
#pragma unroll
        for (int i = 0; i < 8; i++)
          if (t == 0 && it == 8 + i) gs->x1[bid * 2048 + (i >> 2) * 1024 + warp * 128 + (i & 3) * 32 + lane] = make_uint4(pk[4 * i], pk[4 * i + 1], pk[4 * i + 2], pk[4 * i + 3]);
      }, [&] { if (t == 0) fence_async_global(); else if (t == 2) mbar_wait(bar + B_X, 1); });
#pragma unroll
      for (int i = 0; i < 64; i++) pk[i] = pack2(acc[2 * i], acc[2 * i + 1]);
    }
    uint32_t x1[32];
    {
      float acc[64];
      mainloop<128, 6, 10, 0>(acc, 16, false, r6, sb, wg, lane, rel, [&](auto ic) {
        constexpr int b = ic.v > 5, q = ic.v - 5 * b;
        if (q == 1) {
          if (b) stage_done(sb, wg, 0, lane);
#pragma unroll
          for (int i = 4 * b; i < 4 * b + 4; i++) { const uint4 x = lds128(sb + STG + b * BLK + warp * 2048 + (i & 3) * 512 + lane * 16); x1[4 * i] = x.x; x1[4 * i + 1] = x.y; x1[4 * i + 2] = x.z; x1[4 * i + 3] = x.w; }
          __syncwarp();
        } else swiglu(4 * b + q - 2, 32, -1);
      }, [&](int it) { if (it == 11) stage_done(sb, wg, 1, lane); }, [] {});
#pragma unroll
      for (int i = 0; i < 32; i++) pk[i] = pack2(acc[2 * i], acc[2 * i + 1]);
    }
    {
      float acc[64];
      mainloop<128, 6, 4, TAILLAG>(acc, 56, false, r6, sb, wg, lane, rel, [&](auto ic) { swiglu(ic.v - 1, 16, 1); },
                                   [&](int it) { if (it == 5) stage_done(sb, wg, 0, lane); }, [&] {
        if (TAILLAG && wg == 0 && lane == 0) mbar_arrive(bar + B_LAG);
        load_vec(pk + 32, sb, 5, 0, lane); load_vec(pk + 40, sb, 5, 1, lane);
        mbar_wait(fre, 0); mbar_wait(fre + 8, 1);
      });
      __syncwarp();
      cl_arrive_relaxed();
#pragma unroll
      for (int i = 0; i < 16; i += 2) {
        uint32_t w[4];
#pragma unroll
        for (int u = 0; u < 4; u++) {
          const int q = 2 * i + u;
          w[u] = pack2(fmaf(acc[2 * q], bf_lo(pk[32 + (q >> 1)]), bf_lo(x1[q])), fmaf(acc[2 * q + 1], bf_hi(pk[32 + (q >> 1)]), bf_hi(x1[q])));
        }
        stsm4(stg_row + (i >> 3) * BLK + ((((i & 7) + (lane >> 4)) ^ (lane & 7)) << 4), w[0], w[1], w[2], w[3]);
        if ((i & 7) == 6) {
          fence_async_smem();
          named_bar(2 + wg, 128);
          if (wq == 0 && elect()) { tma_store_3d(&maps.out, sb + STG + (i >> 3) * BLK + wg * HALF, j * 128 + (i >> 3) * 64, m * 64, wg); bulk_commit(); }
          if (i < 8) x1[16] |= __float_as_uint(lds32f(bar + ZERO));
        }
      }
      if (wq == 0) bulk_wait_read();
      if (tid == 0) gs->epoch[blockIdx.x] = ep;
      cl_wait();
    }
  }
}

typedef CUresult (*EncodeFn)(CUtensorMap*, CUtensorMapDataType, cuuint32_t, void*, const cuuint64_t*, const cuuint64_t*, const cuuint32_t*, const cuuint32_t*,
                             CUtensorMapInterleave, CUtensorMapSwizzle, CUtensorMapL2promotion, CUtensorMapFloatOOBfill);

void make_map(EncodeFn fn, CUtensorMap* mp, const void* base, uint64_t d0, uint64_t d1, uint64_t d2, uint64_t s1, uint64_t s2, uint32_t b2, uint32_t b0 = 64) {
  cuuint64_t d[3] = {d0, d1, d2}, s[2] = {s1, s2};
  cuuint32_t b[3] = {b0, 64, b2}, e[3] = {1, 1, 1};
  fn(mp, CU_TENSOR_MAP_DATA_TYPE_BFLOAT16, 3, (void*)base, d, s, b, e, CU_TENSOR_MAP_INTERLEAVE_NONE, b0 == 64 ? CU_TENSOR_MAP_SWIZZLE_128B : CU_TENSOR_MAP_SWIZZLE_NONE,
     CU_TENSOR_MAP_L2_PROMOTION_L2_128B, CU_TENSOR_MAP_FLOAT_OOB_FILL_NONE);
}

__global__ void probe_kernel() {}
int max_clusters(int size) {
  cudaLaunchConfig_t cfg = {};
  cudaLaunchAttribute at;
  at.id = cudaLaunchAttributeClusterDimension; at.val.clusterDim.x = size; at.val.clusterDim.y = 1; at.val.clusterDim.z = 1;
  cfg.gridDim = dim3(size * 66); cfg.blockDim = dim3(384); cfg.dynamicSmemBytes = SMEM_BYTES; cfg.attrs = &at; cfg.numAttrs = 1;
  int n = 0;
  if (cudaOccupancyMaxActiveClusters(&n, probe_kernel, &cfg) != cudaSuccess) { cudaGetLastError(); return 0; }
  return n;
}

}

extern "C" void kernel_launch(void* const* d_in, const int* in_sizes, int n_in, void* d_out, int out_size) {
  static EncodeFn fn = nullptr;
  static int by_sm = 0;
  static Scratch* gs = nullptr;
  if (!fn) {
    void* p = nullptr; cudaDriverEntryPointQueryResult q;
    cudaGetDriverEntryPoint("cuTensorMapEncodeTiled", &p, cudaEnableDefault, &q);
    fn = (EncodeFn)p;
    cudaFuncSetAttribute(fused_kernel, cudaFuncAttributeMaxDynamicSharedMemorySize, SMEM_BYTES);
    int dev = 0, sms = 0;
    cudaGetSymbolAddress((void**)&gs, g_scratch);
    cudaGetDevice(&dev);
    cudaDeviceGetAttribute(&sms, cudaDevAttrMultiProcessorCount, dev);
    cudaFuncSetAttribute(probe_kernel, cudaFuncAttributeMaxDynamicSharedMemorySize, SMEM_BYTES);
    by_sm = sms == 132 && max_clusters(2) == 66 && max_clusters(4) == 30 && max_clusters(6) == 17 && max_clusters(8) == 15;
  }
  Maps mp;
  make_map(fn, &mp.x, d_in[0], D_, S_ / 2, 2, 4096, 2048, 2);
  make_map(fn, &mp.out, d_out, D_, S_ / 2, 2, 4096, 2048, 1);
  make_map(fn, &mp.wqkv, d_in[1], 64, D_, 3 * D_ / 64, 3 * D_ * 2, 128, 2);
  make_map(fn, &mp.wo, d_in[2], 64, D_, D_ / 64, D_ * 2, 128, 2);
  make_map(fn, &mp.w1, d_in[4], 64, D_, F_ / 64, F_ * 2, 128, 2);
  make_map(fn, &mp.w3, d_in[5], 64, D_, F_ / 64, F_ * 2, 128, 2);
  make_map(fn, &mp.w1s, d_in[4], 64, D_, F_ / 64, F_ * 2, 128, 1);
  make_map(fn, &mp.w3s, d_in[5], 64, D_, F_ / 64, F_ * 2, 128, 1);
  make_map(fn, &mp.w2, d_in[6], 64, F_, D_ / 64, D_ * 2, 128, 2);
  make_map(fn, &mp.wmod, d_in[8], 256, D_, 24, 6 * D_ * 2, 512, 1, 256);
  fused_kernel<<<132, 384, SMEM_BYTES>>>((const bf16*)d_in[7], (const bf16*)d_in[8], gs, by_sm, mp);
}
```

```cpp
#include <cuda_runtime.h>
#include <cuda_bf16.h>
#include <cuda.h>
#include <stdint.h>

typedef __nv_bfloat16 bf16;

namespace {

constexpr int S_ = 2048, D_ = 1024, F_ = 3584;
constexpr int BLK = 16384;
constexpr int HALF = 8192;
constexpr int RING = 196608;
constexpr int STG = RING;
constexpr int MISC = RING + 2 * BLK;
constexpr int SMEM_BYTES = MISC + 3072;
constexpr int B_FULL4 = 0, B_EMPTY4 = 32, B_FULL6 = 64, B_EMPTY6 = 112, B_RDY = 160, B_FREE = 176, B_LAG = 192, B_X = 208, B_MOD = 224, B_HALO = 232, B_HH = 256, B_ALL = 272, B_HH2 = 288, ZERO = 296;
constexpr int MODV = 512;
constexpr int RED_OFF = 0;
constexpr float SCL = 0.17677669529663687f * 1.4426950408889634f;
constexpr int U_HH = 64;
constexpr int FS = 8;
constexpr int NPIECE = 4, PSLEEP = 300;
constexpr int XSLEEP = 4000, HSLEEP = 400;
constexpr uint32_t XDELAY = 2000, GAP = 300;
constexpr uint32_t B1P = 3500, B1D = 900, B1P2 = 3200;
constexpr int WOLAG = 2, TAILLAG = 5;

struct Maps { CUtensorMap x, out, wqkv, wo, w1, w3, w1s, w3s, w2, wmod; };

struct Scratch {
  uint4 h[16 * 16 * 1024];
  uint4 o[16 * 16 * 1024];
  uint4 hh[16 * 56 * 1024];
  uint4 x1[128 * 8 * 256];
  uint2 stat[2 * 16 * 8 * 128];
  uint4 halo[16 * 8 * 2 * 512];
  uint32_t modp[8 * 2 * 4 * 128];
  uint2 modv[4 * 1024];
  uint32_t flag[16 * 128 * FS];
  uint32_t epoch[132];
};
__device__ __align__(1024) Scratch g_scratch;

__device__ __forceinline__ void bail() { asm volatile("st.global.u32 [%0], %1;" :: "l"(0ull), "r"(0) : "memory"); }
__device__ __forceinline__ uint32_t smem_u32(const void* p) { return (uint32_t)__cvta_generic_to_shared(p); }
__device__ __forceinline__ void mbar_init(uint32_t bar, uint32_t cnt) { asm volatile("mbarrier.init.shared::cta.b64 [%0], %1;" :: "r"(bar), "r"(cnt) : "memory"); }
__device__ __forceinline__ void mbar_expect_tx(uint32_t bar, uint32_t bytes) { asm volatile("mbarrier.arrive.expect_tx.shared::cta.b64 _, [%0], %1;" :: "r"(bar), "r"(bytes) : "memory"); }
__device__ __forceinline__ void mbar_arrive(uint32_t bar) { asm volatile("mbarrier.arrive.shared::cta.b64 _, [%0];" :: "r"(bar) : "memory"); }
__device__ __forceinline__ void mbar_arrive_cl(uint32_t cl_addr) { asm volatile("mbarrier.arrive.shared::cluster.b64 _, [%0];" :: "r"(cl_addr) : "memory"); }
__device__ __forceinline__ uint32_t mapa(uint32_t addr, uint32_t cta) { uint32_t r; asm("mapa.shared::cluster.u32 %0, %1, %2;" : "=r"(r) : "r"(addr), "r"(cta)); return r; }
__device__ __forceinline__ void mbar_wait(uint32_t bar, uint32_t parity) {
  asm volatile("{\n.reg .pred p;\n.reg .b32 n;\n.reg .b64 z;\nmov.b32 n, 0;\nmov.b64 z, 0;\n"
               "W: add.u32 n, n, 1;\nsetp.gt.u32 p, n, 0x400000;\n@p st.global.u32 [z], n;\n"
               "mbarrier.try_wait.parity.shared::cta.b64 p, [%0], %1;\n@!p bra W;\n}" :: "r"(bar), "r"(parity) : "memory");
}
__device__ __forceinline__ void tma_3d(uint32_t dst, const CUtensorMap* m, uint32_t bar, int c0, int c1, int c2) {
  asm volatile("cp.async.bulk.tensor.3d.shared::cluster.global.mbarrier::complete_tx::bytes [%0], [%1, {%3, %4, %5}], [%2];" :: "r"(dst), "l"(m), "r"(bar), "r"(c0), "r"(c1), "r"(c2) : "memory");
}
__device__ __forceinline__ void tma_store_3d(const CUtensorMap* m, uint32_t src, int c0, int c1, int c2) {
  asm volatile("cp.async.bulk.tensor.3d.global.shared::cta.bulk_group [%0, {%2, %3, %4}], [%1];" :: "l"(m), "r"(src), "r"(c0), "r"(c1), "r"(c2) : "memory");
}
__device__ __forceinline__ void bulk_ld(uint32_t dst, const void* src, uint32_t bytes, uint32_t bar) {
  asm volatile("cp.async.bulk.shared::cluster.global.mbarrier::complete_tx::bytes [%0], [%1], %2, [%3];" :: "r"(dst), "l"(src), "r"(bytes), "r"(bar) : "memory");
}
__device__ __forceinline__ void bulk_ld_mc(uint32_t dst, const void* src, uint32_t bytes, uint32_t bar) {
  asm volatile("cp.async.bulk.shared::cluster.global.mbarrier::complete_tx::bytes.multicast::cluster [%0], [%1], %2, [%3], %4;" :: "r"(dst), "l"(src), "r"(bytes), "r"(bar), "h"((uint16_t)3) : "memory");
}
__device__ __forceinline__ void bulk_push(uint32_t dst_cl, uint32_t src, uint32_t bytes, uint32_t bar_cl) {
  asm volatile("cp.async.bulk.shared::cluster.shared::cta.mbarrier::complete_tx::bytes [%0], [%1], %2, [%3];" :: "r"(dst_cl), "r"(src), "r"(bytes), "r"(bar_cl) : "memory");
}
__device__ __forceinline__ void bulk_st(void* dst, uint32_t src, uint32_t bytes) {
  asm volatile("cp.async.bulk.global.shared::cta.bulk_group [%0], [%1], %2;" :: "l"(dst), "r"(src), "r"(bytes) : "memory");
}
__device__ __forceinline__ void bulk_commit() { asm volatile("cp.async.bulk.commit_group;" ::: "memory"); }
__device__ __forceinline__ void bulk_wait_read() { asm volatile("cp.async.bulk.wait_group.read 0;" ::: "memory"); }
__device__ __forceinline__ void bulk_wait_all() { asm volatile("cp.async.bulk.wait_group 0;" ::: "memory"); }
__device__ __forceinline__ void fence_async_global() { asm volatile("fence.proxy.async.global;" ::: "memory"); }
__device__ __forceinline__ void fence_async_smem() { asm volatile("fence.proxy.async.shared::cta;" ::: "memory"); }
__device__ __forceinline__ void wg_arrive() { asm volatile("wgmma.fence.sync.aligned;" ::: "memory"); }
__device__ __forceinline__ void wg_commit() { asm volatile("wgmma.commit_group.sync.aligned;" ::: "memory"); }
template <int N> __device__ __forceinline__ void wg_wait() { asm volatile("wgmma.wait_group.sync.aligned %0;" :: "n"(N) : "memory"); }
__device__ __forceinline__ void cl_arrive_relaxed() { asm volatile("barrier.cluster.arrive.relaxed.aligned;" ::: "memory"); }
__device__ __forceinline__ void cl_wait() { asm volatile("barrier.cluster.wait.acquire.aligned;" ::: "memory"); }
__device__ __forceinline__ bool elect() { uint32_t p; asm volatile("{\n.reg .pred p;\nelect.sync _|p, 0xffffffff;\nselp.u32 %0, 1, 0, p;\n}" : "=r"(p)); return p; }
__device__ __forceinline__ void named_bar(int id, int n) { asm volatile("bar.sync %0, %1;" :: "r"(id), "r"(n) : "memory"); }
__device__ __forceinline__ uint32_t pack2(float lo, float hi) { uint32_t r; asm("cvt.rn.bf16x2.f32 %0, %1, %2;" : "=r"(r) : "f"(hi), "f"(lo)); return r; }
__device__ __forceinline__ float bf_lo(uint32_t w) { return __uint_as_float(w << 16); }
__device__ __forceinline__ float bf_hi(uint32_t w) { return __uint_as_float(w & 0xffff0000u); }
__device__ __forceinline__ float bf_round(float v) { return __bfloat162float(__float2bfloat16_rn(v)); }
__device__ __forceinline__ void stsm4(uint32_t addr, uint32_t a, uint32_t b, uint32_t c, uint32_t d) {
  asm volatile("stmatrix.sync.aligned.m8n8.x4.shared.b16 [%0], {%1, %2, %3, %4};" :: "r"(addr), "r"(a), "r"(b), "r"(c), "r"(d) : "memory");
}
__device__ __forceinline__ void ldsm4(uint32_t addr, uint32_t& a, uint32_t& b, uint32_t& c, uint32_t& d) {
  asm volatile("ldmatrix.sync.aligned.m8n8.x4.shared.b16 {%0, %1, %2, %3}, [%4];" : "=r"(a), "=r"(b), "=r"(c), "=r"(d) : "r"(addr) : "memory");
}
__device__ __forceinline__ uint32_t movm(uint32_t a) { uint32_t r; asm volatile("movmatrix.sync.aligned.m8n8.trans.b16 %0, %1;" : "=r"(r) : "r"(a)); return r; }
__device__ __forceinline__ void mma16(float (&d)[4], uint32_t a0, uint32_t a1, uint32_t a2, uint32_t a3, uint32_t b0, uint32_t b1) {
  asm("mma.sync.aligned.m16n8k16.row.col.f32.bf16.bf16.f32 {%0,%1,%2,%3}, {%4,%5,%6,%7}, {%8,%9}, {%0,%1,%2,%3};"
               : "+f"(d[0]), "+f"(d[1]), "+f"(d[2]), "+f"(d[3]) : "r"(a0), "r"(a1), "r"(a2), "r"(a3), "r"(b0), "r"(b1));
}
__device__ __forceinline__ void mma16z(float (&d)[4], uint32_t a0, uint32_t a1, uint32_t a2, uint32_t a3, uint32_t b0, uint32_t b1) {
  asm("mma.sync.aligned.m16n8k16.row.col.f32.bf16.bf16.f32 {%0,%1,%2,%3}, {%4,%5,%6,%7}, {%8,%9}, {%10,%10,%10,%10};"
      : "=f"(d[0]), "=f"(d[1]), "=f"(d[2]), "=f"(d[3]) : "r"(a0), "r"(a1), "r"(a2), "r"(a3), "r"(b0), "r"(b1), "f"(0.f));
}
__device__ __forceinline__ void mma8z(float (&d)[4], uint32_t a0, uint32_t a1, uint32_t b0) {
  asm("mma.sync.aligned.m16n8k8.row.col.f32.bf16.bf16.f32 {%0,%1,%2,%3}, {%4,%5}, {%6}, {%7,%7,%7,%7};"
      : "=f"(d[0]), "=f"(d[1]), "=f"(d[2]), "=f"(d[3]) : "r"(a0), "r"(a1), "r"(b0), "f"(0.f));
}
__device__ __forceinline__ void mma8(float (&d)[4], uint32_t a0, uint32_t a1, uint32_t b0) {
  asm("mma.sync.aligned.m16n8k8.row.col.f32.bf16.bf16.f32 {%0,%1,%2,%3}, {%4,%5}, {%6}, {%0,%1,%2,%3};"
               : "+f"(d[0]), "+f"(d[1]), "+f"(d[2]), "+f"(d[3]) : "r"(a0), "r"(a1), "r"(b0));
}
__device__ __forceinline__ uint4 lds128(uint32_t a) { uint4 v; asm volatile("ld.shared.v4.u32 {%0,%1,%2,%3}, [%4];" : "=r"(v.x), "=r"(v.y), "=r"(v.z), "=r"(v.w) : "r"(a) : "memory"); return v; }
__device__ __forceinline__ void sts128(uint32_t a, uint32_t x, uint32_t y, uint32_t z, uint32_t w) { asm volatile("st.shared.v4.u32 [%0], {%1,%2,%3,%4};" :: "r"(a), "r"(x), "r"(y), "r"(z), "r"(w) : "memory"); }
__device__ __forceinline__ float lds32f(uint32_t a) { float v; asm volatile("ld.shared.f32 %0, [%1];" : "=f"(v) : "r"(a) : "memory"); return v; }
__device__ __forceinline__ void sts16(uint32_t a, bf16 v) { asm volatile("st.shared.b16 [%0], %1;" :: "r"(a), "h"(__bfloat16_as_ushort(v)) : "memory"); }
__device__ __forceinline__ uint4 ldg_nc(const void* p) { uint4 v; asm volatile("ld.global.nc.L1::no_allocate.v4.u32 {%0,%1,%2,%3}, [%4];" : "=r"(v.x), "=r"(v.y), "=r"(v.z), "=r"(v.w) : "l"(p)); return v; }
__device__ __forceinline__ uint4 ld_rlx4(const uint4* p) {
  unsigned long long a, b; asm volatile("ld.relaxed.gpu.global.v2.b64 {%0,%1}, [%2];" : "=l"(a), "=l"(b) : "l"(p) : "memory");
  return make_uint4((uint32_t)a, (uint32_t)(a >> 32), (uint32_t)b, (uint32_t)(b >> 32));
}
__device__ __forceinline__ uint2 ld_rlx2(const uint2* p) { unsigned long long a; asm volatile("ld.relaxed.gpu.global.b64 %0, [%1];" : "=l"(a) : "l"(p) : "memory"); return make_uint2((uint32_t)a, (uint32_t)(a >> 32)); }
__device__ __forceinline__ void st_rlx4(uint4* p, uint32_t x, uint32_t y, uint32_t z, uint32_t w) {
  asm volatile("st.relaxed.gpu.global.v2.b64 [%0], {%1,%2};" :: "l"(p), "l"((unsigned long long)x | ((unsigned long long)y << 32)), "l"((unsigned long long)z | ((unsigned long long)w << 32)) : "memory");
}
__device__ __forceinline__ void st_rlx2(uint2* p, uint32_t x, uint32_t y) { asm volatile("st.relaxed.gpu.global.b64 [%0], %1;" :: "l"(p), "l"((unsigned long long)x | ((unsigned long long)y << 32)) : "memory"); }
__device__ __forceinline__ void st_rlx1(uint32_t* p, uint32_t v) { asm volatile("st.relaxed.gpu.global.u32 [%0], %1;" :: "l"(p), "r"(v) : "memory"); }
__device__ __forceinline__ uint32_t ld_rlx1(const uint32_t* p) { uint32_t v; asm volatile("ld.relaxed.gpu.global.u32 %0, [%1];" : "=r"(v) : "l"(p) : "memory"); return v; }
__device__ __forceinline__ void st_release(uint32_t* p, uint32_t v) { asm volatile("st.release.gpu.global.u32 [%0], %1;" :: "l"(p), "r"(v) : "memory"); }
__device__ __forceinline__ uint32_t ld_acquire(const uint32_t* p) { uint32_t v; asm volatile("ld.acquire.gpu.global.u32 %0, [%1];" : "=r"(v) : "l"(p) : "memory"); return v; }
__device__ __forceinline__ void prefetch_map(const CUtensorMap* m) { asm volatile("prefetch.tensormap [%0];" :: "l"(m) : "memory"); }
__device__ __forceinline__ float rcp(float x) { float r; asm("rcp.approx.ftz.f32 %0, %1;" : "=f"(r) : "f"(x)); return r; }
__device__ __forceinline__ float ex2(float x) { float r; asm("ex2.approx.ftz.f32 %0, %1;" : "=f"(r) : "f"(x)); return r; }
__device__ __forceinline__ float tanh_fast(float x) { float r; asm("tanh.approx.f32 %0, %1;" : "=f"(r) : "f"(x)); return r; }
#define SPIN_GUARD(n) if (++(n) > (1u << 24)) bail()

__device__ __forceinline__ void wgmma_n128(float (&d)[64], uint64_t da, uint64_t db) {
  asm volatile("wgmma.mma_async.sync.aligned.m64n128k16.f32.bf16.bf16 "
    "{%0, %1, %2, %3, %4, %5, %6, %7, %8, %9, %10, %11, %12, %13, %14, %15, %16, %17, %18, %19, %20, %21, %22, %23, %24, %25, %26, %27, %28, %29, %30, %31, %32, %33, %34, %35, %36, %37, %38, %39, %40, %41, %42, %43, %44, %45, %46, %47, %48, %49, %50, %51, %52, %53, %54, %55, %56, %57, %58, %59, %60, %61, %62, %63}, "
    "%64, %65, 1, 1, 1, 0, 1;\n"
    : "+f"(d[0]), "+f"(d[1]), "+f"(d[2]), "+f"(d[3]), "+f"(d[4]), "+f"(d[5]), "+f"(d[6]), "+f"(d[7]), "+f"(d[8]), "+f"(d[9]), "+f"(d[10]), "+f"(d[11]), "+f"(d[12]), "+f"(d[13]), "+f"(d[14]), "+f"(d[15]), "+f"(d[16]), "+f"(d[17]), "+f"(d[18]), "+f"(d[19]), "+f"(d[20]), "+f"(d[21]), "+f"(d[22]), "+f"(d[23]), "+f"(d[24]), "+f"(d[25]), "+f"(d[26]), "+f"(d[27]), "+f"(d[28]), "+f"(d[29]), "+f"(d[30]), "+f"(d[31]), "+f"(d[32]), "+f"(d[33]), "+f"(d[34]), "+f"(d[35]), "+f"(d[36]), "+f"(d[37]), "+f"(d[38]), "+f"(d[39]), "+f"(d[40]), "+f"(d[41]), "+f"(d[42]), "+f"(d[43]), "+f"(d[44]), "+f"(d[45]), "+f"(d[46]), "+f"(d[47]), "+f"(d[48]), "+f"(d[49]), "+f"(d[50]), "+f"(d[51]), "+f"(d[52]), "+f"(d[53]), "+f"(d[54]), "+f"(d[55]), "+f"(d[56]), "+f"(d[57]), "+f"(d[58]), "+f"(d[59]), "+f"(d[60]), "+f"(d[61]), "+f"(d[62]), "+f"(d[63])
    : "l"(da), "l"(db));
}
__device__ __forceinline__ void wgmma_n128_first(float (&d)[64], uint64_t da, uint64_t db) {
  asm volatile("wgmma.mma_async.sync.aligned.m64n128k16.f32.bf16.bf16 "
    "{%0, %1, %2, %3, %4, %5, %6, %7, %8, %9, %10, %11, %12, %13, %14, %15, %16, %17, %18, %19, %20, %21, %22, %23, %24, %25, %26, %27, %28, %29, %30, %31, %32, %33, %34, %35, %36, %37, %38, %39, %40, %41, %42, %43, %44, %45, %46, %47, %48, %49, %50, %51, %52, %53, %54, %55, %56, %57, %58, %59, %60, %61, %62, %63}, "
    "%64, %65, 0, 1, 1, 0, 1;\n"
    : "=f"(d[0]), "=f"(d[1]), "=f"(d[2]), "=f"(d[3]), "=f"(d[4]), "=f"(d[5]), "=f"(d[6]), "=f"(d[7]), "=f"(d[8]), "=f"(d[9]), "=f"(d[10]), "=f"(d[11]), "=f"(d[12]), "=f"(d[13]), "=f"(d[14]), "=f"(d[15]), "=f"(d[16]), "=f"(d[17]), "=f"(d[18]), "=f"(d[19]), "=f"(d[20]), "=f"(d[21]), "=f"(d[22]), "=f"(d[23]), "=f"(d[24]), "=f"(d[25]), "=f"(d[26]), "=f"(d[27]), "=f"(d[28]), "=f"(d[29]), "=f"(d[30]), "=f"(d[31]), "=f"(d[32]), "=f"(d[33]), "=f"(d[34]), "=f"(d[35]), "=f"(d[36]), "=f"(d[37]), "=f"(d[38]), "=f"(d[39]), "=f"(d[40]), "=f"(d[41]), "=f"(d[42]), "=f"(d[43]), "=f"(d[44]), "=f"(d[45]), "=f"(d[46]), "=f"(d[47]), "=f"(d[48]), "=f"(d[49]), "=f"(d[50]), "=f"(d[51]), "=f"(d[52]), "=f"(d[53]), "=f"(d[54]), "=f"(d[55]), "=f"(d[56]), "=f"(d[57]), "=f"(d[58]), "=f"(d[59]), "=f"(d[60]), "=f"(d[61]), "=f"(d[62]), "=f"(d[63])
    : "l"(da), "l"(db));
}
__device__ __forceinline__ void wgmma_n256(float (&d)[128], uint64_t da, uint64_t db) {
  asm volatile("wgmma.mma_async.sync.aligned.m64n256k16.f32.bf16.bf16 "
    "{%0, %1, %2, %3, %4, %5, %6, %7, %8, %9, %10, %11, %12, %13, %14, %15, %16, %17, %18, %19, %20, %21, %22, %23, %24, %25, %26, %27, %28, %29, %30, %31, %32, %33, %34, %35, %36, %37, %38, %39, %40, %41, %42, %43, %44, %45, %46, %47, %48, %49, %50, %51, %52, %53, %54, %55, %56, %57, %58, %59, %60, %61, %62, %63, %64, %65, %66, %67, %68, %69, %70, %71, %72, %73, %74, %75, %76, %77, %78, %79, %80, %81, %82, %83, %84, %85, %86, %87, %88, %89, %90, %91, %92, %93, %94, %95, %96, %97, %98, %99, %100, %101, %102, %103, %104, %105, %106, %107, %108, %109, %110, %111, %112, %113, %114, %115, %116, %117, %118, %119, %120, %121, %122, %123, %124, %125, %126, %127}, "
    "%128, %129, 1, 1, 1, 0, 1;\n"
    : "+f"(d[0]), "+f"(d[1]), "+f"(d[2]), "+f"(d[3]), "+f"(d[4]), "+f"(d[5]), "+f"(d[6]), "+f"(d[7]), "+f"(d[8]), "+f"(d[9]), "+f"(d[10]), "+f"(d[11]), "+f"(d[12]), "+f"(d[13]), "+f"(d[14]), "+f"(d[15]), "+f"(d[16]), "+f"(d[17]), "+f"(d[18]), "+f"(d[19]), "+f"(d[20]), "+f"(d[21]), "+f"(d[22]), "+f"(d[23]), "+f"(d[24]), "+f"(d[25]), "+f"(d[26]), "+f"(d[27]), "+f"(d[28]), "+f"(d[29]), "+f"(d[30]), "+f"(d[31]), "+f"(d[32]), "+f"(d[33]), "+f"(d[34]), "+f"(d[35]), "+f"(d[36]), "+f"(d[37]), "+f"(d[38]), "+f"(d[39]), "+f"(d[40]), "+f"(d[41]), "+f"(d[42]), "+f"(d[43]), "+f"(d[44]), "+f"(d[45]), "+f"(d[46]), "+f"(d[47]), "+f"(d[48]), "+f"(d[49]), "+f"(d[50]), "+f"(d[51]), "+f"(d[52]), "+f"(d[53]), "+f"(d[54]), "+f"(d[55]), "+f"(d[56]), "+f"(d[57]), "+f"(d[58]), "+f"(d[59]), "+f"(d[60]), "+f"(d[61]), "+f"(d[62]), "+f"(d[63]), "+f"(d[64]), "+f"(d[65]), "+f"(d[66]), "+f"(d[67]), "+f"(d[68]), "+f"(d[69]), "+f"(d[70]), "+f"(d[71]), "+f"(d[72]), "+f"(d[73]), "+f"(d[74]), "+f"(d[75]), "+f"(d[76]), "+f"(d[77]), "+f"(d[78]), "+f"(d[79]), "+f"(d[80]), "+f"(d[81]), "+f"(d[82]), "+f"(d[83]), "+f"(d[84]), "+f"(d[85]), "+f"(d[86]), "+f"(d[87]), "+f"(d[88]), "+f"(d[89]), "+f"(d[90]), "+f"(d[91]), "+f"(d[92]), "+f"(d[93]), "+f"(d[94]), "+f"(d[95]), "+f"(d[96]), "+f"(d[97]), "+f"(d[98]), "+f"(d[99]), "+f"(d[100]), "+f"(d[101]), "+f"(d[102]), "+f"(d[103]), "+f"(d[104]), "+f"(d[105]), "+f"(d[106]), "+f"(d[107]), "+f"(d[108]), "+f"(d[109]), "+f"(d[110]), "+f"(d[111]), "+f"(d[112]), "+f"(d[113]), "+f"(d[114]), "+f"(d[115]), "+f"(d[116]), "+f"(d[117]), "+f"(d[118]), "+f"(d[119]), "+f"(d[120]), "+f"(d[121]), "+f"(d[122]), "+f"(d[123]), "+f"(d[124]), "+f"(d[125]), "+f"(d[126]), "+f"(d[127])
    : "l"(da), "l"(db));
}
__device__ __forceinline__ void wgmma_n256_first(float (&d)[128], uint64_t da, uint64_t db) {
  asm volatile("wgmma.mma_async.sync.aligned.m64n256k16.f32.bf16.bf16 "
    "{%0, %1, %2, %3, %4, %5, %6, %7, %8, %9, %10, %11, %12, %13, %14, %15, %16, %17, %18, %19, %20, %21, %22, %23, %24, %25, %26, %27, %28, %29, %30, %31, %32, %33, %34, %35, %36, %37, %38, %39, %40, %41, %42, %43, %44, %45, %46, %47, %48, %49, %50, %51, %52, %53, %54, %55, %56, %57, %58, %59, %60, %61, %62, %63, %64, %65, %66, %67, %68, %69, %70, %71, %72, %73, %74, %75, %76, %77, %78, %79, %80, %81, %82, %83, %84, %85, %86, %87, %88, %89, %90, %91, %92, %93, %94, %95, %96, %97, %98, %99, %100, %101, %102, %103, %104, %105, %106, %107, %108, %109, %110, %111, %112, %113, %114, %115, %116, %117, %118, %119, %120, %121, %122, %123, %124, %125, %126, %127}, "
    "%128, %129, 0, 1, 1, 0, 1;\n"
    : "=f"(d[0]), "=f"(d[1]), "=f"(d[2]), "=f"(d[3]), "=f"(d[4]), "=f"(d[5]), "=f"(d[6]), "=f"(d[7]), "=f"(d[8]), "=f"(d[9]), "=f"(d[10]), "=f"(d[11]), "=f"(d[12]), "=f"(d[13]), "=f"(d[14]), "=f"(d[15]), "=f"(d[16]), "=f"(d[17]), "=f"(d[18]), "=f"(d[19]), "=f"(d[20]), "=f"(d[21]), "=f"(d[22]), "=f"(d[23]), "=f"(d[24]), "=f"(d[25]), "=f"(d[26]), "=f"(d[27]), "=f"(d[28]), "=f"(d[29]), "=f"(d[30]), "=f"(d[31]), "=f"(d[32]), "=f"(d[33]), "=f"(d[34]), "=f"(d[35]), "=f"(d[36]), "=f"(d[37]), "=f"(d[38]), "=f"(d[39]), "=f"(d[40]), "=f"(d[41]), "=f"(d[42]), "=f"(d[43]), "=f"(d[44]), "=f"(d[45]), "=f"(d[46]), "=f"(d[47]), "=f"(d[48]), "=f"(d[49]), "=f"(d[50]), "=f"(d[51]), "=f"(d[52]), "=f"(d[53]), "=f"(d[54]), "=f"(d[55]), "=f"(d[56]), "=f"(d[57]), "=f"(d[58]), "=f"(d[59]), "=f"(d[60]), "=f"(d[61]), "=f"(d[62]), "=f"(d[63]), "=f"(d[64]), "=f"(d[65]), "=f"(d[66]), "=f"(d[67]), "=f"(d[68]), "=f"(d[69]), "=f"(d[70]), "=f"(d[71]), "=f"(d[72]), "=f"(d[73]), "=f"(d[74]), "=f"(d[75]), "=f"(d[76]), "=f"(d[77]), "=f"(d[78]), "=f"(d[79]), "=f"(d[80]), "=f"(d[81]), "=f"(d[82]), "=f"(d[83]), "=f"(d[84]), "=f"(d[85]), "=f"(d[86]), "=f"(d[87]), "=f"(d[88]), "=f"(d[89]), "=f"(d[90]), "=f"(d[91]), "=f"(d[92]), "=f"(d[93]), "=f"(d[94]), "=f"(d[95]), "=f"(d[96]), "=f"(d[97]), "=f"(d[98]), "=f"(d[99]), "=f"(d[100]), "=f"(d[101]), "=f"(d[102]), "=f"(d[103]), "=f"(d[104]), "=f"(d[105]), "=f"(d[106]), "=f"(d[107]), "=f"(d[108]), "=f"(d[109]), "=f"(d[110]), "=f"(d[111]), "=f"(d[112]), "=f"(d[113]), "=f"(d[114]), "=f"(d[115]), "=f"(d[116]), "=f"(d[117]), "=f"(d[118]), "=f"(d[119]), "=f"(d[120]), "=f"(d[121]), "=f"(d[122]), "=f"(d[123]), "=f"(d[124]), "=f"(d[125]), "=f"(d[126]), "=f"(d[127])
    : "l"(da), "l"(db));
}

template <int N> struct WG;
#define DEF_WG(N) template <> struct WG<N> { \
  static __device__ __forceinline__ void mma(float (&d)[N / 2], uint64_t a, uint64_t b) { wgmma_n##N(d, a, b); } \
  static __device__ __forceinline__ void first(float (&d)[N / 2], uint64_t a, uint64_t b) { wgmma_n##N##_first(d, a, b); } };
DEF_WG(128) DEF_WG(256)

constexpr uint64_t DESC_A = (1ull << 62) | ((uint64_t)(1024 >> 4) << 32) | (1ull << 16);
constexpr uint64_t DESC_B = (1ull << 62) | ((uint64_t)(1024 >> 4) << 32) | ((uint64_t)(8192 >> 4) << 16);

struct Ring { int s; uint32_t ph; int wrap; };
template <int NS> __device__ __forceinline__ void ring_next(Ring& r) { r.s = (r.s + 1 == NS) ? 0 : r.s + 1; if (r.s == r.wrap) r.ph ^= 1; }

__device__ __forceinline__ int own_order(int it, int j) {
  return it < 2 ? 2 * j + it : it < 4 ? 2 * (j ^ 1) + it - 2 : ((j >> 1) * 4 + 2 * it - (it < 10 ? 4 : 15)) & 15;
}

template <int V> struct IC { static constexpr int v = V; };
template <int I, int E, class F> __device__ __forceinline__ void static_for(F&& f) { if constexpr (I < E) { f(IC<I>{}); static_for<I + 1, E>(f); } }

template <int N, int NS, int PRE, int LAG, class Pre, class Mid, class Last>
__device__ __forceinline__ void mainloop(float (&acc)[N / 2], int nkb, bool own, Ring& r, uint32_t sb, int wg, int lane, uint32_t rel_base, Pre pre, Mid mid, Last last) {
  constexpr int SLOT = RING / NS;
  const uint32_t full = sb + MISC + (NS == 4 ? B_FULL4 : B_FULL6);
  const uint32_t rel = rel_base + (NS == 4 ? B_EMPTY4 : B_EMPTY6);
  const uint32_t s0 = (sb & 0x3FFFF) >> 4, a0 = s0 + wg * (HALF >> 4);
  int ps;
  auto issue = [&](int it, bool first) {
    const uint64_t da = DESC_A | (a0 + ((own && it < 2) ? (STG + it * BLK) >> 4 : r.s * (SLOT >> 4))), db = DESC_B | (s0 + r.s * (SLOT >> 4) + (BLK >> 4));
    mbar_wait(full + r.s * 8, r.ph);
    wg_arrive();
    if (first) WG<N>::first(acc, da, db); else WG<N>::mma(acc, da, db);
#pragma unroll
    for (int k = 1; k < 4; k++) WG<N>::mma(acc, da + k * 2, db + k * 128);
    wg_commit();
  };
  auto retire = [&](int it) {
    wg_wait<1>();
    if (lane < 2) mbar_arrive_cl(rel + ps * 8);
    ps = r.s;
    ring_next<NS>(r);
  };
  issue(0, true);
  ps = r.s;
  ring_next<NS>(r);
  static_for<1, PRE + 1>([&](auto ic) { issue(ic.v, false); pre(ic); retire(ic.v); });
#pragma unroll 1
  for (int it = PRE + 1; it < nkb; it++) {
    if (LAG && it == nkb - LAG && wg == 1) mbar_wait(sb + MISC + B_LAG, WOLAG && !own);
    issue(it, false); mid(it); retire(it);
  }
  last();
  wg_wait<0>();
  if (lane < 2) mbar_arrive_cl(rel + ps * 8);
}

__device__ __forceinline__ uint32_t tag_of(uint32_t ep) { return (ep & 127u) + 1u; }
__device__ __forceinline__ void ln_publish(const float (&v)[64], uint2* st, int j, int row0, int lane, uint32_t ep) {
  float s0 = 0, s1 = 0, s2 = 0, s3 = 0, q0 = 0, q1 = 0, q2 = 0, q3 = 0;
#pragma unroll
  for (int i = 0; i < 16; i++) {
    s0 += v[4 * i]; s1 += v[4 * i + 1]; s2 += v[4 * i + 2]; s3 += v[4 * i + 3];
    q0 = fmaf(v[4 * i], v[4 * i], q0); q1 = fmaf(v[4 * i + 1], v[4 * i + 1], q1); q2 = fmaf(v[4 * i + 2], v[4 * i + 2], q2); q3 = fmaf(v[4 * i + 3], v[4 * i + 3], q3);
  }
  s0 += s1; s2 += s3; q0 += q1; q2 += q3;
  const bool odd = lane & 1;
  float s = (odd ? s2 : s0) + __shfl_xor_sync(~0u, odd ? s0 : s2, 1), q = (odd ? q2 : q0) + __shfl_xor_sync(~0u, odd ? q0 : q2, 1);
  s += __shfl_xor_sync(~0u, s, 2); q += __shfl_xor_sync(~0u, q, 2);
  if ((lane & 3) < 2) st_rlx2(st + j * 128 + row0 + (lane & 1) * 8, __float_as_uint(s), (__float_as_uint(fmaf(s * (-1.f / 128), s, q)) & ~255u) | tag_of(ep));
}
__device__ __forceinline__ void ln_gather(const uint2* st, int row0, int lane, uint32_t ep, float& n0, float& r0, float& n1, float& r1, bool rnd) {
  const uint2* p = st + (lane & 2) * 256 + row0 + (lane & 1) * 8;
  const uint32_t tag = tag_of(ep);
  uint2 a, b, c, d; uint32_t n = 0;
  while (true) {
    a = ld_rlx2(p); b = ld_rlx2(p + 128); c = ld_rlx2(p + 256); d = ld_rlx2(p + 384);
    if ((((a.y ^ tag) | (b.y ^ tag) | (c.y ^ tag) | (d.y ^ tag)) & 255u) == 0) break;
    SPIN_GUARD(n);
  }
  __syncwarp();
  const uint32_t fix = tag ^ 128u;
  float s = (__uint_as_float(a.x) + __uint_as_float(b.x)) + (__uint_as_float(c.x) + __uint_as_float(d.x));
  float q = (__uint_as_float(a.y ^ fix) + __uint_as_float(b.y ^ fix)) + (__uint_as_float(c.y ^ fix) + __uint_as_float(d.y ^ fix));
  q = fmaf(fmaf(__uint_as_float(a.x), __uint_as_float(a.x), __uint_as_float(b.x) * __uint_as_float(b.x)) +
           fmaf(__uint_as_float(c.x), __uint_as_float(c.x), __uint_as_float(d.x) * __uint_as_float(d.x)), 1.f / 128, q);
  s += __shfl_xor_sync(~0u, s, 2); q += __shfl_xor_sync(~0u, q, 2);
  s *= 1.f / 1024;
  const float var = fmaxf(fmaf(-s, s, q * (1.f / 1024)), 0.f);
  float r;
  if (rnd) {
    float sd; asm("sqrt.approx.f32 %0, %1;" : "=f"(sd) : "f"(bf_round(bf_round(var) + 1e-5f)));
    r = rcp(bf_round(sd)); s = bf_round(s);
  } else r = rsqrtf(var + 1e-5f);
  const float nn = -s * r;
  const float ro = __shfl_xor_sync(~0u, r, 1), no = __shfl_xor_sync(~0u, nn, 1);
  const bool odd = lane & 1;
  r0 = odd ? ro : r; n0 = odd ? no : nn; r1 = odd ? r : ro; n1 = odd ? nn : no;
}
__device__ __forceinline__ void load_vec(uint32_t* w, uint32_t sb, int sec, int b, int lane) {
#pragma unroll
  for (int q = 0; q < 2; q++) { uint4 t = lds128(sb + MISC + MODV + sec * 256 + (lane & 3) * 64 + b * 32 + q * 16); w[4 * q] = t.x; w[4 * q + 1] = t.y; w[4 * q + 2] = t.z; w[4 * q + 3] = t.w; }
}
__device__ __forceinline__ void stage_done(uint32_t sb, int wg, int b, int lane) {
  fence_async_smem();
  __syncwarp();
  if (lane == 0) mbar_arrive(sb + MISC + B_RDY + b * 8);
}
__device__ __forceinline__ uint32_t hfma2(uint32_t a, uint32_t b, uint32_t c) { uint32_t r; asm("fma.rn.bf16x2 %0, %1, %2, %3;" : "=r"(r) : "r"(a), "r"(b), "r"(c)); return r; }
__device__ __forceinline__ void ln_apply(const float (&v)[64], const uint2* st, int row0, uint32_t ep, uint32_t sb, int sec_shift, int sec_scale, uint32_t stg_row, int wg, int lane) {
  uint32_t sc[16], sh[16];
#pragma unroll
  for (int b = 0; b < 2; b++) { load_vec(sc + 8 * b, sb, sec_scale, b, lane); load_vec(sh + 8 * b, sb, sec_shift, b, lane); }
  float n0, r0, n1, r1;
  ln_gather(st, row0, lane, ep, n0, r0, n1, r1, sec_shift == 0);
#pragma unroll
  for (int i = 0; i < 16; i += 2) {
    if (i == 8) { const float z = lds32f(sb + MISC + ZERO); n0 += z; n1 += z; }
    uint32_t w[4];
#pragma unroll
    for (int u = 0; u < 2; u++) {
      int q = i + u;
      w[2 * u] = hfma2(pack2(fmaf(v[4 * q], r0, n0), fmaf(v[4 * q + 1], r0, n0)), sc[q], sh[q]);
      w[2 * u + 1] = hfma2(pack2(fmaf(v[4 * q + 2], r1, n1), fmaf(v[4 * q + 3], r1, n1)), sc[q], sh[q]);
    }
    stsm4(stg_row + (i >> 3) * BLK + ((((i & 7) + (lane >> 4)) ^ (lane & 7)) << 4), w[0], w[1], w[2], w[3]);
    if ((i & 7) == 6) { stage_done(sb, wg, i >> 3, lane); }
  }
}
__device__ __forceinline__ uint32_t hmul2(uint32_t a, uint32_t b) { uint32_t r; asm("mul.rn.bf16x2 %0, %1, %2;" : "=r"(r) : "r"(a), "r"(b)); return r; }
__device__ __forceinline__ uint32_t silu_mul2(uint32_t g, uint32_t u) {
  const uint32_t h = hmul2(g, 0x3f003f00u);
  const float h0 = bf_lo(h), h1 = bf_hi(h);
  return hmul2(pack2(fmaf(h0, tanh_fast(h0), h0), fmaf(h1, tanh_fast(h1), h1)), u);
}

__device__ __forceinline__ void gemv_fma(float (&a)[8], uint4 w, float s) {
  a[0] = fmaf(bf_lo(w.x), s, a[0]); a[1] = fmaf(bf_hi(w.x), s, a[1]); a[2] = fmaf(bf_lo(w.y), s, a[2]); a[3] = fmaf(bf_hi(w.y), s, a[3]);
  a[4] = fmaf(bf_lo(w.z), s, a[4]); a[5] = fmaf(bf_hi(w.z), s, a[5]); a[6] = fmaf(bf_lo(w.w), s, a[6]); a[7] = fmaf(bf_hi(w.w), s, a[7]);
}
__device__ __forceinline__ float silu_c(float v) { return bf_round(__fdividef(v, 1.f + __expf(-v))); }
__device__ __forceinline__ float mod_gather(const uint32_t* p, uint32_t ep) {
  const uint32_t tag = tag_of(ep), fix = tag ^ 128u;
  uint32_t a, b, c, d, n = 0;
  while (true) {
    a = ld_rlx1(p); b = ld_rlx1(p + 128); c = ld_rlx1(p + 256); d = ld_rlx1(p + 384);
    if ((((a ^ tag) | (b ^ tag) | (c ^ tag) | (d ^ tag)) & 255u) == 0) break;
    SPIN_GUARD(n);
  }
  return (__uint_as_float(a ^ fix) + __uint_as_float(b ^ fix)) + (__uint_as_float(c ^ fix) + __uint_as_float(d ^ fix));
}
__device__ __forceinline__ void mod_store(uint32_t sb, int sec, int col, float v) {
  v = bf_round(v);
  if (sec == 1) v += 1.f;
  sts16(sb + MISC + MODV + sec * 256 + (((col >> 1) & 3) * 16 + (col >> 3)) * 4 + (col & 1) * 2, __float2bfloat16_rn(v));
}

__global__ void __cluster_dims__(2, 1, 1) __launch_bounds__(384, 1)
fused_kernel(const bf16* __restrict__ cvec, const bf16* __restrict__ wmod, Scratch* gs, int by_sm, const __grid_constant__ Maps maps) {
  extern __shared__ __align__(1024) uint8_t smem_raw[];
  const uint32_t sb = smem_u32(smem_raw);
  const int warp = __shfl_sync(~0u, threadIdx.x >> 5, 0), lane = threadIdx.x & 31;
  const int rank = blockIdx.x & 1;
  uint32_t sm; asm volatile("mov.u32 %0, %%smid;" : "=r"(sm));
  const int t = sm >> 1, v = t < 32 ? t : t < 60 ? t + 1 + (((t - 32) * 37) >> 8) : (t - 58) * 8;
  const int cid = !by_sm ? (blockIdx.x >> 1) - 2 : (t & ~1) == 60 ? t - 62 : (v & 1) * 32 + ((v >> 1) & 31);
  const bool extra = cid < 0;
  const int bid = cid * 2 + rank;
  const int m = cid >> 2, j = (cid & 3) * 2 + rank;
  const uint32_t bar = sb + MISC;

  if (warp >= 8) {
    asm volatile("setmaxnreg.dec.sync.aligned.u32 40;");
    if (extra) {
      if (warp == 8) {
        if (lane == 0) { for (int s = 0; s < 6; s++) { mbar_init(bar + B_FULL6 + s * 8, 1); mbar_init(bar + B_EMPTY6 + s * 8, 8); } fence_async_smem(); }
        __syncwarp();
        asm volatile("bar.arrive 2, 288;" ::: "memory");
        __nanosleep(XSLEEP);
#pragma unroll 1
        for (int it = 0, s = 0, par = 1; it < 64; it++) {
          mbar_wait(bar + B_EMPTY6 + s * 8, par);
          if (elect()) { mbar_expect_tx(bar + B_FULL6 + s * 8, 32768); tma_3d(sb + s * 32768, &maps.wmod, bar + B_FULL6 + s * 8, 0, (it & 15) * 64, 12 + (it >> 4) * 4 + bid); }
          if (++s == 6) { s = 0; par ^= 1; }
        }
      }
    } else if (warp < 10) {
      uint32_t s6 = 0, p6 = 1;
      auto next6 = [&]() { if (++s6 == 6) { s6 = 0; p6 ^= 1; } };
      auto drained4 = [&](int q, int late) { if (q < 5) mbar_wait(bar + B_EMPTY4 + (((late ? 0x10332 : 0x32110) >> (4 * q)) & 3) * 8, 1); };
      auto drained6 = [&](int q) { if (q < 3) mbar_wait(bar + B_EMPTY6 + ((0x154 >> (4 * q)) & 7) * 8, q >> 1); };
      auto skip6 = [&]() { mbar_wait(bar + B_EMPTY6 + s6 * 8, p6); if (elect()) mbar_arrive(bar + B_FULL6 + s6 * 8); next6(); };
      if (warp == 8) {
        const uint32_t t_start = clock();
        if (lane == 0) {
          if (sb & 1023) bail();
          for (int b = 0; b < 2; b++) mbar_init(bar + B_X + b * 8, 1);
          for (int s = 0; s < 4; s++) { mbar_init(bar + B_FULL4 + s * 8, 2); mbar_init(bar + B_EMPTY4 + s * 8, 16); }
          for (int s = 0; s < 6; s++) { mbar_init(bar + B_FULL6 + s * 8, 2); mbar_init(bar + B_EMPTY6 + s * 8, 16); }
          for (int b = 0; b < 2; b++) { mbar_init(bar + B_RDY + b * 8, 8); mbar_init(bar + B_FREE + b * 8, 1); mbar_init(bar + B_HH + b * 8, 1); }
          mbar_init(bar + B_MOD, 1); mbar_init(bar + B_LAG, 4); mbar_init(bar + B_HALO, 2); mbar_init(bar + B_ALL, 1); mbar_init(bar + B_HH2, 1);
          asm volatile("st.shared.u32 [%0], 0;" :: "r"(bar + ZERO) : "memory");
          asm volatile("fence.mbarrier_init.release.cluster;" ::: "memory");
          fence_async_smem();
        }
        __syncwarp();
        cl_arrive_relaxed();
        auto wide = [&](int s, int par, const CUtensorMap* m0, int a0, const CUtensorMap* m1, int a1, int kb, bool spaced) {
          const uint32_t full = bar + B_FULL4 + s * 8, d = sb + s * 49152 + BLK;
          mbar_wait(full + 32, par);
          const uint32_t t0 = clock();
          if (elect()) { mbar_expect_tx(full, 2 * BLK); tma_3d(d, m0, full, 0, kb * 64, a0); }
          if (spaced) while ((uint32_t)clock() - t0 < GAP) {}
          if (elect()) tma_3d(d + BLK, m1, full, 0, kb * 64, a1);
          if (spaced) while ((uint32_t)clock() - t0 < 2 * GAP) {}
        };
        while ((uint32_t)clock() - t_start < XDELAY) {}
        if (elect()) for (int b = 0; b < 2; b++) { mbar_expect_tx(bar + B_X + b * 8, BLK); tma_3d(sb + STG + b * BLK, &maps.x, bar + B_X + b * 8, j * 128 + b * 64, m * 64, 0); }
        mbar_wait(bar + B_X + 8, 0);
#pragma unroll 1
        for (int ph = 0; ph < 2; ph++) {
          const CUtensorMap* const m0 = ph ? &maps.w1 : &maps.wqkv;
#pragma unroll 1
          for (int it = 0; it < (ph ? 48 : 16); it++) {
            const int a = (ph ? it & 48 : 16) + 2 * j;
            if (ph) drained6(it);
            wide((it + 2 * ph) & 3, ~(it >> 2) & 1, m0, a, m0 + ph, ph ? a : a + 16, it < 16 ? own_order(it, j) : it & 15, it < 4);
            if (it >= 44) {
              if (it == 44) { mbar_wait(bar + B_FREE, 0); mbar_wait(bar + B_FREE + 8, 0); if (elect()) mbar_expect_tx(bar + B_X, 2 * BLK); }
              if (elect()) bulk_ld(sb + STG + (it - 44) * HALF, gs->x1 + bid * 2048 + (it - 44) * 512, HALF, bar + B_X);
            }
          }
#pragma unroll 1
          for (int it = 0; it < 16; it++) {
            const uint32_t full = bar + B_FULL6 + s6 * 8, d = sb + s6 * 32768 + BLK;
            drained4(it, ph);
            mbar_wait(full + 48, p6);
            if (elect()) {
              mbar_expect_tx(full, BLK);
              tma_3d(d, ph ? &maps.w1s : &maps.wqkv, full, 0, it * 64, ph ? 48 + j : 2 * j);
              if (ph) tma_3d(d + HALF, &maps.w3s, full, 0, it * 64, 48 + j);
            }
            next6();
          }
          const CUtensorMap* const m2 = ph ? &maps.w2 : &maps.wo;
#pragma unroll 1
          for (int it = 0; it < (ph ? 56 : 16); it++) {
            const uint32_t full = bar + B_FULL6 + s6 * 8;
            const int kb = ph ? it : own_order(it, j);
            mbar_wait(full + 48, p6);
            if (elect()) { mbar_expect_tx(full, BLK); tma_3d(sb + s6 * 32768 + BLK, m2, full, 0, kb * 64, 2 * j); }
            next6();
          }
          if (!ph) skip6();
        }
      } else {
        if (lane < 9) prefetch_map(&maps.x + lane);
        const uint32_t ep = gs->epoch[blockIdx.x] + 1;
        cl_arrive_relaxed(); cl_wait();
        auto plain = [&](uint32_t full, uint32_t empty, int par, uint32_t slot, const uint4* blk) {
          mbar_wait(empty, par);
          if (elect()) { mbar_expect_tx(full, BLK); bulk_ld_mc(slot + rank * HALF, blk + rank * 512, HALF, full); }
        };
        auto plain6 = [&](const uint4* blk) { plain(bar + B_FULL6 + s6 * 8, bar + B_EMPTY6 + s6 * 8, p6, sb + s6 * 32768, blk); next6(); };
        uint32_t ready = 0;
        auto poll = [&](int e) { ready = __ballot_sync(~0u, ld_acquire(gs->flag + (m * 128 + e * 16 + (lane & 14)) * FS) == ep); };
        auto need = [&](int e, uint32_t mask) {
          if ((ready & mask) != mask) {
            uint32_t n = 0;
            do { poll(e); SPIN_GUARD(n); } while ((ready & mask) != mask);
            fence_async_global();
          }
        };
        auto fresh = [&](int e, int it, uint32_t full, uint32_t empty, int par, uint32_t slot, uint4* src) {
          if (it >= 4) {
            const int kb = own_order(it, j);
            if (it < 10) need(e, 1u << kb); else if (it == 10) mbar_wait(bar + B_ALL, e & 1);
            plain(full, empty, par, slot, src + kb * 1024);
          } else {
            if (it == 0) ready = 0;
            mbar_wait(empty, par);
            if (it < 2) { if (elect()) mbar_arrive(full); }
            else {
              const int b = it > 2;
              const uint32_t to_peer = mapa(sb, rank ^ 1) - sb;
              if (elect()) mbar_expect_tx(full, BLK);
              const bool push = e != 1;
              mbar_wait(bar + (b ? (push ? B_RDY + 8 : B_FREE + 8) : B_RDY), e & 1);
              if (elect()) {
                if (b == 0) {
                  bulk_st(src + 2 * j * 1024, sb + STG, BLK);
                  bulk_commit();
                  bulk_wait_all();
                  mbar_arrive(bar + B_FREE);
                }
                if (b && push) bulk_push(slot + to_peer, sb + STG + BLK, BLK, full + to_peer);
                else {
                  fence_async_global();
                  bulk_ld(slot + to_peer, src + (2 * j + b) * 1024, BLK, full + to_peer);
                }
              }
              __syncwarp();
            }
          }
        };
        uint4* const h = gs->h + m * 16384;
#pragma unroll 1
        for (int e = 0; e < 3; e++) {
#pragma unroll 1
          for (int it = 0; it < 16; it++) {
            const int s = e == 1 ? s6 : (it + e) & 3;
            const uint32_t full = bar + (e == 1 ? B_FULL6 : B_FULL4) + s * 8;
            if (e == 2) drained6(it);
            fresh(e, it, full, full + (e == 1 ? 48 : 32), e == 1 ? p6 : ~(it >> 2) & 1, sb + s * (e == 1 ? 32768 : 49152), e == 1 ? gs->o + m * 16384 : h);
            if (e == 1) next6();
          }
          if (e == 1) { skip6(); continue; }
#pragma unroll 1
          for (int it = 16; it < 16 + 16 * e; it++) {
            const int s = (it + 2) & 3;
            const uint32_t full = bar + B_FULL4 + s * 8;
            plain(full, full + 32, ~(it >> 2) & 1, sb + s * 49152, h + (it & 15) * 1024);
          }
#pragma unroll 1
          for (int it = 0; it < 16; it++) { drained4(it, e); plain6(h + it * 1024); }
        }
#pragma unroll 1
        for (int it = 0; it < 56; it++) {
          if (it == 0 || it == 32 || it == 48) mbar_wait(bar + (it == 48 ? B_HH2 : B_HH + (it >> 2)), 0);
          plain6(gs->hh + m * 57344 + it * 1024);
        }
      }
    } else {
      const int b = warp - 10;
      const uint32_t ep = gs->epoch[blockIdx.x] + 1;
      const uint32_t stg = sb + STG + b * BLK;
      cl_arrive_relaxed(); cl_wait();
      auto all_there = [&](int u, uint32_t done) {
        const uint32_t* fl = gs->flag + u * FS;
        uint32_t n = 0;
        while (!__all_sync(~0u, ld_acquire(fl) == ep)) { __nanosleep(100); SPIN_GUARD(n); }
        fence_async_global();
        if (lane == 0) mbar_arrive(done);
      };
      auto fetch_mod = [&](int sec) {
        const uint4* p = (const uint4*)(gs->modv + (sec - 2) * 1024 + j * 128) + lane;
        uint4 v0, v1; uint32_t n = 0;
        while (true) {
          v0 = ld_rlx4(p); v1 = ld_rlx4(p + 32);
          if (v0.y == ep && v0.w == ep && v1.y == ep && v1.w == ep) break;
          SPIN_GUARD(n);
        }
        const uint32_t d = sb + MISC + MODV + sec * 256 + ((lane & 3) * 16 + (lane >> 2)) * 4;
        asm volatile("st.shared.u32 [%0], %1;" :: "r"(d), "r"(__byte_perm(v0.x, v0.z, 0x7632)) : "memory");
        asm volatile("st.shared.u32 [%0], %1;" :: "r"(d + 32), "r"(__byte_perm(v1.x, v1.z, 0x7632)) : "memory");
        __syncwarp();
      };
#pragma unroll 1
      for (int e = 0; e < 7 - b; e++) {
        if (lane == 0) {
          if (e < 3) {
            mbar_wait(bar + B_FREE, e & 1);
            if (b) {
              const uint32_t t0 = clock();
              while ((uint32_t)clock() - t0 < (e == 0 ? B1P : e == 2 ? B1P2 : B1D)) {}
              mbar_wait(bar + B_RDY + 8, e & 1);
              bulk_st((e == 1 ? gs->o : gs->h) + m * 16384 + (2 * j + 1) * 1024, stg, BLK);
              bulk_commit();
              bulk_wait_all();
              mbar_arrive(bar + B_FREE + 8);
            }
            st_release(gs->flag + (m * 128 + e * 16 + 2 * j + b) * FS, ep);
          } else {
            const int kb = (e < 6 ? 2 * (8 * (e - 3) + j) : 48 + j) + b;
            mbar_wait(bar + B_RDY + b * 8, e & 1);
#pragma unroll 1
            for (int q = 0; q < NPIECE; q++) { if (q) __nanosleep(PSLEEP); bulk_st(gs->hh + m * 57344 + kb * 1024 + q * (1024 / NPIECE), stg + q * (BLK / NPIECE), BLK / NPIECE); }
            bulk_commit();
            bulk_wait_all();
            mbar_arrive(bar + B_FREE + b * 8);
            st_release(gs->flag + (m * 128 + U_HH + kb) * FS, ep);
          }
        }
        __syncwarp();
        if (e < 3 && b) all_there(m * 128 + e * 16 + (lane & 15), bar + B_ALL);
        if (e == 4 && b) all_there(m * 128 + U_HH + lane, bar + B_HH);
        if (!b && (e == 1 || e == 2)) {
#pragma unroll 1
          for (int sec = e == 1 ? 2 : 5; sec < 4 + e; sec++) fetch_mod(sec);
          if (e == 1) { if (lane == 0) mbar_arrive(bar + B_MOD); }
        }
        if (e == 0) {
          mbar_wait(bar + B_EMPTY6 + 24, 0);
          __nanosleep(HSLEEP);
#pragma unroll 1
          for (int w = 0; w < 4; w++) {
            const uint4* hp = gs->halo + ((m * 8 + j) * 2 + (w & 1)) * 512 + b * 256 + (w >> 1) * 128 + lane;
            uint4 q[4] = {}; uint32_t n = 0;
            while (m > 0) {
              bool ok = true;
#pragma unroll
              for (int i = 0; i < 4; i++) q[i] = ld_rlx4(hp + i * 32);
#pragma unroll
              for (int i = 0; i < 4; i++) ok = ok && q[i].y == ep && q[i].w == ep;
              if (ok) break;
              SPIN_GUARD(n);
            }
#pragma unroll
            for (int i = 0; i < 2; i++) sts128(stg + lane * 16 + (w & 1) * HALF + (w >> 1) * 1024 + i * 512, q[2 * i].x, q[2 * i + 1].x, q[2 * i].z, q[2 * i + 1].z);
          }
          __syncwarp();
          if (lane == 0) mbar_arrive(bar + B_HALO);
        }
      }
      if (b) { all_there(m * 128 + U_HH + 32 + (lane & 15), bar + B_HH + 8); all_there(m * 128 + U_HH + 48 + (lane & 7), bar + B_HH2); }
    }
  } else {
    const int wg = warp >> 2, wq = warp & 3, tid = threadIdx.x;
    const int g = lane >> 2, c = lane & 3;
    const int sec0 = (m >> 1) & 1, hf0 = m & 1, ks0 = (m >> 2) & 3;
    uint4 wv[8];
    uint32_t ep0; uint16_t cv_;
    asm volatile("ld.global.nc.u16 %0, [%1];" : "=h"(cv_) : "l"(cvec + ks0 * 256 + warp * 32 + lane));
    asm volatile("ld.global.u32 %0, [%1];" : "=r"(ep0) : "l"(gs->epoch + (blockIdx.x | (lane & by_sm & 2))));
    if (!extra) {
      const bf16* wp = wmod + (size_t)(ks0 * 256 + warp * 32 + (lane >> 3)) * 6144 + sec0 * 1024 + j * 128 + hf0 * 64 + (lane & 7) * 8;
#pragma unroll
      for (int i = 0; i < 8; i++) wv[i] = ldg_nc(wp + (size_t)i * 4 * 6144);
      cl_arrive_relaxed();
    }
    asm volatile("setmaxnreg.inc.sync.aligned.u32 232;" ::: "memory");
    if (__builtin_expect(extra, 0)) {
      const uint32_t ep = ep0 + 1;
      float sv[4];
#pragma unroll
      for (int p = 0; p < 4; p++) sv[p] = silu_c(__bfloat162float(cvec[64 * (4 * p + (lane >> 3)) + 8 * warp + (lane & 7)]));
      named_bar(2, 288);
      int s = 0, par = 0;
#pragma unroll 1
      for (int sec = 0; sec < 4; sec++) {
        float a[8] = {0, 0, 0, 0, 0, 0, 0, 0};
#pragma unroll 1
        for (int it = 0; it < 16; it++) {
          const float sc = it < 4 ? sv[0] : it < 8 ? sv[1] : it < 12 ? sv[2] : sv[3];
          mbar_wait(bar + B_FULL6 + s * 8, par);
          uint4 w[8];
#pragma unroll
          for (int i = 0; i < 8; i++) w[i] = lds128(sb + s * 32768 + (warp * 8 + i) * 512 + lane * 16);
#pragma unroll
          for (int i = 0; i < 8; i++) gemv_fma(a, w[i], __shfl_sync(~0u, sc, (it & 3) * 8 + i));
          if (lane == 0) mbar_arrive(bar + B_EMPTY6 + s * 8);
          if (++s == 6) { s = 0; par ^= 1; }
        }
        const uint32_t red = sb + STG + sec * 8192;
        sts128(red + warp * 1024 + lane * 32, __float_as_uint(a[0]), __float_as_uint(a[1]), __float_as_uint(a[2]), __float_as_uint(a[3]));
        sts128(red + warp * 1024 + lane * 32 + 16, __float_as_uint(a[4]), __float_as_uint(a[5]), __float_as_uint(a[6]), __float_as_uint(a[7]));
        named_bar(1, 256);
        float t = 0;
#pragma unroll
        for (int q = 0; q < 8; q++) t += lds32f(red + q * 1024 + tid * 4);
        t = bf_round(t);
        if (sec == 2) t = bf_round(t + 1.f);
        st_rlx2(gs->modv + sec * 1024 + (bid + 4) * 256 + tid, __float_as_uint(t), ep);
      }
      if (tid == 0) gs->epoch[blockIdx.x] = ep;
      return;
    }
    const int row0 = wg * 64 + wq * 16 + g;
    if (c < 2) st_rlx2(gs->stat + m * 1024 + j * 128 + row0 + c * 8, 0, 0);
    if (1 && tid < 64) st_rlx1(gs->modp + ((j * 2 + sec0) * 4 + ks0) * 128 + hf0 * 64 + tid, 0);
    cl_wait();
    uint32_t ep;
    asm volatile("add.u32 %0, %1, 1;" : "=r"(ep) : "r"(ep0) : "memory");
    const float sc_ = silu_c(__uint_as_float((uint32_t)cv_ << 16));
    const uint32_t rel = mapa(bar, (lane & 1) ^ rank);
    const uint32_t stg_row = sb + STG + (wg * 64 + wq * 16 + (lane & 15)) * 128;
    const uint32_t fre = bar + B_FREE;
    Ring r4{0, 0, 0}, r6{0, 0, 0};
    auto none = [](auto) {};
    uint32_t xk[32];
    {
      float a[8] = {0, 0, 0, 0, 0, 0, 0, 0};
#pragma unroll
      for (int i = 0; i < 8; i++) gemv_fma(a, wv[i], __shfl_sync(~0u, sc_, i * 4 + (lane >> 3)));
#pragma unroll
      for (int i = 0; i < 8; i++) { a[i] += __shfl_xor_sync(~0u, a[i], 8); a[i] += __shfl_xor_sync(~0u, a[i], 16); }
      if (lane < 8) {
        sts128(sb + RED_OFF + warp * 256 + lane * 32, __float_as_uint(a[0]), __float_as_uint(a[1]), __float_as_uint(a[2]), __float_as_uint(a[3]));
        sts128(sb + RED_OFF + warp * 256 + lane * 32 + 16, __float_as_uint(a[4]), __float_as_uint(a[5]), __float_as_uint(a[6]), __float_as_uint(a[7]));
      }
      named_bar(1, 256);
      if (tid < 64) {
        float s = 0;
#pragma unroll
        for (int w = 0; w < 8; w++) s += lds32f(sb + RED_OFF + w * 256 + tid * 4);
        st_rlx1(gs->modp + ((j * 2 + sec0) * 4 + ks0) * 128 + hf0 * 64 + tid, (__float_as_uint(s) & ~255u) | tag_of(ep));
      }
      float v[64];
      mbar_wait(bar + B_X, 0); mbar_wait(bar + B_X + 8, 0);
#pragma unroll
      for (int i = 0; i < 16; i += 2) {
        uint32_t w0, w1, w2, w3;
        ldsm4(stg_row + (i >> 3) * BLK + ((((i & 7) + (lane >> 4)) ^ (lane & 7)) << 4), w0, w1, w2, w3);
        xk[2 * i] = w0; xk[2 * i + 1] = w1; xk[2 * i + 2] = w2; xk[2 * i + 3] = w3;
        v[4 * i] = bf_lo(w0); v[4 * i + 1] = bf_hi(w0); v[4 * i + 2] = bf_lo(w1); v[4 * i + 3] = bf_hi(w1);
        v[4 * i + 4] = bf_lo(w2); v[4 * i + 5] = bf_hi(w2); v[4 * i + 6] = bf_lo(w3); v[4 * i + 7] = bf_hi(w3);
      }
      ln_publish(v, gs->stat + m * 1024, j, row0, lane, ep);
      mod_store(sb, tid >> 7, tid & 127, mod_gather(gs->modp + (j * 2 + (tid >> 7)) * 512 + (tid & 127), ep));
      named_bar(1, 256);
      ln_apply(v, gs->stat + m * 1024, row0, ep, sb, 0, 1, stg_row, wg, lane);
      named_bar(1, 256);
    }
    {
      uint32_t kf[32], vf[32], pv[32];
      const bool first = wq == 0 && m == 0;
      const uint32_t xa = sb + STG + wg * HALF + wq * 2048 + lane * 16;
      {
        float acc[128];
        mainloop<256, 4, 0, 0>(acc, 16, true, r4, sb, wg, lane, rel, none, none, [&] {
          mbar_wait(fre + 8, 0);
          if (c < 2) st_rlx2(gs->stat + (16 + m) * 1024 + j * 128 + row0 + c * 8, 0, 0);
        });
#pragma unroll
        for (int i = 0; i < 32; i++) { kf[i] = pack2(acc[2 * i], acc[2 * i + 1]); vf[i] = pack2(acc[64 + 2 * i], acc[65 + 2 * i]); }
      }
      float acc[64];
      constexpr int QP = 2;
      mainloop<128, 6, 8 / QP, 0>(acc, 16, false, r6, sb, wg, lane, rel, [&](auto ic) {
        constexpr int q = (ic.v - 1) * QP;
#pragma unroll
        for (int i = 4 * q; i < 4 * (q + QP); i++) vf[i] = movm(vf[i]);
        if (wq == 3) {
          if (m < 15) {
            uint4* hp = gs->halo + (((m + 1) * 8 + j) * 2 + wg) * 512 + lane;
#pragma unroll
            for (int i = 2 * q; i < 2 * (q + QP); i++) st_rlx4(hp + i * 32, kf[2 * i + 1], ep, vf[2 * i + 1], ep);
          }
        } else {
#pragma unroll
          for (int i = q; i < q + QP; i++) sts128(xa + 2048 + (i >> 2) * BLK + (i & 3) * 512, kf[4 * i + 1], kf[4 * i + 3], vf[4 * i + 1], vf[4 * i + 3]);
        }
      }, none, [&] {
        named_bar(2 + wg, 128);
        if (wq == 0) mbar_wait(bar + B_HALO, 0);
#pragma unroll
        for (int i = 0; i < 8; i++) {
          uint4 q = lds128(xa + (i >> 2) * BLK + (i & 3) * 512);
          pv[4 * i] = q.x; pv[4 * i + 1] = q.y; pv[4 * i + 2] = q.z; pv[4 * i + 3] = q.w;
        }
        __syncwarp();
      });
      int gz = g;
#pragma unroll
      for (int b = 0; b < 2; b++) {
        const bool up0 = 2 * c > gz, up1 = 2 * c + 1 > gz;
        const uint32_t mup = (up0 ? 0xffffu : 0u) | (up1 ? 0xffff0000u : 0u);
        float l[2][4], mx[4];
#pragma unroll
        for (int h = 0; h < 2; h++) {
          uint32_t q[8];
          const int k = 16 * b + 8 * h;
#pragma unroll
          for (int i = 0; i < 8; i++) q[i] = pack2(acc[2 * k + 2 * i], acc[2 * k + 2 * i + 1]);
          float s0[4], s1[4], s2[4];
          mma16z(s0, q[0], q[1], q[2], q[3], pv[k], pv[k + 1]); mma16z(s1, q[0], q[1], q[2], q[3], kf[k], kf[k + 2]); mma16z(s2, q[0], q[1], q[2], q[3], kf[k + 1], kf[k + 3]);
          mma16(s0, q[4], q[5], q[6], q[7], pv[k + 4], pv[k + 5]); mma16(s1, q[4], q[5], q[6], q[7], kf[k + 4], kf[k + 6]); mma16(s2, q[4], q[5], q[6], q[7], kf[k + 5], kf[k + 7]);
          if (first) { s0[0] = -INFINITY; s0[1] = -INFINITY; }
          l[h][0] = up0 ? s0[0] : s1[0]; l[h][1] = up1 ? s0[1] : s1[1]; l[h][2] = up0 ? s1[2] : s2[2]; l[h][3] = up1 ? s1[3] : s2[3];
          mx[2 * h] = fmaxf(l[h][0], l[h][1]); mx[2 * h + 1] = fmaxf(l[h][2], l[h][3]);
        }
#pragma unroll
        for (int o = 1; o < 4; o <<= 1) {
#pragma unroll
          for (int h = 0; h < 4; h++) mx[h] = fmaxf(mx[h], __shfl_xor_sync(~0u, mx[h], o));
        }
#pragma unroll
        for (int h = 0; h < 2; h++) {
          const float n0 = -mx[2 * h] * SCL, n1 = -mx[2 * h + 1] * SCL;
          const uint32_t pa = pack2(ex2(fmaf(l[h][0], SCL, n0)), ex2(fmaf(l[h][1], SCL, n0))), pb = pack2(ex2(fmaf(l[h][2], SCL, n1)), ex2(fmaf(l[h][3], SCL, n1)));
          float sm[4];
          mma8z(sm, pa, pb, 0x3f803f80u);
          const float ia = rcp(sm[0]), ib = rcp(sm[2]);
#pragma unroll
          for (int i = 8 * b + 4 * h; i < 8 * b + 4 * h + 4; i += 2) {
            uint32_t of[4];
#pragma unroll
            for (int d = 0; d < 2; d++) {
              float o[4];
              mma16z(o, pa & ~mup, pb & mup, 0u, pb & ~mup, vf[2 * (i + d)], vf[2 * (i + d) + 1]);
              mma8(o, pa & mup, 0u, pv[2 * i + 2 + d]);
              of[2 * d] = pack2(o[0] * ia, o[1] * ia); of[2 * d + 1] = pack2(o[2] * ib, o[3] * ib);
            }
            stsm4(stg_row + b * BLK + ((((i & 7) + (lane >> 4)) ^ (lane & 7)) << 4), of[0], of[1], of[2], of[3]);
          }
        }
        stage_done(sb, wg, b, lane);
        if (b == 0) gz += __float_as_uint(lds32f(bar + ZERO));
      }
      named_bar(1, 256);
    }
    uint32_t pk[64];
    {
      float acc[64];
      mainloop<128, 6, 0, WOLAG>(acc, 16, true, r6, sb, wg, lane, rel, none, none, [&] {
        if (WOLAG && wg == 0 && lane == 0) mbar_arrive(bar + B_LAG);
        mbar_wait(bar + B_MOD, 0); mbar_wait(fre + 8, 1);
        load_vec(pk + 32, sb, 2, 0, lane); load_vec(pk + 40, sb, 2, 1, lane);
#pragma unroll
        for (int i = 0; i < 32; i++) { pk[i] = xk[i]; asm volatile("" : "+r"(pk[i])); }
      });
#pragma unroll
      for (int i = 0; i < 32; i++) {
        acc[2 * i] = fmaf(acc[2 * i], bf_lo(pk[32 + (i >> 1)]), bf_lo(pk[i]));
        acc[2 * i + 1] = fmaf(acc[2 * i + 1], bf_hi(pk[32 + (i >> 1)]), bf_hi(pk[i]));
      }
      ln_publish(acc, gs->stat + (16 + m) * 1024, j, row0, lane, ep);
      mbar_wait(bar + B_FULL6 + 16, 1);
      if (lane < 2) mbar_arrive_cl(rel + B_EMPTY6 + 16);
      ring_next<6>(r6);
#pragma unroll
      for (int i = 0; i < 32; i++) { pk[i] = pack2(acc[2 * i], acc[2 * i + 1]); pk[32 + i] = 0; }
      ln_apply(acc, gs->stat + (16 + m) * 1024, row0, ep, sb, 3, 4, stg_row, wg, lane);
      named_bar(1, 256);
    }
    auto swiglu = [&](int q, int uo, int par) {
      if ((q & 3) == 0 && par >= 0) mbar_wait(fre + 2 * q, par);
      uint32_t w[4];
#pragma unroll
      for (int u = 0; u < 4; u++) w[u] = silu_mul2(pk[4 * q + u], pk[uo + 4 * q + u]);
      stsm4(stg_row + (q >> 2) * BLK + ((((2 * q & 7) + (lane >> 4)) ^ (lane & 7)) << 4), w[0], w[1], w[2], w[3]);
    };
    r4.s = r4.wrap = 2;
#pragma unroll 1
    for (int t = 0; t < 3; t++) {
      float acc[128];
      mainloop<256, 4, 4, 0>(acc, 16, t == 0, r4, sb, wg, lane, rel, [&](auto ic) {
        if (t) {
          if (ic.v == 3) stage_done(sb, wg, 0, lane);
          swiglu(2 * ic.v - 2, 32, ~t & 1); swiglu(2 * ic.v - 1, 32, 0);
        }
      }, [&](int it) {
        if (t && it == 5) stage_done(sb, wg, 1, lane);
#pragma unroll
        for (int i = 0; i < 8; i++)
          if (t == 0 && it == 8 + i) gs->x1[bid * 2048 + (i >> 2) * 1024 + warp * 128 + (i & 3) * 32 + lane] = make_uint4(pk[4 * i], pk[4 * i + 1], pk[4 * i + 2], pk[4 * i + 3]);
      }, [&] { if (t == 0) fence_async_global(); else if (t == 2) mbar_wait(bar + B_X, 1); });
#pragma unroll
      for (int i = 0; i < 64; i++) pk[i] = pack2(acc[2 * i], acc[2 * i + 1]);
    }
    uint32_t x1[32];
    {
      float acc[64];
      mainloop<128, 6, 10, 0>(acc, 16, false, r6, sb, wg, lane, rel, [&](auto ic) {
        constexpr int b = ic.v > 5, q = ic.v - 5 * b;
        if (q == 1) {
          if (b) stage_done(sb, wg, 0, lane);
#pragma unroll
          for (int i = 4 * b; i < 4 * b + 4; i++) { const uint4 x = lds128(sb + STG + b * BLK + warp * 2048 + (i & 3) * 512 + lane * 16); x1[4 * i] = x.x; x1[4 * i + 1] = x.y; x1[4 * i + 2] = x.z; x1[4 * i + 3] = x.w; }
          __syncwarp();
        } else swiglu(4 * b + q - 2, 32, -1);
      }, [&](int it) { if (it == 11) stage_done(sb, wg, 1, lane); }, [] {});
#pragma unroll
      for (int i = 0; i < 32; i++) pk[i] = pack2(acc[2 * i], acc[2 * i + 1]);
    }
    {
      float acc[64];
      mainloop<128, 6, 4, TAILLAG>(acc, 56, false, r6, sb, wg, lane, rel, [&](auto ic) { swiglu(ic.v - 1, 16, 1); },
                                   [&](int it) { if (it == 5) stage_done(sb, wg, 0, lane); }, [&] {
        if (TAILLAG && wg == 0 && lane == 0) mbar_arrive(bar + B_LAG);
        load_vec(pk + 32, sb, 5, 0, lane); load_vec(pk + 40, sb, 5, 1, lane);
        mbar_wait(fre, 0); mbar_wait(fre + 8, 1);
      });
      __syncwarp();
      cl_arrive_relaxed();
#pragma unroll
      for (int i = 0; i < 16; i += 2) {
        uint32_t w[4];
#pragma unroll
        for (int u = 0; u < 4; u++) {
          const int q = 2 * i + u;
          w[u] = pack2(fmaf(acc[2 * q], bf_lo(pk[32 + (q >> 1)]), bf_lo(x1[q])), fmaf(acc[2 * q + 1], bf_hi(pk[32 + (q >> 1)]), bf_hi(x1[q])));
        }
        stsm4(stg_row + (i >> 3) * BLK + ((((i & 7) + (lane >> 4)) ^ (lane & 7)) << 4), w[0], w[1], w[2], w[3]);
        if ((i & 7) == 6) {
          fence_async_smem();
          named_bar(2 + wg, 128);
          if (wq == 0 && elect()) { tma_store_3d(&maps.out, sb + STG + (i >> 3) * BLK + wg * HALF, j * 128 + (i >> 3) * 64, m * 64, wg); bulk_commit(); }
          if (i < 8) x1[16] |= __float_as_uint(lds32f(bar + ZERO));
        }
      }
      if (wq == 0) bulk_wait_read();
      if (tid == 0) gs->epoch[blockIdx.x] = ep;
      cl_wait();
    }
  }
}

typedef CUresult (*EncodeFn)(CUtensorMap*, CUtensorMapDataType, cuuint32_t, void*, const cuuint64_t*, const cuuint64_t*, const cuuint32_t*, const cuuint32_t*,
                             CUtensorMapInterleave, CUtensorMapSwizzle, CUtensorMapL2promotion, CUtensorMapFloatOOBfill);

void make_map(EncodeFn fn, CUtensorMap* mp, const void* base, uint64_t d0, uint64_t d1, uint64_t d2, uint64_t s1, uint64_t s2, uint32_t b2, uint32_t b0 = 64) {
  cuuint64_t d[3] = {d0, d1, d2}, s[2] = {s1, s2};
  cuuint32_t b[3] = {b0, 64, b2}, e[3] = {1, 1, 1};
  fn(mp, CU_TENSOR_MAP_DATA_TYPE_BFLOAT16, 3, (void*)base, d, s, b, e, CU_TENSOR_MAP_INTERLEAVE_NONE, b0 == 64 ? CU_TENSOR_MAP_SWIZZLE_128B : CU_TENSOR_MAP_SWIZZLE_NONE,
     CU_TENSOR_MAP_L2_PROMOTION_L2_128B, CU_TENSOR_MAP_FLOAT_OOB_FILL_NONE);
}

__global__ void probe_kernel() {}
int max_clusters(int size) {
  cudaLaunchConfig_t cfg = {};
  cudaLaunchAttribute at;
  at.id = cudaLaunchAttributeClusterDimension; at.val.clusterDim.x = size; at.val.clusterDim.y = 1; at.val.clusterDim.z = 1;
  cfg.gridDim = dim3(size * 66); cfg.blockDim = dim3(384); cfg.dynamicSmemBytes = SMEM_BYTES; cfg.attrs = &at; cfg.numAttrs = 1;
  int n = 0;
  if (cudaOccupancyMaxActiveClusters(&n, probe_kernel, &cfg) != cudaSuccess) { cudaGetLastError(); return 0; }
  return n;
}

}

extern "C" void kernel_launch(void* const* d_in, const int* in_sizes, int n_in, void* d_out, int out_size) {
  static EncodeFn fn = nullptr;
  static int by_sm = 0;
  static Scratch* gs = nullptr;
  if (!fn) {
    void* p = nullptr; cudaDriverEntryPointQueryResult q;
    cudaGetDriverEntryPoint("cuTensorMapEncodeTiled", &p, cudaEnableDefault, &q);
    fn = (EncodeFn)p;
    cudaFuncSetAttribute(fused_kernel, cudaFuncAttributeMaxDynamicSharedMemorySize, SMEM_BYTES);
    int dev = 0, sms = 0;
    cudaGetSymbolAddress((void**)&gs, g_scratch);
    cudaGetDevice(&dev);
    cudaDeviceGetAttribute(&sms, cudaDevAttrMultiProcessorCount, dev);
    cudaFuncSetAttribute(probe_kernel, cudaFuncAttributeMaxDynamicSharedMemorySize, SMEM_BYTES);
    by_sm = sms == 132 && max_clusters(2) == 66 && max_clusters(4) == 30 && max_clusters(6) == 17 && max_clusters(8) == 15;
  }
  Maps mp;
  make_map(fn, &mp.x, d_in[0], D_, S_ / 2, 2, 4096, 2048, 2);
  make_map(fn, &mp.out, d_out, D_, S_ / 2, 2, 4096, 2048, 1);
  make_map(fn, &mp.wqkv, d_in[1], 64, D_, 3 * D_ / 64, 3 * D_ * 2, 128, 2);
  make_map(fn, &mp.wo, d_in[2], 64, D_, D_ / 64, D_ * 2, 128, 2);
  make_map(fn, &mp.w1, d_in[4], 64, D_, F_ / 64, F_ * 2, 128, 2);
  make_map(fn, &mp.w3, d_in[5], 64, D_, F_ / 64, F_ * 2, 128, 2);
  make_map(fn, &mp.w1s, d_in[4], 64, D_, F_ / 64, F_ * 2, 128, 1);
  make_map(fn, &mp.w3s, d_in[5], 64, D_, F_ / 64, F_ * 2, 128, 1);
  make_map(fn, &mp.w2, d_in[6], 64, F_, D_ / 64, D_ * 2, 128, 2);
  make_map(fn, &mp.wmod, d_in[8], 256, D_, 24, 6 * D_ * 2, 512, 1, 256);
  fused_kernel<<<132, 384, SMEM_BYTES>>>((const bf16*)d_in[7], (const bf16*)d_in[8], gs, by_sm, mp);
}
```

```cpp
#include <cuda_runtime.h>
#include <cuda_bf16.h>
#include <cuda.h>
#include <stdint.h>

typedef __nv_bfloat16 bf16;

namespace {

constexpr int S_ = 2048, D_ = 1024, F_ = 3584;
constexpr int BLK = 16384;
constexpr int HALF = 8192;
constexpr int RING = 196608;
constexpr int STG = RING;
constexpr int MISC = RING + 2 * BLK;
constexpr int SMEM_BYTES = MISC + 3072;
constexpr int B_FULL4 = 0, B_EMPTY4 = 32, B_FULL6 = 64, B_EMPTY6 = 112, B_RDY = 160, B_FREE = 176, B_LAG = 192, B_X = 208, B_MOD = 224, B_HALO = 232, B_HH = 256, B_ALL = 272, B_HH2 = 288, ZERO = 296;
constexpr int MODV = 512;
constexpr int RED_OFF = 0;
constexpr float SCL = 0.17677669529663687f * 1.4426950408889634f;
constexpr int U_HH = 64;
constexpr int FS = 8;
constexpr int NPIECE = 4, PSLEEP = 300;
constexpr int XSLEEP = 4000, HSLEEP = 400;
constexpr uint32_t XDELAY = 2300, GAP = 250;
constexpr uint32_t B1P = 3700, B1D = 700;
constexpr int TAILLAG = 5;

struct Maps { CUtensorMap x, out, wqkv, wo, w1, w3, w1s, w3s, w2, wmod; };

struct Scratch {
  uint4 h[16 * 16 * 1024];
  uint4 o[16 * 16 * 1024];
  uint4 hh[16 * 56 * 1024];
  uint4 x1[128 * 8 * 256];
  uint2 stat[2 * 16 * 8 * 128];
  uint4 halo[16 * 8 * 2 * 512];
  uint32_t modp[8 * 2 * 4 * 128];
  uint2 modv[4 * 1024];
  uint32_t flag[16 * 128 * FS];
  uint32_t epoch[132];
};
__device__ __align__(1024) Scratch g_scratch;

__device__ __forceinline__ void bail() { asm volatile("st.global.u32 [%0], %1;" :: "l"(0ull), "r"(0) : "memory"); }
__device__ __forceinline__ uint32_t smem_u32(const void* p) { return (uint32_t)__cvta_generic_to_shared(p); }
__device__ __forceinline__ void mbar_init(uint32_t bar, uint32_t cnt) { asm volatile("mbarrier.init.shared::cta.b64 [%0], %1;" :: "r"(bar), "r"(cnt) : "memory"); }
__device__ __forceinline__ void mbar_expect_tx(uint32_t bar, uint32_t bytes) { asm volatile("mbarrier.arrive.expect_tx.shared::cta.b64 _, [%0], %1;" :: "r"(bar), "r"(bytes) : "memory"); }
__device__ __forceinline__ void mbar_arrive(uint32_t bar) { asm volatile("mbarrier.arrive.shared::cta.b64 _, [%0];" :: "r"(bar) : "memory"); }
__device__ __forceinline__ void mbar_arrive_cl(uint32_t cl_addr) { asm volatile("mbarrier.arrive.shared::cluster.b64 _, [%0];" :: "r"(cl_addr) : "memory"); }
__device__ __forceinline__ uint32_t mapa(uint32_t addr, uint32_t cta) { uint32_t r; asm("mapa.shared::cluster.u32 %0, %1, %2;" : "=r"(r) : "r"(addr), "r"(cta)); return r; }
__device__ __forceinline__ void mbar_wait(uint32_t bar, uint32_t parity) {
  asm volatile("{\n.reg .pred p;\n.reg .b32 n;\n.reg .b64 z;\nmov.b32 n, 0;\nmov.b64 z, 0;\n"
               "W: add.u32 n, n, 1;\nsetp.gt.u32 p, n, 0x400000;\n@p st.global.u32 [z], n;\n"
               "mbarrier.try_wait.parity.shared::cta.b64 p, [%0], %1;\n@!p bra W;\n}" :: "r"(bar), "r"(parity) : "memory");
}
__device__ __forceinline__ void tma_3d(uint32_t dst, const CUtensorMap* m, uint32_t bar, int c0, int c1, int c2) {
  asm volatile("cp.async.bulk.tensor.3d.shared::cluster.global.mbarrier::complete_tx::bytes [%0], [%1, {%3, %4, %5}], [%2];" :: "r"(dst), "l"(m), "r"(bar), "r"(c0), "r"(c1), "r"(c2) : "memory");
}
__device__ __forceinline__ void tma_store_3d(const CUtensorMap* m, uint32_t src, int c0, int c1, int c2) {
  asm volatile("cp.async.bulk.tensor.3d.global.shared::cta.bulk_group [%0, {%2, %3, %4}], [%1];" :: "l"(m), "r"(src), "r"(c0), "r"(c1), "r"(c2) : "memory");
}
__device__ __forceinline__ void bulk_ld(uint32_t dst, const void* src, uint32_t bytes, uint32_t bar) {
  asm volatile("cp.async.bulk.shared::cluster.global.mbarrier::complete_tx::bytes [%0], [%1], %2, [%3];" :: "r"(dst), "l"(src), "r"(bytes), "r"(bar) : "memory");
}
__device__ __forceinline__ void bulk_ld_mc(uint32_t dst, const void* src, uint32_t bytes, uint32_t bar) {
  asm volatile("cp.async.bulk.shared::cluster.global.mbarrier::complete_tx::bytes.multicast::cluster [%0], [%1], %2, [%3], %4;" :: "r"(dst), "l"(src), "r"(bytes), "r"(bar), "h"((uint16_t)3) : "memory");
}
__device__ __forceinline__ void bulk_push(uint32_t dst_cl, uint32_t src, uint32_t bytes, uint32_t bar_cl) {
  asm volatile("cp.async.bulk.shared::cluster.shared::cta.mbarrier::complete_tx::bytes [%0], [%1], %2, [%3];" :: "r"(dst_cl), "r"(src), "r"(bytes), "r"(bar_cl) : "memory");
}
__device__ __forceinline__ void bulk_st(void* dst, uint32_t src, uint32_t bytes) {
  asm volatile("cp.async.bulk.global.shared::cta.bulk_group [%0], [%1], %2;" :: "l"(dst), "r"(src), "r"(bytes) : "memory");
}
__device__ __forceinline__ void bulk_commit() { asm volatile("cp.async.bulk.commit_group;" ::: "memory"); }
__device__ __forceinline__ void bulk_wait_read() { asm volatile("cp.async.bulk.wait_group.read 0;" ::: "memory"); }
__device__ __forceinline__ void bulk_wait_all() { asm volatile("cp.async.bulk.wait_group 0;" ::: "memory"); }
__device__ __forceinline__ void fence_async_global() { asm volatile("fence.proxy.async.global;" ::: "memory"); }
__device__ __forceinline__ void fence_async_smem() { asm volatile("fence.proxy.async.shared::cta;" ::: "memory"); }
__device__ __forceinline__ void wg_arrive() { asm volatile("wgmma.fence.sync.aligned;" ::: "memory"); }
__device__ __forceinline__ void wg_commit() { asm volatile("wgmma.commit_group.sync.aligned;" ::: "memory"); }
template <int N> __device__ __forceinline__ void wg_wait() { asm volatile("wgmma.wait_group.sync.aligned %0;" :: "n"(N) : "memory"); }
__device__ __forceinline__ void cl_arrive_relaxed() { asm volatile("barrier.cluster.arrive.relaxed.aligned;" ::: "memory"); }
__device__ __forceinline__ void cl_wait() { asm volatile("barrier.cluster.wait.acquire.aligned;" ::: "memory"); }
__device__ __forceinline__ bool elect() { uint32_t p; asm volatile("{\n.reg .pred p;\nelect.sync _|p, 0xffffffff;\nselp.u32 %0, 1, 0, p;\n}" : "=r"(p)); return p; }
__device__ __forceinline__ void named_bar(int id, int n) { asm volatile("bar.sync %0, %1;" :: "r"(id), "r"(n) : "memory"); }
__device__ __forceinline__ uint32_t pack2(float lo, float hi) { uint32_t r; asm("cvt.rn.bf16x2.f32 %0, %1, %2;" : "=r"(r) : "f"(hi), "f"(lo)); return r; }
__device__ __forceinline__ float bf_lo(uint32_t w) { return __uint_as_float(w << 16); }
__device__ __forceinline__ float bf_hi(uint32_t w) { return __uint_as_float(w & 0xffff0000u); }
__device__ __forceinline__ float bf_round(float v) { return __bfloat162float(__float2bfloat16_rn(v)); }
__device__ __forceinline__ void stsm4(uint32_t addr, uint32_t a, uint32_t b, uint32_t c, uint32_t d) {
  asm volatile("stmatrix.sync.aligned.m8n8.x4.shared.b16 [%0], {%1, %2, %3, %4};" :: "r"(addr), "r"(a), "r"(b), "r"(c), "r"(d) : "memory");
}
__device__ __forceinline__ void ldsm4(uint32_t addr, uint32_t& a, uint32_t& b, uint32_t& c, uint32_t& d) {
  asm volatile("ldmatrix.sync.aligned.m8n8.x4.shared.b16 {%0, %1, %2, %3}, [%4];" : "=r"(a), "=r"(b), "=r"(c), "=r"(d) : "r"(addr) : "memory");
}
__device__ __forceinline__ uint32_t movm(uint32_t a) { uint32_t r; asm volatile("movmatrix.sync.aligned.m8n8.trans.b16 %0, %1;" : "=r"(r) : "r"(a)); return r; }
__device__ __forceinline__ void mma16(float (&d)[4], uint32_t a0, uint32_t a1, uint32_t a2, uint32_t a3, uint32_t b0, uint32_t b1) {
  asm("mma.sync.aligned.m16n8k16.row.col.f32.bf16.bf16.f32 {%0,%1,%2,%3}, {%4,%5,%6,%7}, {%8,%9}, {%0,%1,%2,%3};"
               : "+f"(d[0]), "+f"(d[1]), "+f"(d[2]), "+f"(d[3]) : "r"(a0), "r"(a1), "r"(a2), "r"(a3), "r"(b0), "r"(b1));
}
__device__ __forceinline__ void mma16z(float (&d)[4], uint32_t a0, uint32_t a1, uint32_t a2, uint32_t a3, uint32_t b0, uint32_t b1) {
  asm("mma.sync.aligned.m16n8k16.row.col.f32.bf16.bf16.f32 {%0,%1,%2,%3}, {%4,%5,%6,%7}, {%8,%9}, {%10,%10,%10,%10};"
      : "=f"(d[0]), "=f"(d[1]), "=f"(d[2]), "=f"(d[3]) : "r"(a0), "r"(a1), "r"(a2), "r"(a3), "r"(b0), "r"(b1), "f"(0.f));
}
__device__ __forceinline__ void mma8z(float (&d)[4], uint32_t a0, uint32_t a1, uint32_t b0) {
  asm("mma.sync.aligned.m16n8k8.row.col.f32.bf16.bf16.f32 {%0,%1,%2,%3}, {%4,%5}, {%6}, {%7,%7,%7,%7};"
      : "=f"(d[0]), "=f"(d[1]), "=f"(d[2]), "=f"(d[3]) : "r"(a0), "r"(a1), "r"(b0), "f"(0.f));
}
__device__ __forceinline__ void mma8(float (&d)[4], uint32_t a0, uint32_t a1, uint32_t b0) {
  asm("mma.sync.aligned.m16n8k8.row.col.f32.bf16.bf16.f32 {%0,%1,%2,%3}, {%4,%5}, {%6}, {%0,%1,%2,%3};"
               : "+f"(d[0]), "+f"(d[1]), "+f"(d[2]), "+f"(d[3]) : "r"(a0), "r"(a1), "r"(b0));
}
__device__ __forceinline__ uint4 lds128(uint32_t a) { uint4 v; asm volatile("ld.shared.v4.u32 {%0,%1,%2,%3}, [%4];" : "=r"(v.x), "=r"(v.y), "=r"(v.z), "=r"(v.w) : "r"(a) : "memory"); return v; }
__device__ __forceinline__ void sts128(uint32_t a, uint32_t x, uint32_t y, uint32_t z, uint32_t w) { asm volatile("st.shared.v4.u32 [%0], {%1,%2,%3,%4};" :: "r"(a), "r"(x), "r"(y), "r"(z), "r"(w) : "memory"); }
__device__ __forceinline__ float lds32f(uint32_t a) { float v; asm volatile("ld.shared.f32 %0, [%1];" : "=f"(v) : "r"(a) : "memory"); return v; }
__device__ __forceinline__ void sts16(uint32_t a, bf16 v) { asm volatile("st.shared.b16 [%0], %1;" :: "r"(a), "h"(__bfloat16_as_ushort(v)) : "memory"); }
__device__ __forceinline__ uint4 ldg_nc(const void* p) { uint4 v; asm volatile("ld.global.nc.L1::no_allocate.v4.u32 {%0,%1,%2,%3}, [%4];" : "=r"(v.x), "=r"(v.y), "=r"(v.z), "=r"(v.w) : "l"(p)); return v; }
__device__ __forceinline__ uint4 ld_rlx4(const uint4* p) {
  unsigned long long a, b; asm volatile("ld.relaxed.gpu.global.v2.b64 {%0,%1}, [%2];" : "=l"(a), "=l"(b) : "l"(p) : "memory");
  return make_uint4((uint32_t)a, (uint32_t)(a >> 32), (uint32_t)b, (uint32_t)(b >> 32));
}
__device__ __forceinline__ uint2 ld_rlx2(const uint2* p) { unsigned long long a; asm volatile("ld.relaxed.gpu.global.b64 %0, [%1];" : "=l"(a) : "l"(p) : "memory"); return make_uint2((uint32_t)a, (uint32_t)(a >> 32)); }
__device__ __forceinline__ void st_rlx4(uint4* p, uint32_t x, uint32_t y, uint32_t z, uint32_t w) {
  asm volatile("st.relaxed.gpu.global.v2.b64 [%0], {%1,%2};" :: "l"(p), "l"((unsigned long long)x | ((unsigned long long)y << 32)), "l"((unsigned long long)z | ((unsigned long long)w << 32)) : "memory");
}
__device__ __forceinline__ void st_rlx2(uint2* p, uint32_t x, uint32_t y) { asm volatile("st.relaxed.gpu.global.b64 [%0], %1;" :: "l"(p), "l"((unsigned long long)x | ((unsigned long long)y << 32)) : "memory"); }
__device__ __forceinline__ void st_rlx1(uint32_t* p, uint32_t v) { asm volatile("st.relaxed.gpu.global.u32 [%0], %1;" :: "l"(p), "r"(v) : "memory"); }
__device__ __forceinline__ uint32_t ld_rlx1(const uint32_t* p) { uint32_t v; asm volatile("ld.relaxed.gpu.global.u32 %0, [%1];" : "=r"(v) : "l"(p) : "memory"); return v; }
__device__ __forceinline__ void st_release(uint32_t* p, uint32_t v) { asm volatile("st.release.gpu.global.u32 [%0], %1;" :: "l"(p), "r"(v) : "memory"); }
__device__ __forceinline__ uint32_t ld_acquire(const uint32_t* p) { uint32_t v; asm volatile("ld.acquire.gpu.global.u32 %0, [%1];" : "=r"(v) : "l"(p) : "memory"); return v; }
__device__ __forceinline__ void prefetch_map(const CUtensorMap* m) { asm volatile("prefetch.tensormap [%0];" :: "l"(m) : "memory"); }
__device__ __forceinline__ float rcp(float x) { float r; asm("rcp.approx.ftz.f32 %0, %1;" : "=f"(r) : "f"(x)); return r; }
__device__ __forceinline__ float ex2(float x) { float r; asm("ex2.approx.ftz.f32 %0, %1;" : "=f"(r) : "f"(x)); return r; }
__device__ __forceinline__ float tanh_fast(float x) { float r; asm("tanh.approx.f32 %0, %1;" : "=f"(r) : "f"(x)); return r; }
#define SPIN_GUARD(n) if (++(n) > (1u << 24)) bail()

__device__ __forceinline__ void wgmma_n128(float (&d)[64], uint64_t da, uint64_t db) {
  asm volatile("wgmma.mma_async.sync.aligned.m64n128k16.f32.bf16.bf16 "
    "{%0, %1, %2, %3, %4, %5, %6, %7, %8, %9, %10, %11, %12, %13, %14, %15, %16, %17, %18, %19, %20, %21, %22, %23, %24, %25, %26, %27, %28, %29, %30, %31, %32, %33, %34, %35, %36, %37, %38, %39, %40, %41, %42, %43, %44, %45, %46, %47, %48, %49, %50, %51, %52, %53, %54, %55, %56, %57, %58, %59, %60, %61, %62, %63}, "
    "%64, %65, 1, 1, 1, 0, 1;\n"
    : "+f"(d[0]), "+f"(d[1]), "+f"(d[2]), "+f"(d[3]), "+f"(d[4]), "+f"(d[5]), "+f"(d[6]), "+f"(d[7]), "+f"(d[8]), "+f"(d[9]), "+f"(d[10]), "+f"(d[11]), "+f"(d[12]), "+f"(d[13]), "+f"(d[14]), "+f"(d[15]), "+f"(d[16]), "+f"(d[17]), "+f"(d[18]), "+f"(d[19]), "+f"(d[20]), "+f"(d[21]), "+f"(d[22]), "+f"(d[23]), "+f"(d[24]), "+f"(d[25]), "+f"(d[26]), "+f"(d[27]), "+f"(d[28]), "+f"(d[29]), "+f"(d[30]), "+f"(d[31]), "+f"(d[32]), "+f"(d[33]), "+f"(d[34]), "+f"(d[35]), "+f"(d[36]), "+f"(d[37]), "+f"(d[38]), "+f"(d[39]), "+f"(d[40]), "+f"(d[41]), "+f"(d[42]), "+f"(d[43]), "+f"(d[44]), "+f"(d[45]), "+f"(d[46]), "+f"(d[47]), "+f"(d[48]), "+f"(d[49]), "+f"(d[50]), "+f"(d[51]), "+f"(d[52]), "+f"(d[53]), "+f"(d[54]), "+f"(d[55]), "+f"(d[56]), "+f"(d[57]), "+f"(d[58]), "+f"(d[59]), "+f"(d[60]), "+f"(d[61]), "+f"(d[62]), "+f"(d[63])
    : "l"(da), "l"(db));
}
__device__ __forceinline__ void wgmma_n128_first(float (&d)[64], uint64_t da, uint64_t db) {
  asm volatile("wgmma.mma_async.sync.aligned.m64n128k16.f32.bf16.bf16 "
    "{%0, %1, %2, %3, %4, %5, %6, %7, %8, %9, %10, %11, %12, %13, %14, %15, %16, %17, %18, %19, %20, %21, %22, %23, %24, %25, %26, %27, %28, %29, %30, %31, %32, %33, %34, %35, %36, %37, %38, %39, %40, %41, %42, %43, %44, %45, %46, %47, %48, %49, %50, %51, %52, %53, %54, %55, %56, %57, %58, %59, %60, %61, %62, %63}, "
    "%64, %65, 0, 1, 1, 0, 1;\n"
    : "=f"(d[0]), "=f"(d[1]), "=f"(d[2]), "=f"(d[3]), "=f"(d[4]), "=f"(d[5]), "=f"(d[6]), "=f"(d[7]), "=f"(d[8]), "=f"(d[9]), "=f"(d[10]), "=f"(d[11]), "=f"(d[12]), "=f"(d[13]), "=f"(d[14]), "=f"(d[15]), "=f"(d[16]), "=f"(d[17]), "=f"(d[18]), "=f"(d[19]), "=f"(d[20]), "=f"(d[21]), "=f"(d[22]), "=f"(d[23]), "=f"(d[24]), "=f"(d[25]), "=f"(d[26]), "=f"(d[27]), "=f"(d[28]), "=f"(d[29]), "=f"(d[30]), "=f"(d[31]), "=f"(d[32]), "=f"(d[33]), "=f"(d[34]), "=f"(d[35]), "=f"(d[36]), "=f"(d[37]), "=f"(d[38]), "=f"(d[39]), "=f"(d[40]), "=f"(d[41]), "=f"(d[42]), "=f"(d[43]), "=f"(d[44]), "=f"(d[45]), "=f"(d[46]), "=f"(d[47]), "=f"(d[48]), "=f"(d[49]), "=f"(d[50]), "=f"(d[51]), "=f"(d[52]), "=f"(d[53]), "=f"(d[54]), "=f"(d[55]), "=f"(d[56]), "=f"(d[57]), "=f"(d[58]), "=f"(d[59]), "=f"(d[60]), "=f"(d[61]), "=f"(d[62]), "=f"(d[63])
    : "l"(da), "l"(db));
}
__device__ __forceinline__ void wgmma_n256(float (&d)[128], uint64_t da, uint64_t db) {
  asm volatile("wgmma.mma_async.sync.aligned.m64n256k16.f32.bf16.bf16 "
    "{%0, %1, %2, %3, %4, %5, %6, %7, %8, %9, %10, %11, %12, %13, %14, %15, %16, %17, %18, %19, %20, %21, %22, %23, %24, %25, %26, %27, %28, %29, %30, %31, %32, %33, %34, %35, %36, %37, %38, %39, %40, %41, %42, %43, %44, %45, %46, %47, %48, %49, %50, %51, %52, %53, %54, %55, %56, %57, %58, %59, %60, %61, %62, %63, %64, %65, %66, %67, %68, %69, %70, %71, %72, %73, %74, %75, %76, %77, %78, %79, %80, %81, %82, %83, %84, %85, %86, %87, %88, %89, %90, %91, %92, %93, %94, %95, %96, %97, %98, %99, %100, %101, %102, %103, %104, %105, %106, %107, %108, %109, %110, %111, %112, %113, %114, %115, %116, %117, %118, %119, %120, %121, %122, %123, %124, %125, %126, %127}, "
    "%128, %129, 1, 1, 1, 0, 1;\n"
    : "+f"(d[0]), "+f"(d[1]), "+f"(d[2]), "+f"(d[3]), "+f"(d[4]), "+f"(d[5]), "+f"(d[6]), "+f"(d[7]), "+f"(d[8]), "+f"(d[9]), "+f"(d[10]), "+f"(d[11]), "+f"(d[12]), "+f"(d[13]), "+f"(d[14]), "+f"(d[15]), "+f"(d[16]), "+f"(d[17]), "+f"(d[18]), "+f"(d[19]), "+f"(d[20]), "+f"(d[21]), "+f"(d[22]), "+f"(d[23]), "+f"(d[24]), "+f"(d[25]), "+f"(d[26]), "+f"(d[27]), "+f"(d[28]), "+f"(d[29]), "+f"(d[30]), "+f"(d[31]), "+f"(d[32]), "+f"(d[33]), "+f"(d[34]), "+f"(d[35]), "+f"(d[36]), "+f"(d[37]), "+f"(d[38]), "+f"(d[39]), "+f"(d[40]), "+f"(d[41]), "+f"(d[42]), "+f"(d[43]), "+f"(d[44]), "+f"(d[45]), "+f"(d[46]), "+f"(d[47]), "+f"(d[48]), "+f"(d[49]), "+f"(d[50]), "+f"(d[51]), "+f"(d[52]), "+f"(d[53]), "+f"(d[54]), "+f"(d[55]), "+f"(d[56]), "+f"(d[57]), "+f"(d[58]), "+f"(d[59]), "+f"(d[60]), "+f"(d[61]), "+f"(d[62]), "+f"(d[63]), "+f"(d[64]), "+f"(d[65]), "+f"(d[66]), "+f"(d[67]), "+f"(d[68]), "+f"(d[69]), "+f"(d[70]), "+f"(d[71]), "+f"(d[72]), "+f"(d[73]), "+f"(d[74]), "+f"(d[75]), "+f"(d[76]), "+f"(d[77]), "+f"(d[78]), "+f"(d[79]), "+f"(d[80]), "+f"(d[81]), "+f"(d[82]), "+f"(d[83]), "+f"(d[84]), "+f"(d[85]), "+f"(d[86]), "+f"(d[87]), "+f"(d[88]), "+f"(d[89]), "+f"(d[90]), "+f"(d[91]), "+f"(d[92]), "+f"(d[93]), "+f"(d[94]), "+f"(d[95]), "+f"(d[96]), "+f"(d[97]), "+f"(d[98]), "+f"(d[99]), "+f"(d[100]), "+f"(d[101]), "+f"(d[102]), "+f"(d[103]), "+f"(d[104]), "+f"(d[105]), "+f"(d[106]), "+f"(d[107]), "+f"(d[108]), "+f"(d[109]), "+f"(d[110]), "+f"(d[111]), "+f"(d[112]), "+f"(d[113]), "+f"(d[114]), "+f"(d[115]), "+f"(d[116]), "+f"(d[117]), "+f"(d[118]), "+f"(d[119]), "+f"(d[120]), "+f"(d[121]), "+f"(d[122]), "+f"(d[123]), "+f"(d[124]), "+f"(d[125]), "+f"(d[126]), "+f"(d[127])
    : "l"(da), "l"(db));
}
__device__ __forceinline__ void wgmma_n256_first(float (&d)[128], uint64_t da, uint64_t db) {
  asm volatile("wgmma.mma_async.sync.aligned.m64n256k16.f32.bf16.bf16 "
    "{%0, %1, %2, %3, %4, %5, %6, %7, %8, %9, %10, %11, %12, %13, %14, %15, %16, %17, %18, %19, %20, %21, %22, %23, %24, %25, %26, %27, %28, %29, %30, %31, %32, %33, %34, %35, %36, %37, %38, %39, %40, %41, %42, %43, %44, %45, %46, %47, %48, %49, %50, %51, %52, %53, %54, %55, %56, %57, %58, %59, %60, %61, %62, %63, %64, %65, %66, %67, %68, %69, %70, %71, %72, %73, %74, %75, %76, %77, %78, %79, %80, %81, %82, %83, %84, %85, %86, %87, %88, %89, %90, %91, %92, %93, %94, %95, %96, %97, %98, %99, %100, %101, %102, %103, %104, %105, %106, %107, %108, %109, %110, %111, %112, %113, %114, %115, %116, %117, %118, %119, %120, %121, %122, %123, %124, %125, %126, %127}, "
    "%128, %129, 0, 1, 1, 0, 1;\n"
    : "=f"(d[0]), "=f"(d[1]), "=f"(d[2]), "=f"(d[3]), "=f"(d[4]), "=f"(d[5]), "=f"(d[6]), "=f"(d[7]), "=f"(d[8]), "=f"(d[9]), "=f"(d[10]), "=f"(d[11]), "=f"(d[12]), "=f"(d[13]), "=f"(d[14]), "=f"(d[15]), "=f"(d[16]), "=f"(d[17]), "=f"(d[18]), "=f"(d[19]), "=f"(d[20]), "=f"(d[21]), "=f"(d[22]), "=f"(d[23]), "=f"(d[24]), "=f"(d[25]), "=f"(d[26]), "=f"(d[27]), "=f"(d[28]), "=f"(d[29]), "=f"(d[30]), "=f"(d[31]), "=f"(d[32]), "=f"(d[33]), "=f"(d[34]), "=f"(d[35]), "=f"(d[36]), "=f"(d[37]), "=f"(d[38]), "=f"(d[39]), "=f"(d[40]), "=f"(d[41]), "=f"(d[42]), "=f"(d[43]), "=f"(d[44]), "=f"(d[45]), "=f"(d[46]), "=f"(d[47]), "=f"(d[48]), "=f"(d[49]), "=f"(d[50]), "=f"(d[51]), "=f"(d[52]), "=f"(d[53]), "=f"(d[54]), "=f"(d[55]), "=f"(d[56]), "=f"(d[57]), "=f"(d[58]), "=f"(d[59]), "=f"(d[60]), "=f"(d[61]), "=f"(d[62]), "=f"(d[63]), "=f"(d[64]), "=f"(d[65]), "=f"(d[66]), "=f"(d[67]), "=f"(d[68]), "=f"(d[69]), "=f"(d[70]), "=f"(d[71]), "=f"(d[72]), "=f"(d[73]), "=f"(d[74]), "=f"(d[75]), "=f"(d[76]), "=f"(d[77]), "=f"(d[78]), "=f"(d[79]), "=f"(d[80]), "=f"(d[81]), "=f"(d[82]), "=f"(d[83]), "=f"(d[84]), "=f"(d[85]), "=f"(d[86]), "=f"(d[87]), "=f"(d[88]), "=f"(d[89]), "=f"(d[90]), "=f"(d[91]), "=f"(d[92]), "=f"(d[93]), "=f"(d[94]), "=f"(d[95]), "=f"(d[96]), "=f"(d[97]), "=f"(d[98]), "=f"(d[99]), "=f"(d[100]), "=f"(d[101]), "=f"(d[102]), "=f"(d[103]), "=f"(d[104]), "=f"(d[105]), "=f"(d[106]), "=f"(d[107]), "=f"(d[108]), "=f"(d[109]), "=f"(d[110]), "=f"(d[111]), "=f"(d[112]), "=f"(d[113]), "=f"(d[114]), "=f"(d[115]), "=f"(d[116]), "=f"(d[117]), "=f"(d[118]), "=f"(d[119]), "=f"(d[120]), "=f"(d[121]), "=f"(d[122]), "=f"(d[123]), "=f"(d[124]), "=f"(d[125]), "=f"(d[126]), "=f"(d[127])
    : "l"(da), "l"(db));
}

template <int N> struct WG;
#define DEF_WG(N) template <> struct WG<N> { \
  static __device__ __forceinline__ void mma(float (&d)[N / 2], uint64_t a, uint64_t b) { wgmma_n##N(d, a, b); } \
  static __device__ __forceinline__ void first(float (&d)[N / 2], uint64_t a, uint64_t b) { wgmma_n##N##_first(d, a, b); } };
DEF_WG(128) DEF_WG(256)

constexpr uint64_t DESC_A = (1ull << 62) | ((uint64_t)(1024 >> 4) << 32) | (1ull << 16);
constexpr uint64_t DESC_B = (1ull << 62) | ((uint64_t)(1024 >> 4) << 32) | ((uint64_t)(8192 >> 4) << 16);

struct Ring { int s; uint32_t ph; int wrap; };
template <int NS> __device__ __forceinline__ void ring_next(Ring& r) { r.s = (r.s + 1 == NS) ? 0 : r.s + 1; if (r.s == r.wrap) r.ph ^= 1; }

__device__ __forceinline__ int own_order(int it, int j) {
  return it < 2 ? 2 * j + it : it < 4 ? 2 * (j ^ 1) + it - 2 : ((j >> 1) * 4 + 2 * it - (it < 10 ? 4 : 15)) & 15;
}

template <int V> struct IC { static constexpr int v = V; };
template <int I, int E, class F> __device__ __forceinline__ void static_for(F&& f) { if constexpr (I < E) { f(IC<I>{}); static_for<I + 1, E>(f); } }

template <int N, int NS, int PRE, int LAG, class Pre, class Mid, class Last>
__device__ __forceinline__ void mainloop(float (&acc)[N / 2], int nkb, bool own, Ring& r, uint32_t sb, int wg, int lane, uint32_t rel_base, Pre pre, Mid mid, Last last) {
  constexpr int SLOT = RING / NS;
  const uint32_t full = sb + MISC + (NS == 4 ? B_FULL4 : B_FULL6);
  const uint32_t rel = rel_base + (NS == 4 ? B_EMPTY4 : B_EMPTY6);
  const uint32_t s0 = (sb & 0x3FFFF) >> 4, a0 = s0 + wg * (HALF >> 4);
  int ps;
  auto issue = [&](int it, bool first) {
    const uint64_t da = DESC_A | (a0 + ((own && it < 2) ? (STG + it * BLK) >> 4 : r.s * (SLOT >> 4))), db = DESC_B | (s0 + r.s * (SLOT >> 4) + (BLK >> 4));
    mbar_wait(full + r.s * 8, r.ph);
    wg_arrive();
    if (first) WG<N>::first(acc, da, db); else WG<N>::mma(acc, da, db);
#pragma unroll
    for (int k = 1; k < 4; k++) WG<N>::mma(acc, da + k * 2, db + k * 128);
    wg_commit();
  };
  auto retire = [&](int it) {
    wg_wait<1>();
    if (lane < 2) mbar_arrive_cl(rel + ps * 8);
    ps = r.s;
    ring_next<NS>(r);
  };
  issue(0, true);
  ps = r.s;
  ring_next<NS>(r);
  static_for<1, PRE + 1>([&](auto ic) { issue(ic.v, false); pre(ic); retire(ic.v); });
#pragma unroll 1
  for (int it = PRE + 1; it < nkb; it++) {
    if (LAG && it == nkb - LAG && wg == 1) mbar_wait(sb + MISC + B_LAG, 0);
    issue(it, false); mid(it); retire(it);
  }
  last();
  wg_wait<0>();
  if (lane < 2) mbar_arrive_cl(rel + ps * 8);
}

__device__ __forceinline__ uint32_t tag_of(uint32_t ep) { return (ep & 127u) + 1u; }
__device__ __forceinline__ void ln_publish(const float (&v)[64], uint2* st, int j, int row0, int lane, uint32_t ep) {
  float s0 = 0, s1 = 0, s2 = 0, s3 = 0, q0 = 0, q1 = 0, q2 = 0, q3 = 0;
#pragma unroll
  for (int i = 0; i < 16; i++) {
    s0 += v[4 * i]; s1 += v[4 * i + 1]; s2 += v[4 * i + 2]; s3 += v[4 * i + 3];
    q0 = fmaf(v[4 * i], v[4 * i], q0); q1 = fmaf(v[4 * i + 1], v[4 * i + 1], q1); q2 = fmaf(v[4 * i + 2], v[4 * i + 2], q2); q3 = fmaf(v[4 * i + 3], v[4 * i + 3], q3);
  }
  s0 += s1; s2 += s3; q0 += q1; q2 += q3;
  const bool odd = lane & 1;
  float s = (odd ? s2 : s0) + __shfl_xor_sync(~0u, odd ? s0 : s2, 1), q = (odd ? q2 : q0) + __shfl_xor_sync(~0u, odd ? q0 : q2, 1);
  s += __shfl_xor_sync(~0u, s, 2); q += __shfl_xor_sync(~0u, q, 2);
  if ((lane & 3) < 2) st_rlx2(st + j * 128 + row0 + (lane & 1) * 8, __float_as_uint(s), (__float_as_uint(fmaf(s * (-1.f / 128), s, q)) & ~255u) | tag_of(ep));
}
__device__ __forceinline__ void ln_gather(const uint2* st, int row0, int lane, uint32_t ep, float& n0, float& r0, float& n1, float& r1, bool rnd) {
  const uint2* p = st + (lane & 2) * 256 + row0 + (lane & 1) * 8;
  const uint32_t tag = tag_of(ep);
  uint2 a, b, c, d; uint32_t n = 0;
  while (true) {
    a = ld_rlx2(p); b = ld_rlx2(p + 128); c = ld_rlx2(p + 256); d = ld_rlx2(p + 384);
    if ((((a.y ^ tag) | (b.y ^ tag) | (c.y ^ tag) | (d.y ^ tag)) & 255u) == 0) break;
    SPIN_GUARD(n);
  }
  __syncwarp();
  const uint32_t fix = tag ^ 128u;
  float s = (__uint_as_float(a.x) + __uint_as_float(b.x)) + (__uint_as_float(c.x) + __uint_as_float(d.x));
  float q = (__uint_as_float(a.y ^ fix) + __uint_as_float(b.y ^ fix)) + (__uint_as_float(c.y ^ fix) + __uint_as_float(d.y ^ fix));
  q = fmaf(fmaf(__uint_as_float(a.x), __uint_as_float(a.x), __uint_as_float(b.x) * __uint_as_float(b.x)) +
           fmaf(__uint_as_float(c.x), __uint_as_float(c.x), __uint_as_float(d.x) * __uint_as_float(d.x)), 1.f / 128, q);
  s += __shfl_xor_sync(~0u, s, 2); q += __shfl_xor_sync(~0u, q, 2);
  s *= 1.f / 1024;
  const float var = fmaxf(fmaf(-s, s, q * (1.f / 1024)), 0.f);
  float r;
  if (rnd) {
    float sd; asm("sqrt.approx.f32 %0, %1;" : "=f"(sd) : "f"(bf_round(bf_round(var) + 1e-5f)));
    r = rcp(bf_round(sd)); s = bf_round(s);
  } else r = rsqrtf(var + 1e-5f);
  const float nn = -s * r;
  const float ro = __shfl_xor_sync(~0u, r, 1), no = __shfl_xor_sync(~0u, nn, 1);
  const bool odd = lane & 1;
  r0 = odd ? ro : r; n0 = odd ? no : nn; r1 = odd ? r : ro; n1 = odd ? nn : no;
}
__device__ __forceinline__ void load_vec(uint32_t* w, uint32_t sb, int sec, int b, int lane) {
#pragma unroll
  for (int q = 0; q < 2; q++) { uint4 t = lds128(sb + MISC + MODV + sec * 256 + (lane & 3) * 64 + b * 32 + q * 16); w[4 * q] = t.x; w[4 * q + 1] = t.y; w[4 * q + 2] = t.z; w[4 * q + 3] = t.w; }
}
__device__ __forceinline__ void stage_done(uint32_t sb, int wg, int b, int lane) {
  fence_async_smem();
  __syncwarp();
  if (lane == 0) mbar_arrive(sb + MISC + B_RDY + b * 8);
}
__device__ __forceinline__ uint32_t hfma2(uint32_t a, uint32_t b, uint32_t c) { uint32_t r; asm("fma.rn.bf16x2 %0, %1, %2, %3;" : "=r"(r) : "r"(a), "r"(b), "r"(c)); return r; }
__device__ __forceinline__ void ln_apply(const float (&v)[64], const uint2* st, int row0, uint32_t ep, uint32_t sb, int sec_shift, int sec_scale, uint32_t stg_row, int wg, int lane) {
  uint32_t sc[16], sh[16];
#pragma unroll
  for (int b = 0; b < 2; b++) { load_vec(sc + 8 * b, sb, sec_scale, b, lane); load_vec(sh + 8 * b, sb, sec_shift, b, lane); }
  float n0, r0, n1, r1;
  ln_gather(st, row0, lane, ep, n0, r0, n1, r1, sec_shift == 0);
#pragma unroll
  for (int i = 0; i < 16; i += 2) {
    if (i == 8) { const float z = lds32f(sb + MISC + ZERO); n0 += z; n1 += z; }
    uint32_t w[4];
#pragma unroll
    for (int u = 0; u < 2; u++) {
      int q = i + u;
      w[2 * u] = hfma2(pack2(fmaf(v[4 * q], r0, n0), fmaf(v[4 * q + 1], r0, n0)), sc[q], sh[q]);
      w[2 * u + 1] = hfma2(pack2(fmaf(v[4 * q + 2], r1, n1), fmaf(v[4 * q + 3], r1, n1)), sc[q], sh[q]);
    }
    stsm4(stg_row + (i >> 3) * BLK + ((((i & 7) + (lane >> 4)) ^ (lane & 7)) << 4), w[0], w[1], w[2], w[3]);
    if ((i & 7) == 6) { stage_done(sb, wg, i >> 3, lane); }
  }
}
__device__ __forceinline__ uint32_t hmul2(uint32_t a, uint32_t b) { uint32_t r; asm("mul.rn.bf16x2 %0, %1, %2;" : "=r"(r) : "r"(a), "r"(b)); return r; }
__device__ __forceinline__ uint32_t silu_mul2(uint32_t g, uint32_t u) {
  const uint32_t h = hmul2(g, 0x3f003f00u);
  const float h0 = bf_lo(h), h1 = bf_hi(h);
  return hmul2(pack2(fmaf(h0, tanh_fast(h0), h0), fmaf(h1, tanh_fast(h1), h1)), u);
}

__device__ __forceinline__ void gemv_fma(float (&a)[8], uint4 w, float s) {
  a[0] = fmaf(bf_lo(w.x), s, a[0]); a[1] = fmaf(bf_hi(w.x), s, a[1]); a[2] = fmaf(bf_lo(w.y), s, a[2]); a[3] = fmaf(bf_hi(w.y), s, a[3]);
  a[4] = fmaf(bf_lo(w.z), s, a[4]); a[5] = fmaf(bf_hi(w.z), s, a[5]); a[6] = fmaf(bf_lo(w.w), s, a[6]); a[7] = fmaf(bf_hi(w.w), s, a[7]);
}
__device__ __forceinline__ float silu_c(float v) { return bf_round(__fdividef(v, 1.f + __expf(-v))); }
__device__ __forceinline__ float mod_gather(const uint32_t* p, uint32_t ep) {
  const uint32_t tag = tag_of(ep), fix = tag ^ 128u;
  uint32_t a, b, c, d, n = 0;
  while (true) {
    a = ld_rlx1(p); b = ld_rlx1(p + 128); c = ld_rlx1(p + 256); d = ld_rlx1(p + 384);
    if ((((a ^ tag) | (b ^ tag) | (c ^ tag) | (d ^ tag)) & 255u) == 0) break;
    SPIN_GUARD(n);
  }
  return (__uint_as_float(a ^ fix) + __uint_as_float(b ^ fix)) + (__uint_as_float(c ^ fix) + __uint_as_float(d ^ fix));
}
__device__ __forceinline__ void mod_store(uint32_t sb, int sec, int col, float v) {
  v = bf_round(v);
  if (sec == 1) v += 1.f;
  sts16(sb + MISC + MODV + sec * 256 + (((col >> 1) & 3) * 16 + (col >> 3)) * 4 + (col & 1) * 2, __float2bfloat16_rn(v));
}

__global__ void __cluster_dims__(2, 1, 1) __launch_bounds__(384, 1)
fused_kernel(const bf16* __restrict__ cvec, const bf16* __restrict__ wmod, Scratch* gs, int by_sm, const __grid_constant__ Maps maps) {
  extern __shared__ __align__(1024) uint8_t smem_raw[];
  const uint32_t sb = smem_u32(smem_raw);
  const int warp = __shfl_sync(~0u, threadIdx.x >> 5, 0), lane = threadIdx.x & 31;
  const int rank = blockIdx.x & 1;
  uint32_t sm; asm volatile("mov.u32 %0, %%smid;" : "=r"(sm));
  const int t = sm >> 1, v = t < 32 ? t : t < 60 ? t + 1 + (((t - 32) * 37) >> 8) : (t - 58) * 8;
  const int cid = !by_sm ? (blockIdx.x >> 1) - 2 : (t & ~1) == 60 ? t - 62 : (v & 1) * 32 + ((v >> 1) & 31);
  const bool extra = cid < 0;
  const int bid = cid * 2 + rank;
  const int m = cid >> 2, j = (cid & 3) * 2 + rank;
  const uint32_t bar = sb + MISC;

  if (warp >= 8) {
    asm volatile("setmaxnreg.dec.sync.aligned.u32 40;");
    if (extra) {
      if (warp == 8) {
        if (lane == 0) { for (int s = 0; s < 6; s++) { mbar_init(bar + B_FULL6 + s * 8, 1); mbar_init(bar + B_EMPTY6 + s * 8, 8); } fence_async_smem(); }
        __syncwarp();
        asm volatile("bar.arrive 2, 288;" ::: "memory");
        __nanosleep(XSLEEP);
#pragma unroll 1
        for (int it = 0, s = 0, par = 1; it < 64; it++) {
          mbar_wait(bar + B_EMPTY6 + s * 8, par);
          if (elect()) { mbar_expect_tx(bar + B_FULL6 + s * 8, 32768); tma_3d(sb + s * 32768, &maps.wmod, bar + B_FULL6 + s * 8, 0, (it & 15) * 64, 12 + (it >> 4) * 4 + bid); }
          if (++s == 6) { s = 0; par ^= 1; }
        }
      }
    } else if (warp < 10) {
      uint32_t s6 = 0, p6 = 1;
      auto next6 = [&]() { if (++s6 == 6) { s6 = 0; p6 ^= 1; } };
      auto drained4 = [&](int q, int late) { if (q < 5) mbar_wait(bar + B_EMPTY4 + (((late ? 0x10332 : 0x32110) >> (4 * q)) & 3) * 8, 1); };
      auto drained6 = [&](int q) { if (q < 3) mbar_wait(bar + B_EMPTY6 + ((0x154 >> (4 * q)) & 7) * 8, q >> 1); };
      auto skip6 = [&]() { mbar_wait(bar + B_EMPTY6 + s6 * 8, p6); if (elect()) mbar_arrive(bar + B_FULL6 + s6 * 8); next6(); };
      if (warp == 8) {
        const uint32_t t_start = clock();
        if (lane == 0) {
          if (sb & 1023) bail();
          for (int b = 0; b < 2; b++) mbar_init(bar + B_X + b * 8, 1);
          for (int s = 0; s < 4; s++) { mbar_init(bar + B_FULL4 + s * 8, 2); mbar_init(bar + B_EMPTY4 + s * 8, 16); }
          for (int s = 0; s < 6; s++) { mbar_init(bar + B_FULL6 + s * 8, 2); mbar_init(bar + B_EMPTY6 + s * 8, 16); }
          for (int b = 0; b < 2; b++) { mbar_init(bar + B_RDY + b * 8, 8); mbar_init(bar + B_FREE + b * 8, 1); mbar_init(bar + B_HH + b * 8, 1); }
          mbar_init(bar + B_MOD, 1); mbar_init(bar + B_LAG, 4); mbar_init(bar + B_HALO, 2); mbar_init(bar + B_ALL, 1); mbar_init(bar + B_HH2, 1);
          asm volatile("st.shared.u32 [%0], 0;" :: "r"(bar + ZERO) : "memory");
          asm volatile("fence.mbarrier_init.release.cluster;" ::: "memory");
          fence_async_smem();
        }
        __syncwarp();
        cl_arrive_relaxed();
        auto wide = [&](int s, int par, const CUtensorMap* m0, int a0, const CUtensorMap* m1, int a1, int kb, bool spaced) {
          const uint32_t full = bar + B_FULL4 + s * 8, d = sb + s * 49152 + BLK;
          mbar_wait(full + 32, par);
          const uint32_t t0 = clock();
          if (elect()) { mbar_expect_tx(full, 2 * BLK); tma_3d(d, m0, full, 0, kb * 64, a0); }
          if (spaced) while ((uint32_t)clock() - t0 < GAP) {}
          if (elect()) tma_3d(d + BLK, m1, full, 0, kb * 64, a1);
          if (spaced) while ((uint32_t)clock() - t0 < 2 * GAP) {}
        };
        while ((uint32_t)clock() - t_start < XDELAY) {}
        if (elect()) for (int b = 0; b < 2; b++) { mbar_expect_tx(bar + B_X + b * 8, BLK); tma_3d(sb + STG + b * BLK, &maps.x, bar + B_X + b * 8, j * 128 + b * 64, m * 64, 0); }
        mbar_wait(bar + B_X + 8, 0);
#pragma unroll 1
        for (int ph = 0; ph < 2; ph++) {
          const CUtensorMap* const m0 = ph ? &maps.w1 : &maps.wqkv;
#pragma unroll 1
          for (int it = 0; it < (ph ? 48 : 16); it++) {
            const int a = (ph ? it & 48 : 16) + 2 * j;
            if (ph) drained6(it);
            wide((it + 2 * ph) & 3, ~(it >> 2) & 1, m0, a, m0 + ph, ph ? a : a + 16, it < 16 ? own_order(it, j) : it & 15, it < 4);
            if (it >= 44) {
              if (it == 44) { mbar_wait(bar + B_FREE, 0); mbar_wait(bar + B_FREE + 8, 0); if (elect()) mbar_expect_tx(bar + B_X, 2 * BLK); }
              if (elect()) bulk_ld(sb + STG + (it - 44) * HALF, gs->x1 + bid * 2048 + (it - 44) * 512, HALF, bar + B_X);
            }
          }
#pragma unroll 1
          for (int it = 0; it < 16; it++) {
            const uint32_t full = bar + B_FULL6 + s6 * 8, d = sb + s6 * 32768 + BLK;
            drained4(it, ph);
            mbar_wait(full + 48, p6);
            if (elect()) {
              mbar_expect_tx(full, BLK);
              tma_3d(d, ph ? &maps.w1s : &maps.wqkv, full, 0, it * 64, ph ? 48 + j : 2 * j);
              if (ph) tma_3d(d + HALF, &maps.w3s, full, 0, it * 64, 48 + j);
            }
            next6();
          }
          const CUtensorMap* const m2 = ph ? &maps.w2 : &maps.wo;
#pragma unroll 1
          for (int it = 0; it < (ph ? 56 : 16); it++) {
            const uint32_t full = bar + B_FULL6 + s6 * 8;
            const int kb = ph ? it : own_order(it, j);
            mbar_wait(full + 48, p6);
            if (elect()) { mbar_expect_tx(full, BLK); tma_3d(sb + s6 * 32768 + BLK, m2, full, 0, kb * 64, 2 * j); }
            next6();
          }
          if (!ph) skip6();
        }
      } else {
        if (lane < 9) prefetch_map(&maps.x + lane);
        const uint32_t ep = gs->epoch[blockIdx.x] + 1;
        cl_arrive_relaxed(); cl_wait();
        auto plain = [&](uint32_t full, uint32_t empty, int par, uint32_t slot, const uint4* blk) {
          mbar_wait(empty, par);
          if (elect()) { mbar_expect_tx(full, BLK); bulk_ld_mc(slot + rank * HALF, blk + rank * 512, HALF, full); }
        };
        auto plain6 = [&](const uint4* blk) { plain(bar + B_FULL6 + s6 * 8, bar + B_EMPTY6 + s6 * 8, p6, sb + s6 * 32768, blk); next6(); };
        uint32_t ready = 0;
        auto poll = [&](int e) { ready = __ballot_sync(~0u, ld_acquire(gs->flag + (m * 128 + e * 16 + (lane & 14)) * FS) == ep); };
        auto need = [&](int e, uint32_t mask) {
          if ((ready & mask) != mask) {
            uint32_t n = 0;
            do { poll(e); SPIN_GUARD(n); } while ((ready & mask) != mask);
            fence_async_global();
          }
        };
        auto fresh = [&](int e, int it, uint32_t full, uint32_t empty, int par, uint32_t slot, uint4* src) {
          if (it >= 4) {
            const int kb = own_order(it, j);
            if (it < 10) need(e, 1u << kb); else if (it == 10) mbar_wait(bar + B_ALL, e & 1);
            plain(full, empty, par, slot, src + kb * 1024);
          } else {
            if (it == 0) ready = 0;
            mbar_wait(empty, par);
            if (it < 2) { if (elect()) mbar_arrive(full); }
            else {
              const int b = it > 2;
              const uint32_t to_peer = mapa(sb, rank ^ 1) - sb;
              if (elect()) mbar_expect_tx(full, BLK);
              const bool push = e != 1;
              mbar_wait(bar + (b ? (push ? B_RDY + 8 : B_FREE + 8) : B_RDY), e & 1);
              if (elect()) {
                if (b == 0) {
                  bulk_st(src + 2 * j * 1024, sb + STG, BLK);
                  bulk_commit();
                  bulk_wait_all();
                  mbar_arrive(bar + B_FREE);
                }
                if (b && push) bulk_push(slot + to_peer, sb + STG + BLK, BLK, full + to_peer);
                else {
                  fence_async_global();
                  bulk_ld(slot + to_peer, src + (2 * j + b) * 1024, BLK, full + to_peer);
                }
              }
              __syncwarp();
            }
          }
        };
        uint4* const h = gs->h + m * 16384;
#pragma unroll 1
        for (int e = 0; e < 3; e++) {
#pragma unroll 1
          for (int it = 0; it < 16; it++) {
            const int s = e == 1 ? s6 : (it + e) & 3;
            const uint32_t full = bar + (e == 1 ? B_FULL6 : B_FULL4) + s * 8;
            if (e == 2) drained6(it);
            fresh(e, it, full, full + (e == 1 ? 48 : 32), e == 1 ? p6 : ~(it >> 2) & 1, sb + s * (e == 1 ? 32768 : 49152), e == 1 ? gs->o + m * 16384 : h);
            if (e == 1) next6();
          }
          if (e == 1) { skip6(); continue; }
#pragma unroll 1
          for (int it = 16; it < 16 + 16 * e; it++) {
            const int s = (it + 2) & 3;
            const uint32_t full = bar + B_FULL4 + s * 8;
            plain(full, full + 32, ~(it >> 2) & 1, sb + s * 49152, h + (it & 15) * 1024);
          }
#pragma unroll 1
          for (int it = 0; it < 16; it++) { drained4(it, e); plain6(h + it * 1024); }
        }
#pragma unroll 1
        for (int it = 0; it < 56; it++) {
          if (it == 0 || it == 32 || it == 48) mbar_wait(bar + (it == 48 ? B_HH2 : B_HH + (it >> 2)), 0);
          plain6(gs->hh + m * 57344 + it * 1024);
        }
      }
    } else {
      const int b = warp - 10;
      const uint32_t ep = gs->epoch[blockIdx.x] + 1;
      const uint32_t stg = sb + STG + b * BLK;
      cl_arrive_relaxed(); cl_wait();
      auto all_there = [&](int u, uint32_t done) {
        const uint32_t* fl = gs->flag + u * FS;
        uint32_t n = 0;
        while (!__all_sync(~0u, ld_acquire(fl) == ep)) { __nanosleep(100); SPIN_GUARD(n); }
        fence_async_global();
        if (lane == 0) mbar_arrive(done);
      };
      auto fetch_mod = [&](int sec) {
        const uint4* p = (const uint4*)(gs->modv + (sec - 2) * 1024 + j * 128) + lane;
        uint4 v0, v1; uint32_t n = 0;
        while (true) {
          v0 = ld_rlx4(p); v1 = ld_rlx4(p + 32);
          if (v0.y == ep && v0.w == ep && v1.y == ep && v1.w == ep) break;
          SPIN_GUARD(n);
        }
        const uint32_t d = sb + MISC + MODV + sec * 256 + ((lane & 3) * 16 + (lane >> 2)) * 4;
        asm volatile("st.shared.u32 [%0], %1;" :: "r"(d), "r"(__byte_perm(v0.x, v0.z, 0x7632)) : "memory");
        asm volatile("st.shared.u32 [%0], %1;" :: "r"(d + 32), "r"(__byte_perm(v1.x, v1.z, 0x7632)) : "memory");
        __syncwarp();
      };
#pragma unroll 1
      for (int e = 0; e < 7 - b; e++) {
        if (lane == 0) {
          if (e < 3) {
            mbar_wait(bar + B_FREE, e & 1);
            if (b) {
              const uint32_t t0 = clock();
              while ((uint32_t)clock() - t0 < (e == 1 ? B1D : B1P)) {}
              mbar_wait(bar + B_RDY + 8, e & 1);
              bulk_st((e == 1 ? gs->o : gs->h) + m * 16384 + (2 * j + 1) * 1024, stg, BLK);
              bulk_commit();
              bulk_wait_all();
              mbar_arrive(bar + B_FREE + 8);
            }
            st_release(gs->flag + (m * 128 + e * 16 + 2 * j + b) * FS, ep);
          } else {
            const int kb = (e < 6 ? 2 * (8 * (e - 3) + j) : 48 + j) + b;
            mbar_wait(bar + B_RDY + b * 8, e & 1);
#pragma unroll 1
            for (int q = 0; q < NPIECE; q++) { if (q) __nanosleep(PSLEEP); bulk_st(gs->hh + m * 57344 + kb * 1024 + q * (1024 / NPIECE), stg + q * (BLK / NPIECE), BLK / NPIECE); }
            bulk_commit();
            bulk_wait_all();
            mbar_arrive(bar + B_FREE + b * 8);
            st_release(gs->flag + (m * 128 + U_HH + kb) * FS, ep);
          }
        }
        __syncwarp();
        if (e < 3 && b) all_there(m * 128 + e * 16 + (lane & 15), bar + B_ALL);
        if (e == 4 && b) all_there(m * 128 + U_HH + lane, bar + B_HH);
        if (!b && (e == 1 || e == 2)) {
#pragma unroll 1
          for (int sec = e == 1 ? 2 : 5; sec < 4 + e; sec++) fetch_mod(sec);
          if (e == 1) { if (lane == 0) mbar_arrive(bar + B_MOD); }
        }
        if (e == 0) {
          mbar_wait(bar + B_EMPTY6 + 24, 0);
          __nanosleep(HSLEEP);
#pragma unroll 1
          for (int w = 0; w < 4; w++) {
            const uint4* hp = gs->halo + ((m * 8 + j) * 2 + (w & 1)) * 512 + b * 256 + (w >> 1) * 128 + lane;
            uint4 q[4] = {}; uint32_t n = 0;
            while (m > 0) {
              bool ok = true;
#pragma unroll
              for (int i = 0; i < 4; i++) q[i] = ld_rlx4(hp + i * 32);
#pragma unroll
              for (int i = 0; i < 4; i++) ok = ok && q[i].y == ep && q[i].w == ep;
              if (ok) break;
              SPIN_GUARD(n);
            }
#pragma unroll
            for (int i = 0; i < 2; i++) sts128(stg + lane * 16 + (w & 1) * HALF + (w >> 1) * 1024 + i * 512, q[2 * i].x, q[2 * i + 1].x, q[2 * i].z, q[2 * i + 1].z);
          }
          __syncwarp();
          if (lane == 0) mbar_arrive(bar + B_HALO);
        }
      }
      if (b) { all_there(m * 128 + U_HH + 32 + (lane & 15), bar + B_HH + 8); all_there(m * 128 + U_HH + 48 + (lane & 7), bar + B_HH2); }
    }
  } else {
    const int wg = warp >> 2, wq = warp & 3, tid = threadIdx.x;
    const int g = lane >> 2, c = lane & 3;
    const int sec0 = (m >> 1) & 1, hf0 = m & 1, ks0 = (m >> 2) & 3;
    uint4 wv[8];
    uint32_t ep0; uint16_t cv_;
    asm volatile("ld.global.nc.u16 %0, [%1];" : "=h"(cv_) : "l"(cvec + ks0 * 256 + warp * 32 + lane));
    asm volatile("ld.global.u32 %0, [%1];" : "=r"(ep0) : "l"(gs->epoch + (blockIdx.x | (lane & by_sm & 2))));
    if (!extra) {
      const bf16* wp = wmod + (size_t)(ks0 * 256 + warp * 32 + (lane >> 3)) * 6144 + sec0 * 1024 + j * 128 + hf0 * 64 + (lane & 7) * 8;
#pragma unroll
      for (int i = 0; i < 8; i++) wv[i] = ldg_nc(wp + (size_t)i * 4 * 6144);
      cl_arrive_relaxed();
    }
    asm volatile("setmaxnreg.inc.sync.aligned.u32 232;" ::: "memory");
    if (__builtin_expect(extra, 0)) {
      const uint32_t ep = ep0 + 1;
      float sv[4];
#pragma unroll
      for (int p = 0; p < 4; p++) sv[p] = silu_c(__bfloat162float(cvec[64 * (4 * p + (lane >> 3)) + 8 * warp + (lane & 7)]));
      named_bar(2, 288);
      int s = 0, par = 0;
#pragma unroll 1
      for (int sec = 0; sec < 4; sec++) {
        float a[8] = {0, 0, 0, 0, 0, 0, 0, 0};
#pragma unroll 1
        for (int it = 0; it < 16; it++) {
          const float sc = it < 4 ? sv[0] : it < 8 ? sv[1] : it < 12 ? sv[2] : sv[3];
          mbar_wait(bar + B_FULL6 + s * 8, par);
          uint4 w[8];
#pragma unroll
          for (int i = 0; i < 8; i++) w[i] = lds128(sb + s * 32768 + (warp * 8 + i) * 512 + lane * 16);
#pragma unroll
          for (int i = 0; i < 8; i++) gemv_fma(a, w[i], __shfl_sync(~0u, sc, (it & 3) * 8 + i));
          if (lane == 0) mbar_arrive(bar + B_EMPTY6 + s * 8);
          if (++s == 6) { s = 0; par ^= 1; }
        }
        const uint32_t red = sb + STG + sec * 8192;
        sts128(red + warp * 1024 + lane * 32, __float_as_uint(a[0]), __float_as_uint(a[1]), __float_as_uint(a[2]), __float_as_uint(a[3]));
        sts128(red + warp * 1024 + lane * 32 + 16, __float_as_uint(a[4]), __float_as_uint(a[5]), __float_as_uint(a[6]), __float_as_uint(a[7]));
        named_bar(1, 256);
        float t = 0;
#pragma unroll
        for (int q = 0; q < 8; q++) t += lds32f(red + q * 1024 + tid * 4);
        t = bf_round(t);
        if (sec == 2) t = bf_round(t + 1.f);
        st_rlx2(gs->modv + sec * 1024 + (bid + 4) * 256 + tid, __float_as_uint(t), ep);
      }
      if (tid == 0) gs->epoch[blockIdx.x] = ep;
      return;
    }
    const int row0 = wg * 64 + wq * 16 + g;
    if (c < 2) st_rlx2(gs->stat + m * 1024 + j * 128 + row0 + c * 8, 0, 0);
    cl_wait();
    uint32_t ep;
    asm volatile("add.u32 %0, %1, 1;" : "=r"(ep) : "r"(ep0) : "memory");
    const float sc_ = silu_c(__uint_as_float((uint32_t)cv_ << 16));
    const uint32_t rel = mapa(bar, (lane & 1) ^ rank);
    const uint32_t stg_row = sb + STG + (wg * 64 + wq * 16 + (lane & 15)) * 128;
    const uint32_t fre = bar + B_FREE;
    Ring r4{0, 0, 0}, r6{0, 0, 0};
    auto none = [](auto) {};
    uint32_t xk[32];
    {
      float a[8] = {0, 0, 0, 0, 0, 0, 0, 0};
#pragma unroll
      for (int i = 0; i < 8; i++) gemv_fma(a, wv[i], __shfl_sync(~0u, sc_, i * 4 + (lane >> 3)));
#pragma unroll
      for (int i = 0; i < 8; i++) { a[i] += __shfl_xor_sync(~0u, a[i], 8); a[i] += __shfl_xor_sync(~0u, a[i], 16); }
      if (lane < 8) {
        sts128(sb + RED_OFF + warp * 256 + lane * 32, __float_as_uint(a[0]), __float_as_uint(a[1]), __float_as_uint(a[2]), __float_as_uint(a[3]));
        sts128(sb + RED_OFF + warp * 256 + lane * 32 + 16, __float_as_uint(a[4]), __float_as_uint(a[5]), __float_as_uint(a[6]), __float_as_uint(a[7]));
      }
      named_bar(1, 256);
      if (tid < 64) {
        float s = 0;
#pragma unroll
        for (int w = 0; w < 8; w++) s += lds32f(sb + RED_OFF + w * 256 + tid * 4);
        st_rlx1(gs->modp + ((j * 2 + sec0) * 4 + ks0) * 128 + hf0 * 64 + tid, (__float_as_uint(s) & ~255u) | tag_of(ep));
      }
      float v[64];
      mbar_wait(bar + B_X, 0); mbar_wait(bar + B_X + 8, 0);
#pragma unroll
      for (int i = 0; i < 16; i += 2) {
        uint32_t w0, w1, w2, w3;
        ldsm4(stg_row + (i >> 3) * BLK + ((((i & 7) + (lane >> 4)) ^ (lane & 7)) << 4), w0, w1, w2, w3);
        xk[2 * i] = w0; xk[2 * i + 1] = w1; xk[2 * i + 2] = w2; xk[2 * i + 3] = w3;
        v[4 * i] = bf_lo(w0); v[4 * i + 1] = bf_hi(w0); v[4 * i + 2] = bf_lo(w1); v[4 * i + 3] = bf_hi(w1);
        v[4 * i + 4] = bf_lo(w2); v[4 * i + 5] = bf_hi(w2); v[4 * i + 6] = bf_lo(w3); v[4 * i + 7] = bf_hi(w3);
      }
      ln_publish(v, gs->stat + m * 1024, j, row0, lane, ep);
      mod_store(sb, tid >> 7, tid & 127, mod_gather(gs->modp + (j * 2 + (tid >> 7)) * 512 + (tid & 127), ep));
      named_bar(1, 256);
      ln_apply(v, gs->stat + m * 1024, row0, ep, sb, 0, 1, stg_row, wg, lane);
      named_bar(1, 256);
    }
    {
      uint32_t kf[32], vf[32], pv[32];
      const bool first = wq == 0 && m == 0;
      const uint32_t xa = sb + STG + wg * HALF + wq * 2048 + lane * 16;
      {
        float acc[128];
        mainloop<256, 4, 0, 0>(acc, 16, true, r4, sb, wg, lane, rel, none, none, [&] {
          mbar_wait(fre + 8, 0);
          if (c < 2) st_rlx2(gs->stat + (16 + m) * 1024 + j * 128 + row0 + c * 8, 0, 0);
        });
#pragma unroll
        for (int i = 0; i < 32; i++) { kf[i] = pack2(acc[2 * i], acc[2 * i + 1]); vf[i] = pack2(acc[64 + 2 * i], acc[65 + 2 * i]); }
      }
      float acc[64];
      constexpr int QP = 2;
      mainloop<128, 6, 8 / QP, 0>(acc, 16, false, r6, sb, wg, lane, rel, [&](auto ic) {
        constexpr int q = (ic.v - 1) * QP;
#pragma unroll
        for (int i = 4 * q; i < 4 * (q + QP); i++) vf[i] = movm(vf[i]);
        if (wq == 3) {
          if (m < 15) {
            uint4* hp = gs->halo + (((m + 1) * 8 + j) * 2 + wg) * 512 + lane;
#pragma unroll
            for (int i = 2 * q; i < 2 * (q + QP); i++) st_rlx4(hp + i * 32, kf[2 * i + 1], ep, vf[2 * i + 1], ep);
          }
        } else {
#pragma unroll
          for (int i = q; i < q + QP; i++) sts128(xa + 2048 + (i >> 2) * BLK + (i & 3) * 512, kf[4 * i + 1], kf[4 * i + 3], vf[4 * i + 1], vf[4 * i + 3]);
        }
      }, none, [&] {
        named_bar(2 + wg, 128);
        if (wq == 0) mbar_wait(bar + B_HALO, 0);
#pragma unroll
        for (int i = 0; i < 8; i++) {
          uint4 q = lds128(xa + (i >> 2) * BLK + (i & 3) * 512);
          pv[4 * i] = q.x; pv[4 * i + 1] = q.y; pv[4 * i + 2] = q.z; pv[4 * i + 3] = q.w;
        }
        __syncwarp();
      });
      int gz = g;
#pragma unroll
      for (int b = 0; b < 2; b++) {
        const bool up0 = 2 * c > gz, up1 = 2 * c + 1 > gz;
        const uint32_t mup = (up0 ? 0xffffu : 0u) | (up1 ? 0xffff0000u : 0u);
        float l[2][4], mx[4];
#pragma unroll
        for (int h = 0; h < 2; h++) {
          uint32_t q[8];
          const int k = 16 * b + 8 * h;
#pragma unroll
          for (int i = 0; i < 8; i++) q[i] = pack2(acc[2 * k + 2 * i], acc[2 * k + 2 * i + 1]);
          float s0[4], s1[4], s2[4];
          mma16z(s0, q[0], q[1], q[2], q[3], pv[k], pv[k + 1]); mma16z(s1, q[0], q[1], q[2], q[3], kf[k], kf[k + 2]); mma16z(s2, q[0], q[1], q[2], q[3], kf[k + 1], kf[k + 3]);
          mma16(s0, q[4], q[5], q[6], q[7], pv[k + 4], pv[k + 5]); mma16(s1, q[4], q[5], q[6], q[7], kf[k + 4], kf[k + 6]); mma16(s2, q[4], q[5], q[6], q[7], kf[k + 5], kf[k + 7]);
          if (first) { s0[0] = -INFINITY; s0[1] = -INFINITY; }
          l[h][0] = up0 ? s0[0] : s1[0]; l[h][1] = up1 ? s0[1] : s1[1]; l[h][2] = up0 ? s1[2] : s2[2]; l[h][3] = up1 ? s1[3] : s2[3];
          mx[2 * h] = fmaxf(l[h][0], l[h][1]); mx[2 * h + 1] = fmaxf(l[h][2], l[h][3]);
        }
#pragma unroll
        for (int o = 1; o < 4; o <<= 1) {
#pragma unroll
          for (int h = 0; h < 4; h++) mx[h] = fmaxf(mx[h], __shfl_xor_sync(~0u, mx[h], o));
        }
#pragma unroll
        for (int h = 0; h < 2; h++) {
          const float n0 = -mx[2 * h] * SCL, n1 = -mx[2 * h + 1] * SCL;
          const uint32_t pa = pack2(ex2(fmaf(l[h][0], SCL, n0)), ex2(fmaf(l[h][1], SCL, n0))), pb = pack2(ex2(fmaf(l[h][2], SCL, n1)), ex2(fmaf(l[h][3], SCL, n1)));
          float sm[4];
          mma8z(sm, pa, pb, 0x3f803f80u);
          const float ia = rcp(sm[0]), ib = rcp(sm[2]);
#pragma unroll
          for (int i = 8 * b + 4 * h; i < 8 * b + 4 * h + 4; i += 2) {
            uint32_t of[4];
#pragma unroll
            for (int d = 0; d < 2; d++) {
              float o[4];
              mma16z(o, pa & ~mup, pb & mup, 0u, pb & ~mup, vf[2 * (i + d)], vf[2 * (i + d) + 1]);
              mma8(o, pa & mup, 0u, pv[2 * i + 2 + d]);
              of[2 * d] = pack2(o[0] * ia, o[1] * ia); of[2 * d + 1] = pack2(o[2] * ib, o[3] * ib);
            }
            stsm4(stg_row + b * BLK + ((((i & 7) + (lane >> 4)) ^ (lane & 7)) << 4), of[0], of[1], of[2], of[3]);
          }
        }
        stage_done(sb, wg, b, lane);
        if (b == 0) gz += __float_as_uint(lds32f(bar + ZERO));
      }
      named_bar(1, 256);
    }
    uint32_t pk[64];
    {
      float acc[64];
      mainloop<128, 6, 0, 0>(acc, 16, true, r6, sb, wg, lane, rel, none, none, [&] {
        mbar_wait(bar + B_MOD, 0); mbar_wait(fre + 8, 1);
        load_vec(pk + 32, sb, 2, 0, lane); load_vec(pk + 40, sb, 2, 1, lane);
#pragma unroll
        for (int i = 0; i < 32; i++) { pk[i] = xk[i]; asm volatile("" : "+r"(pk[i])); }
      });
#pragma unroll
      for (int i = 0; i < 32; i++) {
        acc[2 * i] = fmaf(acc[2 * i], bf_lo(pk[32 + (i >> 1)]), bf_lo(pk[i]));
        acc[2 * i + 1] = fmaf(acc[2 * i + 1], bf_hi(pk[32 + (i >> 1)]), bf_hi(pk[i]));
      }
      ln_publish(acc, gs->stat + (16 + m) * 1024, j, row0, lane, ep);
      mbar_wait(bar + B_FULL6 + 16, 1);
      if (lane < 2) mbar_arrive_cl(rel + B_EMPTY6 + 16);
      ring_next<6>(r6);
#pragma unroll
      for (int i = 0; i < 32; i++) { pk[i] = pack2(acc[2 * i], acc[2 * i + 1]); pk[32 + i] = 0; }
      ln_apply(acc, gs->stat + (16 + m) * 1024, row0, ep, sb, 3, 4, stg_row, wg, lane);
      named_bar(1, 256);
    }
    auto swiglu = [&](int q, int uo, int par) {
      if ((q & 3) == 0 && par >= 0) mbar_wait(fre + 2 * q, par);
      uint32_t w[4];
#pragma unroll
      for (int u = 0; u < 4; u++) w[u] = silu_mul2(pk[4 * q + u], pk[uo + 4 * q + u]);
      stsm4(stg_row + (q >> 2) * BLK + ((((2 * q & 7) + (lane >> 4)) ^ (lane & 7)) << 4), w[0], w[1], w[2], w[3]);
    };
    r4.s = r4.wrap = 2;
#pragma unroll 1
    for (int t = 0; t < 3; t++) {
      float acc[128];
      mainloop<256, 4, 4, 0>(acc, 16, t == 0, r4, sb, wg, lane, rel, [&](auto ic) {
        if (t) {
          if (ic.v == 3) stage_done(sb, wg, 0, lane);
          swiglu(2 * ic.v - 2, 32, ~t & 1); swiglu(2 * ic.v - 1, 32, 0);
        }
      }, [&](int it) {
        if (t && it == 5) stage_done(sb, wg, 1, lane);
#pragma unroll
        for (int i = 0; i < 8; i++)
          if (t == 0 && it == 8 + i) gs->x1[bid * 2048 + (i >> 2) * 1024 + warp * 128 + (i & 3) * 32 + lane] = make_uint4(pk[4 * i], pk[4 * i + 1], pk[4 * i + 2], pk[4 * i + 3]);
      }, [&] { if (t == 0) fence_async_global(); else if (t == 2) mbar_wait(bar + B_X, 1); });
#pragma unroll
      for (int i = 0; i < 64; i++) pk[i] = pack2(acc[2 * i], acc[2 * i + 1]);
    }
    uint32_t x1[32];
    {
      float acc[64];
      mainloop<128, 6, 10, 0>(acc, 16, false, r6, sb, wg, lane, rel, [&](auto ic) {
        constexpr int b = ic.v > 5, q = ic.v - 5 * b;
        if (q == 1) {
          if (b) stage_done(sb, wg, 0, lane);
#pragma unroll
          for (int i = 4 * b; i < 4 * b + 4; i++) { const uint4 x = lds128(sb + STG + b * BLK + warp * 2048 + (i & 3) * 512 + lane * 16); x1[4 * i] = x.x; x1[4 * i + 1] = x.y; x1[4 * i + 2] = x.z; x1[4 * i + 3] = x.w; }
          __syncwarp();
        } else swiglu(4 * b + q - 2, 32, -1);
      }, [&](int it) { if (it == 11) stage_done(sb, wg, 1, lane); }, [] {});
#pragma unroll
      for (int i = 0; i < 32; i++) pk[i] = pack2(acc[2 * i], acc[2 * i + 1]);
    }
    {
      float acc[64];
      mainloop<128, 6, 4, TAILLAG>(acc, 56, false, r6, sb, wg, lane, rel, [&](auto ic) { swiglu(ic.v - 1, 16, 1); },
                                   [&](int it) { if (it == 5) stage_done(sb, wg, 0, lane); }, [&] {
        if (TAILLAG && wg == 0 && lane == 0) mbar_arrive(bar + B_LAG);
        load_vec(pk + 32, sb, 5, 0, lane); load_vec(pk + 40, sb, 5, 1, lane);
        mbar_wait(fre, 0); mbar_wait(fre + 8, 1);
      });
      __syncwarp();
      cl_arrive_relaxed();
#pragma unroll
      for (int i = 0; i < 16; i += 2) {
        uint32_t w[4];
#pragma unroll
        for (int u = 0; u < 4; u++) {
          const int q = 2 * i + u;
          w[u] = pack2(fmaf(acc[2 * q], bf_lo(pk[32 + (q >> 1)]), bf_lo(x1[q])), fmaf(acc[2 * q + 1], bf_hi(pk[32 + (q >> 1)]), bf_hi(x1[q])));
        }
        stsm4(stg_row + (i >> 3) * BLK + ((((i & 7) + (lane >> 4)) ^ (lane & 7)) << 4), w[0], w[1], w[2], w[3]);
        if ((i & 7) == 6) {
          fence_async_smem();
          named_bar(2 + wg, 128);
          if (wq == 0 && elect()) { tma_store_3d(&maps.out, sb + STG + (i >> 3) * BLK + wg * HALF, j * 128 + (i >> 3) * 64, m * 64, wg); bulk_commit(); }
          if (i < 8) x1[16] |= __float_as_uint(lds32f(bar + ZERO));
        }
      }
      if (wq == 0) bulk_wait_read();
      if (tid == 0) gs->epoch[blockIdx.x] = ep;
      cl_wait();
    }
  }
}

typedef CUresult (*EncodeFn)(CUtensorMap*, CUtensorMapDataType, cuuint32_t, void*, const cuuint64_t*, const cuuint64_t*, const cuuint32_t*, const cuuint32_t*,
                             CUtensorMapInterleave, CUtensorMapSwizzle, CUtensorMapL2promotion, CUtensorMapFloatOOBfill);

void make_map(EncodeFn fn, CUtensorMap* mp, const void* base, uint64_t d0, uint64_t d1, uint64_t d2, uint64_t s1, uint64_t s2, uint32_t b2, uint32_t b0 = 64) {
  cuuint64_t d[3] = {d0, d1, d2}, s[2] = {s1, s2};
  cuuint32_t b[3] = {b0, 64, b2}, e[3] = {1, 1, 1};
  fn(mp, CU_TENSOR_MAP_DATA_TYPE_BFLOAT16, 3, (void*)base, d, s, b, e, CU_TENSOR_MAP_INTERLEAVE_NONE, b0 == 64 ? CU_TENSOR_MAP_SWIZZLE_128B : CU_TENSOR_MAP_SWIZZLE_NONE,
     CU_TENSOR_MAP_L2_PROMOTION_L2_128B, CU_TENSOR_MAP_FLOAT_OOB_FILL_NONE);
}

__global__ void probe_kernel() {}
int max_clusters(int size) {
  cudaLaunchConfig_t cfg = {};
  cudaLaunchAttribute at;
  at.id = cudaLaunchAttributeClusterDimension; at.val.clusterDim.x = size; at.val.clusterDim.y = 1; at.val.clusterDim.z = 1;
  cfg.gridDim = dim3(size * 66); cfg.blockDim = dim3(384); cfg.dynamicSmemBytes = SMEM_BYTES; cfg.attrs = &at; cfg.numAttrs = 1;
  int n = 0;
  if (cudaOccupancyMaxActiveClusters(&n, probe_kernel, &cfg) != cudaSuccess) { cudaGetLastError(); return 0; }
  return n;
}

}

extern "C" void kernel_launch(void* const* d_in, const int* in_sizes, int n_in, void* d_out, int out_size) {
  static EncodeFn fn = nullptr;
  static int by_sm = 0;
  static Scratch* gs = nullptr;
  if (!fn) {
    void* p = nullptr; cudaDriverEntryPointQueryResult q;
    cudaGetDriverEntryPoint("cuTensorMapEncodeTiled", &p, cudaEnableDefault, &q);
    fn = (EncodeFn)p;
    cudaFuncSetAttribute(fused_kernel, cudaFuncAttributeMaxDynamicSharedMemorySize, SMEM_BYTES);
    int dev = 0, sms = 0;
    cudaGetSymbolAddress((void**)&gs, g_scratch);
    cudaGetDevice(&dev);
    cudaDeviceGetAttribute(&sms, cudaDevAttrMultiProcessorCount, dev);
    cudaFuncSetAttribute(probe_kernel, cudaFuncAttributeMaxDynamicSharedMemorySize, SMEM_BYTES);
    by_sm = sms == 132 && max_clusters(2) == 66 && max_clusters(4) == 30 && max_clusters(6) == 17 && max_clusters(8) == 15;
  }
  Maps mp;
  make_map(fn, &mp.x, d_in[0], D_, S_ / 2, 2, 4096, 2048, 2);
  make_map(fn, &mp.out, d_out, D_, S_ / 2, 2, 4096, 2048, 1);
  make_map(fn, &mp.wqkv, d_in[1], 64, D_, 3 * D_ / 64, 3 * D_ * 2, 128, 2);
  make_map(fn, &mp.wo, d_in[2], 64, D_, D_ / 64, D_ * 2, 128, 2);
  make_map(fn, &mp.w1, d_in[4], 64, D_, F_ / 64, F_ * 2, 128, 2);
  make_map(fn, &mp.w3, d_in[5], 64, D_, F_ / 64, F_ * 2, 128, 2);
  make_map(fn, &mp.w1s, d_in[4], 64, D_, F_ / 64, F_ * 2, 128, 1);
  make_map(fn, &mp.w3s, d_in[5], 64, D_, F_ / 64, F_ * 2, 128, 1);
  make_map(fn, &mp.w2, d_in[6], 64, F_, D_ / 64, D_ * 2, 128, 2);
  make_map(fn, &mp.wmod, d_in[8], 256, D_, 24, 6 * D_ * 2, 512, 1, 256);
  fused_kernel<<<132, 384, SMEM_BYTES>>>((const bf16*)d_in[7], (const bf16*)d_in[8], gs, by_sm, mp);
}
```

```cpp
#include <cuda_runtime.h>
#include <cuda_bf16.h>
#include <cuda.h>
#include <stdint.h>

typedef __nv_bfloat16 bf16;

namespace {

constexpr int S_ = 2048, D_ = 1024, F_ = 3584;
constexpr int BLK = 16384;
constexpr int HALF = 8192;
constexpr int RING = 196608;
constexpr int STG = RING;
constexpr int MISC = RING + 2 * BLK;
constexpr int SMEM_BYTES = MISC + 3072;
constexpr int B_FULL4 = 0, B_EMPTY4 = 32, B_FULL6 = 64, B_EMPTY6 = 112, B_RDY = 160, B_FREE = 176, B_LAG = 192, B_X = 208, B_MOD = 224, B_HALO = 232, B_HH = 256, B_ALL = 272, B_HH2 = 288, ZERO = 296;
constexpr int MODV = 512;
constexpr int RED_OFF = 0;
constexpr float SCL = 0.17677669529663687f * 1.4426950408889634f;
constexpr int U_HH = 64;
constexpr int FS = 8;
constexpr int NPIECE = 4, PSLEEP = 300;
constexpr int XSLEEP = 4000, HSLEEP = 400;
constexpr uint32_t XDELAY = 2300, GAP = 250;
constexpr uint32_t B1P = 3700, B1D = 700;
constexpr int TAILLAG = 5;

struct Maps { CUtensorMap x, out, wqkv, wo, w1, w3, w1s, w3s, w2, wmod; };

struct Scratch {
  uint4 h[16 * 16 * 1024];
  uint4 o[16 * 16 * 1024];
  uint4 hh[16 * 56 * 1024];
  uint4 x1[128 * 8 * 256];
  uint2 stat[2 * 16 * 8 * 128];
  uint4 halo[16 * 8 * 2 * 512];
  uint32_t modp[8 * 2 * 4 * 128];
  uint2 modv[4 * 1024];
  uint32_t flag[16 * 128 * FS];
  uint32_t epoch[132];
};
__device__ __align__(1024) Scratch g_scratch;

__device__ __forceinline__ void bail() { asm volatile("st.global.u32 [%0], %1;" :: "l"(0ull), "r"(0) : "memory"); }
__device__ __forceinline__ uint32_t smem_u32(const void* p) { return (uint32_t)__cvta_generic_to_shared(p); }
__device__ __forceinline__ void mbar_init(uint32_t bar, uint32_t cnt) { asm volatile("mbarrier.init.shared::cta.b64 [%0], %1;" :: "r"(bar), "r"(cnt) : "memory"); }
__device__ __forceinline__ void mbar_expect_tx(uint32_t bar, uint32_t bytes) { asm volatile("mbarrier.arrive.expect_tx.shared::cta.b64 _, [%0], %1;" :: "r"(bar), "r"(bytes) : "memory"); }
__device__ __forceinline__ void mbar_arrive(uint32_t bar) { asm volatile("mbarrier.arrive.shared::cta.b64 _, [%0];" :: "r"(bar) : "memory"); }
__device__ __forceinline__ void mbar_arrive_cl(uint32_t cl_addr) { asm volatile("mbarrier.arrive.shared::cluster.b64 _, [%0];" :: "r"(cl_addr) : "memory"); }
__device__ __forceinline__ uint32_t mapa(uint32_t addr, uint32_t cta) { uint32_t r; asm("mapa.shared::cluster.u32 %0, %1, %2;" : "=r"(r) : "r"(addr), "r"(cta)); return r; }
__device__ __forceinline__ void mbar_wait(uint32_t bar, uint32_t parity) {
  asm volatile("{\n.reg .pred p;\n.reg .b32 n;\n.reg .b64 z;\nmov.b32 n, 0;\nmov.b64 z, 0;\n"
               "W: add.u32 n, n, 1;\nsetp.gt.u32 p, n, 0x400000;\n@p st.global.u32 [z], n;\n"
               "mbarrier.try_wait.parity.shared::cta.b64 p, [%0], %1;\n@!p bra W;\n}" :: "r"(bar), "r"(parity) : "memory");
}
__device__ __forceinline__ void tma_3d(uint32_t dst, const CUtensorMap* m, uint32_t bar, int c0, int c1, int c2) {
  asm volatile("cp.async.bulk.tensor.3d.shared::cluster.global.mbarrier::complete_tx::bytes [%0], [%1, {%3, %4, %5}], [%2];" :: "r"(dst), "l"(m), "r"(bar), "r"(c0), "r"(c1), "r"(c2) : "memory");
}
__device__ __forceinline__ void tma_store_3d(const CUtensorMap* m, uint32_t src, int c0, int c1, int c2) {
  asm volatile("cp.async.bulk.tensor.3d.global.shared::cta.bulk_group [%0, {%2, %3, %4}], [%1];" :: "l"(m), "r"(src), "r"(c0), "r"(c1), "r"(c2) : "memory");
}
__device__ __forceinline__ void bulk_ld(uint32_t dst, const void* src, uint32_t bytes, uint32_t bar) {
  asm volatile("cp.async.bulk.shared::cluster.global.mbarrier::complete_tx::bytes [%0], [%1], %2, [%3];" :: "r"(dst), "l"(src), "r"(bytes), "r"(bar) : "memory");
}
__device__ __forceinline__ void bulk_ld_mc(uint32_t dst, const void* src, uint32_t bytes, uint32_t bar) {
  asm volatile("cp.async.bulk.shared::cluster.global.mbarrier::complete_tx::bytes.multicast::cluster [%0], [%1], %2, [%3], %4;" :: "r"(dst), "l"(src), "r"(bytes), "r"(bar), "h"((uint16_t)3) : "memory");
}
__device__ __forceinline__ void bulk_push(uint32_t dst_cl, uint32_t src, uint32_t bytes, uint32_t bar_cl) {
  asm volatile("cp.async.bulk.shared::cluster.shared::cta.mbarrier::complete_tx::bytes [%0], [%1], %2, [%3];" :: "r"(dst_cl), "r"(src), "r"(bytes), "r"(bar_cl) : "memory");
}
__device__ __forceinline__ void bulk_st(void* dst, uint32_t src, uint32_t bytes) {
  asm volatile("cp.async.bulk.global.shared::cta.bulk_group [%0], [%1], %2;" :: "l"(dst), "r"(src), "r"(bytes) : "memory");
}
__device__ __forceinline__ void bulk_commit() { asm volatile("cp.async.bulk.commit_group;" ::: "memory"); }
__device__ __forceinline__ void bulk_wait_read() { asm volatile("cp.async.bulk.wait_group.read 0;" ::: "memory"); }
__device__ __forceinline__ void bulk_wait_all() { asm volatile("cp.async.bulk.wait_group 0;" ::: "memory"); }
__device__ __forceinline__ void fence_async_global() { asm volatile("fence.proxy.async.global;" ::: "memory"); }
__device__ __forceinline__ void fence_async_smem() { asm volatile("fence.proxy.async.shared::cta;" ::: "memory"); }
__device__ __forceinline__ void wg_arrive() { asm volatile("wgmma.fence.sync.aligned;" ::: "memory"); }
__device__ __forceinline__ void wg_commit() { asm volatile("wgmma.commit_group.sync.aligned;" ::: "memory"); }
template <int N> __device__ __forceinline__ void wg_wait() { asm volatile("wgmma.wait_group.sync.aligned %0;" :: "n"(N) : "memory"); }
__device__ __forceinline__ void cl_arrive_relaxed() { asm volatile("barrier.cluster.arrive.relaxed.aligned;" ::: "memory"); }
__device__ __forceinline__ void cl_wait() { asm volatile("barrier.cluster.wait.acquire.aligned;" ::: "memory"); }
__device__ __forceinline__ bool elect() { uint32_t p; asm volatile("{\n.reg .pred p;\nelect.sync _|p, 0xffffffff;\nselp.u32 %0, 1, 0, p;\n}" : "=r"(p)); return p; }
__device__ __forceinline__ void named_bar(int id, int n) { asm volatile("bar.sync %0, %1;" :: "r"(id), "r"(n) : "memory"); }
__device__ __forceinline__ uint32_t pack2(float lo, float hi) { uint32_t r; asm("cvt.rn.bf16x2.f32 %0, %1, %2;" : "=r"(r) : "f"(hi), "f"(lo)); return r; }
__device__ __forceinline__ float bf_lo(uint32_t w) { return __uint_as_float(w << 16); }
__device__ __forceinline__ float bf_hi(uint32_t w) { return __uint_as_float(w & 0xffff0000u); }
__device__ __forceinline__ float bf_round(float v) { return __bfloat162float(__float2bfloat16_rn(v)); }
__device__ __forceinline__ void stsm4(uint32_t addr, uint32_t a, uint32_t b, uint32_t c, uint32_t d) {
  asm volatile("stmatrix.sync.aligned.m8n8.x4.shared.b16 [%0], {%1, %2, %3, %4};" :: "r"(addr), "r"(a), "r"(b), "r"(c), "r"(d) : "memory");
}
__device__ __forceinline__ void ldsm4(uint32_t addr, uint32_t& a, uint32_t& b, uint32_t& c, uint32_t& d) {
  asm volatile("ldmatrix.sync.aligned.m8n8.x4.shared.b16 {%0, %1, %2, %3}, [%4];" : "=r"(a), "=r"(b), "=r"(c), "=r"(d) : "r"(addr) : "memory");
}
__device__ __forceinline__ uint32_t movm(uint32_t a) { uint32_t r; asm volatile("movmatrix.sync.aligned.m8n8.trans.b16 %0, %1;" : "=r"(r) : "r"(a)); return r; }
__device__ __forceinline__ void mma16(float (&d)[4], uint32_t a0, uint32_t a1, uint32_t a2, uint32_t a3, uint32_t b0, uint32_t b1) {
  asm("mma.sync.aligned.m16n8k16.row.col.f32.bf16.bf16.f32 {%0,%1,%2,%3}, {%4,%5,%6,%7}, {%8,%9}, {%0,%1,%2,%3};"
               : "+f"(d[0]), "+f"(d[1]), "+f"(d[2]), "+f"(d[3]) : "r"(a0), "r"(a1), "r"(a2), "r"(a3), "r"(b0), "r"(b1));
}
__device__ __forceinline__ void mma16z(float (&d)[4], uint32_t a0, uint32_t a1, uint32_t a2, uint32_t a3, uint32_t b0, uint32_t b1) {
  asm("mma.sync.aligned.m16n8k16.row.col.f32.bf16.bf16.f32 {%0,%1,%2,%3}, {%4,%5,%6,%7}, {%8,%9}, {%10,%10,%10,%10};"
      : "=f"(d[0]), "=f"(d[1]), "=f"(d[2]), "=f"(d[3]) : "r"(a0), "r"(a1), "r"(a2), "r"(a3), "r"(b0), "r"(b1), "f"(0.f));
}
__device__ __forceinline__ void mma8z(float (&d)[4], uint32_t a0, uint32_t a1, uint32_t b0) {
  asm("mma.sync.aligned.m16n8k8.row.col.f32.bf16.bf16.f32 {%0,%1,%2,%3}, {%4,%5}, {%6}, {%7,%7,%7,%7};"
      : "=f"(d[0]), "=f"(d[1]), "=f"(d[2]), "=f"(d[3]) : "r"(a0), "r"(a1), "r"(b0), "f"(0.f));
}
__device__ __forceinline__ void mma8(float (&d)[4], uint32_t a0, uint32_t a1, uint32_t b0) {
  asm("mma.sync.aligned.m16n8k8.row.col.f32.bf16.bf16.f32 {%0,%1,%2,%3}, {%4,%5}, {%6}, {%0,%1,%2,%3};"
               : "+f"(d[0]), "+f"(d[1]), "+f"(d[2]), "+f"(d[3]) : "r"(a0), "r"(a1), "r"(b0));
}
__device__ __forceinline__ uint4 lds128(uint32_t a) { uint4 v; asm volatile("ld.shared.v4.u32 {%0,%1,%2,%3}, [%4];" : "=r"(v.x), "=r"(v.y), "=r"(v.z), "=r"(v.w) : "r"(a) : "memory"); return v; }
__device__ __forceinline__ void sts128(uint32_t a, uint32_t x, uint32_t y, uint32_t z, uint32_t w) { asm volatile("st.shared.v4.u32 [%0], {%1,%2,%3,%4};" :: "r"(a), "r"(x), "r"(y), "r"(z), "r"(w) : "memory"); }
__device__ __forceinline__ float lds32f(uint32_t a) { float v; asm volatile("ld.shared.f32 %0, [%1];" : "=f"(v) : "r"(a) : "memory"); return v; }
__device__ __forceinline__ void sts16(uint32_t a, bf16 v) { asm volatile("st.shared.b16 [%0], %1;" :: "r"(a), "h"(__bfloat16_as_ushort(v)) : "memory"); }
__device__ __forceinline__ uint4 ldg_nc(const void* p) { uint4 v; asm volatile("ld.global.nc.L1::no_allocate.v4.u32 {%0,%1,%2,%3}, [%4];" : "=r"(v.x), "=r"(v.y), "=r"(v.z), "=r"(v.w) : "l"(p)); return v; }
__device__ __forceinline__ uint4 ld_rlx4(const uint4* p) {
  unsigned long long a, b; asm volatile("ld.relaxed.gpu.global.v2.b64 {%0,%1}, [%2];" : "=l"(a), "=l"(b) : "l"(p) : "memory");
  return make_uint4((uint32_t)a, (uint32_t)(a >> 32), (uint32_t)b, (uint32_t)(b >> 32));
}
__device__ __forceinline__ uint2 ld_rlx2(const uint2* p) { unsigned long long a; asm volatile("ld.relaxed.gpu.global.b64 %0, [%1];" : "=l"(a) : "l"(p) : "memory"); return make_uint2((uint32_t)a, (uint32_t)(a >> 32)); }
__device__ __forceinline__ void st_rlx4(uint4* p, uint32_t x, uint32_t y, uint32_t z, uint32_t w) {
  asm volatile("st.relaxed.gpu.global.v2.b64 [%0], {%1,%2};" :: "l"(p), "l"((unsigned long long)x | ((unsigned long long)y << 32)), "l"((unsigned long long)z | ((unsigned long long)w << 32)) : "memory");
}
__device__ __forceinline__ void st_rlx2(uint2* p, uint32_t x, uint32_t y) { asm volatile("st.relaxed.gpu.global.b64 [%0], %1;" :: "l"(p), "l"((unsigned long long)x | ((unsigned long long)y << 32)) : "memory"); }
__device__ __forceinline__ void st_rlx1(uint32_t* p, uint32_t v) { asm volatile("st.relaxed.gpu.global.u32 [%0], %1;" :: "l"(p), "r"(v) : "memory"); }
__device__ __forceinline__ uint32_t ld_rlx1(const uint32_t* p) { uint32_t v; asm volatile("ld.relaxed.gpu.global.u32 %0, [%1];" : "=r"(v) : "l"(p) : "memory"); return v; }
__device__ __forceinline__ void st_release(uint32_t* p, uint32_t v) { asm volatile("st.release.gpu.global.u32 [%0], %1;" :: "l"(p), "r"(v) : "memory"); }
__device__ __forceinline__ uint32_t ld_acquire(const uint32_t* p) { uint32_t v; asm volatile("ld.acquire.gpu.global.u32 %0, [%1];" : "=r"(v) : "l"(p) : "memory"); return v; }
__device__ __forceinline__ void prefetch_map(const CUtensorMap* m) { asm volatile("prefetch.tensormap [%0];" :: "l"(m) : "memory"); }
__device__ __forceinline__ float rcp(float x) { float r; asm("rcp.approx.ftz.f32 %0, %1;" : "=f"(r) : "f"(x)); return r; }
__device__ __forceinline__ float ex2(float x) { float r; asm("ex2.approx.ftz.f32 %0, %1;" : "=f"(r) : "f"(x)); return r; }
__device__ __forceinline__ float tanh_fast(float x) { float r; asm("tanh.approx.f32 %0, %1;" : "=f"(r) : "f"(x)); return r; }
#define SPIN_GUARD(n) if (++(n) > (1u << 24)) bail()

__device__ __forceinline__ void wgmma_n128(float (&d)[64], uint64_t da, uint64_t db) {
  asm volatile("wgmma.mma_async.sync.aligned.m64n128k16.f32.bf16.bf16 "
    "{%0, %1, %2, %3, %4, %5, %6, %7, %8, %9, %10, %11, %12, %13, %14, %15, %16, %17, %18, %19, %20, %21, %22, %23, %24, %25, %26, %27, %28, %29, %30, %31, %32, %33, %34, %35, %36, %37, %38, %39, %40, %41, %42, %43, %44, %45, %46, %47, %48, %49, %50, %51, %52, %53, %54, %55, %56, %57, %58, %59, %60, %61, %62, %63}, "
    "%64, %65, 1, 1, 1, 0, 1;\n"
    : "+f"(d[0]), "+f"(d[1]), "+f"(d[2]), "+f"(d[3]), "+f"(d[4]), "+f"(d[5]), "+f"(d[6]), "+f"(d[7]), "+f"(d[8]), "+f"(d[9]), "+f"(d[10]), "+f"(d[11]), "+f"(d[12]), "+f"(d[13]), "+f"(d[14]), "+f"(d[15]), "+f"(d[16]), "+f"(d[17]), "+f"(d[18]), "+f"(d[19]), "+f"(d[20]), "+f"(d[21]), "+f"(d[22]), "+f"(d[23]), "+f"(d[24]), "+f"(d[25]), "+f"(d[26]), "+f"(d[27]), "+f"(d[28]), "+f"(d[29]), "+f"(d[30]), "+f"(d[31]), "+f"(d[32]), "+f"(d[33]), "+f"(d[34]), "+f"(d[35]), "+f"(d[36]), "+f"(d[37]), "+f"(d[38]), "+f"(d[39]), "+f"(d[40]), "+f"(d[41]), "+f"(d[42]), "+f"(d[43]), "+f"(d[44]), "+f"(d[45]), "+f"(d[46]), "+f"(d[47]), "+f"(d[48]), "+f"(d[49]), "+f"(d[50]), "+f"(d[51]), "+f"(d[52]), "+f"(d[53]), "+f"(d[54]), "+f"(d[55]), "+f"(d[56]), "+f"(d[57]), "+f"(d[58]), "+f"(d[59]), "+f"(d[60]), "+f"(d[61]), "+f"(d[62]), "+f"(d[63])
    : "l"(da), "l"(db));
}
__device__ __forceinline__ void wgmma_n128_first(float (&d)[64], uint64_t da, uint64_t db) {
  asm volatile("wgmma.mma_async.sync.aligned.m64n128k16.f32.bf16.bf16 "
    "{%0, %1, %2, %3, %4, %5, %6, %7, %8, %9, %10, %11, %12, %13, %14, %15, %16, %17, %18, %19, %20, %21, %22, %23, %24, %25, %26, %27, %28, %29, %30, %31, %32, %33, %34, %35, %36, %37, %38, %39, %40, %41, %42, %43, %44, %45, %46, %47, %48, %49, %50, %51, %52, %53, %54, %55, %56, %57, %58, %59, %60, %61, %62, %63}, "
    "%64, %65, 0, 1, 1, 0, 1;\n"
    : "=f"(d[0]), "=f"(d[1]), "=f"(d[2]), "=f"(d[3]), "=f"(d[4]), "=f"(d[5]), "=f"(d[6]), "=f"(d[7]), "=f"(d[8]), "=f"(d[9]), "=f"(d[10]), "=f"(d[11]), "=f"(d[12]), "=f"(d[13]), "=f"(d[14]), "=f"(d[15]), "=f"(d[16]), "=f"(d[17]), "=f"(d[18]), "=f"(d[19]), "=f"(d[20]), "=f"(d[21]), "=f"(d[22]), "=f"(d[23]), "=f"(d[24]), "=f"(d[25]), "=f"(d[26]), "=f"(d[27]), "=f"(d[28]), "=f"(d[29]), "=f"(d[30]), "=f"(d[31]), "=f"(d[32]), "=f"(d[33]), "=f"(d[34]), "=f"(d[35]), "=f"(d[36]), "=f"(d[37]), "=f"(d[38]), "=f"(d[39]), "=f"(d[40]), "=f"(d[41]), "=f"(d[42]), "=f"(d[43]), "=f"(d[44]), "=f"(d[45]), "=f"(d[46]), "=f"(d[47]), "=f"(d[48]), "=f"(d[49]), "=f"(d[50]), "=f"(d[51]), "=f"(d[52]), "=f"(d[53]), "=f"(d[54]), "=f"(d[55]), "=f"(d[56]), "=f"(d[57]), "=f"(d[58]), "=f"(d[59]), "=f"(d[60]), "=f"(d[61]), "=f"(d[62]), "=f"(d[63])
    : "l"(da), "l"(db));
}
__device__ __forceinline__ void wgmma_n256(float (&d)[128], uint64_t da, uint64_t db) {
  asm volatile("wgmma.mma_async.sync.aligned.m64n256k16.f32.bf16.bf16 "
    "{%0, %1, %2, %3, %4, %5, %6, %7, %8, %9, %10, %11, %12, %13, %14, %15, %16, %17, %18, %19, %20, %21, %22, %23, %24, %25, %26, %27, %28, %29, %30, %31, %32, %33, %34, %35, %36, %37, %38, %39, %40, %41, %42, %43, %44, %45, %46, %47, %48, %49, %50, %51, %52, %53, %54, %55, %56, %57, %58, %59, %60, %61, %62, %63, %64, %65, %66, %67, %68, %69, %70, %71, %72, %73, %74, %75, %76, %77, %78, %79, %80, %81, %82, %83, %84, %85, %86, %87, %88, %89, %90, %91, %92, %93, %94, %95, %96, %97, %98, %99, %100, %101, %102, %103, %104, %105, %106, %107, %108, %109, %110, %111, %112, %113, %114, %115, %116, %117, %118, %119, %120, %121, %122, %123, %124, %125, %126, %127}, "
    "%128, %129, 1, 1, 1, 0, 1;\n"
    : "+f"(d[0]), "+f"(d[1]), "+f"(d[2]), "+f"(d[3]), "+f"(d[4]), "+f"(d[5]), "+f"(d[6]), "+f"(d[7]), "+f"(d[8]), "+f"(d[9]), "+f"(d[10]), "+f"(d[11]), "+f"(d[12]), "+f"(d[13]), "+f"(d[14]), "+f"(d[15]), "+f"(d[16]), "+f"(d[17]), "+f"(d[18]), "+f"(d[19]), "+f"(d[20]), "+f"(d[21]), "+f"(d[22]), "+f"(d[23]), "+f"(d[24]), "+f"(d[25]), "+f"(d[26]), "+f"(d[27]), "+f"(d[28]), "+f"(d[29]), "+f"(d[30]), "+f"(d[31]), "+f"(d[32]), "+f"(d[33]), "+f"(d[34]), "+f"(d[35]), "+f"(d[36]), "+f"(d[37]), "+f"(d[38]), "+f"(d[39]), "+f"(d[40]), "+f"(d[41]), "+f"(d[42]), "+f"(d[43]), "+f"(d[44]), "+f"(d[45]), "+f"(d[46]), "+f"(d[47]), "+f"(d[48]), "+f"(d[49]), "+f"(d[50]), "+f"(d[51]), "+f"(d[52]), "+f"(d[53]), "+f"(d[54]), "+f"(d[55]), "+f"(d[56]), "+f"(d[57]), "+f"(d[58]), "+f"(d[59]), "+f"(d[60]), "+f"(d[61]), "+f"(d[62]), "+f"(d[63]), "+f"(d[64]), "+f"(d[65]), "+f"(d[66]), "+f"(d[67]), "+f"(d[68]), "+f"(d[69]), "+f"(d[70]), "+f"(d[71]), "+f"(d[72]), "+f"(d[73]), "+f"(d[74]), "+f"(d[75]), "+f"(d[76]), "+f"(d[77]), "+f"(d[78]), "+f"(d[79]), "+f"(d[80]), "+f"(d[81]), "+f"(d[82]), "+f"(d[83]), "+f"(d[84]), "+f"(d[85]), "+f"(d[86]), "+f"(d[87]), "+f"(d[88]), "+f"(d[89]), "+f"(d[90]), "+f"(d[91]), "+f"(d[92]), "+f"(d[93]), "+f"(d[94]), "+f"(d[95]), "+f"(d[96]), "+f"(d[97]), "+f"(d[98]), "+f"(d[99]), "+f"(d[100]), "+f"(d[101]), "+f"(d[102]), "+f"(d[103]), "+f"(d[104]), "+f"(d[105]), "+f"(d[106]), "+f"(d[107]), "+f"(d[108]), "+f"(d[109]), "+f"(d[110]), "+f"(d[111]), "+f"(d[112]), "+f"(d[113]), "+f"(d[114]), "+f"(d[115]), "+f"(d[116]), "+f"(d[117]), "+f"(d[118]), "+f"(d[119]), "+f"(d[120]), "+f"(d[121]), "+f"(d[122]), "+f"(d[123]), "+f"(d[124]), "+f"(d[125]), "+f"(d[126]), "+f"(d[127])
    : "l"(da), "l"(db));
}
__device__ __forceinline__ void wgmma_n256_first(float (&d)[128], uint64_t da, uint64_t db) {
  asm volatile("wgmma.mma_async.sync.aligned.m64n256k16.f32.bf16.bf16 "
    "{%0, %1, %2, %3, %4, %5, %6, %7, %8, %9, %10, %11, %12, %13, %14, %15, %16, %17, %18, %19, %20, %21, %22, %23, %24, %25, %26, %27, %28, %29, %30, %31, %32, %33, %34, %35, %36, %37, %38, %39, %40, %41, %42, %43, %44, %45, %46, %47, %48, %49, %50, %51, %52, %53, %54, %55, %56, %57, %58, %59, %60, %61, %62, %63, %64, %65, %66, %67, %68, %69, %70, %71, %72, %73, %74, %75, %76, %77, %78, %79, %80, %81, %82, %83, %84, %85, %86, %87, %88, %89, %90, %91, %92, %93, %94, %95, %96, %97, %98, %99, %100, %101, %102, %103, %104, %105, %106, %107, %108, %109, %110, %111, %112, %113, %114, %115, %116, %117, %118, %119, %120, %121, %122, %123, %124, %125, %126, %127}, "
    "%128, %129, 0, 1, 1, 0, 1;\n"
    : "=f"(d[0]), "=f"(d[1]), "=f"(d[2]), "=f"(d[3]), "=f"(d[4]), "=f"(d[5]), "=f"(d[6]), "=f"(d[7]), "=f"(d[8]), "=f"(d[9]), "=f"(d[10]), "=f"(d[11]), "=f"(d[12]), "=f"(d[13]), "=f"(d[14]), "=f"(d[15]), "=f"(d[16]), "=f"(d[17]), "=f"(d[18]), "=f"(d[19]), "=f"(d[20]), "=f"(d[21]), "=f"(d[22]), "=f"(d[23]), "=f"(d[24]), "=f"(d[25]), "=f"(d[26]), "=f"(d[27]), "=f"(d[28]), "=f"(d[29]), "=f"(d[30]), "=f"(d[31]), "=f"(d[32]), "=f"(d[33]), "=f"(d[34]), "=f"(d[35]), "=f"(d[36]), "=f"(d[37]), "=f"(d[38]), "=f"(d[39]), "=f"(d[40]), "=f"(d[41]), "=f"(d[42]), "=f"(d[43]), "=f"(d[44]), "=f"(d[45]), "=f"(d[46]), "=f"(d[47]), "=f"(d[48]), "=f"(d[49]), "=f"(d[50]), "=f"(d[51]), "=f"(d[52]), "=f"(d[53]), "=f"(d[54]), "=f"(d[55]), "=f"(d[56]), "=f"(d[57]), "=f"(d[58]), "=f"(d[59]), "=f"(d[60]), "=f"(d[61]), "=f"(d[62]), "=f"(d[63]), "=f"(d[64]), "=f"(d[65]), "=f"(d[66]), "=f"(d[67]), "=f"(d[68]), "=f"(d[69]), "=f"(d[70]), "=f"(d[71]), "=f"(d[72]), "=f"(d[73]), "=f"(d[74]), "=f"(d[75]), "=f"(d[76]), "=f"(d[77]), "=f"(d[78]), "=f"(d[79]), "=f"(d[80]), "=f"(d[81]), "=f"(d[82]), "=f"(d[83]), "=f"(d[84]), "=f"(d[85]), "=f"(d[86]), "=f"(d[87]), "=f"(d[88]), "=f"(d[89]), "=f"(d[90]), "=f"(d[91]), "=f"(d[92]), "=f"(d[93]), "=f"(d[94]), "=f"(d[95]), "=f"(d[96]), "=f"(d[97]), "=f"(d[98]), "=f"(d[99]), "=f"(d[100]), "=f"(d[101]), "=f"(d[102]), "=f"(d[103]), "=f"(d[104]), "=f"(d[105]), "=f"(d[106]), "=f"(d[107]), "=f"(d[108]), "=f"(d[109]), "=f"(d[110]), "=f"(d[111]), "=f"(d[112]), "=f"(d[113]), "=f"(d[114]), "=f"(d[115]), "=f"(d[116]), "=f"(d[117]), "=f"(d[118]), "=f"(d[119]), "=f"(d[120]), "=f"(d[121]), "=f"(d[122]), "=f"(d[123]), "=f"(d[124]), "=f"(d[125]), "=f"(d[126]), "=f"(d[127])
    : "l"(da), "l"(db));
}

template <int N> struct WG;
#define DEF_WG(N) template <> struct WG<N> { \
  static __device__ __forceinline__ void mma(float (&d)[N / 2], uint64_t a, uint64_t b) { wgmma_n##N(d, a, b); } \
  static __device__ __forceinline__ void first(float (&d)[N / 2], uint64_t a, uint64_t b) { wgmma_n##N##_first(d, a, b); } };
DEF_WG(128) DEF_WG(256)

constexpr uint64_t DESC_A = (1ull << 62) | ((uint64_t)(1024 >> 4) << 32) | (1ull << 16);
constexpr uint64_t DESC_B = (1ull << 62) | ((uint64_t)(1024 >> 4) << 32) | ((uint64_t)(8192 >> 4) << 16);

struct Ring { int s; uint32_t ph; int wrap; };
template <int NS> __device__ __forceinline__ void ring_next(Ring& r) { r.s = (r.s + 1 == NS) ? 0 : r.s + 1; if (r.s == r.wrap) r.ph ^= 1; }

__device__ __forceinline__ int own_order(int it, int j) {
  return it < 2 ? 2 * j + it : it < 4 ? 2 * (j ^ 1) + it - 2 : ((j >> 1) * 4 + 2 * it - (it < 10 ? 4 : 15)) & 15;
}

template <int V> struct IC { static constexpr int v = V; };
template <int I, int E, class F> __device__ __forceinline__ void static_for(F&& f) { if constexpr (I < E) { f(IC<I>{}); static_for<I + 1, E>(f); } }

template <int N, int NS, int PRE, int LAG, class Pre, class Mid, class Last>
__device__ __forceinline__ void mainloop(float (&acc)[N / 2], int nkb, bool own, Ring& r, uint32_t sb, int wg, int lane, uint32_t rel_base, Pre pre, Mid mid, Last last, int lag_par = 0) {
  constexpr int SLOT = RING / NS;
  const uint32_t full = sb + MISC + (NS == 4 ? B_FULL4 : B_FULL6);
  const uint32_t rel = rel_base + (NS == 4 ? B_EMPTY4 : B_EMPTY6);
  const uint32_t s0 = (sb & 0x3FFFF) >> 4, a0 = s0 + wg * (HALF >> 4);
  int ps;
  auto issue = [&](int it, bool first) {
    const uint64_t da = DESC_A | (a0 + ((own && it < 2) ? (STG + it * BLK) >> 4 : r.s * (SLOT >> 4))), db = DESC_B | (s0 + r.s * (SLOT >> 4) + (BLK >> 4));
    mbar_wait(full + r.s * 8, r.ph);
    wg_arrive();
    if (first) WG<N>::first(acc, da, db); else WG<N>::mma(acc, da, db);
#pragma unroll
    for (int k = 1; k < 4; k++) WG<N>::mma(acc, da + k * 2, db + k * 128);
    wg_commit();
  };
  auto retire = [&](int it) {
    wg_wait<1>();
    if (lane < 2) mbar_arrive_cl(rel + ps * 8);
    ps = r.s;
    ring_next<NS>(r);
  };
  issue(0, true);
  ps = r.s;
  ring_next<NS>(r);
  static_for<1, PRE + 1>([&](auto ic) { issue(ic.v, false); pre(ic); retire(ic.v); });
#pragma unroll 1
  for (int it = PRE + 1; it < nkb; it++) {
    if (LAG && it == nkb - LAG && wg == 1) mbar_wait(sb + MISC + B_LAG, lag_par);
    issue(it, false); mid(it); retire(it);
  }
  if (LAG && wg == 0 && lane == 0) mbar_arrive(sb + MISC + B_LAG);
  last();
  wg_wait<0>();
  if (lane < 2) mbar_arrive_cl(rel + ps * 8);
}

__device__ __forceinline__ uint32_t tag_of(uint32_t ep) { return (ep & 127u) + 1u; }
__device__ __forceinline__ void ln_publish(const float (&v)[64], uint2* st, int j, int row0, int lane, uint32_t ep) {
  float s0 = 0, s1 = 0, s2 = 0, s3 = 0, q0 = 0, q1 = 0, q2 = 0, q3 = 0;
#pragma unroll
  for (int i = 0; i < 16; i++) {
    s0 += v[4 * i]; s1 += v[4 * i + 1]; s2 += v[4 * i + 2]; s3 += v[4 * i + 3];
    q0 = fmaf(v[4 * i], v[4 * i], q0); q1 = fmaf(v[4 * i + 1], v[4 * i + 1], q1); q2 = fmaf(v[4 * i + 2], v[4 * i + 2], q2); q3 = fmaf(v[4 * i + 3], v[4 * i + 3], q3);
  }
  s0 += s1; s2 += s3; q0 += q1; q2 += q3;
  const bool odd = lane & 1;
  float s = (odd ? s2 : s0) + __shfl_xor_sync(~0u, odd ? s0 : s2, 1), q = (odd ? q2 : q0) + __shfl_xor_sync(~0u, odd ? q0 : q2, 1);
  s += __shfl_xor_sync(~0u, s, 2); q += __shfl_xor_sync(~0u, q, 2);
  if ((lane & 3) < 2) st_rlx2(st + j * 128 + row0 + (lane & 1) * 8, __float_as_uint(s), (__float_as_uint(fmaf(s * (-1.f / 128), s, q)) & ~255u) | tag_of(ep));
}
__device__ __forceinline__ void ln_gather(const uint2* st, int row0, int lane, uint32_t ep, float& n0, float& r0, float& n1, float& r1, bool rnd) {
  const uint2* p = st + (lane & 2) * 256 + row0 + (lane & 1) * 8;
  const uint32_t tag = tag_of(ep);
  uint2 a, b, c, d; uint32_t n = 0;
  while (true) {
    a = ld_rlx2(p); b = ld_rlx2(p + 128); c = ld_rlx2(p + 256); d = ld_rlx2(p + 384);
    if ((((a.y ^ tag) | (b.y ^ tag) | (c.y ^ tag) | (d.y ^ tag)) & 255u) == 0) break;
    SPIN_GUARD(n);
  }
  __syncwarp();
  const uint32_t fix = tag ^ 128u;
  float s = (__uint_as_float(a.x) + __uint_as_float(b.x)) + (__uint_as_float(c.x) + __uint_as_float(d.x));
  float q = (__uint_as_float(a.y ^ fix) + __uint_as_float(b.y ^ fix)) + (__uint_as_float(c.y ^ fix) + __uint_as_float(d.y ^ fix));
  q = fmaf(fmaf(__uint_as_float(a.x), __uint_as_float(a.x), __uint_as_float(b.x) * __uint_as_float(b.x)) +
           fmaf(__uint_as_float(c.x), __uint_as_float(c.x), __uint_as_float(d.x) * __uint_as_float(d.x)), 1.f / 128, q);
  s += __shfl_xor_sync(~0u, s, 2); q += __shfl_xor_sync(~0u, q, 2);
  s *= 1.f / 1024;
  const float var = fmaxf(fmaf(-s, s, q * (1.f / 1024)), 0.f);
  float r;
  if (rnd) {
    float sd; asm("sqrt.approx.f32 %0, %1;" : "=f"(sd) : "f"(bf_round(bf_round(var) + 1e-5f)));
    r = rcp(bf_round(sd)); s = bf_round(s);
  } else r = rsqrtf(var + 1e-5f);
  const float nn = -s * r;
  const float ro = __shfl_xor_sync(~0u, r, 1), no = __shfl_xor_sync(~0u, nn, 1);
  const bool odd = lane & 1;
  r0 = odd ? ro : r; n0 = odd ? no : nn; r1 = odd ? r : ro; n1 = odd ? nn : no;
}
__device__ __forceinline__ void load_vec(uint32_t* w, uint32_t sb, int sec, int b, int lane) {
#pragma unroll
  for (int q = 0; q < 2; q++) { uint4 t = lds128(sb + MISC + MODV + sec * 256 + (lane & 3) * 64 + b * 32 + q * 16); w[4 * q] = t.x; w[4 * q + 1] = t.y; w[4 * q + 2] = t.z; w[4 * q + 3] = t.w; }
}
__device__ __forceinline__ void stage_done(uint32_t sb, int wg, int b, int lane) {
  fence_async_smem();
  __syncwarp();
  if (lane == 0) mbar_arrive(sb + MISC + B_RDY + b * 8);
}
__device__ __forceinline__ uint32_t hfma2(uint32_t a, uint32_t b, uint32_t c) { uint32_t r; asm("fma.rn.bf16x2 %0, %1, %2, %3;" : "=r"(r) : "r"(a), "r"(b), "r"(c)); return r; }
__device__ __forceinline__ void ln_apply(const float (&v)[64], const uint2* st, int row0, uint32_t ep, uint32_t sb, int sec_shift, int sec_scale, uint32_t stg_row, int wg, int lane) {
  uint32_t sc[16], sh[16];
#pragma unroll
  for (int b = 0; b < 2; b++) { load_vec(sc + 8 * b, sb, sec_scale, b, lane); load_vec(sh + 8 * b, sb, sec_shift, b, lane); }
  float n0, r0, n1, r1;
  ln_gather(st, row0, lane, ep, n0, r0, n1, r1, sec_shift == 0);
#pragma unroll
  for (int i = 0; i < 16; i += 2) {
    if (i == 8) { const float z = lds32f(sb + MISC + ZERO); n0 += z; n1 += z; }
    uint32_t w[4];
#pragma unroll
    for (int u = 0; u < 2; u++) {
      int q = i + u;
      w[2 * u] = hfma2(pack2(fmaf(v[4 * q], r0, n0), fmaf(v[4 * q + 1], r0, n0)), sc[q], sh[q]);
      w[2 * u + 1] = hfma2(pack2(fmaf(v[4 * q + 2], r1, n1), fmaf(v[4 * q + 3], r1, n1)), sc[q], sh[q]);
    }
    stsm4(stg_row + (i >> 3) * BLK + ((((i & 7) + (lane >> 4)) ^ (lane & 7)) << 4), w[0], w[1], w[2], w[3]);
    if ((i & 7) == 6) { stage_done(sb, wg, i >> 3, lane); }
  }
}
__device__ __forceinline__ uint32_t hmul2(uint32_t a, uint32_t b) { uint32_t r; asm("mul.rn.bf16x2 %0, %1, %2;" : "=r"(r) : "r"(a), "r"(b)); return r; }
__device__ __forceinline__ uint32_t silu_mul2(uint32_t g, uint32_t u) {
  const uint32_t h = hmul2(g, 0x3f003f00u);
  const float h0 = bf_lo(h), h1 = bf_hi(h);
  return hmul2(pack2(fmaf(h0, tanh_fast(h0), h0), fmaf(h1, tanh_fast(h1), h1)), u);
}

__device__ __forceinline__ void gemv_fma(float (&a)[8], uint4 w, float s) {
  a[0] = fmaf(bf_lo(w.x), s, a[0]); a[1] = fmaf(bf_hi(w.x), s, a[1]); a[2] = fmaf(bf_lo(w.y), s, a[2]); a[3] = fmaf(bf_hi(w.y), s, a[3]);
  a[4] = fmaf(bf_lo(w.z), s, a[4]); a[5] = fmaf(bf_hi(w.z), s, a[5]); a[6] = fmaf(bf_lo(w.w), s, a[6]); a[7] = fmaf(bf_hi(w.w), s, a[7]);
}
__device__ __forceinline__ float silu_c(float v) { return bf_round(__fdividef(v, 1.f + __expf(-v))); }
__device__ __forceinline__ float mod_gather(const uint32_t* p, uint32_t ep) {
  const uint32_t tag = tag_of(ep), fix = tag ^ 128u;
  uint32_t a, b, c, d, n = 0;
  while (true) {
    a = ld_rlx1(p); b = ld_rlx1(p + 128); c = ld_rlx1(p + 256); d = ld_rlx1(p + 384);
    if ((((a ^ tag) | (b ^ tag) | (c ^ tag) | (d ^ tag)) & 255u) == 0) break;
    SPIN_GUARD(n);
  }
  return (__uint_as_float(a ^ fix) + __uint_as_float(b ^ fix)) + (__uint_as_float(c ^ fix) + __uint_as_float(d ^ fix));
}
__device__ __forceinline__ void mod_store(uint32_t sb, int sec, int col, float v) {
  v = bf_round(v);
  if (sec == 1) v += 1.f;
  sts16(sb + MISC + MODV + sec * 256 + (((col >> 1) & 3) * 16 + (col >> 3)) * 4 + (col & 1) * 2, __float2bfloat16_rn(v));
}

__global__ void __cluster_dims__(2, 1, 1) __launch_bounds__(384, 1)
fused_kernel(const bf16* __restrict__ cvec, const bf16* __restrict__ wmod, Scratch* gs, int by_sm, const __grid_constant__ Maps maps) {
  extern __shared__ __align__(1024) uint8_t smem_raw[];
  const uint32_t sb = smem_u32(smem_raw);
  const int warp = __shfl_sync(~0u, threadIdx.x >> 5, 0), lane = threadIdx.x & 31;
  const int rank = blockIdx.x & 1;
  uint32_t sm; asm volatile("mov.u32 %0, %%smid;" : "=r"(sm));
  const int t = sm >> 1, v = t < 32 ? t : t < 60 ? t + 1 + (((t - 32) * 37) >> 8) : (t - 58) * 8;
  const int gr = 0x71546320u >> ((v & 7) * 4);
  const int cid = !by_sm ? (blockIdx.x >> 1) - 2 : (t & ~1) == 60 ? t - 62 : (gr & 4) * 8 + (v >> 3) * 4 + (gr & 3);
  const bool extra = cid < 0;
  const int bid = cid * 2 + rank;
  const int m = cid >> 2, j = (cid & 3) * 2 + rank;
  const uint32_t bar = sb + MISC;

  if (warp >= 8) {
    asm volatile("setmaxnreg.dec.sync.aligned.u32 40;");
    if (extra) {
      if (warp == 8) {
        if (lane == 0) { for (int s = 0; s < 6; s++) { mbar_init(bar + B_FULL6 + s * 8, 1); mbar_init(bar + B_EMPTY6 + s * 8, 8); } fence_async_smem(); }
        __syncwarp();
        asm volatile("bar.arrive 2, 288;" ::: "memory");
        __nanosleep(XSLEEP);
#pragma unroll 1
        for (int it = 0, s = 0, par = 1; it < 64; it++) {
          mbar_wait(bar + B_EMPTY6 + s * 8, par);
          if (elect()) { mbar_expect_tx(bar + B_FULL6 + s * 8, 32768); tma_3d(sb + s * 32768, &maps.wmod, bar + B_FULL6 + s * 8, 0, (it & 15) * 64, 12 + (it >> 4) * 4 + bid); }
          if (++s == 6) { s = 0; par ^= 1; }
        }
      }
    } else if (warp < 10) {
      uint32_t s6 = 0, p6 = 1;
      auto next6 = [&]() { if (++s6 == 6) { s6 = 0; p6 ^= 1; } };
      auto drained4 = [&](int q, int late) { if (q < 5) mbar_wait(bar + B_EMPTY4 + (((late ? 0x10332 : 0x32110) >> (4 * q)) & 3) * 8, 1); };
      auto drained6 = [&](int q) { if (q < 3) mbar_wait(bar + B_EMPTY6 + ((0x154 >> (4 * q)) & 7) * 8, q >> 1); };
      auto skip6 = [&]() { mbar_wait(bar + B_EMPTY6 + s6 * 8, p6); if (elect()) mbar_arrive(bar + B_FULL6 + s6 * 8); next6(); };
      if (warp == 8) {
        const uint32_t t_start = clock();
        if (lane == 0) {
          if (sb & 1023) bail();
          for (int b = 0; b < 2; b++) mbar_init(bar + B_X + b * 8, 1);
          for (int s = 0; s < 4; s++) { mbar_init(bar + B_FULL4 + s * 8, 2); mbar_init(bar + B_EMPTY4 + s * 8, 16); }
          for (int s = 0; s < 6; s++) { mbar_init(bar + B_FULL6 + s * 8, 2); mbar_init(bar + B_EMPTY6 + s * 8, 16); }
          for (int b = 0; b < 2; b++) { mbar_init(bar + B_RDY + b * 8, 8); mbar_init(bar + B_FREE + b * 8, 1); mbar_init(bar + B_HH + b * 8, 1); }
          mbar_init(bar + B_MOD, 1); mbar_init(bar + B_LAG, 4); mbar_init(bar + B_HALO, 2); mbar_init(bar + B_ALL, 1); mbar_init(bar + B_HH2, 1);
          asm volatile("st.shared.u32 [%0], 0;" :: "r"(bar + ZERO) : "memory");
          asm volatile("fence.mbarrier_init.release.cluster;" ::: "memory");
          fence_async_smem();
        }
        __syncwarp();
        cl_arrive_relaxed();
        auto wide = [&](int s, int par, const CUtensorMap* m0, int a0, const CUtensorMap* m1, int a1, int kb, bool spaced) {
          const uint32_t full = bar + B_FULL4 + s * 8, d = sb + s * 49152 + BLK;
          mbar_wait(full + 32, par);
          const uint32_t t0 = clock();
          if (elect()) { mbar_expect_tx(full, 2 * BLK); tma_3d(d, m0, full, 0, kb * 64, a0); }
          if (spaced) while ((uint32_t)clock() - t0 < GAP) {}
          if (elect()) tma_3d(d + BLK, m1, full, 0, kb * 64, a1);
          if (spaced) while ((uint32_t)clock() - t0 < 2 * GAP) {}
        };
        while ((uint32_t)clock() - t_start < XDELAY) {}
        if (elect()) for (int b = 0; b < 2; b++) { mbar_expect_tx(bar + B_X + b * 8, BLK); tma_3d(sb + STG + b * BLK, &maps.x, bar + B_X + b * 8, j * 128 + b * 64, m * 64, 0); }
        mbar_wait(bar + B_X + 8, 0);
#pragma unroll 1
        for (int ph = 0; ph < 2; ph++) {
          const CUtensorMap* const m0 = ph ? &maps.w1 : &maps.wqkv;
#pragma unroll 1
          for (int it = 0; it < (ph ? 48 : 16); it++) {
            const int a = (ph ? it & 48 : 16) + 2 * j;
            if (ph) drained6(it);
            wide((it + 2 * ph) & 3, ~(it >> 2) & 1, m0, a, m0 + ph, ph ? a : a + 16, it < 16 ? own_order(it, j) : it & 15, it < 4);
            if (it >= 44) {
              if (it == 44) { mbar_wait(bar + B_FREE, 0); mbar_wait(bar + B_FREE + 8, 0); if (elect()) mbar_expect_tx(bar + B_X, 2 * BLK); }
              if (elect()) bulk_ld(sb + STG + (it - 44) * HALF, gs->x1 + bid * 2048 + (it - 44) * 512, HALF, bar + B_X);
            }
          }
#pragma unroll 1
          for (int it = 0; it < 16; it++) {
            const uint32_t full = bar + B_FULL6 + s6 * 8, d = sb + s6 * 32768 + BLK;
            drained4(it, ph);
            mbar_wait(full + 48, p6);
            if (elect()) {
              mbar_expect_tx(full, BLK);
              tma_3d(d, ph ? &maps.w1s : &maps.wqkv, full, 0, it * 64, ph ? 48 + j : 2 * j);
              if (ph) tma_3d(d + HALF, &maps.w3s, full, 0, it * 64, 48 + j);
            }
            next6();
          }
          const CUtensorMap* const m2 = ph ? &maps.w2 : &maps.wo;
#pragma unroll 1
          for (int it = 0; it < (ph ? 56 : 16); it++) {
            const uint32_t full = bar + B_FULL6 + s6 * 8;
            const int kb = ph ? it : own_order(it, j);
            mbar_wait(full + 48, p6);
            if (elect()) { mbar_expect_tx(full, BLK); tma_3d(sb + s6 * 32768 + BLK, m2, full, 0, kb * 64, 2 * j); }
            next6();
          }
          if (!ph) skip6();
        }
      } else {
        if (lane < 9) prefetch_map(&maps.x + lane);
        const uint32_t ep = gs->epoch[blockIdx.x] + 1;
        cl_arrive_relaxed(); cl_wait();
        auto plain = [&](uint32_t full, uint32_t empty, int par, uint32_t slot, const uint4* blk) {
          mbar_wait(empty, par);
          if (elect()) { mbar_expect_tx(full, BLK); bulk_ld_mc(slot + rank * HALF, blk + rank * 512, HALF, full); }
        };
        auto plain6 = [&](const uint4* blk) { plain(bar + B_FULL6 + s6 * 8, bar + B_EMPTY6 + s6 * 8, p6, sb + s6 * 32768, blk); next6(); };
        uint32_t ready = 0;
        auto poll = [&](int e) { ready = __ballot_sync(~0u, ld_acquire(gs->flag + (m * 128 + e * 16 + (lane & 14)) * FS) == ep); };
        auto need = [&](int e, uint32_t mask) {
          if ((ready & mask) != mask) {
            uint32_t n = 0;
            do { poll(e); SPIN_GUARD(n); } while ((ready & mask) != mask);
            fence_async_global();
          }
        };
        auto fresh = [&](int e, int it, uint32_t full, uint32_t empty, int par, uint32_t slot, uint4* src) {
          if (it >= 4) {
            const int kb = own_order(it, j);
            if (it < 10) need(e, 1u << kb); else if (it == 10) mbar_wait(bar + B_ALL, e & 1);
            plain(full, empty, par, slot, src + kb * 1024);
          } else {
            if (it == 0) ready = 0;
            mbar_wait(empty, par);
            if (it < 2) { if (elect()) mbar_arrive(full); }
            else {
              const int b = it > 2;
              const uint32_t to_peer = mapa(sb, rank ^ 1) - sb;
              if (elect()) mbar_expect_tx(full, BLK);
              const bool push = e != 1;
              mbar_wait(bar + (b ? (push ? B_RDY + 8 : B_FREE + 8) : B_RDY), e & 1);
              if (elect()) {
                if (b == 0) {
                  bulk_st(src + 2 * j * 1024, sb + STG, BLK);
                  bulk_commit();
                  bulk_wait_all();
                  mbar_arrive(bar + B_FREE);
                }
                if (b && push) bulk_push(slot + to_peer, sb + STG + BLK, BLK, full + to_peer);
                else {
                  fence_async_global();
                  bulk_ld(slot + to_peer, src + (2 * j + b) * 1024, BLK, full + to_peer);
                }
              }
              __syncwarp();
            }
          }
        };
        uint4* const h = gs->h + m * 16384;
#pragma unroll 1
        for (int e = 0; e < 3; e++) {
#pragma unroll 1
          for (int it = 0; it < 16; it++) {
            const int s = e == 1 ? s6 : (it + e) & 3;
            const uint32_t full = bar + (e == 1 ? B_FULL6 : B_FULL4) + s * 8;
            if (e == 2) drained6(it);
            fresh(e, it, full, full + (e == 1 ? 48 : 32), e == 1 ? p6 : ~(it >> 2) & 1, sb + s * (e == 1 ? 32768 : 49152), e == 1 ? gs->o + m * 16384 : h);
            if (e == 1) next6();
          }
          if (e == 1) { skip6(); continue; }
#pragma unroll 1
          for (int it = 16; it < 16 + 16 * e; it++) {
            const int s = (it + 2) & 3;
            const uint32_t full = bar + B_FULL4 + s * 8;
            plain(full, full + 32, ~(it >> 2) & 1, sb + s * 49152, h + (it & 15) * 1024);
          }
#pragma unroll 1
          for (int it = 0; it < 16; it++) { drained4(it, e); plain6(h + it * 1024); }
        }
#pragma unroll 1
        for (int it = 0; it < 56; it++) {
          if (it == 0 || it == 32 || it == 48) mbar_wait(bar + (it == 48 ? B_HH2 : B_HH + (it >> 2)), 0);
          plain6(gs->hh + m * 57344 + it * 1024);
        }
      }
    } else {
      const int b = warp - 10;
      const uint32_t ep = gs->epoch[blockIdx.x] + 1;
      const uint32_t stg = sb + STG + b * BLK;
      cl_arrive_relaxed(); cl_wait();
      auto all_there = [&](int u, uint32_t done) {
        const uint32_t* fl = gs->flag + u * FS;
        uint32_t n = 0;
        while (!__all_sync(~0u, ld_acquire(fl) == ep)) { __nanosleep(100); SPIN_GUARD(n); }
        fence_async_global();
        if (lane == 0) mbar_arrive(done);
      };
      auto fetch_mod = [&](int sec) {
        const uint4* p = (const uint4*)(gs->modv + (sec - 2) * 1024 + j * 128) + lane;
        uint4 v0, v1; uint32_t n = 0;
        while (true) {
          v0 = ld_rlx4(p); v1 = ld_rlx4(p + 32);
          if (v0.y == ep && v0.w == ep && v1.y == ep && v1.w == ep) break;
          SPIN_GUARD(n);
        }
        const uint32_t d = sb + MISC + MODV + sec * 256 + ((lane & 3) * 16 + (lane >> 2)) * 4;
        asm volatile("st.shared.u32 [%0], %1;" :: "r"(d), "r"(__byte_perm(v0.x, v0.z, 0x7632)) : "memory");
        asm volatile("st.shared.u32 [%0], %1;" :: "r"(d + 32), "r"(__byte_perm(v1.x, v1.z, 0x7632)) : "memory");
        __syncwarp();
      };
#pragma unroll 1
      for (int e = 0; e < 7 - b; e++) {
        if (lane == 0) {
          if (e < 3) {
            mbar_wait(bar + B_FREE, e & 1);
            if (b) {
              const uint32_t t0 = clock();
              while ((uint32_t)clock() - t0 < (e == 1 ? B1D : B1P)) {}
              mbar_wait(bar + B_RDY + 8, e & 1);
              bulk_st((e == 1 ? gs->o : gs->h) + m * 16384 + (2 * j + 1) * 1024, stg, BLK);
              bulk_commit();
              bulk_wait_all();
              mbar_arrive(bar + B_FREE + 8);
            }
            st_release(gs->flag + (m * 128 + e * 16 + 2 * j + b) * FS, ep);
          } else {
            const int kb = (e < 6 ? 2 * (8 * (e - 3) + j) : 48 + j) + b;
            mbar_wait(bar + B_RDY + b * 8, e & 1);
#pragma unroll 1
            for (int q = 0; q < NPIECE; q++) { if (q) __nanosleep(PSLEEP); bulk_st(gs->hh + m * 57344 + kb * 1024 + q * (1024 / NPIECE), stg + q * (BLK / NPIECE), BLK / NPIECE); }
            bulk_commit();
            bulk_wait_all();
            mbar_arrive(bar + B_FREE + b * 8);
            st_release(gs->flag + (m * 128 + U_HH + kb) * FS, ep);
          }
        }
        __syncwarp();
        if (e < 3 && b) all_there(m * 128 + e * 16 + (lane & 15), bar + B_ALL);
        if (e == 4 && b) all_there(m * 128 + U_HH + lane, bar + B_HH);
        if (!b && (e == 1 || e == 2)) {
#pragma unroll 1
          for (int sec = e == 1 ? 2 : 5; sec < 4 + e; sec++) fetch_mod(sec);
          if (e == 1) { if (lane == 0) mbar_arrive(bar + B_MOD); }
        }
        if (e == 0) {
          mbar_wait(bar + B_EMPTY6 + 24, 0);
          __nanosleep(HSLEEP);
#pragma unroll 1
          for (int w = 0; w < 4; w++) {
            const uint4* hp = gs->halo + ((m * 8 + j) * 2 + (w & 1)) * 512 + b * 256 + (w >> 1) * 128 + lane;
            uint4 q[4] = {}; uint32_t n = 0;
            while (m > 0) {
              bool ok = true;
#pragma unroll
              for (int i = 0; i < 4; i++) q[i] = ld_rlx4(hp + i * 32);
#pragma unroll
              for (int i = 0; i < 4; i++) ok = ok && q[i].y == ep && q[i].w == ep;
              if (ok) break;
              SPIN_GUARD(n);
            }
#pragma unroll
            for (int i = 0; i < 2; i++) sts128(stg + lane * 16 + (w & 1) * HALF + (w >> 1) * 1024 + i * 512, q[2 * i].x, q[2 * i + 1].x, q[2 * i].z, q[2 * i + 1].z);
          }
          __syncwarp();
          if (lane == 0) mbar_arrive(bar + B_HALO);
        }
      }
      if (b) { all_there(m * 128 + U_HH + 32 + (lane & 15), bar + B_HH + 8); all_there(m * 128 + U_HH + 48 + (lane & 7), bar + B_HH2); }
    }
  } else {
    const int wg = warp >> 2, wq = warp & 3, tid = threadIdx.x;
    const int g = lane >> 2, c = lane & 3;
    const int sec0 = (m >> 1) & 1, hf0 = m & 1, ks0 = (m >> 2) & 3;
    uint4 wv[8];
    uint32_t ep0; uint16_t cv_;
    asm volatile("ld.global.nc.u16 %0, [%1];" : "=h"(cv_) : "l"(cvec + ks0 * 256 + warp * 32 + lane));
    asm volatile("ld.global.u32 %0, [%1];" : "=r"(ep0) : "l"(gs->epoch + (blockIdx.x | (lane & by_sm & 2))));
    if (!extra) {
      const bf16* wp = wmod + (size_t)(ks0 * 256 + warp * 32 + (lane >> 3)) * 6144 + sec0 * 1024 + j * 128 + hf0 * 64 + (lane & 7) * 8;
#pragma unroll
      for (int i = 0; i < 8; i++) wv[i] = ldg_nc(wp + (size_t)i * 4 * 6144);
      cl_arrive_relaxed();
    }
    asm volatile("setmaxnreg.inc.sync.aligned.u32 232;" ::: "memory");
    if (__builtin_expect(extra, 0)) {
      const uint32_t ep = ep0 + 1;
      float sv[4];
#pragma unroll
      for (int p = 0; p < 4; p++) sv[p] = silu_c(__bfloat162float(cvec[64 * (4 * p + (lane >> 3)) + 8 * warp + (lane & 7)]));
      named_bar(2, 288);
      int s = 0, par = 0;
#pragma unroll 1
      for (int sec = 0; sec < 4; sec++) {
        float a[8] = {0, 0, 0, 0, 0, 0, 0, 0};
#pragma unroll 1
        for (int it = 0; it < 16; it++) {
          const float sc = it < 4 ? sv[0] : it < 8 ? sv[1] : it < 12 ? sv[2] : sv[3];
          mbar_wait(bar + B_FULL6 + s * 8, par);
          uint4 w[8];
#pragma unroll
          for (int i = 0; i < 8; i++) w[i] = lds128(sb + s * 32768 + (warp * 8 + i) * 512 + lane * 16);
#pragma unroll
          for (int i = 0; i < 8; i++) gemv_fma(a, w[i], __shfl_sync(~0u, sc, (it & 3) * 8 + i));
          if (lane == 0) mbar_arrive(bar + B_EMPTY6 + s * 8);
          if (++s == 6) { s = 0; par ^= 1; }
        }
        const uint32_t red = sb + STG + sec * 8192;
        sts128(red + warp * 1024 + lane * 32, __float_as_uint(a[0]), __float_as_uint(a[1]), __float_as_uint(a[2]), __float_as_uint(a[3]));
        sts128(red + warp * 1024 + lane * 32 + 16, __float_as_uint(a[4]), __float_as_uint(a[5]), __float_as_uint(a[6]), __float_as_uint(a[7]));
        named_bar(1, 256);
        float t = 0;
#pragma unroll
        for (int q = 0; q < 8; q++) t += lds32f(red + q * 1024 + tid * 4);
        t = bf_round(t);
        if (sec == 2) t = bf_round(t + 1.f);
        st_rlx2(gs->modv + sec * 1024 + (bid + 4) * 256 + tid, __float_as_uint(t), ep);
      }
      if (tid == 0) gs->epoch[blockIdx.x] = ep;
      return;
    }
    const int row0 = wg * 64 + wq * 16 + g;
    if (c < 2) st_rlx2(gs->stat + m * 1024 + j * 128 + row0 + c * 8, 0, 0);
    cl_wait();
    uint32_t ep;
    asm volatile("add.u32 %0, %1, 1;" : "=r"(ep) : "r"(ep0) : "memory");
    const float sc_ = silu_c(__uint_as_float((uint32_t)cv_ << 16));
    const uint32_t rel = mapa(bar, (lane & 1) ^ rank);
    const uint32_t stg_row = sb + STG + (wg * 64 + wq * 16 + (lane & 15)) * 128;
    const uint32_t fre = bar + B_FREE;
    Ring r4{0, 0, 0}, r6{0, 0, 0};
    auto none = [](auto) {};
    uint32_t xk[32];
    {
      float a[8] = {0, 0, 0, 0, 0, 0, 0, 0};
#pragma unroll
      for (int i = 0; i < 8; i++) gemv_fma(a, wv[i], __shfl_sync(~0u, sc_, i * 4 + (lane >> 3)));
#pragma unroll
      for (int i = 0; i < 8; i++) { a[i] += __shfl_xor_sync(~0u, a[i], 8); a[i] += __shfl_xor_sync(~0u, a[i], 16); }
      if (lane < 8) {
        sts128(sb + RED_OFF + warp * 256 + lane * 32, __float_as_uint(a[0]), __float_as_uint(a[1]), __float_as_uint(a[2]), __float_as_uint(a[3]));
        sts128(sb + RED_OFF + warp * 256 + lane * 32 + 16, __float_as_uint(a[4]), __float_as_uint(a[5]), __float_as_uint(a[6]), __float_as_uint(a[7]));
      }
      named_bar(1, 256);
      if (tid < 64) {
        float s = 0;
#pragma unroll
        for (int w = 0; w < 8; w++) s += lds32f(sb + RED_OFF + w * 256 + tid * 4);
        st_rlx1(gs->modp + ((j * 2 + sec0) * 4 + ks0) * 128 + hf0 * 64 + tid, (__float_as_uint(s) & ~255u) | tag_of(ep));
      }
      float v[64];
      mbar_wait(bar + B_X, 0); mbar_wait(bar + B_X + 8, 0);
#pragma unroll
      for (int i = 0; i < 16; i += 2) {
        uint32_t w0, w1, w2, w3;
        ldsm4(stg_row + (i >> 3) * BLK + ((((i & 7) + (lane >> 4)) ^ (lane & 7)) << 4), w0, w1, w2, w3);
        xk[2 * i] = w0; xk[2 * i + 1] = w1; xk[2 * i + 2] = w2; xk[2 * i + 3] = w3;
        v[4 * i] = bf_lo(w0); v[4 * i + 1] = bf_hi(w0); v[4 * i + 2] = bf_lo(w1); v[4 * i + 3] = bf_hi(w1);
        v[4 * i + 4] = bf_lo(w2); v[4 * i + 5] = bf_hi(w2); v[4 * i + 6] = bf_lo(w3); v[4 * i + 7] = bf_hi(w3);
      }
      ln_publish(v, gs->stat + m * 1024, j, row0, lane, ep);
      mod_store(sb, tid >> 7, tid & 127, mod_gather(gs->modp + (j * 2 + (tid >> 7)) * 512 + (tid & 127), ep));
      named_bar(1, 256);
      ln_apply(v, gs->stat + m * 1024, row0, ep, sb, 0, 1, stg_row, wg, lane);
      named_bar(1, 256);
    }
    {
      uint32_t kf[32], vf[32], pv[32];
      const bool first = wq == 0 && m == 0;
      const uint32_t xa = sb + STG + wg * HALF + wq * 2048 + lane * 16;
      {
        float acc[128];
        mainloop<256, 4, 0, 0>(acc, 16, true, r4, sb, wg, lane, rel, none, none, [&] {
          mbar_wait(fre + 8, 0);
          if (c < 2) st_rlx2(gs->stat + (16 + m) * 1024 + j * 128 + row0 + c * 8, 0, 0);
        });
#pragma unroll
        for (int i = 0; i < 32; i++) { kf[i] = pack2(acc[2 * i], acc[2 * i + 1]); vf[i] = pack2(acc[64 + 2 * i], acc[65 + 2 * i]); }
      }
      float acc[64];
      constexpr int QP = 2;
      mainloop<128, 6, 8 / QP, 0>(acc, 16, false, r6, sb, wg, lane, rel, [&](auto ic) {
        constexpr int q = (ic.v - 1) * QP;
#pragma unroll
        for (int i = 4 * q; i < 4 * (q + QP); i++) vf[i] = movm(vf[i]);
        if (wq == 3) {
          if (m < 15) {
            uint4* hp = gs->halo + (((m + 1) * 8 + j) * 2 + wg) * 512 + lane;
#pragma unroll
            for (int i = 2 * q; i < 2 * (q + QP); i++) st_rlx4(hp + i * 32, kf[2 * i + 1], ep, vf[2 * i + 1], ep);
          }
        } else {
#pragma unroll
          for (int i = q; i < q + QP; i++) sts128(xa + 2048 + (i >> 2) * BLK + (i & 3) * 512, kf[4 * i + 1], kf[4 * i + 3], vf[4 * i + 1], vf[4 * i + 3]);
        }
      }, none, [&] {
        named_bar(2 + wg, 128);
        if (wq == 0) mbar_wait(bar + B_HALO, 0);
#pragma unroll
        for (int i = 0; i < 8; i++) {
          uint4 q = lds128(xa + (i >> 2) * BLK + (i & 3) * 512);
          pv[4 * i] = q.x; pv[4 * i + 1] = q.y; pv[4 * i + 2] = q.z; pv[4 * i + 3] = q.w;
        }
        __syncwarp();
      });
      int gz = g;
#pragma unroll
      for (int b = 0; b < 2; b++) {
        const bool up0 = 2 * c > gz, up1 = 2 * c + 1 > gz;
        const uint32_t mup = (up0 ? 0xffffu : 0u) | (up1 ? 0xffff0000u : 0u);
        float l[2][4], mx[4];
#pragma unroll
        for (int h = 0; h < 2; h++) {
          uint32_t q[8];
          const int k = 16 * b + 8 * h;
#pragma unroll
          for (int i = 0; i < 8; i++) q[i] = pack2(acc[2 * k + 2 * i], acc[2 * k + 2 * i + 1]);
          float s0[4], s1[4], s2[4];
          mma16z(s0, q[0], q[1], q[2], q[3], pv[k], pv[k + 1]); mma16z(s1, q[0], q[1], q[2], q[3], kf[k], kf[k + 2]); mma16z(s2, q[0], q[1], q[2], q[3], kf[k + 1], kf[k + 3]);
          mma16(s0, q[4], q[5], q[6], q[7], pv[k + 4], pv[k + 5]); mma16(s1, q[4], q[5], q[6], q[7], kf[k + 4], kf[k + 6]); mma16(s2, q[4], q[5], q[6], q[7], kf[k + 5], kf[k + 7]);
          if (first) { s0[0] = -INFINITY; s0[1] = -INFINITY; }
          l[h][0] = up0 ? s0[0] : s1[0]; l[h][1] = up1 ? s0[1] : s1[1]; l[h][2] = up0 ? s1[2] : s2[2]; l[h][3] = up1 ? s1[3] : s2[3];
          mx[2 * h] = fmaxf(l[h][0], l[h][1]); mx[2 * h + 1] = fmaxf(l[h][2], l[h][3]);
        }
#pragma unroll
        for (int o = 1; o < 4; o <<= 1) {
#pragma unroll
          for (int h = 0; h < 4; h++) mx[h] = fmaxf(mx[h], __shfl_xor_sync(~0u, mx[h], o));
        }
#pragma unroll
        for (int h = 0; h < 2; h++) {
          const float n0 = -mx[2 * h] * SCL, n1 = -mx[2 * h + 1] * SCL;
          const uint32_t pa = pack2(ex2(fmaf(l[h][0], SCL, n0)), ex2(fmaf(l[h][1], SCL, n0))), pb = pack2(ex2(fmaf(l[h][2], SCL, n1)), ex2(fmaf(l[h][3], SCL, n1)));
          float sm[4];
          mma8z(sm, pa, pb, 0x3f803f80u);
          const float ia = rcp(sm[0]), ib = rcp(sm[2]);
#pragma unroll
          for (int i = 8 * b + 4 * h; i < 8 * b + 4 * h + 4; i += 2) {
            uint32_t of[4];
#pragma unroll
            for (int d = 0; d < 2; d++) {
              float o[4];
              mma16z(o, pa & ~mup, pb & mup, 0u, pb & ~mup, vf[2 * (i + d)], vf[2 * (i + d) + 1]);
              mma8(o, pa & mup, 0u, pv[2 * i + 2 + d]);
              of[2 * d] = pack2(o[0] * ia, o[1] * ia); of[2 * d + 1] = pack2(o[2] * ib, o[3] * ib);
            }
            stsm4(stg_row + b * BLK + ((((i & 7) + (lane >> 4)) ^ (lane & 7)) << 4), of[0], of[1], of[2], of[3]);
          }
        }
        stage_done(sb, wg, b, lane);
        if (b == 0) gz += __float_as_uint(lds32f(bar + ZERO));
      }
      named_bar(1, 256);
    }
    uint32_t pk[64];
    {
      float acc[64];
      mainloop<128, 6, 0, 0>(acc, 16, true, r6, sb, wg, lane, rel, none, none, [&] {
        mbar_wait(bar + B_MOD, 0); mbar_wait(fre + 8, 1);
        load_vec(pk + 32, sb, 2, 0, lane); load_vec(pk + 40, sb, 2, 1, lane);
#pragma unroll
        for (int i = 0; i < 32; i++) { pk[i] = xk[i]; asm volatile("" : "+r"(pk[i])); }
      });
#pragma unroll
      for (int i = 0; i < 32; i++) {
        acc[2 * i] = fmaf(acc[2 * i], bf_lo(pk[32 + (i >> 1)]), bf_lo(pk[i]));
        acc[2 * i + 1] = fmaf(acc[2 * i + 1], bf_hi(pk[32 + (i >> 1)]), bf_hi(pk[i]));
      }
      ln_publish(acc, gs->stat + (16 + m) * 1024, j, row0, lane, ep);
      mbar_wait(bar + B_FULL6 + 16, 1);
      if (lane < 2) mbar_arrive_cl(rel + B_EMPTY6 + 16);
      ring_next<6>(r6);
#pragma unroll
      for (int i = 0; i < 32; i++) { pk[i] = pack2(acc[2 * i], acc[2 * i + 1]); pk[32 + i] = 0; }
      ln_apply(acc, gs->stat + (16 + m) * 1024, row0, ep, sb, 3, 4, stg_row, wg, lane);
      named_bar(1, 256);
    }
    auto swiglu = [&](int q, int uo, int par) {
      if ((q & 3) == 0 && par >= 0) mbar_wait(fre + 2 * q, par);
      uint32_t w[4];
#pragma unroll
      for (int u = 0; u < 4; u++) w[u] = silu_mul2(pk[4 * q + u], pk[uo + 4 * q + u]);
      stsm4(stg_row + (q >> 2) * BLK + ((((2 * q & 7) + (lane >> 4)) ^ (lane & 7)) << 4), w[0], w[1], w[2], w[3]);
    };
    r4.s = r4.wrap = 2;
#pragma unroll 1
    for (int t = 0; t < 3; t++) {
      float acc[128];
      mainloop<256, 4, 4, 1>(acc, 16, t == 0, r4, sb, wg, lane, rel, [&](auto ic) {
        if (t) {
          if (ic.v == 3) stage_done(sb, wg, 0, lane);
          swiglu(2 * ic.v - 2, 32, ~t & 1); swiglu(2 * ic.v - 1, 32, 0);
        }
      }, [&](int it) {
        if (t && it == 5) stage_done(sb, wg, 1, lane);
#pragma unroll
        for (int i = 0; i < 8; i++)
          if (t == 0 && it == 8 + i) gs->x1[bid * 2048 + (i >> 2) * 1024 + warp * 128 + (i & 3) * 32 + lane] = make_uint4(pk[4 * i], pk[4 * i + 1], pk[4 * i + 2], pk[4 * i + 3]);
      }, [&] { if (t == 0) fence_async_global(); else if (t == 2) mbar_wait(bar + B_X, 1); }, t & 1);
#pragma unroll
      for (int i = 0; i < 64; i++) pk[i] = pack2(acc[2 * i], acc[2 * i + 1]);
    }
    uint32_t x1[32];
    {
      float acc[64];
      mainloop<128, 6, 10, 1>(acc, 16, false, r6, sb, wg, lane, rel, [&](auto ic) {
        constexpr int b = ic.v > 5, q = ic.v - 5 * b;
        if (q == 1) {
          if (b) stage_done(sb, wg, 0, lane);
#pragma unroll
          for (int i = 4 * b; i < 4 * b + 4; i++) { const uint4 x = lds128(sb + STG + b * BLK + warp * 2048 + (i & 3) * 512 + lane * 16); x1[4 * i] = x.x; x1[4 * i + 1] = x.y; x1[4 * i + 2] = x.z; x1[4 * i + 3] = x.w; }
          __syncwarp();
        } else swiglu(4 * b + q - 2, 32, -1);
      }, [&](int it) { if (it == 11) stage_done(sb, wg, 1, lane); }, [] {}, 1);
#pragma unroll
      for (int i = 0; i < 32; i++) pk[i] = pack2(acc[2 * i], acc[2 * i + 1]);
    }
    {
      float acc[64];
      mainloop<128, 6, 4, TAILLAG>(acc, 56, false, r6, sb, wg, lane, rel, [&](auto ic) { swiglu(ic.v - 1, 16, 1); },
                                   [&](int it) { if (it == 5) stage_done(sb, wg, 0, lane); }, [&] {
        load_vec(pk + 32, sb, 5, 0, lane); load_vec(pk + 40, sb, 5, 1, lane);
        mbar_wait(fre, 0); mbar_wait(fre + 8, 1);
      }, 0);
      __syncwarp();
      cl_arrive_relaxed();
#pragma unroll
      for (int i = 0; i < 16; i += 2) {
        uint32_t w[4];
#pragma unroll
        for (int u = 0; u < 4; u++) {
          const int q = 2 * i + u;
          w[u] = pack2(fmaf(acc[2 * q], bf_lo(pk[32 + (q >> 1)]), bf_lo(x1[q])), fmaf(acc[2 * q + 1], bf_hi(pk[32 + (q >> 1)]), bf_hi(x1[q])));
        }
        stsm4(stg_row + (i >> 3) * BLK + ((((i & 7) + (lane >> 4)) ^ (lane & 7)) << 4), w[0], w[1], w[2], w[3]);
        if ((i & 7) == 6) {
          fence_async_smem();
          named_bar(2 + wg, 128);
          if (wq == 0 && elect()) { tma_store_3d(&maps.out, sb + STG + (i >> 3) * BLK + wg * HALF, j * 128 + (i >> 3) * 64, m * 64, wg); bulk_commit(); }
          if (i < 8) x1[16] |= __float_as_uint(lds32f(bar + ZERO));
        }
      }
      if (wq == 0) bulk_wait_read();
      if (tid == 0) gs->epoch[blockIdx.x] = ep;
      cl_wait();
    }
  }
}

typedef CUresult (*EncodeFn)(CUtensorMap*, CUtensorMapDataType, cuuint32_t, void*, const cuuint64_t*, const cuuint64_t*, const cuuint32_t*, const cuuint32_t*,
                             CUtensorMapInterleave, CUtensorMapSwizzle, CUtensorMapL2promotion, CUtensorMapFloatOOBfill);

void make_map(EncodeFn fn, CUtensorMap* mp, const void* base, uint64_t d0, uint64_t d1, uint64_t d2, uint64_t s1, uint64_t s2, uint32_t b2, uint32_t b0 = 64) {
  cuuint64_t d[3] = {d0, d1, d2}, s[2] = {s1, s2};
  cuuint32_t b[3] = {b0, 64, b2}, e[3] = {1, 1, 1};
  fn(mp, CU_TENSOR_MAP_DATA_TYPE_BFLOAT16, 3, (void*)base, d, s, b, e, CU_TENSOR_MAP_INTERLEAVE_NONE, b0 == 64 ? CU_TENSOR_MAP_SWIZZLE_128B : CU_TENSOR_MAP_SWIZZLE_NONE,
     CU_TENSOR_MAP_L2_PROMOTION_L2_128B, CU_TENSOR_MAP_FLOAT_OOB_FILL_NONE);
}

__global__ void probe_kernel() {}
int max_clusters(int size) {
  cudaLaunchConfig_t cfg = {};
  cudaLaunchAttribute at;
  at.id = cudaLaunchAttributeClusterDimension; at.val.clusterDim.x = size; at.val.clusterDim.y = 1; at.val.clusterDim.z = 1;
  cfg.gridDim = dim3(size * 66); cfg.blockDim = dim3(384); cfg.dynamicSmemBytes = SMEM_BYTES; cfg.attrs = &at; cfg.numAttrs = 1;
  int n = 0;
  if (cudaOccupancyMaxActiveClusters(&n, probe_kernel, &cfg) != cudaSuccess) { cudaGetLastError(); return 0; }
  return n;
}

}

extern "C" void kernel_launch(void* const* d_in, const int* in_sizes, int n_in, void* d_out, int out_size) {
  static EncodeFn fn = nullptr;
  static int by_sm = 0;
  static Scratch* gs = nullptr;
  if (!fn) {
    void* p = nullptr; cudaDriverEntryPointQueryResult q;
    cudaGetDriverEntryPoint("cuTensorMapEncodeTiled", &p, cudaEnableDefault, &q);
    fn = (EncodeFn)p;
    cudaFuncSetAttribute(fused_kernel, cudaFuncAttributeMaxDynamicSharedMemorySize, SMEM_BYTES);
    int dev = 0, sms = 0;
    cudaGetSymbolAddress((void**)&gs, g_scratch);
    cudaGetDevice(&dev);
    cudaDeviceGetAttribute(&sms, cudaDevAttrMultiProcessorCount, dev);
    cudaFuncSetAttribute(probe_kernel, cudaFuncAttributeMaxDynamicSharedMemorySize, SMEM_BYTES);
    by_sm = sms == 132 && max_clusters(2) == 66 && max_clusters(4) == 30 && max_clusters(6) == 17 && max_clusters(8) == 15;
  }
  Maps mp;
  make_map(fn, &mp.x, d_in[0], D_, S_ / 2, 2, 4096, 2048, 2);
  make_map(fn, &mp.out, d_out, D_, S_ / 2, 2, 4096, 2048, 1);
  make_map(fn, &mp.wqkv, d_in[1], 64, D_, 3 * D_ / 64, 3 * D_ * 2, 128, 2);
  make_map(fn, &mp.wo, d_in[2], 64, D_, D_ / 64, D_ * 2, 128, 2);
  make_map(fn, &mp.w1, d_in[4], 64, D_, F_ / 64, F_ * 2, 128, 2);
  make_map(fn, &mp.w3, d_in[5], 64, D_, F_ / 64, F_ * 2, 128, 2);
  make_map(fn, &mp.w1s, d_in[4], 64, D_, F_ / 64, F_ * 2, 128, 1);
  make_map(fn, &mp.w3s, d_in[5], 64, D_, F_ / 64, F_ * 2, 128, 1);
  make_map(fn, &mp.w2, d_in[6], 64, F_, D_ / 64, D_ * 2, 128, 2);
  make_map(fn, &mp.wmod, d_in[8], 256, D_, 24, 6 * D_ * 2, 512, 1, 256);
  fused_kernel<<<132, 384, SMEM_BYTES>>>((const bf16*)d_in[7], (const bf16*)d_in[8], gs, by_sm, mp);
}
```

```cpp
#include <cuda_runtime.h>
#include <cuda_bf16.h>
#include <cuda.h>
#include <stdint.h>

typedef __nv_bfloat16 bf16;

namespace {

constexpr int S_ = 2048, D_ = 1024, F_ = 3584;
constexpr int BLK = 16384;
constexpr int HALF = 8192;
constexpr int RING = 196608;
constexpr int STG = RING;
constexpr int MISC = RING + 2 * BLK;
constexpr int SMEM_BYTES = MISC + 3072;
constexpr int B_FULL4 = 0, B_EMPTY4 = 32, B_FULL6 = 64, B_EMPTY6 = 112, B_RDY = 160, B_FREE = 176, B_LAG = 192, B_X = 208, B_MOD = 224, B_HALO = 232, B_HH = 256, B_ALL = 272, B_HH2 = 288, ZERO = 296;
constexpr int MODV = 512;
constexpr int RED_OFF = 0;
constexpr float SCL = 0.17677669529663687f * 1.4426950408889634f;
constexpr int U_HH = 64;
constexpr int FS = 8;
constexpr int NPIECE = 4, PSLEEP = 300;
constexpr int XSLEEP = 4000, HSLEEP = 400;
constexpr uint32_t XDELAY = 2300, GAP = 250;
constexpr uint32_t B1P = 3700, B1D = 700;
constexpr int TAILLAG = 5;

struct Maps { CUtensorMap x, out, wqkv, wo, w1, w3, w1s, w3s, w2, wmod; };

struct Scratch {
  uint4 h[16 * 16 * 1024];
  uint4 o[16 * 16 * 1024];
  uint4 hh[16 * 56 * 1024];
  uint4 x1[128 * 8 * 256];
  uint2 stat[2 * 16 * 8 * 128];
  uint4 halo[16 * 8 * 2 * 512];
  uint32_t modp[8 * 2 * 4 * 128];
  uint2 modv[4 * 1024];
  uint32_t flag[16 * 128 * FS];
  uint32_t epoch[132];
};
__device__ __align__(1024) Scratch g_scratch;

__device__ __forceinline__ void bail() { asm volatile("st.global.u32 [%0], %1;" :: "l"(0ull), "r"(0) : "memory"); }
__device__ __forceinline__ uint32_t smem_u32(const void* p) { return (uint32_t)__cvta_generic_to_shared(p); }
__device__ __forceinline__ void mbar_init(uint32_t bar, uint32_t cnt) { asm volatile("mbarrier.init.shared::cta.b64 [%0], %1;" :: "r"(bar), "r"(cnt) : "memory"); }
__device__ __forceinline__ void mbar_arrive(uint32_t bar) { asm volatile("mbarrier.arrive.shared::cta.b64 _, [%0];" :: "r"(bar) : "memory"); }
__device__ __forceinline__ void mbar_arrive_cl(uint32_t cl_addr) { asm volatile("mbarrier.arrive.shared::cluster.b64 _, [%0];" :: "r"(cl_addr) : "memory"); }
__device__ __forceinline__ uint32_t mapa(uint32_t addr, uint32_t cta) { uint32_t r; asm("mapa.shared::cluster.u32 %0, %1, %2;" : "=r"(r) : "r"(addr), "r"(cta)); return r; }
__device__ __forceinline__ void mbar_wait(uint32_t bar, uint32_t parity) {
  asm volatile("{\n.reg .pred p;\n.reg .b32 n;\n.reg .b64 z;\nmov.b32 n, 0;\nmov.b64 z, 0;\n"
               "W: add.u32 n, n, 1;\nsetp.gt.u32 p, n, 0x400000;\n@p st.global.u32 [z], n;\n"
               "mbarrier.try_wait.parity.shared::cta.b64 p, [%0], %1;\n@!p bra W;\n}" :: "r"(bar), "r"(parity) : "memory");
}
__device__ __forceinline__ void tma_store_3d(const CUtensorMap* m, uint32_t src, int c0, int c1, int c2) {
  asm volatile("cp.async.bulk.tensor.3d.global.shared::cta.bulk_group [%0, {%2, %3, %4}], [%1];" :: "l"(m), "r"(src), "r"(c0), "r"(c1), "r"(c2) : "memory");
}
#define ELECT "{\n.reg .pred p;\nelect.sync _|p, 0xffffffff;\n@p "
__device__ __forceinline__ void expect_e(uint32_t bar, uint32_t bytes) { asm volatile(ELECT "mbarrier.arrive.expect_tx.shared::cta.b64 _, [%0], %1;\n}" :: "r"(bar), "r"(bytes) : "memory"); }
__device__ __forceinline__ void tma_3d_e(uint32_t dst, const CUtensorMap* m, uint32_t bar, int c0, int c1, int c2) {
  asm volatile(ELECT "cp.async.bulk.tensor.3d.shared::cluster.global.mbarrier::complete_tx::bytes [%0], [%1, {%3, %4, %5}], [%2];\n}" :: "r"(dst), "l"(m), "r"(bar), "r"(c0), "r"(c1), "r"(c2) : "memory");
}
__device__ __forceinline__ void bulk_ld_e(uint32_t dst, const void* src, uint32_t bytes, uint32_t bar) {
  asm volatile(ELECT "cp.async.bulk.shared::cluster.global.mbarrier::complete_tx::bytes [%0], [%1], %2, [%3];\n}" :: "r"(dst), "l"(src), "r"(bytes), "r"(bar) : "memory");
}
__device__ __forceinline__ void bulk_ld_mc_e(uint32_t dst, const void* src, uint32_t bytes, uint32_t bar) {
  asm volatile(ELECT "cp.async.bulk.shared::cluster.global.mbarrier::complete_tx::bytes.multicast::cluster [%0], [%1], %2, [%3], %4;\n}" :: "r"(dst), "l"(src), "r"(bytes), "r"(bar), "h"((uint16_t)3) : "memory");
}
__device__ __forceinline__ void bulk_push_e(uint32_t dst_cl, uint32_t src, uint32_t bytes, uint32_t bar_cl) {
  asm volatile(ELECT "cp.async.bulk.shared::cluster.shared::cta.mbarrier::complete_tx::bytes [%0], [%1], %2, [%3];\n}" :: "r"(dst_cl), "r"(src), "r"(bytes), "r"(bar_cl) : "memory");
}
__device__ __forceinline__ void bulk_st(void* dst, uint32_t src, uint32_t bytes) {
  asm volatile("cp.async.bulk.global.shared::cta.bulk_group [%0], [%1], %2;" :: "l"(dst), "r"(src), "r"(bytes) : "memory");
}
__device__ __forceinline__ void bulk_commit() { asm volatile("cp.async.bulk.commit_group;" ::: "memory"); }
__device__ __forceinline__ void bulk_wait_read() { asm volatile("cp.async.bulk.wait_group.read 0;" ::: "memory"); }
__device__ __forceinline__ void bulk_wait_all() { asm volatile("cp.async.bulk.wait_group 0;" ::: "memory"); }
__device__ __forceinline__ void fence_async_global() { asm volatile("fence.proxy.async.global;" ::: "memory"); }
__device__ __forceinline__ void fence_async_smem() { asm volatile("fence.proxy.async.shared::cta;" ::: "memory"); }
__device__ __forceinline__ void wg_arrive() { asm volatile("wgmma.fence.sync.aligned;" ::: "memory"); }
__device__ __forceinline__ void wg_commit() { asm volatile("wgmma.commit_group.sync.aligned;" ::: "memory"); }
template <int N> __device__ __forceinline__ void wg_wait() { asm volatile("wgmma.wait_group.sync.aligned %0;" :: "n"(N) : "memory"); }
__device__ __forceinline__ void cl_arrive_relaxed() { asm volatile("barrier.cluster.arrive.relaxed.aligned;" ::: "memory"); }
__device__ __forceinline__ void cl_wait() { asm volatile("barrier.cluster.wait.acquire.aligned;" ::: "memory"); }
__device__ __forceinline__ bool elect() { uint32_t p; asm volatile("{\n.reg .pred p;\nelect.sync _|p, 0xffffffff;\nselp.u32 %0, 1, 0, p;\n}" : "=r"(p)); return p; }
__device__ __forceinline__ void named_bar(int id, int n) { asm volatile("bar.sync %0, %1;" :: "r"(id), "r"(n) : "memory"); }
__device__ __forceinline__ uint32_t pack2(float lo, float hi) { uint32_t r; asm("cvt.rn.bf16x2.f32 %0, %1, %2;" : "=r"(r) : "f"(hi), "f"(lo)); return r; }
__device__ __forceinline__ float bf_lo(uint32_t w) { return __uint_as_float(w << 16); }
__device__ __forceinline__ float bf_hi(uint32_t w) { return __uint_as_float(w & 0xffff0000u); }
__device__ __forceinline__ float bf_round(float v) { return __bfloat162float(__float2bfloat16_rn(v)); }
__device__ __forceinline__ void stsm4(uint32_t addr, uint32_t a, uint32_t b, uint32_t c, uint32_t d) {
  asm volatile("stmatrix.sync.aligned.m8n8.x4.shared.b16 [%0], {%1, %2, %3, %4};" :: "r"(addr), "r"(a), "r"(b), "r"(c), "r"(d) : "memory");
}
__device__ __forceinline__ void ldsm4(uint32_t addr, uint32_t& a, uint32_t& b, uint32_t& c, uint32_t& d) {
  asm volatile("ldmatrix.sync.aligned.m8n8.x4.shared.b16 {%0, %1, %2, %3}, [%4];" : "=r"(a), "=r"(b), "=r"(c), "=r"(d) : "r"(addr) : "memory");
}
__device__ __forceinline__ uint32_t movm(uint32_t a) { uint32_t r; asm volatile("movmatrix.sync.aligned.m8n8.trans.b16 %0, %1;" : "=r"(r) : "r"(a)); return r; }
__device__ __forceinline__ void mma16(float (&d)[4], uint32_t a0, uint32_t a1, uint32_t a2, uint32_t a3, uint32_t b0, uint32_t b1) {
  asm("mma.sync.aligned.m16n8k16.row.col.f32.bf16.bf16.f32 {%0,%1,%2,%3}, {%4,%5,%6,%7}, {%8,%9}, {%0,%1,%2,%3};"
               : "+f"(d[0]), "+f"(d[1]), "+f"(d[2]), "+f"(d[3]) : "r"(a0), "r"(a1), "r"(a2), "r"(a3), "r"(b0), "r"(b1));
}
__device__ __forceinline__ void mma16z(float (&d)[4], uint32_t a0, uint32_t a1, uint32_t a2, uint32_t a3, uint32_t b0, uint32_t b1) {
  asm("mma.sync.aligned.m16n8k16.row.col.f32.bf16.bf16.f32 {%0,%1,%2,%3}, {%4,%5,%6,%7}, {%8,%9}, {%10,%10,%10,%10};"
      : "=f"(d[0]), "=f"(d[1]), "=f"(d[2]), "=f"(d[3]) : "r"(a0), "r"(a1), "r"(a2), "r"(a3), "r"(b0), "r"(b1), "f"(0.f));
}
__device__ __forceinline__ void mma8z(float (&d)[4], uint32_t a0, uint32_t a1, uint32_t b0) {
  asm("mma.sync.aligned.m16n8k8.row.col.f32.bf16.bf16.f32 {%0,%1,%2,%3}, {%4,%5}, {%6}, {%7,%7,%7,%7};"
      : "=f"(d[0]), "=f"(d[1]), "=f"(d[2]), "=f"(d[3]) : "r"(a0), "r"(a1), "r"(b0), "f"(0.f));
}
__device__ __forceinline__ void mma8(float (&d)[4], uint32_t a0, uint32_t a1, uint32_t b0) {
  asm("mma.sync.aligned.m16n8k8.row.col.f32.bf16.bf16.f32 {%0,%1,%2,%3}, {%4,%5}, {%6}, {%0,%1,%2,%3};"
               : "+f"(d[0]), "+f"(d[1]), "+f"(d[2]), "+f"(d[3]) : "r"(a0), "r"(a1), "r"(b0));
}
__device__ __forceinline__ uint4 lds128(uint32_t a) { uint4 v; asm volatile("ld.shared.v4.u32 {%0,%1,%2,%3}, [%4];" : "=r"(v.x), "=r"(v.y), "=r"(v.z), "=r"(v.w) : "r"(a) : "memory"); return v; }
__device__ __forceinline__ void sts128(uint32_t a, uint32_t x, uint32_t y, uint32_t z, uint32_t w) { asm volatile("st.shared.v4.u32 [%0], {%1,%2,%3,%4};" :: "r"(a), "r"(x), "r"(y), "r"(z), "r"(w) : "memory"); }
__device__ __forceinline__ float lds32f(uint32_t a) { float v; asm volatile("ld.shared.f32 %0, [%1];" : "=f"(v) : "r"(a) : "memory"); return v; }
__device__ __forceinline__ void sts16(uint32_t a, bf16 v) { asm volatile("st.shared.b16 [%0], %1;" :: "r"(a), "h"(__bfloat16_as_ushort(v)) : "memory"); }
__device__ __forceinline__ uint4 ldg_nc(const void* p) { uint4 v; asm volatile("ld.global.nc.L1::no_allocate.v4.u32 {%0,%1,%2,%3}, [%4];" : "=r"(v.x), "=r"(v.y), "=r"(v.z), "=r"(v.w) : "l"(p)); return v; }
__device__ __forceinline__ uint4 ld_rlx4(const uint4* p) {
  unsigned long long a, b; asm volatile("ld.relaxed.gpu.global.v2.b64 {%0,%1}, [%2];" : "=l"(a), "=l"(b) : "l"(p) : "memory");
  return make_uint4((uint32_t)a, (uint32_t)(a >> 32), (uint32_t)b, (uint32_t)(b >> 32));
}
__device__ __forceinline__ uint2 ld_rlx2(const uint2* p) { unsigned long long a; asm volatile("ld.relaxed.gpu.global.b64 %0, [%1];" : "=l"(a) : "l"(p) : "memory"); return make_uint2((uint32_t)a, (uint32_t)(a >> 32)); }
__device__ __forceinline__ void st_rlx4(uint4* p, uint32_t x, uint32_t y, uint32_t z, uint32_t w) {
  asm volatile("st.relaxed.gpu.global.v2.b64 [%0], {%1,%2};" :: "l"(p), "l"((unsigned long long)x | ((unsigned long long)y << 32)), "l"((unsigned long long)z | ((unsigned long long)w << 32)) : "memory");
}
__device__ __forceinline__ void st_rlx2(uint2* p, uint32_t x, uint32_t y) { asm volatile("st.relaxed.gpu.global.b64 [%0], %1;" :: "l"(p), "l"((unsigned long long)x | ((unsigned long long)y << 32)) : "memory"); }
__device__ __forceinline__ void st_rlx1(uint32_t* p, uint32_t v) { asm volatile("st.relaxed.gpu.global.u32 [%0], %1;" :: "l"(p), "r"(v) : "memory"); }
__device__ __forceinline__ uint32_t ld_rlx1(const uint32_t* p) { uint32_t v; asm volatile("ld.relaxed.gpu.global.u32 %0, [%1];" : "=r"(v) : "l"(p) : "memory"); return v; }
__device__ __forceinline__ void st_release(uint32_t* p, uint32_t v) { asm volatile("st.release.gpu.global.u32 [%0], %1;" :: "l"(p), "r"(v) : "memory"); }
__device__ __forceinline__ uint32_t ld_acquire(const uint32_t* p) { uint32_t v; asm volatile("ld.acquire.gpu.global.u32 %0, [%1];" : "=r"(v) : "l"(p) : "memory"); return v; }
__device__ __forceinline__ void prefetch_map(const CUtensorMap* m) { asm volatile("prefetch.tensormap [%0];" :: "l"(m) : "memory"); }
__device__ __forceinline__ float rcp(float x) { float r; asm("rcp.approx.ftz.f32 %0, %1;" : "=f"(r) : "f"(x)); return r; }
__device__ __forceinline__ float ex2(float x) { float r; asm("ex2.approx.ftz.f32 %0, %1;" : "=f"(r) : "f"(x)); return r; }
__device__ __forceinline__ float tanh_fast(float x) { float r; asm("tanh.approx.f32 %0, %1;" : "=f"(r) : "f"(x)); return r; }
#define SPIN_GUARD(n) if (++(n) > (1u << 24)) bail()

__device__ __forceinline__ void wgmma_n128(float (&d)[64], uint64_t da, uint64_t db) {
  asm volatile("wgmma.mma_async.sync.aligned.m64n128k16.f32.bf16.bf16 "
    "{%0, %1, %2, %3, %4, %5, %6, %7, %8, %9, %10, %11, %12, %13, %14, %15, %16, %17, %18, %19, %20, %21, %22, %23, %24, %25, %26, %27, %28, %29, %30, %31, %32, %33, %34, %35, %36, %37, %38, %39, %40, %41, %42, %43, %44, %45, %46, %47, %48, %49, %50, %51, %52, %53, %54, %55, %56, %57, %58, %59, %60, %61, %62, %63}, "
    "%64, %65, 1, 1, 1, 0, 1;\n"
    : "+f"(d[0]), "+f"(d[1]), "+f"(d[2]), "+f"(d[3]), "+f"(d[4]), "+f"(d[5]), "+f"(d[6]), "+f"(d[7]), "+f"(d[8]), "+f"(d[9]), "+f"(d[10]), "+f"(d[11]), "+f"(d[12]), "+f"(d[13]), "+f"(d[14]), "+f"(d[15]), "+f"(d[16]), "+f"(d[17]), "+f"(d[18]), "+f"(d[19]), "+f"(d[20]), "+f"(d[21]), "+f"(d[22]), "+f"(d[23]), "+f"(d[24]), "+f"(d[25]), "+f"(d[26]), "+f"(d[27]), "+f"(d[28]), "+f"(d[29]), "+f"(d[30]), "+f"(d[31]), "+f"(d[32]), "+f"(d[33]), "+f"(d[34]), "+f"(d[35]), "+f"(d[36]), "+f"(d[37]), "+f"(d[38]), "+f"(d[39]), "+f"(d[40]), "+f"(d[41]), "+f"(d[42]), "+f"(d[43]), "+f"(d[44]), "+f"(d[45]), "+f"(d[46]), "+f"(d[47]), "+f"(d[48]), "+f"(d[49]), "+f"(d[50]), "+f"(d[51]), "+f"(d[52]), "+f"(d[53]), "+f"(d[54]), "+f"(d[55]), "+f"(d[56]), "+f"(d[57]), "+f"(d[58]), "+f"(d[59]), "+f"(d[60]), "+f"(d[61]), "+f"(d[62]), "+f"(d[63])
    : "l"(da), "l"(db));
}
__device__ __forceinline__ void wgmma_n128_first(float (&d)[64], uint64_t da, uint64_t db) {
  asm volatile("wgmma.mma_async.sync.aligned.m64n128k16.f32.bf16.bf16 "
    "{%0, %1, %2, %3, %4, %5, %6, %7, %8, %9, %10, %11, %12, %13, %14, %15, %16, %17, %18, %19, %20, %21, %22, %23, %24, %25, %26, %27, %28, %29, %30, %31, %32, %33, %34, %35, %36, %37, %38, %39, %40, %41, %42, %43, %44, %45, %46, %47, %48, %49, %50, %51, %52, %53, %54, %55, %56, %57, %58, %59, %60, %61, %62, %63}, "
    "%64, %65, 0, 1, 1, 0, 1;\n"
    : "=f"(d[0]), "=f"(d[1]), "=f"(d[2]), "=f"(d[3]), "=f"(d[4]), "=f"(d[5]), "=f"(d[6]), "=f"(d[7]), "=f"(d[8]), "=f"(d[9]), "=f"(d[10]), "=f"(d[11]), "=f"(d[12]), "=f"(d[13]), "=f"(d[14]), "=f"(d[15]), "=f"(d[16]), "=f"(d[17]), "=f"(d[18]), "=f"(d[19]), "=f"(d[20]), "=f"(d[21]), "=f"(d[22]), "=f"(d[23]), "=f"(d[24]), "=f"(d[25]), "=f"(d[26]), "=f"(d[27]), "=f"(d[28]), "=f"(d[29]), "=f"(d[30]), "=f"(d[31]), "=f"(d[32]), "=f"(d[33]), "=f"(d[34]), "=f"(d[35]), "=f"(d[36]), "=f"(d[37]), "=f"(d[38]), "=f"(d[39]), "=f"(d[40]), "=f"(d[41]), "=f"(d[42]), "=f"(d[43]), "=f"(d[44]), "=f"(d[45]), "=f"(d[46]), "=f"(d[47]), "=f"(d[48]), "=f"(d[49]), "=f"(d[50]), "=f"(d[51]), "=f"(d[52]), "=f"(d[53]), "=f"(d[54]), "=f"(d[55]), "=f"(d[56]), "=f"(d[57]), "=f"(d[58]), "=f"(d[59]), "=f"(d[60]), "=f"(d[61]), "=f"(d[62]), "=f"(d[63])
    : "l"(da), "l"(db));
}
__device__ __forceinline__ void wgmma_n256(float (&d)[128], uint64_t da, uint64_t db) {
  asm volatile("wgmma.mma_async.sync.aligned.m64n256k16.f32.bf16.bf16 "
    "{%0, %1, %2, %3, %4, %5, %6, %7, %8, %9, %10, %11, %12, %13, %14, %15, %16, %17, %18, %19, %20, %21, %22, %23, %24, %25, %26, %27, %28, %29, %30, %31, %32, %33, %34, %35, %36, %37, %38, %39, %40, %41, %42, %43, %44, %45, %46, %47, %48, %49, %50, %51, %52, %53, %54, %55, %56, %57, %58, %59, %60, %61, %62, %63, %64, %65, %66, %67, %68, %69, %70, %71, %72, %73, %74, %75, %76, %77, %78, %79, %80, %81, %82, %83, %84, %85, %86, %87, %88, %89, %90, %91, %92, %93, %94, %95, %96, %97, %98, %99, %100, %101, %102, %103, %104, %105, %106, %107, %108, %109, %110, %111, %112, %113, %114, %115, %116, %117, %118, %119, %120, %121, %122, %123, %124, %125, %126, %127}, "
    "%128, %129, 1, 1, 1, 0, 1;\n"
    : "+f"(d[0]), "+f"(d[1]), "+f"(d[2]), "+f"(d[3]), "+f"(d[4]), "+f"(d[5]), "+f"(d[6]), "+f"(d[7]), "+f"(d[8]), "+f"(d[9]), "+f"(d[10]), "+f"(d[11]), "+f"(d[12]), "+f"(d[13]), "+f"(d[14]), "+f"(d[15]), "+f"(d[16]), "+f"(d[17]), "+f"(d[18]), "+f"(d[19]), "+f"(d[20]), "+f"(d[21]), "+f"(d[22]), "+f"(d[23]), "+f"(d[24]), "+f"(d[25]), "+f"(d[26]), "+f"(d[27]), "+f"(d[28]), "+f"(d[29]), "+f"(d[30]), "+f"(d[31]), "+f"(d[32]), "+f"(d[33]), "+f"(d[34]), "+f"(d[35]), "+f"(d[36]), "+f"(d[37]), "+f"(d[38]), "+f"(d[39]), "+f"(d[40]), "+f"(d[41]), "+f"(d[42]), "+f"(d[43]), "+f"(d[44]), "+f"(d[45]), "+f"(d[46]), "+f"(d[47]), "+f"(d[48]), "+f"(d[49]), "+f"(d[50]), "+f"(d[51]), "+f"(d[52]), "+f"(d[53]), "+f"(d[54]), "+f"(d[55]), "+f"(d[56]), "+f"(d[57]), "+f"(d[58]), "+f"(d[59]), "+f"(d[60]), "+f"(d[61]), "+f"(d[62]), "+f"(d[63]), "+f"(d[64]), "+f"(d[65]), "+f"(d[66]), "+f"(d[67]), "+f"(d[68]), "+f"(d[69]), "+f"(d[70]), "+f"(d[71]), "+f"(d[72]), "+f"(d[73]), "+f"(d[74]), "+f"(d[75]), "+f"(d[76]), "+f"(d[77]), "+f"(d[78]), "+f"(d[79]), "+f"(d[80]), "+f"(d[81]), "+f"(d[82]), "+f"(d[83]), "+f"(d[84]), "+f"(d[85]), "+f"(d[86]), "+f"(d[87]), "+f"(d[88]), "+f"(d[89]), "+f"(d[90]), "+f"(d[91]), "+f"(d[92]), "+f"(d[93]), "+f"(d[94]), "+f"(d[95]), "+f"(d[96]), "+f"(d[97]), "+f"(d[98]), "+f"(d[99]), "+f"(d[100]), "+f"(d[101]), "+f"(d[102]), "+f"(d[103]), "+f"(d[104]), "+f"(d[105]), "+f"(d[106]), "+f"(d[107]), "+f"(d[108]), "+f"(d[109]), "+f"(d[110]), "+f"(d[111]), "+f"(d[112]), "+f"(d[113]), "+f"(d[114]), "+f"(d[115]), "+f"(d[116]), "+f"(d[117]), "+f"(d[118]), "+f"(d[119]), "+f"(d[120]), "+f"(d[121]), "+f"(d[122]), "+f"(d[123]), "+f"(d[124]), "+f"(d[125]), "+f"(d[126]), "+f"(d[127])
    : "l"(da), "l"(db));
}
__device__ __forceinline__ void wgmma_n256_first(float (&d)[128], uint64_t da, uint64_t db) {
  asm volatile("wgmma.mma_async.sync.aligned.m64n256k16.f32.bf16.bf16 "
    "{%0, %1, %2, %3, %4, %5, %6, %7, %8, %9, %10, %11, %12, %13, %14, %15, %16, %17, %18, %19, %20, %21, %22, %23, %24, %25, %26, %27, %28, %29, %30, %31, %32, %33, %34, %35, %36, %37, %38, %39, %40, %41, %42, %43, %44, %45, %46, %47, %48, %49, %50, %51, %52, %53, %54, %55, %56, %57, %58, %59, %60, %61, %62, %63, %64, %65, %66, %67, %68, %69, %70, %71, %72, %73, %74, %75, %76, %77, %78, %79, %80, %81, %82, %83, %84, %85, %86, %87, %88, %89, %90, %91, %92, %93, %94, %95, %96, %97, %98, %99, %100, %101, %102, %103, %104, %105, %106, %107, %108, %109, %110, %111, %112, %113, %114, %115, %116, %117, %118, %119, %120, %121, %122, %123, %124, %125, %126, %127}, "
    "%128, %129, 0, 1, 1, 0, 1;\n"
    : "=f"(d[0]), "=f"(d[1]), "=f"(d[2]), "=f"(d[3]), "=f"(d[4]), "=f"(d[5]), "=f"(d[6]), "=f"(d[7]), "=f"(d[8]), "=f"(d[9]), "=f"(d[10]), "=f"(d[11]), "=f"(d[12]), "=f"(d[13]), "=f"(d[14]), "=f"(d[15]), "=f"(d[16]), "=f"(d[17]), "=f"(d[18]), "=f"(d[19]), "=f"(d[20]), "=f"(d[21]), "=f"(d[22]), "=f"(d[23]), "=f"(d[24]), "=f"(d[25]), "=f"(d[26]), "=f"(d[27]), "=f"(d[28]), "=f"(d[29]), "=f"(d[30]), "=f"(d[31]), "=f"(d[32]), "=f"(d[33]), "=f"(d[34]), "=f"(d[35]), "=f"(d[36]), "=f"(d[37]), "=f"(d[38]), "=f"(d[39]), "=f"(d[40]), "=f"(d[41]), "=f"(d[42]), "=f"(d[43]), "=f"(d[44]), "=f"(d[45]), "=f"(d[46]), "=f"(d[47]), "=f"(d[48]), "=f"(d[49]), "=f"(d[50]), "=f"(d[51]), "=f"(d[52]), "=f"(d[53]), "=f"(d[54]), "=f"(d[55]), "=f"(d[56]), "=f"(d[57]), "=f"(d[58]), "=f"(d[59]), "=f"(d[60]), "=f"(d[61]), "=f"(d[62]), "=f"(d[63]), "=f"(d[64]), "=f"(d[65]), "=f"(d[66]), "=f"(d[67]), "=f"(d[68]), "=f"(d[69]), "=f"(d[70]), "=f"(d[71]), "=f"(d[72]), "=f"(d[73]), "=f"(d[74]), "=f"(d[75]), "=f"(d[76]), "=f"(d[77]), "=f"(d[78]), "=f"(d[79]), "=f"(d[80]), "=f"(d[81]), "=f"(d[82]), "=f"(d[83]), "=f"(d[84]), "=f"(d[85]), "=f"(d[86]), "=f"(d[87]), "=f"(d[88]), "=f"(d[89]), "=f"(d[90]), "=f"(d[91]), "=f"(d[92]), "=f"(d[93]), "=f"(d[94]), "=f"(d[95]), "=f"(d[96]), "=f"(d[97]), "=f"(d[98]), "=f"(d[99]), "=f"(d[100]), "=f"(d[101]), "=f"(d[102]), "=f"(d[103]), "=f"(d[104]), "=f"(d[105]), "=f"(d[106]), "=f"(d[107]), "=f"(d[108]), "=f"(d[109]), "=f"(d[110]), "=f"(d[111]), "=f"(d[112]), "=f"(d[113]), "=f"(d[114]), "=f"(d[115]), "=f"(d[116]), "=f"(d[117]), "=f"(d[118]), "=f"(d[119]), "=f"(d[120]), "=f"(d[121]), "=f"(d[122]), "=f"(d[123]), "=f"(d[124]), "=f"(d[125]), "=f"(d[126]), "=f"(d[127])
    : "l"(da), "l"(db));
}

template <int N> struct WG;
#define DEF_WG(N) template <> struct WG<N> { \
  static __device__ __forceinline__ void mma(float (&d)[N / 2], uint64_t a, uint64_t b) { wgmma_n##N(d, a, b); } \
  static __device__ __forceinline__ void first(float (&d)[N / 2], uint64_t a, uint64_t b) { wgmma_n##N##_first(d, a, b); } };
DEF_WG(128) DEF_WG(256)

constexpr uint64_t DESC_A = (1ull << 62) | ((uint64_t)(1024 >> 4) << 32) | (1ull << 16);
constexpr uint64_t DESC_B = (1ull << 62) | ((uint64_t)(1024 >> 4) << 32) | ((uint64_t)(8192 >> 4) << 16);

struct Ring { int s; uint32_t ph; int wrap; };
template <int NS> __device__ __forceinline__ void ring_next(Ring& r) { r.s = (r.s + 1 == NS) ? 0 : r.s + 1; if (r.s == r.wrap) r.ph ^= 1; }

__device__ __forceinline__ int own_order(int it, int j) {
  return it < 2 ? 2 * j + it : it < 4 ? 2 * (j ^ 1) + it - 2 : ((j >> 1) * 4 + 2 * it - (it < 10 ? 4 : 15)) & 15;
}

template <int V> struct IC { static constexpr int v = V; };
template <int I, int E, class F> __device__ __forceinline__ void static_for(F&& f) { if constexpr (I < E) { f(IC<I>{}); static_for<I + 1, E>(f); } }

template <int N, int NS, int PRE, int LAG, class Pre, class Mid, class Last>
__device__ __forceinline__ void mainloop(float (&acc)[N / 2], int nkb, bool own, Ring& r, uint32_t sb, int wg, int lane, uint32_t rel_base, Pre pre, Mid mid, Last last, int lag_par = 0) {
  constexpr int SLOT = RING / NS;
  const uint32_t full = sb + MISC + (NS == 4 ? B_FULL4 : B_FULL6);
  const uint32_t rel = rel_base + (NS == 4 ? B_EMPTY4 : B_EMPTY6);
  const uint32_t s0 = (sb & 0x3FFFF) >> 4, a0 = s0 + wg * (HALF >> 4);
  int ps;
  auto issue = [&](int it, bool first) {
    const uint64_t da = DESC_A | (a0 + ((own && it < 2) ? (STG + it * BLK) >> 4 : r.s * (SLOT >> 4))), db = DESC_B | (s0 + r.s * (SLOT >> 4) + (BLK >> 4));
    mbar_wait(full + r.s * 8, r.ph);
    wg_arrive();
    if (first) WG<N>::first(acc, da, db); else WG<N>::mma(acc, da, db);
#pragma unroll
    for (int k = 1; k < 4; k++) WG<N>::mma(acc, da + k * 2, db + k * 128);
    wg_commit();
  };
  auto retire = [&](int it) {
    wg_wait<1>();
    if (lane < 2) mbar_arrive_cl(rel + ps * 8);
    ps = r.s;
    ring_next<NS>(r);
  };
  issue(0, true);
  ps = r.s;
  ring_next<NS>(r);
  static_for<1, PRE + 1>([&](auto ic) { issue(ic.v, false); pre(ic); retire(ic.v); });
#pragma unroll 1
  for (int it = PRE + 1; it < nkb; it++) {
    if (LAG && it == nkb - LAG && wg == 1) mbar_wait(sb + MISC + B_LAG, lag_par);
    issue(it, false); mid(it); retire(it);
  }
  if (LAG && wg == 0 && lane == 0) mbar_arrive(sb + MISC + B_LAG);
  last();
  wg_wait<0>();
  if (lane < 2) mbar_arrive_cl(rel + ps * 8);
}

__device__ __forceinline__ uint32_t tag_of(uint32_t ep) { return (ep & 127u) + 1u; }
__device__ __forceinline__ void ln_publish(const float (&v)[64], uint2* st, int j, int row0, int lane, uint32_t ep) {
  float s0 = 0, s1 = 0, s2 = 0, s3 = 0, q0 = 0, q1 = 0, q2 = 0, q3 = 0;
#pragma unroll
  for (int i = 0; i < 16; i++) {
    s0 += v[4 * i]; s1 += v[4 * i + 1]; s2 += v[4 * i + 2]; s3 += v[4 * i + 3];
    q0 = fmaf(v[4 * i], v[4 * i], q0); q1 = fmaf(v[4 * i + 1], v[4 * i + 1], q1); q2 = fmaf(v[4 * i + 2], v[4 * i + 2], q2); q3 = fmaf(v[4 * i + 3], v[4 * i + 3], q3);
  }
  s0 += s1; s2 += s3; q0 += q1; q2 += q3;
  const bool odd = lane & 1;
  float s = (odd ? s2 : s0) + __shfl_xor_sync(~0u, odd ? s0 : s2, 1), q = (odd ? q2 : q0) + __shfl_xor_sync(~0u, odd ? q0 : q2, 1);
  s += __shfl_xor_sync(~0u, s, 2); q += __shfl_xor_sync(~0u, q, 2);
  if ((lane & 3) < 2) st_rlx2(st + j * 128 + row0 + (lane & 1) * 8, __float_as_uint(s), (__float_as_uint(fmaf(s * (-1.f / 128), s, q)) & ~255u) | tag_of(ep));
}
__device__ __forceinline__ void ln_gather(const uint2* st, int row0, int lane, uint32_t ep, float& n0, float& r0, float& n1, float& r1, bool rnd) {
  const uint2* p = st + (lane & 2) * 256 + row0 + (lane & 1) * 8;
  const uint32_t tag = tag_of(ep);
  uint2 a, b, c, d; uint32_t n = 0;
  while (true) {
    a = ld_rlx2(p); b = ld_rlx2(p + 128); c = ld_rlx2(p + 256); d = ld_rlx2(p + 384);
    if ((((a.y ^ tag) | (b.y ^ tag) | (c.y ^ tag) | (d.y ^ tag)) & 255u) == 0) break;
    SPIN_GUARD(n);
  }
  __syncwarp();
  const uint32_t fix = tag ^ 128u;
  float s = (__uint_as_float(a.x) + __uint_as_float(b.x)) + (__uint_as_float(c.x) + __uint_as_float(d.x));
  float q = (__uint_as_float(a.y ^ fix) + __uint_as_float(b.y ^ fix)) + (__uint_as_float(c.y ^ fix) + __uint_as_float(d.y ^ fix));
  q = fmaf(fmaf(__uint_as_float(a.x), __uint_as_float(a.x), __uint_as_float(b.x) * __uint_as_float(b.x)) +
           fmaf(__uint_as_float(c.x), __uint_as_float(c.x), __uint_as_float(d.x) * __uint_as_float(d.x)), 1.f / 128, q);
  s += __shfl_xor_sync(~0u, s, 2); q += __shfl_xor_sync(~0u, q, 2);
  s *= 1.f / 1024;
  const float var = fmaxf(fmaf(-s, s, q * (1.f / 1024)), 0.f);
  float r;
  if (rnd) {
    float sd; asm("sqrt.approx.f32 %0, %1;" : "=f"(sd) : "f"(bf_round(bf_round(var) + 1e-5f)));
    r = rcp(bf_round(sd)); s = bf_round(s);
  } else r = rsqrtf(var + 1e-5f);
  const float nn = -s * r;
  const float ro = __shfl_xor_sync(~0u, r, 1), no = __shfl_xor_sync(~0u, nn, 1);
  const bool odd = lane & 1;
  r0 = odd ? ro : r; n0 = odd ? no : nn; r1 = odd ? r : ro; n1 = odd ? nn : no;
}
__device__ __forceinline__ void load_vec(uint32_t* w, uint32_t sb, int sec, int b, int lane) {
#pragma unroll
  for (int q = 0; q < 2; q++) { uint4 t = lds128(sb + MISC + MODV + sec * 256 + (lane & 3) * 64 + b * 32 + q * 16); w[4 * q] = t.x; w[4 * q + 1] = t.y; w[4 * q + 2] = t.z; w[4 * q + 3] = t.w; }
}
__device__ __forceinline__ void stage_done(uint32_t sb, int wg, int b, int lane) {
  fence_async_smem();
  __syncwarp();
  if (lane == 0) mbar_arrive(sb + MISC + B_RDY + b * 8);
}
__device__ __forceinline__ uint32_t hfma2(uint32_t a, uint32_t b, uint32_t c) { uint32_t r; asm("fma.rn.bf16x2 %0, %1, %2, %3;" : "=r"(r) : "r"(a), "r"(b), "r"(c)); return r; }
__device__ __forceinline__ void ln_apply(const float (&v)[64], const uint2* st, int row0, uint32_t ep, uint32_t sb, int sec_shift, int sec_scale, uint32_t stg_row, int wg, int lane) {
  uint32_t sc[16], sh[16];
#pragma unroll
  for (int b = 0; b < 2; b++) { load_vec(sc + 8 * b, sb, sec_scale, b, lane); load_vec(sh + 8 * b, sb, sec_shift, b, lane); }
  float n0, r0, n1, r1;
  ln_gather(st, row0, lane, ep, n0, r0, n1, r1, sec_shift == 0);
#pragma unroll
  for (int i = 0; i < 16; i += 2) {
    if (i == 8) { const float z = lds32f(sb + MISC + ZERO); n0 += z; n1 += z; }
    uint32_t w[4];
#pragma unroll
    for (int u = 0; u < 2; u++) {
      int q = i + u;
      w[2 * u] = hfma2(pack2(fmaf(v[4 * q], r0, n0), fmaf(v[4 * q + 1], r0, n0)), sc[q], sh[q]);
      w[2 * u + 1] = hfma2(pack2(fmaf(v[4 * q + 2], r1, n1), fmaf(v[4 * q + 3], r1, n1)), sc[q], sh[q]);
    }
    stsm4(stg_row + (i >> 3) * BLK + ((((i & 7) + (lane >> 4)) ^ (lane & 7)) << 4), w[0], w[1], w[2], w[3]);
    if ((i & 7) == 6) { stage_done(sb, wg, i >> 3, lane); }
  }
}
__device__ __forceinline__ uint32_t hmul2(uint32_t a, uint32_t b) { uint32_t r; asm("mul.rn.bf16x2 %0, %1, %2;" : "=r"(r) : "r"(a), "r"(b)); return r; }
__device__ __forceinline__ uint32_t silu_mul2(uint32_t g, uint32_t u) {
  const uint32_t h = hmul2(g, 0x3f003f00u);
  const float h0 = bf_lo(h), h1 = bf_hi(h);
  return hmul2(pack2(fmaf(h0, tanh_fast(h0), h0), fmaf(h1, tanh_fast(h1), h1)), u);
}

__device__ __forceinline__ void gemv_fma(float (&a)[8], uint4 w, float s) {
  a[0] = fmaf(bf_lo(w.x), s, a[0]); a[1] = fmaf(bf_hi(w.x), s, a[1]); a[2] = fmaf(bf_lo(w.y), s, a[2]); a[3] = fmaf(bf_hi(w.y), s, a[3]);
  a[4] = fmaf(bf_lo(w.z), s, a[4]); a[5] = fmaf(bf_hi(w.z), s, a[5]); a[6] = fmaf(bf_lo(w.w), s, a[6]); a[7] = fmaf(bf_hi(w.w), s, a[7]);
}
__device__ __forceinline__ float silu_c(float v) { return bf_round(__fdividef(v, 1.f + __expf(-v))); }
__device__ __forceinline__ float mod_gather(const uint32_t* p, uint32_t ep) {
  const uint32_t tag = tag_of(ep), fix = tag ^ 128u;
  uint32_t a, b, c, d, n = 0;
  while (true) {
    a = ld_rlx1(p); b = ld_rlx1(p + 128); c = ld_rlx1(p + 256); d = ld_rlx1(p + 384);
    if ((((a ^ tag) | (b ^ tag) | (c ^ tag) | (d ^ tag)) & 255u) == 0) break;
    SPIN_GUARD(n);
  }
  return (__uint_as_float(a ^ fix) + __uint_as_float(b ^ fix)) + (__uint_as_float(c ^ fix) + __uint_as_float(d ^ fix));
}
__device__ __forceinline__ void mod_store(uint32_t sb, int sec, int col, float v) {
  v = bf_round(v);
  if (sec == 1) v += 1.f;
  sts16(sb + MISC + MODV + sec * 256 + (((col >> 1) & 3) * 16 + (col >> 3)) * 4 + (col & 1) * 2, __float2bfloat16_rn(v));
}

__global__ void __cluster_dims__(2, 1, 1) __launch_bounds__(384, 1)
fused_kernel(const bf16* __restrict__ cvec, const bf16* __restrict__ wmod, Scratch* gs, int by_sm, const __grid_constant__ Maps maps) {
  extern __shared__ __align__(1024) uint8_t smem_raw[];
  const uint32_t sb = smem_u32(smem_raw);
  const int warp = __shfl_sync(~0u, threadIdx.x >> 5, 0), lane = threadIdx.x & 31;
  const int rank = blockIdx.x & 1;
  uint32_t sm; asm volatile("mov.u32 %0, %%smid;" : "=r"(sm));
  const int t = sm >> 1, v = t < 32 ? t : t < 60 ? t + 1 + (((t - 32) * 37) >> 8) : (t - 58) * 8;
  const int gr = 0x71546320u >> ((v & 7) * 4);
  const int cid = !by_sm ? (blockIdx.x >> 1) - 2 : (t & ~1) == 60 ? t - 62 : (gr & 4) * 8 + (v >> 3) * 4 + (gr & 3);
  const bool extra = cid < 0;
  const int bid = cid * 2 + rank;
  const int m = cid >> 2, j = (cid & 3) * 2 + rank;
  const uint32_t bar = sb + MISC;

  if (warp >= 8) {
    asm volatile("setmaxnreg.dec.sync.aligned.u32 40;");
    if (extra) {
      if (warp == 8) {
        if (lane == 0) { for (int s = 0; s < 6; s++) { mbar_init(bar + B_FULL6 + s * 8, 1); mbar_init(bar + B_EMPTY6 + s * 8, 8); } fence_async_smem(); }
        __syncwarp();
        asm volatile("bar.arrive 2, 288;" ::: "memory");
        __nanosleep(XSLEEP);
#pragma unroll 1
        for (int it = 0, s = 0, par = 1; it < 64; it++) {
          mbar_wait(bar + B_EMPTY6 + s * 8, par);
          expect_e(bar + B_FULL6 + s * 8, 32768); tma_3d_e(sb + s * 32768, &maps.wmod, bar + B_FULL6 + s * 8, 0, (it & 15) * 64, 12 + (it >> 4) * 4 + bid);
          if (++s == 6) { s = 0; par ^= 1; }
        }
      }
    } else if (warp < 10) {
      uint32_t s6 = 0, p6 = 1;
      auto next6 = [&]() { if (++s6 == 6) { s6 = 0; p6 ^= 1; } };
      auto drained4 = [&](int q, int late) { if (q < 5) mbar_wait(bar + B_EMPTY4 + (((late ? 0x10332 : 0x32110) >> (4 * q)) & 3) * 8, 1); };
      auto drained6 = [&](int q) { if (q < 3) mbar_wait(bar + B_EMPTY6 + ((0x154 >> (4 * q)) & 7) * 8, q >> 1); };
      auto skip6 = [&]() { mbar_wait(bar + B_EMPTY6 + s6 * 8, p6); expect_e(bar + B_FULL6 + s6 * 8, 0); next6(); };
      if (warp == 8) {
        const uint32_t t_start = clock();
        if (lane == 0) {
          if (sb & 1023) bail();
          for (int b = 0; b < 2; b++) mbar_init(bar + B_X + b * 8, 1);
          for (int s = 0; s < 4; s++) { mbar_init(bar + B_FULL4 + s * 8, 2); mbar_init(bar + B_EMPTY4 + s * 8, 16); }
          for (int s = 0; s < 6; s++) { mbar_init(bar + B_FULL6 + s * 8, 2); mbar_init(bar + B_EMPTY6 + s * 8, 16); }
          for (int b = 0; b < 2; b++) { mbar_init(bar + B_RDY + b * 8, 8); mbar_init(bar + B_FREE + b * 8, 1); mbar_init(bar + B_HH + b * 8, 1); }
          mbar_init(bar + B_MOD, 1); mbar_init(bar + B_LAG, 4); mbar_init(bar + B_HALO, 2); mbar_init(bar + B_ALL, 1); mbar_init(bar + B_HH2, 1);
          asm volatile("st.shared.u32 [%0], 0;" :: "r"(bar + ZERO) : "memory");
          asm volatile("fence.mbarrier_init.release.cluster;" ::: "memory");
          fence_async_smem();
        }
        __syncwarp();
        cl_arrive_relaxed();
        auto wide = [&](int s, int par, const CUtensorMap* m0, int a0, const CUtensorMap* m1, int a1, int kb, bool spaced) {
          const uint32_t full = bar + B_FULL4 + s * 8, d = sb + s * 49152 + BLK;
          mbar_wait(full + 32, par);
          const uint32_t t0 = clock();
          tma_3d_e(d, m0, full, 0, kb * 64, a0);
          if (spaced) while ((uint32_t)clock() - t0 < GAP) {}
          tma_3d_e(d + BLK, m1, full, 0, kb * 64, a1);
          expect_e(full, 2 * BLK);
          if (spaced) while ((uint32_t)clock() - t0 < 2 * GAP) {}
        };
        while ((uint32_t)clock() - t_start < XDELAY) {}
        for (int b = 0; b < 2; b++) { expect_e(bar + B_X + b * 8, BLK); tma_3d_e(sb + STG + b * BLK, &maps.x, bar + B_X + b * 8, j * 128 + b * 64, m * 64, 0); }
        mbar_wait(bar + B_X + 8, 0);
#pragma unroll 1
        for (int ph = 0; ph < 2; ph++) {
          const CUtensorMap* const m0 = ph ? &maps.w1 : &maps.wqkv;
#pragma unroll 1
          for (int it = 0; it < (ph ? 48 : 16); it++) {
            const int a = (ph ? it & 48 : 16) + 2 * j;
            if (ph) drained6(it);
            wide((it + 2 * ph) & 3, ~(it >> 2) & 1, m0, a, m0 + ph, ph ? a : a + 16, it < 16 ? own_order(it, j) : it & 15, it < 4);
            if (it >= 44) {
              if (it == 44) { mbar_wait(bar + B_FREE, 0); mbar_wait(bar + B_FREE + 8, 0); expect_e(bar + B_X, 2 * BLK); }
              bulk_ld_e(sb + STG + (it - 44) * HALF, gs->x1 + bid * 2048 + (it - 44) * 512, HALF, bar + B_X);
            }
          }
#pragma unroll 1
          for (int it = 0; it < 16; it++) {
            const uint32_t full = bar + B_FULL6 + s6 * 8, d = sb + s6 * 32768 + BLK;
            drained4(it, ph);
            mbar_wait(full + 48, p6);
            tma_3d_e(d, ph ? &maps.w1s : &maps.wqkv, full, 0, it * 64, ph ? 48 + j : 2 * j);
            if (ph) tma_3d_e(d + HALF, &maps.w3s, full, 0, it * 64, 48 + j);
            expect_e(full, BLK);
            next6();
          }
          const CUtensorMap* const m2 = ph ? &maps.w2 : &maps.wo;
#pragma unroll 1
          for (int it = 0; it < (ph ? 56 : 16); it++) {
            const uint32_t full = bar + B_FULL6 + s6 * 8;
            const int kb = ph ? it : own_order(it, j);
            mbar_wait(full + 48, p6);
            tma_3d_e(sb + s6 * 32768 + BLK, m2, full, 0, kb * 64, 2 * j);
            expect_e(full, BLK);
            next6();
          }
          if (!ph) skip6();
        }
      } else {
        if (lane < 9) prefetch_map(&maps.x + lane);
        const uint32_t ep = gs->epoch[blockIdx.x] + 1;
        cl_arrive_relaxed(); cl_wait();
        auto plain = [&](uint32_t full, uint32_t empty, int par, uint32_t slot, const uint4* blk) {
          mbar_wait(empty, par);
          bulk_ld_mc_e(slot + rank * HALF, blk + rank * 512, HALF, full);
          expect_e(full, BLK);
        };
        auto plain6 = [&](const uint4* blk) { plain(bar + B_FULL6 + s6 * 8, bar + B_EMPTY6 + s6 * 8, p6, sb + s6 * 32768, blk); next6(); };
        uint32_t ready = 0;
        auto poll = [&](int e) { ready = __ballot_sync(~0u, ld_acquire(gs->flag + (m * 128 + e * 16 + (lane & 14)) * FS) == ep); };
        auto need = [&](int e, uint32_t mask) {
          if ((ready & mask) != mask) {
            uint32_t n = 0;
            do { poll(e); SPIN_GUARD(n); } while ((ready & mask) != mask);
            fence_async_global();
          }
        };
        auto fresh = [&](int e, int it, uint32_t full, uint32_t empty, int par, uint32_t slot, uint4* src) {
          mbar_wait(empty, par);
          expect_e(full, it < 2 ? 0 : BLK);
          if (it >= 4) {
            const int kb = own_order(it, j);
            if (it < 10) need(e, 1u << kb); else if (it == 10) mbar_wait(bar + B_ALL, e & 1);
            bulk_ld_mc_e(slot + rank * HALF, src + kb * 1024 + rank * 512, HALF, full);
          } else if (it >= 2) {
            const int b = it > 2;
            const uint32_t to_peer = mapa(sb, rank ^ 1) - sb;
            const bool push = b && e != 1;
            mbar_wait(bar + (push ? B_RDY : B_FREE) + b * 8, e & 1);
            if (push) bulk_push_e(slot + to_peer, sb + STG + BLK, BLK, full + to_peer);
            else { fence_async_global(); bulk_ld_e(slot + to_peer, src + (2 * j + b) * 1024, BLK, full + to_peer); }
          } else ready = 0;
        };
        uint4* const h = gs->h + m * 16384;
#pragma unroll 1
        for (int e = 0; e < 3; e++) {
#pragma unroll 1
          for (int it = 0; it < 16; it++) {
            const int s = e == 1 ? s6 : (it + e) & 3;
            const uint32_t full = bar + (e == 1 ? B_FULL6 : B_FULL4) + s * 8;
            if (e == 2) drained6(it);
            fresh(e, it, full, full + (e == 1 ? 48 : 32), e == 1 ? p6 : ~(it >> 2) & 1, sb + s * (e == 1 ? 32768 : 49152), e == 1 ? gs->o + m * 16384 : h);
            if (e == 1) next6();
          }
          if (e == 1) { skip6(); continue; }
#pragma unroll 1
          for (int it = 16; it < 16 + 16 * e; it++) {
            const int s = (it + 2) & 3;
            const uint32_t full = bar + B_FULL4 + s * 8;
            plain(full, full + 32, ~(it >> 2) & 1, sb + s * 49152, h + (it & 15) * 1024);
          }
#pragma unroll 1
          for (int it = 0; it < 16; it++) { drained4(it, e); plain6(h + it * 1024); }
        }
#pragma unroll 1
        for (int it = 0; it < 56; it++) {
          if (it == 0 || it == 32 || it == 48) mbar_wait(bar + (it == 48 ? B_HH2 : B_HH + (it >> 2)), 0);
          plain6(gs->hh + m * 57344 + it * 1024);
        }
      }
    } else {
      const int b = warp - 10;
      const uint32_t ep = gs->epoch[blockIdx.x] + 1;
      const uint32_t stg = sb + STG + b * BLK;
      cl_arrive_relaxed(); cl_wait();
      auto all_there = [&](int u, uint32_t done) {
        const uint32_t* fl = gs->flag + u * FS;
        uint32_t n = 0;
        while (!__all_sync(~0u, ld_acquire(fl) == ep)) { __nanosleep(100); SPIN_GUARD(n); }
        fence_async_global();
        if (lane == 0) mbar_arrive(done);
      };
      auto fetch_mod = [&](int sec) {
        const uint4* p = (const uint4*)(gs->modv + (sec - 2) * 1024 + j * 128) + lane;
        uint4 v0, v1; uint32_t n = 0;
        while (true) {
          v0 = ld_rlx4(p); v1 = ld_rlx4(p + 32);
          if (v0.y == ep && v0.w == ep && v1.y == ep && v1.w == ep) break;
          SPIN_GUARD(n);
        }
        const uint32_t d = sb + MISC + MODV + sec * 256 + ((lane & 3) * 16 + (lane >> 2)) * 4;
        asm volatile("st.shared.u32 [%0], %1;" :: "r"(d), "r"(__byte_perm(v0.x, v0.z, 0x7632)) : "memory");
        asm volatile("st.shared.u32 [%0], %1;" :: "r"(d + 32), "r"(__byte_perm(v1.x, v1.z, 0x7632)) : "memory");
        __syncwarp();
      };
#pragma unroll 1
      for (int e = 0; e < 7 - b; e++) {
        if (e < 3) {
          uint4* const dst = (e == 1 ? gs->o : gs->h) + m * 16384 + (2 * j + b) * 1024;
          uint32_t* const fl = gs->flag + (m * 128 + e * 16 + 2 * j + b) * FS;
          if (b) {
            mbar_wait(bar + B_FREE, e & 1);
            const uint32_t t0 = clock();
            while ((uint32_t)clock() - t0 < (e == 1 ? B1D : B1P)) {}
          }
          mbar_wait(bar + B_RDY + b * 8, e & 1);
          if (elect()) {
            bulk_st(dst, stg, BLK);
            bulk_commit();
            bulk_wait_all();
            mbar_arrive(bar + B_FREE + b * 8);
            st_release(fl, ep);
          }
        } else if (lane == 0) {
          {
            const int kb = (e < 6 ? 2 * (8 * (e - 3) + j) : 48 + j) + b;
            mbar_wait(bar + B_RDY + b * 8, e & 1);
#pragma unroll 1
            for (int q = 0; q < NPIECE; q++) { if (q) __nanosleep(PSLEEP); bulk_st(gs->hh + m * 57344 + kb * 1024 + q * (1024 / NPIECE), stg + q * (BLK / NPIECE), BLK / NPIECE); }
            bulk_commit();
            bulk_wait_all();
            mbar_arrive(bar + B_FREE + b * 8);
            st_release(gs->flag + (m * 128 + U_HH + kb) * FS, ep);
          }
        }
        __syncwarp();
        if (e < 3 && b) all_there(m * 128 + e * 16 + (lane & 15), bar + B_ALL);
        if (e == 4 && b) all_there(m * 128 + U_HH + lane, bar + B_HH);
        if (!b && (e == 1 || e == 2)) {
#pragma unroll 1
          for (int sec = e == 1 ? 2 : 5; sec < 4 + e; sec++) fetch_mod(sec);
          if (e == 1) { if (lane == 0) mbar_arrive(bar + B_MOD); }
        }
        if (e == 0) {
          mbar_wait(bar + B_EMPTY6 + 24, 0);
          __nanosleep(HSLEEP);
#pragma unroll 1
          for (int w = 0; w < 4; w++) {
            const uint4* hp = gs->halo + ((m * 8 + j) * 2 + (w & 1)) * 512 + b * 256 + (w >> 1) * 128 + lane;
            uint4 q[4] = {}; uint32_t n = 0;
            while (m > 0) {
              bool ok = true;
#pragma unroll
              for (int i = 0; i < 4; i++) q[i] = ld_rlx4(hp + i * 32);
#pragma unroll
              for (int i = 0; i < 4; i++) ok = ok && q[i].y == ep && q[i].w == ep;
              if (ok) break;
              SPIN_GUARD(n);
            }
#pragma unroll
            for (int i = 0; i < 2; i++) sts128(stg + lane * 16 + (w & 1) * HALF + (w >> 1) * 1024 + i * 512, q[2 * i].x, q[2 * i + 1].x, q[2 * i].z, q[2 * i + 1].z);
          }
          __syncwarp();
          if (lane == 0) mbar_arrive(bar + B_HALO);
        }
      }
      if (b) { all_there(m * 128 + U_HH + 32 + (lane & 15), bar + B_HH + 8); all_there(m * 128 + U_HH + 48 + (lane & 7), bar + B_HH2); }
    }
  } else {
    const int wg = warp >> 2, wq = warp & 3, tid = threadIdx.x;
    const int g = lane >> 2, c = lane & 3;
    const int sec0 = (m >> 1) & 1, hf0 = m & 1, ks0 = (m >> 2) & 3;
    uint4 wv[8];
    uint32_t ep0; uint16_t cv_;
    asm volatile("ld.global.nc.u16 %0, [%1];" : "=h"(cv_) : "l"(cvec + ks0 * 256 + warp * 32 + lane));
    asm volatile("ld.global.u32 %0, [%1];" : "=r"(ep0) : "l"(gs->epoch + (blockIdx.x | (lane & by_sm & 2))));
    if (!extra) {
      const bf16* wp = wmod + (size_t)(ks0 * 256 + warp * 32 + (lane >> 3)) * 6144 + sec0 * 1024 + j * 128 + hf0 * 64 + (lane & 7) * 8;
#pragma unroll
      for (int i = 0; i < 8; i++) wv[i] = ldg_nc(wp + (size_t)i * 4 * 6144);
      cl_arrive_relaxed();
    }
    asm volatile("setmaxnreg.inc.sync.aligned.u32 232;" ::: "memory");
    if (__builtin_expect(extra, 0)) {
      const uint32_t ep = ep0 + 1;
      float sv[4];
#pragma unroll
      for (int p = 0; p < 4; p++) sv[p] = silu_c(__bfloat162float(cvec[64 * (4 * p + (lane >> 3)) + 8 * warp + (lane & 7)]));
      named_bar(2, 288);
      int s = 0, par = 0;
#pragma unroll 1
      for (int sec = 0; sec < 4; sec++) {
        float a[8] = {0, 0, 0, 0, 0, 0, 0, 0};
#pragma unroll 1
        for (int it = 0; it < 16; it++) {
          const float sc = it < 4 ? sv[0] : it < 8 ? sv[1] : it < 12 ? sv[2] : sv[3];
          mbar_wait(bar + B_FULL6 + s * 8, par);
          uint4 w[8];
#pragma unroll
          for (int i = 0; i < 8; i++) w[i] = lds128(sb + s * 32768 + (warp * 8 + i) * 512 + lane * 16);
#pragma unroll
          for (int i = 0; i < 8; i++) gemv_fma(a, w[i], __shfl_sync(~0u, sc, (it & 3) * 8 + i));
          if (lane == 0) mbar_arrive(bar + B_EMPTY6 + s * 8);
          if (++s == 6) { s = 0; par ^= 1; }
        }
        const uint32_t red = sb + STG + sec * 8192;
        sts128(red + warp * 1024 + lane * 32, __float_as_uint(a[0]), __float_as_uint(a[1]), __float_as_uint(a[2]), __float_as_uint(a[3]));
        sts128(red + warp * 1024 + lane * 32 + 16, __float_as_uint(a[4]), __float_as_uint(a[5]), __float_as_uint(a[6]), __float_as_uint(a[7]));
        named_bar(1, 256);
        float t = 0;
#pragma unroll
        for (int q = 0; q < 8; q++) t += lds32f(red + q * 1024 + tid * 4);
        t = bf_round(t);
        if (sec == 2) t = bf_round(t + 1.f);
        st_rlx2(gs->modv + sec * 1024 + (bid + 4) * 256 + tid, __float_as_uint(t), ep);
      }
      if (tid == 0) gs->epoch[blockIdx.x] = ep;
      return;
    }
    const int row0 = wg * 64 + wq * 16 + g;
    if (c < 2) st_rlx2(gs->stat + m * 1024 + j * 128 + row0 + c * 8, 0, 0);
    cl_wait();
    uint32_t ep;
    asm volatile("add.u32 %0, %1, 1;" : "=r"(ep) : "r"(ep0) : "memory");
    const float sc_ = silu_c(__uint_as_float((uint32_t)cv_ << 16));
    const uint32_t rel = mapa(bar, (lane & 1) ^ rank);
    const uint32_t stg_row = sb + STG + (wg * 64 + wq * 16 + (lane & 15)) * 128;
    const uint32_t fre = bar + B_FREE;
    Ring r4{0, 0, 0}, r6{0, 0, 0};
    auto none = [](auto) {};
    uint32_t xk[32];
    {
      float a[8] = {0, 0, 0, 0, 0, 0, 0, 0};
#pragma unroll
      for (int i = 0; i < 8; i++) gemv_fma(a, wv[i], __shfl_sync(~0u, sc_, i * 4 + (lane >> 3)));
#pragma unroll
      for (int i = 0; i < 8; i++) { a[i] += __shfl_xor_sync(~0u, a[i], 8); a[i] += __shfl_xor_sync(~0u, a[i], 16); }
      if (lane < 8) {
        sts128(sb + RED_OFF + warp * 256 + lane * 32, __float_as_uint(a[0]), __float_as_uint(a[1]), __float_as_uint(a[2]), __float_as_uint(a[3]));
        sts128(sb + RED_OFF + warp * 256 + lane * 32 + 16, __float_as_uint(a[4]), __float_as_uint(a[5]), __float_as_uint(a[6]), __float_as_uint(a[7]));
      }
      named_bar(1, 256);
      if (tid < 64) {
        float s = 0;
#pragma unroll
        for (int w = 0; w < 8; w++) s += lds32f(sb + RED_OFF + w * 256 + tid * 4);
        st_rlx1(gs->modp + ((j * 2 + sec0) * 4 + ks0) * 128 + hf0 * 64 + tid, (__float_as_uint(s) & ~255u) | tag_of(ep));
      }
      float v[64];
      mbar_wait(bar + B_X, 0); mbar_wait(bar + B_X + 8, 0);
#pragma unroll
      for (int i = 0; i < 16; i += 2) {
        uint32_t w0, w1, w2, w3;
        ldsm4(stg_row + (i >> 3) * BLK + ((((i & 7) + (lane >> 4)) ^ (lane & 7)) << 4), w0, w1, w2, w3);
        xk[2 * i] = w0; xk[2 * i + 1] = w1; xk[2 * i + 2] = w2; xk[2 * i + 3] = w3;
        v[4 * i] = bf_lo(w0); v[4 * i + 1] = bf_hi(w0); v[4 * i + 2] = bf_lo(w1); v[4 * i + 3] = bf_hi(w1);
        v[4 * i + 4] = bf_lo(w2); v[4 * i + 5] = bf_hi(w2); v[4 * i + 6] = bf_lo(w3); v[4 * i + 7] = bf_hi(w3);
      }
      ln_publish(v, gs->stat + m * 1024, j, row0, lane, ep);
      mod_store(sb, tid >> 7, tid & 127, mod_gather(gs->modp + (j * 2 + (tid >> 7)) * 512 + (tid & 127), ep));
      named_bar(1, 256);
      ln_apply(v, gs->stat + m * 1024, row0, ep, sb, 0, 1, stg_row, wg, lane);
      named_bar(1, 256);
    }
    {
      uint32_t kf[32], vf[32], pv[32];
      const bool first = wq == 0 && m == 0;
      const uint32_t xa = sb + STG + wg * HALF + wq * 2048 + lane * 16;
      {
        float acc[128];
        mainloop<256, 4, 0, 0>(acc, 16, true, r4, sb, wg, lane, rel, none, none, [&] {
          mbar_wait(fre + 8, 0);
          if (c < 2) st_rlx2(gs->stat + (16 + m) * 1024 + j * 128 + row0 + c * 8, 0, 0);
        });
#pragma unroll
        for (int i = 0; i < 32; i++) { kf[i] = pack2(acc[2 * i], acc[2 * i + 1]); vf[i] = pack2(acc[64 + 2 * i], acc[65 + 2 * i]); }
      }
      float acc[64];
      constexpr int QP = 2;
      mainloop<128, 6, 8 / QP, 0>(acc, 16, false, r6, sb, wg, lane, rel, [&](auto ic) {
        constexpr int q = (ic.v - 1) * QP;
#pragma unroll
        for (int i = 4 * q; i < 4 * (q + QP); i++) vf[i] = movm(vf[i]);
        if (wq == 3) {
          if (m < 15) {
            uint4* hp = gs->halo + (((m + 1) * 8 + j) * 2 + wg) * 512 + lane;
#pragma unroll
            for (int i = 2 * q; i < 2 * (q + QP); i++) st_rlx4(hp + i * 32, kf[2 * i + 1], ep, vf[2 * i + 1], ep);
          }
        } else {
#pragma unroll
          for (int i = q; i < q + QP; i++) sts128(xa + 2048 + (i >> 2) * BLK + (i & 3) * 512, kf[4 * i + 1], kf[4 * i + 3], vf[4 * i + 1], vf[4 * i + 3]);
        }
      }, none, [&] {
        named_bar(2 + wg, 128);
        if (wq == 0) mbar_wait(bar + B_HALO, 0);
#pragma unroll
        for (int i = 0; i < 8; i++) {
          uint4 q = lds128(xa + (i >> 2) * BLK + (i & 3) * 512);
          pv[4 * i] = q.x; pv[4 * i + 1] = q.y; pv[4 * i + 2] = q.z; pv[4 * i + 3] = q.w;
        }
        __syncwarp();
      });
      int gz = g;
#pragma unroll
      for (int b = 0; b < 2; b++) {
        const bool up0 = 2 * c > gz, up1 = 2 * c + 1 > gz;
        const uint32_t mup = (up0 ? 0xffffu : 0u) | (up1 ? 0xffff0000u : 0u);
        float l[2][4], mx[4];
#pragma unroll
        for (int h = 0; h < 2; h++) {
          uint32_t q[8];
          const int k = 16 * b + 8 * h;
#pragma unroll
          for (int i = 0; i < 8; i++) q[i] = pack2(acc[2 * k + 2 * i], acc[2 * k + 2 * i + 1]);
          float s0[4], s1[4], s2[4];
          mma16z(s0, q[0], q[1], q[2], q[3], pv[k], pv[k + 1]); mma16z(s1, q[0], q[1], q[2], q[3], kf[k], kf[k + 2]); mma16z(s2, q[0], q[1], q[2], q[3], kf[k + 1], kf[k + 3]);
          mma16(s0, q[4], q[5], q[6], q[7], pv[k + 4], pv[k + 5]); mma16(s1, q[4], q[5], q[6], q[7], kf[k + 4], kf[k + 6]); mma16(s2, q[4], q[5], q[6], q[7], kf[k + 5], kf[k + 7]);
          if (first) { s0[0] = -INFINITY; s0[1] = -INFINITY; }
          l[h][0] = up0 ? s0[0] : s1[0]; l[h][1] = up1 ? s0[1] : s1[1]; l[h][2] = up0 ? s1[2] : s2[2]; l[h][3] = up1 ? s1[3] : s2[3];
          mx[2 * h] = fmaxf(l[h][0], l[h][1]); mx[2 * h + 1] = fmaxf(l[h][2], l[h][3]);
        }
#pragma unroll
        for (int o = 1; o < 4; o <<= 1) {
#pragma unroll
          for (int h = 0; h < 4; h++) mx[h] = fmaxf(mx[h], __shfl_xor_sync(~0u, mx[h], o));
        }
#pragma unroll
        for (int h = 0; h < 2; h++) {
          const float n0 = -mx[2 * h] * SCL, n1 = -mx[2 * h + 1] * SCL;
          const uint32_t pa = pack2(ex2(fmaf(l[h][0], SCL, n0)), ex2(fmaf(l[h][1], SCL, n0))), pb = pack2(ex2(fmaf(l[h][2], SCL, n1)), ex2(fmaf(l[h][3], SCL, n1)));
          float sm[4];
          mma8z(sm, pa, pb, 0x3f803f80u);
          const float ia = rcp(sm[0]), ib = rcp(sm[2]);
#pragma unroll
          for (int i = 8 * b + 4 * h; i < 8 * b + 4 * h + 4; i += 2) {
            uint32_t of[4];
#pragma unroll
            for (int d = 0; d < 2; d++) {
              float o[4];
              mma16z(o, pa & ~mup, pb & mup, 0u, pb & ~mup, vf[2 * (i + d)], vf[2 * (i + d) + 1]);
              mma8(o, pa & mup, 0u, pv[2 * i + 2 + d]);
              of[2 * d] = pack2(o[0] * ia, o[1] * ia); of[2 * d + 1] = pack2(o[2] * ib, o[3] * ib);
            }
            stsm4(stg_row + b * BLK + ((((i & 7) + (lane >> 4)) ^ (lane & 7)) << 4), of[0], of[1], of[2], of[3]);
          }
        }
        stage_done(sb, wg, b, lane);
        if (b == 0) gz += __float_as_uint(lds32f(bar + ZERO));
      }
      named_bar(1, 256);
    }
    uint32_t pk[64];
    {
      float acc[64];
      mainloop<128, 6, 0, 0>(acc, 16, true, r6, sb, wg, lane, rel, none, none, [&] {
        mbar_wait(bar + B_MOD, 0); mbar_wait(fre + 8, 1);
        load_vec(pk + 32, sb, 2, 0, lane); load_vec(pk + 40, sb, 2, 1, lane);
#pragma unroll
        for (int i = 0; i < 32; i++) { pk[i] = xk[i]; asm volatile("" : "+r"(pk[i])); }
      });
#pragma unroll
      for (int i = 0; i < 32; i++) {
        acc[2 * i] = fmaf(acc[2 * i], bf_lo(pk[32 + (i >> 1)]), bf_lo(pk[i]));
        acc[2 * i + 1] = fmaf(acc[2 * i + 1], bf_hi(pk[32 + (i >> 1)]), bf_hi(pk[i]));
      }
      ln_publish(acc, gs->stat + (16 + m) * 1024, j, row0, lane, ep);
      mbar_wait(bar + B_FULL6 + 16, 1);
      if (lane < 2) mbar_arrive_cl(rel + B_EMPTY6 + 16);
      ring_next<6>(r6);
#pragma unroll
      for (int i = 0; i < 32; i++) { pk[i] = pack2(acc[2 * i], acc[2 * i + 1]); pk[32 + i] = 0; }
      ln_apply(acc, gs->stat + (16 + m) * 1024, row0, ep, sb, 3, 4, stg_row, wg, lane);
      named_bar(1, 256);
    }
    auto swiglu = [&](int q, int uo, int par) {
      if ((q & 3) == 0 && par >= 0) mbar_wait(fre + 2 * q, par);
      uint32_t w[4];
#pragma unroll
      for (int u = 0; u < 4; u++) w[u] = silu_mul2(pk[4 * q + u], pk[uo + 4 * q + u]);
      stsm4(stg_row + (q >> 2) * BLK + ((((2 * q & 7) + (lane >> 4)) ^ (lane & 7)) << 4), w[0], w[1], w[2], w[3]);
    };
    r4.s = r4.wrap = 2;
#pragma unroll 1
    for (int t = 0; t < 3; t++) {
      float acc[128];
      mainloop<256, 4, 4, 1>(acc, 16, t == 0, r4, sb, wg, lane, rel, [&](auto ic) {
        if (t) {
          if (ic.v == 3) stage_done(sb, wg, 0, lane);
          swiglu(2 * ic.v - 2, 32, ~t & 1); swiglu(2 * ic.v - 1, 32, 0);
        }
      }, [&](int it) {
        if (t && it == 5) stage_done(sb, wg, 1, lane);
#pragma unroll
        for (int i = 0; i < 8; i++)
          if (t == 0 && it == 8 + i) gs->x1[bid * 2048 + (i >> 2) * 1024 + warp * 128 + (i & 3) * 32 + lane] = make_uint4(pk[4 * i], pk[4 * i + 1], pk[4 * i + 2], pk[4 * i + 3]);
      }, [&] { if (t == 0) fence_async_global(); else if (t == 2) mbar_wait(bar + B_X, 1); }, t & 1);
#pragma unroll
      for (int i = 0; i < 64; i++) pk[i] = pack2(acc[2 * i], acc[2 * i + 1]);
    }
    uint32_t x1[32];
    {
      float acc[64];
      mainloop<128, 6, 10, 1>(acc, 16, false, r6, sb, wg, lane, rel, [&](auto ic) {
        constexpr int b = ic.v > 5, q = ic.v - 5 * b;
        if (q == 1) {
          if (b) stage_done(sb, wg, 0, lane);
#pragma unroll
          for (int i = 4 * b; i < 4 * b + 4; i++) { const uint4 x = lds128(sb + STG + b * BLK + warp * 2048 + (i & 3) * 512 + lane * 16); x1[4 * i] = x.x; x1[4 * i + 1] = x.y; x1[4 * i + 2] = x.z; x1[4 * i + 3] = x.w; }
          __syncwarp();
        } else swiglu(4 * b + q - 2, 32, -1);
      }, [&](int it) { if (it == 11) stage_done(sb, wg, 1, lane); }, [] {}, 1);
#pragma unroll
      for (int i = 0; i < 32; i++) pk[i] = pack2(acc[2 * i], acc[2 * i + 1]);
    }
    {
      float acc[64];
      mainloop<128, 6, 4, TAILLAG>(acc, 56, false, r6, sb, wg, lane, rel, [&](auto ic) { swiglu(ic.v - 1, 16, 1); },
                                   [&](int it) { if (it == 5) stage_done(sb, wg, 0, lane); }, [&] {
        load_vec(pk + 32, sb, 5, 0, lane); load_vec(pk + 40, sb, 5, 1, lane);
        mbar_wait(fre, 0); mbar_wait(fre + 8, 1);
      }, 0);
      __syncwarp();
      cl_arrive_relaxed();
#pragma unroll
      for (int i = 0; i < 16; i += 2) {
        uint32_t w[4];
#pragma unroll
        for (int u = 0; u < 4; u++) {
          const int q = 2 * i + u;
          w[u] = pack2(fmaf(acc[2 * q], bf_lo(pk[32 + (q >> 1)]), bf_lo(x1[q])), fmaf(acc[2 * q + 1], bf_hi(pk[32 + (q >> 1)]), bf_hi(x1[q])));
        }
        stsm4(stg_row + (i >> 3) * BLK + ((((i & 7) + (lane >> 4)) ^ (lane & 7)) << 4), w[0], w[1], w[2], w[3]);
        if ((i & 7) == 6) {
          fence_async_smem();
          named_bar(2 + wg, 128);
          if (wq == 0 && elect()) { tma_store_3d(&maps.out, sb + STG + (i >> 3) * BLK + wg * HALF, j * 128 + (i >> 3) * 64, m * 64, wg); bulk_commit(); }
          if (i < 8) x1[16] |= __float_as_uint(lds32f(bar + ZERO));
        }
      }
      if (wq == 0) bulk_wait_read();
      if (tid == 0) gs->epoch[blockIdx.x] = ep;
      cl_wait();
    }
  }
}

typedef CUresult (*EncodeFn)(CUtensorMap*, CUtensorMapDataType, cuuint32_t, void*, const cuuint64_t*, const cuuint64_t*, const cuuint32_t*, const cuuint32_t*,
                             CUtensorMapInterleave, CUtensorMapSwizzle, CUtensorMapL2promotion, CUtensorMapFloatOOBfill);

void make_map(EncodeFn fn, CUtensorMap* mp, const void* base, uint64_t d0, uint64_t d1, uint64_t d2, uint64_t s1, uint64_t s2, uint32_t b2, uint32_t b0 = 64) {
  cuuint64_t d[3] = {d0, d1, d2}, s[2] = {s1, s2};
  cuuint32_t b[3] = {b0, 64, b2}, e[3] = {1, 1, 1};
  fn(mp, CU_TENSOR_MAP_DATA_TYPE_BFLOAT16, 3, (void*)base, d, s, b, e, CU_TENSOR_MAP_INTERLEAVE_NONE, b0 == 64 ? CU_TENSOR_MAP_SWIZZLE_128B : CU_TENSOR_MAP_SWIZZLE_NONE,
     CU_TENSOR_MAP_L2_PROMOTION_L2_128B, CU_TENSOR_MAP_FLOAT_OOB_FILL_NONE);
}

__global__ void probe_kernel() {}
int max_clusters(int size) {
  cudaLaunchConfig_t cfg = {};
  cudaLaunchAttribute at;
  at.id = cudaLaunchAttributeClusterDimension; at.val.clusterDim.x = size; at.val.clusterDim.y = 1; at.val.clusterDim.z = 1;
  cfg.gridDim = dim3(size * 66); cfg.blockDim = dim3(384); cfg.dynamicSmemBytes = SMEM_BYTES; cfg.attrs = &at; cfg.numAttrs = 1;
  int n = 0;
  if (cudaOccupancyMaxActiveClusters(&n, probe_kernel, &cfg) != cudaSuccess) { cudaGetLastError(); return 0; }
  return n;
}

}

extern "C" void kernel_launch(void* const* d_in, const int* in_sizes, int n_in, void* d_out, int out_size) {
  static EncodeFn fn = nullptr;
  static int by_sm = 0;
  static Scratch* gs = nullptr;
  if (!fn) {
    void* p = nullptr; cudaDriverEntryPointQueryResult q;
    cudaGetDriverEntryPoint("cuTensorMapEncodeTiled", &p, cudaEnableDefault, &q);
    fn = (EncodeFn)p;
    cudaFuncSetAttribute(fused_kernel, cudaFuncAttributeMaxDynamicSharedMemorySize, SMEM_BYTES);
    int dev = 0, sms = 0;
    cudaGetSymbolAddress((void**)&gs, g_scratch);
    cudaGetDevice(&dev);
    cudaDeviceGetAttribute(&sms, cudaDevAttrMultiProcessorCount, dev);
    cudaFuncSetAttribute(probe_kernel, cudaFuncAttributeMaxDynamicSharedMemorySize, SMEM_BYTES);
    by_sm = sms == 132 && max_clusters(2) == 66 && max_clusters(4) == 30 && max_clusters(6) == 17 && max_clusters(8) == 15;
  }
  Maps mp;
  make_map(fn, &mp.x, d_in[0], D_, S_ / 2, 2, 4096, 2048, 2);
  make_map(fn, &mp.out, d_out, D_, S_ / 2, 2, 4096, 2048, 1);
  make_map(fn, &mp.wqkv, d_in[1], 64, D_, 3 * D_ / 64, 3 * D_ * 2, 128, 2);
  make_map(fn, &mp.wo, d_in[2], 64, D_, D_ / 64, D_ * 2, 128, 2);
  make_map(fn, &mp.w1, d_in[4], 64, D_, F_ / 64, F_ * 2, 128, 2);
  make_map(fn, &mp.w3, d_in[5], 64, D_, F_ / 64, F_ * 2, 128, 2);
  make_map(fn, &mp.w1s, d_in[4], 64, D_, F_ / 64, F_ * 2, 128, 1);
  make_map(fn, &mp.w3s, d_in[5], 64, D_, F_ / 64, F_ * 2, 128, 1);
  make_map(fn, &mp.w2, d_in[6], 64, F_, D_ / 64, D_ * 2, 128, 2);
  make_map(fn, &mp.wmod, d_in[8], 256, D_, 24, 6 * D_ * 2, 512, 1, 256);
  fused_kernel<<<132, 384, SMEM_BYTES>>>((const bf16*)d_in[7], (const bf16*)d_in[8], gs, by_sm, mp);
}
```

```cpp
#include <cuda_runtime.h>
#include <cuda_bf16.h>
#include <cuda.h>
#include <stdint.h>

typedef __nv_bfloat16 bf16;

namespace {

constexpr int S_ = 2048, D_ = 1024, F_ = 3584;
constexpr int BLK = 16384;
constexpr int HALF = 8192;
constexpr int RING = 196608;
constexpr int STG = RING;
constexpr int MISC = RING + 2 * BLK;
constexpr int SMEM_BYTES = MISC + 3072;
constexpr int B_FULL4 = 0, B_EMPTY4 = 32, B_FULL6 = 64, B_EMPTY6 = 112, B_RDY = 160, B_FREE = 176, B_LAG = 192, B_X = 208, B_MOD = 224, B_HALO = 232, B_HH = 256, B_ALL = 272, B_HH2 = 288, ZERO = 296;
constexpr int MODV = 512;
constexpr int RED_OFF = 0;
constexpr float SCL = 0.17677669529663687f * 1.4426950408889634f;
constexpr int U_HH = 64;
constexpr int FS = 8;
constexpr int NPIECE = 4, PSLEEP = 300;
constexpr int XSLEEP = 4000, HSLEEP = 400;
constexpr uint32_t XDELAY = 2300, GAP = 250;
constexpr uint32_t B1P = 3700, B1D = 700;
constexpr int TAILLAG = 5;

struct Maps { CUtensorMap x, out, wqkv, wo, w1, w3, w1s, w3s, w2, wmod; };

struct Scratch {
  uint4 h[16 * 16 * 1024];
  uint4 o[16 * 16 * 1024];
  uint4 hh[16 * 56 * 1024];
  uint4 x1[128 * 8 * 256];
  uint2 stat[2 * 16 * 8 * 128];
  uint4 halo[16 * 8 * 2 * 512];
  uint32_t modp[8 * 2 * 4 * 128];
  uint2 modv[4 * 1024];
  uint32_t flag[16 * 128 * FS];
  uint32_t epoch[132];
};
__device__ __align__(1024) Scratch g_scratch;

__device__ __forceinline__ void bail() { asm volatile("st.global.u32 [%0], %1;" :: "l"(0ull), "r"(0) : "memory"); }
__device__ __forceinline__ uint32_t smem_u32(const void* p) { return (uint32_t)__cvta_generic_to_shared(p); }
__device__ __forceinline__ void mbar_init(uint32_t bar, uint32_t cnt) { asm volatile("mbarrier.init.shared::cta.b64 [%0], %1;" :: "r"(bar), "r"(cnt) : "memory"); }
__device__ __forceinline__ void mbar_arrive(uint32_t bar) { asm volatile("mbarrier.arrive.shared::cta.b64 _, [%0];" :: "r"(bar) : "memory"); }
__device__ __forceinline__ void mbar_arrive_cl(uint32_t cl_addr) { asm volatile("mbarrier.arrive.shared::cluster.b64 _, [%0];" :: "r"(cl_addr) : "memory"); }
__device__ __forceinline__ uint32_t mapa(uint32_t addr, uint32_t cta) { uint32_t r; asm("mapa.shared::cluster.u32 %0, %1, %2;" : "=r"(r) : "r"(addr), "r"(cta)); return r; }
__device__ __forceinline__ void mbar_wait(uint32_t bar, uint32_t parity) {
  asm volatile("{\n.reg .pred p;\n.reg .b32 n;\n.reg .b64 z;\nmov.b32 n, 0;\nmov.b64 z, 0;\n"
               "W: add.u32 n, n, 1;\nsetp.gt.u32 p, n, 0x400000;\n@p st.global.u32 [z], n;\n"
               "mbarrier.try_wait.parity.shared::cta.b64 p, [%0], %1;\n@!p bra W;\n}" :: "r"(bar), "r"(parity) : "memory");
}
__device__ __forceinline__ void tma_store_3d(const CUtensorMap* m, uint32_t src, int c0, int c1, int c2) {
  asm volatile("cp.async.bulk.tensor.3d.global.shared::cta.bulk_group [%0, {%2, %3, %4}], [%1];" :: "l"(m), "r"(src), "r"(c0), "r"(c1), "r"(c2) : "memory");
}
#define ELECT "{\n.reg .pred p;\nelect.sync _|p, 0xffffffff;\n@p "
__device__ __forceinline__ void expect_e(uint32_t bar, uint32_t bytes) { asm volatile(ELECT "mbarrier.arrive.expect_tx.shared::cta.b64 _, [%0], %1;\n}" :: "r"(bar), "r"(bytes) : "memory"); }
__device__ __forceinline__ void tma_3d_e(uint32_t dst, const CUtensorMap* m, uint32_t bar, int c0, int c1, int c2) {
  asm volatile(ELECT "cp.async.bulk.tensor.3d.shared::cluster.global.mbarrier::complete_tx::bytes [%0], [%1, {%3, %4, %5}], [%2];\n}" :: "r"(dst), "l"(m), "r"(bar), "r"(c0), "r"(c1), "r"(c2) : "memory");
}
__device__ __forceinline__ void bulk_ld_e(uint32_t dst, const void* src, uint32_t bytes, uint32_t bar) {
  asm volatile(ELECT "cp.async.bulk.shared::cluster.global.mbarrier::complete_tx::bytes [%0], [%1], %2, [%3];\n}" :: "r"(dst), "l"(src), "r"(bytes), "r"(bar) : "memory");
}
__device__ __forceinline__ void bulk_ld_mc_e(uint32_t dst, const void* src, uint32_t bytes, uint32_t bar) {
  asm volatile(ELECT "cp.async.bulk.shared::cluster.global.mbarrier::complete_tx::bytes.multicast::cluster [%0], [%1], %2, [%3], %4;\n}" :: "r"(dst), "l"(src), "r"(bytes), "r"(bar), "h"((uint16_t)3) : "memory");
}
__device__ __forceinline__ void bulk_push_e(uint32_t dst_cl, uint32_t src, uint32_t bytes, uint32_t bar_cl) {
  asm volatile(ELECT "cp.async.bulk.shared::cluster.shared::cta.mbarrier::complete_tx::bytes [%0], [%1], %2, [%3];\n}" :: "r"(dst_cl), "r"(src), "r"(bytes), "r"(bar_cl) : "memory");
}
__device__ __forceinline__ void bulk_st(void* dst, uint32_t src, uint32_t bytes) {
  asm volatile("cp.async.bulk.global.shared::cta.bulk_group [%0], [%1], %2;" :: "l"(dst), "r"(src), "r"(bytes) : "memory");
}
__device__ __forceinline__ void bulk_commit() { asm volatile("cp.async.bulk.commit_group;" ::: "memory"); }
__device__ __forceinline__ void bulk_wait_read() { asm volatile("cp.async.bulk.wait_group.read 0;" ::: "memory"); }
__device__ __forceinline__ void bulk_wait_all() { asm volatile("cp.async.bulk.wait_group 0;" ::: "memory"); }
__device__ __forceinline__ void fence_async_global() { asm volatile("fence.proxy.async.global;" ::: "memory"); }
__device__ __forceinline__ void fence_async_smem() { asm volatile("fence.proxy.async.shared::cta;" ::: "memory"); }
__device__ __forceinline__ void wg_arrive() { asm volatile("wgmma.fence.sync.aligned;" ::: "memory"); }
__device__ __forceinline__ void wg_commit() { asm volatile("wgmma.commit_group.sync.aligned;" ::: "memory"); }
template <int N> __device__ __forceinline__ void wg_wait() { asm volatile("wgmma.wait_group.sync.aligned %0;" :: "n"(N) : "memory"); }
__device__ __forceinline__ void cl_arrive_relaxed() { asm volatile("barrier.cluster.arrive.relaxed.aligned;" ::: "memory"); }
__device__ __forceinline__ void cl_wait() { asm volatile("barrier.cluster.wait.acquire.aligned;" ::: "memory"); }
__device__ __forceinline__ bool elect() { uint32_t p; asm volatile("{\n.reg .pred p;\nelect.sync _|p, 0xffffffff;\nselp.u32 %0, 1, 0, p;\n}" : "=r"(p)); return p; }
__device__ __forceinline__ void named_bar(int id, int n) { asm volatile("bar.sync %0, %1;" :: "r"(id), "r"(n) : "memory"); }
__device__ __forceinline__ uint32_t pack2(float lo, float hi) { uint32_t r; asm("cvt.rn.bf16x2.f32 %0, %1, %2;" : "=r"(r) : "f"(hi), "f"(lo)); return r; }
__device__ __forceinline__ float bf_lo(uint32_t w) { return __uint_as_float(w << 16); }
__device__ __forceinline__ float bf_hi(uint32_t w) { return __uint_as_float(w & 0xffff0000u); }
__device__ __forceinline__ float bf_round(float v) { return __bfloat162float(__float2bfloat16_rn(v)); }
__device__ __forceinline__ void stsm4(uint32_t addr, uint32_t a, uint32_t b, uint32_t c, uint32_t d) {
  asm volatile("stmatrix.sync.aligned.m8n8.x4.shared.b16 [%0], {%1, %2, %3, %4};" :: "r"(addr), "r"(a), "r"(b), "r"(c), "r"(d) : "memory");
}
__device__ __forceinline__ void ldsm4(uint32_t addr, uint32_t& a, uint32_t& b, uint32_t& c, uint32_t& d) {
  asm volatile("ldmatrix.sync.aligned.m8n8.x4.shared.b16 {%0, %1, %2, %3}, [%4];" : "=r"(a), "=r"(b), "=r"(c), "=r"(d) : "r"(addr) : "memory");
}
__device__ __forceinline__ uint32_t movm(uint32_t a) { uint32_t r; asm volatile("movmatrix.sync.aligned.m8n8.trans.b16 %0, %1;" : "=r"(r) : "r"(a)); return r; }
__device__ __forceinline__ void mma16(float (&d)[4], uint32_t a0, uint32_t a1, uint32_t a2, uint32_t a3, uint32_t b0, uint32_t b1) {
  asm("mma.sync.aligned.m16n8k16.row.col.f32.bf16.bf16.f32 {%0,%1,%2,%3}, {%4,%5,%6,%7}, {%8,%9}, {%0,%1,%2,%3};"
               : "+f"(d[0]), "+f"(d[1]), "+f"(d[2]), "+f"(d[3]) : "r"(a0), "r"(a1), "r"(a2), "r"(a3), "r"(b0), "r"(b1));
}
__device__ __forceinline__ void mma16z(float (&d)[4], uint32_t a0, uint32_t a1, uint32_t a2, uint32_t a3, uint32_t b0, uint32_t b1) {
  asm("mma.sync.aligned.m16n8k16.row.col.f32.bf16.bf16.f32 {%0,%1,%2,%3}, {%4,%5,%6,%7}, {%8,%9}, {%10,%10,%10,%10};"
      : "=f"(d[0]), "=f"(d[1]), "=f"(d[2]), "=f"(d[3]) : "r"(a0), "r"(a1), "r"(a2), "r"(a3), "r"(b0), "r"(b1), "f"(0.f));
}
__device__ __forceinline__ void mma8z(float (&d)[4], uint32_t a0, uint32_t a1, uint32_t b0) {
  asm("mma.sync.aligned.m16n8k8.row.col.f32.bf16.bf16.f32 {%0,%1,%2,%3}, {%4,%5}, {%6}, {%7,%7,%7,%7};"
      : "=f"(d[0]), "=f"(d[1]), "=f"(d[2]), "=f"(d[3]) : "r"(a0), "r"(a1), "r"(b0), "f"(0.f));
}
__device__ __forceinline__ void mma8(float (&d)[4], uint32_t a0, uint32_t a1, uint32_t b0) {
  asm("mma.sync.aligned.m16n8k8.row.col.f32.bf16.bf16.f32 {%0,%1,%2,%3}, {%4,%5}, {%6}, {%0,%1,%2,%3};"
               : "+f"(d[0]), "+f"(d[1]), "+f"(d[2]), "+f"(d[3]) : "r"(a0), "r"(a1), "r"(b0));
}
__device__ __forceinline__ uint4 lds128(uint32_t a) { uint4 v; asm volatile("ld.shared.v4.u32 {%0,%1,%2,%3}, [%4];" : "=r"(v.x), "=r"(v.y), "=r"(v.z), "=r"(v.w) : "r"(a) : "memory"); return v; }
__device__ __forceinline__ void sts128(uint32_t a, uint32_t x, uint32_t y, uint32_t z, uint32_t w) { asm volatile("st.shared.v4.u32 [%0], {%1,%2,%3,%4};" :: "r"(a), "r"(x), "r"(y), "r"(z), "r"(w) : "memory"); }
__device__ __forceinline__ float lds32f(uint32_t a) { float v; asm volatile("ld.shared.f32 %0, [%1];" : "=f"(v) : "r"(a) : "memory"); return v; }
__device__ __forceinline__ void sts16(uint32_t a, bf16 v) { asm volatile("st.shared.b16 [%0], %1;" :: "r"(a), "h"(__bfloat16_as_ushort(v)) : "memory"); }
__device__ __forceinline__ uint4 ldg_nc(const void* p) { uint4 v; asm volatile("ld.global.nc.L1::no_allocate.v4.u32 {%0,%1,%2,%3}, [%4];" : "=r"(v.x), "=r"(v.y), "=r"(v.z), "=r"(v.w) : "l"(p)); return v; }
__device__ __forceinline__ uint4 ld_rlx4(const uint4* p) {
  unsigned long long a, b; asm volatile("ld.relaxed.gpu.global.v2.b64 {%0,%1}, [%2];" : "=l"(a), "=l"(b) : "l"(p) : "memory");
  return make_uint4((uint32_t)a, (uint32_t)(a >> 32), (uint32_t)b, (uint32_t)(b >> 32));
}
__device__ __forceinline__ uint2 ld_rlx2(const uint2* p) { unsigned long long a; asm volatile("ld.relaxed.gpu.global.b64 %0, [%1];" : "=l"(a) : "l"(p) : "memory"); return make_uint2((uint32_t)a, (uint32_t)(a >> 32)); }
__device__ __forceinline__ void st_rlx4(uint4* p, uint32_t x, uint32_t y, uint32_t z, uint32_t w) {
  asm volatile("st.relaxed.gpu.global.v2.b64 [%0], {%1,%2};" :: "l"(p), "l"((unsigned long long)x | ((unsigned long long)y << 32)), "l"((unsigned long long)z | ((unsigned long long)w << 32)) : "memory");
}
__device__ __forceinline__ void st_rlx2(uint2* p, uint32_t x, uint32_t y) { asm volatile("st.relaxed.gpu.global.b64 [%0], %1;" :: "l"(p), "l"((unsigned long long)x | ((unsigned long long)y << 32)) : "memory"); }
__device__ __forceinline__ void st_rlx1(uint32_t* p, uint32_t v) { asm volatile("st.relaxed.gpu.global.u32 [%0], %1;" :: "l"(p), "r"(v) : "memory"); }
__device__ __forceinline__ uint32_t ld_rlx1(const uint32_t* p) { uint32_t v; asm volatile("ld.relaxed.gpu.global.u32 %0, [%1];" : "=r"(v) : "l"(p) : "memory"); return v; }
__device__ __forceinline__ void st_release(uint32_t* p, uint32_t v) { asm volatile("st.release.gpu.global.u32 [%0], %1;" :: "l"(p), "r"(v) : "memory"); }
__device__ __forceinline__ uint32_t ld_acquire(const uint32_t* p) { uint32_t v; asm volatile("ld.acquire.gpu.global.u32 %0, [%1];" : "=r"(v) : "l"(p) : "memory"); return v; }
__device__ __forceinline__ void prefetch_map(const CUtensorMap* m) { asm volatile("prefetch.tensormap [%0];" :: "l"(m) : "memory"); }
__device__ __forceinline__ float rcp(float x) { float r; asm("rcp.approx.ftz.f32 %0, %1;" : "=f"(r) : "f"(x)); return r; }
__device__ __forceinline__ float ex2(float x) { float r; asm("ex2.approx.ftz.f32 %0, %1;" : "=f"(r) : "f"(x)); return r; }
__device__ __forceinline__ float tanh_fast(float x) { float r; asm("tanh.approx.f32 %0, %1;" : "=f"(r) : "f"(x)); return r; }
#define SPIN_GUARD(n) if (++(n) > (1u << 24)) bail()

__device__ __forceinline__ void wgmma_n128(float (&d)[64], uint64_t da, uint64_t db) {
  asm volatile("wgmma.mma_async.sync.aligned.m64n128k16.f32.bf16.bf16 "
    "{%0, %1, %2, %3, %4, %5, %6, %7, %8, %9, %10, %11, %12, %13, %14, %15, %16, %17, %18, %19, %20, %21, %22, %23, %24, %25, %26, %27, %28, %29, %30, %31, %32, %33, %34, %35, %36, %37, %38, %39, %40, %41, %42, %43, %44, %45, %46, %47, %48, %49, %50, %51, %52, %53, %54, %55, %56, %57, %58, %59, %60, %61, %62, %63}, "
    "%64, %65, 1, 1, 1, 0, 1;\n"
    : "+f"(d[0]), "+f"(d[1]), "+f"(d[2]), "+f"(d[3]), "+f"(d[4]), "+f"(d[5]), "+f"(d[6]), "+f"(d[7]), "+f"(d[8]), "+f"(d[9]), "+f"(d[10]), "+f"(d[11]), "+f"(d[12]), "+f"(d[13]), "+f"(d[14]), "+f"(d[15]), "+f"(d[16]), "+f"(d[17]), "+f"(d[18]), "+f"(d[19]), "+f"(d[20]), "+f"(d[21]), "+f"(d[22]), "+f"(d[23]), "+f"(d[24]), "+f"(d[25]), "+f"(d[26]), "+f"(d[27]), "+f"(d[28]), "+f"(d[29]), "+f"(d[30]), "+f"(d[31]), "+f"(d[32]), "+f"(d[33]), "+f"(d[34]), "+f"(d[35]), "+f"(d[36]), "+f"(d[37]), "+f"(d[38]), "+f"(d[39]), "+f"(d[40]), "+f"(d[41]), "+f"(d[42]), "+f"(d[43]), "+f"(d[44]), "+f"(d[45]), "+f"(d[46]), "+f"(d[47]), "+f"(d[48]), "+f"(d[49]), "+f"(d[50]), "+f"(d[51]), "+f"(d[52]), "+f"(d[53]), "+f"(d[54]), "+f"(d[55]), "+f"(d[56]), "+f"(d[57]), "+f"(d[58]), "+f"(d[59]), "+f"(d[60]), "+f"(d[61]), "+f"(d[62]), "+f"(d[63])
    : "l"(da), "l"(db));
}
__device__ __forceinline__ void wgmma_n128_first(float (&d)[64], uint64_t da, uint64_t db) {
  asm volatile("wgmma.mma_async.sync.aligned.m64n128k16.f32.bf16.bf16 "
    "{%0, %1, %2, %3, %4, %5, %6, %7, %8, %9, %10, %11, %12, %13, %14, %15, %16, %17, %18, %19, %20, %21, %22, %23, %24, %25, %26, %27, %28, %29, %30, %31, %32, %33, %34, %35, %36, %37, %38, %39, %40, %41, %42, %43, %44, %45, %46, %47, %48, %49, %50, %51, %52, %53, %54, %55, %56, %57, %58, %59, %60, %61, %62, %63}, "
    "%64, %65, 0, 1, 1, 0, 1;\n"
    : "=f"(d[0]), "=f"(d[1]), "=f"(d[2]), "=f"(d[3]), "=f"(d[4]), "=f"(d[5]), "=f"(d[6]), "=f"(d[7]), "=f"(d[8]), "=f"(d[9]), "=f"(d[10]), "=f"(d[11]), "=f"(d[12]), "=f"(d[13]), "=f"(d[14]), "=f"(d[15]), "=f"(d[16]), "=f"(d[17]), "=f"(d[18]), "=f"(d[19]), "=f"(d[20]), "=f"(d[21]), "=f"(d[22]), "=f"(d[23]), "=f"(d[24]), "=f"(d[25]), "=f"(d[26]), "=f"(d[27]), "=f"(d[28]), "=f"(d[29]), "=f"(d[30]), "=f"(d[31]), "=f"(d[32]), "=f"(d[33]), "=f"(d[34]), "=f"(d[35]), "=f"(d[36]), "=f"(d[37]), "=f"(d[38]), "=f"(d[39]), "=f"(d[40]), "=f"(d[41]), "=f"(d[42]), "=f"(d[43]), "=f"(d[44]), "=f"(d[45]), "=f"(d[46]), "=f"(d[47]), "=f"(d[48]), "=f"(d[49]), "=f"(d[50]), "=f"(d[51]), "=f"(d[52]), "=f"(d[53]), "=f"(d[54]), "=f"(d[55]), "=f"(d[56]), "=f"(d[57]), "=f"(d[58]), "=f"(d[59]), "=f"(d[60]), "=f"(d[61]), "=f"(d[62]), "=f"(d[63])
    : "l"(da), "l"(db));
}
__device__ __forceinline__ void wgmma_n256(float (&d)[128], uint64_t da, uint64_t db) {
  asm volatile("wgmma.mma_async.sync.aligned.m64n256k16.f32.bf16.bf16 "
    "{%0, %1, %2, %3, %4, %5, %6, %7, %8, %9, %10, %11, %12, %13, %14, %15, %16, %17, %18, %19, %20, %21, %22, %23, %24, %25, %26, %27, %28, %29, %30, %31, %32, %33, %34, %35, %36, %37, %38, %39, %40, %41, %42, %43, %44, %45, %46, %47, %48, %49, %50, %51, %52, %53, %54, %55, %56, %57, %58, %59, %60, %61, %62, %63, %64, %65, %66, %67, %68, %69, %70, %71, %72, %73, %74, %75, %76, %77, %78, %79, %80, %81, %82, %83, %84, %85, %86, %87, %88, %89, %90, %91, %92, %93, %94, %95, %96, %97, %98, %99, %100, %101, %102, %103, %104, %105, %106, %107, %108, %109, %110, %111, %112, %113, %114, %115, %116, %117, %118, %119, %120, %121, %122, %123, %124, %125, %126, %127}, "
    "%128, %129, 1, 1, 1, 0, 1;\n"
    : "+f"(d[0]), "+f"(d[1]), "+f"(d[2]), "+f"(d[3]), "+f"(d[4]), "+f"(d[5]), "+f"(d[6]), "+f"(d[7]), "+f"(d[8]), "+f"(d[9]), "+f"(d[10]), "+f"(d[11]), "+f"(d[12]), "+f"(d[13]), "+f"(d[14]), "+f"(d[15]), "+f"(d[16]), "+f"(d[17]), "+f"(d[18]), "+f"(d[19]), "+f"(d[20]), "+f"(d[21]), "+f"(d[22]), "+f"(d[23]), "+f"(d[24]), "+f"(d[25]), "+f"(d[26]), "+f"(d[27]), "+f"(d[28]), "+f"(d[29]), "+f"(d[30]), "+f"(d[31]), "+f"(d[32]), "+f"(d[33]), "+f"(d[34]), "+f"(d[35]), "+f"(d[36]), "+f"(d[37]), "+f"(d[38]), "+f"(d[39]), "+f"(d[40]), "+f"(d[41]), "+f"(d[42]), "+f"(d[43]), "+f"(d[44]), "+f"(d[45]), "+f"(d[46]), "+f"(d[47]), "+f"(d[48]), "+f"(d[49]), "+f"(d[50]), "+f"(d[51]), "+f"(d[52]), "+f"(d[53]), "+f"(d[54]), "+f"(d[55]), "+f"(d[56]), "+f"(d[57]), "+f"(d[58]), "+f"(d[59]), "+f"(d[60]), "+f"(d[61]), "+f"(d[62]), "+f"(d[63]), "+f"(d[64]), "+f"(d[65]), "+f"(d[66]), "+f"(d[67]), "+f"(d[68]), "+f"(d[69]), "+f"(d[70]), "+f"(d[71]), "+f"(d[72]), "+f"(d[73]), "+f"(d[74]), "+f"(d[75]), "+f"(d[76]), "+f"(d[77]), "+f"(d[78]), "+f"(d[79]), "+f"(d[80]), "+f"(d[81]), "+f"(d[82]), "+f"(d[83]), "+f"(d[84]), "+f"(d[85]), "+f"(d[86]), "+f"(d[87]), "+f"(d[88]), "+f"(d[89]), "+f"(d[90]), "+f"(d[91]), "+f"(d[92]), "+f"(d[93]), "+f"(d[94]), "+f"(d[95]), "+f"(d[96]), "+f"(d[97]), "+f"(d[98]), "+f"(d[99]), "+f"(d[100]), "+f"(d[101]), "+f"(d[102]), "+f"(d[103]), "+f"(d[104]), "+f"(d[105]), "+f"(d[106]), "+f"(d[107]), "+f"(d[108]), "+f"(d[109]), "+f"(d[110]), "+f"(d[111]), "+f"(d[112]), "+f"(d[113]), "+f"(d[114]), "+f"(d[115]), "+f"(d[116]), "+f"(d[117]), "+f"(d[118]), "+f"(d[119]), "+f"(d[120]), "+f"(d[121]), "+f"(d[122]), "+f"(d[123]), "+f"(d[124]), "+f"(d[125]), "+f"(d[126]), "+f"(d[127])
    : "l"(da), "l"(db));
}
__device__ __forceinline__ void wgmma_n256_first(float (&d)[128], uint64_t da, uint64_t db) {
  asm volatile("wgmma.mma_async.sync.aligned.m64n256k16.f32.bf16.bf16 "
    "{%0, %1, %2, %3, %4, %5, %6, %7, %8, %9, %10, %11, %12, %13, %14, %15, %16, %17, %18, %19, %20, %21, %22, %23, %24, %25, %26, %27, %28, %29, %30, %31, %32, %33, %34, %35, %36, %37, %38, %39, %40, %41, %42, %43, %44, %45, %46, %47, %48, %49, %50, %51, %52, %53, %54, %55, %56, %57, %58, %59, %60, %61, %62, %63, %64, %65, %66, %67, %68, %69, %70, %71, %72, %73, %74, %75, %76, %77, %78, %79, %80, %81, %82, %83, %84, %85, %86, %87, %88, %89, %90, %91, %92, %93, %94, %95, %96, %97, %98, %99, %100, %101, %102, %103, %104, %105, %106, %107, %108, %109, %110, %111, %112, %113, %114, %115, %116, %117, %118, %119, %120, %121, %122, %123, %124, %125, %126, %127}, "
    "%128, %129, 0, 1, 1, 0, 1;\n"
    : "=f"(d[0]), "=f"(d[1]), "=f"(d[2]), "=f"(d[3]), "=f"(d[4]), "=f"(d[5]), "=f"(d[6]), "=f"(d[7]), "=f"(d[8]), "=f"(d[9]), "=f"(d[10]), "=f"(d[11]), "=f"(d[12]), "=f"(d[13]), "=f"(d[14]), "=f"(d[15]), "=f"(d[16]), "=f"(d[17]), "=f"(d[18]), "=f"(d[19]), "=f"(d[20]), "=f"(d[21]), "=f"(d[22]), "=f"(d[23]), "=f"(d[24]), "=f"(d[25]), "=f"(d[26]), "=f"(d[27]), "=f"(d[28]), "=f"(d[29]), "=f"(d[30]), "=f"(d[31]), "=f"(d[32]), "=f"(d[33]), "=f"(d[34]), "=f"(d[35]), "=f"(d[36]), "=f"(d[37]), "=f"(d[38]), "=f"(d[39]), "=f"(d[40]), "=f"(d[41]), "=f"(d[42]), "=f"(d[43]), "=f"(d[44]), "=f"(d[45]), "=f"(d[46]), "=f"(d[47]), "=f"(d[48]), "=f"(d[49]), "=f"(d[50]), "=f"(d[51]), "=f"(d[52]), "=f"(d[53]), "=f"(d[54]), "=f"(d[55]), "=f"(d[56]), "=f"(d[57]), "=f"(d[58]), "=f"(d[59]), "=f"(d[60]), "=f"(d[61]), "=f"(d[62]), "=f"(d[63]), "=f"(d[64]), "=f"(d[65]), "=f"(d[66]), "=f"(d[67]), "=f"(d[68]), "=f"(d[69]), "=f"(d[70]), "=f"(d[71]), "=f"(d[72]), "=f"(d[73]), "=f"(d[74]), "=f"(d[75]), "=f"(d[76]), "=f"(d[77]), "=f"(d[78]), "=f"(d[79]), "=f"(d[80]), "=f"(d[81]), "=f"(d[82]), "=f"(d[83]), "=f"(d[84]), "=f"(d[85]), "=f"(d[86]), "=f"(d[87]), "=f"(d[88]), "=f"(d[89]), "=f"(d[90]), "=f"(d[91]), "=f"(d[92]), "=f"(d[93]), "=f"(d[94]), "=f"(d[95]), "=f"(d[96]), "=f"(d[97]), "=f"(d[98]), "=f"(d[99]), "=f"(d[100]), "=f"(d[101]), "=f"(d[102]), "=f"(d[103]), "=f"(d[104]), "=f"(d[105]), "=f"(d[106]), "=f"(d[107]), "=f"(d[108]), "=f"(d[109]), "=f"(d[110]), "=f"(d[111]), "=f"(d[112]), "=f"(d[113]), "=f"(d[114]), "=f"(d[115]), "=f"(d[116]), "=f"(d[117]), "=f"(d[118]), "=f"(d[119]), "=f"(d[120]), "=f"(d[121]), "=f"(d[122]), "=f"(d[123]), "=f"(d[124]), "=f"(d[125]), "=f"(d[126]), "=f"(d[127])
    : "l"(da), "l"(db));
}

template <int N> struct WG;
#define DEF_WG(N) template <> struct WG<N> { \
  static __device__ __forceinline__ void mma(float (&d)[N / 2], uint64_t a, uint64_t b) { wgmma_n##N(d, a, b); } \
  static __device__ __forceinline__ void first(float (&d)[N / 2], uint64_t a, uint64_t b) { wgmma_n##N##_first(d, a, b); } };
DEF_WG(128) DEF_WG(256)

constexpr uint64_t DESC_A = (1ull << 62) | ((uint64_t)(1024 >> 4) << 32) | (1ull << 16);
constexpr uint64_t DESC_B = (1ull << 62) | ((uint64_t)(1024 >> 4) << 32) | ((uint64_t)(8192 >> 4) << 16);

struct Ring { int s; uint32_t ph; int wrap; };
template <int NS> __device__ __forceinline__ void ring_next(Ring& r) { r.s = (r.s + 1 == NS) ? 0 : r.s + 1; if (r.s == r.wrap) r.ph ^= 1; }

__device__ __forceinline__ int own_order(int it, int j) {
  return it < 2 ? 2 * j + it : it < 4 ? 2 * (j ^ 1) + it - 2 : ((j >> 1) * 4 + 2 * it - (it < 10 ? 4 : 15)) & 15;
}

template <int V> struct IC { static constexpr int v = V; };
template <int I, int E, class F> __device__ __forceinline__ void static_for(F&& f) { if constexpr (I < E) { f(IC<I>{}); static_for<I + 1, E>(f); } }

template <int N, int NS, int PRE, int LAG, class Pre, class Mid, class Last>
__device__ __forceinline__ void mainloop(float (&acc)[N / 2], int nkb, bool own, Ring& r, uint32_t sb, int wg, int lane, uint32_t rel_base, Pre pre, Mid mid, Last last, int lag_par = 0) {
  constexpr int SLOT = RING / NS;
  const uint32_t full = sb + MISC + (NS == 4 ? B_FULL4 : B_FULL6);
  const uint32_t rel = rel_base + (NS == 4 ? B_EMPTY4 : B_EMPTY6);
  const uint32_t s0 = (sb & 0x3FFFF) >> 4, a0 = s0 + wg * (HALF >> 4);
  int ps;
  auto issue = [&](int it, bool first) {
    const uint64_t da = DESC_A | (a0 + ((own && it < 2) ? (STG + it * BLK) >> 4 : r.s * (SLOT >> 4))), db = DESC_B | (s0 + r.s * (SLOT >> 4) + (BLK >> 4));
    mbar_wait(full + r.s * 8, r.ph);
    wg_arrive();
    if (first) WG<N>::first(acc, da, db); else WG<N>::mma(acc, da, db);
#pragma unroll
    for (int k = 1; k < 4; k++) WG<N>::mma(acc, da + k * 2, db + k * 128);
    wg_commit();
  };
  auto retire = [&](int it) {
    wg_wait<1>();
    if (lane < 2) mbar_arrive_cl(rel + ps * 8);
    ps = r.s;
    ring_next<NS>(r);
  };
  issue(0, true);
  ps = r.s;
  ring_next<NS>(r);
  static_for<1, PRE + 1>([&](auto ic) { issue(ic.v, false); pre(ic); retire(ic.v); });
#pragma unroll 1
  for (int it = PRE + 1; it < nkb; it++) {
    if (LAG && it == nkb - LAG && wg == 1) mbar_wait(sb + MISC + B_LAG, lag_par);
    issue(it, false); mid(it); retire(it);
  }
  if (LAG && wg == 0 && lane == 0) mbar_arrive(sb + MISC + B_LAG);
  last();
  wg_wait<0>();
  if (lane < 2) mbar_arrive_cl(rel + ps * 8);
}

__device__ __forceinline__ uint32_t tag_of(uint32_t ep) { return (ep & 127u) + 1u; }
__device__ __forceinline__ void ln_publish(const float (&v)[64], uint2* st, int j, int row0, int lane, uint32_t ep) {
  float s0 = 0, s1 = 0, s2 = 0, s3 = 0, q0 = 0, q1 = 0, q2 = 0, q3 = 0;
#pragma unroll
  for (int i = 0; i < 16; i++) {
    s0 += v[4 * i]; s1 += v[4 * i + 1]; s2 += v[4 * i + 2]; s3 += v[4 * i + 3];
    q0 = fmaf(v[4 * i], v[4 * i], q0); q1 = fmaf(v[4 * i + 1], v[4 * i + 1], q1); q2 = fmaf(v[4 * i + 2], v[4 * i + 2], q2); q3 = fmaf(v[4 * i + 3], v[4 * i + 3], q3);
  }
  s0 += s1; s2 += s3; q0 += q1; q2 += q3;
  const bool odd = lane & 1;
  float s = (odd ? s2 : s0) + __shfl_xor_sync(~0u, odd ? s0 : s2, 1), q = (odd ? q2 : q0) + __shfl_xor_sync(~0u, odd ? q0 : q2, 1);
  s += __shfl_xor_sync(~0u, s, 2); q += __shfl_xor_sync(~0u, q, 2);
  if ((lane & 3) < 2) st_rlx2(st + j * 128 + row0 + (lane & 1) * 8, __float_as_uint(s), (__float_as_uint(fmaf(s * (-1.f / 128), s, q)) & ~255u) | tag_of(ep));
}
__device__ __forceinline__ void ln_gather(const uint2* st, int row0, int lane, uint32_t ep, float& n0, float& r0, float& n1, float& r1, bool rnd) {
  const uint2* p = st + (lane & 2) * 256 + row0 + (lane & 1) * 8;
  const uint32_t tag = tag_of(ep);
  uint2 a, b, c, d; uint32_t n = 0;
  while (true) {
    a = ld_rlx2(p); b = ld_rlx2(p + 128); c = ld_rlx2(p + 256); d = ld_rlx2(p + 384);
    if ((((a.y ^ tag) | (b.y ^ tag) | (c.y ^ tag) | (d.y ^ tag)) & 255u) == 0) break;
    SPIN_GUARD(n);
  }
  __syncwarp();
  const uint32_t fix = tag ^ 128u;
  float s = (__uint_as_float(a.x) + __uint_as_float(b.x)) + (__uint_as_float(c.x) + __uint_as_float(d.x));
  float q = (__uint_as_float(a.y ^ fix) + __uint_as_float(b.y ^ fix)) + (__uint_as_float(c.y ^ fix) + __uint_as_float(d.y ^ fix));
  q = fmaf(fmaf(__uint_as_float(a.x), __uint_as_float(a.x), __uint_as_float(b.x) * __uint_as_float(b.x)) +
           fmaf(__uint_as_float(c.x), __uint_as_float(c.x), __uint_as_float(d.x) * __uint_as_float(d.x)), 1.f / 128, q);
  s += __shfl_xor_sync(~0u, s, 2); q += __shfl_xor_sync(~0u, q, 2);
  s *= 1.f / 1024;
  const float var = fmaxf(fmaf(-s, s, q * (1.f / 1024)), 0.f);
  float r;
  if (rnd) {
    float sd; asm("sqrt.approx.f32 %0, %1;" : "=f"(sd) : "f"(bf_round(bf_round(var) + 1e-5f)));
    r = rcp(bf_round(sd)); s = bf_round(s);
  } else r = rsqrtf(var + 1e-5f);
  const float nn = -s * r;
  const float ro = __shfl_xor_sync(~0u, r, 1), no = __shfl_xor_sync(~0u, nn, 1);
  const bool odd = lane & 1;
  r0 = odd ? ro : r; n0 = odd ? no : nn; r1 = odd ? r : ro; n1 = odd ? nn : no;
}
__device__ __forceinline__ void load_vec(uint32_t* w, uint32_t sb, int sec, int b, int lane) {
#pragma unroll
  for (int q = 0; q < 2; q++) { uint4 t = lds128(sb + MISC + MODV + sec * 256 + (lane & 3) * 64 + b * 32 + q * 16); w[4 * q] = t.x; w[4 * q + 1] = t.y; w[4 * q + 2] = t.z; w[4 * q + 3] = t.w; }
}
__device__ __forceinline__ void stage_done(uint32_t sb, int wg, int b, int lane) {
  fence_async_smem();
  __syncwarp();
  if (lane == 0) mbar_arrive(sb + MISC + B_RDY + b * 8);
}
__device__ __forceinline__ uint32_t hfma2(uint32_t a, uint32_t b, uint32_t c) { uint32_t r; asm("fma.rn.bf16x2 %0, %1, %2, %3;" : "=r"(r) : "r"(a), "r"(b), "r"(c)); return r; }
__device__ __forceinline__ void ln_apply(const float (&v)[64], const uint2* st, int row0, uint32_t ep, uint32_t sb, int sec_shift, int sec_scale, uint32_t stg_row, int wg, int lane) {
  uint32_t sc[16], sh[16];
#pragma unroll
  for (int b = 0; b < 2; b++) { load_vec(sc + 8 * b, sb, sec_scale, b, lane); load_vec(sh + 8 * b, sb, sec_shift, b, lane); }
  float n0, r0, n1, r1;
  ln_gather(st, row0, lane, ep, n0, r0, n1, r1, sec_shift == 0);
#pragma unroll
  for (int i = 0; i < 16; i += 2) {
    if (i == 8) { const float z = lds32f(sb + MISC + ZERO); n0 += z; n1 += z; }
    uint32_t w[4];
#pragma unroll
    for (int u = 0; u < 2; u++) {
      int q = i + u;
      w[2 * u] = hfma2(pack2(fmaf(v[4 * q], r0, n0), fmaf(v[4 * q + 1], r0, n0)), sc[q], sh[q]);
      w[2 * u + 1] = hfma2(pack2(fmaf(v[4 * q + 2], r1, n1), fmaf(v[4 * q + 3], r1, n1)), sc[q], sh[q]);
    }
    stsm4(stg_row + (i >> 3) * BLK + ((((i & 7) + (lane >> 4)) ^ (lane & 7)) << 4), w[0], w[1], w[2], w[3]);
    if ((i & 7) == 6) { stage_done(sb, wg, i >> 3, lane); }
  }
}
__device__ __forceinline__ uint32_t hmul2(uint32_t a, uint32_t b) { uint32_t r; asm("mul.rn.bf16x2 %0, %1, %2;" : "=r"(r) : "r"(a), "r"(b)); return r; }
__device__ __forceinline__ uint32_t silu_mul2(uint32_t g, uint32_t u) {
  const uint32_t h = hmul2(g, 0x3f003f00u);
  const float h0 = bf_lo(h), h1 = bf_hi(h);
  return hmul2(pack2(fmaf(h0, tanh_fast(h0), h0), fmaf(h1, tanh_fast(h1), h1)), u);
}

__device__ __forceinline__ void gemv_fma(float (&a)[8], uint4 w, float s) {
  a[0] = fmaf(bf_lo(w.x), s, a[0]); a[1] = fmaf(bf_hi(w.x), s, a[1]); a[2] = fmaf(bf_lo(w.y), s, a[2]); a[3] = fmaf(bf_hi(w.y), s, a[3]);
  a[4] = fmaf(bf_lo(w.z), s, a[4]); a[5] = fmaf(bf_hi(w.z), s, a[5]); a[6] = fmaf(bf_lo(w.w), s, a[6]); a[7] = fmaf(bf_hi(w.w), s, a[7]);
}
__device__ __forceinline__ float silu_c(float v) { return bf_round(__fdividef(v, 1.f + __expf(-v))); }
__device__ __forceinline__ float mod_gather(const uint32_t* p, uint32_t ep) {
  const uint32_t tag = tag_of(ep), fix = tag ^ 128u;
  uint32_t a, b, c, d, n = 0;
  while (true) {
    a = ld_rlx1(p); b = ld_rlx1(p + 128); c = ld_rlx1(p + 256); d = ld_rlx1(p + 384);
    if ((((a ^ tag) | (b ^ tag) | (c ^ tag) | (d ^ tag)) & 255u) == 0) break;
    SPIN_GUARD(n);
  }
  return (__uint_as_float(a ^ fix) + __uint_as_float(b ^ fix)) + (__uint_as_float(c ^ fix) + __uint_as_float(d ^ fix));
}
__device__ __forceinline__ void mod_store(uint32_t sb, int sec, int col, float v) {
  v = bf_round(v);
  if (sec == 1) v += 1.f;
  sts16(sb + MISC + MODV + sec * 256 + (((col >> 1) & 3) * 16 + (col >> 3)) * 4 + (col & 1) * 2, __float2bfloat16_rn(v));
}

__global__ void __cluster_dims__(2, 1, 1) __launch_bounds__(384, 1)
fused_kernel(const bf16* __restrict__ cvec, const bf16* __restrict__ wmod, Scratch* gs, int by_sm, const __grid_constant__ Maps maps) {
  extern __shared__ __align__(1024) uint8_t smem_raw[];
  const uint32_t sb = smem_u32(smem_raw);
  const int warp = __shfl_sync(~0u, threadIdx.x >> 5, 0), lane = threadIdx.x & 31;
  const int rank = blockIdx.x & 1;
  uint32_t sm; asm volatile("mov.u32 %0, %%smid;" : "=r"(sm));
  const int t = sm >> 1, v = t < 32 ? t : t < 60 ? t + 1 + (((t - 32) * 37) >> 8) : (t - 58) * 8;
  const int gr = 0x71546320u >> ((v & 7) * 4);
  const int cid = !by_sm ? (blockIdx.x >> 1) - 2 : (t & ~1) == 60 ? t - 62 : (gr & 4) * 8 + (v >> 3) * 4 + (gr & 3);
  const bool extra = cid < 0;
  const int bid = cid * 2 + rank;
  const int m = cid >> 2, j = (cid & 3) * 2 + rank;
  const uint32_t bar = sb + MISC;

  if (warp >= 8) {
    asm volatile("setmaxnreg.dec.sync.aligned.u32 40;");
    if (extra) {
      if (warp == 8) {
        if (lane == 0) { for (int s = 0; s < 6; s++) { mbar_init(bar + B_FULL6 + s * 8, 1); mbar_init(bar + B_EMPTY6 + s * 8, 8); } fence_async_smem(); }
        __syncwarp();
        asm volatile("bar.arrive 2, 288;" ::: "memory");
        __nanosleep(XSLEEP);
#pragma unroll 1
        for (int it = 0, s = 0, par = 1; it < 64; it++) {
          mbar_wait(bar + B_EMPTY6 + s * 8, par);
          expect_e(bar + B_FULL6 + s * 8, 32768); tma_3d_e(sb + s * 32768, &maps.wmod, bar + B_FULL6 + s * 8, 0, (it & 15) * 64, 12 + (it >> 4) * 4 + bid);
          if (++s == 6) { s = 0; par ^= 1; }
        }
      }
    } else if (warp < 10) {
      uint32_t f6 = bar + B_FULL6, d6 = sb + (warp == 8 ? BLK : rank * HALF), p6 = 1;
      auto next6 = [&]() { f6 += 8; d6 += 32768; if (f6 == bar + B_FULL6 + 48) { f6 -= 48; d6 -= RING; p6 ^= 1; } };
      auto drained4 = [&](int q, int late) { if (q < 5) mbar_wait(bar + B_EMPTY4 + (((late ? 0x10332 : 0x32110) >> (4 * q)) & 3) * 8, 1); };
      auto drained6 = [&](int q) { if (q < 3) mbar_wait(bar + B_EMPTY6 + ((0x154 >> (4 * q)) & 7) * 8, q >> 1); };
      auto skip6 = [&]() { mbar_wait(f6 + 48, p6); expect_e(f6, 0); next6(); };
      if (warp == 8) {
        const uint32_t t_start = clock();
        if (lane == 0) {
          if (sb & 1023) bail();
          for (int b = 0; b < 2; b++) mbar_init(bar + B_X + b * 8, 1);
          for (int s = 0; s < 4; s++) { mbar_init(bar + B_FULL4 + s * 8, 2); mbar_init(bar + B_EMPTY4 + s * 8, 16); }
          for (int s = 0; s < 6; s++) { mbar_init(bar + B_FULL6 + s * 8, 2); mbar_init(bar + B_EMPTY6 + s * 8, 16); }
          for (int b = 0; b < 2; b++) { mbar_init(bar + B_RDY + b * 8, 8); mbar_init(bar + B_FREE + b * 8, 1); mbar_init(bar + B_HH + b * 8, 1); }
          mbar_init(bar + B_MOD, 1); mbar_init(bar + B_LAG, 4); mbar_init(bar + B_HALO, 2); mbar_init(bar + B_ALL, 1); mbar_init(bar + B_HH2, 1);
          asm volatile("st.shared.u32 [%0], 0;" :: "r"(bar + ZERO) : "memory");
          asm volatile("fence.mbarrier_init.release.cluster;" ::: "memory");
          fence_async_smem();
        }
        __syncwarp();
        cl_arrive_relaxed();
        while ((uint32_t)clock() - t_start < XDELAY) {}
        for (int b = 0; b < 2; b++) { expect_e(bar + B_X + b * 8, BLK); tma_3d_e(sb + STG + b * BLK, &maps.x, bar + B_X + b * 8, j * 128 + b * 64, m * 64, 0); }
        mbar_wait(bar + B_X + 8, 0);
#pragma unroll 1
        for (int ph = 0; ph < 2; ph++) {
          const CUtensorMap* const m0 = ph ? &maps.w1 : &maps.wqkv;
#pragma unroll 1
          for (int it = 0; it < (ph ? 48 : 16); it++) {
            const int s = (it + 2 * ph) & 3;
            int a0 = (ph ? it & 48 : 16) + 2 * j, a1 = ph ? a0 : a0 + 16, k0 = (it < 16 ? own_order(it, j) : it & 15) * 64;
            uint32_t full = bar + B_FULL4 + s * 8, d = sb + s * 49152 + BLK;
            if (ph) drained6(it);
            mbar_wait(full + 32, ~(it >> 2) & 1);
            tma_3d_e(d, m0, full, 0, k0, a0);
            if (it < 4) { const uint32_t t0 = clock(); while ((uint32_t)clock() - t0 < GAP) {} }
            tma_3d_e(d + BLK, m0 + ph, full, 0, k0, a1);
            expect_e(full, 2 * BLK);
            if (it < 4) { const uint32_t t0 = clock(); while ((uint32_t)clock() - t0 < GAP) {} }
            if (it >= 44) {
              if (it == 44) { mbar_wait(bar + B_FREE, 0); mbar_wait(bar + B_FREE + 8, 0); expect_e(bar + B_X, 2 * BLK); }
              bulk_ld_e(sb + STG + (it - 44) * HALF, gs->x1 + bid * 2048 + (it - 44) * 512, HALF, bar + B_X);
            }
          }
          const CUtensorMap* const m1 = ph ? &maps.w1s : &maps.wqkv;
          const int a = ph ? 48 + j : 2 * j;
#pragma unroll 1
          for (int k0 = 0; k0 < 1024; k0 += 64) {
            drained4(k0 >> 6, ph);
            mbar_wait(f6 + 48, p6);
            tma_3d_e(d6, m1, f6, 0, k0, a);
            if (ph) tma_3d_e(d6 + HALF, &maps.w3s, f6, 0, k0, a);
            expect_e(f6, BLK);
            next6();
          }
          if (ph) break;
#pragma unroll 1
          for (int it = 0; it < 16; it++) {
            const int k0 = own_order(it, j) * 64;
            mbar_wait(f6 + 48, p6);
            tma_3d_e(d6, &maps.wo, f6, 0, k0, 2 * j);
            expect_e(f6, BLK);
            next6();
          }
          skip6();
        }
#pragma unroll 1
        for (int k0 = 0; k0 < F_; k0 += 64) {
          mbar_wait(f6 + 48, p6);
          tma_3d_e(d6, &maps.w2, f6, 0, k0, 2 * j);
          expect_e(f6, BLK);
          next6();
        }
      } else {
        if (lane < 9) prefetch_map(&maps.x + lane);
        const uint32_t ep = gs->epoch[blockIdx.x] + 1;
        cl_arrive_relaxed(); cl_wait();
        auto run6 = [&](const uint4* src, int n, int sw) {
          src += rank * 512;
#pragma unroll 1
          for (int it = 0; it < n; it++) {
            if (sw >= 0) drained4(it, sw);
            mbar_wait(f6 + 48, p6);
            bulk_ld_mc_e(d6, src, HALF, f6);
            expect_e(f6, BLK);
            next6();
            src += 1024;
          }
        };
        uint32_t ready = 0;
        auto need = [&](int e, uint32_t mask) {
          if (!(ready & mask)) {
            uint32_t n = 0;
            do { ready = __ballot_sync(~0u, ld_acquire(gs->flag + (m * 128 + e * 16 + (lane & 14)) * FS) == ep); SPIN_GUARD(n); } while (!(ready & mask));
            fence_async_global();
          }
        };
        auto fresh = [&](int e, int it, uint32_t full, uint32_t empty, int par, uint32_t slot, uint4* src) {
          mbar_wait(empty, par);
          expect_e(full, it < 2 ? 0 : BLK);
          if (it >= 4) {
            const int kb = own_order(it, j);
            if (it < 10) need(e, 1u << kb); else if (it == 10) mbar_wait(bar + B_ALL, e & 1);
            bulk_ld_mc_e(slot + rank * HALF, src + kb * 1024 + rank * 512, HALF, full);
          } else if (it >= 2) {
            const int b = it > 2;
            const uint32_t to_peer = mapa(sb, rank ^ 1) - sb;
            const bool push = b && e != 1;
            mbar_wait(bar + (push ? B_RDY : B_FREE) + b * 8, e & 1);
            if (push) bulk_push_e(slot + to_peer, sb + STG + BLK, BLK, full + to_peer);
            else { fence_async_global(); bulk_ld_e(slot + to_peer, src + (2 * j + b) * 1024, BLK, full + to_peer); }
          } else ready = 0;
        };
        uint4* const h = gs->h + m * 16384;
#pragma unroll 1
        for (int e = 0; e < 3; e++) {
#pragma unroll 1
          for (int it = 0; it < 16; it++) {
            const int s = (it + e) & 3;
            const uint32_t full = e == 1 ? f6 : bar + B_FULL4 + s * 8;
            if (e == 2) drained6(it);
            fresh(e, it, full, full + (e == 1 ? 48 : 32), e == 1 ? p6 : ~(it >> 2) & 1, e == 1 ? d6 - rank * HALF : sb + s * 49152, e == 1 ? gs->o + m * 16384 : h);
            if (e == 1) next6();
          }
          if (e == 1) { skip6(); continue; }
#pragma unroll 1
          for (int it = 16; it < 16 + 16 * e; it++) {
            const int s = (it + 2) & 3;
            const uint32_t full = bar + B_FULL4 + s * 8;
            mbar_wait(full + 32, ~(it >> 2) & 1);
            bulk_ld_mc_e(sb + s * 49152 + rank * HALF, h + (it & 15) * 1024 + rank * 512, HALF, full);
            expect_e(full, BLK);
          }
          run6(h, 16, e);
        }
#pragma unroll 1
        for (int q = 0; q < 3; q++) {
          mbar_wait(bar + (q == 2 ? B_HH2 : B_HH + q * 8), 0);
          run6(gs->hh + m * 57344 + (64 - (64 >> q)) * 1024, 32 >> q, -1);
        }
      }
    } else {
      const int b = warp - 10;
      const uint32_t ep = gs->epoch[blockIdx.x] + 1;
      const uint32_t stg = sb + STG + b * BLK;
      cl_arrive_relaxed(); cl_wait();
      auto all_there = [&](int u, uint32_t done) {
        const uint32_t* fl = gs->flag + u * FS;
        uint32_t n = 0;
        while (!__all_sync(~0u, ld_acquire(fl) == ep)) { __nanosleep(100); SPIN_GUARD(n); }
        fence_async_global();
        if (lane == 0) mbar_arrive(done);
      };
      auto fetch_mod = [&](int sec) {
        const uint4* p = (const uint4*)(gs->modv + (sec - 2) * 1024 + j * 128) + lane;
        uint4 v0, v1; uint32_t n = 0;
        while (true) {
          v0 = ld_rlx4(p); v1 = ld_rlx4(p + 32);
          if (v0.y == ep && v0.w == ep && v1.y == ep && v1.w == ep) break;
          SPIN_GUARD(n);
        }
        const uint32_t d = sb + MISC + MODV + sec * 256 + ((lane & 3) * 16 + (lane >> 2)) * 4;
        asm volatile("st.shared.u32 [%0], %1;" :: "r"(d), "r"(__byte_perm(v0.x, v0.z, 0x7632)) : "memory");
        asm volatile("st.shared.u32 [%0], %1;" :: "r"(d + 32), "r"(__byte_perm(v1.x, v1.z, 0x7632)) : "memory");
        __syncwarp();
      };
#pragma unroll 1
      for (int e = 0; e < 7 - b; e++) {
        if (e < 3) {
          uint4* const dst = (e == 1 ? gs->o : gs->h) + m * 16384 + (2 * j + b) * 1024;
          uint32_t* const fl = gs->flag + (m * 128 + e * 16 + 2 * j + b) * FS;
          if (b) {
            mbar_wait(bar + B_FREE, e & 1);
            const uint32_t t0 = clock();
            while ((uint32_t)clock() - t0 < (e == 1 ? B1D : B1P)) {}
          }
          mbar_wait(bar + B_RDY + b * 8, e & 1);
          if (elect()) {
            bulk_st(dst, stg, BLK);
            bulk_commit();
            bulk_wait_all();
            mbar_arrive(bar + B_FREE + b * 8);
            st_release(fl, ep);
          }
        } else if (lane == 0) {
          {
            const int kb = (e < 6 ? 2 * (8 * (e - 3) + j) : 48 + j) + b;
            mbar_wait(bar + B_RDY + b * 8, e & 1);
#pragma unroll 1
            for (int q = 0; q < NPIECE; q++) { if (q) __nanosleep(PSLEEP); bulk_st(gs->hh + m * 57344 + kb * 1024 + q * (1024 / NPIECE), stg + q * (BLK / NPIECE), BLK / NPIECE); }
            bulk_commit();
            bulk_wait_all();
            mbar_arrive(bar + B_FREE + b * 8);
            st_release(gs->flag + (m * 128 + U_HH + kb) * FS, ep);
          }
        }
        __syncwarp();
        if (e < 3 && b) all_there(m * 128 + e * 16 + (lane & 15), bar + B_ALL);
        if (e == 4 && b) all_there(m * 128 + U_HH + lane, bar + B_HH);
        if (!b && (e == 1 || e == 2)) {
#pragma unroll 1
          for (int sec = e == 1 ? 2 : 5; sec < 4 + e; sec++) fetch_mod(sec);
          if (e == 1) { if (lane == 0) mbar_arrive(bar + B_MOD); }
        }
        if (e == 0) {
          mbar_wait(bar + B_EMPTY6 + 24, 0);
          __nanosleep(HSLEEP);
#pragma unroll 1
          for (int w = 0; w < 4; w++) {
            const uint4* hp = gs->halo + ((m * 8 + j) * 2 + (w & 1)) * 512 + b * 256 + (w >> 1) * 128 + lane;
            uint4 q[4] = {}; uint32_t n = 0;
            while (m > 0) {
              bool ok = true;
#pragma unroll
              for (int i = 0; i < 4; i++) q[i] = ld_rlx4(hp + i * 32);
#pragma unroll
              for (int i = 0; i < 4; i++) ok = ok && q[i].y == ep && q[i].w == ep;
              if (ok) break;
              SPIN_GUARD(n);
            }
#pragma unroll
            for (int i = 0; i < 2; i++) sts128(stg + lane * 16 + (w & 1) * HALF + (w >> 1) * 1024 + i * 512, q[2 * i].x, q[2 * i + 1].x, q[2 * i].z, q[2 * i + 1].z);
          }
          __syncwarp();
          if (lane == 0) mbar_arrive(bar + B_HALO);
        }
      }
      if (b) { all_there(m * 128 + U_HH + 32 + (lane & 15), bar + B_HH + 8); all_there(m * 128 + U_HH + 48 + (lane & 7), bar + B_HH2); }
    }
  } else {
    const int wg = warp >> 2, wq = warp & 3, tid = threadIdx.x;
    const int g = lane >> 2, c = lane & 3;
    const int sec0 = (m >> 1) & 1, hf0 = m & 1, ks0 = (m >> 2) & 3;
    uint4 wv[8];
    uint32_t ep0; uint16_t cv_;
    asm volatile("ld.global.nc.u16 %0, [%1];" : "=h"(cv_) : "l"(cvec + ks0 * 256 + warp * 32 + lane));
    asm volatile("ld.global.u32 %0, [%1];" : "=r"(ep0) : "l"(gs->epoch + (blockIdx.x | (lane & by_sm & 2))));
    if (!extra) {
      const bf16* wp = wmod + (size_t)(ks0 * 256 + warp * 32 + (lane >> 3)) * 6144 + sec0 * 1024 + j * 128 + hf0 * 64 + (lane & 7) * 8;
#pragma unroll
      for (int i = 0; i < 8; i++) wv[i] = ldg_nc(wp + (size_t)i * 4 * 6144);
      cl_arrive_relaxed();
    }
    asm volatile("setmaxnreg.inc.sync.aligned.u32 232;" ::: "memory");
    if (__builtin_expect(extra, 0)) {
      const uint32_t ep = ep0 + 1;
      float sv[4];
#pragma unroll
      for (int p = 0; p < 4; p++) sv[p] = silu_c(__bfloat162float(cvec[64 * (4 * p + (lane >> 3)) + 8 * warp + (lane & 7)]));
      named_bar(2, 288);
      int s = 0, par = 0;
#pragma unroll 1
      for (int sec = 0; sec < 4; sec++) {
        float a[8] = {0, 0, 0, 0, 0, 0, 0, 0};
#pragma unroll 1
        for (int it = 0; it < 16; it++) {
          const float sc = it < 4 ? sv[0] : it < 8 ? sv[1] : it < 12 ? sv[2] : sv[3];
          mbar_wait(bar + B_FULL6 + s * 8, par);
          uint4 w[8];
#pragma unroll
          for (int i = 0; i < 8; i++) w[i] = lds128(sb + s * 32768 + (warp * 8 + i) * 512 + lane * 16);
#pragma unroll
          for (int i = 0; i < 8; i++) gemv_fma(a, w[i], __shfl_sync(~0u, sc, (it & 3) * 8 + i));
          if (lane == 0) mbar_arrive(bar + B_EMPTY6 + s * 8);
          if (++s == 6) { s = 0; par ^= 1; }
        }
        const uint32_t red = sb + STG + sec * 8192;
        sts128(red + warp * 1024 + lane * 32, __float_as_uint(a[0]), __float_as_uint(a[1]), __float_as_uint(a[2]), __float_as_uint(a[3]));
        sts128(red + warp * 1024 + lane * 32 + 16, __float_as_uint(a[4]), __float_as_uint(a[5]), __float_as_uint(a[6]), __float_as_uint(a[7]));
        named_bar(1, 256);
        float t = 0;
#pragma unroll
        for (int q = 0; q < 8; q++) t += lds32f(red + q * 1024 + tid * 4);
        t = bf_round(t);
        if (sec == 2) t = bf_round(t + 1.f);
        st_rlx2(gs->modv + sec * 1024 + (bid + 4) * 256 + tid, __float_as_uint(t), ep);
      }
      if (tid == 0) gs->epoch[blockIdx.x] = ep;
      return;
    }
    const int row0 = wg * 64 + wq * 16 + g;
    if (c < 2) st_rlx2(gs->stat + m * 1024 + j * 128 + row0 + c * 8, 0, 0);
    cl_wait();
    uint32_t ep;
    asm volatile("add.u32 %0, %1, 1;" : "=r"(ep) : "r"(ep0) : "memory");
    const float sc_ = silu_c(__uint_as_float((uint32_t)cv_ << 16));
    const uint32_t rel = mapa(bar, (lane & 1) ^ rank);
    const uint32_t stg_row = sb + STG + (wg * 64 + wq * 16 + (lane & 15)) * 128;
    const uint32_t fre = bar + B_FREE;
    Ring r4{0, 0, 0}, r6{0, 0, 0};
    auto none = [](auto) {};
    uint32_t xk[32];
    {
      float a[8] = {0, 0, 0, 0, 0, 0, 0, 0};
#pragma unroll
      for (int i = 0; i < 8; i++) gemv_fma(a, wv[i], __shfl_sync(~0u, sc_, i * 4 + (lane >> 3)));
#pragma unroll
      for (int i = 0; i < 8; i++) { a[i] += __shfl_xor_sync(~0u, a[i], 8); a[i] += __shfl_xor_sync(~0u, a[i], 16); }
      if (lane < 8) {
        sts128(sb + RED_OFF + warp * 256 + lane * 32, __float_as_uint(a[0]), __float_as_uint(a[1]), __float_as_uint(a[2]), __float_as_uint(a[3]));
        sts128(sb + RED_OFF + warp * 256 + lane * 32 + 16, __float_as_uint(a[4]), __float_as_uint(a[5]), __float_as_uint(a[6]), __float_as_uint(a[7]));
      }
      named_bar(1, 256);
      if (tid < 64) {
        float s = 0;
#pragma unroll
        for (int w = 0; w < 8; w++) s += lds32f(sb + RED_OFF + w * 256 + tid * 4);
        st_rlx1(gs->modp + ((j * 2 + sec0) * 4 + ks0) * 128 + hf0 * 64 + tid, (__float_as_uint(s) & ~255u) | tag_of(ep));
      }
      float v[64];
      mbar_wait(bar + B_X, 0); mbar_wait(bar + B_X + 8, 0);
#pragma unroll
      for (int i = 0; i < 16; i += 2) {
        uint32_t w0, w1, w2, w3;
        ldsm4(stg_row + (i >> 3) * BLK + ((((i & 7) + (lane >> 4)) ^ (lane & 7)) << 4), w0, w1, w2, w3);
        xk[2 * i] = w0; xk[2 * i + 1] = w1; xk[2 * i + 2] = w2; xk[2 * i + 3] = w3;
        v[4 * i] = bf_lo(w0); v[4 * i + 1] = bf_hi(w0); v[4 * i + 2] = bf_lo(w1); v[4 * i + 3] = bf_hi(w1);
        v[4 * i + 4] = bf_lo(w2); v[4 * i + 5] = bf_hi(w2); v[4 * i + 6] = bf_lo(w3); v[4 * i + 7] = bf_hi(w3);
      }
      ln_publish(v, gs->stat + m * 1024, j, row0, lane, ep);
      mod_store(sb, tid >> 7, tid & 127, mod_gather(gs->modp + (j * 2 + (tid >> 7)) * 512 + (tid & 127), ep));
      named_bar(1, 256);
      ln_apply(v, gs->stat + m * 1024, row0, ep, sb, 0, 1, stg_row, wg, lane);
      named_bar(1, 256);
    }
    {
      uint32_t kf[32], vf[32], pv[32];
      const bool first = wq == 0 && m == 0;
      const uint32_t xa = sb + STG + wg * HALF + wq * 2048 + lane * 16;
      {
        float acc[128];
        mainloop<256, 4, 0, 0>(acc, 16, true, r4, sb, wg, lane, rel, none, none, [&] {
          mbar_wait(fre + 8, 0);
          if (c < 2) st_rlx2(gs->stat + (16 + m) * 1024 + j * 128 + row0 + c * 8, 0, 0);
        });
#pragma unroll
        for (int i = 0; i < 32; i++) { kf[i] = pack2(acc[2 * i], acc[2 * i + 1]); vf[i] = pack2(acc[64 + 2 * i], acc[65 + 2 * i]); }
      }
      float acc[64];
      constexpr int QP = 2;
      mainloop<128, 6, 8 / QP, 0>(acc, 16, false, r6, sb, wg, lane, rel, [&](auto ic) {
        constexpr int q = (ic.v - 1) * QP;
#pragma unroll
        for (int i = 4 * q; i < 4 * (q + QP); i++) vf[i] = movm(vf[i]);
        if (wq == 3) {
          if (m < 15) {
            uint4* hp = gs->halo + (((m + 1) * 8 + j) * 2 + wg) * 512 + lane;
#pragma unroll
            for (int i = 2 * q; i < 2 * (q + QP); i++) st_rlx4(hp + i * 32, kf[2 * i + 1], ep, vf[2 * i + 1], ep);
          }
        } else {
#pragma unroll
          for (int i = q; i < q + QP; i++) sts128(xa + 2048 + (i >> 2) * BLK + (i & 3) * 512, kf[4 * i + 1], kf[4 * i + 3], vf[4 * i + 1], vf[4 * i + 3]);
        }
      }, none, [&] {
        named_bar(2 + wg, 128);
        if (wq == 0) mbar_wait(bar + B_HALO, 0);
#pragma unroll
        for (int i = 0; i < 8; i++) {
          uint4 q = lds128(xa + (i >> 2) * BLK + (i & 3) * 512);
          pv[4 * i] = q.x; pv[4 * i + 1] = q.y; pv[4 * i + 2] = q.z; pv[4 * i + 3] = q.w;
        }
        __syncwarp();
      });
      int gz = g;
#pragma unroll
      for (int b = 0; b < 2; b++) {
        const bool up0 = 2 * c > gz, up1 = 2 * c + 1 > gz;
        const uint32_t mup = (up0 ? 0xffffu : 0u) | (up1 ? 0xffff0000u : 0u);
        float l[2][4], mx[4];
#pragma unroll
        for (int h = 0; h < 2; h++) {
          uint32_t q[8];
          const int k = 16 * b + 8 * h;
#pragma unroll
          for (int i = 0; i < 8; i++) q[i] = pack2(acc[2 * k + 2 * i], acc[2 * k + 2 * i + 1]);
          float s0[4], s1[4], s2[4];
          mma16z(s0, q[0], q[1], q[2], q[3], pv[k], pv[k + 1]); mma16z(s1, q[0], q[1], q[2], q[3], kf[k], kf[k + 2]); mma16z(s2, q[0], q[1], q[2], q[3], kf[k + 1], kf[k + 3]);
          mma16(s0, q[4], q[5], q[6], q[7], pv[k + 4], pv[k + 5]); mma16(s1, q[4], q[5], q[6], q[7], kf[k + 4], kf[k + 6]); mma16(s2, q[4], q[5], q[6], q[7], kf[k + 5], kf[k + 7]);
          if (first) { s0[0] = -INFINITY; s0[1] = -INFINITY; }
          l[h][0] = up0 ? s0[0] : s1[0]; l[h][1] = up1 ? s0[1] : s1[1]; l[h][2] = up0 ? s1[2] : s2[2]; l[h][3] = up1 ? s1[3] : s2[3];
          mx[2 * h] = fmaxf(l[h][0], l[h][1]); mx[2 * h + 1] = fmaxf(l[h][2], l[h][3]);
        }
#pragma unroll
        for (int o = 1; o < 4; o <<= 1) {
#pragma unroll
          for (int h = 0; h < 4; h++) mx[h] = fmaxf(mx[h], __shfl_xor_sync(~0u, mx[h], o));
        }
#pragma unroll
        for (int h = 0; h < 2; h++) {
          const float n0 = -mx[2 * h] * SCL, n1 = -mx[2 * h + 1] * SCL;
          const uint32_t pa = pack2(ex2(fmaf(l[h][0], SCL, n0)), ex2(fmaf(l[h][1], SCL, n0))), pb = pack2(ex2(fmaf(l[h][2], SCL, n1)), ex2(fmaf(l[h][3], SCL, n1)));
          float sm[4];
          mma8z(sm, pa, pb, 0x3f803f80u);
          const float ia = rcp(sm[0]), ib = rcp(sm[2]);
#pragma unroll
          for (int i = 8 * b + 4 * h; i < 8 * b + 4 * h + 4; i += 2) {
            uint32_t of[4];
#pragma unroll
            for (int d = 0; d < 2; d++) {
              float o[4];
              mma16z(o, pa & ~mup, pb & mup, 0u, pb & ~mup, vf[2 * (i + d)], vf[2 * (i + d) + 1]);
              mma8(o, pa & mup, 0u, pv[2 * i + 2 + d]);
              of[2 * d] = pack2(o[0] * ia, o[1] * ia); of[2 * d + 1] = pack2(o[2] * ib, o[3] * ib);
            }
            stsm4(stg_row + b * BLK + ((((i & 7) + (lane >> 4)) ^ (lane & 7)) << 4), of[0], of[1], of[2], of[3]);
          }
        }
        stage_done(sb, wg, b, lane);
        if (b == 0) gz += __float_as_uint(lds32f(bar + ZERO));
      }
      named_bar(1, 256);
    }
    uint32_t pk[64];
    {
      float acc[64];
      mainloop<128, 6, 0, 0>(acc, 16, true, r6, sb, wg, lane, rel, none, none, [&] {
        mbar_wait(bar + B_MOD, 0); mbar_wait(fre + 8, 1);
        load_vec(pk + 32, sb, 2, 0, lane); load_vec(pk + 40, sb, 2, 1, lane);
#pragma unroll
        for (int i = 0; i < 32; i++) { pk[i] = xk[i]; asm volatile("" : "+r"(pk[i])); }
      });
#pragma unroll
      for (int i = 0; i < 32; i++) {
        acc[2 * i] = fmaf(acc[2 * i], bf_lo(pk[32 + (i >> 1)]), bf_lo(pk[i]));
        acc[2 * i + 1] = fmaf(acc[2 * i + 1], bf_hi(pk[32 + (i >> 1)]), bf_hi(pk[i]));
      }
      ln_publish(acc, gs->stat + (16 + m) * 1024, j, row0, lane, ep);
      mbar_wait(bar + B_FULL6 + 16, 1);
      if (lane < 2) mbar_arrive_cl(rel + B_EMPTY6 + 16);
      ring_next<6>(r6);
#pragma unroll
      for (int i = 0; i < 32; i++) { pk[i] = pack2(acc[2 * i], acc[2 * i + 1]); pk[32 + i] = 0; }
      ln_apply(acc, gs->stat + (16 + m) * 1024, row0, ep, sb, 3, 4, stg_row, wg, lane);
      named_bar(1, 256);
    }
    auto swiglu = [&](int q, int uo, int par) {
      if ((q & 3) == 0 && par >= 0) mbar_wait(fre + 2 * q, par);
      uint32_t w[4];
#pragma unroll
      for (int u = 0; u < 4; u++) w[u] = silu_mul2(pk[4 * q + u], pk[uo + 4 * q + u]);
      stsm4(stg_row + (q >> 2) * BLK + ((((2 * q & 7) + (lane >> 4)) ^ (lane & 7)) << 4), w[0], w[1], w[2], w[3]);
    };
    r4.s = r4.wrap = 2;
#pragma unroll 1
    for (int t = 0; t < 3; t++) {
      float acc[128];
      mainloop<256, 4, 4, 1>(acc, 16, t == 0, r4, sb, wg, lane, rel, [&](auto ic) {
        if (t) {
          if (ic.v == 3) stage_done(sb, wg, 0, lane);
          swiglu(2 * ic.v - 2, 32, ~t & 1); swiglu(2 * ic.v - 1, 32, 0);
        }
      }, [&](int it) {
        if (t && it == 5) stage_done(sb, wg, 1, lane);
#pragma unroll
        for (int i = 0; i < 8; i++)
          if (t == 0 && it == 8 + i) gs->x1[bid * 2048 + (i >> 2) * 1024 + warp * 128 + (i & 3) * 32 + lane] = make_uint4(pk[4 * i], pk[4 * i + 1], pk[4 * i + 2], pk[4 * i + 3]);
      }, [&] { if (t == 0) fence_async_global(); else if (t == 2) mbar_wait(bar + B_X, 1); }, t & 1);
#pragma unroll
      for (int i = 0; i < 64; i++) pk[i] = pack2(acc[2 * i], acc[2 * i + 1]);
    }
    uint32_t x1[32];
    {
      float acc[64];
      mainloop<128, 6, 10, 1>(acc, 16, false, r6, sb, wg, lane, rel, [&](auto ic) {
        constexpr int b = ic.v > 5, q = ic.v - 5 * b;
        if (q == 1) {
          if (b) stage_done(sb, wg, 0, lane);
#pragma unroll
          for (int i = 4 * b; i < 4 * b + 4; i++) { const uint4 x = lds128(sb + STG + b * BLK + warp * 2048 + (i & 3) * 512 + lane * 16); x1[4 * i] = x.x; x1[4 * i + 1] = x.y; x1[4 * i + 2] = x.z; x1[4 * i + 3] = x.w; }
          __syncwarp();
        } else swiglu(4 * b + q - 2, 32, -1);
      }, [&](int it) { if (it == 11) stage_done(sb, wg, 1, lane); }, [] {}, 1);
#pragma unroll
      for (int i = 0; i < 32; i++) pk[i] = pack2(acc[2 * i], acc[2 * i + 1]);
    }
    {
      float acc[64];
      mainloop<128, 6, 4, TAILLAG>(acc, 56, false, r6, sb, wg, lane, rel, [&](auto ic) { swiglu(ic.v - 1, 16, 1); },
                                   [&](int it) { if (it == 5) stage_done(sb, wg, 0, lane); }, [&] {
        load_vec(pk + 32, sb, 5, 0, lane); load_vec(pk + 40, sb, 5, 1, lane);
        mbar_wait(fre, 0); mbar_wait(fre + 8, 1);
      }, 0);
      __syncwarp();
      cl_arrive_relaxed();
#pragma unroll
      for (int i = 0; i < 16; i += 2) {
        uint32_t w[4];
#pragma unroll
        for (int u = 0; u < 4; u++) {
          const int q = 2 * i + u;
          w[u] = pack2(fmaf(acc[2 * q], bf_lo(pk[32 + (q >> 1)]), bf_lo(x1[q])), fmaf(acc[2 * q + 1], bf_hi(pk[32 + (q >> 1)]), bf_hi(x1[q])));
        }
        stsm4(stg_row + (i >> 3) * BLK + ((((i & 7) + (lane >> 4)) ^ (lane & 7)) << 4), w[0], w[1], w[2], w[3]);
        if ((i & 7) == 6) {
          fence_async_smem();
          named_bar(2 + wg, 128);
          if (wq == 0 && elect()) { tma_store_3d(&maps.out, sb + STG + (i >> 3) * BLK + wg * HALF, j * 128 + (i >> 3) * 64, m * 64, wg); bulk_commit(); }
          if (i < 8) x1[16] |= __float_as_uint(lds32f(bar + ZERO));
        }
      }
      if (wq == 0) bulk_wait_read();
      if (tid == 0) gs->epoch[blockIdx.x] = ep;
      cl_wait();
    }
  }
}

typedef CUresult (*EncodeFn)(CUtensorMap*, CUtensorMapDataType, cuuint32_t, void*, const cuuint64_t*, const cuuint64_t*, const cuuint32_t*, const cuuint32_t*,
                             CUtensorMapInterleave, CUtensorMapSwizzle, CUtensorMapL2promotion, CUtensorMapFloatOOBfill);

void make_map(EncodeFn fn, CUtensorMap* mp, const void* base, uint64_t d0, uint64_t d1, uint64_t d2, uint64_t s1, uint64_t s2, uint32_t b2, uint32_t b0 = 64) {
  cuuint64_t d[3] = {d0, d1, d2}, s[2] = {s1, s2};
  cuuint32_t b[3] = {b0, 64, b2}, e[3] = {1, 1, 1};
  fn(mp, CU_TENSOR_MAP_DATA_TYPE_BFLOAT16, 3, (void*)base, d, s, b, e, CU_TENSOR_MAP_INTERLEAVE_NONE, b0 == 64 ? CU_TENSOR_MAP_SWIZZLE_128B : CU_TENSOR_MAP_SWIZZLE_NONE,
     CU_TENSOR_MAP_L2_PROMOTION_L2_128B, CU_TENSOR_MAP_FLOAT_OOB_FILL_NONE);
}

__global__ void probe_kernel() {}
int max_clusters(int size) {
  cudaLaunchConfig_t cfg = {};
  cudaLaunchAttribute at;
  at.id = cudaLaunchAttributeClusterDimension; at.val.clusterDim.x = size; at.val.clusterDim.y = 1; at.val.clusterDim.z = 1;
  cfg.gridDim = dim3(size * 66); cfg.blockDim = dim3(384); cfg.dynamicSmemBytes = SMEM_BYTES; cfg.attrs = &at; cfg.numAttrs = 1;
  int n = 0;
  if (cudaOccupancyMaxActiveClusters(&n, probe_kernel, &cfg) != cudaSuccess) { cudaGetLastError(); return 0; }
  return n;
}

}

extern "C" void kernel_launch(void* const* d_in, const int* in_sizes, int n_in, void* d_out, int out_size) {
  static EncodeFn fn = nullptr;
  static int by_sm = 0;
  static Scratch* gs = nullptr;
  if (!fn) {
    void* p = nullptr; cudaDriverEntryPointQueryResult q;
    cudaGetDriverEntryPoint("cuTensorMapEncodeTiled", &p, cudaEnableDefault, &q);
    fn = (EncodeFn)p;
    cudaFuncSetAttribute(fused_kernel, cudaFuncAttributeMaxDynamicSharedMemorySize, SMEM_BYTES);
    int dev = 0, sms = 0;
    cudaGetSymbolAddress((void**)&gs, g_scratch);
    cudaGetDevice(&dev);
    cudaDeviceGetAttribute(&sms, cudaDevAttrMultiProcessorCount, dev);
    cudaFuncSetAttribute(probe_kernel, cudaFuncAttributeMaxDynamicSharedMemorySize, SMEM_BYTES);
    by_sm = sms == 132 && max_clusters(2) == 66 && max_clusters(4) == 30 && max_clusters(6) == 17 && max_clusters(8) == 15;
  }
  Maps mp;
  make_map(fn, &mp.x, d_in[0], D_, S_ / 2, 2, 4096, 2048, 2);
  make_map(fn, &mp.out, d_out, D_, S_ / 2, 2, 4096, 2048, 1);
  make_map(fn, &mp.wqkv, d_in[1], 64, D_, 3 * D_ / 64, 3 * D_ * 2, 128, 2);
  make_map(fn, &mp.wo, d_in[2], 64, D_, D_ / 64, D_ * 2, 128, 2);
  make_map(fn, &mp.w1, d_in[4], 64, D_, F_ / 64, F_ * 2, 128, 2);
  make_map(fn, &mp.w3, d_in[5], 64, D_, F_ / 64, F_ * 2, 128, 2);
  make_map(fn, &mp.w1s, d_in[4], 64, D_, F_ / 64, F_ * 2, 128, 1);
  make_map(fn, &mp.w3s, d_in[5], 64, D_, F_ / 64, F_ * 2, 128, 1);
  make_map(fn, &mp.w2, d_in[6], 64, F_, D_ / 64, D_ * 2, 128, 2);
  make_map(fn, &mp.wmod, d_in[8], 256, D_, 24, 6 * D_ * 2, 512, 1, 256);
  fused_kernel<<<132, 384, SMEM_BYTES>>>((const bf16*)d_in[7], (const bf16*)d_in[8], gs, by_sm, mp);
}
```

```cpp
#include <cuda_runtime.h>
#include <cuda_bf16.h>
#include <cuda.h>
#include <stdint.h>

typedef __nv_bfloat16 bf16;

namespace {

constexpr int S_ = 2048, D_ = 1024, F_ = 3584;
constexpr int BLK = 16384;
constexpr int HALF = 8192;
constexpr int RING = 196608;
constexpr int STG = RING;
constexpr int MISC = RING + 2 * BLK;
constexpr int SMEM_BYTES = MISC + 3072;
constexpr int B_FULL4 = 0, B_EMPTY4 = 32, B_FULL6 = 64, B_EMPTY6 = 112, B_RDY = 160, B_FREE = 176, B_LAG = 192, B_X = 208, B_MOD = 224, B_HALO = 232, B_HH = 256, B_ALL = 272, B_HH2 = 288, ZERO = 296;
constexpr int MODV = 512;
constexpr int RED_OFF = 0;
constexpr float SCL = 0.17677669529663687f * 1.4426950408889634f;
constexpr int U_HH = 64;
constexpr int FS = 8;
constexpr int NPIECE = 4, PSLEEP = 300;
constexpr int XSLEEP = 4000, HSLEEP = 400;
constexpr uint32_t XDELAY = 2300, GAP = 250;
constexpr uint32_t B1P = 3700, B1D = 700;
constexpr int TAILLAG = 5;

struct Maps { CUtensorMap x, out, wqkv, wo, w1, w3, w1s, w3s, w2, wmod; };

struct Scratch {
  uint4 h[16 * 16 * 1024];
  uint4 o[16 * 16 * 1024];
  uint4 hh[16 * 56 * 1024];
  uint4 x1[128 * 8 * 256];
  uint2 stat[2 * 16 * 8 * 128];
  uint4 halo[16 * 8 * 2 * 512];
  uint32_t modp[8 * 2 * 4 * 128];
  uint2 modv[4 * 1024];
  uint32_t flag[16 * 128 * FS];
  uint32_t epoch[132];
};
__device__ __align__(1024) Scratch g_scratch;

__device__ __forceinline__ void bail() { asm volatile("st.global.u32 [%0], %1;" :: "l"(0ull), "r"(0) : "memory"); }
__device__ __forceinline__ uint32_t smem_u32(const void* p) { return (uint32_t)__cvta_generic_to_shared(p); }
__device__ __forceinline__ void mbar_init(uint32_t bar, uint32_t cnt) { asm volatile("mbarrier.init.shared::cta.b64 [%0], %1;" :: "r"(bar), "r"(cnt) : "memory"); }
__device__ __forceinline__ void mbar_arrive(uint32_t bar) { asm volatile("mbarrier.arrive.shared::cta.b64 _, [%0];" :: "r"(bar) : "memory"); }
__device__ __forceinline__ void mbar_arrive_cl(uint32_t cl_addr) { asm volatile("mbarrier.arrive.shared::cluster.b64 _, [%0];" :: "r"(cl_addr) : "memory"); }
__device__ __forceinline__ uint32_t mapa(uint32_t addr, uint32_t cta) { uint32_t r; asm("mapa.shared::cluster.u32 %0, %1, %2;" : "=r"(r) : "r"(addr), "r"(cta)); return r; }
__device__ __forceinline__ void mbar_wait(uint32_t bar, uint32_t parity) {
  asm volatile("{\n.reg .pred p;\n.reg .b32 n;\n.reg .b64 z;\nmov.b32 n, 0;\nmov.b64 z, 0;\n"
               "W: add.u32 n, n, 1;\nsetp.gt.u32 p, n, 0x400000;\n@p st.global.u32 [z], n;\n"
               "mbarrier.try_wait.parity.shared::cta.b64 p, [%0], %1;\n@!p bra W;\n}" :: "r"(bar), "r"(parity) : "memory");
}
__device__ __forceinline__ void tma_store_3d(const CUtensorMap* m, uint32_t src, int c0, int c1, int c2) {
  asm volatile("cp.async.bulk.tensor.3d.global.shared::cta.bulk_group [%0, {%2, %3, %4}], [%1];" :: "l"(m), "r"(src), "r"(c0), "r"(c1), "r"(c2) : "memory");
}
#define ELECT "{\n.reg .pred p;\nelect.sync _|p, 0xffffffff;\n@p "
__device__ __forceinline__ void expect_e(uint32_t bar, uint32_t bytes) { asm volatile(ELECT "mbarrier.arrive.expect_tx.shared::cta.b64 _, [%0], %1;\n}" :: "r"(bar), "r"(bytes) : "memory"); }
__device__ __forceinline__ void tma_3d_e(uint32_t dst, const CUtensorMap* m, uint32_t bar, int c0, int c1, int c2) {
  asm volatile(ELECT "cp.async.bulk.tensor.3d.shared::cluster.global.mbarrier::complete_tx::bytes [%0], [%1, {%3, %4, %5}], [%2];\n}" :: "r"(dst), "l"(m), "r"(bar), "r"(c0), "r"(c1), "r"(c2) : "memory");
}
__device__ __forceinline__ void bulk_ld_e(uint32_t dst, const void* src, uint32_t bytes, uint32_t bar) {
  asm volatile(ELECT "cp.async.bulk.shared::cluster.global.mbarrier::complete_tx::bytes [%0], [%1], %2, [%3];\n}" :: "r"(dst), "l"(src), "r"(bytes), "r"(bar) : "memory");
}
__device__ __forceinline__ void bulk_ld_mc_e(uint32_t dst, const void* src, uint32_t bytes, uint32_t bar) {
  asm volatile(ELECT "cp.async.bulk.shared::cluster.global.mbarrier::complete_tx::bytes.multicast::cluster [%0], [%1], %2, [%3], %4;\n}" :: "r"(dst), "l"(src), "r"(bytes), "r"(bar), "h"((uint16_t)3) : "memory");
}
__device__ __forceinline__ void bulk_push_e(uint32_t dst_cl, uint32_t src, uint32_t bytes, uint32_t bar_cl) {
  asm volatile(ELECT "cp.async.bulk.shared::cluster.shared::cta.mbarrier::complete_tx::bytes [%0], [%1], %2, [%3];\n}" :: "r"(dst_cl), "r"(src), "r"(bytes), "r"(bar_cl) : "memory");
}
__device__ __forceinline__ void arrive_e(uint32_t bar) { asm volatile(ELECT "mbarrier.arrive.shared::cta.b64 _, [%0];\n}" :: "r"(bar) : "memory"); }
__device__ __forceinline__ void bulk_st_e(void* dst, uint32_t src, uint32_t bytes) {
  asm volatile(ELECT "cp.async.bulk.global.shared::cta.bulk_group [%0], [%1], %2;\n}" :: "l"(dst), "r"(src), "r"(bytes) : "memory");
}
__device__ __forceinline__ void publish_e(uint32_t free_bar, uint32_t* flag, uint32_t ep) {
  asm volatile(ELECT "cp.async.bulk.commit_group;\n@p cp.async.bulk.wait_group 0;\n@p mbarrier.arrive.shared::cta.b64 _, [%0];\n@p st.release.gpu.global.u32 [%1], %2;\n}"
               :: "r"(free_bar), "l"(flag), "r"(ep) : "memory");
}
__device__ __forceinline__ void bulk_commit() { asm volatile("cp.async.bulk.commit_group;" ::: "memory"); }
__device__ __forceinline__ void bulk_wait_read() { asm volatile("cp.async.bulk.wait_group.read 0;" ::: "memory"); }
__device__ __forceinline__ void fence_async_global() { asm volatile("fence.proxy.async.global;" ::: "memory"); }
__device__ __forceinline__ void fence_async_smem() { asm volatile("fence.proxy.async.shared::cta;" ::: "memory"); }
__device__ __forceinline__ void wg_arrive() { asm volatile("wgmma.fence.sync.aligned;" ::: "memory"); }
__device__ __forceinline__ void wg_commit() { asm volatile("wgmma.commit_group.sync.aligned;" ::: "memory"); }
template <int N> __device__ __forceinline__ void wg_wait() { asm volatile("wgmma.wait_group.sync.aligned %0;" :: "n"(N) : "memory"); }
__device__ __forceinline__ void cl_arrive_relaxed() { asm volatile("barrier.cluster.arrive.relaxed.aligned;" ::: "memory"); }
__device__ __forceinline__ void cl_wait() { asm volatile("barrier.cluster.wait.acquire.aligned;" ::: "memory"); }
__device__ __forceinline__ bool elect() { uint32_t p; asm volatile("{\n.reg .pred p;\nelect.sync _|p, 0xffffffff;\nselp.u32 %0, 1, 0, p;\n}" : "=r"(p)); return p; }
__device__ __forceinline__ void named_bar(int id, int n) { asm volatile("bar.sync %0, %1;" :: "r"(id), "r"(n) : "memory"); }
__device__ __forceinline__ uint32_t pack2(float lo, float hi) { uint32_t r; asm("cvt.rn.bf16x2.f32 %0, %1, %2;" : "=r"(r) : "f"(hi), "f"(lo)); return r; }
__device__ __forceinline__ float bf_lo(uint32_t w) { return __uint_as_float(w << 16); }
__device__ __forceinline__ float bf_hi(uint32_t w) { return __uint_as_float(w & 0xffff0000u); }
__device__ __forceinline__ float bf_round(float v) { return __bfloat162float(__float2bfloat16_rn(v)); }
__device__ __forceinline__ void stsm4(uint32_t addr, uint32_t a, uint32_t b, uint32_t c, uint32_t d) {
  asm volatile("stmatrix.sync.aligned.m8n8.x4.shared.b16 [%0], {%1, %2, %3, %4};" :: "r"(addr), "r"(a), "r"(b), "r"(c), "r"(d) : "memory");
}
__device__ __forceinline__ void ldsm4(uint32_t addr, uint32_t& a, uint32_t& b, uint32_t& c, uint32_t& d) {
  asm volatile("ldmatrix.sync.aligned.m8n8.x4.shared.b16 {%0, %1, %2, %3}, [%4];" : "=r"(a), "=r"(b), "=r"(c), "=r"(d) : "r"(addr) : "memory");
}
__device__ __forceinline__ uint32_t movm(uint32_t a) { uint32_t r; asm volatile("movmatrix.sync.aligned.m8n8.trans.b16 %0, %1;" : "=r"(r) : "r"(a)); return r; }
__device__ __forceinline__ void mma16(float (&d)[4], uint32_t a0, uint32_t a1, uint32_t a2, uint32_t a3, uint32_t b0, uint32_t b1) {
  asm("mma.sync.aligned.m16n8k16.row.col.f32.bf16.bf16.f32 {%0,%1,%2,%3}, {%4,%5,%6,%7}, {%8,%9}, {%0,%1,%2,%3};"
               : "+f"(d[0]), "+f"(d[1]), "+f"(d[2]), "+f"(d[3]) : "r"(a0), "r"(a1), "r"(a2), "r"(a3), "r"(b0), "r"(b1));
}
__device__ __forceinline__ void mma16z(float (&d)[4], uint32_t a0, uint32_t a1, uint32_t a2, uint32_t a3, uint32_t b0, uint32_t b1) {
  asm("mma.sync.aligned.m16n8k16.row.col.f32.bf16.bf16.f32 {%0,%1,%2,%3}, {%4,%5,%6,%7}, {%8,%9}, {%10,%10,%10,%10};"
      : "=f"(d[0]), "=f"(d[1]), "=f"(d[2]), "=f"(d[3]) : "r"(a0), "r"(a1), "r"(a2), "r"(a3), "r"(b0), "r"(b1), "f"(0.f));
}
__device__ __forceinline__ void mma8z(float (&d)[4], uint32_t a0, uint32_t a1, uint32_t b0) {
  asm("mma.sync.aligned.m16n8k8.row.col.f32.bf16.bf16.f32 {%0,%1,%2,%3}, {%4,%5}, {%6}, {%7,%7,%7,%7};"
      : "=f"(d[0]), "=f"(d[1]), "=f"(d[2]), "=f"(d[3]) : "r"(a0), "r"(a1), "r"(b0), "f"(0.f));
}
__device__ __forceinline__ void mma8(float (&d)[4], uint32_t a0, uint32_t a1, uint32_t b0) {
  asm("mma.sync.aligned.m16n8k8.row.col.f32.bf16.bf16.f32 {%0,%1,%2,%3}, {%4,%5}, {%6}, {%0,%1,%2,%3};"
               : "+f"(d[0]), "+f"(d[1]), "+f"(d[2]), "+f"(d[3]) : "r"(a0), "r"(a1), "r"(b0));
}
__device__ __forceinline__ uint4 lds128(uint32_t a) { uint4 v; asm volatile("ld.shared.v4.u32 {%0,%1,%2,%3}, [%4];" : "=r"(v.x), "=r"(v.y), "=r"(v.z), "=r"(v.w) : "r"(a) : "memory"); return v; }
__device__ __forceinline__ void sts128(uint32_t a, uint32_t x, uint32_t y, uint32_t z, uint32_t w) { asm volatile("st.shared.v4.u32 [%0], {%1,%2,%3,%4};" :: "r"(a), "r"(x), "r"(y), "r"(z), "r"(w) : "memory"); }
__device__ __forceinline__ float lds32f(uint32_t a) { float v; asm volatile("ld.shared.f32 %0, [%1];" : "=f"(v) : "r"(a) : "memory"); return v; }
__device__ __forceinline__ void sts16(uint32_t a, bf16 v) { asm volatile("st.shared.b16 [%0], %1;" :: "r"(a), "h"(__bfloat16_as_ushort(v)) : "memory"); }
__device__ __forceinline__ uint4 ldg_nc(const void* p) { uint4 v; asm volatile("ld.global.nc.L1::no_allocate.v4.u32 {%0,%1,%2,%3}, [%4];" : "=r"(v.x), "=r"(v.y), "=r"(v.z), "=r"(v.w) : "l"(p)); return v; }
__device__ __forceinline__ uint4 ld_rlx4(const uint4* p) {
  unsigned long long a, b; asm volatile("ld.relaxed.gpu.global.v2.b64 {%0,%1}, [%2];" : "=l"(a), "=l"(b) : "l"(p) : "memory");
  return make_uint4((uint32_t)a, (uint32_t)(a >> 32), (uint32_t)b, (uint32_t)(b >> 32));
}
__device__ __forceinline__ uint2 ld_rlx2(const uint2* p) { unsigned long long a; asm volatile("ld.relaxed.gpu.global.b64 %0, [%1];" : "=l"(a) : "l"(p) : "memory"); return make_uint2((uint32_t)a, (uint32_t)(a >> 32)); }
__device__ __forceinline__ void st_rlx4(uint4* p, uint32_t x, uint32_t y, uint32_t z, uint32_t w) {
  asm volatile("st.relaxed.gpu.global.v2.b64 [%0], {%1,%2};" :: "l"(p), "l"((unsigned long long)x | ((unsigned long long)y << 32)), "l"((unsigned long long)z | ((unsigned long long)w << 32)) : "memory");
}
__device__ __forceinline__ void st_rlx2(uint2* p, uint32_t x, uint32_t y) { asm volatile("st.relaxed.gpu.global.b64 [%0], %1;" :: "l"(p), "l"((unsigned long long)x | ((unsigned long long)y << 32)) : "memory"); }
__device__ __forceinline__ void st_rlx1(uint32_t* p, uint32_t v) { asm volatile("st.relaxed.gpu.global.u32 [%0], %1;" :: "l"(p), "r"(v) : "memory"); }
__device__ __forceinline__ uint32_t ld_rlx1(const uint32_t* p) { uint32_t v; asm volatile("ld.relaxed.gpu.global.u32 %0, [%1];" : "=r"(v) : "l"(p) : "memory"); return v; }
__device__ __forceinline__ uint32_t ld_acquire(const uint32_t* p) { uint32_t v; asm volatile("ld.acquire.gpu.global.u32 %0, [%1];" : "=r"(v) : "l"(p) : "memory"); return v; }
__device__ __forceinline__ void prefetch_map(const CUtensorMap* m) { asm volatile("prefetch.tensormap [%0];" :: "l"(m) : "memory"); }
__device__ __forceinline__ float rcp(float x) { float r; asm("rcp.approx.ftz.f32 %0, %1;" : "=f"(r) : "f"(x)); return r; }
__device__ __forceinline__ float ex2(float x) { float r; asm("ex2.approx.ftz.f32 %0, %1;" : "=f"(r) : "f"(x)); return r; }
__device__ __forceinline__ float tanh_fast(float x) { float r; asm("tanh.approx.f32 %0, %1;" : "=f"(r) : "f"(x)); return r; }
#define SPIN_GUARD(n) if (++(n) > (1u << 24)) bail()

__device__ __forceinline__ void wgmma_n128(float (&d)[64], uint64_t da, uint64_t db) {
  asm volatile("wgmma.mma_async.sync.aligned.m64n128k16.f32.bf16.bf16 "
    "{%0, %1, %2, %3, %4, %5, %6, %7, %8, %9, %10, %11, %12, %13, %14, %15, %16, %17, %18, %19, %20, %21, %22, %23, %24, %25, %26, %27, %28, %29, %30, %31, %32, %33, %34, %35, %36, %37, %38, %39, %40, %41, %42, %43, %44, %45, %46, %47, %48, %49, %50, %51, %52, %53, %54, %55, %56, %57, %58, %59, %60, %61, %62, %63}, "
    "%64, %65, 1, 1, 1, 0, 1;\n"
    : "+f"(d[0]), "+f"(d[1]), "+f"(d[2]), "+f"(d[3]), "+f"(d[4]), "+f"(d[5]), "+f"(d[6]), "+f"(d[7]), "+f"(d[8]), "+f"(d[9]), "+f"(d[10]), "+f"(d[11]), "+f"(d[12]), "+f"(d[13]), "+f"(d[14]), "+f"(d[15]), "+f"(d[16]), "+f"(d[17]), "+f"(d[18]), "+f"(d[19]), "+f"(d[20]), "+f"(d[21]), "+f"(d[22]), "+f"(d[23]), "+f"(d[24]), "+f"(d[25]), "+f"(d[26]), "+f"(d[27]), "+f"(d[28]), "+f"(d[29]), "+f"(d[30]), "+f"(d[31]), "+f"(d[32]), "+f"(d[33]), "+f"(d[34]), "+f"(d[35]), "+f"(d[36]), "+f"(d[37]), "+f"(d[38]), "+f"(d[39]), "+f"(d[40]), "+f"(d[41]), "+f"(d[42]), "+f"(d[43]), "+f"(d[44]), "+f"(d[45]), "+f"(d[46]), "+f"(d[47]), "+f"(d[48]), "+f"(d[49]), "+f"(d[50]), "+f"(d[51]), "+f"(d[52]), "+f"(d[53]), "+f"(d[54]), "+f"(d[55]), "+f"(d[56]), "+f"(d[57]), "+f"(d[58]), "+f"(d[59]), "+f"(d[60]), "+f"(d[61]), "+f"(d[62]), "+f"(d[63])
    : "l"(da), "l"(db));
}
__device__ __forceinline__ void wgmma_n128_first(float (&d)[64], uint64_t da, uint64_t db) {
  asm volatile("wgmma.mma_async.sync.aligned.m64n128k16.f32.bf16.bf16 "
    "{%0, %1, %2, %3, %4, %5, %6, %7, %8, %9, %10, %11, %12, %13, %14, %15, %16, %17, %18, %19, %20, %21, %22, %23, %24, %25, %26, %27, %28, %29, %30, %31, %32, %33, %34, %35, %36, %37, %38, %39, %40, %41, %42, %43, %44, %45, %46, %47, %48, %49, %50, %51, %52, %53, %54, %55, %56, %57, %58, %59, %60, %61, %62, %63}, "
    "%64, %65, 0, 1, 1, 0, 1;\n"
    : "=f"(d[0]), "=f"(d[1]), "=f"(d[2]), "=f"(d[3]), "=f"(d[4]), "=f"(d[5]), "=f"(d[6]), "=f"(d[7]), "=f"(d[8]), "=f"(d[9]), "=f"(d[10]), "=f"(d[11]), "=f"(d[12]), "=f"(d[13]), "=f"(d[14]), "=f"(d[15]), "=f"(d[16]), "=f"(d[17]), "=f"(d[18]), "=f"(d[19]), "=f"(d[20]), "=f"(d[21]), "=f"(d[22]), "=f"(d[23]), "=f"(d[24]), "=f"(d[25]), "=f"(d[26]), "=f"(d[27]), "=f"(d[28]), "=f"(d[29]), "=f"(d[30]), "=f"(d[31]), "=f"(d[32]), "=f"(d[33]), "=f"(d[34]), "=f"(d[35]), "=f"(d[36]), "=f"(d[37]), "=f"(d[38]), "=f"(d[39]), "=f"(d[40]), "=f"(d[41]), "=f"(d[42]), "=f"(d[43]), "=f"(d[44]), "=f"(d[45]), "=f"(d[46]), "=f"(d[47]), "=f"(d[48]), "=f"(d[49]), "=f"(d[50]), "=f"(d[51]), "=f"(d[52]), "=f"(d[53]), "=f"(d[54]), "=f"(d[55]), "=f"(d[56]), "=f"(d[57]), "=f"(d[58]), "=f"(d[59]), "=f"(d[60]), "=f"(d[61]), "=f"(d[62]), "=f"(d[63])
    : "l"(da), "l"(db));
}
__device__ __forceinline__ void wgmma_n256(float (&d)[128], uint64_t da, uint64_t db) {
  asm volatile("wgmma.mma_async.sync.aligned.m64n256k16.f32.bf16.bf16 "
    "{%0, %1, %2, %3, %4, %5, %6, %7, %8, %9, %10, %11, %12, %13, %14, %15, %16, %17, %18, %19, %20, %21, %22, %23, %24, %25, %26, %27, %28, %29, %30, %31, %32, %33, %34, %35, %36, %37, %38, %39, %40, %41, %42, %43, %44, %45, %46, %47, %48, %49, %50, %51, %52, %53, %54, %55, %56, %57, %58, %59, %60, %61, %62, %63, %64, %65, %66, %67, %68, %69, %70, %71, %72, %73, %74, %75, %76, %77, %78, %79, %80, %81, %82, %83, %84, %85, %86, %87, %88, %89, %90, %91, %92, %93, %94, %95, %96, %97, %98, %99, %100, %101, %102, %103, %104, %105, %106, %107, %108, %109, %110, %111, %112, %113, %114, %115, %116, %117, %118, %119, %120, %121, %122, %123, %124, %125, %126, %127}, "
    "%128, %129, 1, 1, 1, 0, 1;\n"
    : "+f"(d[0]), "+f"(d[1]), "+f"(d[2]), "+f"(d[3]), "+f"(d[4]), "+f"(d[5]), "+f"(d[6]), "+f"(d[7]), "+f"(d[8]), "+f"(d[9]), "+f"(d[10]), "+f"(d[11]), "+f"(d[12]), "+f"(d[13]), "+f"(d[14]), "+f"(d[15]), "+f"(d[16]), "+f"(d[17]), "+f"(d[18]), "+f"(d[19]), "+f"(d[20]), "+f"(d[21]), "+f"(d[22]), "+f"(d[23]), "+f"(d[24]), "+f"(d[25]), "+f"(d[26]), "+f"(d[27]), "+f"(d[28]), "+f"(d[29]), "+f"(d[30]), "+f"(d[31]), "+f"(d[32]), "+f"(d[33]), "+f"(d[34]), "+f"(d[35]), "+f"(d[36]), "+f"(d[37]), "+f"(d[38]), "+f"(d[39]), "+f"(d[40]), "+f"(d[41]), "+f"(d[42]), "+f"(d[43]), "+f"(d[44]), "+f"(d[45]), "+f"(d[46]), "+f"(d[47]), "+f"(d[48]), "+f"(d[49]), "+f"(d[50]), "+f"(d[51]), "+f"(d[52]), "+f"(d[53]), "+f"(d[54]), "+f"(d[55]), "+f"(d[56]), "+f"(d[57]), "+f"(d[58]), "+f"(d[59]), "+f"(d[60]), "+f"(d[61]), "+f"(d[62]), "+f"(d[63]), "+f"(d[64]), "+f"(d[65]), "+f"(d[66]), "+f"(d[67]), "+f"(d[68]), "+f"(d[69]), "+f"(d[70]), "+f"(d[71]), "+f"(d[72]), "+f"(d[73]), "+f"(d[74]), "+f"(d[75]), "+f"(d[76]), "+f"(d[77]), "+f"(d[78]), "+f"(d[79]), "+f"(d[80]), "+f"(d[81]), "+f"(d[82]), "+f"(d[83]), "+f"(d[84]), "+f"(d[85]), "+f"(d[86]), "+f"(d[87]), "+f"(d[88]), "+f"(d[89]), "+f"(d[90]), "+f"(d[91]), "+f"(d[92]), "+f"(d[93]), "+f"(d[94]), "+f"(d[95]), "+f"(d[96]), "+f"(d[97]), "+f"(d[98]), "+f"(d[99]), "+f"(d[100]), "+f"(d[101]), "+f"(d[102]), "+f"(d[103]), "+f"(d[104]), "+f"(d[105]), "+f"(d[106]), "+f"(d[107]), "+f"(d[108]), "+f"(d[109]), "+f"(d[110]), "+f"(d[111]), "+f"(d[112]), "+f"(d[113]), "+f"(d[114]), "+f"(d[115]), "+f"(d[116]), "+f"(d[117]), "+f"(d[118]), "+f"(d[119]), "+f"(d[120]), "+f"(d[121]), "+f"(d[122]), "+f"(d[123]), "+f"(d[124]), "+f"(d[125]), "+f"(d[126]), "+f"(d[127])
    : "l"(da), "l"(db));
}
__device__ __forceinline__ void wgmma_n256_first(float (&d)[128], uint64_t da, uint64_t db) {
  asm volatile("wgmma.mma_async.sync.aligned.m64n256k16.f32.bf16.bf16 "
    "{%0, %1, %2, %3, %4, %5, %6, %7, %8, %9, %10, %11, %12, %13, %14, %15, %16, %17, %18, %19, %20, %21, %22, %23, %24, %25, %26, %27, %28, %29, %30, %31, %32, %33, %34, %35, %36, %37, %38, %39, %40, %41, %42, %43, %44, %45, %46, %47, %48, %49, %50, %51, %52, %53, %54, %55, %56, %57, %58, %59, %60, %61, %62, %63, %64, %65, %66, %67, %68, %69, %70, %71, %72, %73, %74, %75, %76, %77, %78, %79, %80, %81, %82, %83, %84, %85, %86, %87, %88, %89, %90, %91, %92, %93, %94, %95, %96, %97, %98, %99, %100, %101, %102, %103, %104, %105, %106, %107, %108, %109, %110, %111, %112, %113, %114, %115, %116, %117, %118, %119, %120, %121, %122, %123, %124, %125, %126, %127}, "
    "%128, %129, 0, 1, 1, 0, 1;\n"
    : "=f"(d[0]), "=f"(d[1]), "=f"(d[2]), "=f"(d[3]), "=f"(d[4]), "=f"(d[5]), "=f"(d[6]), "=f"(d[7]), "=f"(d[8]), "=f"(d[9]), "=f"(d[10]), "=f"(d[11]), "=f"(d[12]), "=f"(d[13]), "=f"(d[14]), "=f"(d[15]), "=f"(d[16]), "=f"(d[17]), "=f"(d[18]), "=f"(d[19]), "=f"(d[20]), "=f"(d[21]), "=f"(d[22]), "=f"(d[23]), "=f"(d[24]), "=f"(d[25]), "=f"(d[26]), "=f"(d[27]), "=f"(d[28]), "=f"(d[29]), "=f"(d[30]), "=f"(d[31]), "=f"(d[32]), "=f"(d[33]), "=f"(d[34]), "=f"(d[35]), "=f"(d[36]), "=f"(d[37]), "=f"(d[38]), "=f"(d[39]), "=f"(d[40]), "=f"(d[41]), "=f"(d[42]), "=f"(d[43]), "=f"(d[44]), "=f"(d[45]), "=f"(d[46]), "=f"(d[47]), "=f"(d[48]), "=f"(d[49]), "=f"(d[50]), "=f"(d[51]), "=f"(d[52]), "=f"(d[53]), "=f"(d[54]), "=f"(d[55]), "=f"(d[56]), "=f"(d[57]), "=f"(d[58]), "=f"(d[59]), "=f"(d[60]), "=f"(d[61]), "=f"(d[62]), "=f"(d[63]), "=f"(d[64]), "=f"(d[65]), "=f"(d[66]), "=f"(d[67]), "=f"(d[68]), "=f"(d[69]), "=f"(d[70]), "=f"(d[71]), "=f"(d[72]), "=f"(d[73]), "=f"(d[74]), "=f"(d[75]), "=f"(d[76]), "=f"(d[77]), "=f"(d[78]), "=f"(d[79]), "=f"(d[80]), "=f"(d[81]), "=f"(d[82]), "=f"(d[83]), "=f"(d[84]), "=f"(d[85]), "=f"(d[86]), "=f"(d[87]), "=f"(d[88]), "=f"(d[89]), "=f"(d[90]), "=f"(d[91]), "=f"(d[92]), "=f"(d[93]), "=f"(d[94]), "=f"(d[95]), "=f"(d[96]), "=f"(d[97]), "=f"(d[98]), "=f"(d[99]), "=f"(d[100]), "=f"(d[101]), "=f"(d[102]), "=f"(d[103]), "=f"(d[104]), "=f"(d[105]), "=f"(d[106]), "=f"(d[107]), "=f"(d[108]), "=f"(d[109]), "=f"(d[110]), "=f"(d[111]), "=f"(d[112]), "=f"(d[113]), "=f"(d[114]), "=f"(d[115]), "=f"(d[116]), "=f"(d[117]), "=f"(d[118]), "=f"(d[119]), "=f"(d[120]), "=f"(d[121]), "=f"(d[122]), "=f"(d[123]), "=f"(d[124]), "=f"(d[125]), "=f"(d[126]), "=f"(d[127])
    : "l"(da), "l"(db));
}

template <int N> struct WG;
#define DEF_WG(N) template <> struct WG<N> { \
  static __device__ __forceinline__ void mma(float (&d)[N / 2], uint64_t a, uint64_t b) { wgmma_n##N(d, a, b); } \
  static __device__ __forceinline__ void first(float (&d)[N / 2], uint64_t a, uint64_t b) { wgmma_n##N##_first(d, a, b); } };
DEF_WG(128) DEF_WG(256)

constexpr uint64_t DESC_A = (1ull << 62) | ((uint64_t)(1024 >> 4) << 32) | (1ull << 16);
constexpr uint64_t DESC_B = (1ull << 62) | ((uint64_t)(1024 >> 4) << 32) | ((uint64_t)(8192 >> 4) << 16);

struct Ring { int s; uint32_t ph; int wrap; };
template <int NS> __device__ __forceinline__ void ring_next(Ring& r) { r.s = (r.s + 1 == NS) ? 0 : r.s + 1; if (r.s == r.wrap) r.ph ^= 1; }

__device__ __forceinline__ int own_order(int it, int j) {
  return it < 2 ? 2 * j + it : it < 4 ? 2 * (j ^ 1) + it - 2 : ((j >> 1) * 4 + 2 * it - (it < 10 ? 4 : 15)) & 15;
}

template <int V> struct IC { static constexpr int v = V; };
template <int I, int E, class F> __device__ __forceinline__ void static_for(F&& f) { if constexpr (I < E) { f(IC<I>{}); static_for<I + 1, E>(f); } }

template <int N, int NS, int PRE, int LAG, class Pre, class Mid, class Last>
__device__ __forceinline__ void mainloop(float (&acc)[N / 2], int nkb, bool own, Ring& r, uint32_t sb, int wg, int lane, uint32_t rel_base, Pre pre, Mid mid, Last last, int lag_par = 0) {
  constexpr int SLOT = RING / NS;
  const uint32_t full = sb + MISC + (NS == 4 ? B_FULL4 : B_FULL6);
  const uint32_t rel = rel_base + (NS == 4 ? B_EMPTY4 : B_EMPTY6);
  const uint32_t s0 = (sb & 0x3FFFF) >> 4, a0 = s0 + wg * (HALF >> 4);
  int ps;
  auto issue = [&](int it, bool first) {
    const uint64_t da = DESC_A | (a0 + ((own && it < 2) ? (STG + it * BLK) >> 4 : r.s * (SLOT >> 4))), db = DESC_B | (s0 + r.s * (SLOT >> 4) + (BLK >> 4));
    mbar_wait(full + r.s * 8, r.ph);
    wg_arrive();
    if (first) WG<N>::first(acc, da, db); else WG<N>::mma(acc, da, db);
#pragma unroll
    for (int k = 1; k < 4; k++) WG<N>::mma(acc, da + k * 2, db + k * 128);
    wg_commit();
  };
  auto retire = [&](int it) {
    wg_wait<1>();
    if (lane < 2) mbar_arrive_cl(rel + ps * 8);
    ps = r.s;
    ring_next<NS>(r);
  };
  issue(0, true);
  ps = r.s;
  ring_next<NS>(r);
  static_for<1, PRE + 1>([&](auto ic) { issue(ic.v, false); pre(ic); retire(ic.v); });
#pragma unroll 1
  for (int it = PRE + 1; it < nkb; it++) {
    if (LAG && it == nkb - LAG && wg == 1) mbar_wait(sb + MISC + B_LAG, lag_par);
    issue(it, false); mid(it); retire(it);
  }
  if (LAG && wg == 0 && lane == 0) mbar_arrive(sb + MISC + B_LAG);
  last();
  wg_wait<0>();
  if (lane < 2) mbar_arrive_cl(rel + ps * 8);
}

__device__ __forceinline__ uint32_t tag_of(uint32_t ep) { return (ep & 127u) + 1u; }
__device__ __forceinline__ void ln_publish(const float (&v)[64], uint2* st, int j, int row0, int lane, uint32_t ep) {
  float s0 = 0, s1 = 0, s2 = 0, s3 = 0, q0 = 0, q1 = 0, q2 = 0, q3 = 0;
#pragma unroll
  for (int i = 0; i < 16; i++) {
    s0 += v[4 * i]; s1 += v[4 * i + 1]; s2 += v[4 * i + 2]; s3 += v[4 * i + 3];
    q0 = fmaf(v[4 * i], v[4 * i], q0); q1 = fmaf(v[4 * i + 1], v[4 * i + 1], q1); q2 = fmaf(v[4 * i + 2], v[4 * i + 2], q2); q3 = fmaf(v[4 * i + 3], v[4 * i + 3], q3);
  }
  s0 += s1; s2 += s3; q0 += q1; q2 += q3;
  const bool odd = lane & 1;
  float s = (odd ? s2 : s0) + __shfl_xor_sync(~0u, odd ? s0 : s2, 1), q = (odd ? q2 : q0) + __shfl_xor_sync(~0u, odd ? q0 : q2, 1);
  s += __shfl_xor_sync(~0u, s, 2); q += __shfl_xor_sync(~0u, q, 2);
  if ((lane & 3) < 2) st_rlx2(st + j * 128 + row0 + (lane & 1) * 8, __float_as_uint(s), (__float_as_uint(fmaf(s * (-1.f / 128), s, q)) & ~255u) | tag_of(ep));
}
__device__ __forceinline__ void ln_gather(const uint2* st, int row0, int lane, uint32_t ep, float& n0, float& r0, float& n1, float& r1, bool rnd) {
  const uint2* p = st + (lane & 2) * 256 + row0 + (lane & 1) * 8;
  const uint32_t tag = tag_of(ep);
  uint2 a, b, c, d; uint32_t n = 0;
  while (true) {
    a = ld_rlx2(p); b = ld_rlx2(p + 128); c = ld_rlx2(p + 256); d = ld_rlx2(p + 384);
    if ((((a.y ^ tag) | (b.y ^ tag) | (c.y ^ tag) | (d.y ^ tag)) & 255u) == 0) break;
    SPIN_GUARD(n);
  }
  __syncwarp();
  const uint32_t fix = tag ^ 128u;
  float s = (__uint_as_float(a.x) + __uint_as_float(b.x)) + (__uint_as_float(c.x) + __uint_as_float(d.x));
  float q = (__uint_as_float(a.y ^ fix) + __uint_as_float(b.y ^ fix)) + (__uint_as_float(c.y ^ fix) + __uint_as_float(d.y ^ fix));
  q = fmaf(fmaf(__uint_as_float(a.x), __uint_as_float(a.x), __uint_as_float(b.x) * __uint_as_float(b.x)) +
           fmaf(__uint_as_float(c.x), __uint_as_float(c.x), __uint_as_float(d.x) * __uint_as_float(d.x)), 1.f / 128, q);
  s += __shfl_xor_sync(~0u, s, 2); q += __shfl_xor_sync(~0u, q, 2);
  s *= 1.f / 1024;
  const float var = fmaxf(fmaf(-s, s, q * (1.f / 1024)), 0.f);
  float r;
  if (rnd) {
    float sd; asm("sqrt.approx.f32 %0, %1;" : "=f"(sd) : "f"(bf_round(bf_round(var) + 1e-5f)));
    r = rcp(bf_round(sd)); s = bf_round(s);
  } else r = rsqrtf(var + 1e-5f);
  const float nn = -s * r;
  const float ro = __shfl_xor_sync(~0u, r, 1), no = __shfl_xor_sync(~0u, nn, 1);
  const bool odd = lane & 1;
  r0 = odd ? ro : r; n0 = odd ? no : nn; r1 = odd ? r : ro; n1 = odd ? nn : no;
}
__device__ __forceinline__ void load_vec(uint32_t* w, uint32_t sb, int sec, int b, int lane) {
#pragma unroll
  for (int q = 0; q < 2; q++) { uint4 t = lds128(sb + MISC + MODV + sec * 256 + (lane & 3) * 64 + b * 32 + q * 16); w[4 * q] = t.x; w[4 * q + 1] = t.y; w[4 * q + 2] = t.z; w[4 * q + 3] = t.w; }
}
__device__ __forceinline__ void stage_done(uint32_t sb, int wg, int b, int lane) {
  fence_async_smem();
  __syncwarp();
  if (lane == 0) mbar_arrive(sb + MISC + B_RDY + b * 8);
}
__device__ __forceinline__ uint32_t hfma2(uint32_t a, uint32_t b, uint32_t c) { uint32_t r; asm("fma.rn.bf16x2 %0, %1, %2, %3;" : "=r"(r) : "r"(a), "r"(b), "r"(c)); return r; }
__device__ __forceinline__ void ln_apply(const float (&v)[64], const uint2* st, int row0, uint32_t ep, uint32_t sb, int sec_shift, int sec_scale, uint32_t stg_row, int wg, int lane) {
  uint32_t sc[16], sh[16];
#pragma unroll
  for (int b = 0; b < 2; b++) { load_vec(sc + 8 * b, sb, sec_scale, b, lane); load_vec(sh + 8 * b, sb, sec_shift, b, lane); }
  float n0, r0, n1, r1;
  ln_gather(st, row0, lane, ep, n0, r0, n1, r1, sec_shift == 0);
#pragma unroll
  for (int i = 0; i < 16; i += 2) {
    if (i == 8) { const float z = lds32f(sb + MISC + ZERO); n0 += z; n1 += z; }
    uint32_t w[4];
#pragma unroll
    for (int u = 0; u < 2; u++) {
      int q = i + u;
      w[2 * u] = hfma2(pack2(fmaf(v[4 * q], r0, n0), fmaf(v[4 * q + 1], r0, n0)), sc[q], sh[q]);
      w[2 * u + 1] = hfma2(pack2(fmaf(v[4 * q + 2], r1, n1), fmaf(v[4 * q + 3], r1, n1)), sc[q], sh[q]);
    }
    stsm4(stg_row + (i >> 3) * BLK + ((((i & 7) + (lane >> 4)) ^ (lane & 7)) << 4), w[0], w[1], w[2], w[3]);
    if ((i & 7) == 6) { stage_done(sb, wg, i >> 3, lane); }
  }
}
__device__ __forceinline__ uint32_t hmul2(uint32_t a, uint32_t b) { uint32_t r; asm("mul.rn.bf16x2 %0, %1, %2;" : "=r"(r) : "r"(a), "r"(b)); return r; }
__device__ __forceinline__ uint32_t silu_mul2(uint32_t g, uint32_t u) {
  const uint32_t h = hmul2(g, 0x3f003f00u);
  const float h0 = bf_lo(h), h1 = bf_hi(h);
  return hmul2(pack2(fmaf(h0, tanh_fast(h0), h0), fmaf(h1, tanh_fast(h1), h1)), u);
}

__device__ __forceinline__ void gemv_fma(float (&a)[8], uint4 w, float s) {
  a[0] = fmaf(bf_lo(w.x), s, a[0]); a[1] = fmaf(bf_hi(w.x), s, a[1]); a[2] = fmaf(bf_lo(w.y), s, a[2]); a[3] = fmaf(bf_hi(w.y), s, a[3]);
  a[4] = fmaf(bf_lo(w.z), s, a[4]); a[5] = fmaf(bf_hi(w.z), s, a[5]); a[6] = fmaf(bf_lo(w.w), s, a[6]); a[7] = fmaf(bf_hi(w.w), s, a[7]);
}
__device__ __forceinline__ float silu_c(float v) { return bf_round(__fdividef(v, 1.f + __expf(-v))); }
__device__ __forceinline__ float mod_gather(const uint32_t* p, uint32_t ep) {
  const uint32_t tag = tag_of(ep), fix = tag ^ 128u;
  uint32_t a, b, c, d, n = 0;
  while (true) {
    a = ld_rlx1(p); b = ld_rlx1(p + 128); c = ld_rlx1(p + 256); d = ld_rlx1(p + 384);
    if ((((a ^ tag) | (b ^ tag) | (c ^ tag) | (d ^ tag)) & 255u) == 0) break;
    SPIN_GUARD(n);
  }
  return (__uint_as_float(a ^ fix) + __uint_as_float(b ^ fix)) + (__uint_as_float(c ^ fix) + __uint_as_float(d ^ fix));
}
__device__ __forceinline__ void mod_store(uint32_t sb, int sec, int col, float v) {
  v = bf_round(v);
  if (sec == 1) v += 1.f;
  sts16(sb + MISC + MODV + sec * 256 + (((col >> 1) & 3) * 16 + (col >> 3)) * 4 + (col & 1) * 2, __float2bfloat16_rn(v));
}

__global__ void __cluster_dims__(2, 1, 1) __launch_bounds__(384, 1)
fused_kernel(const bf16* __restrict__ cvec, const bf16* __restrict__ wmod, Scratch* gs, int by_sm, const __grid_constant__ Maps maps) {
  extern __shared__ __align__(1024) uint8_t smem_raw[];
  const uint32_t sb = smem_u32(smem_raw);
  const int warp = __shfl_sync(~0u, threadIdx.x >> 5, 0), lane = threadIdx.x & 31;
  const int rank = blockIdx.x & 1;
  uint32_t sm; asm volatile("mov.u32 %0, %%smid;" : "=r"(sm));
  const int t = sm >> 1, v = t < 32 ? t : t < 60 ? t + 1 + (((t - 32) * 37) >> 8) : (t - 58) * 8;
  const int gr = 0x71546320u >> ((v & 7) * 4);
  const int cid = !by_sm ? (blockIdx.x >> 1) - 2 : (t & ~1) == 60 ? t - 62 : (gr & 4) * 8 + (v >> 3) * 4 + (gr & 3);
  const bool extra = cid < 0;
  const int bid = cid * 2 + rank;
  const int m = cid >> 2, j = (cid & 3) * 2 + rank;
  const uint32_t bar = sb + MISC;

  if (warp >= 8) {
    asm volatile("setmaxnreg.dec.sync.aligned.u32 40;");
    if (extra) {
      if (warp == 8) {
        if (lane == 0) { for (int s = 0; s < 6; s++) { mbar_init(bar + B_FULL6 + s * 8, 1); mbar_init(bar + B_EMPTY6 + s * 8, 8); } fence_async_smem(); }
        __syncwarp();
        asm volatile("bar.arrive 2, 288;" ::: "memory");
        __nanosleep(XSLEEP);
#pragma unroll 1
        for (int it = 0, s = 0, par = 1; it < 64; it++) {
          mbar_wait(bar + B_EMPTY6 + s * 8, par);
          expect_e(bar + B_FULL6 + s * 8, 32768); tma_3d_e(sb + s * 32768, &maps.wmod, bar + B_FULL6 + s * 8, 0, (it & 15) * 64, 12 + (it >> 4) * 4 + bid);
          if (++s == 6) { s = 0; par ^= 1; }
        }
      }
    } else if (warp < 10) {
      uint32_t f6 = bar + B_FULL6, d6 = sb + (warp == 8 ? BLK : rank * HALF), p6 = 1;
      auto next6 = [&]() { f6 += 8; d6 += 32768; if (f6 == bar + B_FULL6 + 48) { f6 -= 48; d6 -= RING; p6 ^= 1; } };
      auto drained4 = [&](int q, int late) { if (q < 5) mbar_wait(bar + B_EMPTY4 + (((late ? 0x10332 : 0x32110) >> (4 * q)) & 3) * 8, 1); };
      auto drained6 = [&](int q) { if (q < 3) mbar_wait(bar + B_EMPTY6 + ((0x154 >> (4 * q)) & 7) * 8, q >> 1); };
      auto skip6 = [&]() { mbar_wait(f6 + 48, p6); expect_e(f6, 0); next6(); };
      if (warp == 8) {
        const uint32_t t_start = clock();
        if (lane == 0) {
          if (sb & 1023) bail();
          for (int b = 0; b < 2; b++) mbar_init(bar + B_X + b * 8, 1);
          for (int s = 0; s < 4; s++) { mbar_init(bar + B_FULL4 + s * 8, 2); mbar_init(bar + B_EMPTY4 + s * 8, 16); }
          for (int s = 0; s < 6; s++) { mbar_init(bar + B_FULL6 + s * 8, 2); mbar_init(bar + B_EMPTY6 + s * 8, 16); }
          for (int b = 0; b < 2; b++) { mbar_init(bar + B_RDY + b * 8, 8); mbar_init(bar + B_FREE + b * 8, 1); mbar_init(bar + B_HH + b * 8, 1); }
          mbar_init(bar + B_MOD, 1); mbar_init(bar + B_LAG, 4); mbar_init(bar + B_HALO, 2); mbar_init(bar + B_ALL, 1); mbar_init(bar + B_HH2, 1);
          asm volatile("st.shared.u32 [%0], 0;" :: "r"(bar + ZERO) : "memory");
          asm volatile("fence.mbarrier_init.release.cluster;" ::: "memory");
          fence_async_smem();
        }
        __syncwarp();
        cl_arrive_relaxed();
        while ((uint32_t)clock() - t_start < XDELAY) {}
        for (int b = 0; b < 2; b++) { expect_e(bar + B_X + b * 8, BLK); tma_3d_e(sb + STG + b * BLK, &maps.x, bar + B_X + b * 8, j * 128 + b * 64, m * 64, 0); }
        mbar_wait(bar + B_X + 8, 0);
#pragma unroll 1
        for (int ph = 0; ph < 2; ph++) {
          const CUtensorMap* const m0 = ph ? &maps.w1 : &maps.wqkv;
#pragma unroll 1
          for (int it = 0; it < (ph ? 48 : 16); it++) {
            const int s = (it + 2 * ph) & 3;
            int a0 = (ph ? it & 48 : 16) + 2 * j, a1 = ph ? a0 : a0 + 16, k0 = (it < 16 ? own_order(it, j) : it & 15) * 64;
            uint32_t full = bar + B_FULL4 + s * 8, d = sb + s * 49152 + BLK;
            if (ph) drained6(it);
            mbar_wait(full + 32, ~(it >> 2) & 1);
            tma_3d_e(d, m0, full, 0, k0, a0);
            if (it < 4) { const uint32_t t0 = clock(); while ((uint32_t)clock() - t0 < GAP) {} }
            tma_3d_e(d + BLK, m0 + ph, full, 0, k0, a1);
            expect_e(full, 2 * BLK);
            if (it < 4) { const uint32_t t0 = clock(); while ((uint32_t)clock() - t0 < GAP) {} }
            if (it >= 44) {
              if (it == 44) { mbar_wait(bar + B_FREE, 0); mbar_wait(bar + B_FREE + 8, 0); expect_e(bar + B_X, 2 * BLK); }
              bulk_ld_e(sb + STG + (it - 44) * HALF, gs->x1 + bid * 2048 + (it - 44) * 512, HALF, bar + B_X);
            }
          }
          const CUtensorMap* const m1 = ph ? &maps.w1s : &maps.wqkv;
          const int a = ph ? 48 + j : 2 * j;
#pragma unroll 1
          for (int k0 = 0; k0 < 1024; k0 += 64) {
            drained4(k0 >> 6, ph);
            mbar_wait(f6 + 48, p6);
            tma_3d_e(d6, m1, f6, 0, k0, a);
            if (ph) tma_3d_e(d6 + HALF, &maps.w3s, f6, 0, k0, a);
            expect_e(f6, BLK);
            next6();
          }
          if (ph) break;
#pragma unroll 1
          for (int it = 0; it < 16; it++) {
            const int k0 = own_order(it, j) * 64;
            mbar_wait(f6 + 48, p6);
            tma_3d_e(d6, &maps.wo, f6, 0, k0, 2 * j);
            expect_e(f6, BLK);
            next6();
          }
          skip6();
        }
#pragma unroll 1
        for (int k0 = 0; k0 < F_; k0 += 64) {
          mbar_wait(f6 + 48, p6);
          tma_3d_e(d6, &maps.w2, f6, 0, k0, 2 * j);
          expect_e(f6, BLK);
          next6();
        }
      } else {
        if (lane < 9) prefetch_map(&maps.x + lane);
        const uint32_t ep = gs->epoch[blockIdx.x] + 1;
        cl_arrive_relaxed(); cl_wait();
        auto run6 = [&](const uint4* src, int n, int sw) {
          src += rank * 512;
#pragma unroll 1
          for (int it = 0; it < n; it++) {
            if (sw >= 0) drained4(it, sw);
            mbar_wait(f6 + 48, p6);
            bulk_ld_mc_e(d6, src, HALF, f6);
            expect_e(f6, BLK);
            next6();
            src += 1024;
          }
        };
        uint32_t ready = 0;
        auto need = [&](int e, uint32_t mask) {
          if (!(ready & mask)) {
            uint32_t n = 0;
            do { ready = __ballot_sync(~0u, ld_acquire(gs->flag + (m * 128 + e * 16 + (lane & 14)) * FS) == ep); SPIN_GUARD(n); } while (!(ready & mask));
            fence_async_global();
          }
        };
        auto fresh = [&](int e, int it, uint32_t full, uint32_t empty, int par, uint32_t slot, uint4* src) {
          mbar_wait(empty, par);
          expect_e(full, it < 2 ? 0 : BLK);
          if (it >= 4) {
            const int kb = own_order(it, j);
            if (it < 10) need(e, 1u << kb); else if (it == 10) mbar_wait(bar + B_ALL, e & 1);
            bulk_ld_mc_e(slot + rank * HALF, src + kb * 1024 + rank * 512, HALF, full);
          } else if (it >= 2) {
            const int b = it > 2;
            const uint32_t to_peer = mapa(sb, rank ^ 1) - sb;
            const bool push = b && e != 1;
            mbar_wait(bar + (push ? B_RDY : B_FREE) + b * 8, e & 1);
            if (push) bulk_push_e(slot + to_peer, sb + STG + BLK, BLK, full + to_peer);
            else { fence_async_global(); bulk_ld_e(slot + to_peer, src + (2 * j + b) * 1024, BLK, full + to_peer); }
          } else ready = 0;
        };
        uint4* const h = gs->h + m * 16384;
#pragma unroll 1
        for (int e = 0; e < 3; e++) {
#pragma unroll 1
          for (int it = 0; it < 16; it++) {
            const int s = (it + e) & 3;
            const uint32_t full = e == 1 ? f6 : bar + B_FULL4 + s * 8;
            if (e == 2) drained6(it);
            fresh(e, it, full, full + (e == 1 ? 48 : 32), e == 1 ? p6 : ~(it >> 2) & 1, e == 1 ? d6 - rank * HALF : sb + s * 49152, e == 1 ? gs->o + m * 16384 : h);
            if (e == 1) next6();
          }
          if (e == 1) { skip6(); continue; }
#pragma unroll 1
          for (int it = 16; it < 16 + 16 * e; it++) {
            const int s = (it + 2) & 3;
            const uint32_t full = bar + B_FULL4 + s * 8;
            mbar_wait(full + 32, ~(it >> 2) & 1);
            bulk_ld_mc_e(sb + s * 49152 + rank * HALF, h + (it & 15) * 1024 + rank * 512, HALF, full);
            expect_e(full, BLK);
          }
          run6(h, 16, e);
        }
#pragma unroll 1
        for (int q = 0; q < 3; q++) {
          mbar_wait(bar + (q == 2 ? B_HH2 : B_HH + q * 8), 0);
          run6(gs->hh + m * 57344 + (64 - (64 >> q)) * 1024, 32 >> q, -1);
        }
      }
    } else {
      const int b = warp - 10;
      const uint32_t ep = gs->epoch[blockIdx.x] + 1;
      const uint32_t stg = sb + STG + b * BLK;
      cl_arrive_relaxed(); cl_wait();
      auto all_there = [&](int u, uint32_t done) {
        const uint32_t* fl = gs->flag + u * FS;
        uint32_t n = 0;
        while (!__all_sync(~0u, ld_acquire(fl) == ep)) { __nanosleep(100); SPIN_GUARD(n); }
        fence_async_global();
        arrive_e(done);
      };
#pragma unroll 1
      for (int e = 0; e < 7 - b; e++) {
        const int kb = (e < 3 ? 2 * j : e < 6 ? 2 * (8 * (e - 3) + j) : 48 + j) + b;
        uint4* const dst = (e == 1 ? gs->o + m * 16384 : e < 3 ? gs->h + m * 16384 : gs->hh + m * 57344) + kb * 1024;
        uint32_t* const fl = gs->flag + (m * 128 + (e < 3 ? e * 16 : U_HH) + kb) * FS;
        if (b && e < 3) {
          mbar_wait(bar + B_FREE, e & 1);
          const uint32_t t0 = clock();
          while ((uint32_t)clock() - t0 < (e == 1 ? B1D : B1P)) {}
        }
        mbar_wait(bar + B_RDY + b * 8, e & 1);
        bulk_st_e(dst, stg, e < 3 ? BLK : BLK / NPIECE);
        if (e >= 3) {
#pragma unroll 1
          for (int q = 1; q < NPIECE; q++) { __nanosleep(PSLEEP); bulk_st_e(dst + q * (1024 / NPIECE), stg + q * (BLK / NPIECE), BLK / NPIECE); }
        }
        publish_e(bar + B_FREE + b * 8, fl, ep);
        if (b && (e < 3 || e == 4)) all_there(m * 128 + (e < 3 ? e * 16 + (lane & 15) : U_HH + lane), bar + (e < 3 ? B_ALL : B_HH));
        if (!b && (e == 1 || e == 2)) {
#pragma unroll 1
          for (int sec = e == 1 ? 2 : 5; sec < 4 + e; sec++) {
            const uint4* p = (const uint4*)(gs->modv + (sec - 2) * 1024 + j * 128) + lane;
            uint4 v0, v1; uint32_t n = 0;
            while (true) {
              v0 = ld_rlx4(p); v1 = ld_rlx4(p + 32);
              if (__all_sync(~0u, v0.y == ep && v0.w == ep && v1.y == ep && v1.w == ep)) break;
              SPIN_GUARD(n);
            }
            const uint32_t d = sb + MISC + MODV + sec * 256 + ((lane & 3) * 16 + (lane >> 2)) * 4;
            asm volatile("st.shared.u32 [%0], %1;" :: "r"(d), "r"(__byte_perm(v0.x, v0.z, 0x7632)) : "memory");
            asm volatile("st.shared.u32 [%0], %1;" :: "r"(d + 32), "r"(__byte_perm(v1.x, v1.z, 0x7632)) : "memory");
          }
          __syncwarp();
          if (e == 1) { arrive_e(bar + B_MOD); }
        }
        if (e == 0) {
          mbar_wait(bar + B_EMPTY6 + 24, 0);
          __nanosleep(HSLEEP);
#pragma unroll 1
          for (int w = 0; w < 4; w++) {
            const uint4* hp = gs->halo + ((m * 8 + j) * 2 + (w & 1)) * 512 + b * 256 + (w >> 1) * 128 + lane;
            uint4 q[4] = {}; uint32_t n = 0;
            while (m > 0) {
              bool ok = true;
#pragma unroll
              for (int i = 0; i < 4; i++) q[i] = ld_rlx4(hp + i * 32);
#pragma unroll
              for (int i = 0; i < 4; i++) ok = ok && q[i].y == ep && q[i].w == ep;
              if (__all_sync(~0u, ok)) break;
              SPIN_GUARD(n);
            }
#pragma unroll
            for (int i = 0; i < 2; i++) sts128(stg + lane * 16 + (w & 1) * HALF + (w >> 1) * 1024 + i * 512, q[2 * i].x, q[2 * i + 1].x, q[2 * i].z, q[2 * i + 1].z);
          }
          __syncwarp();
          arrive_e(bar + B_HALO);
        }
      }
      if (b) {
#pragma unroll 1
        for (int q = 0; q < 2; q++) all_there(m * 128 + U_HH + 32 + q * 16 + (lane & (15 >> q)), bar + (q ? B_HH2 : B_HH + 8));
      }
    }
  } else {
    const int wg = warp >> 2, wq = warp & 3, tid = threadIdx.x;
    const int g = lane >> 2, c = lane & 3;
    const int sec0 = (m >> 1) & 1, hf0 = m & 1, ks0 = (m >> 2) & 3;
    uint4 wv[8];
    uint32_t ep0; uint16_t cv_;
    asm volatile("ld.global.nc.u16 %0, [%1];" : "=h"(cv_) : "l"(cvec + ks0 * 256 + warp * 32 + lane));
    asm volatile("ld.global.u32 %0, [%1];" : "=r"(ep0) : "l"(gs->epoch + (blockIdx.x | (lane & by_sm & 2))));
    if (!extra) {
      const bf16* wp = wmod + (size_t)(ks0 * 256 + warp * 32 + (lane >> 3)) * 6144 + sec0 * 1024 + j * 128 + hf0 * 64 + (lane & 7) * 8;
#pragma unroll
      for (int i = 0; i < 8; i++) wv[i] = ldg_nc(wp + (size_t)i * 4 * 6144);
      cl_arrive_relaxed();
    }
    asm volatile("setmaxnreg.inc.sync.aligned.u32 232;" ::: "memory");
    if (__builtin_expect(extra, 0)) {
      const uint32_t ep = ep0 + 1;
      float sv[4];
#pragma unroll
      for (int p = 0; p < 4; p++) sv[p] = silu_c(__bfloat162float(cvec[64 * (4 * p + (lane >> 3)) + 8 * warp + (lane & 7)]));
      named_bar(2, 288);
      int s = 0, par = 0;
#pragma unroll 1
      for (int sec = 0; sec < 4; sec++) {
        float a[8] = {0, 0, 0, 0, 0, 0, 0, 0};
#pragma unroll 1
        for (int it = 0; it < 16; it++) {
          const float sc = it < 4 ? sv[0] : it < 8 ? sv[1] : it < 12 ? sv[2] : sv[3];
          mbar_wait(bar + B_FULL6 + s * 8, par);
          uint4 w[8];
#pragma unroll
          for (int i = 0; i < 8; i++) w[i] = lds128(sb + s * 32768 + (warp * 8 + i) * 512 + lane * 16);
#pragma unroll
          for (int i = 0; i < 8; i++) gemv_fma(a, w[i], __shfl_sync(~0u, sc, (it & 3) * 8 + i));
          if (lane == 0) mbar_arrive(bar + B_EMPTY6 + s * 8);
          if (++s == 6) { s = 0; par ^= 1; }
        }
        const uint32_t red = sb + STG + sec * 8192;
        sts128(red + warp * 1024 + lane * 32, __float_as_uint(a[0]), __float_as_uint(a[1]), __float_as_uint(a[2]), __float_as_uint(a[3]));
        sts128(red + warp * 1024 + lane * 32 + 16, __float_as_uint(a[4]), __float_as_uint(a[5]), __float_as_uint(a[6]), __float_as_uint(a[7]));
        named_bar(1, 256);
        float t = 0;
#pragma unroll
        for (int q = 0; q < 8; q++) t += lds32f(red + q * 1024 + tid * 4);
        t = bf_round(t);
        if (sec == 2) t = bf_round(t + 1.f);
        st_rlx2(gs->modv + sec * 1024 + (bid + 4) * 256 + tid, __float_as_uint(t), ep);
      }
      if (tid == 0) gs->epoch[blockIdx.x] = ep;
      return;
    }
    const int row0 = wg * 64 + wq * 16 + g;
    if (c < 2) st_rlx2(gs->stat + m * 1024 + j * 128 + row0 + c * 8, 0, 0);
    cl_wait();
    uint32_t ep;
    asm volatile("add.u32 %0, %1, 1;" : "=r"(ep) : "r"(ep0) : "memory");
    const float sc_ = silu_c(__uint_as_float((uint32_t)cv_ << 16));
    const uint32_t rel = mapa(bar, (lane & 1) ^ rank);
    const uint32_t stg_row = sb + STG + (wg * 64 + wq * 16 + (lane & 15)) * 128;
    const uint32_t fre = bar + B_FREE;
    Ring r4{0, 0, 0}, r6{0, 0, 0};
    auto none = [](auto) {};
    uint32_t xk[32];
    {
      float a[8] = {0, 0, 0, 0, 0, 0, 0, 0};
#pragma unroll
      for (int i = 0; i < 8; i++) gemv_fma(a, wv[i], __shfl_sync(~0u, sc_, i * 4 + (lane >> 3)));
#pragma unroll
      for (int i = 0; i < 8; i++) { a[i] += __shfl_xor_sync(~0u, a[i], 8); a[i] += __shfl_xor_sync(~0u, a[i], 16); }
      if (lane < 8) {
        sts128(sb + RED_OFF + warp * 256 + lane * 32, __float_as_uint(a[0]), __float_as_uint(a[1]), __float_as_uint(a[2]), __float_as_uint(a[3]));
        sts128(sb + RED_OFF + warp * 256 + lane * 32 + 16, __float_as_uint(a[4]), __float_as_uint(a[5]), __float_as_uint(a[6]), __float_as_uint(a[7]));
      }
      named_bar(1, 256);
      if (tid < 64) {
        float s = 0;
#pragma unroll
        for (int w = 0; w < 8; w++) s += lds32f(sb + RED_OFF + w * 256 + tid * 4);
        st_rlx1(gs->modp + ((j * 2 + sec0) * 4 + ks0) * 128 + hf0 * 64 + tid, (__float_as_uint(s) & ~255u) | tag_of(ep));
      }
      float v[64];
      mbar_wait(bar + B_X, 0); mbar_wait(bar + B_X + 8, 0);
#pragma unroll
      for (int i = 0; i < 16; i += 2) {
        uint32_t w0, w1, w2, w3;
        ldsm4(stg_row + (i >> 3) * BLK + ((((i & 7) + (lane >> 4)) ^ (lane & 7)) << 4), w0, w1, w2, w3);
        xk[2 * i] = w0; xk[2 * i + 1] = w1; xk[2 * i + 2] = w2; xk[2 * i + 3] = w3;
        v[4 * i] = bf_lo(w0); v[4 * i + 1] = bf_hi(w0); v[4 * i + 2] = bf_lo(w1); v[4 * i + 3] = bf_hi(w1);
        v[4 * i + 4] = bf_lo(w2); v[4 * i + 5] = bf_hi(w2); v[4 * i + 6] = bf_lo(w3); v[4 * i + 7] = bf_hi(w3);
      }
      ln_publish(v, gs->stat + m * 1024, j, row0, lane, ep);
      mod_store(sb, tid >> 7, tid & 127, mod_gather(gs->modp + (j * 2 + (tid >> 7)) * 512 + (tid & 127), ep));
      named_bar(1, 256);
      ln_apply(v, gs->stat + m * 1024, row0, ep, sb, 0, 1, stg_row, wg, lane);
      named_bar(1, 256);
    }
    {
      uint32_t kf[32], vf[32], pv[32];
      const bool first = wq == 0 && m == 0;
      const uint32_t xa = sb + STG + wg * HALF + wq * 2048 + lane * 16;
      {
        float acc[128];
        mainloop<256, 4, 0, 0>(acc, 16, true, r4, sb, wg, lane, rel, none, none, [&] {
          mbar_wait(fre + 8, 0);
          if (c < 2) st_rlx2(gs->stat + (16 + m) * 1024 + j * 128 + row0 + c * 8, 0, 0);
        });
#pragma unroll
        for (int i = 0; i < 32; i++) { kf[i] = pack2(acc[2 * i], acc[2 * i + 1]); vf[i] = pack2(acc[64 + 2 * i], acc[65 + 2 * i]); }
      }
      float acc[64];
      constexpr int QP = 2;
      mainloop<128, 6, 8 / QP, 0>(acc, 16, false, r6, sb, wg, lane, rel, [&](auto ic) {
        constexpr int q = (ic.v - 1) * QP;
#pragma unroll
        for (int i = 4 * q; i < 4 * (q + QP); i++) vf[i] = movm(vf[i]);
        if (wq == 3) {
          if (m < 15) {
            uint4* hp = gs->halo + (((m + 1) * 8 + j) * 2 + wg) * 512 + lane;
#pragma unroll
            for (int i = 2 * q; i < 2 * (q + QP); i++) st_rlx4(hp + i * 32, kf[2 * i + 1], ep, vf[2 * i + 1], ep);
          }
        } else {
#pragma unroll
          for (int i = q; i < q + QP; i++) sts128(xa + 2048 + (i >> 2) * BLK + (i & 3) * 512, kf[4 * i + 1], kf[4 * i + 3], vf[4 * i + 1], vf[4 * i + 3]);
        }
      }, none, [&] {
        named_bar(2 + wg, 128);
        if (wq == 0) mbar_wait(bar + B_HALO, 0);
#pragma unroll
        for (int i = 0; i < 8; i++) {
          uint4 q = lds128(xa + (i >> 2) * BLK + (i & 3) * 512);
          pv[4 * i] = q.x; pv[4 * i + 1] = q.y; pv[4 * i + 2] = q.z; pv[4 * i + 3] = q.w;
        }
        __syncwarp();
      });
      int gz = g;
#pragma unroll
      for (int b = 0; b < 2; b++) {
        const bool up0 = 2 * c > gz, up1 = 2 * c + 1 > gz;
        const uint32_t mup = (up0 ? 0xffffu : 0u) | (up1 ? 0xffff0000u : 0u);
        float l[2][4], mx[4];
#pragma unroll
        for (int h = 0; h < 2; h++) {
          uint32_t q[8];
          const int k = 16 * b + 8 * h;
#pragma unroll
          for (int i = 0; i < 8; i++) q[i] = pack2(acc[2 * k + 2 * i], acc[2 * k + 2 * i + 1]);
          float s0[4], s1[4], s2[4];
          mma16z(s0, q[0], q[1], q[2], q[3], pv[k], pv[k + 1]); mma16z(s1, q[0], q[1], q[2], q[3], kf[k], kf[k + 2]); mma16z(s2, q[0], q[1], q[2], q[3], kf[k + 1], kf[k + 3]);
          mma16(s0, q[4], q[5], q[6], q[7], pv[k + 4], pv[k + 5]); mma16(s1, q[4], q[5], q[6], q[7], kf[k + 4], kf[k + 6]); mma16(s2, q[4], q[5], q[6], q[7], kf[k + 5], kf[k + 7]);
          if (first) { s0[0] = -INFINITY; s0[1] = -INFINITY; }
          l[h][0] = up0 ? s0[0] : s1[0]; l[h][1] = up1 ? s0[1] : s1[1]; l[h][2] = up0 ? s1[2] : s2[2]; l[h][3] = up1 ? s1[3] : s2[3];
          mx[2 * h] = fmaxf(l[h][0], l[h][1]); mx[2 * h + 1] = fmaxf(l[h][2], l[h][3]);
        }
#pragma unroll
        for (int o = 1; o < 4; o <<= 1) {
#pragma unroll
          for (int h = 0; h < 4; h++) mx[h] = fmaxf(mx[h], __shfl_xor_sync(~0u, mx[h], o));
        }
#pragma unroll
        for (int h = 0; h < 2; h++) {
          const float n0 = -mx[2 * h] * SCL, n1 = -mx[2 * h + 1] * SCL;
          const uint32_t pa = pack2(ex2(fmaf(l[h][0], SCL, n0)), ex2(fmaf(l[h][1], SCL, n0))), pb = pack2(ex2(fmaf(l[h][2], SCL, n1)), ex2(fmaf(l[h][3], SCL, n1)));
          float sm[4];
          mma8z(sm, pa, pb, 0x3f803f80u);
          const float ia = rcp(sm[0]), ib = rcp(sm[2]);
#pragma unroll
          for (int i = 8 * b + 4 * h; i < 8 * b + 4 * h + 4; i += 2) {
            uint32_t of[4];
#pragma unroll
            for (int d = 0; d < 2; d++) {
              float o[4];
              mma16z(o, pa & ~mup, pb & mup, 0u, pb & ~mup, vf[2 * (i + d)], vf[2 * (i + d) + 1]);
              mma8(o, pa & mup, 0u, pv[2 * i + 2 + d]);
              of[2 * d] = pack2(o[0] * ia, o[1] * ia); of[2 * d + 1] = pack2(o[2] * ib, o[3] * ib);
            }
            stsm4(stg_row + b * BLK + ((((i & 7) + (lane >> 4)) ^ (lane & 7)) << 4), of[0], of[1], of[2], of[3]);
          }
        }
        stage_done(sb, wg, b, lane);
        if (b == 0) gz += __float_as_uint(lds32f(bar + ZERO));
      }
      named_bar(1, 256);
    }
    uint32_t pk[64];
    {
      float acc[64];
      mainloop<128, 6, 0, 0>(acc, 16, true, r6, sb, wg, lane, rel, none, none, [&] {
        mbar_wait(bar + B_MOD, 0); mbar_wait(fre + 8, 1);
        load_vec(pk + 32, sb, 2, 0, lane); load_vec(pk + 40, sb, 2, 1, lane);
#pragma unroll
        for (int i = 0; i < 32; i++) { pk[i] = xk[i]; asm volatile("" : "+r"(pk[i])); }
      });
#pragma unroll
      for (int i = 0; i < 32; i++) {
        acc[2 * i] = fmaf(acc[2 * i], bf_lo(pk[32 + (i >> 1)]), bf_lo(pk[i]));
        acc[2 * i + 1] = fmaf(acc[2 * i + 1], bf_hi(pk[32 + (i >> 1)]), bf_hi(pk[i]));
      }
      ln_publish(acc, gs->stat + (16 + m) * 1024, j, row0, lane, ep);
      mbar_wait(bar + B_FULL6 + 16, 1);
      if (lane < 2) mbar_arrive_cl(rel + B_EMPTY6 + 16);
      ring_next<6>(r6);
#pragma unroll
      for (int i = 0; i < 32; i++) { pk[i] = pack2(acc[2 * i], acc[2 * i + 1]); pk[32 + i] = 0; }
      ln_apply(acc, gs->stat + (16 + m) * 1024, row0, ep, sb, 3, 4, stg_row, wg, lane);
      named_bar(1, 256);
    }
    auto swiglu = [&](int q, int uo, int par) {
      if ((q & 3) == 0 && par >= 0) mbar_wait(fre + 2 * q, par);
      uint32_t w[4];
#pragma unroll
      for (int u = 0; u < 4; u++) w[u] = silu_mul2(pk[4 * q + u], pk[uo + 4 * q + u]);
      stsm4(stg_row + (q >> 2) * BLK + ((((2 * q & 7) + (lane >> 4)) ^ (lane & 7)) << 4), w[0], w[1], w[2], w[3]);
    };
    r4.s = r4.wrap = 2;
#pragma unroll 1
    for (int t = 0; t < 3; t++) {
      float acc[128];
      mainloop<256, 4, 4, 1>(acc, 16, t == 0, r4, sb, wg, lane, rel, [&](auto ic) {
        if (t) {
          if (ic.v == 3) stage_done(sb, wg, 0, lane);
          swiglu(2 * ic.v - 2, 32, ~t & 1); swiglu(2 * ic.v - 1, 32, 0);
        }
      }, [&](int it) {
        if (t && it == 5) stage_done(sb, wg, 1, lane);
#pragma unroll
        for (int i = 0; i < 8; i++)
          if (t == 0 && it == 8 + i) gs->x1[bid * 2048 + (i >> 2) * 1024 + warp * 128 + (i & 3) * 32 + lane] = make_uint4(pk[4 * i], pk[4 * i + 1], pk[4 * i + 2], pk[4 * i + 3]);
      }, [&] { if (t == 0) fence_async_global(); else if (t == 2) mbar_wait(bar + B_X, 1); }, t & 1);
#pragma unroll
      for (int i = 0; i < 64; i++) pk[i] = pack2(acc[2 * i], acc[2 * i + 1]);
    }
    uint32_t x1[32];
    {
      float acc[64];
      mainloop<128, 6, 10, 1>(acc, 16, false, r6, sb, wg, lane, rel, [&](auto ic) {
        constexpr int b = ic.v > 5, q = ic.v - 5 * b;
        if (q == 1) {
          if (b) stage_done(sb, wg, 0, lane);
#pragma unroll
          for (int i = 4 * b; i < 4 * b + 4; i++) { const uint4 x = lds128(sb + STG + b * BLK + warp * 2048 + (i & 3) * 512 + lane * 16); x1[4 * i] = x.x; x1[4 * i + 1] = x.y; x1[4 * i + 2] = x.z; x1[4 * i + 3] = x.w; }
          __syncwarp();
        } else swiglu(4 * b + q - 2, 32, -1);
      }, [&](int it) { if (it == 11) stage_done(sb, wg, 1, lane); }, [] {}, 1);
#pragma unroll
      for (int i = 0; i < 32; i++) pk[i] = pack2(acc[2 * i], acc[2 * i + 1]);
    }
    {
      float acc[64];
      mainloop<128, 6, 4, TAILLAG>(acc, 56, false, r6, sb, wg, lane, rel, [&](auto ic) { swiglu(ic.v - 1, 16, 1); },
                                   [&](int it) { if (it == 5) stage_done(sb, wg, 0, lane); }, [&] {
        load_vec(pk + 32, sb, 5, 0, lane); load_vec(pk + 40, sb, 5, 1, lane);
        mbar_wait(fre, 0); mbar_wait(fre + 8, 1);
      }, 0);
      __syncwarp();
      cl_arrive_relaxed();
#pragma unroll
      for (int i = 0; i < 16; i += 2) {
        uint32_t w[4];
#pragma unroll
        for (int u = 0; u < 4; u++) {
          const int q = 2 * i + u;
          w[u] = pack2(fmaf(acc[2 * q], bf_lo(pk[32 + (q >> 1)]), bf_lo(x1[q])), fmaf(acc[2 * q + 1], bf_hi(pk[32 + (q >> 1)]), bf_hi(x1[q])));
        }
        stsm4(stg_row + (i >> 3) * BLK + ((((i & 7) + (lane >> 4)) ^ (lane & 7)) << 4), w[0], w[1], w[2], w[3]);
        if ((i & 7) == 6) {
          fence_async_smem();
          named_bar(2 + wg, 128);
          if (wq == 0 && elect()) { tma_store_3d(&maps.out, sb + STG + (i >> 3) * BLK + wg * HALF, j * 128 + (i >> 3) * 64, m * 64, wg); bulk_commit(); }
          if (i < 8) x1[16] |= __float_as_uint(lds32f(bar + ZERO));
        }
      }
      if (wq == 0) bulk_wait_read();
      if (tid == 0) gs->epoch[blockIdx.x] = ep;
      cl_wait();
    }
  }
}

typedef CUresult (*EncodeFn)(CUtensorMap*, CUtensorMapDataType, cuuint32_t, void*, const cuuint64_t*, const cuuint64_t*, const cuuint32_t*, const cuuint32_t*,
                             CUtensorMapInterleave, CUtensorMapSwizzle, CUtensorMapL2promotion, CUtensorMapFloatOOBfill);

void make_map(EncodeFn fn, CUtensorMap* mp, const void* base, uint64_t d0, uint64_t d1, uint64_t d2, uint64_t s1, uint64_t s2, uint32_t b2, uint32_t b0 = 64) {
  cuuint64_t d[3] = {d0, d1, d2}, s[2] = {s1, s2};
  cuuint32_t b[3] = {b0, 64, b2}, e[3] = {1, 1, 1};
  fn(mp, CU_TENSOR_MAP_DATA_TYPE_BFLOAT16, 3, (void*)base, d, s, b, e, CU_TENSOR_MAP_INTERLEAVE_NONE, b0 == 64 ? CU_TENSOR_MAP_SWIZZLE_128B : CU_TENSOR_MAP_SWIZZLE_NONE,
     CU_TENSOR_MAP_L2_PROMOTION_L2_128B, CU_TENSOR_MAP_FLOAT_OOB_FILL_NONE);
}

__global__ void probe_kernel() {}
int max_clusters(int size) {
  cudaLaunchConfig_t cfg = {};
  cudaLaunchAttribute at;
  at.id = cudaLaunchAttributeClusterDimension; at.val.clusterDim.x = size; at.val.clusterDim.y = 1; at.val.clusterDim.z = 1;
  cfg.gridDim = dim3(size * 66); cfg.blockDim = dim3(384); cfg.dynamicSmemBytes = SMEM_BYTES; cfg.attrs = &at; cfg.numAttrs = 1;
  int n = 0;
  if (cudaOccupancyMaxActiveClusters(&n, probe_kernel, &cfg) != cudaSuccess) { cudaGetLastError(); return 0; }
  return n;
}

}

extern "C" void kernel_launch(void* const* d_in, const int* in_sizes, int n_in, void* d_out, int out_size) {
  static EncodeFn fn = nullptr;
  static int by_sm = 0;
  static Scratch* gs = nullptr;
  if (!fn) {
    void* p = nullptr; cudaDriverEntryPointQueryResult q;
    cudaGetDriverEntryPoint("cuTensorMapEncodeTiled", &p, cudaEnableDefault, &q);
    fn = (EncodeFn)p;
    cudaFuncSetAttribute(fused_kernel, cudaFuncAttributeMaxDynamicSharedMemorySize, SMEM_BYTES);
    int dev = 0, sms = 0;
    cudaGetSymbolAddress((void**)&gs, g_scratch);
    cudaGetDevice(&dev);
    cudaDeviceGetAttribute(&sms, cudaDevAttrMultiProcessorCount, dev);
    cudaFuncSetAttribute(probe_kernel, cudaFuncAttributeMaxDynamicSharedMemorySize, SMEM_BYTES);
    by_sm = sms == 132 && max_clusters(2) == 66 && max_clusters(4) == 30 && max_clusters(6) == 17 && max_clusters(8) == 15;
  }
  Maps mp;
  make_map(fn, &mp.x, d_in[0], D_, S_ / 2, 2, 4096, 2048, 2);
  make_map(fn, &mp.out, d_out, D_, S_ / 2, 2, 4096, 2048, 1);
  make_map(fn, &mp.wqkv, d_in[1], 64, D_, 3 * D_ / 64, 3 * D_ * 2, 128, 2);
  make_map(fn, &mp.wo, d_in[2], 64, D_, D_ / 64, D_ * 2, 128, 2);
  make_map(fn, &mp.w1, d_in[4], 64, D_, F_ / 64, F_ * 2, 128, 2);
  make_map(fn, &mp.w3, d_in[5], 64, D_, F_ / 64, F_ * 2, 128, 2);
  make_map(fn, &mp.w1s, d_in[4], 64, D_, F_ / 64, F_ * 2, 128, 1);
  make_map(fn, &mp.w3s, d_in[5], 64, D_, F_ / 64, F_ * 2, 128, 1);
  make_map(fn, &mp.w2, d_in[6], 64, F_, D_ / 64, D_ * 2, 128, 2);
  make_map(fn, &mp.wmod, d_in[8], 256, D_, 24, 6 * D_ * 2, 512, 1, 256);
  fused_kernel<<<132, 384, SMEM_BYTES>>>((const bf16*)d_in[7], (const bf16*)d_in[8], gs, by_sm, mp);
}
```

```cpp
#include <cuda_runtime.h>
#include <cuda_bf16.h>
#include <cuda.h>
#include <stdint.h>

typedef __nv_bfloat16 bf16;

namespace {

constexpr int S_ = 2048, D_ = 1024, F_ = 3584;
constexpr int BLK = 16384;
constexpr int HALF = 8192;
constexpr int RING = 196608;
constexpr int STG = RING;
constexpr int MISC = RING + 2 * BLK;
constexpr int SMEM_BYTES = MISC + 3072;
constexpr int B_FULL4 = 0, B_EMPTY4 = 32, B_FULL6 = 64, B_EMPTY6 = 112, B_RDY = 160, B_FREE = 176, B_LAG = 192, B_X = 208, B_MOD = 224, B_HALO = 232, B_HH = 256, B_ALL = 272, B_HH2 = 288, ZERO = 296;
constexpr int MODV = 512;
constexpr int RED_OFF = 0;
constexpr float SCL = 0.17677669529663687f * 1.4426950408889634f;
constexpr int U_HH = 64;
constexpr int FS = 8;
constexpr int NPIECE = 4, PSLEEP = 300;
constexpr int XSLEEP = 4000, HSLEEP = 400;
constexpr uint32_t XDELAY = 2300, GAP = 250;
constexpr uint32_t B1P = 3700, B1D = 700;
constexpr int TAILLAG = 5;

struct Maps { CUtensorMap x, out, wqkv, wo, w1, w3, w1s, w3s, w2, wmod; };

struct Scratch {
  uint32_t epoch[256];
  uint32_t flag[16 * 128 * FS];
  uint32_t modp[8 * 2 * 4 * 128];
  uint2 modv[4 * 1024];
  uint2 stat[2 * 16 * 8 * 128];
  uint4 halo[16 * 8 * 2 * 512];
  uint4 x1[128 * 8 * 256];
  uint4 h[16 * 16 * 1024];
  uint4 o[16 * 16 * 1024];
  uint4 hh[16 * 56 * 1024];
};
__device__ __align__(1024) Scratch g_scratch;

__device__ __forceinline__ void bail() { asm volatile("st.global.u32 [%0], %1;" :: "l"(0ull), "r"(0) : "memory"); }
__device__ __forceinline__ uint32_t smem_u32(const void* p) { return (uint32_t)__cvta_generic_to_shared(p); }
__device__ __forceinline__ void mbar_init(uint32_t bar, uint32_t cnt) { asm volatile("mbarrier.init.shared::cta.b64 [%0], %1;" :: "r"(bar), "r"(cnt) : "memory"); }
__device__ __forceinline__ void mbar_arrive(uint32_t bar) { asm volatile("mbarrier.arrive.shared::cta.b64 _, [%0];" :: "r"(bar) : "memory"); }
__device__ __forceinline__ void mbar_arrive_cl(uint32_t cl_addr) { asm volatile("mbarrier.arrive.shared::cluster.b64 _, [%0];" :: "r"(cl_addr) : "memory"); }
__device__ __forceinline__ uint32_t mapa(uint32_t addr, uint32_t cta) { uint32_t r; asm("mapa.shared::cluster.u32 %0, %1, %2;" : "=r"(r) : "r"(addr), "r"(cta)); return r; }
__device__ __forceinline__ void mbar_wait(uint32_t bar, uint32_t parity) {
  asm volatile("{\n.reg .pred p;\n.reg .b32 n;\n.reg .b64 z;\nmov.b32 n, 0;\nmov.b64 z, 0;\n"
               "W: add.u32 n, n, 1;\nsetp.gt.u32 p, n, 0x400000;\n@p st.global.u32 [z], n;\n"
               "mbarrier.try_wait.parity.shared::cta.b64 p, [%0], %1;\n@!p bra W;\n}" :: "r"(bar), "r"(parity) : "memory");
}
__device__ __forceinline__ void tma_store_3d(const CUtensorMap* m, uint32_t src, int c0, int c1, int c2) {
  asm volatile("cp.async.bulk.tensor.3d.global.shared::cta.bulk_group [%0, {%2, %3, %4}], [%1];" :: "l"(m), "r"(src), "r"(c0), "r"(c1), "r"(c2) : "memory");
}
#define ELECT "{\n.reg .pred p;\nelect.sync _|p, 0xffffffff;\n@p "
__device__ __forceinline__ void expect_e(uint32_t bar, uint32_t bytes) { asm volatile(ELECT "mbarrier.arrive.expect_tx.shared::cta.b64 _, [%0], %1;\n}" :: "r"(bar), "r"(bytes) : "memory"); }
__device__ __forceinline__ void tma_3d_e(uint32_t dst, const CUtensorMap* m, uint32_t bar, int c0, int c1, int c2) {
  asm volatile(ELECT "cp.async.bulk.tensor.3d.shared::cluster.global.mbarrier::complete_tx::bytes [%0], [%1, {%3, %4, %5}], [%2];\n}" :: "r"(dst), "l"(m), "r"(bar), "r"(c0), "r"(c1), "r"(c2) : "memory");
}
__device__ __forceinline__ void bulk_ld_e(uint32_t dst, const void* src, uint32_t bytes, uint32_t bar) {
  asm volatile(ELECT "cp.async.bulk.shared::cluster.global.mbarrier::complete_tx::bytes [%0], [%1], %2, [%3];\n}" :: "r"(dst), "l"(src), "r"(bytes), "r"(bar) : "memory");
}
__device__ __forceinline__ void bulk_ld_mc_e(uint32_t dst, const void* src, uint32_t bytes, uint32_t bar) {
  asm volatile(ELECT "cp.async.bulk.shared::cluster.global.mbarrier::complete_tx::bytes.multicast::cluster [%0], [%1], %2, [%3], %4;\n}" :: "r"(dst), "l"(src), "r"(bytes), "r"(bar), "h"((uint16_t)3) : "memory");
}
__device__ __forceinline__ void bulk_push_e(uint32_t dst_cl, uint32_t src, uint32_t bytes, uint32_t bar_cl) {
  asm volatile(ELECT "cp.async.bulk.shared::cluster.shared::cta.mbarrier::complete_tx::bytes [%0], [%1], %2, [%3];\n}" :: "r"(dst_cl), "r"(src), "r"(bytes), "r"(bar_cl) : "memory");
}
__device__ __forceinline__ void arrive_e(uint32_t bar) { asm volatile(ELECT "mbarrier.arrive.shared::cta.b64 _, [%0];\n}" :: "r"(bar) : "memory"); }
__device__ __forceinline__ void bulk_st_e(void* dst, uint32_t src, uint32_t bytes) {
  asm volatile(ELECT "cp.async.bulk.global.shared::cta.bulk_group [%0], [%1], %2;\n}" :: "l"(dst), "r"(src), "r"(bytes) : "memory");
}
__device__ __forceinline__ void publish_e(uint32_t free_bar, uint32_t* flag, uint32_t ep) {
  asm volatile(ELECT "cp.async.bulk.commit_group;\n@p cp.async.bulk.wait_group 0;\n@p mbarrier.arrive.shared::cta.b64 _, [%0];\n@p st.release.gpu.global.u32 [%1], %2;\n}"
               :: "r"(free_bar), "l"(flag), "r"(ep) : "memory");
}
__device__ __forceinline__ void bulk_commit() { asm volatile("cp.async.bulk.commit_group;" ::: "memory"); }
__device__ __forceinline__ void bulk_wait_read() { asm volatile("cp.async.bulk.wait_group.read 0;" ::: "memory"); }
__device__ __forceinline__ void fence_async_global() { asm volatile("fence.proxy.async.global;" ::: "memory"); }
__device__ __forceinline__ void fence_async_smem() { asm volatile("fence.proxy.async.shared::cta;" ::: "memory"); }
__device__ __forceinline__ void wg_arrive() { asm volatile("wgmma.fence.sync.aligned;" ::: "memory"); }
__device__ __forceinline__ void wg_commit() { asm volatile("wgmma.commit_group.sync.aligned;" ::: "memory"); }
template <int N> __device__ __forceinline__ void wg_wait() { asm volatile("wgmma.wait_group.sync.aligned %0;" :: "n"(N) : "memory"); }
__device__ __forceinline__ void cl_arrive_relaxed() { asm volatile("barrier.cluster.arrive.relaxed.aligned;" ::: "memory"); }
__device__ __forceinline__ void cl_wait() { asm volatile("barrier.cluster.wait.acquire.aligned;" ::: "memory"); }
__device__ __forceinline__ bool elect() { uint32_t p; asm volatile("{\n.reg .pred p;\nelect.sync _|p, 0xffffffff;\nselp.u32 %0, 1, 0, p;\n}" : "=r"(p)); return p; }
__device__ __forceinline__ void named_bar(int id, int n) { asm volatile("bar.sync %0, %1;" :: "r"(id), "r"(n) : "memory"); }
__device__ __forceinline__ uint32_t pack2(float lo, float hi) { uint32_t r; asm("cvt.rn.bf16x2.f32 %0, %1, %2;" : "=r"(r) : "f"(hi), "f"(lo)); return r; }
__device__ __forceinline__ float bf_lo(uint32_t w) { return __uint_as_float(w << 16); }
__device__ __forceinline__ float bf_hi(uint32_t w) { return __uint_as_float(w & 0xffff0000u); }
__device__ __forceinline__ float bf_round(float v) { return __bfloat162float(__float2bfloat16_rn(v)); }
__device__ __forceinline__ void stsm4(uint32_t addr, uint32_t a, uint32_t b, uint32_t c, uint32_t d) {
  asm volatile("stmatrix.sync.aligned.m8n8.x4.shared.b16 [%0], {%1, %2, %3, %4};" :: "r"(addr), "r"(a), "r"(b), "r"(c), "r"(d) : "memory");
}
__device__ __forceinline__ void ldsm4(uint32_t addr, uint32_t& a, uint32_t& b, uint32_t& c, uint32_t& d) {
  asm volatile("ldmatrix.sync.aligned.m8n8.x4.shared.b16 {%0, %1, %2, %3}, [%4];" : "=r"(a), "=r"(b), "=r"(c), "=r"(d) : "r"(addr) : "memory");
}
__device__ __forceinline__ uint32_t movm(uint32_t a) { uint32_t r; asm volatile("movmatrix.sync.aligned.m8n8.trans.b16 %0, %1;" : "=r"(r) : "r"(a)); return r; }
__device__ __forceinline__ void mma16(float (&d)[4], uint32_t a0, uint32_t a1, uint32_t a2, uint32_t a3, uint32_t b0, uint32_t b1) {
  asm("mma.sync.aligned.m16n8k16.row.col.f32.bf16.bf16.f32 {%0,%1,%2,%3}, {%4,%5,%6,%7}, {%8,%9}, {%0,%1,%2,%3};"
               : "+f"(d[0]), "+f"(d[1]), "+f"(d[2]), "+f"(d[3]) : "r"(a0), "r"(a1), "r"(a2), "r"(a3), "r"(b0), "r"(b1));
}
__device__ __forceinline__ void mma16z(float (&d)[4], uint32_t a0, uint32_t a1, uint32_t a2, uint32_t a3, uint32_t b0, uint32_t b1) {
  asm("mma.sync.aligned.m16n8k16.row.col.f32.bf16.bf16.f32 {%0,%1,%2,%3}, {%4,%5,%6,%7}, {%8,%9}, {%10,%10,%10,%10};"
      : "=f"(d[0]), "=f"(d[1]), "=f"(d[2]), "=f"(d[3]) : "r"(a0), "r"(a1), "r"(a2), "r"(a3), "r"(b0), "r"(b1), "f"(0.f));
}
__device__ __forceinline__ void mma8z(float (&d)[4], uint32_t a0, uint32_t a1, uint32_t b0) {
  asm("mma.sync.aligned.m16n8k8.row.col.f32.bf16.bf16.f32 {%0,%1,%2,%3}, {%4,%5}, {%6}, {%7,%7,%7,%7};"
      : "=f"(d[0]), "=f"(d[1]), "=f"(d[2]), "=f"(d[3]) : "r"(a0), "r"(a1), "r"(b0), "f"(0.f));
}
__device__ __forceinline__ void mma8(float (&d)[4], uint32_t a0, uint32_t a1, uint32_t b0) {
  asm("mma.sync.aligned.m16n8k8.row.col.f32.bf16.bf16.f32 {%0,%1,%2,%3}, {%4,%5}, {%6}, {%0,%1,%2,%3};"
               : "+f"(d[0]), "+f"(d[1]), "+f"(d[2]), "+f"(d[3]) : "r"(a0), "r"(a1), "r"(b0));
}
__device__ __forceinline__ uint4 lds128(uint32_t a) { uint4 v; asm volatile("ld.shared.v4.u32 {%0,%1,%2,%3}, [%4];" : "=r"(v.x), "=r"(v.y), "=r"(v.z), "=r"(v.w) : "r"(a) : "memory"); return v; }
__device__ __forceinline__ void sts128(uint32_t a, uint32_t x, uint32_t y, uint32_t z, uint32_t w) { asm volatile("st.shared.v4.u32 [%0], {%1,%2,%3,%4};" :: "r"(a), "r"(x), "r"(y), "r"(z), "r"(w) : "memory"); }
__device__ __forceinline__ float lds32f(uint32_t a) { float v; asm volatile("ld.shared.f32 %0, [%1];" : "=f"(v) : "r"(a) : "memory"); return v; }
__device__ __forceinline__ void sts16(uint32_t a, bf16 v) { asm volatile("st.shared.b16 [%0], %1;" :: "r"(a), "h"(__bfloat16_as_ushort(v)) : "memory"); }
__device__ __forceinline__ uint4 ldg_nc(const void* p) { uint4 v; asm volatile("ld.global.nc.L1::no_allocate.v4.u32 {%0,%1,%2,%3}, [%4];" : "=r"(v.x), "=r"(v.y), "=r"(v.z), "=r"(v.w) : "l"(p)); return v; }
__device__ __forceinline__ uint4 ld_rlx4(const uint4* p) {
  unsigned long long a, b; asm volatile("ld.relaxed.gpu.global.v2.b64 {%0,%1}, [%2];" : "=l"(a), "=l"(b) : "l"(p) : "memory");
  return make_uint4((uint32_t)a, (uint32_t)(a >> 32), (uint32_t)b, (uint32_t)(b >> 32));
}
__device__ __forceinline__ uint2 ld_rlx2(const uint2* p) { unsigned long long a; asm volatile("ld.relaxed.gpu.global.b64 %0, [%1];" : "=l"(a) : "l"(p) : "memory"); return make_uint2((uint32_t)a, (uint32_t)(a >> 32)); }
__device__ __forceinline__ void st_rlx4(uint4* p, uint32_t x, uint32_t y, uint32_t z, uint32_t w) {
  asm volatile("st.relaxed.gpu.global.v2.b64 [%0], {%1,%2};" :: "l"(p), "l"((unsigned long long)x | ((unsigned long long)y << 32)), "l"((unsigned long long)z | ((unsigned long long)w << 32)) : "memory");
}
__device__ __forceinline__ void st_rlx2(uint2* p, uint32_t x, uint32_t y) { asm volatile("st.relaxed.gpu.global.b64 [%0], %1;" :: "l"(p), "l"((unsigned long long)x | ((unsigned long long)y << 32)) : "memory"); }
__device__ __forceinline__ void st_rlx1(uint32_t* p, uint32_t v) { asm volatile("st.relaxed.gpu.global.u32 [%0], %1;" :: "l"(p), "r"(v) : "memory"); }
__device__ __forceinline__ uint32_t ld_rlx1(const uint32_t* p) { uint32_t v; asm volatile("ld.relaxed.gpu.global.u32 %0, [%1];" : "=r"(v) : "l"(p) : "memory"); return v; }
__device__ __forceinline__ uint32_t ld_acquire(const uint32_t* p) { uint32_t v; asm volatile("ld.acquire.gpu.global.u32 %0, [%1];" : "=r"(v) : "l"(p) : "memory"); return v; }
__device__ __forceinline__ void prefetch_map(const CUtensorMap* m) { asm volatile("prefetch.tensormap [%0];" :: "l"(m) : "memory"); }
__device__ __forceinline__ float rcp(float x) { float r; asm("rcp.approx.ftz.f32 %0, %1;" : "=f"(r) : "f"(x)); return r; }
__device__ __forceinline__ float ex2(float x) { float r; asm("ex2.approx.ftz.f32 %0, %1;" : "=f"(r) : "f"(x)); return r; }
__device__ __forceinline__ float tanh_fast(float x) { float r; asm("tanh.approx.f32 %0, %1;" : "=f"(r) : "f"(x)); return r; }
#define SPIN_GUARD(n) if (++(n) > (1u << 24)) bail()

__device__ __forceinline__ void wgmma_n128(float (&d)[64], uint64_t da, uint64_t db) {
  asm volatile("wgmma.mma_async.sync.aligned.m64n128k16.f32.bf16.bf16 "
    "{%0, %1, %2, %3, %4, %5, %6, %7, %8, %9, %10, %11, %12, %13, %14, %15, %16, %17, %18, %19, %20, %21, %22, %23, %24, %25, %26, %27, %28, %29, %30, %31, %32, %33, %34, %35, %36, %37, %38, %39, %40, %41, %42, %43, %44, %45, %46, %47, %48, %49, %50, %51, %52, %53, %54, %55, %56, %57, %58, %59, %60, %61, %62, %63}, "
    "%64, %65, 1, 1, 1, 0, 1;\n"
    : "+f"(d[0]), "+f"(d[1]), "+f"(d[2]), "+f"(d[3]), "+f"(d[4]), "+f"(d[5]), "+f"(d[6]), "+f"(d[7]), "+f"(d[8]), "+f"(d[9]), "+f"(d[10]), "+f"(d[11]), "+f"(d[12]), "+f"(d[13]), "+f"(d[14]), "+f"(d[15]), "+f"(d[16]), "+f"(d[17]), "+f"(d[18]), "+f"(d[19]), "+f"(d[20]), "+f"(d[21]), "+f"(d[22]), "+f"(d[23]), "+f"(d[24]), "+f"(d[25]), "+f"(d[26]), "+f"(d[27]), "+f"(d[28]), "+f"(d[29]), "+f"(d[30]), "+f"(d[31]), "+f"(d[32]), "+f"(d[33]), "+f"(d[34]), "+f"(d[35]), "+f"(d[36]), "+f"(d[37]), "+f"(d[38]), "+f"(d[39]), "+f"(d[40]), "+f"(d[41]), "+f"(d[42]), "+f"(d[43]), "+f"(d[44]), "+f"(d[45]), "+f"(d[46]), "+f"(d[47]), "+f"(d[48]), "+f"(d[49]), "+f"(d[50]), "+f"(d[51]), "+f"(d[52]), "+f"(d[53]), "+f"(d[54]), "+f"(d[55]), "+f"(d[56]), "+f"(d[57]), "+f"(d[58]), "+f"(d[59]), "+f"(d[60]), "+f"(d[61]), "+f"(d[62]), "+f"(d[63])
    : "l"(da), "l"(db));
}
__device__ __forceinline__ void wgmma_n128_first(float (&d)[64], uint64_t da, uint64_t db) {
  asm volatile("wgmma.mma_async.sync.aligned.m64n128k16.f32.bf16.bf16 "
    "{%0, %1, %2, %3, %4, %5, %6, %7, %8, %9, %10, %11, %12, %13, %14, %15, %16, %17, %18, %19, %20, %21, %22, %23, %24, %25, %26, %27, %28, %29, %30, %31, %32, %33, %34, %35, %36, %37, %38, %39, %40, %41, %42, %43, %44, %45, %46, %47, %48, %49, %50, %51, %52, %53, %54, %55, %56, %57, %58, %59, %60, %61, %62, %63}, "
    "%64, %65, 0, 1, 1, 0, 1;\n"
    : "=f"(d[0]), "=f"(d[1]), "=f"(d[2]), "=f"(d[3]), "=f"(d[4]), "=f"(d[5]), "=f"(d[6]), "=f"(d[7]), "=f"(d[8]), "=f"(d[9]), "=f"(d[10]), "=f"(d[11]), "=f"(d[12]), "=f"(d[13]), "=f"(d[14]), "=f"(d[15]), "=f"(d[16]), "=f"(d[17]), "=f"(d[18]), "=f"(d[19]), "=f"(d[20]), "=f"(d[21]), "=f"(d[22]), "=f"(d[23]), "=f"(d[24]), "=f"(d[25]), "=f"(d[26]), "=f"(d[27]), "=f"(d[28]), "=f"(d[29]), "=f"(d[30]), "=f"(d[31]), "=f"(d[32]), "=f"(d[33]), "=f"(d[34]), "=f"(d[35]), "=f"(d[36]), "=f"(d[37]), "=f"(d[38]), "=f"(d[39]), "=f"(d[40]), "=f"(d[41]), "=f"(d[42]), "=f"(d[43]), "=f"(d[44]), "=f"(d[45]), "=f"(d[46]), "=f"(d[47]), "=f"(d[48]), "=f"(d[49]), "=f"(d[50]), "=f"(d[51]), "=f"(d[52]), "=f"(d[53]), "=f"(d[54]), "=f"(d[55]), "=f"(d[56]), "=f"(d[57]), "=f"(d[58]), "=f"(d[59]), "=f"(d[60]), "=f"(d[61]), "=f"(d[62]), "=f"(d[63])
    : "l"(da), "l"(db));
}
__device__ __forceinline__ void wgmma_n256(float (&d)[128], uint64_t da, uint64_t db) {
  asm volatile("wgmma.mma_async.sync.aligned.m64n256k16.f32.bf16.bf16 "
    "{%0, %1, %2, %3, %4, %5, %6, %7, %8, %9, %10, %11, %12, %13, %14, %15, %16, %17, %18, %19, %20, %21, %22, %23, %24, %25, %26, %27, %28, %29, %30, %31, %32, %33, %34, %35, %36, %37, %38, %39, %40, %41, %42, %43, %44, %45, %46, %47, %48, %49, %50, %51, %52, %53, %54, %55, %56, %57, %58, %59, %60, %61, %62, %63, %64, %65, %66, %67, %68, %69, %70, %71, %72, %73, %74, %75, %76, %77, %78, %79, %80, %81, %82, %83, %84, %85, %86, %87, %88, %89, %90, %91, %92, %93, %94, %95, %96, %97, %98, %99, %100, %101, %102, %103, %104, %105, %106, %107, %108, %109, %110, %111, %112, %113, %114, %115, %116, %117, %118, %119, %120, %121, %122, %123, %124, %125, %126, %127}, "
    "%128, %129, 1, 1, 1, 0, 1;\n"
    : "+f"(d[0]), "+f"(d[1]), "+f"(d[2]), "+f"(d[3]), "+f"(d[4]), "+f"(d[5]), "+f"(d[6]), "+f"(d[7]), "+f"(d[8]), "+f"(d[9]), "+f"(d[10]), "+f"(d[11]), "+f"(d[12]), "+f"(d[13]), "+f"(d[14]), "+f"(d[15]), "+f"(d[16]), "+f"(d[17]), "+f"(d[18]), "+f"(d[19]), "+f"(d[20]), "+f"(d[21]), "+f"(d[22]), "+f"(d[23]), "+f"(d[24]), "+f"(d[25]), "+f"(d[26]), "+f"(d[27]), "+f"(d[28]), "+f"(d[29]), "+f"(d[30]), "+f"(d[31]), "+f"(d[32]), "+f"(d[33]), "+f"(d[34]), "+f"(d[35]), "+f"(d[36]), "+f"(d[37]), "+f"(d[38]), "+f"(d[39]), "+f"(d[40]), "+f"(d[41]), "+f"(d[42]), "+f"(d[43]), "+f"(d[44]), "+f"(d[45]), "+f"(d[46]), "+f"(d[47]), "+f"(d[48]), "+f"(d[49]), "+f"(d[50]), "+f"(d[51]), "+f"(d[52]), "+f"(d[53]), "+f"(d[54]), "+f"(d[55]), "+f"(d[56]), "+f"(d[57]), "+f"(d[58]), "+f"(d[59]), "+f"(d[60]), "+f"(d[61]), "+f"(d[62]), "+f"(d[63]), "+f"(d[64]), "+f"(d[65]), "+f"(d[66]), "+f"(d[67]), "+f"(d[68]), "+f"(d[69]), "+f"(d[70]), "+f"(d[71]), "+f"(d[72]), "+f"(d[73]), "+f"(d[74]), "+f"(d[75]), "+f"(d[76]), "+f"(d[77]), "+f"(d[78]), "+f"(d[79]), "+f"(d[80]), "+f"(d[81]), "+f"(d[82]), "+f"(d[83]), "+f"(d[84]), "+f"(d[85]), "+f"(d[86]), "+f"(d[87]), "+f"(d[88]), "+f"(d[89]), "+f"(d[90]), "+f"(d[91]), "+f"(d[92]), "+f"(d[93]), "+f"(d[94]), "+f"(d[95]), "+f"(d[96]), "+f"(d[97]), "+f"(d[98]), "+f"(d[99]), "+f"(d[100]), "+f"(d[101]), "+f"(d[102]), "+f"(d[103]), "+f"(d[104]), "+f"(d[105]), "+f"(d[106]), "+f"(d[107]), "+f"(d[108]), "+f"(d[109]), "+f"(d[110]), "+f"(d[111]), "+f"(d[112]), "+f"(d[113]), "+f"(d[114]), "+f"(d[115]), "+f"(d[116]), "+f"(d[117]), "+f"(d[118]), "+f"(d[119]), "+f"(d[120]), "+f"(d[121]), "+f"(d[122]), "+f"(d[123]), "+f"(d[124]), "+f"(d[125]), "+f"(d[126]), "+f"(d[127])
    : "l"(da), "l"(db));
}
__device__ __forceinline__ void wgmma_n256_first(float (&d)[128], uint64_t da, uint64_t db) {
  asm volatile("wgmma.mma_async.sync.aligned.m64n256k16.f32.bf16.bf16 "
    "{%0, %1, %2, %3, %4, %5, %6, %7, %8, %9, %10, %11, %12, %13, %14, %15, %16, %17, %18, %19, %20, %21, %22, %23, %24, %25, %26, %27, %28, %29, %30, %31, %32, %33, %34, %35, %36, %37, %38, %39, %40, %41, %42, %43, %44, %45, %46, %47, %48, %49, %50, %51, %52, %53, %54, %55, %56, %57, %58, %59, %60, %61, %62, %63, %64, %65, %66, %67, %68, %69, %70, %71, %72, %73, %74, %75, %76, %77, %78, %79, %80, %81, %82, %83, %84, %85, %86, %87, %88, %89, %90, %91, %92, %93, %94, %95, %96, %97, %98, %99, %100, %101, %102, %103, %104, %105, %106, %107, %108, %109, %110, %111, %112, %113, %114, %115, %116, %117, %118, %119, %120, %121, %122, %123, %124, %125, %126, %127}, "
    "%128, %129, 0, 1, 1, 0, 1;\n"
    : "=f"(d[0]), "=f"(d[1]), "=f"(d[2]), "=f"(d[3]), "=f"(d[4]), "=f"(d[5]), "=f"(d[6]), "=f"(d[7]), "=f"(d[8]), "=f"(d[9]), "=f"(d[10]), "=f"(d[11]), "=f"(d[12]), "=f"(d[13]), "=f"(d[14]), "=f"(d[15]), "=f"(d[16]), "=f"(d[17]), "=f"(d[18]), "=f"(d[19]), "=f"(d[20]), "=f"(d[21]), "=f"(d[22]), "=f"(d[23]), "=f"(d[24]), "=f"(d[25]), "=f"(d[26]), "=f"(d[27]), "=f"(d[28]), "=f"(d[29]), "=f"(d[30]), "=f"(d[31]), "=f"(d[32]), "=f"(d[33]), "=f"(d[34]), "=f"(d[35]), "=f"(d[36]), "=f"(d[37]), "=f"(d[38]), "=f"(d[39]), "=f"(d[40]), "=f"(d[41]), "=f"(d[42]), "=f"(d[43]), "=f"(d[44]), "=f"(d[45]), "=f"(d[46]), "=f"(d[47]), "=f"(d[48]), "=f"(d[49]), "=f"(d[50]), "=f"(d[51]), "=f"(d[52]), "=f"(d[53]), "=f"(d[54]), "=f"(d[55]), "=f"(d[56]), "=f"(d[57]), "=f"(d[58]), "=f"(d[59]), "=f"(d[60]), "=f"(d[61]), "=f"(d[62]), "=f"(d[63]), "=f"(d[64]), "=f"(d[65]), "=f"(d[66]), "=f"(d[67]), "=f"(d[68]), "=f"(d[69]), "=f"(d[70]), "=f"(d[71]), "=f"(d[72]), "=f"(d[73]), "=f"(d[74]), "=f"(d[75]), "=f"(d[76]), "=f"(d[77]), "=f"(d[78]), "=f"(d[79]), "=f"(d[80]), "=f"(d[81]), "=f"(d[82]), "=f"(d[83]), "=f"(d[84]), "=f"(d[85]), "=f"(d[86]), "=f"(d[87]), "=f"(d[88]), "=f"(d[89]), "=f"(d[90]), "=f"(d[91]), "=f"(d[92]), "=f"(d[93]), "=f"(d[94]), "=f"(d[95]), "=f"(d[96]), "=f"(d[97]), "=f"(d[98]), "=f"(d[99]), "=f"(d[100]), "=f"(d[101]), "=f"(d[102]), "=f"(d[103]), "=f"(d[104]), "=f"(d[105]), "=f"(d[106]), "=f"(d[107]), "=f"(d[108]), "=f"(d[109]), "=f"(d[110]), "=f"(d[111]), "=f"(d[112]), "=f"(d[113]), "=f"(d[114]), "=f"(d[115]), "=f"(d[116]), "=f"(d[117]), "=f"(d[118]), "=f"(d[119]), "=f"(d[120]), "=f"(d[121]), "=f"(d[122]), "=f"(d[123]), "=f"(d[124]), "=f"(d[125]), "=f"(d[126]), "=f"(d[127])
    : "l"(da), "l"(db));
}

template <int N> struct WG;
#define DEF_WG(N) template <> struct WG<N> { \
  static __device__ __forceinline__ void mma(float (&d)[N / 2], uint64_t a, uint64_t b) { wgmma_n##N(d, a, b); } \
  static __device__ __forceinline__ void first(float (&d)[N / 2], uint64_t a, uint64_t b) { wgmma_n##N##_first(d, a, b); } };
DEF_WG(128) DEF_WG(256)

constexpr uint64_t DESC_A = (1ull << 62) | ((uint64_t)(1024 >> 4) << 32) | (1ull << 16);
constexpr uint64_t DESC_B = (1ull << 62) | ((uint64_t)(1024 >> 4) << 32) | ((uint64_t)(8192 >> 4) << 16);

struct Ring { int s; uint32_t ph; int wrap; };
template <int NS> __device__ __forceinline__ void ring_next(Ring& r) { r.s = (r.s + 1 == NS) ? 0 : r.s + 1; if (r.s == r.wrap) r.ph ^= 1; }

__device__ __forceinline__ int own_order(int it, int j) {
  return it < 2 ? 2 * j + it : it < 4 ? 2 * (j ^ 1) + it - 2 : ((j >> 1) * 4 + 2 * it - (it < 10 ? 4 : 15)) & 15;
}

template <int V> struct IC { static constexpr int v = V; };
template <int I, int E, class F> __device__ __forceinline__ void static_for(F&& f) { if constexpr (I < E) { f(IC<I>{}); static_for<I + 1, E>(f); } }

template <int N, int NS, int PRE, int LAG, class Pre, class Mid, class Last>
__device__ __forceinline__ void mainloop(float (&acc)[N / 2], int nkb, bool own, Ring& r, uint32_t sb, int wg, int lane, uint32_t rel_base, Pre pre, Mid mid, Last last, int lag_par = 0) {
  constexpr int SLOT = RING / NS;
  const uint32_t full = sb + MISC + (NS == 4 ? B_FULL4 : B_FULL6);
  const uint32_t rel = rel_base + (NS == 4 ? B_EMPTY4 : B_EMPTY6);
  const uint32_t s0 = (sb & 0x3FFFF) >> 4, a0 = s0 + wg * (HALF >> 4);
  int ps;
  auto issue = [&](int it, bool first) {
    const uint64_t da = DESC_A | (a0 + ((own && it < 2) ? (STG + it * BLK) >> 4 : r.s * (SLOT >> 4))), db = DESC_B | (s0 + r.s * (SLOT >> 4) + (BLK >> 4));
    mbar_wait(full + r.s * 8, r.ph);
    wg_arrive();
    if (first) WG<N>::first(acc, da, db); else WG<N>::mma(acc, da, db);
#pragma unroll
    for (int k = 1; k < 4; k++) WG<N>::mma(acc, da + k * 2, db + k * 128);
    wg_commit();
  };
  auto retire = [&](int it) {
    wg_wait<1>();
    if (lane < 2) mbar_arrive_cl(rel + ps * 8);
    ps = r.s;
    ring_next<NS>(r);
  };
  issue(0, true);
  ps = r.s;
  ring_next<NS>(r);
  static_for<1, PRE + 1>([&](auto ic) { issue(ic.v, false); pre(ic); retire(ic.v); });
#pragma unroll 1
  for (int it = PRE + 1; it < nkb; it++) {
    if (LAG && it == nkb - LAG && wg == 1) mbar_wait(sb + MISC + B_LAG, lag_par);
    issue(it, false); mid(it); retire(it);
  }
  if (LAG && wg == 0 && lane == 0) mbar_arrive(sb + MISC + B_LAG);
  last();
  wg_wait<0>();
  if (lane < 2) mbar_arrive_cl(rel + ps * 8);
}

__device__ __forceinline__ uint32_t tag_of(uint32_t ep) { return (ep & 127u) + 1u; }
__device__ __forceinline__ void ln_publish(const float (&v)[64], uint2* st, int j, int row0, int lane, uint32_t ep) {
  float s0 = 0, s1 = 0, s2 = 0, s3 = 0, q0 = 0, q1 = 0, q2 = 0, q3 = 0;
#pragma unroll
  for (int i = 0; i < 16; i++) {
    s0 += v[4 * i]; s1 += v[4 * i + 1]; s2 += v[4 * i + 2]; s3 += v[4 * i + 3];
    q0 = fmaf(v[4 * i], v[4 * i], q0); q1 = fmaf(v[4 * i + 1], v[4 * i + 1], q1); q2 = fmaf(v[4 * i + 2], v[4 * i + 2], q2); q3 = fmaf(v[4 * i + 3], v[4 * i + 3], q3);
  }
  s0 += s1; s2 += s3; q0 += q1; q2 += q3;
  const bool odd = lane & 1;
  float s = (odd ? s2 : s0) + __shfl_xor_sync(~0u, odd ? s0 : s2, 1), q = (odd ? q2 : q0) + __shfl_xor_sync(~0u, odd ? q0 : q2, 1);
  s += __shfl_xor_sync(~0u, s, 2); q += __shfl_xor_sync(~0u, q, 2);
  if ((lane & 3) < 2) st_rlx2(st + j * 128 + row0 + (lane & 1) * 8, __float_as_uint(s), (__float_as_uint(fmaf(s * (-1.f / 128), s, q)) & ~255u) | tag_of(ep));
}
__device__ __forceinline__ void ln_gather(const uint2* st, int row0, int lane, uint32_t ep, float& n0, float& r0, float& n1, float& r1, bool rnd) {
  const uint2* p = st + (lane & 2) * 256 + row0 + (lane & 1) * 8;
  const uint32_t tag = tag_of(ep);
  uint2 a, b, c, d; uint32_t n = 0;
  while (true) {
    a = ld_rlx2(p); b = ld_rlx2(p + 128); c = ld_rlx2(p + 256); d = ld_rlx2(p + 384);
    if ((((a.y ^ tag) | (b.y ^ tag) | (c.y ^ tag) | (d.y ^ tag)) & 255u) == 0) break;
    SPIN_GUARD(n);
  }
  __syncwarp();
  const uint32_t fix = tag ^ 128u;
  float s = (__uint_as_float(a.x) + __uint_as_float(b.x)) + (__uint_as_float(c.x) + __uint_as_float(d.x));
  float q = (__uint_as_float(a.y ^ fix) + __uint_as_float(b.y ^ fix)) + (__uint_as_float(c.y ^ fix) + __uint_as_float(d.y ^ fix));
  q = fmaf(fmaf(__uint_as_float(a.x), __uint_as_float(a.x), __uint_as_float(b.x) * __uint_as_float(b.x)) +
           fmaf(__uint_as_float(c.x), __uint_as_float(c.x), __uint_as_float(d.x) * __uint_as_float(d.x)), 1.f / 128, q);
  s += __shfl_xor_sync(~0u, s, 2); q += __shfl_xor_sync(~0u, q, 2);
  s *= 1.f / 1024;
  const float var = fmaxf(fmaf(-s, s, q * (1.f / 1024)), 0.f);
  float r;
  if (rnd) {
    float sd; asm("sqrt.approx.f32 %0, %1;" : "=f"(sd) : "f"(bf_round(bf_round(var) + 1e-5f)));
    r = rcp(bf_round(sd)); s = bf_round(s);
  } else r = rsqrtf(var + 1e-5f);
  const float nn = -s * r;
  const float ro = __shfl_xor_sync(~0u, r, 1), no = __shfl_xor_sync(~0u, nn, 1);
  const bool odd = lane & 1;
  r0 = odd ? ro : r; n0 = odd ? no : nn; r1 = odd ? r : ro; n1 = odd ? nn : no;
}
__device__ __forceinline__ void load_vec(uint32_t* w, uint32_t sb, int sec, int b, int lane) {
#pragma unroll
  for (int q = 0; q < 2; q++) { uint4 t = lds128(sb + MISC + MODV + sec * 256 + (lane & 3) * 64 + b * 32 + q * 16); w[4 * q] = t.x; w[4 * q + 1] = t.y; w[4 * q + 2] = t.z; w[4 * q + 3] = t.w; }
}
__device__ __forceinline__ void stage_done(uint32_t sb, int wg, int b, int lane) {
  fence_async_smem();
  __syncwarp();
  if (lane == 0) mbar_arrive(sb + MISC + B_RDY + b * 8);
}
__device__ __forceinline__ uint32_t hfma2(uint32_t a, uint32_t b, uint32_t c) { uint32_t r; asm("fma.rn.bf16x2 %0, %1, %2, %3;" : "=r"(r) : "r"(a), "r"(b), "r"(c)); return r; }
__device__ __forceinline__ void ln_apply(const float (&v)[64], const uint2* st, int row0, uint32_t ep, uint32_t sb, int sec_shift, int sec_scale, uint32_t stg_row, int wg, int lane) {
  uint32_t sc[16], sh[16];
#pragma unroll
  for (int b = 0; b < 2; b++) { load_vec(sc + 8 * b, sb, sec_scale, b, lane); load_vec(sh + 8 * b, sb, sec_shift, b, lane); }
  float n0, r0, n1, r1;
  ln_gather(st, row0, lane, ep, n0, r0, n1, r1, sec_shift == 0);
#pragma unroll
  for (int i = 0; i < 16; i += 2) {
    if (i == 8) { const float z = lds32f(sb + MISC + ZERO); n0 += z; n1 += z; }
    uint32_t w[4];
#pragma unroll
    for (int u = 0; u < 2; u++) {
      int q = i + u;
      w[2 * u] = hfma2(pack2(fmaf(v[4 * q], r0, n0), fmaf(v[4 * q + 1], r0, n0)), sc[q], sh[q]);
      w[2 * u + 1] = hfma2(pack2(fmaf(v[4 * q + 2], r1, n1), fmaf(v[4 * q + 3], r1, n1)), sc[q], sh[q]);
    }
    stsm4(stg_row + (i >> 3) * BLK + ((((i & 7) + (lane >> 4)) ^ (lane & 7)) << 4), w[0], w[1], w[2], w[3]);
    if ((i & 7) == 6) { stage_done(sb, wg, i >> 3, lane); }
  }
}
__device__ __forceinline__ uint32_t hmul2(uint32_t a, uint32_t b) { uint32_t r; asm("mul.rn.bf16x2 %0, %1, %2;" : "=r"(r) : "r"(a), "r"(b)); return r; }
__device__ __forceinline__ uint32_t silu_mul2(uint32_t g, uint32_t u) {
  const uint32_t h = hmul2(g, 0x3f003f00u);
  const float h0 = bf_lo(h), h1 = bf_hi(h);
  return hmul2(pack2(fmaf(h0, tanh_fast(h0), h0), fmaf(h1, tanh_fast(h1), h1)), u);
}

__device__ __forceinline__ void gemv_fma(float (&a)[8], uint4 w, float s) {
  a[0] = fmaf(bf_lo(w.x), s, a[0]); a[1] = fmaf(bf_hi(w.x), s, a[1]); a[2] = fmaf(bf_lo(w.y), s, a[2]); a[3] = fmaf(bf_hi(w.y), s, a[3]);
  a[4] = fmaf(bf_lo(w.z), s, a[4]); a[5] = fmaf(bf_hi(w.z), s, a[5]); a[6] = fmaf(bf_lo(w.w), s, a[6]); a[7] = fmaf(bf_hi(w.w), s, a[7]);
}
__device__ __forceinline__ float silu_c(float v) { return bf_round(__fdividef(v, 1.f + __expf(-v))); }
__device__ __forceinline__ float mod_gather(const uint32_t* p, uint32_t ep) {
  const uint32_t tag = tag_of(ep), fix = tag ^ 128u;
  uint32_t a, b, c, d, n = 0;
  while (true) {
    a = ld_rlx1(p); b = ld_rlx1(p + 128); c = ld_rlx1(p + 256); d = ld_rlx1(p + 384);
    if ((((a ^ tag) | (b ^ tag) | (c ^ tag) | (d ^ tag)) & 255u) == 0) break;
    SPIN_GUARD(n);
  }
  return (__uint_as_float(a ^ fix) + __uint_as_float(b ^ fix)) + (__uint_as_float(c ^ fix) + __uint_as_float(d ^ fix));
}
__device__ __forceinline__ void mod_store(uint32_t sb, int sec, int col, float v) {
  v = bf_round(v);
  if (sec == 1) v += 1.f;
  sts16(sb + MISC + MODV + sec * 256 + (((col >> 1) & 3) * 16 + (col >> 3)) * 4 + (col & 1) * 2, __float2bfloat16_rn(v));
}

__global__ void __cluster_dims__(2, 1, 1) __launch_bounds__(384, 1)
fused_kernel(const bf16* __restrict__ cvec, const bf16* __restrict__ wmod, Scratch* gs, int by_sm, const __grid_constant__ Maps maps) {
  extern __shared__ __align__(1024) uint8_t smem_raw[];
  const uint32_t sb = smem_u32(smem_raw);
  const int warp = __shfl_sync(~0u, threadIdx.x >> 5, 0), lane = threadIdx.x & 31;
  const int rank = blockIdx.x & 1;
  uint32_t sm; asm volatile("mov.u32 %0, %%smid;" : "=r"(sm));
  const int t = sm >> 1, v = t < 32 ? t : t < 60 ? t + 1 + (((t - 32) * 37) >> 8) : (t - 58) * 8;
  const int gr = 0x71546320u >> ((v & 7) * 4);
  const int cid = !by_sm ? (blockIdx.x >> 1) - 2 : (t & ~1) == 60 ? t - 62 : (gr & 4) * 8 + (v >> 3) * 4 + (gr & 3);
  const bool extra = cid < 0;
  const int bid = cid * 2 + rank;
  const int m = cid >> 2, j = (cid & 3) * 2 + rank;
  const uint32_t bar = sb + MISC;

  if (warp >= 8) {
    asm volatile("setmaxnreg.dec.sync.aligned.u32 40;");
    if (extra) {
      if (warp == 8) {
        if (lane == 0) { for (int s = 0; s < 6; s++) { mbar_init(bar + B_FULL6 + s * 8, 1); mbar_init(bar + B_EMPTY6 + s * 8, 8); } fence_async_smem(); }
        __syncwarp();
        asm volatile("bar.arrive 2, 288;" ::: "memory");
        __nanosleep(XSLEEP);
#pragma unroll 1
        for (int it = 0, s = 0, par = 1; it < 64; it++) {
          mbar_wait(bar + B_EMPTY6 + s * 8, par);
          expect_e(bar + B_FULL6 + s * 8, 32768); tma_3d_e(sb + s * 32768, &maps.wmod, bar + B_FULL6 + s * 8, 0, (it & 15) * 64, 12 + (it >> 4) * 4 + bid);
          if (++s == 6) { s = 0; par ^= 1; }
        }
      }
    } else if (warp < 10) {
      uint32_t f6 = bar + B_FULL6, d6 = sb + (warp == 8 ? BLK : rank * HALF), p6 = 1;
      auto next6 = [&]() { f6 += 8; d6 += 32768; if (f6 == bar + B_FULL6 + 48) { f6 -= 48; d6 -= RING; p6 ^= 1; } };
      auto drained4 = [&](int q, int late) { if (q < 5) mbar_wait(bar + B_EMPTY4 + (((late ? 0x10332 : 0x32110) >> (4 * q)) & 3) * 8, 1); };
      auto drained6 = [&](int q) { if (q < 3) mbar_wait(bar + B_EMPTY6 + ((0x154 >> (4 * q)) & 7) * 8, q >> 1); };
      auto skip6 = [&]() { mbar_wait(f6 + 48, p6); expect_e(f6, 0); next6(); };
      if (warp == 8) {
        const uint32_t t_start = clock();
        if (lane == 0) {
          if (sb & 1023) bail();
          for (int b = 0; b < 2; b++) mbar_init(bar + B_X + b * 8, 1);
          for (int s = 0; s < 4; s++) { mbar_init(bar + B_FULL4 + s * 8, 2); mbar_init(bar + B_EMPTY4 + s * 8, 16); }
          for (int s = 0; s < 6; s++) { mbar_init(bar + B_FULL6 + s * 8, 2); mbar_init(bar + B_EMPTY6 + s * 8, 16); }
          for (int b = 0; b < 2; b++) { mbar_init(bar + B_RDY + b * 8, 8); mbar_init(bar + B_FREE + b * 8, 1); mbar_init(bar + B_HH + b * 8, 1); }
          mbar_init(bar + B_MOD, 1); mbar_init(bar + B_LAG, 4); mbar_init(bar + B_HALO, 2); mbar_init(bar + B_ALL, 1); mbar_init(bar + B_HH2, 1);
          asm volatile("st.shared.u32 [%0], 0;" :: "r"(bar + ZERO) : "memory");
          asm volatile("fence.mbarrier_init.release.cluster;" ::: "memory");
          fence_async_smem();
        }
        __syncwarp();
        cl_arrive_relaxed();
        while ((uint32_t)clock() - t_start < XDELAY) {}
        for (int b = 0; b < 2; b++) { expect_e(bar + B_X + b * 8, BLK); tma_3d_e(sb + STG + b * BLK, &maps.x, bar + B_X + b * 8, j * 128 + b * 64, m * 64, 0); }
        mbar_wait(bar + B_X + 8, 0);
#pragma unroll 1
        for (int ph = 0; ph < 2; ph++) {
          const CUtensorMap* const m0 = ph ? &maps.w1 : &maps.wqkv;
#pragma unroll 1
          for (int it = 0; it < (ph ? 48 : 16); it++) {
            const int s = (it + 2 * ph) & 3;
            int a0 = (ph ? it & 48 : 16) + 2 * j, a1 = ph ? a0 : a0 + 16, k0 = (it < 16 ? own_order(it, j) : it & 15) * 64;
            uint32_t full = bar + B_FULL4 + s * 8, d = sb + s * 49152 + BLK;
            if (ph) drained6(it);
            mbar_wait(full + 32, ~(it >> 2) & 1);
            tma_3d_e(d, m0, full, 0, k0, a0);
            if (it < 4) { const uint32_t t0 = clock(); while ((uint32_t)clock() - t0 < GAP) {} }
            tma_3d_e(d + BLK, m0 + ph, full, 0, k0, a1);
            expect_e(full, 2 * BLK);
            if (it < 4) { const uint32_t t0 = clock(); while ((uint32_t)clock() - t0 < GAP) {} }
            if (it >= 44) {
              if (it == 44) { mbar_wait(bar + B_FREE, 0); mbar_wait(bar + B_FREE + 8, 0); expect_e(bar + B_X, 2 * BLK); }
              bulk_ld_e(sb + STG + (it - 44) * HALF, gs->x1 + bid * 2048 + (it - 44) * 512, HALF, bar + B_X);
            }
          }
          const CUtensorMap* const m1 = ph ? &maps.w1s : &maps.wqkv;
          const int a = ph ? 48 + j : 2 * j;
#pragma unroll 1
          for (int k0 = 0; k0 < 1024; k0 += 64) {
            drained4(k0 >> 6, ph);
            mbar_wait(f6 + 48, p6);
            tma_3d_e(d6, m1, f6, 0, k0, a);
            if (ph) tma_3d_e(d6 + HALF, &maps.w3s, f6, 0, k0, a);
            expect_e(f6, BLK);
            next6();
          }
          if (ph) break;
#pragma unroll 1
          for (int it = 0; it < 16; it++) {
            const int k0 = own_order(it, j) * 64;
            mbar_wait(f6 + 48, p6);
            tma_3d_e(d6, &maps.wo, f6, 0, k0, 2 * j);
            expect_e(f6, BLK);
            next6();
          }
          skip6();
        }
#pragma unroll 1
        for (int k0 = 0; k0 < F_; k0 += 64) {
          mbar_wait(f6 + 48, p6);
          tma_3d_e(d6, &maps.w2, f6, 0, k0, 2 * j);
          expect_e(f6, BLK);
          next6();
        }
      } else {
        if (lane < 9) prefetch_map(&maps.x + lane);
        const uint32_t ep = gs->epoch[blockIdx.x] + 1;
        cl_arrive_relaxed(); cl_wait();
        auto run6 = [&](const uint4* src, int n, int sw) {
          src += rank * 512;
#pragma unroll 1
          for (int it = 0; it < n; it++) {
            if (sw >= 0) drained4(it, sw);
            mbar_wait(f6 + 48, p6);
            bulk_ld_mc_e(d6, src, HALF, f6);
            expect_e(f6, BLK);
            next6();
            src += 1024;
          }
        };
        uint32_t ready = 0;
        auto need = [&](int e, uint32_t mask) {
          if (!(ready & mask)) {
            uint32_t n = 0;
            do { ready = __ballot_sync(~0u, ld_acquire(gs->flag + (m * 128 + e * 16 + (lane & 14)) * FS) == ep); SPIN_GUARD(n); } while (!(ready & mask));
            fence_async_global();
          }
        };
        auto fresh = [&](int e, int it, uint32_t full, uint32_t empty, int par, uint32_t slot, uint4* src) {
          mbar_wait(empty, par);
          expect_e(full, it < 2 ? 0 : BLK);
          if (it >= 4) {
            const int kb = own_order(it, j);
            if (it < 10) need(e, 1u << kb); else if (it == 10) mbar_wait(bar + B_ALL, e & 1);
            bulk_ld_mc_e(slot + rank * HALF, src + kb * 1024 + rank * 512, HALF, full);
          } else if (it >= 2) {
            const int b = it > 2;
            const uint32_t to_peer = mapa(sb, rank ^ 1) - sb;
            const bool push = b && e != 1;
            mbar_wait(bar + (push ? B_RDY : B_FREE) + b * 8, e & 1);
            if (push) bulk_push_e(slot + to_peer, sb + STG + BLK, BLK, full + to_peer);
            else { fence_async_global(); bulk_ld_e(slot + to_peer, src + (2 * j + b) * 1024, BLK, full + to_peer); }
          } else ready = 0;
        };
        uint4* const h = gs->h + m * 16384;
#pragma unroll 1
        for (int e = 0; e < 3; e++) {
#pragma unroll 1
          for (int it = 0; it < 16; it++) {
            const int s = (it + e) & 3;
            const uint32_t full = e == 1 ? f6 : bar + B_FULL4 + s * 8;
            if (e == 2) drained6(it);
            fresh(e, it, full, full + (e == 1 ? 48 : 32), e == 1 ? p6 : ~(it >> 2) & 1, e == 1 ? d6 - rank * HALF : sb + s * 49152, e == 1 ? gs->o + m * 16384 : h);
            if (e == 1) next6();
          }
          if (e == 1) { skip6(); continue; }
#pragma unroll 1
          for (int it = 16; it < 16 + 16 * e; it++) {
            const int s = (it + 2) & 3;
            const uint32_t full = bar + B_FULL4 + s * 8;
            mbar_wait(full + 32, ~(it >> 2) & 1);
            bulk_ld_mc_e(sb + s * 49152 + rank * HALF, h + (it & 15) * 1024 + rank * 512, HALF, full);
            expect_e(full, BLK);
          }
          run6(h, 16, e);
        }
#pragma unroll 1
        for (int q = 0; q < 3; q++) {
          mbar_wait(bar + (q == 2 ? B_HH2 : B_HH + q * 8), 0);
          run6(gs->hh + m * 57344 + (64 - (64 >> q)) * 1024, 32 >> q, -1);
        }
      }
    } else {
      const int b = warp - 10;
      const uint32_t ep = gs->epoch[blockIdx.x] + 1;
      const uint32_t stg = sb + STG + b * BLK;
      cl_arrive_relaxed(); cl_wait();
      auto all_there = [&](int u, uint32_t done) {
        const uint32_t* fl = gs->flag + u * FS;
        uint32_t n = 0;
        while (!__all_sync(~0u, ld_acquire(fl) == ep)) { __nanosleep(100); SPIN_GUARD(n); }
        fence_async_global();
        arrive_e(done);
      };
#pragma unroll 1
      for (int e = 0; e < 7 - b; e++) {
        const int kb = (e < 3 ? 2 * j : e < 6 ? 2 * (8 * (e - 3) + j) : 48 + j) + b;
        uint4* const dst = (e == 1 ? gs->o + m * 16384 : e < 3 ? gs->h + m * 16384 : gs->hh + m * 57344) + kb * 1024;
        uint32_t* const fl = gs->flag + (m * 128 + (e < 3 ? e * 16 : U_HH) + kb) * FS;
        if (b && e < 3) {
          mbar_wait(bar + B_FREE, e & 1);
          const uint32_t t0 = clock();
          while ((uint32_t)clock() - t0 < (e == 1 ? B1D : B1P)) {}
        }
        mbar_wait(bar + B_RDY + b * 8, e & 1);
        bulk_st_e(dst, stg, e < 3 ? BLK : BLK / NPIECE);
        if (e >= 3) {
#pragma unroll 1
          for (int q = 1; q < NPIECE; q++) { __nanosleep(PSLEEP); bulk_st_e(dst + q * (1024 / NPIECE), stg + q * (BLK / NPIECE), BLK / NPIECE); }
        }
        publish_e(bar + B_FREE + b * 8, fl, ep);
        if (b && (e < 3 || e == 4)) all_there(m * 128 + (e < 3 ? e * 16 + (lane & 15) : U_HH + lane), bar + (e < 3 ? B_ALL : B_HH));
        if (!b && (e == 1 || e == 2)) {
#pragma unroll 1
          for (int sec = e == 1 ? 2 : 5; sec < 4 + e; sec++) {
            const uint4* p = (const uint4*)(gs->modv + (sec - 2) * 1024 + j * 128) + lane;
            uint4 v0, v1; uint32_t n = 0;
            while (true) {
              v0 = ld_rlx4(p); v1 = ld_rlx4(p + 32);
              if (__all_sync(~0u, v0.y == ep && v0.w == ep && v1.y == ep && v1.w == ep)) break;
              SPIN_GUARD(n);
            }
            const uint32_t d = sb + MISC + MODV + sec * 256 + ((lane & 3) * 16 + (lane >> 2)) * 4;
            asm volatile("st.shared.u32 [%0], %1;" :: "r"(d), "r"(__byte_perm(v0.x, v0.z, 0x7632)) : "memory");
            asm volatile("st.shared.u32 [%0], %1;" :: "r"(d + 32), "r"(__byte_perm(v1.x, v1.z, 0x7632)) : "memory");
          }
          __syncwarp();
          if (e == 1) { arrive_e(bar + B_MOD); }
        }
        if (e == 0) {
          mbar_wait(bar + B_EMPTY6 + 24, 0);
          __nanosleep(HSLEEP);
#pragma unroll 1
          for (int w = 0; w < 4; w++) {
            const uint4* hp = gs->halo + ((m * 8 + j) * 2 + (w & 1)) * 512 + b * 256 + (w >> 1) * 128 + lane;
            uint4 q[4] = {}; uint32_t n = 0;
            while (m > 0) {
              bool ok = true;
#pragma unroll
              for (int i = 0; i < 4; i++) q[i] = ld_rlx4(hp + i * 32);
#pragma unroll
              for (int i = 0; i < 4; i++) ok = ok && q[i].y == ep && q[i].w == ep;
              if (__all_sync(~0u, ok)) break;
              SPIN_GUARD(n);
            }
#pragma unroll
            for (int i = 0; i < 2; i++) sts128(stg + lane * 16 + (w & 1) * HALF + (w >> 1) * 1024 + i * 512, q[2 * i].x, q[2 * i + 1].x, q[2 * i].z, q[2 * i + 1].z);
          }
          __syncwarp();
          arrive_e(bar + B_HALO);
        }
      }
      if (b) {
#pragma unroll 1
        for (int q = 0; q < 2; q++) all_there(m * 128 + U_HH + 32 + q * 16 + (lane & (15 >> q)), bar + (q ? B_HH2 : B_HH + 8));
      }
    }
  } else {
    const int wg = warp >> 2, wq = warp & 3, tid = threadIdx.x;
    const int g = lane >> 2, c = lane & 3;
    const int sec0 = (m >> 1) & 1, hf0 = m & 1, ks0 = (m >> 2) & 3;
    uint4 wv[8];
    uint32_t ep0; uint16_t cv_;
    asm volatile("ld.global.nc.u16 %0, [%1];" : "=h"(cv_) : "l"(cvec + ks0 * 256 + warp * 32 + lane));
    asm volatile("ld.global.u32 %0, [%1];" : "=r"(ep0) : "l"(gs->epoch + (blockIdx.x | (lane & by_sm & 2))));
    if (!extra) {
      const bf16* wp = wmod + (size_t)(ks0 * 256 + warp * 32 + (lane >> 3)) * 6144 + sec0 * 1024 + j * 128 + hf0 * 64 + (lane & 7) * 8;
#pragma unroll
      for (int i = 0; i < 8; i++) wv[i] = ldg_nc(wp + (size_t)i * 4 * 6144);
      cl_arrive_relaxed();
    }
    asm volatile("setmaxnreg.inc.sync.aligned.u32 232;" ::: "memory");
    if (__builtin_expect(extra, 0)) {
      const uint32_t ep = ep0 + 1;
      float sv[4];
#pragma unroll
      for (int p = 0; p < 4; p++) sv[p] = silu_c(__bfloat162float(cvec[64 * (4 * p + (lane >> 3)) + 8 * warp + (lane & 7)]));
      named_bar(2, 288);
      int s = 0, par = 0;
#pragma unroll 1
      for (int sec = 0; sec < 4; sec++) {
        float a[8] = {0, 0, 0, 0, 0, 0, 0, 0};
#pragma unroll 1
        for (int it = 0; it < 16; it++) {
          const float sc = it < 4 ? sv[0] : it < 8 ? sv[1] : it < 12 ? sv[2] : sv[3];
          mbar_wait(bar + B_FULL6 + s * 8, par);
          uint4 w[8];
#pragma unroll
          for (int i = 0; i < 8; i++) w[i] = lds128(sb + s * 32768 + (warp * 8 + i) * 512 + lane * 16);
#pragma unroll
          for (int i = 0; i < 8; i++) gemv_fma(a, w[i], __shfl_sync(~0u, sc, (it & 3) * 8 + i));
          if (lane == 0) mbar_arrive(bar + B_EMPTY6 + s * 8);
          if (++s == 6) { s = 0; par ^= 1; }
        }
        const uint32_t red = sb + STG + sec * 8192;
        sts128(red + warp * 1024 + lane * 32, __float_as_uint(a[0]), __float_as_uint(a[1]), __float_as_uint(a[2]), __float_as_uint(a[3]));
        sts128(red + warp * 1024 + lane * 32 + 16, __float_as_uint(a[4]), __float_as_uint(a[5]), __float_as_uint(a[6]), __float_as_uint(a[7]));
        named_bar(1, 256);
        float t = 0;
#pragma unroll
        for (int q = 0; q < 8; q++) t += lds32f(red + q * 1024 + tid * 4);
        t = bf_round(t);
        if (sec == 2) t = bf_round(t + 1.f);
        st_rlx2(gs->modv + sec * 1024 + (bid + 4) * 256 + tid, __float_as_uint(t), ep);
      }
      if (tid == 0) gs->epoch[blockIdx.x] = ep;
      return;
    }
    const int row0 = wg * 64 + wq * 16 + g;
    if (c < 2) st_rlx2(gs->stat + m * 1024 + j * 128 + row0 + c * 8, 0, 0);
    cl_wait();
    uint32_t ep;
    asm volatile("add.u32 %0, %1, 1;" : "=r"(ep) : "r"(ep0) : "memory");
    const float sc_ = silu_c(__uint_as_float((uint32_t)cv_ << 16));
    const uint32_t rel = mapa(bar, (lane & 1) ^ rank);
    const uint32_t stg_row = sb + STG + (wg * 64 + wq * 16 + (lane & 15)) * 128;
    const uint32_t fre = bar + B_FREE;
    Ring r4{0, 0, 0}, r6{0, 0, 0};
    auto none = [](auto) {};
    uint32_t xk[32];
    {
      float a[8] = {0, 0, 0, 0, 0, 0, 0, 0};
#pragma unroll
      for (int i = 0; i < 8; i++) gemv_fma(a, wv[i], __shfl_sync(~0u, sc_, i * 4 + (lane >> 3)));
#pragma unroll
      for (int i = 0; i < 8; i++) { a[i] += __shfl_xor_sync(~0u, a[i], 8); a[i] += __shfl_xor_sync(~0u, a[i], 16); }
      if (lane < 8) {
        sts128(sb + RED_OFF + warp * 256 + lane * 32, __float_as_uint(a[0]), __float_as_uint(a[1]), __float_as_uint(a[2]), __float_as_uint(a[3]));
        sts128(sb + RED_OFF + warp * 256 + lane * 32 + 16, __float_as_uint(a[4]), __float_as_uint(a[5]), __float_as_uint(a[6]), __float_as_uint(a[7]));
      }
      named_bar(1, 256);
      if (tid < 64) {
        float s = 0;
#pragma unroll
        for (int w = 0; w < 8; w++) s += lds32f(sb + RED_OFF + w * 256 + tid * 4);
        st_rlx1(gs->modp + ((j * 2 + sec0) * 4 + ks0) * 128 + hf0 * 64 + tid, (__float_as_uint(s) & ~255u) | tag_of(ep));
      }
      float v[64];
      mbar_wait(bar + B_X, 0); mbar_wait(bar + B_X + 8, 0);
#pragma unroll
      for (int i = 0; i < 16; i += 2) {
        uint32_t w0, w1, w2, w3;
        ldsm4(stg_row + (i >> 3) * BLK + ((((i & 7) + (lane >> 4)) ^ (lane & 7)) << 4), w0, w1, w2, w3);
        xk[2 * i] = w0; xk[2 * i + 1] = w1; xk[2 * i + 2] = w2; xk[2 * i + 3] = w3;
        v[4 * i] = bf_lo(w0); v[4 * i + 1] = bf_hi(w0); v[4 * i + 2] = bf_lo(w1); v[4 * i + 3] = bf_hi(w1);
        v[4 * i + 4] = bf_lo(w2); v[4 * i + 5] = bf_hi(w2); v[4 * i + 6] = bf_lo(w3); v[4 * i + 7] = bf_hi(w3);
      }
      ln_publish(v, gs->stat + m * 1024, j, row0, lane, ep);
      mod_store(sb, tid >> 7, tid & 127, mod_gather(gs->modp + (j * 2 + (tid >> 7)) * 512 + (tid & 127), ep));
      named_bar(1, 256);
      ln_apply(v, gs->stat + m * 1024, row0, ep, sb, 0, 1, stg_row, wg, lane);
      named_bar(1, 256);
    }
    {
      uint32_t kf[32], vf[32], pv[32];
      const bool first = wq == 0 && m == 0;
      const uint32_t xa = sb + STG + wg * HALF + wq * 2048 + lane * 16;
      {
        float acc[128];
        mainloop<256, 4, 0, 0>(acc, 16, true, r4, sb, wg, lane, rel, none, none, [&] {
          mbar_wait(fre + 8, 0);
          if (c < 2) st_rlx2(gs->stat + (16 + m) * 1024 + j * 128 + row0 + c * 8, 0, 0);
        });
#pragma unroll
        for (int i = 0; i < 32; i++) { kf[i] = pack2(acc[2 * i], acc[2 * i + 1]); vf[i] = pack2(acc[64 + 2 * i], acc[65 + 2 * i]); }
      }
      float acc[64];
      constexpr int QP = 2;
      mainloop<128, 6, 8 / QP, 0>(acc, 16, false, r6, sb, wg, lane, rel, [&](auto ic) {
        constexpr int q = (ic.v - 1) * QP;
#pragma unroll
        for (int i = 4 * q; i < 4 * (q + QP); i++) vf[i] = movm(vf[i]);
        if (wq == 3) {
          if (m < 15) {
            uint4* hp = gs->halo + (((m + 1) * 8 + j) * 2 + wg) * 512 + lane;
#pragma unroll
            for (int i = 2 * q; i < 2 * (q + QP); i++) st_rlx4(hp + i * 32, kf[2 * i + 1], ep, vf[2 * i + 1], ep);
          }
        } else {
#pragma unroll
          for (int i = q; i < q + QP; i++) sts128(xa + 2048 + (i >> 2) * BLK + (i & 3) * 512, kf[4 * i + 1], kf[4 * i + 3], vf[4 * i + 1], vf[4 * i + 3]);
        }
      }, none, [&] {
        named_bar(2 + wg, 128);
        if (wq == 0) mbar_wait(bar + B_HALO, 0);
#pragma unroll
        for (int i = 0; i < 8; i++) {
          uint4 q = lds128(xa + (i >> 2) * BLK + (i & 3) * 512);
          pv[4 * i] = q.x; pv[4 * i + 1] = q.y; pv[4 * i + 2] = q.z; pv[4 * i + 3] = q.w;
        }
        __syncwarp();
      });
      int gz = g;
#pragma unroll
      for (int b = 0; b < 2; b++) {
        const bool up0 = 2 * c > gz, up1 = 2 * c + 1 > gz;
        const uint32_t mup = (up0 ? 0xffffu : 0u) | (up1 ? 0xffff0000u : 0u);
        float l[2][4], mx[4];
#pragma unroll
        for (int h = 0; h < 2; h++) {
          uint32_t q[8];
          const int k = 16 * b + 8 * h;
#pragma unroll
          for (int i = 0; i < 8; i++) q[i] = pack2(acc[2 * k + 2 * i], acc[2 * k + 2 * i + 1]);
          float s0[4], s1[4], s2[4];
          mma16z(s0, q[0], q[1], q[2], q[3], pv[k], pv[k + 1]); mma16z(s1, q[0], q[1], q[2], q[3], kf[k], kf[k + 2]); mma16z(s2, q[0], q[1], q[2], q[3], kf[k + 1], kf[k + 3]);
          mma16(s0, q[4], q[5], q[6], q[7], pv[k + 4], pv[k + 5]); mma16(s1, q[4], q[5], q[6], q[7], kf[k + 4], kf[k + 6]); mma16(s2, q[4], q[5], q[6], q[7], kf[k + 5], kf[k + 7]);
          if (first) { s0[0] = -INFINITY; s0[1] = -INFINITY; }
          l[h][0] = up0 ? s0[0] : s1[0]; l[h][1] = up1 ? s0[1] : s1[1]; l[h][2] = up0 ? s1[2] : s2[2]; l[h][3] = up1 ? s1[3] : s2[3];
          mx[2 * h] = fmaxf(l[h][0], l[h][1]); mx[2 * h + 1] = fmaxf(l[h][2], l[h][3]);
        }
#pragma unroll
        for (int o = 1; o < 4; o <<= 1) {
#pragma unroll
          for (int h = 0; h < 4; h++) mx[h] = fmaxf(mx[h], __shfl_xor_sync(~0u, mx[h], o));
        }
#pragma unroll
        for (int h = 0; h < 2; h++) {
          const float n0 = -mx[2 * h] * SCL, n1 = -mx[2 * h + 1] * SCL;
          const uint32_t pa = pack2(ex2(fmaf(l[h][0], SCL, n0)), ex2(fmaf(l[h][1], SCL, n0))), pb = pack2(ex2(fmaf(l[h][2], SCL, n1)), ex2(fmaf(l[h][3], SCL, n1)));
          float sm[4];
          mma8z(sm, pa, pb, 0x3f803f80u);
          const float ia = rcp(sm[0]), ib = rcp(sm[2]);
#pragma unroll
          for (int i = 8 * b + 4 * h; i < 8 * b + 4 * h + 4; i += 2) {
            uint32_t of[4];
#pragma unroll
            for (int d = 0; d < 2; d++) {
              float o[4];
              mma16z(o, pa & ~mup, pb & mup, 0u, pb & ~mup, vf[2 * (i + d)], vf[2 * (i + d) + 1]);
              mma8(o, pa & mup, 0u, pv[2 * i + 2 + d]);
              of[2 * d] = pack2(o[0] * ia, o[1] * ia); of[2 * d + 1] = pack2(o[2] * ib, o[3] * ib);
            }
            stsm4(stg_row + b * BLK + ((((i & 7) + (lane >> 4)) ^ (lane & 7)) << 4), of[0], of[1], of[2], of[3]);
          }
        }
        stage_done(sb, wg, b, lane);
        if (b == 0) gz += __float_as_uint(lds32f(bar + ZERO));
      }
      named_bar(1, 256);
    }
    uint32_t pk[64];
    {
      float acc[64];
      mainloop<128, 6, 0, 0>(acc, 16, true, r6, sb, wg, lane, rel, none, none, [&] {
        mbar_wait(bar + B_MOD, 0); mbar_wait(fre + 8, 1);
        load_vec(pk + 32, sb, 2, 0, lane); load_vec(pk + 40, sb, 2, 1, lane);
#pragma unroll
        for (int i = 0; i < 32; i++) { pk[i] = xk[i]; asm volatile("" : "+r"(pk[i])); }
      });
#pragma unroll
      for (int i = 0; i < 32; i++) {
        acc[2 * i] = fmaf(acc[2 * i], bf_lo(pk[32 + (i >> 1)]), bf_lo(pk[i]));
        acc[2 * i + 1] = fmaf(acc[2 * i + 1], bf_hi(pk[32 + (i >> 1)]), bf_hi(pk[i]));
      }
      ln_publish(acc, gs->stat + (16 + m) * 1024, j, row0, lane, ep);
      mbar_wait(bar + B_FULL6 + 16, 1);
      if (lane < 2) mbar_arrive_cl(rel + B_EMPTY6 + 16);
      ring_next<6>(r6);
#pragma unroll
      for (int i = 0; i < 32; i++) { pk[i] = pack2(acc[2 * i], acc[2 * i + 1]); pk[32 + i] = 0; }
      ln_apply(acc, gs->stat + (16 + m) * 1024, row0, ep, sb, 3, 4, stg_row, wg, lane);
      named_bar(1, 256);
    }
    auto swiglu = [&](int q, int uo, int par) {
      if ((q & 3) == 0 && par >= 0) mbar_wait(fre + 2 * q, par);
      uint32_t w[4];
#pragma unroll
      for (int u = 0; u < 4; u++) w[u] = silu_mul2(pk[4 * q + u], pk[uo + 4 * q + u]);
      stsm4(stg_row + (q >> 2) * BLK + ((((2 * q & 7) + (lane >> 4)) ^ (lane & 7)) << 4), w[0], w[1], w[2], w[3]);
    };
    r4.s = r4.wrap = 2;
#pragma unroll 1
    for (int t = 0; t < 3; t++) {
      float acc[128];
      mainloop<256, 4, 4, 1>(acc, 16, t == 0, r4, sb, wg, lane, rel, [&](auto ic) {
        if (t) {
          if (ic.v == 3) stage_done(sb, wg, 0, lane);
          swiglu(2 * ic.v - 2, 32, ~t & 1); swiglu(2 * ic.v - 1, 32, 0);
        }
      }, [&](int it) {
        if (t && it == 5) stage_done(sb, wg, 1, lane);
        if (t == 0 && it >= 8) {
          uint4* p = gs->x1 + bid * 2048 + ((it >> 2) & 1) * 1024 + warp * 128 + (it & 3) * 32 + lane;
#pragma unroll
          for (int i = 0; i < 8; i++)
            asm volatile("{\n.reg .pred p;\nsetp.eq.u32 p, %5, %6;\n@p st.global.v4.u32 [%0], {%1,%2,%3,%4};\n}" :: "l"(p), "r"(pk[4 * i]), "r"(pk[4 * i + 1]), "r"(pk[4 * i + 2]), "r"(pk[4 * i + 3]), "r"(it), "r"(8 + i) : "memory");
        }
      }, [&] { if (t == 0) fence_async_global(); else if (t == 2) mbar_wait(bar + B_X, 1); }, t & 1);
#pragma unroll
      for (int i = 0; i < 64; i++) pk[i] = pack2(acc[2 * i], acc[2 * i + 1]);
    }
    uint32_t x1[32];
    {
      float acc[64];
      mainloop<128, 6, 10, 1>(acc, 16, false, r6, sb, wg, lane, rel, [&](auto ic) {
        constexpr int b = ic.v > 5, q = ic.v - 5 * b;
        if (q == 1) {
          if (b) stage_done(sb, wg, 0, lane);
#pragma unroll
          for (int i = 4 * b; i < 4 * b + 4; i++) { const uint4 x = lds128(sb + STG + b * BLK + warp * 2048 + (i & 3) * 512 + lane * 16); x1[4 * i] = x.x; x1[4 * i + 1] = x.y; x1[4 * i + 2] = x.z; x1[4 * i + 3] = x.w; }
          __syncwarp();
        } else swiglu(4 * b + q - 2, 32, -1);
      }, [&](int it) { if (it == 11) stage_done(sb, wg, 1, lane); }, [] {}, 1);
#pragma unroll
      for (int i = 0; i < 32; i++) pk[i] = pack2(acc[2 * i], acc[2 * i + 1]);
    }
    {
      float acc[64];
      mainloop<128, 6, 4, TAILLAG>(acc, 56, false, r6, sb, wg, lane, rel, [&](auto ic) { swiglu(ic.v - 1, 16, 1); },
                                   [&](int it) { if (it == 5) stage_done(sb, wg, 0, lane); }, [&] {
        load_vec(pk + 32, sb, 5, 0, lane); load_vec(pk + 40, sb, 5, 1, lane);
        mbar_wait(fre, 0); mbar_wait(fre + 8, 1);
      }, 0);
      __syncwarp();
      cl_arrive_relaxed();
#pragma unroll
      for (int i = 0; i < 16; i += 2) {
        uint32_t w[4];
#pragma unroll
        for (int u = 0; u < 4; u++) {
          const int q = 2 * i + u;
          w[u] = pack2(fmaf(acc[2 * q], bf_lo(pk[32 + (q >> 1)]), bf_lo(x1[q])), fmaf(acc[2 * q + 1], bf_hi(pk[32 + (q >> 1)]), bf_hi(x1[q])));
        }
        stsm4(stg_row + (i >> 3) * BLK + ((((i & 7) + (lane >> 4)) ^ (lane & 7)) << 4), w[0], w[1], w[2], w[3]);
        if ((i & 7) == 6) {
          fence_async_smem();
          named_bar(2 + wg, 128);
          if (wq == 0 && elect()) { tma_store_3d(&maps.out, sb + STG + (i >> 3) * BLK + wg * HALF, j * 128 + (i >> 3) * 64, m * 64, wg); bulk_commit(); }
          if (i < 8) x1[16] |= __float_as_uint(lds32f(bar + ZERO));
        }
      }
      if (wq == 0) bulk_wait_read();
      if (tid == 0) gs->epoch[blockIdx.x] = ep;
      cl_wait();
    }
  }
}

typedef CUresult (*EncodeFn)(CUtensorMap*, CUtensorMapDataType, cuuint32_t, void*, const cuuint64_t*, const cuuint64_t*, const cuuint32_t*, const cuuint32_t*,
                             CUtensorMapInterleave, CUtensorMapSwizzle, CUtensorMapL2promotion, CUtensorMapFloatOOBfill);

void make_map(EncodeFn fn, CUtensorMap* mp, const void* base, uint64_t d0, uint64_t d1, uint64_t d2, uint64_t s1, uint64_t s2, uint32_t b2, uint32_t b0 = 64) {
  cuuint64_t d[3] = {d0, d1, d2}, s[2] = {s1, s2};
  cuuint32_t b[3] = {b0, 64, b2}, e[3] = {1, 1, 1};
  fn(mp, CU_TENSOR_MAP_DATA_TYPE_BFLOAT16, 3, (void*)base, d, s, b, e, CU_TENSOR_MAP_INTERLEAVE_NONE, b0 == 64 ? CU_TENSOR_MAP_SWIZZLE_128B : CU_TENSOR_MAP_SWIZZLE_NONE,
     CU_TENSOR_MAP_L2_PROMOTION_L2_128B, CU_TENSOR_MAP_FLOAT_OOB_FILL_NONE);
}

__global__ void probe_kernel() {}
int max_clusters(int size) {
  cudaLaunchConfig_t cfg = {};
  cudaLaunchAttribute at;
  at.id = cudaLaunchAttributeClusterDimension; at.val.clusterDim.x = size; at.val.clusterDim.y = 1; at.val.clusterDim.z = 1;
  cfg.gridDim = dim3(size * 66); cfg.blockDim = dim3(384); cfg.dynamicSmemBytes = SMEM_BYTES; cfg.attrs = &at; cfg.numAttrs = 1;
  int n = 0;
  if (cudaOccupancyMaxActiveClusters(&n, probe_kernel, &cfg) != cudaSuccess) { cudaGetLastError(); return 0; }
  return n;
}

}

extern "C" void kernel_launch(void* const* d_in, const int* in_sizes, int n_in, void* d_out, int out_size) {
  static EncodeFn fn = nullptr;
  static int by_sm = 0;
  static Scratch* gs = nullptr;
  if (!fn) {
    void* p = nullptr; cudaDriverEntryPointQueryResult q;
    cudaGetDriverEntryPoint("cuTensorMapEncodeTiled", &p, cudaEnableDefault, &q);
    fn = (EncodeFn)p;
    cudaFuncSetAttribute(fused_kernel, cudaFuncAttributeMaxDynamicSharedMemorySize, SMEM_BYTES);
    int dev = 0, sms = 0;
    cudaGetSymbolAddress((void**)&gs, g_scratch);
    cudaGetDevice(&dev);
    cudaDeviceGetAttribute(&sms, cudaDevAttrMultiProcessorCount, dev);
    cudaFuncSetAttribute(probe_kernel, cudaFuncAttributeMaxDynamicSharedMemorySize, SMEM_BYTES);
    by_sm = sms == 132 && max_clusters(2) == 66 && max_clusters(4) == 30 && max_clusters(6) == 17 && max_clusters(8) == 15;
  }
  Maps mp;
  make_map(fn, &mp.x, d_in[0], D_, S_ / 2, 2, 4096, 2048, 2);
  make_map(fn, &mp.out, d_out, D_, S_ / 2, 2, 4096, 2048, 1);
  make_map(fn, &mp.wqkv, d_in[1], 64, D_, 3 * D_ / 64, 3 * D_ * 2, 128, 2);
  make_map(fn, &mp.wo, d_in[2], 64, D_, D_ / 64, D_ * 2, 128, 2);
  make_map(fn, &mp.w1, d_in[4], 64, D_, F_ / 64, F_ * 2, 128, 2);
  make_map(fn, &mp.w3, d_in[5], 64, D_, F_ / 64, F_ * 2, 128, 2);
  make_map(fn, &mp.w1s, d_in[4], 64, D_, F_ / 64, F_ * 2, 128, 1);
  make_map(fn, &mp.w3s, d_in[5], 64, D_, F_ / 64, F_ * 2, 128, 1);
  make_map(fn, &mp.w2, d_in[6], 64, F_, D_ / 64, D_ * 2, 128, 2);
  make_map(fn, &mp.wmod, d_in[8], 256, D_, 24, 6 * D_ * 2, 512, 1, 256);
  fused_kernel<<<132, 384, SMEM_BYTES>>>((const bf16*)d_in[7], (const bf16*)d_in[8], gs, by_sm, mp);
}
```

```cpp
#include <cuda_runtime.h>
#include <cuda_bf16.h>
#include <cuda.h>
#include <stdint.h>

typedef __nv_bfloat16 bf16;

namespace {

constexpr int S_ = 2048, D_ = 1024, F_ = 3584;
constexpr int BLK = 16384;
constexpr int HALF = 8192;
constexpr int RING = 196608;
constexpr int STG = RING;
constexpr int MISC = RING + 2 * BLK;
constexpr int SMEM_BYTES = MISC + 3072;
constexpr int B_FULL4 = 0, B_EMPTY4 = 32, B_FULL6 = 64, B_EMPTY6 = 112, B_RDY = 160, B_FREE = 176, B_LAG = 192, B_X = 208, B_MOD = 224, B_HALO = 232, B_HH = 256, B_ALL = 272, B_HH2 = 288, ZERO = 296;
constexpr int MODV = 512;
constexpr int RED_OFF = 0;
constexpr float SCL = 0.17677669529663687f * 1.4426950408889634f;
constexpr int U_HH = 64;
constexpr int FS = 8;
constexpr int NPIECE = 4, PSLEEP = 300;
constexpr int XSLEEP = 4000, HSLEEP = 400;
constexpr uint32_t XDELAY = 2300, GAP = 250;
constexpr uint32_t B1P = 3700, B1D = 700;
constexpr int TAILLAG = 5;

struct Maps { CUtensorMap x, out, wqkv, wo, w1, w3, w1s, w3s, w2, wmod; };

struct Scratch {
  uint32_t epoch[256];
  uint32_t flag[16 * 128 * FS];
  uint32_t modp[8 * 2 * 4 * 128];
  uint2 modv[4 * 1024];
  uint2 stat[2 * 16 * 8 * 128];
  uint4 halo[16 * 8 * 2 * 512];
  uint4 x1[128 * 8 * 256];
  uint4 h[16 * 16 * 1024];
  uint4 o[16 * 16 * 1024];
  uint4 hh[16 * 56 * 1024];
};
__device__ __align__(1024) Scratch g_scratch;

__device__ __forceinline__ void bail() { asm volatile("st.global.u32 [%0], %1;" :: "l"(0ull), "r"(0) : "memory"); }
__device__ __forceinline__ uint32_t smem_u32(const void* p) { return (uint32_t)__cvta_generic_to_shared(p); }
__device__ __forceinline__ void mbar_init(uint32_t bar, uint32_t cnt) { asm volatile("mbarrier.init.shared::cta.b64 [%0], %1;" :: "r"(bar), "r"(cnt) : "memory"); }
__device__ __forceinline__ void mbar_arrive(uint32_t bar) { asm volatile("mbarrier.arrive.shared::cta.b64 _, [%0];" :: "r"(bar) : "memory"); }
__device__ __forceinline__ void mbar_arrive_cl(uint32_t cl_addr) { asm volatile("mbarrier.arrive.shared::cluster.b64 _, [%0];" :: "r"(cl_addr) : "memory"); }
__device__ __forceinline__ uint32_t mapa(uint32_t addr, uint32_t cta) { uint32_t r; asm("mapa.shared::cluster.u32 %0, %1, %2;" : "=r"(r) : "r"(addr), "r"(cta)); return r; }
__device__ __forceinline__ void mbar_wait(uint32_t bar, uint32_t parity) {
  asm volatile("{\n.reg .pred p;\n.reg .b32 n;\n.reg .b64 z;\nmov.b32 n, 0;\nmov.b64 z, 0;\n"
               "W: add.u32 n, n, 1;\nsetp.gt.u32 p, n, 0x400000;\n@p st.global.u32 [z], n;\n"
               "mbarrier.try_wait.parity.shared::cta.b64 p, [%0], %1;\n@!p bra W;\n}" :: "r"(bar), "r"(parity) : "memory");
}
__device__ __forceinline__ void tma_store_3d(const CUtensorMap* m, uint32_t src, int c0, int c1, int c2) {
  asm volatile("cp.async.bulk.tensor.3d.global.shared::cta.bulk_group [%0, {%2, %3, %4}], [%1];" :: "l"(m), "r"(src), "r"(c0), "r"(c1), "r"(c2) : "memory");
}
#define ELECT "{\n.reg .pred p;\nelect.sync _|p, 0xffffffff;\n@p "
__device__ __forceinline__ void expect_e(uint32_t bar, uint32_t bytes) { asm volatile(ELECT "mbarrier.arrive.expect_tx.shared::cta.b64 _, [%0], %1;\n}" :: "r"(bar), "r"(bytes) : "memory"); }
__device__ __forceinline__ void tma_3d_e(uint32_t dst, const CUtensorMap* m, uint32_t bar, int c0, int c1, int c2) {
  asm volatile(ELECT "cp.async.bulk.tensor.3d.shared::cluster.global.mbarrier::complete_tx::bytes [%0], [%1, {%3, %4, %5}], [%2];\n}" :: "r"(dst), "l"(m), "r"(bar), "r"(c0), "r"(c1), "r"(c2) : "memory");
}
__device__ __forceinline__ void bulk_ld_e(uint32_t dst, const void* src, uint32_t bytes, uint32_t bar) {
  asm volatile(ELECT "cp.async.bulk.shared::cluster.global.mbarrier::complete_tx::bytes [%0], [%1], %2, [%3];\n}" :: "r"(dst), "l"(src), "r"(bytes), "r"(bar) : "memory");
}
__device__ __forceinline__ void bulk_ld_mc_e(uint32_t dst, const void* src, uint32_t bytes, uint32_t bar) {
  asm volatile(ELECT "cp.async.bulk.shared::cluster.global.mbarrier::complete_tx::bytes.multicast::cluster [%0], [%1], %2, [%3], %4;\n}" :: "r"(dst), "l"(src), "r"(bytes), "r"(bar), "h"((uint16_t)3) : "memory");
}
__device__ __forceinline__ void bulk_push_e(uint32_t dst_cl, uint32_t src, uint32_t bytes, uint32_t bar_cl) {
  asm volatile(ELECT "cp.async.bulk.shared::cluster.shared::cta.mbarrier::complete_tx::bytes [%0], [%1], %2, [%3];\n}" :: "r"(dst_cl), "r"(src), "r"(bytes), "r"(bar_cl) : "memory");
}
__device__ __forceinline__ void arrive_e(uint32_t bar) { asm volatile(ELECT "mbarrier.arrive.shared::cta.b64 _, [%0];\n}" :: "r"(bar) : "memory"); }
__device__ __forceinline__ void bulk_st_e(void* dst, uint32_t src, uint32_t bytes) {
  asm volatile(ELECT "cp.async.bulk.global.shared::cta.bulk_group [%0], [%1], %2;\n}" :: "l"(dst), "r"(src), "r"(bytes) : "memory");
}
__device__ __forceinline__ void publish_e(uint32_t free_bar, uint32_t* flag, uint32_t ep) {
  asm volatile(ELECT "cp.async.bulk.commit_group;\n@p cp.async.bulk.wait_group 0;\n@p mbarrier.arrive.shared::cta.b64 _, [%0];\n@p st.release.gpu.global.u32 [%1], %2;\n}"
               :: "r"(free_bar), "l"(flag), "r"(ep) : "memory");
}
__device__ __forceinline__ void bulk_commit() { asm volatile("cp.async.bulk.commit_group;" ::: "memory"); }
__device__ __forceinline__ void bulk_wait_read() { asm volatile("cp.async.bulk.wait_group.read 0;" ::: "memory"); }
__device__ __forceinline__ void fence_async_global() { asm volatile("fence.proxy.async.global;" ::: "memory"); }
__device__ __forceinline__ void fence_async_smem() { asm volatile("fence.proxy.async.shared::cta;" ::: "memory"); }
__device__ __forceinline__ void wg_arrive() { asm volatile("wgmma.fence.sync.aligned;" ::: "memory"); }
__device__ __forceinline__ void wg_commit() { asm volatile("wgmma.commit_group.sync.aligned;" ::: "memory"); }
template <int N> __device__ __forceinline__ void wg_wait() { asm volatile("wgmma.wait_group.sync.aligned %0;" :: "n"(N) : "memory"); }
__device__ __forceinline__ void cl_arrive_relaxed() { asm volatile("barrier.cluster.arrive.relaxed.aligned;" ::: "memory"); }
__device__ __forceinline__ void cl_wait() { asm volatile("barrier.cluster.wait.acquire.aligned;" ::: "memory"); }
__device__ __forceinline__ bool elect() { uint32_t p; asm volatile("{\n.reg .pred p;\nelect.sync _|p, 0xffffffff;\nselp.u32 %0, 1, 0, p;\n}" : "=r"(p)); return p; }
__device__ __forceinline__ void named_bar(int id, int n) { asm volatile("bar.sync %0, %1;" :: "r"(id), "r"(n) : "memory"); }
__device__ __forceinline__ uint32_t pack2(float lo, float hi) { uint32_t r; asm("cvt.rn.bf16x2.f32 %0, %1, %2;" : "=r"(r) : "f"(hi), "f"(lo)); return r; }
__device__ __forceinline__ float bf_lo(uint32_t w) { return __uint_as_float(w << 16); }
__device__ __forceinline__ float bf_hi(uint32_t w) { return __uint_as_float(w & 0xffff0000u); }
__device__ __forceinline__ float bf_round(float v) { return __bfloat162float(__float2bfloat16_rn(v)); }
__device__ __forceinline__ void stsm4(uint32_t addr, uint32_t a, uint32_t b, uint32_t c, uint32_t d) {
  asm volatile("stmatrix.sync.aligned.m8n8.x4.shared.b16 [%0], {%1, %2, %3, %4};" :: "r"(addr), "r"(a), "r"(b), "r"(c), "r"(d) : "memory");
}
__device__ __forceinline__ void ldsm4(uint32_t addr, uint32_t& a, uint32_t& b, uint32_t& c, uint32_t& d) {
  asm volatile("ldmatrix.sync.aligned.m8n8.x4.shared.b16 {%0, %1, %2, %3}, [%4];" : "=r"(a), "=r"(b), "=r"(c), "=r"(d) : "r"(addr) : "memory");
}
__device__ __forceinline__ uint32_t movm(uint32_t a) { uint32_t r; asm volatile("movmatrix.sync.aligned.m8n8.trans.b16 %0, %1;" : "=r"(r) : "r"(a)); return r; }
__device__ __forceinline__ void mma16(float (&d)[4], uint32_t a0, uint32_t a1, uint32_t a2, uint32_t a3, uint32_t b0, uint32_t b1) {
  asm("mma.sync.aligned.m16n8k16.row.col.f32.bf16.bf16.f32 {%0,%1,%2,%3}, {%4,%5,%6,%7}, {%8,%9}, {%0,%1,%2,%3};"
               : "+f"(d[0]), "+f"(d[1]), "+f"(d[2]), "+f"(d[3]) : "r"(a0), "r"(a1), "r"(a2), "r"(a3), "r"(b0), "r"(b1));
}
__device__ __forceinline__ void mma16z(float (&d)[4], uint32_t a0, uint32_t a1, uint32_t a2, uint32_t a3, uint32_t b0, uint32_t b1) {
  asm("mma.sync.aligned.m16n8k16.row.col.f32.bf16.bf16.f32 {%0,%1,%2,%3}, {%4,%5,%6,%7}, {%8,%9}, {%10,%10,%10,%10};"
      : "=f"(d[0]), "=f"(d[1]), "=f"(d[2]), "=f"(d[3]) : "r"(a0), "r"(a1), "r"(a2), "r"(a3), "r"(b0), "r"(b1), "f"(0.f));
}
__device__ __forceinline__ void mma8z(float (&d)[4], uint32_t a0, uint32_t a1, uint32_t b0) {
  asm("mma.sync.aligned.m16n8k8.row.col.f32.bf16.bf16.f32 {%0,%1,%2,%3}, {%4,%5}, {%6}, {%7,%7,%7,%7};"
      : "=f"(d[0]), "=f"(d[1]), "=f"(d[2]), "=f"(d[3]) : "r"(a0), "r"(a1), "r"(b0), "f"(0.f));
}
__device__ __forceinline__ void mma8(float (&d)[4], uint32_t a0, uint32_t a1, uint32_t b0) {
  asm("mma.sync.aligned.m16n8k8.row.col.f32.bf16.bf16.f32 {%0,%1,%2,%3}, {%4,%5}, {%6}, {%0,%1,%2,%3};"
               : "+f"(d[0]), "+f"(d[1]), "+f"(d[2]), "+f"(d[3]) : "r"(a0), "r"(a1), "r"(b0));
}
__device__ __forceinline__ uint4 lds128(uint32_t a) { uint4 v; asm volatile("ld.shared.v4.u32 {%0,%1,%2,%3}, [%4];" : "=r"(v.x), "=r"(v.y), "=r"(v.z), "=r"(v.w) : "r"(a) : "memory"); return v; }
__device__ __forceinline__ void sts128(uint32_t a, uint32_t x, uint32_t y, uint32_t z, uint32_t w) { asm volatile("st.shared.v4.u32 [%0], {%1,%2,%3,%4};" :: "r"(a), "r"(x), "r"(y), "r"(z), "r"(w) : "memory"); }
__device__ __forceinline__ float lds32f(uint32_t a) { float v; asm volatile("ld.shared.f32 %0, [%1];" : "=f"(v) : "r"(a) : "memory"); return v; }
__device__ __forceinline__ void sts16(uint32_t a, bf16 v) { asm volatile("st.shared.b16 [%0], %1;" :: "r"(a), "h"(__bfloat16_as_ushort(v)) : "memory"); }
__device__ __forceinline__ uint4 ldg_nc(const void* p) { uint4 v; asm volatile("ld.global.nc.L1::no_allocate.v4.u32 {%0,%1,%2,%3}, [%4];" : "=r"(v.x), "=r"(v.y), "=r"(v.z), "=r"(v.w) : "l"(p)); return v; }
__device__ __forceinline__ uint4 ld_rlx4(const uint4* p) {
  unsigned long long a, b; asm volatile("ld.relaxed.gpu.global.v2.b64 {%0,%1}, [%2];" : "=l"(a), "=l"(b) : "l"(p) : "memory");
  return make_uint4((uint32_t)a, (uint32_t)(a >> 32), (uint32_t)b, (uint32_t)(b >> 32));
}
__device__ __forceinline__ uint2 ld_rlx2(const uint2* p) { unsigned long long a; asm volatile("ld.relaxed.gpu.global.b64 %0, [%1];" : "=l"(a) : "l"(p) : "memory"); return make_uint2((uint32_t)a, (uint32_t)(a >> 32)); }
__device__ __forceinline__ void st_rlx4(uint4* p, uint32_t x, uint32_t y, uint32_t z, uint32_t w) {
  asm volatile("st.relaxed.gpu.global.v2.b64 [%0], {%1,%2};" :: "l"(p), "l"((unsigned long long)x | ((unsigned long long)y << 32)), "l"((unsigned long long)z | ((unsigned long long)w << 32)) : "memory");
}
__device__ __forceinline__ void st_rlx2(uint2* p, uint32_t x, uint32_t y) { asm volatile("st.relaxed.gpu.global.b64 [%0], %1;" :: "l"(p), "l"((unsigned long long)x | ((unsigned long long)y << 32)) : "memory"); }
__device__ __forceinline__ void st_rlx1(uint32_t* p, uint32_t v) { asm volatile("st.relaxed.gpu.global.u32 [%0], %1;" :: "l"(p), "r"(v) : "memory"); }
__device__ __forceinline__ uint32_t ld_rlx1(const uint32_t* p) { uint32_t v; asm volatile("ld.relaxed.gpu.global.u32 %0, [%1];" : "=r"(v) : "l"(p) : "memory"); return v; }
__device__ __forceinline__ uint32_t ld_acquire(const uint32_t* p) { uint32_t v; asm volatile("ld.acquire.gpu.global.u32 %0, [%1];" : "=r"(v) : "l"(p) : "memory"); return v; }
__device__ __forceinline__ void prefetch_map(const CUtensorMap* m) { asm volatile("prefetch.tensormap [%0];" :: "l"(m) : "memory"); }
__device__ __forceinline__ float rcp(float x) { float r; asm("rcp.approx.ftz.f32 %0, %1;" : "=f"(r) : "f"(x)); return r; }
__device__ __forceinline__ float ex2(float x) { float r; asm("ex2.approx.ftz.f32 %0, %1;" : "=f"(r) : "f"(x)); return r; }
__device__ __forceinline__ float tanh_fast(float x) { float r; asm("tanh.approx.f32 %0, %1;" : "=f"(r) : "f"(x)); return r; }
#define SPIN_GUARD(n) if (++(n) > (1u << 24)) bail()

__device__ __forceinline__ void wgmma_n128(float (&d)[64], uint64_t da, uint64_t db) {
  asm volatile("wgmma.mma_async.sync.aligned.m64n128k16.f32.bf16.bf16 "
    "{%0, %1, %2, %3, %4, %5, %6, %7, %8, %9, %10, %11, %12, %13, %14, %15, %16, %17, %18, %19, %20, %21, %22, %23, %24, %25, %26, %27, %28, %29, %30, %31, %32, %33, %34, %35, %36, %37, %38, %39, %40, %41, %42, %43, %44, %45, %46, %47, %48, %49, %50, %51, %52, %53, %54, %55, %56, %57, %58, %59, %60, %61, %62, %63}, "
    "%64, %65, 1, 1, 1, 0, 1;\n"
    : "+f"(d[0]), "+f"(d[1]), "+f"(d[2]), "+f"(d[3]), "+f"(d[4]), "+f"(d[5]), "+f"(d[6]), "+f"(d[7]), "+f"(d[8]), "+f"(d[9]), "+f"(d[10]), "+f"(d[11]), "+f"(d[12]), "+f"(d[13]), "+f"(d[14]), "+f"(d[15]), "+f"(d[16]), "+f"(d[17]), "+f"(d[18]), "+f"(d[19]), "+f"(d[20]), "+f"(d[21]), "+f"(d[22]), "+f"(d[23]), "+f"(d[24]), "+f"(d[25]), "+f"(d[26]), "+f"(d[27]), "+f"(d[28]), "+f"(d[29]), "+f"(d[30]), "+f"(d[31]), "+f"(d[32]), "+f"(d[33]), "+f"(d[34]), "+f"(d[35]), "+f"(d[36]), "+f"(d[37]), "+f"(d[38]), "+f"(d[39]), "+f"(d[40]), "+f"(d[41]), "+f"(d[42]), "+f"(d[43]), "+f"(d[44]), "+f"(d[45]), "+f"(d[46]), "+f"(d[47]), "+f"(d[48]), "+f"(d[49]), "+f"(d[50]), "+f"(d[51]), "+f"(d[52]), "+f"(d[53]), "+f"(d[54]), "+f"(d[55]), "+f"(d[56]), "+f"(d[57]), "+f"(d[58]), "+f"(d[59]), "+f"(d[60]), "+f"(d[61]), "+f"(d[62]), "+f"(d[63])
    : "l"(da), "l"(db));
}
__device__ __forceinline__ void wgmma_n128_first(float (&d)[64], uint64_t da, uint64_t db) {
  asm volatile("wgmma.mma_async.sync.aligned.m64n128k16.f32.bf16.bf16 "
    "{%0, %1, %2, %3, %4, %5, %6, %7, %8, %9, %10, %11, %12, %13, %14, %15, %16, %17, %18, %19, %20, %21, %22, %23, %24, %25, %26, %27, %28, %29, %30, %31, %32, %33, %34, %35, %36, %37, %38, %39, %40, %41, %42, %43, %44, %45, %46, %47, %48, %49, %50, %51, %52, %53, %54, %55, %56, %57, %58, %59, %60, %61, %62, %63}, "
    "%64, %65, 0, 1, 1, 0, 1;\n"
    : "=f"(d[0]), "=f"(d[1]), "=f"(d[2]), "=f"(d[3]), "=f"(d[4]), "=f"(d[5]), "=f"(d[6]), "=f"(d[7]), "=f"(d[8]), "=f"(d[9]), "=f"(d[10]), "=f"(d[11]), "=f"(d[12]), "=f"(d[13]), "=f"(d[14]), "=f"(d[15]), "=f"(d[16]), "=f"(d[17]), "=f"(d[18]), "=f"(d[19]), "=f"(d[20]), "=f"(d[21]), "=f"(d[22]), "=f"(d[23]), "=f"(d[24]), "=f"(d[25]), "=f"(d[26]), "=f"(d[27]), "=f"(d[28]), "=f"(d[29]), "=f"(d[30]), "=f"(d[31]), "=f"(d[32]), "=f"(d[33]), "=f"(d[34]), "=f"(d[35]), "=f"(d[36]), "=f"(d[37]), "=f"(d[38]), "=f"(d[39]), "=f"(d[40]), "=f"(d[41]), "=f"(d[42]), "=f"(d[43]), "=f"(d[44]), "=f"(d[45]), "=f"(d[46]), "=f"(d[47]), "=f"(d[48]), "=f"(d[49]), "=f"(d[50]), "=f"(d[51]), "=f"(d[52]), "=f"(d[53]), "=f"(d[54]), "=f"(d[55]), "=f"(d[56]), "=f"(d[57]), "=f"(d[58]), "=f"(d[59]), "=f"(d[60]), "=f"(d[61]), "=f"(d[62]), "=f"(d[63])
    : "l"(da), "l"(db));
}
__device__ __forceinline__ void wgmma_n256(float (&d)[128], uint64_t da, uint64_t db) {
  asm volatile("wgmma.mma_async.sync.aligned.m64n256k16.f32.bf16.bf16 "
    "{%0, %1, %2, %3, %4, %5, %6, %7, %8, %9, %10, %11, %12, %13, %14, %15, %16, %17, %18, %19, %20, %21, %22, %23, %24, %25, %26, %27, %28, %29, %30, %31, %32, %33, %34, %35, %36, %37, %38, %39, %40, %41, %42, %43, %44, %45, %46, %47, %48, %49, %50, %51, %52, %53, %54, %55, %56, %57, %58, %59, %60, %61, %62, %63, %64, %65, %66, %67, %68, %69, %70, %71, %72, %73, %74, %75, %76, %77, %78, %79, %80, %81, %82, %83, %84, %85, %86, %87, %88, %89, %90, %91, %92, %93, %94, %95, %96, %97, %98, %99, %100, %101, %102, %103, %104, %105, %106, %107, %108, %109, %110, %111, %112, %113, %114, %115, %116, %117, %118, %119, %120, %121, %122, %123, %124, %125, %126, %127}, "
    "%128, %129, 1, 1, 1, 0, 1;\n"
    : "+f"(d[0]), "+f"(d[1]), "+f"(d[2]), "+f"(d[3]), "+f"(d[4]), "+f"(d[5]), "+f"(d[6]), "+f"(d[7]), "+f"(d[8]), "+f"(d[9]), "+f"(d[10]), "+f"(d[11]), "+f"(d[12]), "+f"(d[13]), "+f"(d[14]), "+f"(d[15]), "+f"(d[16]), "+f"(d[17]), "+f"(d[18]), "+f"(d[19]), "+f"(d[20]), "+f"(d[21]), "+f"(d[22]), "+f"(d[23]), "+f"(d[24]), "+f"(d[25]), "+f"(d[26]), "+f"(d[27]), "+f"(d[28]), "+f"(d[29]), "+f"(d[30]), "+f"(d[31]), "+f"(d[32]), "+f"(d[33]), "+f"(d[34]), "+f"(d[35]), "+f"(d[36]), "+f"(d[37]), "+f"(d[38]), "+f"(d[39]), "+f"(d[40]), "+f"(d[41]), "+f"(d[42]), "+f"(d[43]), "+f"(d[44]), "+f"(d[45]), "+f"(d[46]), "+f"(d[47]), "+f"(d[48]), "+f"(d[49]), "+f"(d[50]), "+f"(d[51]), "+f"(d[52]), "+f"(d[53]), "+f"(d[54]), "+f"(d[55]), "+f"(d[56]), "+f"(d[57]), "+f"(d[58]), "+f"(d[59]), "+f"(d[60]), "+f"(d[61]), "+f"(d[62]), "+f"(d[63]), "+f"(d[64]), "+f"(d[65]), "+f"(d[66]), "+f"(d[67]), "+f"(d[68]), "+f"(d[69]), "+f"(d[70]), "+f"(d[71]), "+f"(d[72]), "+f"(d[73]), "+f"(d[74]), "+f"(d[75]), "+f"(d[76]), "+f"(d[77]), "+f"(d[78]), "+f"(d[79]), "+f"(d[80]), "+f"(d[81]), "+f"(d[82]), "+f"(d[83]), "+f"(d[84]), "+f"(d[85]), "+f"(d[86]), "+f"(d[87]), "+f"(d[88]), "+f"(d[89]), "+f"(d[90]), "+f"(d[91]), "+f"(d[92]), "+f"(d[93]), "+f"(d[94]), "+f"(d[95]), "+f"(d[96]), "+f"(d[97]), "+f"(d[98]), "+f"(d[99]), "+f"(d[100]), "+f"(d[101]), "+f"(d[102]), "+f"(d[103]), "+f"(d[104]), "+f"(d[105]), "+f"(d[106]), "+f"(d[107]), "+f"(d[108]), "+f"(d[109]), "+f"(d[110]), "+f"(d[111]), "+f"(d[112]), "+f"(d[113]), "+f"(d[114]), "+f"(d[115]), "+f"(d[116]), "+f"(d[117]), "+f"(d[118]), "+f"(d[119]), "+f"(d[120]), "+f"(d[121]), "+f"(d[122]), "+f"(d[123]), "+f"(d[124]), "+f"(d[125]), "+f"(d[126]), "+f"(d[127])
    : "l"(da), "l"(db));
}
__device__ __forceinline__ void wgmma_n256_first(float (&d)[128], uint64_t da, uint64_t db) {
  asm volatile("wgmma.mma_async.sync.aligned.m64n256k16.f32.bf16.bf16 "
    "{%0, %1, %2, %3, %4, %5, %6, %7, %8, %9, %10, %11, %12, %13, %14, %15, %16, %17, %18, %19, %20, %21, %22, %23, %24, %25, %26, %27, %28, %29, %30, %31, %32, %33, %34, %35, %36, %37, %38, %39, %40, %41, %42, %43, %44, %45, %46, %47, %48, %49, %50, %51, %52, %53, %54, %55, %56, %57, %58, %59, %60, %61, %62, %63, %64, %65, %66, %67, %68, %69, %70, %71, %72, %73, %74, %75, %76, %77, %78, %79, %80, %81, %82, %83, %84, %85, %86, %87, %88, %89, %90, %91, %92, %93, %94, %95, %96, %97, %98, %99, %100, %101, %102, %103, %104, %105, %106, %107, %108, %109, %110, %111, %112, %113, %114, %115, %116, %117, %118, %119, %120, %121, %122, %123, %124, %125, %126, %127}, "
    "%128, %129, 0, 1, 1, 0, 1;\n"
    : "=f"(d[0]), "=f"(d[1]), "=f"(d[2]), "=f"(d[3]), "=f"(d[4]), "=f"(d[5]), "=f"(d[6]), "=f"(d[7]), "=f"(d[8]), "=f"(d[9]), "=f"(d[10]), "=f"(d[11]), "=f"(d[12]), "=f"(d[13]), "=f"(d[14]), "=f"(d[15]), "=f"(d[16]), "=f"(d[17]), "=f"(d[18]), "=f"(d[19]), "=f"(d[20]), "=f"(d[21]), "=f"(d[22]), "=f"(d[23]), "=f"(d[24]), "=f"(d[25]), "=f"(d[26]), "=f"(d[27]), "=f"(d[28]), "=f"(d[29]), "=f"(d[30]), "=f"(d[31]), "=f"(d[32]), "=f"(d[33]), "=f"(d[34]), "=f"(d[35]), "=f"(d[36]), "=f"(d[37]), "=f"(d[38]), "=f"(d[39]), "=f"(d[40]), "=f"(d[41]), "=f"(d[42]), "=f"(d[43]), "=f"(d[44]), "=f"(d[45]), "=f"(d[46]), "=f"(d[47]), "=f"(d[48]), "=f"(d[49]), "=f"(d[50]), "=f"(d[51]), "=f"(d[52]), "=f"(d[53]), "=f"(d[54]), "=f"(d[55]), "=f"(d[56]), "=f"(d[57]), "=f"(d[58]), "=f"(d[59]), "=f"(d[60]), "=f"(d[61]), "=f"(d[62]), "=f"(d[63]), "=f"(d[64]), "=f"(d[65]), "=f"(d[66]), "=f"(d[67]), "=f"(d[68]), "=f"(d[69]), "=f"(d[70]), "=f"(d[71]), "=f"(d[72]), "=f"(d[73]), "=f"(d[74]), "=f"(d[75]), "=f"(d[76]), "=f"(d[77]), "=f"(d[78]), "=f"(d[79]), "=f"(d[80]), "=f"(d[81]), "=f"(d[82]), "=f"(d[83]), "=f"(d[84]), "=f"(d[85]), "=f"(d[86]), "=f"(d[87]), "=f"(d[88]), "=f"(d[89]), "=f"(d[90]), "=f"(d[91]), "=f"(d[92]), "=f"(d[93]), "=f"(d[94]), "=f"(d[95]), "=f"(d[96]), "=f"(d[97]), "=f"(d[98]), "=f"(d[99]), "=f"(d[100]), "=f"(d[101]), "=f"(d[102]), "=f"(d[103]), "=f"(d[104]), "=f"(d[105]), "=f"(d[106]), "=f"(d[107]), "=f"(d[108]), "=f"(d[109]), "=f"(d[110]), "=f"(d[111]), "=f"(d[112]), "=f"(d[113]), "=f"(d[114]), "=f"(d[115]), "=f"(d[116]), "=f"(d[117]), "=f"(d[118]), "=f"(d[119]), "=f"(d[120]), "=f"(d[121]), "=f"(d[122]), "=f"(d[123]), "=f"(d[124]), "=f"(d[125]), "=f"(d[126]), "=f"(d[127])
    : "l"(da), "l"(db));
}

template <int N> struct WG;
#define DEF_WG(N) template <> struct WG<N> { \
  static __device__ __forceinline__ void mma(float (&d)[N / 2], uint64_t a, uint64_t b) { wgmma_n##N(d, a, b); } \
  static __device__ __forceinline__ void first(float (&d)[N / 2], uint64_t a, uint64_t b) { wgmma_n##N##_first(d, a, b); } };
DEF_WG(128) DEF_WG(256)

constexpr uint64_t DESC_A = (1ull << 62) | ((uint64_t)(1024 >> 4) << 32) | (1ull << 16);
constexpr uint64_t DESC_B = (1ull << 62) | ((uint64_t)(1024 >> 4) << 32) | ((uint64_t)(8192 >> 4) << 16);

struct Ring { int s; uint32_t ph; int wrap; };
template <int NS> __device__ __forceinline__ void ring_next(Ring& r) { r.s = (r.s + 1 == NS) ? 0 : r.s + 1; if (r.s == r.wrap) r.ph ^= 1; }

__device__ __forceinline__ int own_order(int it, int j) {
  return it < 2 ? 2 * j + it : it < 4 ? 2 * (j ^ 1) + it - 2 : ((j >> 1) * 4 + 2 * it - (it < 10 ? 4 : 15)) & 15;
}

template <int V> struct IC { static constexpr int v = V; };
template <int I, int E, class F> __device__ __forceinline__ void static_for(F&& f) { if constexpr (I < E) { f(IC<I>{}); static_for<I + 1, E>(f); } }

template <int N, int NS, int PRE, int LAG, class Pre, class Mid, class Last>
__device__ __forceinline__ void mainloop(float (&acc)[N / 2], int nkb, bool own, Ring& r, uint32_t sb, int wg, int lane, uint32_t rel_base, Pre pre, Mid mid, Last last, int lag_par = 0) {
  constexpr int SLOT = RING / NS;
  const uint32_t full = sb + MISC + (NS == 4 ? B_FULL4 : B_FULL6);
  const uint32_t rel = rel_base + (NS == 4 ? B_EMPTY4 : B_EMPTY6);
  const uint32_t s0 = (sb & 0x3FFFF) >> 4, a0 = s0 + wg * (HALF >> 4);
  int ps;
  auto issue = [&](int it, bool first) {
    const uint64_t da = DESC_A | (a0 + ((own && it < 2) ? (STG + it * BLK) >> 4 : r.s * (SLOT >> 4))), db = DESC_B | (s0 + r.s * (SLOT >> 4) + (BLK >> 4));
    mbar_wait(full + r.s * 8, r.ph);
    wg_arrive();
    if (first) WG<N>::first(acc, da, db); else WG<N>::mma(acc, da, db);
#pragma unroll
    for (int k = 1; k < 4; k++) WG<N>::mma(acc, da + k * 2, db + k * 128);
    wg_commit();
  };
  auto retire = [&](int it) {
    wg_wait<1>();
    if (lane < 2) mbar_arrive_cl(rel + ps * 8);
    ps = r.s;
    ring_next<NS>(r);
  };
  issue(0, true);
  ps = r.s;
  ring_next<NS>(r);
  static_for<1, PRE + 1>([&](auto ic) { issue(ic.v, false); pre(ic); retire(ic.v); });
#pragma unroll 1
  for (int it = PRE + 1; it < nkb; it++) {
    if (LAG && it == nkb - LAG && wg == 1) mbar_wait(sb + MISC + B_LAG, lag_par);
    issue(it, false); mid(it); retire(it);
  }
  if (LAG && wg == 0 && lane == 0) mbar_arrive(sb + MISC + B_LAG);
  last();
  wg_wait<0>();
  if (lane < 2) mbar_arrive_cl(rel + ps * 8);
}

__device__ __forceinline__ uint32_t tag_of(uint32_t ep) { return (ep & 127u) + 1u; }
__device__ __forceinline__ void ln_publish(const float (&v)[64], uint2* st, int j, int row0, int lane, uint32_t ep) {
  float s0 = 0, s1 = 0, s2 = 0, s3 = 0, q0 = 0, q1 = 0, q2 = 0, q3 = 0;
#pragma unroll
  for (int i = 0; i < 16; i++) {
    s0 += v[4 * i]; s1 += v[4 * i + 1]; s2 += v[4 * i + 2]; s3 += v[4 * i + 3];
    q0 = fmaf(v[4 * i], v[4 * i], q0); q1 = fmaf(v[4 * i + 1], v[4 * i + 1], q1); q2 = fmaf(v[4 * i + 2], v[4 * i + 2], q2); q3 = fmaf(v[4 * i + 3], v[4 * i + 3], q3);
  }
  s0 += s1; s2 += s3; q0 += q1; q2 += q3;
  const bool odd = lane & 1;
  float s = (odd ? s2 : s0) + __shfl_xor_sync(~0u, odd ? s0 : s2, 1), q = (odd ? q2 : q0) + __shfl_xor_sync(~0u, odd ? q0 : q2, 1);
  s += __shfl_xor_sync(~0u, s, 2); q += __shfl_xor_sync(~0u, q, 2);
  if ((lane & 3) < 2) st_rlx2(st + j * 128 + row0 + (lane & 1) * 8, __float_as_uint(s), (__float_as_uint(fmaf(s * (-1.f / 128), s, q)) & ~255u) | tag_of(ep));
}
__device__ __forceinline__ void ln_gather(const uint2* st, int row0, int lane, uint32_t ep, float& n0, float& r0, float& n1, float& r1, bool rnd) {
  const uint2* p = st + (lane & 2) * 256 + row0 + (lane & 1) * 8;
  const uint32_t tag = tag_of(ep);
  uint2 a, b, c, d; uint32_t n = 0;
  while (true) {
    a = ld_rlx2(p); b = ld_rlx2(p + 128); c = ld_rlx2(p + 256); d = ld_rlx2(p + 384);
    if ((((a.y ^ tag) | (b.y ^ tag) | (c.y ^ tag) | (d.y ^ tag)) & 255u) == 0) break;
    SPIN_GUARD(n);
  }
  __syncwarp();
  const uint32_t fix = tag ^ 128u;
  float s = (__uint_as_float(a.x) + __uint_as_float(b.x)) + (__uint_as_float(c.x) + __uint_as_float(d.x));
  float q = (__uint_as_float(a.y ^ fix) + __uint_as_float(b.y ^ fix)) + (__uint_as_float(c.y ^ fix) + __uint_as_float(d.y ^ fix));
  q = fmaf(fmaf(__uint_as_float(a.x), __uint_as_float(a.x), __uint_as_float(b.x) * __uint_as_float(b.x)) +
           fmaf(__uint_as_float(c.x), __uint_as_float(c.x), __uint_as_float(d.x) * __uint_as_float(d.x)), 1.f / 128, q);
  s += __shfl_xor_sync(~0u, s, 2); q += __shfl_xor_sync(~0u, q, 2);
  s *= 1.f / 1024;
  const float var = fmaxf(fmaf(-s, s, q * (1.f / 1024)), 0.f);
  float r;
  if (rnd) {
    float sd; asm("sqrt.approx.f32 %0, %1;" : "=f"(sd) : "f"(bf_round(bf_round(var) + 1e-5f)));
    r = rcp(bf_round(sd)); s = bf_round(s);
  } else r = rsqrtf(var + 1e-5f);
  const float nn = -s * r;
  const float ro = __shfl_xor_sync(~0u, r, 1), no = __shfl_xor_sync(~0u, nn, 1);
  const bool odd = lane & 1;
  r0 = odd ? ro : r; n0 = odd ? no : nn; r1 = odd ? r : ro; n1 = odd ? nn : no;
}
__device__ __forceinline__ void load_vec(uint32_t* w, uint32_t sb, int sec, int b, int lane) {
#pragma unroll
  for (int q = 0; q < 2; q++) { uint4 t = lds128(sb + MISC + MODV + sec * 256 + (lane & 3) * 64 + b * 32 + q * 16); w[4 * q] = t.x; w[4 * q + 1] = t.y; w[4 * q + 2] = t.z; w[4 * q + 3] = t.w; }
}
__device__ __forceinline__ void stage_done(uint32_t sb, int wg, int b, int lane) {
  fence_async_smem();
  __syncwarp();
  if (lane == 0) mbar_arrive(sb + MISC + B_RDY + b * 8);
}
__device__ __forceinline__ uint32_t hfma2(uint32_t a, uint32_t b, uint32_t c) { uint32_t r; asm("fma.rn.bf16x2 %0, %1, %2, %3;" : "=r"(r) : "r"(a), "r"(b), "r"(c)); return r; }
__device__ __forceinline__ void ln_apply(const float (&v)[64], const uint2* st, int row0, uint32_t ep, uint32_t sb, int sec_shift, int sec_scale, uint32_t stg_row, int wg, int lane) {
  uint32_t sc[16], sh[16];
#pragma unroll
  for (int b = 0; b < 2; b++) { load_vec(sc + 8 * b, sb, sec_scale, b, lane); load_vec(sh + 8 * b, sb, sec_shift, b, lane); }
  float n0, r0, n1, r1;
  ln_gather(st, row0, lane, ep, n0, r0, n1, r1, sec_shift == 0);
#pragma unroll
  for (int i = 0; i < 16; i += 2) {
    if (i == 8) { const float z = lds32f(sb + MISC + ZERO); n0 += z; n1 += z; }
    uint32_t w[4];
#pragma unroll
    for (int u = 0; u < 2; u++) {
      int q = i + u;
      w[2 * u] = hfma2(pack2(fmaf(v[4 * q], r0, n0), fmaf(v[4 * q + 1], r0, n0)), sc[q], sh[q]);
      w[2 * u + 1] = hfma2(pack2(fmaf(v[4 * q + 2], r1, n1), fmaf(v[4 * q + 3], r1, n1)), sc[q], sh[q]);
    }
    stsm4(stg_row + (i >> 3) * BLK + ((((i & 7) + (lane >> 4)) ^ (lane & 7)) << 4), w[0], w[1], w[2], w[3]);
    if ((i & 7) == 6) { stage_done(sb, wg, i >> 3, lane); }
  }
}
__device__ __forceinline__ uint32_t hmul2(uint32_t a, uint32_t b) { uint32_t r; asm("mul.rn.bf16x2 %0, %1, %2;" : "=r"(r) : "r"(a), "r"(b)); return r; }
__device__ __forceinline__ uint32_t silu_mul2(uint32_t g, uint32_t u) {
  const uint32_t h = hmul2(g, 0x3f003f00u);
  const float h0 = bf_lo(h), h1 = bf_hi(h);
  return hmul2(pack2(fmaf(h0, tanh_fast(h0), h0), fmaf(h1, tanh_fast(h1), h1)), u);
}

__device__ __forceinline__ void gemv_fma(float (&a)[8], uint4 w, float s) {
  a[0] = fmaf(bf_lo(w.x), s, a[0]); a[1] = fmaf(bf_hi(w.x), s, a[1]); a[2] = fmaf(bf_lo(w.y), s, a[2]); a[3] = fmaf(bf_hi(w.y), s, a[3]);
  a[4] = fmaf(bf_lo(w.z), s, a[4]); a[5] = fmaf(bf_hi(w.z), s, a[5]); a[6] = fmaf(bf_lo(w.w), s, a[6]); a[7] = fmaf(bf_hi(w.w), s, a[7]);
}
__device__ __forceinline__ float silu_c(float v) { return bf_round(__fdividef(v, 1.f + __expf(-v))); }
__device__ __forceinline__ float mod_gather(const uint32_t* p, uint32_t ep) {
  const uint32_t tag = tag_of(ep), fix = tag ^ 128u;
  uint32_t a, b, c, d, n = 0;
  while (true) {
    a = ld_rlx1(p); b = ld_rlx1(p + 128); c = ld_rlx1(p + 256); d = ld_rlx1(p + 384);
    if ((((a ^ tag) | (b ^ tag) | (c ^ tag) | (d ^ tag)) & 255u) == 0) break;
    SPIN_GUARD(n);
  }
  return (__uint_as_float(a ^ fix) + __uint_as_float(b ^ fix)) + (__uint_as_float(c ^ fix) + __uint_as_float(d ^ fix));
}
__device__ __forceinline__ void mod_store(uint32_t sb, int sec, int col, float v) {
  v = bf_round(v);
  if (sec == 1) v += 1.f;
  sts16(sb + MISC + MODV + sec * 256 + (((col >> 1) & 3) * 16 + (col >> 3)) * 4 + (col & 1) * 2, __float2bfloat16_rn(v));
}

__global__ void __cluster_dims__(2, 1, 1) __launch_bounds__(384, 1)
fused_kernel(const bf16* __restrict__ cvec, const bf16* __restrict__ wmod, Scratch* gs, int by_sm, const __grid_constant__ Maps maps) {
  extern __shared__ __align__(1024) uint8_t smem_raw[];
  const uint32_t sb = smem_u32(smem_raw);
  const int warp = __shfl_sync(~0u, threadIdx.x >> 5, 0), lane = threadIdx.x & 31;
  const int rank = blockIdx.x & 1;
  uint32_t sm; asm volatile("mov.u32 %0, %%smid;" : "=r"(sm));
  const int t = sm >> 1, v = t < 32 || by_sm == 2 ? t : t < 60 ? t + 1 + (((t - 32) * 37) >> 8) : (t - 58) * 8;
  const int gr = 0x71546320u >> ((v & 7) * 4);
  const int cid = !by_sm ? (blockIdx.x >> 1) - 2 : (t & ~1) == 56 + 4 * by_sm ? (t & 1) - 2 : (gr & 4) * 8 + (v >> 3) * 4 + (gr & 3);
  const bool extra = cid < 0;
  const int bid = cid * 2 + rank;
  const int m = cid >> 2, j = (cid & 3) * 2 + rank;
  const uint32_t bar = sb + MISC;

  if (warp >= 8) {
    asm volatile("setmaxnreg.dec.sync.aligned.u32 40;");
    if (extra) {
      if (warp == 8) {
        if (lane == 0) { for (int s = 0; s < 6; s++) { mbar_init(bar + B_FULL6 + s * 8, 1); mbar_init(bar + B_EMPTY6 + s * 8, 8); } fence_async_smem(); }
        __syncwarp();
        asm volatile("bar.arrive 2, 288;" ::: "memory");
        __nanosleep(XSLEEP);
#pragma unroll 1
        for (int it = 0, s = 0, par = 1; it < 64; it++) {
          mbar_wait(bar + B_EMPTY6 + s * 8, par);
          expect_e(bar + B_FULL6 + s * 8, 32768); tma_3d_e(sb + s * 32768, &maps.wmod, bar + B_FULL6 + s * 8, 0, (it & 15) * 64, 12 + (it >> 4) * 4 + bid);
          if (++s == 6) { s = 0; par ^= 1; }
        }
      }
    } else if (warp < 10) {
      uint32_t f6 = bar + B_FULL6, d6 = sb + (warp == 8 ? BLK : rank * HALF), p6 = 1;
      auto next6 = [&]() { f6 += 8; d6 += 32768; if (f6 == bar + B_FULL6 + 48) { f6 -= 48; d6 -= RING; p6 ^= 1; } };
      auto drained4 = [&](int q, int late) { if (q < 5) mbar_wait(bar + B_EMPTY4 + (((late ? 0x10332 : 0x32110) >> (4 * q)) & 3) * 8, 1); };
      auto drained6 = [&](int q) { if (q < 3) mbar_wait(bar + B_EMPTY6 + ((0x154 >> (4 * q)) & 7) * 8, q >> 1); };
      auto skip6 = [&]() { mbar_wait(f6 + 48, p6); expect_e(f6, 0); next6(); };
      if (warp == 8) {
        const uint32_t t_start = clock();
        if (lane == 0) {
          if (sb & 1023) bail();
          for (int b = 0; b < 2; b++) mbar_init(bar + B_X + b * 8, 1);
          for (int s = 0; s < 4; s++) { mbar_init(bar + B_FULL4 + s * 8, 2); mbar_init(bar + B_EMPTY4 + s * 8, 16); }
          for (int s = 0; s < 6; s++) { mbar_init(bar + B_FULL6 + s * 8, 2); mbar_init(bar + B_EMPTY6 + s * 8, 16); }
          for (int b = 0; b < 2; b++) { mbar_init(bar + B_RDY + b * 8, 8); mbar_init(bar + B_FREE + b * 8, 1); mbar_init(bar + B_HH + b * 8, 1); }
          mbar_init(bar + B_MOD, 1); mbar_init(bar + B_LAG, 4); mbar_init(bar + B_HALO, 2); mbar_init(bar + B_ALL, 1); mbar_init(bar + B_HH2, 1);
          asm volatile("st.shared.u32 [%0], 0;" :: "r"(bar + ZERO) : "memory");
          asm volatile("fence.mbarrier_init.release.cluster;" ::: "memory");
          fence_async_smem();
        }
        __syncwarp();
        cl_arrive_relaxed();
        while ((uint32_t)clock() - t_start < XDELAY) {}
        for (int b = 0; b < 2; b++) { expect_e(bar + B_X + b * 8, BLK); tma_3d_e(sb + STG + b * BLK, &maps.x, bar + B_X + b * 8, j * 128 + b * 64, m * 64, 0); }
        mbar_wait(bar + B_X + 8, 0);
#pragma unroll 1
        for (int ph = 0; ph < 2; ph++) {
          const CUtensorMap* const m0 = ph ? &maps.w1 : &maps.wqkv;
#pragma unroll 1
          for (int it = 0; it < (ph ? 48 : 16); it++) {
            const int s = (it + 2 * ph) & 3;
            int a0 = (ph ? it & 48 : 16) + 2 * j, a1 = ph ? a0 : a0 + 16, k0 = (it < 16 ? own_order(it, j) : it & 15) * 64;
            uint32_t full = bar + B_FULL4 + s * 8, d = sb + s * 49152 + BLK;
            if (ph) drained6(it);
            mbar_wait(full + 32, ~(it >> 2) & 1);
            tma_3d_e(d, m0, full, 0, k0, a0);
            if (it < 4) { const uint32_t t0 = clock(); while ((uint32_t)clock() - t0 < GAP) {} }
            tma_3d_e(d + BLK, m0 + ph, full, 0, k0, a1);
            expect_e(full, 2 * BLK);
            if (it < 4) { const uint32_t t0 = clock(); while ((uint32_t)clock() - t0 < GAP) {} }
            if (it >= 44) {
              if (it == 44) { mbar_wait(bar + B_FREE, 0); mbar_wait(bar + B_FREE + 8, 0); expect_e(bar + B_X, 2 * BLK); }
              bulk_ld_e(sb + STG + (it - 44) * HALF, gs->x1 + bid * 2048 + (it - 44) * 512, HALF, bar + B_X);
            }
          }
          const CUtensorMap* const m1 = ph ? &maps.w1s : &maps.wqkv;
          const int a = ph ? 48 + j : 2 * j;
#pragma unroll 1
          for (int k0 = 0; k0 < 1024; k0 += 64) {
            drained4(k0 >> 6, ph);
            mbar_wait(f6 + 48, p6);
            tma_3d_e(d6, m1, f6, 0, k0, a);
            if (ph) tma_3d_e(d6 + HALF, &maps.w3s, f6, 0, k0, a);
            expect_e(f6, BLK);
            next6();
          }
          if (ph) break;
#pragma unroll 1
          for (int it = 0; it < 16; it++) {
            const int k0 = own_order(it, j) * 64;
            mbar_wait(f6 + 48, p6);
            tma_3d_e(d6, &maps.wo, f6, 0, k0, 2 * j);
            expect_e(f6, BLK);
            next6();
          }
          skip6();
        }
#pragma unroll 1
        for (int k0 = 0; k0 < F_; k0 += 64) {
          mbar_wait(f6 + 48, p6);
          tma_3d_e(d6, &maps.w2, f6, 0, k0, 2 * j);
          expect_e(f6, BLK);
          next6();
        }
      } else {
        if (lane < 9) prefetch_map(&maps.x + lane);
        const uint32_t ep = gs->epoch[blockIdx.x] + 1;
        cl_arrive_relaxed(); cl_wait();
        auto run6 = [&](const uint4* src, int n, int sw) {
          src += rank * 512;
#pragma unroll 1
          for (int it = 0; it < n; it++) {
            if (sw >= 0) drained4(it, sw);
            mbar_wait(f6 + 48, p6);
            bulk_ld_mc_e(d6, src, HALF, f6);
            expect_e(f6, BLK);
            next6();
            src += 1024;
          }
        };
        uint32_t ready = 0;
        auto need = [&](int e, uint32_t mask) {
          if (!(ready & mask)) {
            uint32_t n = 0;
            do { ready = __ballot_sync(~0u, ld_acquire(gs->flag + (m * 128 + e * 16 + (lane & 14)) * FS) == ep); SPIN_GUARD(n); } while (!(ready & mask));
            fence_async_global();
          }
        };
        auto fresh = [&](int e, int it, uint32_t full, uint32_t empty, int par, uint32_t slot, uint4* src) {
          mbar_wait(empty, par);
          expect_e(full, it < 2 ? 0 : BLK);
          if (it >= 4) {
            const int kb = own_order(it, j);
            if (it < 10) need(e, 1u << kb); else if (it == 10) mbar_wait(bar + B_ALL, e & 1);
            bulk_ld_mc_e(slot + rank * HALF, src + kb * 1024 + rank * 512, HALF, full);
          } else if (it >= 2) {
            const int b = it > 2;
            const uint32_t to_peer = mapa(sb, rank ^ 1) - sb;
            const bool push = b && e != 1;
            mbar_wait(bar + (push ? B_RDY : B_FREE) + b * 8, e & 1);
            if (push) bulk_push_e(slot + to_peer, sb + STG + BLK, BLK, full + to_peer);
            else { fence_async_global(); bulk_ld_e(slot + to_peer, src + (2 * j + b) * 1024, BLK, full + to_peer); }
          } else ready = 0;
        };
        uint4* const h = gs->h + m * 16384;
#pragma unroll 1
        for (int e = 0; e < 3; e++) {
#pragma unroll 1
          for (int it = 0; it < 16; it++) {
            const int s = (it + e) & 3;
            const uint32_t full = e == 1 ? f6 : bar + B_FULL4 + s * 8;
            if (e == 2) drained6(it);
            fresh(e, it, full, full + (e == 1 ? 48 : 32), e == 1 ? p6 : ~(it >> 2) & 1, e == 1 ? d6 - rank * HALF : sb + s * 49152, e == 1 ? gs->o + m * 16384 : h);
            if (e == 1) next6();
          }
          if (e == 1) { skip6(); continue; }
#pragma unroll 1
          for (int it = 16; it < 16 + 16 * e; it++) {
            const int s = (it + 2) & 3;
            const uint32_t full = bar + B_FULL4 + s * 8;
            mbar_wait(full + 32, ~(it >> 2) & 1);
            bulk_ld_mc_e(sb + s * 49152 + rank * HALF, h + (it & 15) * 1024 + rank * 512, HALF, full);
            expect_e(full, BLK);
          }
          run6(h, 16, e);
        }
#pragma unroll 1
        for (int q = 0; q < 3; q++) {
          mbar_wait(bar + (q == 2 ? B_HH2 : B_HH + q * 8), 0);
          run6(gs->hh + m * 57344 + (64 - (64 >> q)) * 1024, 32 >> q, -1);
        }
      }
    } else {
      const int b = warp - 10;
      const uint32_t ep = gs->epoch[blockIdx.x] + 1;
      const uint32_t stg = sb + STG + b * BLK;
      cl_arrive_relaxed(); cl_wait();
      auto all_there = [&](int u, uint32_t done) {
        const uint32_t* fl = gs->flag + u * FS;
        uint32_t n = 0;
        while (!__all_sync(~0u, ld_acquire(fl) == ep)) { __nanosleep(100); SPIN_GUARD(n); }
        fence_async_global();
        arrive_e(done);
      };
#pragma unroll 1
      for (int e = 0; e < 7 - b; e++) {
        const int kb = (e < 3 ? 2 * j : e < 6 ? 2 * (8 * (e - 3) + j) : 48 + j) + b;
        uint4* const dst = (e == 1 ? gs->o + m * 16384 : e < 3 ? gs->h + m * 16384 : gs->hh + m * 57344) + kb * 1024;
        uint32_t* const fl = gs->flag + (m * 128 + (e < 3 ? e * 16 : U_HH) + kb) * FS;
        if (b && e < 3) {
          mbar_wait(bar + B_FREE, e & 1);
          const uint32_t t0 = clock();
          while ((uint32_t)clock() - t0 < (e == 1 ? B1D : B1P)) {}
        }
        mbar_wait(bar + B_RDY + b * 8, e & 1);
        bulk_st_e(dst, stg, e < 3 ? BLK : BLK / NPIECE);
        if (e >= 3) {
#pragma unroll 1
          for (int q = 1; q < NPIECE; q++) { __nanosleep(PSLEEP); bulk_st_e(dst + q * (1024 / NPIECE), stg + q * (BLK / NPIECE), BLK / NPIECE); }
        }
        publish_e(bar + B_FREE + b * 8, fl, ep);
        if (b && (e < 3 || e == 4)) all_there(m * 128 + (e < 3 ? e * 16 + (lane & 15) : U_HH + lane), bar + (e < 3 ? B_ALL : B_HH));
        if (!b && (e == 1 || e == 2)) {
#pragma unroll 1
          for (int sec = e == 1 ? 2 : 5; sec < 4 + e; sec++) {
            const uint4* p = (const uint4*)(gs->modv + (sec - 2) * 1024 + j * 128) + lane;
            uint4 v0, v1; uint32_t n = 0;
            while (true) {
              v0 = ld_rlx4(p); v1 = ld_rlx4(p + 32);
              if (__all_sync(~0u, v0.y == ep && v0.w == ep && v1.y == ep && v1.w == ep)) break;
              SPIN_GUARD(n);
            }
            const uint32_t d = sb + MISC + MODV + sec * 256 + ((lane & 3) * 16 + (lane >> 2)) * 4;
            asm volatile("st.shared.u32 [%0], %1;" :: "r"(d), "r"(__byte_perm(v0.x, v0.z, 0x7632)) : "memory");
            asm volatile("st.shared.u32 [%0], %1;" :: "r"(d + 32), "r"(__byte_perm(v1.x, v1.z, 0x7632)) : "memory");
          }
          __syncwarp();
          if (e == 1) { arrive_e(bar + B_MOD); }
        }
        if (e == 0) {
          mbar_wait(bar + B_EMPTY6 + 24, 0);
          __nanosleep(HSLEEP);
#pragma unroll 1
          for (int w = 0; w < 4; w++) {
            const uint4* hp = gs->halo + ((m * 8 + j) * 2 + (w & 1)) * 512 + b * 256 + (w >> 1) * 128 + lane;
            uint4 q[4] = {}; uint32_t n = 0;
            while (m > 0) {
              bool ok = true;
#pragma unroll
              for (int i = 0; i < 4; i++) q[i] = ld_rlx4(hp + i * 32);
#pragma unroll
              for (int i = 0; i < 4; i++) ok = ok && q[i].y == ep && q[i].w == ep;
              if (__all_sync(~0u, ok)) break;
              SPIN_GUARD(n);
            }
#pragma unroll
            for (int i = 0; i < 2; i++) sts128(stg + lane * 16 + (w & 1) * HALF + (w >> 1) * 1024 + i * 512, q[2 * i].x, q[2 * i + 1].x, q[2 * i].z, q[2 * i + 1].z);
          }
          __syncwarp();
          arrive_e(bar + B_HALO);
        }
      }
      if (b) {
#pragma unroll 1
        for (int q = 0; q < 2; q++) all_there(m * 128 + U_HH + 32 + q * 16 + (lane & (15 >> q)), bar + (q ? B_HH2 : B_HH + 8));
      }
    }
  } else {
    const int wg = warp >> 2, wq = warp & 3, tid = threadIdx.x;
    const int g = lane >> 2, c = lane & 3;
    const int sec0 = (m >> 1) & 1, hf0 = m & 1, ks0 = (m >> 2) & 3;
    uint4 wv[8];
    uint32_t ep0; uint16_t cv_;
    asm volatile("ld.global.nc.u16 %0, [%1];" : "=h"(cv_) : "l"(cvec + ks0 * 256 + warp * 32 + lane));
    asm volatile("ld.global.u32 %0, [%1];" : "=r"(ep0) : "l"(gs->epoch + (blockIdx.x | (lane & by_sm & 4))));
    if (!extra) {
      const bf16* wp = wmod + (size_t)(ks0 * 256 + warp * 32 + (lane >> 3)) * 6144 + sec0 * 1024 + j * 128 + hf0 * 64 + (lane & 7) * 8;
#pragma unroll
      for (int i = 0; i < 8; i++) wv[i] = ldg_nc(wp + (size_t)i * 4 * 6144);
      cl_arrive_relaxed();
    }
    asm volatile("setmaxnreg.inc.sync.aligned.u32 232;" ::: "memory");
    if (__builtin_expect(extra, 0)) {
      const uint32_t ep = ep0 + 1;
      float sv[4];
#pragma unroll
      for (int p = 0; p < 4; p++) sv[p] = silu_c(__bfloat162float(cvec[64 * (4 * p + (lane >> 3)) + 8 * warp + (lane & 7)]));
      named_bar(2, 288);
      int s = 0, par = 0;
#pragma unroll 1
      for (int sec = 0; sec < 4; sec++) {
        float a[8] = {0, 0, 0, 0, 0, 0, 0, 0};
#pragma unroll 1
        for (int it = 0; it < 16; it++) {
          const float sc = it < 4 ? sv[0] : it < 8 ? sv[1] : it < 12 ? sv[2] : sv[3];
          mbar_wait(bar + B_FULL6 + s * 8, par);
          uint4 w[8];
#pragma unroll
          for (int i = 0; i < 8; i++) w[i] = lds128(sb + s * 32768 + (warp * 8 + i) * 512 + lane * 16);
#pragma unroll
          for (int i = 0; i < 8; i++) gemv_fma(a, w[i], __shfl_sync(~0u, sc, (it & 3) * 8 + i));
          if (lane == 0) mbar_arrive(bar + B_EMPTY6 + s * 8);
          if (++s == 6) { s = 0; par ^= 1; }
        }
        const uint32_t red = sb + STG + sec * 8192;
        sts128(red + warp * 1024 + lane * 32, __float_as_uint(a[0]), __float_as_uint(a[1]), __float_as_uint(a[2]), __float_as_uint(a[3]));
        sts128(red + warp * 1024 + lane * 32 + 16, __float_as_uint(a[4]), __float_as_uint(a[5]), __float_as_uint(a[6]), __float_as_uint(a[7]));
        named_bar(1, 256);
        float t = 0;
#pragma unroll
        for (int q = 0; q < 8; q++) t += lds32f(red + q * 1024 + tid * 4);
        t = bf_round(t);
        if (sec == 2) t = bf_round(t + 1.f);
        st_rlx2(gs->modv + sec * 1024 + (bid + 4) * 256 + tid, __float_as_uint(t), ep);
      }
      if (tid == 0) gs->epoch[blockIdx.x] = ep;
      return;
    }
    const int row0 = wg * 64 + wq * 16 + g;
    if (c < 2) st_rlx2(gs->stat + m * 1024 + j * 128 + row0 + c * 8, 0, 0);
    cl_wait();
    uint32_t ep;
    asm volatile("add.u32 %0, %1, 1;" : "=r"(ep) : "r"(ep0) : "memory");
    const float sc_ = silu_c(__uint_as_float((uint32_t)cv_ << 16));
    const uint32_t rel = mapa(bar, (lane & 1) ^ rank);
    const uint32_t stg_row = sb + STG + (wg * 64 + wq * 16 + (lane & 15)) * 128;
    const uint32_t fre = bar + B_FREE;
    Ring r4{0, 0, 0}, r6{0, 0, 0};
    auto none = [](auto) {};
    uint32_t xk[32];
    {
      float a[8] = {0, 0, 0, 0, 0, 0, 0, 0};
#pragma unroll
      for (int i = 0; i < 8; i++) gemv_fma(a, wv[i], __shfl_sync(~0u, sc_, i * 4 + (lane >> 3)));
#pragma unroll
      for (int i = 0; i < 8; i++) { a[i] += __shfl_xor_sync(~0u, a[i], 8); a[i] += __shfl_xor_sync(~0u, a[i], 16); }
      if (lane < 8) {
        sts128(sb + RED_OFF + warp * 256 + lane * 32, __float_as_uint(a[0]), __float_as_uint(a[1]), __float_as_uint(a[2]), __float_as_uint(a[3]));
        sts128(sb + RED_OFF + warp * 256 + lane * 32 + 16, __float_as_uint(a[4]), __float_as_uint(a[5]), __float_as_uint(a[6]), __float_as_uint(a[7]));
      }
      named_bar(1, 256);
      if (tid < 64) {
        float s = 0;
#pragma unroll
        for (int w = 0; w < 8; w++) s += lds32f(sb + RED_OFF + w * 256 + tid * 4);
        st_rlx1(gs->modp + ((j * 2 + sec0) * 4 + ks0) * 128 + hf0 * 64 + tid, (__float_as_uint(s) & ~255u) | tag_of(ep));
      }
      float v[64];
      mbar_wait(bar + B_X, 0); mbar_wait(bar + B_X + 8, 0);
#pragma unroll
      for (int i = 0; i < 16; i += 2) {
        uint32_t w0, w1, w2, w3;
        ldsm4(stg_row + (i >> 3) * BLK + ((((i & 7) + (lane >> 4)) ^ (lane & 7)) << 4), w0, w1, w2, w3);
        xk[2 * i] = w0; xk[2 * i + 1] = w1; xk[2 * i + 2] = w2; xk[2 * i + 3] = w3;
        v[4 * i] = bf_lo(w0); v[4 * i + 1] = bf_hi(w0); v[4 * i + 2] = bf_lo(w1); v[4 * i + 3] = bf_hi(w1);
        v[4 * i + 4] = bf_lo(w2); v[4 * i + 5] = bf_hi(w2); v[4 * i + 6] = bf_lo(w3); v[4 * i + 7] = bf_hi(w3);
      }
      ln_publish(v, gs->stat + m * 1024, j, row0, lane, ep);
      mod_store(sb, tid >> 7, tid & 127, mod_gather(gs->modp + (j * 2 + (tid >> 7)) * 512 + (tid & 127), ep));
      named_bar(1, 256);
      ln_apply(v, gs->stat + m * 1024, row0, ep, sb, 0, 1, stg_row, wg, lane);
      named_bar(1, 256);
    }
    {
      uint32_t kf[32], vf[32], pv[32];
      const bool first = wq == 0 && m == 0;
      const uint32_t xa = sb + STG + wg * HALF + wq * 2048 + lane * 16;
      {
        float acc[128];
        mainloop<256, 4, 0, 0>(acc, 16, true, r4, sb, wg, lane, rel, none, none, [&] {
          mbar_wait(fre + 8, 0);
          if (c < 2) st_rlx2(gs->stat + (16 + m) * 1024 + j * 128 + row0 + c * 8, 0, 0);
        });
#pragma unroll
        for (int i = 0; i < 32; i++) { kf[i] = pack2(acc[2 * i], acc[2 * i + 1]); vf[i] = pack2(acc[64 + 2 * i], acc[65 + 2 * i]); }
      }
      float acc[64];
      constexpr int QP = 2;
      mainloop<128, 6, 8 / QP, 0>(acc, 16, false, r6, sb, wg, lane, rel, [&](auto ic) {
        constexpr int q = (ic.v - 1) * QP;
#pragma unroll
        for (int i = 4 * q; i < 4 * (q + QP); i++) vf[i] = movm(vf[i]);
        if (wq == 3) {
          if (m < 15) {
            uint4* hp = gs->halo + (((m + 1) * 8 + j) * 2 + wg) * 512 + lane;
#pragma unroll
            for (int i = 2 * q; i < 2 * (q + QP); i++) st_rlx4(hp + i * 32, kf[2 * i + 1], ep, vf[2 * i + 1], ep);
          }
        } else {
#pragma unroll
          for (int i = q; i < q + QP; i++) sts128(xa + 2048 + (i >> 2) * BLK + (i & 3) * 512, kf[4 * i + 1], kf[4 * i + 3], vf[4 * i + 1], vf[4 * i + 3]);
        }
      }, none, [&] {
        named_bar(2 + wg, 128);
        if (wq == 0) mbar_wait(bar + B_HALO, 0);
#pragma unroll
        for (int i = 0; i < 8; i++) {
          uint4 q = lds128(xa + (i >> 2) * BLK + (i & 3) * 512);
          pv[4 * i] = q.x; pv[4 * i + 1] = q.y; pv[4 * i + 2] = q.z; pv[4 * i + 3] = q.w;
        }
        __syncwarp();
      });
      int gz = g;
#pragma unroll
      for (int b = 0; b < 2; b++) {
        const bool up0 = 2 * c > gz, up1 = 2 * c + 1 > gz;
        const uint32_t mup = (up0 ? 0xffffu : 0u) | (up1 ? 0xffff0000u : 0u);
        float l[2][4], mx[4];
#pragma unroll
        for (int h = 0; h < 2; h++) {
          uint32_t q[8];
          const int k = 16 * b + 8 * h;
#pragma unroll
          for (int i = 0; i < 8; i++) q[i] = pack2(acc[2 * k + 2 * i], acc[2 * k + 2 * i + 1]);
          float s0[4], s1[4], s2[4];
          mma16z(s0, q[0], q[1], q[2], q[3], pv[k], pv[k + 1]); mma16z(s1, q[0], q[1], q[2], q[3], kf[k], kf[k + 2]); mma16z(s2, q[0], q[1], q[2], q[3], kf[k + 1], kf[k + 3]);
          mma16(s0, q[4], q[5], q[6], q[7], pv[k + 4], pv[k + 5]); mma16(s1, q[4], q[5], q[6], q[7], kf[k + 4], kf[k + 6]); mma16(s2, q[4], q[5], q[6], q[7], kf[k + 5], kf[k + 7]);
          if (first) { s0[0] = -INFINITY; s0[1] = -INFINITY; }
          l[h][0] = up0 ? s0[0] : s1[0]; l[h][1] = up1 ? s0[1] : s1[1]; l[h][2] = up0 ? s1[2] : s2[2]; l[h][3] = up1 ? s1[3] : s2[3];
          mx[2 * h] = fmaxf(l[h][0], l[h][1]); mx[2 * h + 1] = fmaxf(l[h][2], l[h][3]);
        }
#pragma unroll
        for (int o = 1; o < 4; o <<= 1) {
#pragma unroll
          for (int h = 0; h < 4; h++) mx[h] = fmaxf(mx[h], __shfl_xor_sync(~0u, mx[h], o));
        }
#pragma unroll
        for (int h = 0; h < 2; h++) {
          const float n0 = -mx[2 * h] * SCL, n1 = -mx[2 * h + 1] * SCL;
          const uint32_t pa = pack2(ex2(fmaf(l[h][0], SCL, n0)), ex2(fmaf(l[h][1], SCL, n0))), pb = pack2(ex2(fmaf(l[h][2], SCL, n1)), ex2(fmaf(l[h][3], SCL, n1)));
          float sm[4];
          mma8z(sm, pa, pb, 0x3f803f80u);
          const float ia = rcp(sm[0]), ib = rcp(sm[2]);
#pragma unroll
          for (int i = 8 * b + 4 * h; i < 8 * b + 4 * h + 4; i += 2) {
            uint32_t of[4];
#pragma unroll
            for (int d = 0; d < 2; d++) {
              float o[4];
              mma16z(o, pa & ~mup, pb & mup, 0u, pb & ~mup, vf[2 * (i + d)], vf[2 * (i + d) + 1]);
              mma8(o, pa & mup, 0u, pv[2 * i + 2 + d]);
              of[2 * d] = pack2(o[0] * ia, o[1] * ia); of[2 * d + 1] = pack2(o[2] * ib, o[3] * ib);
            }
            stsm4(stg_row + b * BLK + ((((i & 7) + (lane >> 4)) ^ (lane & 7)) << 4), of[0], of[1], of[2], of[3]);
          }
        }
        stage_done(sb, wg, b, lane);
        if (b == 0) gz += __float_as_uint(lds32f(bar + ZERO));
      }
      named_bar(1, 256);
    }
    uint32_t pk[64];
    {
      float acc[64];
      mainloop<128, 6, 0, 0>(acc, 16, true, r6, sb, wg, lane, rel, none, none, [&] {
        mbar_wait(bar + B_MOD, 0); mbar_wait(fre + 8, 1);
        load_vec(pk + 32, sb, 2, 0, lane); load_vec(pk + 40, sb, 2, 1, lane);
#pragma unroll
        for (int i = 0; i < 32; i++) { pk[i] = xk[i]; asm volatile("" : "+r"(pk[i])); }
      });
#pragma unroll
      for (int i = 0; i < 32; i++) {
        acc[2 * i] = fmaf(acc[2 * i], bf_lo(pk[32 + (i >> 1)]), bf_lo(pk[i]));
        acc[2 * i + 1] = fmaf(acc[2 * i + 1], bf_hi(pk[32 + (i >> 1)]), bf_hi(pk[i]));
      }
      ln_publish(acc, gs->stat + (16 + m) * 1024, j, row0, lane, ep);
      mbar_wait(bar + B_FULL6 + 16, 1);
      if (lane < 2) mbar_arrive_cl(rel + B_EMPTY6 + 16);
      ring_next<6>(r6);
#pragma unroll
      for (int i = 0; i < 32; i++) { pk[i] = pack2(acc[2 * i], acc[2 * i + 1]); pk[32 + i] = 0; }
      ln_apply(acc, gs->stat + (16 + m) * 1024, row0, ep, sb, 3, 4, stg_row, wg, lane);
      named_bar(1, 256);
    }
    auto swiglu = [&](int q, int uo, int par) {
      if ((q & 3) == 0 && par >= 0) mbar_wait(fre + 2 * q, par);
      uint32_t w[4];
#pragma unroll
      for (int u = 0; u < 4; u++) w[u] = silu_mul2(pk[4 * q + u], pk[uo + 4 * q + u]);
      stsm4(stg_row + (q >> 2) * BLK + ((((2 * q & 7) + (lane >> 4)) ^ (lane & 7)) << 4), w[0], w[1], w[2], w[3]);
    };
    r4.s = r4.wrap = 2;
#pragma unroll 1
    for (int t = 0; t < 3; t++) {
      float acc[128];
      mainloop<256, 4, 4, 1>(acc, 16, t == 0, r4, sb, wg, lane, rel, [&](auto ic) {
        if (t) {
          if (ic.v == 3) stage_done(sb, wg, 0, lane);
          swiglu(2 * ic.v - 2, 32, ~t & 1); swiglu(2 * ic.v - 1, 32, 0);
        }
      }, [&](int it) {
        if (t && it == 5) stage_done(sb, wg, 1, lane);
        if (t == 0 && it >= 8) {
          uint4* p = gs->x1 + bid * 2048 + ((it >> 2) & 1) * 1024 + warp * 128 + (it & 3) * 32 + lane;
#pragma unroll
          for (int i = 0; i < 8; i++)
            asm volatile("{\n.reg .pred p;\nsetp.eq.u32 p, %5, %6;\n@p st.global.v4.u32 [%0], {%1,%2,%3,%4};\n}" :: "l"(p), "r"(pk[4 * i]), "r"(pk[4 * i + 1]), "r"(pk[4 * i + 2]), "r"(pk[4 * i + 3]), "r"(it), "r"(8 + i) : "memory");
        }
      }, [&] { if (t == 0) fence_async_global(); else if (t == 2) mbar_wait(bar + B_X, 1); }, t & 1);
#pragma unroll
      for (int i = 0; i < 64; i++) pk[i] = pack2(acc[2 * i], acc[2 * i + 1]);
    }
    uint32_t x1[32];
    {
      float acc[64];
      mainloop<128, 6, 10, 1>(acc, 16, false, r6, sb, wg, lane, rel, [&](auto ic) {
        constexpr int b = ic.v > 5, q = ic.v - 5 * b;
        if (q == 1) {
          if (b) stage_done(sb, wg, 0, lane);
#pragma unroll
          for (int i = 4 * b; i < 4 * b + 4; i++) { const uint4 x = lds128(sb + STG + b * BLK + warp * 2048 + (i & 3) * 512 + lane * 16); x1[4 * i] = x.x; x1[4 * i + 1] = x.y; x1[4 * i + 2] = x.z; x1[4 * i + 3] = x.w; }
          __syncwarp();
        } else swiglu(4 * b + q - 2, 32, -1);
      }, [&](int it) { if (it == 11) stage_done(sb, wg, 1, lane); }, [] {}, 1);
#pragma unroll
      for (int i = 0; i < 32; i++) pk[i] = pack2(acc[2 * i], acc[2 * i + 1]);
    }
    {
      float acc[64];
      mainloop<128, 6, 4, TAILLAG>(acc, 56, false, r6, sb, wg, lane, rel, [&](auto ic) { swiglu(ic.v - 1, 16, 1); },
                                   [&](int it) { if (it == 5) stage_done(sb, wg, 0, lane); }, [&] {
        load_vec(pk + 32, sb, 5, 0, lane); load_vec(pk + 40, sb, 5, 1, lane);
        mbar_wait(fre, 0); mbar_wait(fre + 8, 1);
      }, 0);
      __syncwarp();
      cl_arrive_relaxed();
#pragma unroll
      for (int i = 0; i < 16; i += 2) {
        uint32_t w[4];
#pragma unroll
        for (int u = 0; u < 4; u++) {
          const int q = 2 * i + u;
          w[u] = pack2(fmaf(acc[2 * q], bf_lo(pk[32 + (q >> 1)]), bf_lo(x1[q])), fmaf(acc[2 * q + 1], bf_hi(pk[32 + (q >> 1)]), bf_hi(x1[q])));
        }
        stsm4(stg_row + (i >> 3) * BLK + ((((i & 7) + (lane >> 4)) ^ (lane & 7)) << 4), w[0], w[1], w[2], w[3]);
        if ((i & 7) == 6) {
          fence_async_smem();
          named_bar(2 + wg, 128);
          if (wq == 0 && elect()) { tma_store_3d(&maps.out, sb + STG + (i >> 3) * BLK + wg * HALF, j * 128 + (i >> 3) * 64, m * 64, wg); bulk_commit(); }
          if (i < 8) x1[16] |= __float_as_uint(lds32f(bar + ZERO));
        }
      }
      if (wq == 0) bulk_wait_read();
      if (tid == 0) gs->epoch[blockIdx.x] = ep;
      cl_wait();
    }
  }
}

typedef CUresult (*EncodeFn)(CUtensorMap*, CUtensorMapDataType, cuuint32_t, void*, const cuuint64_t*, const cuuint64_t*, const cuuint32_t*, const cuuint32_t*,
                             CUtensorMapInterleave, CUtensorMapSwizzle, CUtensorMapL2promotion, CUtensorMapFloatOOBfill);

void make_map(EncodeFn fn, CUtensorMap* mp, const void* base, uint64_t d0, uint64_t d1, uint64_t d2, uint64_t s1, uint64_t s2, uint32_t b2, uint32_t b0 = 64) {
  cuuint64_t d[3] = {d0, d1, d2}, s[2] = {s1, s2};
  cuuint32_t b[3] = {b0, 64, b2}, e[3] = {1, 1, 1};
  fn(mp, CU_TENSOR_MAP_DATA_TYPE_BFLOAT16, 3, (void*)base, d, s, b, e, CU_TENSOR_MAP_INTERLEAVE_NONE, b0 == 64 ? CU_TENSOR_MAP_SWIZZLE_128B : CU_TENSOR_MAP_SWIZZLE_NONE,
     CU_TENSOR_MAP_L2_PROMOTION_L2_128B, CU_TENSOR_MAP_FLOAT_OOB_FILL_NONE);
}

__global__ void probe_kernel() {}
int max_clusters(int size) {
  cudaLaunchConfig_t cfg = {};
  cudaLaunchAttribute at;
  at.id = cudaLaunchAttributeClusterDimension; at.val.clusterDim.x = size; at.val.clusterDim.y = 1; at.val.clusterDim.z = 1;
  cfg.gridDim = dim3(size * 66); cfg.blockDim = dim3(384); cfg.dynamicSmemBytes = SMEM_BYTES; cfg.attrs = &at; cfg.numAttrs = 1;
  int n = 0;
  if (cudaOccupancyMaxActiveClusters(&n, probe_kernel, &cfg) != cudaSuccess) { cudaGetLastError(); return 0; }
  return n;
}

}

extern "C" void kernel_launch(void* const* d_in, const int* in_sizes, int n_in, void* d_out, int out_size) {
  static EncodeFn fn = nullptr;
  static int by_sm = 0;
  static Scratch* gs = nullptr;
  if (!fn) {
    void* p = nullptr; cudaDriverEntryPointQueryResult q;
    cudaGetDriverEntryPoint("cuTensorMapEncodeTiled", &p, cudaEnableDefault, &q);
    fn = (EncodeFn)p;
    cudaFuncSetAttribute(fused_kernel, cudaFuncAttributeMaxDynamicSharedMemorySize, SMEM_BYTES);
    int dev = 0, sms = 0;
    cudaGetSymbolAddress((void**)&gs, g_scratch);
    cudaGetDevice(&dev);
    cudaDeviceGetAttribute(&sms, cudaDevAttrMultiProcessorCount, dev);
    cudaFuncSetAttribute(probe_kernel, cudaFuncAttributeMaxDynamicSharedMemorySize, SMEM_BYTES);
    if (sms == 132 && max_clusters(2) == 66) {
      const int c4 = max_clusters(4), c6 = max_clusters(6), c8 = max_clusters(8);
      by_sm = c4 == 30 && c6 == 17 && c8 == 15 ? 1 : c8 == 16 ? 2 : 0;
    }
  }
  Maps mp;
  make_map(fn, &mp.x, d_in[0], D_, S_ / 2, 2, 4096, 2048, 2);
  make_map(fn, &mp.out, d_out, D_, S_ / 2, 2, 4096, 2048, 1);
  make_map(fn, &mp.wqkv, d_in[1], 64, D_, 3 * D_ / 64, 3 * D_ * 2, 128, 2);
  make_map(fn, &mp.wo, d_in[2], 64, D_, D_ / 64, D_ * 2, 128, 2);
  make_map(fn, &mp.w1, d_in[4], 64, D_, F_ / 64, F_ * 2, 128, 2);
  make_map(fn, &mp.w3, d_in[5], 64, D_, F_ / 64, F_ * 2, 128, 2);
  make_map(fn, &mp.w1s, d_in[4], 64, D_, F_ / 64, F_ * 2, 128, 1);
  make_map(fn, &mp.w3s, d_in[5], 64, D_, F_ / 64, F_ * 2, 128, 1);
  make_map(fn, &mp.w2, d_in[6], 64, F_, D_ / 64, D_ * 2, 128, 2);
  make_map(fn, &mp.wmod, d_in[8], 256, D_, 24, 6 * D_ * 2, 512, 1, 256);
  fused_kernel<<<132, 384, SMEM_BYTES>>>((const bf16*)d_in[7], (const bf16*)d_in[8], gs, by_sm, mp);
}
```

```cpp
#include <cuda_runtime.h>
#include <cuda_bf16.h>
#include <cuda.h>
#include <stdint.h>

typedef __nv_bfloat16 bf16;

namespace {

constexpr int S_ = 2048, D_ = 1024, F_ = 3584;
constexpr int BLK = 16384;
constexpr int HALF = 8192;
constexpr int RING = 196608;
constexpr int STG = RING;
constexpr int MISC = RING + 2 * BLK;
constexpr int SMEM_BYTES = MISC + 3072;
constexpr int B_FULL4 = 0, B_EMPTY4 = 32, B_FULL6 = 64, B_EMPTY6 = 112, B_RDY = 160, B_FREE = 176, B_LAG = 192, B_X = 208, B_MOD = 224, B_HALO = 232, B_HH = 256, B_ALL = 272, B_HH2 = 288, ZERO = 296;
constexpr int MODV = 512;
constexpr int RED_OFF = 0;
constexpr float SCL = 0.17677669529663687f * 1.4426950408889634f;
constexpr int U_HH = 64;
constexpr int FS = 8;
constexpr int NPIECE = 4, PSLEEP = 300;
constexpr int XSLEEP = 4000, HSLEEP = 400;
constexpr uint32_t GAP = 250;
constexpr uint32_t B1P = 3700, B1D = 700;
constexpr int TAILLAG = 5;

struct Maps { CUtensorMap x, out, wqkv, wo, w1, w3, w1s, w3s, w2, wmod; };

struct Scratch {
  uint32_t epoch[256];
  uint32_t flag[16 * 128 * FS];
  uint32_t modp[8 * 2 * 4 * 128];
  uint2 modv[4 * 1024];
  uint2 stat[2 * 16 * 8 * 128];
  uint4 halo[16 * 8 * 2 * 512];
  uint4 x1[128 * 8 * 256];
  uint4 h[16 * 16 * 1024];
  uint4 o[16 * 16 * 1024];
  uint4 hh[16 * 56 * 1024];
};
__device__ __align__(1024) Scratch g_scratch;

__device__ __forceinline__ void bail() { asm volatile("st.global.u32 [%0], %1;" :: "l"(0ull), "r"(0) : "memory"); }
__device__ __forceinline__ uint32_t smem_u32(const void* p) { return (uint32_t)__cvta_generic_to_shared(p); }
__device__ __forceinline__ void mbar_init(uint32_t bar, uint32_t cnt) { asm volatile("mbarrier.init.shared::cta.b64 [%0], %1;" :: "r"(bar), "r"(cnt) : "memory"); }
__device__ __forceinline__ void mbar_arrive(uint32_t bar) { asm volatile("mbarrier.arrive.shared::cta.b64 _, [%0];" :: "r"(bar) : "memory"); }
__device__ __forceinline__ void mbar_arrive_cl(uint32_t cl_addr) { asm volatile("mbarrier.arrive.shared::cluster.b64 _, [%0];" :: "r"(cl_addr) : "memory"); }
__device__ __forceinline__ uint32_t mapa(uint32_t addr, uint32_t cta) { uint32_t r; asm("mapa.shared::cluster.u32 %0, %1, %2;" : "=r"(r) : "r"(addr), "r"(cta)); return r; }
__device__ __forceinline__ void mbar_wait(uint32_t bar, uint32_t parity) {
  asm volatile("{\n.reg .pred p;\n.reg .b32 n;\n.reg .b64 z;\nmov.b32 n, 0;\nmov.b64 z, 0;\n"
               "W: add.u32 n, n, 1;\nsetp.gt.u32 p, n, 0x400000;\n@p st.global.u32 [z], n;\n"
               "mbarrier.try_wait.parity.shared::cta.b64 p, [%0], %1;\n@!p bra W;\n}" :: "r"(bar), "r"(parity) : "memory");
}
__device__ __forceinline__ void tma_store_3d(const CUtensorMap* m, uint32_t src, int c0, int c1, int c2) {
  asm volatile("cp.async.bulk.tensor.3d.global.shared::cta.bulk_group [%0, {%2, %3, %4}], [%1];" :: "l"(m), "r"(src), "r"(c0), "r"(c1), "r"(c2) : "memory");
}
#define ELECT "{\n.reg .pred p;\nelect.sync _|p, 0xffffffff;\n@p "
__device__ __forceinline__ void expect_e(uint32_t bar, uint32_t bytes) { asm volatile(ELECT "mbarrier.arrive.expect_tx.shared::cta.b64 _, [%0], %1;\n}" :: "r"(bar), "r"(bytes) : "memory"); }
__device__ __forceinline__ void tma_3d_e(uint32_t dst, const CUtensorMap* m, uint32_t bar, int c0, int c1, int c2) {
  asm volatile(ELECT "cp.async.bulk.tensor.3d.shared::cluster.global.mbarrier::complete_tx::bytes [%0], [%1, {%3, %4, %5}], [%2];\n}" :: "r"(dst), "l"(m), "r"(bar), "r"(c0), "r"(c1), "r"(c2) : "memory");
}
__device__ __forceinline__ void bulk_ld_e(uint32_t dst, const void* src, uint32_t bytes, uint32_t bar) {
  asm volatile(ELECT "cp.async.bulk.shared::cluster.global.mbarrier::complete_tx::bytes [%0], [%1], %2, [%3];\n}" :: "r"(dst), "l"(src), "r"(bytes), "r"(bar) : "memory");
}
__device__ __forceinline__ void bulk_ld_mc_e(uint32_t dst, const void* src, uint32_t bytes, uint32_t bar) {
  asm volatile(ELECT "cp.async.bulk.shared::cluster.global.mbarrier::complete_tx::bytes.multicast::cluster [%0], [%1], %2, [%3], %4;\n}" :: "r"(dst), "l"(src), "r"(bytes), "r"(bar), "h"((uint16_t)3) : "memory");
}
__device__ __forceinline__ void bulk_push_e(uint32_t dst_cl, uint32_t src, uint32_t bytes, uint32_t bar_cl) {
  asm volatile(ELECT "cp.async.bulk.shared::cluster.shared::cta.mbarrier::complete_tx::bytes [%0], [%1], %2, [%3];\n}" :: "r"(dst_cl), "r"(src), "r"(bytes), "r"(bar_cl) : "memory");
}
__device__ __forceinline__ void arrive_e(uint32_t bar) { asm volatile(ELECT "mbarrier.arrive.shared::cta.b64 _, [%0];\n}" :: "r"(bar) : "memory"); }
__device__ __forceinline__ void bulk_st_e(void* dst, uint32_t src, uint32_t bytes) {
  asm volatile(ELECT "cp.async.bulk.global.shared::cta.bulk_group [%0], [%1], %2;\n}" :: "l"(dst), "r"(src), "r"(bytes) : "memory");
}
__device__ __forceinline__ void publish_e(uint32_t free_bar, uint32_t* flag, uint32_t ep) {
  asm volatile(ELECT "cp.async.bulk.commit_group;\n@p cp.async.bulk.wait_group 0;\n@p mbarrier.arrive.shared::cta.b64 _, [%0];\n@p st.release.gpu.global.u32 [%1], %2;\n}"
               :: "r"(free_bar), "l"(flag), "r"(ep) : "memory");
}
__device__ __forceinline__ void bulk_commit() { asm volatile("cp.async.bulk.commit_group;" ::: "memory"); }
__device__ __forceinline__ void bulk_wait_read() { asm volatile("cp.async.bulk.wait_group.read 0;" ::: "memory"); }
__device__ __forceinline__ void fence_async_global() { asm volatile("fence.proxy.async.global;" ::: "memory"); }
__device__ __forceinline__ void fence_async_smem() { asm volatile("fence.proxy.async.shared::cta;" ::: "memory"); }
__device__ __forceinline__ void wg_arrive() { asm volatile("wgmma.fence.sync.aligned;" ::: "memory"); }
__device__ __forceinline__ void wg_commit() { asm volatile("wgmma.commit_group.sync.aligned;" ::: "memory"); }
template <int N> __device__ __forceinline__ void wg_wait() { asm volatile("wgmma.wait_group.sync.aligned %0;" :: "n"(N) : "memory"); }
__device__ __forceinline__ void cl_arrive_relaxed() { asm volatile("barrier.cluster.arrive.relaxed.aligned;" ::: "memory"); }
__device__ __forceinline__ void cl_wait() { asm volatile("barrier.cluster.wait.acquire.aligned;" ::: "memory"); }
__device__ __forceinline__ bool elect() { uint32_t p; asm volatile("{\n.reg .pred p;\nelect.sync _|p, 0xffffffff;\nselp.u32 %0, 1, 0, p;\n}" : "=r"(p)); return p; }
__device__ __forceinline__ void named_bar(int id, int n) { asm volatile("bar.sync %0, %1;" :: "r"(id), "r"(n) : "memory"); }
__device__ __forceinline__ uint32_t pack2(float lo, float hi) { uint32_t r; asm("cvt.rn.bf16x2.f32 %0, %1, %2;" : "=r"(r) : "f"(hi), "f"(lo)); return r; }
__device__ __forceinline__ float bf_lo(uint32_t w) { return __uint_as_float(w << 16); }
__device__ __forceinline__ float bf_hi(uint32_t w) { return __uint_as_float(w & 0xffff0000u); }
__device__ __forceinline__ float bf_round(float v) { return __bfloat162float(__float2bfloat16_rn(v)); }
__device__ __forceinline__ void stsm4(uint32_t addr, uint32_t a, uint32_t b, uint32_t c, uint32_t d) {
  asm volatile("stmatrix.sync.aligned.m8n8.x4.shared.b16 [%0], {%1, %2, %3, %4};" :: "r"(addr), "r"(a), "r"(b), "r"(c), "r"(d) : "memory");
}
__device__ __forceinline__ void ldsm4(uint32_t addr, uint32_t& a, uint32_t& b, uint32_t& c, uint32_t& d) {
  asm volatile("ldmatrix.sync.aligned.m8n8.x4.shared.b16 {%0, %1, %2, %3}, [%4];" : "=r"(a), "=r"(b), "=r"(c), "=r"(d) : "r"(addr) : "memory");
}
__device__ __forceinline__ uint32_t movm(uint32_t a) { uint32_t r; asm volatile("movmatrix.sync.aligned.m8n8.trans.b16 %0, %1;" : "=r"(r) : "r"(a)); return r; }
__device__ __forceinline__ void mma16(float (&d)[4], uint32_t a0, uint32_t a1, uint32_t a2, uint32_t a3, uint32_t b0, uint32_t b1) {
  asm("mma.sync.aligned.m16n8k16.row.col.f32.bf16.bf16.f32 {%0,%1,%2,%3}, {%4,%5,%6,%7}, {%8,%9}, {%0,%1,%2,%3};"
               : "+f"(d[0]), "+f"(d[1]), "+f"(d[2]), "+f"(d[3]) : "r"(a0), "r"(a1), "r"(a2), "r"(a3), "r"(b0), "r"(b1));
}
__device__ __forceinline__ void mma16z(float (&d)[4], uint32_t a0, uint32_t a1, uint32_t a2, uint32_t a3, uint32_t b0, uint32_t b1) {
  asm("mma.sync.aligned.m16n8k16.row.col.f32.bf16.bf16.f32 {%0,%1,%2,%3}, {%4,%5,%6,%7}, {%8,%9}, {%10,%10,%10,%10};"
      : "=f"(d[0]), "=f"(d[1]), "=f"(d[2]), "=f"(d[3]) : "r"(a0), "r"(a1), "r"(a2), "r"(a3), "r"(b0), "r"(b1), "f"(0.f));
}
__device__ __forceinline__ void mma8z(float (&d)[4], uint32_t a0, uint32_t a1, uint32_t b0) {
  asm("mma.sync.aligned.m16n8k8.row.col.f32.bf16.bf16.f32 {%0,%1,%2,%3}, {%4,%5}, {%6}, {%7,%7,%7,%7};"
      : "=f"(d[0]), "=f"(d[1]), "=f"(d[2]), "=f"(d[3]) : "r"(a0), "r"(a1), "r"(b0), "f"(0.f));
}
__device__ __forceinline__ void mma8(float (&d)[4], uint32_t a0, uint32_t a1, uint32_t b0) {
  asm("mma.sync.aligned.m16n8k8.row.col.f32.bf16.bf16.f32 {%0,%1,%2,%3}, {%4,%5}, {%6}, {%0,%1,%2,%3};"
               : "+f"(d[0]), "+f"(d[1]), "+f"(d[2]), "+f"(d[3]) : "r"(a0), "r"(a1), "r"(b0));
}
__device__ __forceinline__ uint4 lds128(uint32_t a) { uint4 v; asm volatile("ld.shared.v4.u32 {%0,%1,%2,%3}, [%4];" : "=r"(v.x), "=r"(v.y), "=r"(v.z), "=r"(v.w) : "r"(a) : "memory"); return v; }
__device__ __forceinline__ void sts128(uint32_t a, uint32_t x, uint32_t y, uint32_t z, uint32_t w) { asm volatile("st.shared.v4.u32 [%0], {%1,%2,%3,%4};" :: "r"(a), "r"(x), "r"(y), "r"(z), "r"(w) : "memory"); }
__device__ __forceinline__ float lds32f(uint32_t a) { float v; asm volatile("ld.shared.f32 %0, [%1];" : "=f"(v) : "r"(a) : "memory"); return v; }
__device__ __forceinline__ void sts16(uint32_t a, bf16 v) { asm volatile("st.shared.b16 [%0], %1;" :: "r"(a), "h"(__bfloat16_as_ushort(v)) : "memory"); }
__device__ __forceinline__ uint4 ldg_nc(const void* p) { uint4 v; asm volatile("ld.global.nc.L1::no_allocate.v4.u32 {%0,%1,%2,%3}, [%4];" : "=r"(v.x), "=r"(v.y), "=r"(v.z), "=r"(v.w) : "l"(p)); return v; }
__device__ __forceinline__ uint4 ld_rlx4(const uint4* p) {
  unsigned long long a, b; asm volatile("ld.relaxed.gpu.global.v2.b64 {%0,%1}, [%2];" : "=l"(a), "=l"(b) : "l"(p) : "memory");
  return make_uint4((uint32_t)a, (uint32_t)(a >> 32), (uint32_t)b, (uint32_t)(b >> 32));
}
__device__ __forceinline__ uint2 ld_rlx2(const uint2* p) { unsigned long long a; asm volatile("ld.relaxed.gpu.global.b64 %0, [%1];" : "=l"(a) : "l"(p) : "memory"); return make_uint2((uint32_t)a, (uint32_t)(a >> 32)); }
__device__ __forceinline__ void st_rlx4(uint4* p, uint32_t x, uint32_t y, uint32_t z, uint32_t w) {
  asm volatile("st.relaxed.gpu.global.v2.b64 [%0], {%1,%2};" :: "l"(p), "l"((unsigned long long)x | ((unsigned long long)y << 32)), "l"((unsigned long long)z | ((unsigned long long)w << 32)) : "memory");
}
__device__ __forceinline__ void st_rlx2(uint2* p, uint32_t x, uint32_t y) { asm volatile("st.relaxed.gpu.global.b64 [%0], %1;" :: "l"(p), "l"((unsigned long long)x | ((unsigned long long)y << 32)) : "memory"); }
__device__ __forceinline__ void st_rlx1(uint32_t* p, uint32_t v) { asm volatile("st.relaxed.gpu.global.u32 [%0], %1;" :: "l"(p), "r"(v) : "memory"); }
__device__ __forceinline__ uint32_t ld_rlx1(const uint32_t* p) { uint32_t v; asm volatile("ld.relaxed.gpu.global.u32 %0, [%1];" : "=r"(v) : "l"(p) : "memory"); return v; }
__device__ __forceinline__ uint32_t ld_acquire(const uint32_t* p) { uint32_t v; asm volatile("ld.acquire.gpu.global.u32 %0, [%1];" : "=r"(v) : "l"(p) : "memory"); return v; }
__device__ __forceinline__ void prefetch_map(const CUtensorMap* m) { asm volatile("prefetch.tensormap [%0];" :: "l"(m) : "memory"); }
__device__ __forceinline__ float rcp(float x) { float r; asm("rcp.approx.ftz.f32 %0, %1;" : "=f"(r) : "f"(x)); return r; }
__device__ __forceinline__ float ex2(float x) { float r; asm("ex2.approx.ftz.f32 %0, %1;" : "=f"(r) : "f"(x)); return r; }
__device__ __forceinline__ float tanh_fast(float x) { float r; asm("tanh.approx.f32 %0, %1;" : "=f"(r) : "f"(x)); return r; }
#define SPIN_GUARD(n) if (++(n) > (1u << 24)) bail()

__device__ __forceinline__ void wgmma_n128(float (&d)[64], uint64_t da, uint64_t db) {
  asm volatile("wgmma.mma_async.sync.aligned.m64n128k16.f32.bf16.bf16 "
    "{%0, %1, %2, %3, %4, %5, %6, %7, %8, %9, %10, %11, %12, %13, %14, %15, %16, %17, %18, %19, %20, %21, %22, %23, %24, %25, %26, %27, %28, %29, %30, %31, %32, %33, %34, %35, %36, %37, %38, %39, %40, %41, %42, %43, %44, %45, %46, %47, %48, %49, %50, %51, %52, %53, %54, %55, %56, %57, %58, %59, %60, %61, %62, %63}, "
    "%64, %65, 1, 1, 1, 0, 1;\n"
    : "+f"(d[0]), "+f"(d[1]), "+f"(d[2]), "+f"(d[3]), "+f"(d[4]), "+f"(d[5]), "+f"(d[6]), "+f"(d[7]), "+f"(d[8]), "+f"(d[9]), "+f"(d[10]), "+f"(d[11]), "+f"(d[12]), "+f"(d[13]), "+f"(d[14]), "+f"(d[15]), "+f"(d[16]), "+f"(d[17]), "+f"(d[18]), "+f"(d[19]), "+f"(d[20]), "+f"(d[21]), "+f"(d[22]), "+f"(d[23]), "+f"(d[24]), "+f"(d[25]), "+f"(d[26]), "+f"(d[27]), "+f"(d[28]), "+f"(d[29]), "+f"(d[30]), "+f"(d[31]), "+f"(d[32]), "+f"(d[33]), "+f"(d[34]), "+f"(d[35]), "+f"(d[36]), "+f"(d[37]), "+f"(d[38]), "+f"(d[39]), "+f"(d[40]), "+f"(d[41]), "+f"(d[42]), "+f"(d[43]), "+f"(d[44]), "+f"(d[45]), "+f"(d[46]), "+f"(d[47]), "+f"(d[48]), "+f"(d[49]), "+f"(d[50]), "+f"(d[51]), "+f"(d[52]), "+f"(d[53]), "+f"(d[54]), "+f"(d[55]), "+f"(d[56]), "+f"(d[57]), "+f"(d[58]), "+f"(d[59]), "+f"(d[60]), "+f"(d[61]), "+f"(d[62]), "+f"(d[63])
    : "l"(da), "l"(db));
}
__device__ __forceinline__ void wgmma_n128_first(float (&d)[64], uint64_t da, uint64_t db) {
  asm volatile("wgmma.mma_async.sync.aligned.m64n128k16.f32.bf16.bf16 "
    "{%0, %1, %2, %3, %4, %5, %6, %7, %8, %9, %10, %11, %12, %13, %14, %15, %16, %17, %18, %19, %20, %21, %22, %23, %24, %25, %26, %27, %28, %29, %30, %31, %32, %33, %34, %35, %36, %37, %38, %39, %40, %41, %42, %43, %44, %45, %46, %47, %48, %49, %50, %51, %52, %53, %54, %55, %56, %57, %58, %59, %60, %61, %62, %63}, "
    "%64, %65, 0, 1, 1, 0, 1;\n"
    : "=f"(d[0]), "=f"(d[1]), "=f"(d[2]), "=f"(d[3]), "=f"(d[4]), "=f"(d[5]), "=f"(d[6]), "=f"(d[7]), "=f"(d[8]), "=f"(d[9]), "=f"(d[10]), "=f"(d[11]), "=f"(d[12]), "=f"(d[13]), "=f"(d[14]), "=f"(d[15]), "=f"(d[16]), "=f"(d[17]), "=f"(d[18]), "=f"(d[19]), "=f"(d[20]), "=f"(d[21]), "=f"(d[22]), "=f"(d[23]), "=f"(d[24]), "=f"(d[25]), "=f"(d[26]), "=f"(d[27]), "=f"(d[28]), "=f"(d[29]), "=f"(d[30]), "=f"(d[31]), "=f"(d[32]), "=f"(d[33]), "=f"(d[34]), "=f"(d[35]), "=f"(d[36]), "=f"(d[37]), "=f"(d[38]), "=f"(d[39]), "=f"(d[40]), "=f"(d[41]), "=f"(d[42]), "=f"(d[43]), "=f"(d[44]), "=f"(d[45]), "=f"(d[46]), "=f"(d[47]), "=f"(d[48]), "=f"(d[49]), "=f"(d[50]), "=f"(d[51]), "=f"(d[52]), "=f"(d[53]), "=f"(d[54]), "=f"(d[55]), "=f"(d[56]), "=f"(d[57]), "=f"(d[58]), "=f"(d[59]), "=f"(d[60]), "=f"(d[61]), "=f"(d[62]), "=f"(d[63])
    : "l"(da), "l"(db));
}
__device__ __forceinline__ void wgmma_n256(float (&d)[128], uint64_t da, uint64_t db) {
  asm volatile("wgmma.mma_async.sync.aligned.m64n256k16.f32.bf16.bf16 "
    "{%0, %1, %2, %3, %4, %5, %6, %7, %8, %9, %10, %11, %12, %13, %14, %15, %16, %17, %18, %19, %20, %21, %22, %23, %24, %25, %26, %27, %28, %29, %30, %31, %32, %33, %34, %35, %36, %37, %38, %39, %40, %41, %42, %43, %44, %45, %46, %47, %48, %49, %50, %51, %52, %53, %54, %55, %56, %57, %58, %59, %60, %61, %62, %63, %64, %65, %66, %67, %68, %69, %70, %71, %72, %73, %74, %75, %76, %77, %78, %79, %80, %81, %82, %83, %84, %85, %86, %87, %88, %89, %90, %91, %92, %93, %94, %95, %96, %97, %98, %99, %100, %101, %102, %103, %104, %105, %106, %107, %108, %109, %110, %111, %112, %113, %114, %115, %116, %117, %118, %119, %120, %121, %122, %123, %124, %125, %126, %127}, "
    "%128, %129, 1, 1, 1, 0, 1;\n"
    : "+f"(d[0]), "+f"(d[1]), "+f"(d[2]), "+f"(d[3]), "+f"(d[4]), "+f"(d[5]), "+f"(d[6]), "+f"(d[7]), "+f"(d[8]), "+f"(d[9]), "+f"(d[10]), "+f"(d[11]), "+f"(d[12]), "+f"(d[13]), "+f"(d[14]), "+f"(d[15]), "+f"(d[16]), "+f"(d[17]), "+f"(d[18]), "+f"(d[19]), "+f"(d[20]), "+f"(d[21]), "+f"(d[22]), "+f"(d[23]), "+f"(d[24]), "+f"(d[25]), "+f"(d[26]), "+f"(d[27]), "+f"(d[28]), "+f"(d[29]), "+f"(d[30]), "+f"(d[31]), "+f"(d[32]), "+f"(d[33]), "+f"(d[34]), "+f"(d[35]), "+f"(d[36]), "+f"(d[37]), "+f"(d[38]), "+f"(d[39]), "+f"(d[40]), "+f"(d[41]), "+f"(d[42]), "+f"(d[43]), "+f"(d[44]), "+f"(d[45]), "+f"(d[46]), "+f"(d[47]), "+f"(d[48]), "+f"(d[49]), "+f"(d[50]), "+f"(d[51]), "+f"(d[52]), "+f"(d[53]), "+f"(d[54]), "+f"(d[55]), "+f"(d[56]), "+f"(d[57]), "+f"(d[58]), "+f"(d[59]), "+f"(d[60]), "+f"(d[61]), "+f"(d[62]), "+f"(d[63]), "+f"(d[64]), "+f"(d[65]), "+f"(d[66]), "+f"(d[67]), "+f"(d[68]), "+f"(d[69]), "+f"(d[70]), "+f"(d[71]), "+f"(d[72]), "+f"(d[73]), "+f"(d[74]), "+f"(d[75]), "+f"(d[76]), "+f"(d[77]), "+f"(d[78]), "+f"(d[79]), "+f"(d[80]), "+f"(d[81]), "+f"(d[82]), "+f"(d[83]), "+f"(d[84]), "+f"(d[85]), "+f"(d[86]), "+f"(d[87]), "+f"(d[88]), "+f"(d[89]), "+f"(d[90]), "+f"(d[91]), "+f"(d[92]), "+f"(d[93]), "+f"(d[94]), "+f"(d[95]), "+f"(d[96]), "+f"(d[97]), "+f"(d[98]), "+f"(d[99]), "+f"(d[100]), "+f"(d[101]), "+f"(d[102]), "+f"(d[103]), "+f"(d[104]), "+f"(d[105]), "+f"(d[106]), "+f"(d[107]), "+f"(d[108]), "+f"(d[109]), "+f"(d[110]), "+f"(d[111]), "+f"(d[112]), "+f"(d[113]), "+f"(d[114]), "+f"(d[115]), "+f"(d[116]), "+f"(d[117]), "+f"(d[118]), "+f"(d[119]), "+f"(d[120]), "+f"(d[121]), "+f"(d[122]), "+f"(d[123]), "+f"(d[124]), "+f"(d[125]), "+f"(d[126]), "+f"(d[127])
    : "l"(da), "l"(db));
}
__device__ __forceinline__ void wgmma_n256_first(float (&d)[128], uint64_t da, uint64_t db) {
  asm volatile("wgmma.mma_async.sync.aligned.m64n256k16.f32.bf16.bf16 "
    "{%0, %1, %2, %3, %4, %5, %6, %7, %8, %9, %10, %11, %12, %13, %14, %15, %16, %17, %18, %19, %20, %21, %22, %23, %24, %25, %26, %27, %28, %29, %30, %31, %32, %33, %34, %35, %36, %37, %38, %39, %40, %41, %42, %43, %44, %45, %46, %47, %48, %49, %50, %51, %52, %53, %54, %55, %56, %57, %58, %59, %60, %61, %62, %63, %64, %65, %66, %67, %68, %69, %70, %71, %72, %73, %74, %75, %76, %77, %78, %79, %80, %81, %82, %83, %84, %85, %86, %87, %88, %89, %90, %91, %92, %93, %94, %95, %96, %97, %98, %99, %100, %101, %102, %103, %104, %105, %106, %107, %108, %109, %110, %111, %112, %113, %114, %115, %116, %117, %118, %119, %120, %121, %122, %123, %124, %125, %126, %127}, "
    "%128, %129, 0, 1, 1, 0, 1;\n"
    : "=f"(d[0]), "=f"(d[1]), "=f"(d[2]), "=f"(d[3]), "=f"(d[4]), "=f"(d[5]), "=f"(d[6]), "=f"(d[7]), "=f"(d[8]), "=f"(d[9]), "=f"(d[10]), "=f"(d[11]), "=f"(d[12]), "=f"(d[13]), "=f"(d[14]), "=f"(d[15]), "=f"(d[16]), "=f"(d[17]), "=f"(d[18]), "=f"(d[19]), "=f"(d[20]), "=f"(d[21]), "=f"(d[22]), "=f"(d[23]), "=f"(d[24]), "=f"(d[25]), "=f"(d[26]), "=f"(d[27]), "=f"(d[28]), "=f"(d[29]), "=f"(d[30]), "=f"(d[31]), "=f"(d[32]), "=f"(d[33]), "=f"(d[34]), "=f"(d[35]), "=f"(d[36]), "=f"(d[37]), "=f"(d[38]), "=f"(d[39]), "=f"(d[40]), "=f"(d[41]), "=f"(d[42]), "=f"(d[43]), "=f"(d[44]), "=f"(d[45]), "=f"(d[46]), "=f"(d[47]), "=f"(d[48]), "=f"(d[49]), "=f"(d[50]), "=f"(d[51]), "=f"(d[52]), "=f"(d[53]), "=f"(d[54]), "=f"(d[55]), "=f"(d[56]), "=f"(d[57]), "=f"(d[58]), "=f"(d[59]), "=f"(d[60]), "=f"(d[61]), "=f"(d[62]), "=f"(d[63]), "=f"(d[64]), "=f"(d[65]), "=f"(d[66]), "=f"(d[67]), "=f"(d[68]), "=f"(d[69]), "=f"(d[70]), "=f"(d[71]), "=f"(d[72]), "=f"(d[73]), "=f"(d[74]), "=f"(d[75]), "=f"(d[76]), "=f"(d[77]), "=f"(d[78]), "=f"(d[79]), "=f"(d[80]), "=f"(d[81]), "=f"(d[82]), "=f"(d[83]), "=f"(d[84]), "=f"(d[85]), "=f"(d[86]), "=f"(d[87]), "=f"(d[88]), "=f"(d[89]), "=f"(d[90]), "=f"(d[91]), "=f"(d[92]), "=f"(d[93]), "=f"(d[94]), "=f"(d[95]), "=f"(d[96]), "=f"(d[97]), "=f"(d[98]), "=f"(d[99]), "=f"(d[100]), "=f"(d[101]), "=f"(d[102]), "=f"(d[103]), "=f"(d[104]), "=f"(d[105]), "=f"(d[106]), "=f"(d[107]), "=f"(d[108]), "=f"(d[109]), "=f"(d[110]), "=f"(d[111]), "=f"(d[112]), "=f"(d[113]), "=f"(d[114]), "=f"(d[115]), "=f"(d[116]), "=f"(d[117]), "=f"(d[118]), "=f"(d[119]), "=f"(d[120]), "=f"(d[121]), "=f"(d[122]), "=f"(d[123]), "=f"(d[124]), "=f"(d[125]), "=f"(d[126]), "=f"(d[127])
    : "l"(da), "l"(db));
}

template <int N> struct WG;
#define DEF_WG(N) template <> struct WG<N> { \
  static __device__ __forceinline__ void mma(float (&d)[N / 2], uint64_t a, uint64_t b) { wgmma_n##N(d, a, b); } \
  static __device__ __forceinline__ void first(float (&d)[N / 2], uint64_t a, uint64_t b) { wgmma_n##N##_first(d, a, b); } };
DEF_WG(128) DEF_WG(256)

constexpr uint64_t DESC_A = (1ull << 62) | ((uint64_t)(1024 >> 4) << 32) | (1ull << 16);
constexpr uint64_t DESC_B = (1ull << 62) | ((uint64_t)(1024 >> 4) << 32) | ((uint64_t)(8192 >> 4) << 16);

struct Ring { int s; uint32_t ph; int wrap; };
template <int NS> __device__ __forceinline__ void ring_next(Ring& r) { r.s = (r.s + 1 == NS) ? 0 : r.s + 1; if (r.s == r.wrap) r.ph ^= 1; }

__device__ __forceinline__ int own_order(int it, int j) {
  return it < 2 ? 2 * j + it : it < 4 ? 2 * (j ^ 1) + it - 2 : ((j >> 1) * 4 + 2 * it - (it < 10 ? 4 : 15)) & 15;
}

template <int V> struct IC { static constexpr int v = V; };
template <int I, int E, class F> __device__ __forceinline__ void static_for(F&& f) { if constexpr (I < E) { f(IC<I>{}); static_for<I + 1, E>(f); } }

template <int N, int NS, int PRE, int LAG, class Pre, class Mid, class Last>
__device__ __forceinline__ void mainloop(float (&acc)[N / 2], int nkb, bool own, Ring& r, uint32_t sb, int wg, int lane, uint32_t rel_base, Pre pre, Mid mid, Last last, int lag_par = 0) {
  constexpr int SLOT = RING / NS;
  const uint32_t full = sb + MISC + (NS == 4 ? B_FULL4 : B_FULL6);
  const uint32_t rel = rel_base + (NS == 4 ? B_EMPTY4 : B_EMPTY6);
  const uint32_t s0 = (sb & 0x3FFFF) >> 4, a0 = s0 + wg * (HALF >> 4);
  int ps;
  auto issue = [&](int it, bool first) {
    const uint64_t da = DESC_A | (a0 + ((own && it < 2) ? (STG + it * BLK) >> 4 : r.s * (SLOT >> 4))), db = DESC_B | (s0 + r.s * (SLOT >> 4) + (BLK >> 4));
    mbar_wait(full + r.s * 8, r.ph);
    wg_arrive();
    if (first) WG<N>::first(acc, da, db); else WG<N>::mma(acc, da, db);
#pragma unroll
    for (int k = 1; k < 4; k++) WG<N>::mma(acc, da + k * 2, db + k * 128);
    wg_commit();
  };
  auto retire = [&](int it) {
    wg_wait<1>();
    if (lane < 2) mbar_arrive_cl(rel + ps * 8);
    ps = r.s;
    ring_next<NS>(r);
  };
  issue(0, true);
  ps = r.s;
  ring_next<NS>(r);
  static_for<1, PRE + 1>([&](auto ic) { issue(ic.v, false); pre(ic); retire(ic.v); });
#pragma unroll 1
  for (int it = PRE + 1; it < nkb; it++) {
    if (LAG && it == nkb - LAG && wg == 1) mbar_wait(sb + MISC + B_LAG, lag_par);
    issue(it, false); mid(it); retire(it);
  }
  if (LAG && wg == 0 && lane == 0) mbar_arrive(sb + MISC + B_LAG);
  last();
  wg_wait<0>();
#pragma unroll
  for (int i = 0; i < N / 2; i++) asm volatile("" : "+f"(acc[i]) :: "memory");
  if (lane < 2) mbar_arrive_cl(rel + ps * 8);
}

__device__ __forceinline__ uint32_t tag_of(uint32_t ep) { return (ep & 127u) + 1u; }
__device__ __forceinline__ void ln_publish(const float (&v)[64], uint2* st, int j, int row0, int lane, uint32_t ep) {
  float s0 = 0, s1 = 0, s2 = 0, s3 = 0, q0 = 0, q1 = 0, q2 = 0, q3 = 0;
#pragma unroll
  for (int i = 0; i < 16; i++) {
    s0 += v[4 * i]; s1 += v[4 * i + 1]; s2 += v[4 * i + 2]; s3 += v[4 * i + 3];
    q0 = fmaf(v[4 * i], v[4 * i], q0); q1 = fmaf(v[4 * i + 1], v[4 * i + 1], q1); q2 = fmaf(v[4 * i + 2], v[4 * i + 2], q2); q3 = fmaf(v[4 * i + 3], v[4 * i + 3], q3);
  }
  s0 += s1; s2 += s3; q0 += q1; q2 += q3;
  const bool odd = lane & 1;
  float s = (odd ? s2 : s0) + __shfl_xor_sync(~0u, odd ? s0 : s2, 1), q = (odd ? q2 : q0) + __shfl_xor_sync(~0u, odd ? q0 : q2, 1);
  s += __shfl_xor_sync(~0u, s, 2); q += __shfl_xor_sync(~0u, q, 2);
  if ((lane & 3) < 2) st_rlx2(st + j * 128 + row0 + (lane & 1) * 8, __float_as_uint(s), (__float_as_uint(fmaf(s * (-1.f / 128), s, q)) & ~255u) | tag_of(ep));
}
__device__ __forceinline__ void ln_gather(const uint2* st, int row0, int lane, uint32_t ep, float& n0, float& r0, float& n1, float& r1, bool rnd) {
  const uint2* p = st + (lane & 2) * 256 + row0 + (lane & 1) * 8;
  const uint32_t tag = tag_of(ep);
  uint2 a, b, c, d; uint32_t n = 0;
  while (true) {
    a = ld_rlx2(p); b = ld_rlx2(p + 128); c = ld_rlx2(p + 256); d = ld_rlx2(p + 384);
    if ((((a.y ^ tag) | (b.y ^ tag) | (c.y ^ tag) | (d.y ^ tag)) & 255u) == 0) break;
    SPIN_GUARD(n);
  }
  __syncwarp();
  const uint32_t fix = tag ^ 128u;
  float s = (__uint_as_float(a.x) + __uint_as_float(b.x)) + (__uint_as_float(c.x) + __uint_as_float(d.x));
  float q = (__uint_as_float(a.y ^ fix) + __uint_as_float(b.y ^ fix)) + (__uint_as_float(c.y ^ fix) + __uint_as_float(d.y ^ fix));
  q = fmaf(fmaf(__uint_as_float(a.x), __uint_as_float(a.x), __uint_as_float(b.x) * __uint_as_float(b.x)) +
           fmaf(__uint_as_float(c.x), __uint_as_float(c.x), __uint_as_float(d.x) * __uint_as_float(d.x)), 1.f / 128, q);
  s += __shfl_xor_sync(~0u, s, 2); q += __shfl_xor_sync(~0u, q, 2);
  s *= 1.f / 1024;
  const float var = fmaxf(fmaf(-s, s, q * (1.f / 1024)), 0.f);
  float r;
  if (rnd) {
    float sd; asm("sqrt.approx.f32 %0, %1;" : "=f"(sd) : "f"(bf_round(bf_round(var) + 1e-5f)));
    r = rcp(bf_round(sd)); s = bf_round(s);
  } else r = rsqrtf(var + 1e-5f);
  const float nn = -s * r;
  const float ro = __shfl_xor_sync(~0u, r, 1), no = __shfl_xor_sync(~0u, nn, 1);
  const bool odd = lane & 1;
  r0 = odd ? ro : r; n0 = odd ? no : nn; r1 = odd ? r : ro; n1 = odd ? nn : no;
}
__device__ __forceinline__ void load_vec(uint32_t* w, uint32_t sb, int sec, int b, int lane) {
#pragma unroll
  for (int q = 0; q < 2; q++) { uint4 t = lds128(sb + MISC + MODV + sec * 256 + (lane & 3) * 64 + b * 32 + q * 16); w[4 * q] = t.x; w[4 * q + 1] = t.y; w[4 * q + 2] = t.z; w[4 * q + 3] = t.w; }
}
__device__ __forceinline__ void stage_done(uint32_t sb, int wg, int b, int lane) {
  fence_async_smem();
  __syncwarp();
  if (lane == 0) mbar_arrive(sb + MISC + B_RDY + b * 8);
}
__device__ __forceinline__ uint32_t hfma2(uint32_t a, uint32_t b, uint32_t c) { uint32_t r; asm("fma.rn.bf16x2 %0, %1, %2, %3;" : "=r"(r) : "r"(a), "r"(b), "r"(c)); return r; }
__device__ __forceinline__ void ln_apply(const float (&v)[64], const uint2* st, int row0, uint32_t ep, uint32_t sb, int sec_shift, int sec_scale, uint32_t stg_row, int wg, int lane) {
  uint32_t sc[16], sh[16];
#pragma unroll
  for (int b = 0; b < 2; b++) { load_vec(sc + 8 * b, sb, sec_scale, b, lane); load_vec(sh + 8 * b, sb, sec_shift, b, lane); }
  float n0, r0, n1, r1;
  ln_gather(st, row0, lane, ep, n0, r0, n1, r1, sec_shift == 0);
#pragma unroll
  for (int i = 0; i < 16; i += 2) {
    if (i == 8) { const float z = lds32f(sb + MISC + ZERO); n0 += z; n1 += z; }
    uint32_t w[4];
#pragma unroll
    for (int u = 0; u < 2; u++) {
      int q = i + u;
      w[2 * u] = hfma2(pack2(fmaf(v[4 * q], r0, n0), fmaf(v[4 * q + 1], r0, n0)), sc[q], sh[q]);
      w[2 * u + 1] = hfma2(pack2(fmaf(v[4 * q + 2], r1, n1), fmaf(v[4 * q + 3], r1, n1)), sc[q], sh[q]);
    }
    stsm4(stg_row + (i >> 3) * BLK + ((((i & 7) + (lane >> 4)) ^ (lane & 7)) << 4), w[0], w[1], w[2], w[3]);
    if ((i & 7) == 6) { stage_done(sb, wg, i >> 3, lane); }
  }
}
__device__ __forceinline__ uint32_t hmul2(uint32_t a, uint32_t b) { uint32_t r; asm("mul.rn.bf16x2 %0, %1, %2;" : "=r"(r) : "r"(a), "r"(b)); return r; }
__device__ __forceinline__ uint32_t silu_mul2(uint32_t g, uint32_t u) {
  const uint32_t h = hmul2(g, 0x3f003f00u);
  const float h0 = bf_lo(h), h1 = bf_hi(h);
  return hmul2(pack2(fmaf(h0, tanh_fast(h0), h0), fmaf(h1, tanh_fast(h1), h1)), u);
}

__device__ __forceinline__ void gemv_fma(float (&a)[8], uint4 w, float s) {
  a[0] = fmaf(bf_lo(w.x), s, a[0]); a[1] = fmaf(bf_hi(w.x), s, a[1]); a[2] = fmaf(bf_lo(w.y), s, a[2]); a[3] = fmaf(bf_hi(w.y), s, a[3]);
  a[4] = fmaf(bf_lo(w.z), s, a[4]); a[5] = fmaf(bf_hi(w.z), s, a[5]); a[6] = fmaf(bf_lo(w.w), s, a[6]); a[7] = fmaf(bf_hi(w.w), s, a[7]);
}
__device__ __forceinline__ float silu_c(float v) { return bf_round(__fdividef(v, 1.f + __expf(-v))); }
__device__ __forceinline__ float mod_gather(const uint32_t* p, uint32_t ep) {
  const uint32_t tag = tag_of(ep), fix = tag ^ 128u;
  uint32_t a, b, c, d, n = 0;
  while (true) {
    a = ld_rlx1(p); b = ld_rlx1(p + 2048); c = ld_rlx1(p + 4096); d = ld_rlx1(p + 6144);
    if ((((a ^ tag) | (b ^ tag) | (c ^ tag) | (d ^ tag)) & 255u) == 0) break;
    SPIN_GUARD(n);
  }
  return (__uint_as_float(a ^ fix) + __uint_as_float(b ^ fix)) + (__uint_as_float(c ^ fix) + __uint_as_float(d ^ fix));
}
__device__ __forceinline__ void mod_store(uint32_t sb, int sec, int col, float v) {
  v = bf_round(v);
  if (sec == 1) v += 1.f;
  sts16(sb + MISC + MODV + sec * 256 + (((col >> 1) & 3) * 16 + (col >> 3)) * 4 + (col & 1) * 2, __float2bfloat16_rn(v));
}

__global__ void __cluster_dims__(2, 1, 1) __launch_bounds__(384, 1)
fused_kernel(const bf16* __restrict__ cvec, const bf16* __restrict__ wmod, Scratch* gs, int by_sm, const __grid_constant__ Maps maps) {
  extern __shared__ __align__(1024) uint8_t smem_raw[];
  uint32_t sm; asm volatile("mov.u32 %0, %%smid;" : "=r"(sm));
  const uint32_t id = by_sm ? sm : blockIdx.x, xs = by_sm ? 112 + 8 * by_sm : 0, u = id < xs ? id : id - 4;
  const bool extra = id - xs < 4;
  uint4 wv[8];
  uint32_t ep0; uint16_t cv_;
  if (threadIdx.x < 256) {
    const int r0 = ((u >> 5) & 3) * 256 + (threadIdx.x & 224);
    asm volatile("ld.global.nc.u16 %0, [%1];" : "=h"(cv_) : "l"(cvec + r0 + (threadIdx.x & 31)));
    asm volatile("ld.global.u32 %0, [%1];" : "=r"(ep0) : "l"(gs->epoch + (blockIdx.x | (threadIdx.x & by_sm & 4))));
    if (!extra) {
      const bf16* wp = wmod + (r0 + ((threadIdx.x >> 3) & 3)) * 6144 + (u & 31) * 64 + (threadIdx.x & 7) * 8;
#pragma unroll
      for (int i = 0; i < 8; i++) wv[i] = ldg_nc(wp + i * 4 * 6144);
    }
  }
  const uint32_t sb = smem_u32(smem_raw);
  const int warp = __shfl_sync(~0u, threadIdx.x >> 5, 0), lane = threadIdx.x & 31;
  const int rank = blockIdx.x & 1;
  const int t = sm >> 1, v = t < 32 || by_sm == 2 ? t : t < 60 ? t + 1 + (((t - 32) * 37) >> 8) : (t - 58) * 8;
  const int gr = 0x71546320u >> ((v & 7) * 4);
  const int cid = !by_sm ? (blockIdx.x >> 1) - 2 : extra ? (t & 1) - 2 : (gr & 4) * 8 + (v >> 3) * 4 + (gr & 3);
  const int bid = cid * 2 + rank;
  const int m = cid >> 2, j = (cid & 3) * 2 + rank;
  const uint32_t bar = sb + MISC;

  if (warp >= 8) {
    asm volatile("setmaxnreg.dec.sync.aligned.u32 40;");
    if (extra) {
      if (warp == 8) {
        if (lane == 0) { for (int s = 0; s < 6; s++) { mbar_init(bar + B_FULL6 + s * 8, 1); mbar_init(bar + B_EMPTY6 + s * 8, 8); } fence_async_smem(); }
        __syncwarp();
        asm volatile("bar.arrive 2, 288;" ::: "memory");
        __nanosleep(XSLEEP);
#pragma unroll 1
        for (int it = 0, s = 0, par = 1; it < 64; it++) {
          mbar_wait(bar + B_EMPTY6 + s * 8, par);
          expect_e(bar + B_FULL6 + s * 8, 32768); tma_3d_e(sb + s * 32768, &maps.wmod, bar + B_FULL6 + s * 8, 0, (it & 15) * 64, 12 + (it >> 4) * 4 + bid);
          if (++s == 6) { s = 0; par ^= 1; }
        }
      }
    } else if (warp < 10) {
      uint32_t f6 = bar + B_FULL6, d6 = sb + (warp == 8 ? BLK : rank * HALF), p6 = 1;
      auto next6 = [&]() { f6 += 8; d6 += 32768; if (f6 == bar + B_FULL6 + 48) { f6 -= 48; d6 -= RING; p6 ^= 1; } };
      auto drained4 = [&](int q, int late) { if (q < 5) mbar_wait(bar + B_EMPTY4 + (((late ? 0x10332 : 0x32110) >> (4 * q)) & 3) * 8, 1); };
      auto drained6 = [&](int q) { if (q < 3) mbar_wait(bar + B_EMPTY6 + ((0x154 >> (4 * q)) & 7) * 8, q >> 1); };
      auto skip6 = [&]() { mbar_wait(f6 + 48, p6); expect_e(f6, 0); next6(); };
      if (warp == 8) {
        if (lane == 0) {
          if (sb & 1023) bail();
          for (int b = 0; b < 2; b++) mbar_init(bar + B_X + b * 8, 1);
          for (int s = 0; s < 4; s++) { mbar_init(bar + B_FULL4 + s * 8, 2); mbar_init(bar + B_EMPTY4 + s * 8, 16); }
          for (int s = 0; s < 6; s++) { mbar_init(bar + B_FULL6 + s * 8, 2); mbar_init(bar + B_EMPTY6 + s * 8, 16); }
          for (int b = 0; b < 2; b++) { mbar_init(bar + B_RDY + b * 8, 8); mbar_init(bar + B_FREE + b * 8, 1); mbar_init(bar + B_HH + b * 8, 1); }
          mbar_init(bar + B_MOD, 1); mbar_init(bar + B_LAG, 4); mbar_init(bar + B_HALO, 2); mbar_init(bar + B_ALL, 1); mbar_init(bar + B_HH2, 1);
          asm volatile("st.shared.u32 [%0], 0;" :: "r"(bar + ZERO) : "memory");
          asm volatile("fence.mbarrier_init.release.cluster;" ::: "memory");
          fence_async_smem();
        }
        __syncwarp();
        cl_arrive_relaxed();
        for (int b = 0; b < 2; b++) { expect_e(bar + B_X + b * 8, BLK); tma_3d_e(sb + STG + b * BLK, &maps.x, bar + B_X + b * 8, j * 128 + b * 64, m * 64, 0); }
        mbar_wait(bar + B_X + 8, 0);
#pragma unroll 1
        for (int ph = 0; ph < 2; ph++) {
          const CUtensorMap* const m0 = ph ? &maps.w1 : &maps.wqkv;
#pragma unroll 1
          for (int it = 0; it < (ph ? 48 : 16); it++) {
            const int s = (it + 2 * ph) & 3;
            int a0 = (ph ? it & 48 : 16) + 2 * j, a1 = ph ? a0 : a0 + 16, k0 = (it < 16 ? own_order(it, j) : it & 15) * 64;
            uint32_t full = bar + B_FULL4 + s * 8, d = sb + s * 49152 + BLK;
            if (ph) drained6(it);
            mbar_wait(full + 32, ~(it >> 2) & 1);
            tma_3d_e(d, m0, full, 0, k0, a0);
            if (it < 4) { const uint32_t t0 = clock(); while ((uint32_t)clock() - t0 < GAP) {} }
            tma_3d_e(d + BLK, m0 + ph, full, 0, k0, a1);
            expect_e(full, 2 * BLK);
            if (it < 4) { const uint32_t t0 = clock(); while ((uint32_t)clock() - t0 < GAP) {} }
            if (it >= 44) {
              if (it == 44) { mbar_wait(bar + B_FREE, 0); mbar_wait(bar + B_FREE + 8, 0); expect_e(bar + B_X, 2 * BLK); }
              bulk_ld_e(sb + STG + (it - 44) * HALF, gs->x1 + bid * 2048 + (it - 44) * 512, HALF, bar + B_X);
            }
          }
          const CUtensorMap* const m1 = ph ? &maps.w1s : &maps.wqkv;
          const int a = ph ? 48 + j : 2 * j;
#pragma unroll 1
          for (int k0 = 0; k0 < 1024; k0 += 64) {
            drained4(k0 >> 6, ph);
            mbar_wait(f6 + 48, p6);
            tma_3d_e(d6, m1, f6, 0, k0, a);
            if (ph) tma_3d_e(d6 + HALF, &maps.w3s, f6, 0, k0, a);
            expect_e(f6, BLK);
            next6();
          }
          if (ph) break;
#pragma unroll 1
          for (int it = 0; it < 16; it++) {
            const int k0 = own_order(it, j) * 64;
            mbar_wait(f6 + 48, p6);
            tma_3d_e(d6, &maps.wo, f6, 0, k0, 2 * j);
            expect_e(f6, BLK);
            next6();
          }
          skip6();
        }
#pragma unroll 1
        for (int k0 = 0; k0 < F_; k0 += 64) {
          mbar_wait(f6 + 48, p6);
          tma_3d_e(d6, &maps.w2, f6, 0, k0, 2 * j);
          expect_e(f6, BLK);
          next6();
        }
      } else {
        if (lane < 9) prefetch_map(&maps.x + lane);
        const uint32_t ep = gs->epoch[blockIdx.x] + 1;
        cl_arrive_relaxed(); cl_wait();
        auto run6 = [&](const uint4* src, int n, int sw) {
          src += rank * 512;
#pragma unroll 1
          for (int it = 0; it < n; it++) {
            if (sw >= 0) drained4(it, sw);
            mbar_wait(f6 + 48, p6);
            bulk_ld_mc_e(d6, src, HALF, f6);
            expect_e(f6, BLK);
            next6();
            src += 1024;
          }
        };
        uint32_t ready = 0;
        auto need = [&](int e, uint32_t mask) {
          if (!(ready & mask)) {
            uint32_t n = 0;
            do { ready = __ballot_sync(~0u, ld_acquire(gs->flag + (m * 128 + e * 16 + (lane & 14)) * FS) == ep); SPIN_GUARD(n); } while (!(ready & mask));
            fence_async_global();
          }
        };
        auto fresh = [&](int e, int it, uint32_t full, uint32_t empty, int par, uint32_t slot, uint4* src) {
          mbar_wait(empty, par);
          expect_e(full, it < 2 ? 0 : BLK);
          if (it >= 4) {
            const int kb = own_order(it, j);
            if (it < 10) need(e, 1u << kb); else if (it == 10) mbar_wait(bar + B_ALL, e & 1);
            bulk_ld_mc_e(slot + rank * HALF, src + kb * 1024 + rank * 512, HALF, full);
          } else if (it >= 2) {
            const int b = it > 2;
            const uint32_t to_peer = mapa(sb, rank ^ 1) - sb;
            const bool push = b && e != 1;
            mbar_wait(bar + (push ? B_RDY : B_FREE) + b * 8, e & 1);
            if (push) bulk_push_e(slot + to_peer, sb + STG + BLK, BLK, full + to_peer);
            else { fence_async_global(); bulk_ld_e(slot + to_peer, src + (2 * j + b) * 1024, BLK, full + to_peer); }
          } else ready = 0;
        };
        uint4* const h = gs->h + m * 16384;
#pragma unroll 1
        for (int e = 0; e < 3; e++) {
#pragma unroll 1
          for (int it = 0; it < 16; it++) {
            const int s = (it + e) & 3;
            const uint32_t full = e == 1 ? f6 : bar + B_FULL4 + s * 8;
            if (e == 2) drained6(it);
            fresh(e, it, full, full + (e == 1 ? 48 : 32), e == 1 ? p6 : ~(it >> 2) & 1, e == 1 ? d6 - rank * HALF : sb + s * 49152, e == 1 ? gs->o + m * 16384 : h);
            if (e == 1) next6();
          }
          if (e == 1) { skip6(); continue; }
#pragma unroll 1
          for (int it = 16; it < 16 + 16 * e; it++) {
            const int s = (it + 2) & 3;
            const uint32_t full = bar + B_FULL4 + s * 8;
            mbar_wait(full + 32, ~(it >> 2) & 1);
            bulk_ld_mc_e(sb + s * 49152 + rank * HALF, h + (it & 15) * 1024 + rank * 512, HALF, full);
            expect_e(full, BLK);
          }
          run6(h, 16, e);
        }
#pragma unroll 1
        for (int q = 0; q < 3; q++) {
          mbar_wait(bar + (q == 2 ? B_HH2 : B_HH + q * 8), 0);
          run6(gs->hh + m * 57344 + (64 - (64 >> q)) * 1024, 32 >> q, -1);
        }
      }
    } else {
      const int b = warp - 10;
      const uint32_t ep = gs->epoch[blockIdx.x] + 1;
      const uint32_t stg = sb + STG + b * BLK;
      cl_arrive_relaxed(); cl_wait();
      auto all_there = [&](int u, uint32_t done) {
        const uint32_t* fl = gs->flag + u * FS;
        uint32_t n = 0;
        while (!__all_sync(~0u, ld_acquire(fl) == ep)) { __nanosleep(100); SPIN_GUARD(n); }
        fence_async_global();
        arrive_e(done);
      };
#pragma unroll 1
      for (int e = 0; e < 7 - b; e++) {
        const int kb = (e < 3 ? 2 * j : e < 6 ? 2 * (8 * (e - 3) + j) : 48 + j) + b;
        uint4* const dst = (e == 1 ? gs->o + m * 16384 : e < 3 ? gs->h + m * 16384 : gs->hh + m * 57344) + kb * 1024;
        uint32_t* const fl = gs->flag + (m * 128 + (e < 3 ? e * 16 : U_HH) + kb) * FS;
        if (e < 3 && lane < 8) st_rlx1(fl + lane, 0);
        if (b && e < 3) {
          mbar_wait(bar + B_FREE, e & 1);
          const uint32_t t0 = clock();
          while ((uint32_t)clock() - t0 < (e == 1 ? B1D : B1P)) {}
        }
        mbar_wait(bar + B_RDY + b * 8, e & 1);
        bulk_st_e(dst, stg, e < 3 ? BLK : BLK / NPIECE);
        if (e >= 3) {
#pragma unroll 1
          for (int q = 1; q < NPIECE; q++) { __nanosleep(PSLEEP); bulk_st_e(dst + q * (1024 / NPIECE), stg + q * (BLK / NPIECE), BLK / NPIECE); }
        }
        publish_e(bar + B_FREE + b * 8, fl, ep);
        if (b && (e < 3 || e == 4)) all_there(m * 128 + (e < 3 ? e * 16 + (lane & 15) : U_HH + lane), bar + (e < 3 ? B_ALL : B_HH));
        if (!b && (e == 1 || e == 2)) {
#pragma unroll 1
          for (int sec = e == 1 ? 2 : 5; sec < 4 + e; sec++) {
            const uint4* p = (const uint4*)(gs->modv + (sec - 2) * 1024 + j * 128) + lane;
            uint4 v0, v1; uint32_t n = 0;
            while (true) {
              v0 = ld_rlx4(p); v1 = ld_rlx4(p + 32);
              if (__all_sync(~0u, v0.y == ep && v0.w == ep && v1.y == ep && v1.w == ep)) break;
              SPIN_GUARD(n);
            }
            const uint32_t d = sb + MISC + MODV + sec * 256 + ((lane & 3) * 16 + (lane >> 2)) * 4;
            asm volatile("st.shared.u32 [%0], %1;" :: "r"(d), "r"(__byte_perm(v0.x, v0.z, 0x7632)) : "memory");
            asm volatile("st.shared.u32 [%0], %1;" :: "r"(d + 32), "r"(__byte_perm(v1.x, v1.z, 0x7632)) : "memory");
          }
          __syncwarp();
          if (e == 1) { arrive_e(bar + B_MOD); }
        }
        if (e == 0) {
          mbar_wait(bar + B_EMPTY6 + 24, 0);
          __nanosleep(HSLEEP);
#pragma unroll 1
          for (int w = 0; w < 4; w++) {
            const uint4* hp = gs->halo + ((m * 8 + j) * 2 + (w & 1)) * 512 + b * 256 + (w >> 1) * 128 + lane;
            uint4 q[4] = {}; uint32_t n = 0;
            while (m > 0) {
              bool ok = true;
#pragma unroll
              for (int i = 0; i < 4; i++) q[i] = ld_rlx4(hp + i * 32);
#pragma unroll
              for (int i = 0; i < 4; i++) ok = ok && q[i].y == ep && q[i].w == ep;
              if (__all_sync(~0u, ok)) break;
              SPIN_GUARD(n);
            }
#pragma unroll
            for (int i = 0; i < 2; i++) sts128(stg + lane * 16 + (w & 1) * HALF + (w >> 1) * 1024 + i * 512, q[2 * i].x, q[2 * i + 1].x, q[2 * i].z, q[2 * i + 1].z);
          }
          __syncwarp();
          arrive_e(bar + B_HALO);
        }
      }
      if (b) {
#pragma unroll 1
        for (int q = 0; q < 2; q++) all_there(m * 128 + U_HH + 32 + q * 16 + (lane & (15 >> q)), bar + (q ? B_HH2 : B_HH + 8));
      }
    }
  } else {
    const int wg = warp >> 2, wq = warp & 3, tid = threadIdx.x;
    const int g = lane >> 2, c = lane & 3;
    if (!extra) cl_arrive_relaxed();
    asm volatile("setmaxnreg.inc.sync.aligned.u32 232;" ::: "memory");
    if (__builtin_expect(extra, 0)) {
      const uint32_t ep = ep0 + 1;
      float sv[4];
#pragma unroll
      for (int p = 0; p < 4; p++) sv[p] = silu_c(__bfloat162float(cvec[64 * (4 * p + (lane >> 3)) + 8 * warp + (lane & 7)]));
      named_bar(2, 288);
      int s = 0, par = 0;
#pragma unroll 1
      for (int sec = 0; sec < 4; sec++) {
        float a[8] = {0, 0, 0, 0, 0, 0, 0, 0};
#pragma unroll 1
        for (int it = 0; it < 16; it++) {
          const float sc = it < 4 ? sv[0] : it < 8 ? sv[1] : it < 12 ? sv[2] : sv[3];
          mbar_wait(bar + B_FULL6 + s * 8, par);
          uint4 w[8];
#pragma unroll
          for (int i = 0; i < 8; i++) w[i] = lds128(sb + s * 32768 + (warp * 8 + i) * 512 + lane * 16);
#pragma unroll
          for (int i = 0; i < 8; i++) gemv_fma(a, w[i], __shfl_sync(~0u, sc, (it & 3) * 8 + i));
          if (lane == 0) mbar_arrive(bar + B_EMPTY6 + s * 8);
          if (++s == 6) { s = 0; par ^= 1; }
        }
        const uint32_t red = sb + STG + sec * 8192;
        sts128(red + warp * 1024 + lane * 32, __float_as_uint(a[0]), __float_as_uint(a[1]), __float_as_uint(a[2]), __float_as_uint(a[3]));
        sts128(red + warp * 1024 + lane * 32 + 16, __float_as_uint(a[4]), __float_as_uint(a[5]), __float_as_uint(a[6]), __float_as_uint(a[7]));
        named_bar(1, 256);
        float t = 0;
#pragma unroll
        for (int q = 0; q < 8; q++) t += lds32f(red + q * 1024 + tid * 4);
        t = bf_round(t);
        if (sec == 2) t = bf_round(t + 1.f);
        st_rlx2(gs->modv + sec * 1024 + (bid + 4) * 256 + tid, __float_as_uint(t), ep);
      }
      if (tid == 0) gs->epoch[blockIdx.x] = ep;
      return;
    }
    const int row0 = wg * 64 + wq * 16 + g;
    if (c < 2) st_rlx2(gs->stat + m * 1024 + j * 128 + row0 + c * 8, 0, 0);
    cl_wait();
    uint32_t ep;
    asm volatile("add.u32 %0, %1, 1;" : "=r"(ep) : "r"(ep0) : "memory");
    const float sc_ = silu_c(__uint_as_float((uint32_t)cv_ << 16));
    const uint32_t rel = mapa(bar, (lane & 1) ^ rank);
    const uint32_t stg_row = sb + STG + (wg * 64 + wq * 16 + (lane & 15)) * 128;
    const uint32_t fre = bar + B_FREE;
    Ring r4{0, 0, 0}, r6{0, 0, 0};
    auto none = [](auto) {};
    uint32_t xk[32];
    {
      float a[8] = {0, 0, 0, 0, 0, 0, 0, 0};
#pragma unroll
      for (int i = 0; i < 8; i++) gemv_fma(a, wv[i], __shfl_sync(~0u, sc_, i * 4 + (lane >> 3)));
#pragma unroll
      for (int i = 0; i < 8; i++) { a[i] += __shfl_xor_sync(~0u, a[i], 8); a[i] += __shfl_xor_sync(~0u, a[i], 16); }
      if (lane < 8) {
        sts128(sb + RED_OFF + warp * 256 + lane * 32, __float_as_uint(a[0]), __float_as_uint(a[1]), __float_as_uint(a[2]), __float_as_uint(a[3]));
        sts128(sb + RED_OFF + warp * 256 + lane * 32 + 16, __float_as_uint(a[4]), __float_as_uint(a[5]), __float_as_uint(a[6]), __float_as_uint(a[7]));
      }
      named_bar(1, 256);
      if (tid < 64) {
        float s = 0;
#pragma unroll
        for (int w = 0; w < 8; w++) s += lds32f(sb + RED_OFF + w * 256 + tid * 4);
        st_rlx1(gs->modp + u * 64 + tid, (__float_as_uint(s) & ~255u) | tag_of(ep));
      }
      float v[64];
      mbar_wait(bar + B_X, 0); mbar_wait(bar + B_X + 8, 0);
#pragma unroll
      for (int i = 0; i < 16; i += 2) {
        uint32_t w0, w1, w2, w3;
        ldsm4(stg_row + (i >> 3) * BLK + ((((i & 7) + (lane >> 4)) ^ (lane & 7)) << 4), w0, w1, w2, w3);
        xk[2 * i] = w0; xk[2 * i + 1] = w1; xk[2 * i + 2] = w2; xk[2 * i + 3] = w3;
        v[4 * i] = bf_lo(w0); v[4 * i + 1] = bf_hi(w0); v[4 * i + 2] = bf_lo(w1); v[4 * i + 3] = bf_hi(w1);
        v[4 * i + 4] = bf_lo(w2); v[4 * i + 5] = bf_hi(w2); v[4 * i + 6] = bf_lo(w3); v[4 * i + 7] = bf_hi(w3);
      }
      ln_publish(v, gs->stat + m * 1024, j, row0, lane, ep);
      mod_store(sb, tid >> 7, tid & 127, mod_gather(gs->modp + (tid >> 7) * 1024 + j * 128 + (tid & 127), ep));
      named_bar(1, 256);
      ln_apply(v, gs->stat + m * 1024, row0, ep, sb, 0, 1, stg_row, wg, lane);
      named_bar(1, 256);
    }
    {
      uint32_t kf[32], vf[32], pv[32];
      const bool first = wq == 0 && m == 0;
      const uint32_t xa = sb + STG + wg * HALF + wq * 2048 + lane * 16;
      {
        float acc[128];
        mainloop<256, 4, 0, 0>(acc, 16, true, r4, sb, wg, lane, rel, none, none, [&] {
          mbar_wait(fre + 8, 0);
          if (c < 2) st_rlx2(gs->stat + (16 + m) * 1024 + j * 128 + row0 + c * 8, 0, 0);
        });
#pragma unroll
        for (int i = 0; i < 32; i++) { kf[i] = pack2(acc[2 * i], acc[2 * i + 1]); vf[i] = pack2(acc[64 + 2 * i], acc[65 + 2 * i]); }
      }
      float acc[64];
      constexpr int QP = 2;
      mainloop<128, 6, 8 / QP, 0>(acc, 16, false, r6, sb, wg, lane, rel, [&](auto ic) {
        constexpr int q = (ic.v - 1) * QP;
#pragma unroll
        for (int i = 4 * q; i < 4 * (q + QP); i++) vf[i] = movm(vf[i]);
        if (wq == 3) {
          if (m < 15) {
            uint4* hp = gs->halo + (((m + 1) * 8 + j) * 2 + wg) * 512 + lane;
#pragma unroll
            for (int i = 2 * q; i < 2 * (q + QP); i++) st_rlx4(hp + i * 32, kf[2 * i + 1], ep, vf[2 * i + 1], ep);
          }
        } else {
#pragma unroll
          for (int i = q; i < q + QP; i++) sts128(xa + 2048 + (i >> 2) * BLK + (i & 3) * 512, kf[4 * i + 1], kf[4 * i + 3], vf[4 * i + 1], vf[4 * i + 3]);
        }
      }, none, [&] {
        named_bar(2 + wg, 128);
        if (wq == 0) mbar_wait(bar + B_HALO, 0);
#pragma unroll
        for (int i = 0; i < 8; i++) {
          uint4 q = lds128(xa + (i >> 2) * BLK + (i & 3) * 512);
          pv[4 * i] = q.x; pv[4 * i + 1] = q.y; pv[4 * i + 2] = q.z; pv[4 * i + 3] = q.w;
        }
        __syncwarp();
      });
      int gz = g;
#pragma unroll
      for (int b = 0; b < 2; b++) {
        const bool up0 = 2 * c > gz, up1 = 2 * c + 1 > gz;
        const uint32_t mup = (up0 ? 0xffffu : 0u) | (up1 ? 0xffff0000u : 0u);
        float l[2][4], mx[4];
#pragma unroll
        for (int h = 0; h < 2; h++) {
          uint32_t q[8];
          const int k = 16 * b + 8 * h;
#pragma unroll
          for (int i = 0; i < 8; i++) q[i] = pack2(acc[2 * k + 2 * i], acc[2 * k + 2 * i + 1]);
          float s0[4], s1[4], s2[4];
          mma16z(s0, q[0], q[1], q[2], q[3], pv[k], pv[k + 1]); mma16z(s1, q[0], q[1], q[2], q[3], kf[k], kf[k + 2]); mma16z(s2, q[0], q[1], q[2], q[3], kf[k + 1], kf[k + 3]);
          mma16(s0, q[4], q[5], q[6], q[7], pv[k + 4], pv[k + 5]); mma16(s1, q[4], q[5], q[6], q[7], kf[k + 4], kf[k + 6]); mma16(s2, q[4], q[5], q[6], q[7], kf[k + 5], kf[k + 7]);
          if (first) { s0[0] = -INFINITY; s0[1] = -INFINITY; }
          l[h][0] = up0 ? s0[0] : s1[0]; l[h][1] = up1 ? s0[1] : s1[1]; l[h][2] = up0 ? s1[2] : s2[2]; l[h][3] = up1 ? s1[3] : s2[3];
          mx[2 * h] = fmaxf(l[h][0], l[h][1]); mx[2 * h + 1] = fmaxf(l[h][2], l[h][3]);
        }
#pragma unroll
        for (int o = 1; o < 4; o <<= 1) {
#pragma unroll
          for (int h = 0; h < 4; h++) mx[h] = fmaxf(mx[h], __shfl_xor_sync(~0u, mx[h], o));
        }
#pragma unroll
        for (int h = 0; h < 2; h++) {
          const float n0 = -mx[2 * h] * SCL, n1 = -mx[2 * h + 1] * SCL;
          const uint32_t pa = pack2(ex2(fmaf(l[h][0], SCL, n0)), ex2(fmaf(l[h][1], SCL, n0))), pb = pack2(ex2(fmaf(l[h][2], SCL, n1)), ex2(fmaf(l[h][3], SCL, n1)));
          float sm[4];
          mma8z(sm, pa, pb, 0x3f803f80u);
          const float ia = rcp(sm[0]), ib = rcp(sm[2]);
#pragma unroll
          for (int i = 8 * b + 4 * h; i < 8 * b + 4 * h + 4; i += 2) {
            uint32_t of[4];
#pragma unroll
            for (int d = 0; d < 2; d++) {
              float o[4];
              mma16z(o, pa & ~mup, pb & mup, 0u, pb & ~mup, vf[2 * (i + d)], vf[2 * (i + d) + 1]);
              mma8(o, pa & mup, 0u, pv[2 * i + 2 + d]);
              of[2 * d] = pack2(o[0] * ia, o[1] * ia); of[2 * d + 1] = pack2(o[2] * ib, o[3] * ib);
            }
            stsm4(stg_row + b * BLK + ((((i & 7) + (lane >> 4)) ^ (lane & 7)) << 4), of[0], of[1], of[2], of[3]);
          }
        }
        stage_done(sb, wg, b, lane);
        if (b == 0) gz += __float_as_uint(lds32f(bar + ZERO));
      }
      named_bar(1, 256);
    }
    uint32_t pk[64];
    {
      float acc[64];
      mainloop<128, 6, 0, 0>(acc, 16, true, r6, sb, wg, lane, rel, none, none, [&] {
        mbar_wait(bar + B_MOD, 0); mbar_wait(fre + 8, 1);
        load_vec(pk + 32, sb, 2, 0, lane); load_vec(pk + 40, sb, 2, 1, lane);
#pragma unroll
        for (int i = 0; i < 32; i++) { pk[i] = xk[i]; asm volatile("" : "+r"(pk[i])); }
      });
#pragma unroll
      for (int i = 0; i < 32; i++) {
        acc[2 * i] = fmaf(acc[2 * i], bf_lo(pk[32 + (i >> 1)]), bf_lo(pk[i]));
        acc[2 * i + 1] = fmaf(acc[2 * i + 1], bf_hi(pk[32 + (i >> 1)]), bf_hi(pk[i]));
      }
      ln_publish(acc, gs->stat + (16 + m) * 1024, j, row0, lane, ep);
      mbar_wait(bar + B_FULL6 + 16, 1);
      if (lane < 2) mbar_arrive_cl(rel + B_EMPTY6 + 16);
      ring_next<6>(r6);
#pragma unroll
      for (int i = 0; i < 32; i++) { pk[i] = pack2(acc[2 * i], acc[2 * i + 1]); pk[32 + i] = 0; }
      ln_apply(acc, gs->stat + (16 + m) * 1024, row0, ep, sb, 3, 4, stg_row, wg, lane);
      named_bar(1, 256);
    }
    auto swiglu = [&](int q, int uo, int par) {
      if ((q & 3) == 0 && par >= 0) mbar_wait(fre + 2 * q, par);
      uint32_t w[4];
#pragma unroll
      for (int u = 0; u < 4; u++) w[u] = silu_mul2(pk[4 * q + u], pk[uo + 4 * q + u]);
      stsm4(stg_row + (q >> 2) * BLK + ((((2 * q & 7) + (lane >> 4)) ^ (lane & 7)) << 4), w[0], w[1], w[2], w[3]);
    };
    r4.s = r4.wrap = 2;
#pragma unroll 1
    for (int t = 0; t < 3; t++) {
      float acc[128];
      mainloop<256, 4, 4, 1>(acc, 16, t == 0, r4, sb, wg, lane, rel, [&](auto ic) {
        if (t) {
          if (ic.v == 3) stage_done(sb, wg, 0, lane);
          swiglu(2 * ic.v - 2, 32, ~t & 1); swiglu(2 * ic.v - 1, 32, 0);
        }
      }, [&](int it) {
        if (t && it == 5) stage_done(sb, wg, 1, lane);
        if (t == 0 && it >= 8) {
          uint4* p = gs->x1 + bid * 2048 + ((it >> 2) & 1) * 1024 + warp * 128 + (it & 3) * 32 + lane;
#pragma unroll
          for (int i = 0; i < 8; i++)
            asm volatile("{\n.reg .pred p;\nsetp.eq.u32 p, %5, %6;\n@p st.global.v4.u32 [%0], {%1,%2,%3,%4};\n}" :: "l"(p), "r"(pk[4 * i]), "r"(pk[4 * i + 1]), "r"(pk[4 * i + 2]), "r"(pk[4 * i + 3]), "r"(it), "r"(8 + i) : "memory");
        }
      }, [&] { if (t == 0) fence_async_global(); else if (t == 2) mbar_wait(bar + B_X, 1); }, t & 1);
#pragma unroll
      for (int i = 0; i < 64; i++) pk[i] = pack2(acc[2 * i], acc[2 * i + 1]);
    }
    uint32_t x1[32];
    {
      float acc[64];
      mainloop<128, 6, 10, 1>(acc, 16, false, r6, sb, wg, lane, rel, [&](auto ic) {
        constexpr int b = ic.v > 5, q = ic.v - 5 * b;
        if (q == 1) {
          if (b) stage_done(sb, wg, 0, lane);
#pragma unroll
          for (int i = 4 * b; i < 4 * b + 4; i++) { const uint4 x = lds128(sb + STG + b * BLK + warp * 2048 + (i & 3) * 512 + lane * 16); x1[4 * i] = x.x; x1[4 * i + 1] = x.y; x1[4 * i + 2] = x.z; x1[4 * i + 3] = x.w; }
          __syncwarp();
        } else swiglu(4 * b + q - 2, 32, -1);
      }, [&](int it) { if (it == 11) stage_done(sb, wg, 1, lane); }, [] {}, 1);
#pragma unroll
      for (int i = 0; i < 32; i++) pk[i] = pack2(acc[2 * i], acc[2 * i + 1]);
    }
    {
      float acc[64];
      mainloop<128, 6, 4, TAILLAG>(acc, 56, false, r6, sb, wg, lane, rel, [&](auto ic) { swiglu(ic.v - 1, 16, 1); },
                                   [&](int it) { if (it == 5) stage_done(sb, wg, 0, lane); }, [&] {
        load_vec(pk + 32, sb, 5, 0, lane); load_vec(pk + 40, sb, 5, 1, lane);
        mbar_wait(fre, 0); mbar_wait(fre + 8, 1);
      }, 0);
      __syncwarp();
      cl_arrive_relaxed();
#pragma unroll
      for (int i = 0; i < 16; i += 2) {
        uint32_t w[4];
#pragma unroll
        for (int u = 0; u < 4; u++) {
          const int q = 2 * i + u;
          w[u] = pack2(fmaf(acc[2 * q], bf_lo(pk[32 + (q >> 1)]), bf_lo(x1[q])), fmaf(acc[2 * q + 1], bf_hi(pk[32 + (q >> 1)]), bf_hi(x1[q])));
        }
        stsm4(stg_row + (i >> 3) * BLK + ((((i & 7) + (lane >> 4)) ^ (lane & 7)) << 4), w[0], w[1], w[2], w[3]);
        if ((i & 7) == 6) {
          fence_async_smem();
          named_bar(2 + wg, 128);
          if (wq == 0 && elect()) { tma_store_3d(&maps.out, sb + STG + (i >> 3) * BLK + wg * HALF, j * 128 + (i >> 3) * 64, m * 64, wg); bulk_commit(); }
          if (i < 8) x1[16] |= __float_as_uint(lds32f(bar + ZERO));
        }
      }
      if (wq == 0) bulk_wait_read();
      if (tid == 0) gs->epoch[blockIdx.x] = ep;
      cl_wait();
    }
  }
}

typedef CUresult (*EncodeFn)(CUtensorMap*, CUtensorMapDataType, cuuint32_t, void*, const cuuint64_t*, const cuuint64_t*, const cuuint32_t*, const cuuint32_t*,
                             CUtensorMapInterleave, CUtensorMapSwizzle, CUtensorMapL2promotion, CUtensorMapFloatOOBfill);

void make_map(EncodeFn fn, CUtensorMap* mp, const void* base, uint64_t d0, uint64_t d1, uint64_t d2, uint64_t s1, uint64_t s2, uint32_t b2, uint32_t b0 = 64) {
  cuuint64_t d[3] = {d0, d1, d2}, s[2] = {s1, s2};
  cuuint32_t b[3] = {b0, 64, b2}, e[3] = {1, 1, 1};
  fn(mp, CU_TENSOR_MAP_DATA_TYPE_BFLOAT16, 3, (void*)base, d, s, b, e, CU_TENSOR_MAP_INTERLEAVE_NONE, b0 == 64 ? CU_TENSOR_MAP_SWIZZLE_128B : CU_TENSOR_MAP_SWIZZLE_NONE,
     CU_TENSOR_MAP_L2_PROMOTION_L2_128B, CU_TENSOR_MAP_FLOAT_OOB_FILL_NONE);
}

__global__ void probe_kernel() {}
int max_clusters(int size) {
  cudaLaunchConfig_t cfg = {};
  cudaLaunchAttribute at;
  at.id = cudaLaunchAttributeClusterDimension; at.val.clusterDim.x = size; at.val.clusterDim.y = 1; at.val.clusterDim.z = 1;
  cfg.gridDim = dim3(size * 66); cfg.blockDim = dim3(384); cfg.dynamicSmemBytes = SMEM_BYTES; cfg.attrs = &at; cfg.numAttrs = 1;
  int n = 0;
  if (cudaOccupancyMaxActiveClusters(&n, probe_kernel, &cfg) != cudaSuccess) { cudaGetLastError(); return 0; }
  return n;
}

}

extern "C" void kernel_launch(void* const* d_in, const int* in_sizes, int n_in, void* d_out, int out_size) {
  static EncodeFn fn = nullptr;
  static int by_sm = 0;
  static Scratch* gs = nullptr;
  if (!fn) {
    void* p = nullptr; cudaDriverEntryPointQueryResult q;
    cudaGetDriverEntryPoint("cuTensorMapEncodeTiled", &p, cudaEnableDefault, &q);
    fn = (EncodeFn)p;
    cudaFuncSetAttribute(fused_kernel, cudaFuncAttributeMaxDynamicSharedMemorySize, SMEM_BYTES);
    int dev = 0, sms = 0;
    cudaGetSymbolAddress((void**)&gs, g_scratch);
    cudaGetDevice(&dev);
    cudaDeviceGetAttribute(&sms, cudaDevAttrMultiProcessorCount, dev);
    cudaFuncSetAttribute(probe_kernel, cudaFuncAttributeMaxDynamicSharedMemorySize, SMEM_BYTES);
    if (sms == 132 && max_clusters(2) == 66) {
      const int c4 = max_clusters(4), c6 = max_clusters(6), c8 = max_clusters(8);
      by_sm = c4 == 30 && c6 == 17 && c8 == 15 ? 1 : c8 == 16 ? 2 : 0;
    }
  }
  Maps mp;
  make_map(fn, &mp.x, d_in[0], D_, S_ / 2, 2, 4096, 2048, 2);
  make_map(fn, &mp.out, d_out, D_, S_ / 2, 2, 4096, 2048, 1);
  make_map(fn, &mp.wqkv, d_in[1], 64, D_, 3 * D_ / 64, 3 * D_ * 2, 128, 2);
  make_map(fn, &mp.wo, d_in[2], 64, D_, D_ / 64, D_ * 2, 128, 2);
  make_map(fn, &mp.w1, d_in[4], 64, D_, F_ / 64, F_ * 2, 128, 2);
  make_map(fn, &mp.w3, d_in[5], 64, D_, F_ / 64, F_ * 2, 128, 2);
  make_map(fn, &mp.w1s, d_in[4], 64, D_, F_ / 64, F_ * 2, 128, 1);
  make_map(fn, &mp.w3s, d_in[5], 64, D_, F_ / 64, F_ * 2, 128, 1);
  make_map(fn, &mp.w2, d_in[6], 64, F_, D_ / 64, D_ * 2, 128, 2);
  make_map(fn, &mp.wmod, d_in[8], 256, D_, 24, 6 * D_ * 2, 512, 1, 256);
  fused_kernel<<<132, 384, SMEM_BYTES>>>((const bf16*)d_in[7], (const bf16*)d_in[8], gs, by_sm, mp);
}
```

```cpp
#include <cuda_runtime.h>
#include <cuda_bf16.h>
#include <cuda.h>
#include <stdint.h>

typedef __nv_bfloat16 bf16;

namespace {

constexpr int S_ = 2048, D_ = 1024, F_ = 3584;
constexpr int BLK = 16384;
constexpr int HALF = 8192;
constexpr int RING = 196608;
constexpr int STG = RING;
constexpr int MISC = RING + 2 * BLK;
constexpr int SMEM_BYTES = MISC + 3072;
constexpr int B_FULL4 = 0, B_EMPTY4 = 32, B_FULL6 = 64, B_EMPTY6 = 112, B_RDY = 160, B_FREE = 176, B_LAG = 192, B_X = 208, B_MOD = 224, B_OUT = 240, B_HH = 256, B_ALL = 272, B_HH2 = 288, ZERO = 296, B_HALO = 304;
constexpr int MODV = 512;
constexpr int RED_OFF = 0;
constexpr float SCL = 0.17677669529663687f * 1.4426950408889634f;
constexpr int U_HH = 64;
constexpr int FS = 8;
constexpr int NPIECE = 4, PSLEEP = 300;
constexpr int XSLEEP = 4000;
constexpr uint32_t GAP = 250;
constexpr uint32_t B1P = 3700, B1D = 700;
constexpr int TAILLAG = 5;

struct Maps { CUtensorMap x, out, wqkv, wo, w1, w3, w1s, w3s, w2, wmod; };

struct Scratch {
  uint32_t epoch[256];
  uint32_t flag[16 * 128 * FS];
  uint32_t modp[8 * 2 * 4 * 128];
  uint2 modv[4 * 1024];
  uint2 stat[2 * 16 * 8 * 128];
  uint4 halo[16 * 8 * 2 * 256];
  uint4 x1[128 * 8 * 256];
  uint4 h[16 * 16 * 1024];
  uint4 o[16 * 16 * 1024];
  uint4 hh[16 * 56 * 1024];
};
__device__ __align__(1024) Scratch g_scratch;

__device__ __forceinline__ void bail() { asm volatile("st.global.u32 [%0], %1;" :: "l"(0ull), "r"(0) : "memory"); }
__device__ __forceinline__ uint32_t smem_u32(const void* p) { return (uint32_t)__cvta_generic_to_shared(p); }
__device__ __forceinline__ void mbar_init(uint32_t bar, uint32_t cnt) { asm volatile("mbarrier.init.shared::cta.b64 [%0], %1;" :: "r"(bar), "r"(cnt) : "memory"); }
__device__ __forceinline__ void mbar_arrive(uint32_t bar) { asm volatile("mbarrier.arrive.shared::cta.b64 _, [%0];" :: "r"(bar) : "memory"); }
__device__ __forceinline__ void mbar_arrive_cl(uint32_t cl_addr) { asm volatile("mbarrier.arrive.shared::cluster.b64 _, [%0];" :: "r"(cl_addr) : "memory"); }
__device__ __forceinline__ uint32_t mapa(uint32_t addr, uint32_t cta) { uint32_t r; asm("mapa.shared::cluster.u32 %0, %1, %2;" : "=r"(r) : "r"(addr), "r"(cta)); return r; }
__device__ __forceinline__ void mbar_wait(uint32_t bar, uint32_t parity) {
  asm volatile("{\n.reg .pred p;\n.reg .b32 n;\n.reg .b64 z;\nmov.b32 n, 0;\nmov.b64 z, 0;\n"
               "W: add.u32 n, n, 1;\nsetp.gt.u32 p, n, 0x400000;\n@p st.global.u32 [z], n;\n"
               "mbarrier.try_wait.parity.shared::cta.b64 p, [%0], %1;\n@!p bra W;\n}" :: "r"(bar), "r"(parity) : "memory");
}
__device__ __forceinline__ void tma_store_3d(const CUtensorMap* m, uint32_t src, int c0, int c1, int c2) {
  asm volatile("cp.async.bulk.tensor.3d.global.shared::cta.bulk_group [%0, {%2, %3, %4}], [%1];" :: "l"(m), "r"(src), "r"(c0), "r"(c1), "r"(c2) : "memory");
}
#define ELECT "{\n.reg .pred p;\nelect.sync _|p, 0xffffffff;\n@p "
__device__ __forceinline__ void expect_e(uint32_t bar, uint32_t bytes) { asm volatile(ELECT "mbarrier.arrive.expect_tx.shared::cta.b64 _, [%0], %1;\n}" :: "r"(bar), "r"(bytes) : "memory"); }
__device__ __forceinline__ void tma_3d_e(uint32_t dst, const CUtensorMap* m, uint32_t bar, int c0, int c1, int c2) {
  asm volatile(ELECT "cp.async.bulk.tensor.3d.shared::cluster.global.mbarrier::complete_tx::bytes [%0], [%1, {%3, %4, %5}], [%2];\n}" :: "r"(dst), "l"(m), "r"(bar), "r"(c0), "r"(c1), "r"(c2) : "memory");
}
__device__ __forceinline__ void bulk_ld_e(uint32_t dst, const void* src, uint32_t bytes, uint32_t bar) {
  asm volatile(ELECT "cp.async.bulk.shared::cluster.global.mbarrier::complete_tx::bytes [%0], [%1], %2, [%3];\n}" :: "r"(dst), "l"(src), "r"(bytes), "r"(bar) : "memory");
}
__device__ __forceinline__ void bulk_ld_mc_e(uint32_t dst, const void* src, uint32_t bytes, uint32_t bar) {
  asm volatile(ELECT "cp.async.bulk.shared::cluster.global.mbarrier::complete_tx::bytes.multicast::cluster [%0], [%1], %2, [%3], %4;\n}" :: "r"(dst), "l"(src), "r"(bytes), "r"(bar), "h"((uint16_t)3) : "memory");
}
__device__ __forceinline__ void bulk_push_e(uint32_t dst_cl, uint32_t src, uint32_t bytes, uint32_t bar_cl) {
  asm volatile(ELECT "cp.async.bulk.shared::cluster.shared::cta.mbarrier::complete_tx::bytes [%0], [%1], %2, [%3];\n}" :: "r"(dst_cl), "r"(src), "r"(bytes), "r"(bar_cl) : "memory");
}
__device__ __forceinline__ void arrive_e(uint32_t bar) { asm volatile(ELECT "mbarrier.arrive.shared::cta.b64 _, [%0];\n}" :: "r"(bar) : "memory"); }
__device__ __forceinline__ void bulk_st_e(void* dst, uint32_t src, uint32_t bytes) {
  asm volatile(ELECT "cp.async.bulk.global.shared::cta.bulk_group [%0], [%1], %2;\n}" :: "l"(dst), "r"(src), "r"(bytes) : "memory");
}
__device__ __forceinline__ void publish_e(uint32_t free_bar, uint32_t* flag, uint32_t ep) {
  asm volatile(ELECT "cp.async.bulk.commit_group;\n@p cp.async.bulk.wait_group 0;\n@p mbarrier.arrive.shared::cta.b64 _, [%0];\n@p st.release.gpu.global.u32 [%1], %2;\n}"
               :: "r"(free_bar), "l"(flag), "r"(ep) : "memory");
}
__device__ __forceinline__ void bulk_commit() { asm volatile("cp.async.bulk.commit_group;" ::: "memory"); }
__device__ __forceinline__ void bulk_wait_read() { asm volatile("cp.async.bulk.wait_group.read 0;" ::: "memory"); }
__device__ __forceinline__ void fence_async_global() { asm volatile("fence.proxy.async.global;" ::: "memory"); }
__device__ __forceinline__ void fence_async_smem() { asm volatile("fence.proxy.async.shared::cta;" ::: "memory"); }
__device__ __forceinline__ void wg_arrive() { asm volatile("wgmma.fence.sync.aligned;" ::: "memory"); }
__device__ __forceinline__ void wg_commit() { asm volatile("wgmma.commit_group.sync.aligned;" ::: "memory"); }
template <int N> __device__ __forceinline__ void wg_wait() { asm volatile("wgmma.wait_group.sync.aligned %0;" :: "n"(N) : "memory"); }
__device__ __forceinline__ void cl_arrive_relaxed() { asm volatile("barrier.cluster.arrive.relaxed.aligned;" ::: "memory"); }
__device__ __forceinline__ void cl_wait() { asm volatile("barrier.cluster.wait.acquire.aligned;" ::: "memory"); }
__device__ __forceinline__ bool elect() { uint32_t p; asm volatile("{\n.reg .pred p;\nelect.sync _|p, 0xffffffff;\nselp.u32 %0, 1, 0, p;\n}" : "=r"(p)); return p; }
__device__ __forceinline__ void named_bar(int id, int n) { asm volatile("bar.sync %0, %1;" :: "r"(id), "r"(n) : "memory"); }
__device__ __forceinline__ uint32_t pack2(float lo, float hi) { uint32_t r; asm("cvt.rn.bf16x2.f32 %0, %1, %2;" : "=r"(r) : "f"(hi), "f"(lo)); return r; }
__device__ __forceinline__ float bf_lo(uint32_t w) { return __uint_as_float(w << 16); }
__device__ __forceinline__ float bf_hi(uint32_t w) { return __uint_as_float(w & 0xffff0000u); }
__device__ __forceinline__ float bf_round(float v) { return __bfloat162float(__float2bfloat16_rn(v)); }
__device__ __forceinline__ void stsm4(uint32_t addr, uint32_t a, uint32_t b, uint32_t c, uint32_t d) {
  asm volatile("stmatrix.sync.aligned.m8n8.x4.shared.b16 [%0], {%1, %2, %3, %4};" :: "r"(addr), "r"(a), "r"(b), "r"(c), "r"(d) : "memory");
}
__device__ __forceinline__ void ldsm4(uint32_t addr, uint32_t& a, uint32_t& b, uint32_t& c, uint32_t& d) {
  asm volatile("ldmatrix.sync.aligned.m8n8.x4.shared.b16 {%0, %1, %2, %3}, [%4];" : "=r"(a), "=r"(b), "=r"(c), "=r"(d) : "r"(addr) : "memory");
}
__device__ __forceinline__ uint32_t movm(uint32_t a) { uint32_t r; asm volatile("movmatrix.sync.aligned.m8n8.trans.b16 %0, %1;" : "=r"(r) : "r"(a)); return r; }
__device__ __forceinline__ void mma16(float (&d)[4], uint32_t a0, uint32_t a1, uint32_t a2, uint32_t a3, uint32_t b0, uint32_t b1) {
  asm("mma.sync.aligned.m16n8k16.row.col.f32.bf16.bf16.f32 {%0,%1,%2,%3}, {%4,%5,%6,%7}, {%8,%9}, {%0,%1,%2,%3};"
               : "+f"(d[0]), "+f"(d[1]), "+f"(d[2]), "+f"(d[3]) : "r"(a0), "r"(a1), "r"(a2), "r"(a3), "r"(b0), "r"(b1));
}
__device__ __forceinline__ void mma16z(float (&d)[4], uint32_t a0, uint32_t a1, uint32_t a2, uint32_t a3, uint32_t b0, uint32_t b1) {
  asm("mma.sync.aligned.m16n8k16.row.col.f32.bf16.bf16.f32 {%0,%1,%2,%3}, {%4,%5,%6,%7}, {%8,%9}, {%10,%10,%10,%10};"
      : "=f"(d[0]), "=f"(d[1]), "=f"(d[2]), "=f"(d[3]) : "r"(a0), "r"(a1), "r"(a2), "r"(a3), "r"(b0), "r"(b1), "f"(0.f));
}
__device__ __forceinline__ void mma8z(float (&d)[4], uint32_t a0, uint32_t a1, uint32_t b0) {
  asm("mma.sync.aligned.m16n8k8.row.col.f32.bf16.bf16.f32 {%0,%1,%2,%3}, {%4,%5}, {%6}, {%7,%7,%7,%7};"
      : "=f"(d[0]), "=f"(d[1]), "=f"(d[2]), "=f"(d[3]) : "r"(a0), "r"(a1), "r"(b0), "f"(0.f));
}
__device__ __forceinline__ void mma8(float (&d)[4], uint32_t a0, uint32_t a1, uint32_t b0) {
  asm("mma.sync.aligned.m16n8k8.row.col.f32.bf16.bf16.f32 {%0,%1,%2,%3}, {%4,%5}, {%6}, {%0,%1,%2,%3};"
               : "+f"(d[0]), "+f"(d[1]), "+f"(d[2]), "+f"(d[3]) : "r"(a0), "r"(a1), "r"(b0));
}
__device__ __forceinline__ uint4 lds128(uint32_t a) { uint4 v; asm volatile("ld.shared.v4.u32 {%0,%1,%2,%3}, [%4];" : "=r"(v.x), "=r"(v.y), "=r"(v.z), "=r"(v.w) : "r"(a) : "memory"); return v; }
__device__ __forceinline__ void sts128(uint32_t a, uint32_t x, uint32_t y, uint32_t z, uint32_t w) { asm volatile("st.shared.v4.u32 [%0], {%1,%2,%3,%4};" :: "r"(a), "r"(x), "r"(y), "r"(z), "r"(w) : "memory"); }
__device__ __forceinline__ float lds32f(uint32_t a) { float v; asm volatile("ld.shared.f32 %0, [%1];" : "=f"(v) : "r"(a) : "memory"); return v; }
__device__ __forceinline__ void sts16(uint32_t a, bf16 v) { asm volatile("st.shared.b16 [%0], %1;" :: "r"(a), "h"(__bfloat16_as_ushort(v)) : "memory"); }
__device__ __forceinline__ uint4 ldg_nc(const void* p) { uint4 v; asm volatile("ld.global.nc.L1::no_allocate.v4.u32 {%0,%1,%2,%3}, [%4];" : "=r"(v.x), "=r"(v.y), "=r"(v.z), "=r"(v.w) : "l"(p)); return v; }
__device__ __forceinline__ uint4 ld_rlx4(const uint4* p) {
  unsigned long long a, b; asm volatile("ld.relaxed.gpu.global.v2.b64 {%0,%1}, [%2];" : "=l"(a), "=l"(b) : "l"(p) : "memory");
  return make_uint4((uint32_t)a, (uint32_t)(a >> 32), (uint32_t)b, (uint32_t)(b >> 32));
}
__device__ __forceinline__ uint2 ld_rlx2(const uint2* p) { unsigned long long a; asm volatile("ld.relaxed.gpu.global.b64 %0, [%1];" : "=l"(a) : "l"(p) : "memory"); return make_uint2((uint32_t)a, (uint32_t)(a >> 32)); }
__device__ __forceinline__ void st_rlx2(uint2* p, uint32_t x, uint32_t y) { asm volatile("st.relaxed.gpu.global.b64 [%0], %1;" :: "l"(p), "l"((unsigned long long)x | ((unsigned long long)y << 32)) : "memory"); }
__device__ __forceinline__ void st_rlx1(uint32_t* p, uint32_t v) { asm volatile("st.relaxed.gpu.global.u32 [%0], %1;" :: "l"(p), "r"(v) : "memory"); }
__device__ __forceinline__ uint32_t ld_rlx1(const uint32_t* p) { uint32_t v; asm volatile("ld.relaxed.gpu.global.u32 %0, [%1];" : "=r"(v) : "l"(p) : "memory"); return v; }
__device__ __forceinline__ uint32_t ld_acquire(const uint32_t* p) { uint32_t v; asm volatile("ld.acquire.gpu.global.u32 %0, [%1];" : "=r"(v) : "l"(p) : "memory"); return v; }
__device__ __forceinline__ void prefetch_map(const CUtensorMap* m) { asm volatile("prefetch.tensormap [%0];" :: "l"(m) : "memory"); }
__device__ __forceinline__ float rcp(float x) { float r; asm("rcp.approx.ftz.f32 %0, %1;" : "=f"(r) : "f"(x)); return r; }
__device__ __forceinline__ float ex2(float x) { float r; asm("ex2.approx.ftz.f32 %0, %1;" : "=f"(r) : "f"(x)); return r; }
__device__ __forceinline__ float tanh_fast(float x) { float r; asm("tanh.approx.f32 %0, %1;" : "=f"(r) : "f"(x)); return r; }
#define SPIN_GUARD(n) if (++(n) > (1u << 24)) bail()

__device__ __forceinline__ void wgmma_n128(float (&d)[64], uint64_t da, uint64_t db) {
  asm volatile("wgmma.mma_async.sync.aligned.m64n128k16.f32.bf16.bf16 "
    "{%0, %1, %2, %3, %4, %5, %6, %7, %8, %9, %10, %11, %12, %13, %14, %15, %16, %17, %18, %19, %20, %21, %22, %23, %24, %25, %26, %27, %28, %29, %30, %31, %32, %33, %34, %35, %36, %37, %38, %39, %40, %41, %42, %43, %44, %45, %46, %47, %48, %49, %50, %51, %52, %53, %54, %55, %56, %57, %58, %59, %60, %61, %62, %63}, "
    "%64, %65, 1, 1, 1, 0, 1;\n"
    : "+f"(d[0]), "+f"(d[1]), "+f"(d[2]), "+f"(d[3]), "+f"(d[4]), "+f"(d[5]), "+f"(d[6]), "+f"(d[7]), "+f"(d[8]), "+f"(d[9]), "+f"(d[10]), "+f"(d[11]), "+f"(d[12]), "+f"(d[13]), "+f"(d[14]), "+f"(d[15]), "+f"(d[16]), "+f"(d[17]), "+f"(d[18]), "+f"(d[19]), "+f"(d[20]), "+f"(d[21]), "+f"(d[22]), "+f"(d[23]), "+f"(d[24]), "+f"(d[25]), "+f"(d[26]), "+f"(d[27]), "+f"(d[28]), "+f"(d[29]), "+f"(d[30]), "+f"(d[31]), "+f"(d[32]), "+f"(d[33]), "+f"(d[34]), "+f"(d[35]), "+f"(d[36]), "+f"(d[37]), "+f"(d[38]), "+f"(d[39]), "+f"(d[40]), "+f"(d[41]), "+f"(d[42]), "+f"(d[43]), "+f"(d[44]), "+f"(d[45]), "+f"(d[46]), "+f"(d[47]), "+f"(d[48]), "+f"(d[49]), "+f"(d[50]), "+f"(d[51]), "+f"(d[52]), "+f"(d[53]), "+f"(d[54]), "+f"(d[55]), "+f"(d[56]), "+f"(d[57]), "+f"(d[58]), "+f"(d[59]), "+f"(d[60]), "+f"(d[61]), "+f"(d[62]), "+f"(d[63])
    : "l"(da), "l"(db));
}
__device__ __forceinline__ void wgmma_n128_first(float (&d)[64], uint64_t da, uint64_t db) {
  asm volatile("wgmma.mma_async.sync.aligned.m64n128k16.f32.bf16.bf16 "
    "{%0, %1, %2, %3, %4, %5, %6, %7, %8, %9, %10, %11, %12, %13, %14, %15, %16, %17, %18, %19, %20, %21, %22, %23, %24, %25, %26, %27, %28, %29, %30, %31, %32, %33, %34, %35, %36, %37, %38, %39, %40, %41, %42, %43, %44, %45, %46, %47, %48, %49, %50, %51, %52, %53, %54, %55, %56, %57, %58, %59, %60, %61, %62, %63}, "
    "%64, %65, 0, 1, 1, 0, 1;\n"
    : "=f"(d[0]), "=f"(d[1]), "=f"(d[2]), "=f"(d[3]), "=f"(d[4]), "=f"(d[5]), "=f"(d[6]), "=f"(d[7]), "=f"(d[8]), "=f"(d[9]), "=f"(d[10]), "=f"(d[11]), "=f"(d[12]), "=f"(d[13]), "=f"(d[14]), "=f"(d[15]), "=f"(d[16]), "=f"(d[17]), "=f"(d[18]), "=f"(d[19]), "=f"(d[20]), "=f"(d[21]), "=f"(d[22]), "=f"(d[23]), "=f"(d[24]), "=f"(d[25]), "=f"(d[26]), "=f"(d[27]), "=f"(d[28]), "=f"(d[29]), "=f"(d[30]), "=f"(d[31]), "=f"(d[32]), "=f"(d[33]), "=f"(d[34]), "=f"(d[35]), "=f"(d[36]), "=f"(d[37]), "=f"(d[38]), "=f"(d[39]), "=f"(d[40]), "=f"(d[41]), "=f"(d[42]), "=f"(d[43]), "=f"(d[44]), "=f"(d[45]), "=f"(d[46]), "=f"(d[47]), "=f"(d[48]), "=f"(d[49]), "=f"(d[50]), "=f"(d[51]), "=f"(d[52]), "=f"(d[53]), "=f"(d[54]), "=f"(d[55]), "=f"(d[56]), "=f"(d[57]), "=f"(d[58]), "=f"(d[59]), "=f"(d[60]), "=f"(d[61]), "=f"(d[62]), "=f"(d[63])
    : "l"(da), "l"(db));
}
__device__ __forceinline__ void wgmma_n256(float (&d)[128], uint64_t da, uint64_t db) {
  asm volatile("wgmma.mma_async.sync.aligned.m64n256k16.f32.bf16.bf16 "
    "{%0, %1, %2, %3, %4, %5, %6, %7, %8, %9, %10, %11, %12, %13, %14, %15, %16, %17, %18, %19, %20, %21, %22, %23, %24, %25, %26, %27, %28, %29, %30, %31, %32, %33, %34, %35, %36, %37, %38, %39, %40, %41, %42, %43, %44, %45, %46, %47, %48, %49, %50, %51, %52, %53, %54, %55, %56, %57, %58, %59, %60, %61, %62, %63, %64, %65, %66, %67, %68, %69, %70, %71, %72, %73, %74, %75, %76, %77, %78, %79, %80, %81, %82, %83, %84, %85, %86, %87, %88, %89, %90, %91, %92, %93, %94, %95, %96, %97, %98, %99, %100, %101, %102, %103, %104, %105, %106, %107, %108, %109, %110, %111, %112, %113, %114, %115, %116, %117, %118, %119, %120, %121, %122, %123, %124, %125, %126, %127}, "
    "%128, %129, 1, 1, 1, 0, 1;\n"
    : "+f"(d[0]), "+f"(d[1]), "+f"(d[2]), "+f"(d[3]), "+f"(d[4]), "+f"(d[5]), "+f"(d[6]), "+f"(d[7]), "+f"(d[8]), "+f"(d[9]), "+f"(d[10]), "+f"(d[11]), "+f"(d[12]), "+f"(d[13]), "+f"(d[14]), "+f"(d[15]), "+f"(d[16]), "+f"(d[17]), "+f"(d[18]), "+f"(d[19]), "+f"(d[20]), "+f"(d[21]), "+f"(d[22]), "+f"(d[23]), "+f"(d[24]), "+f"(d[25]), "+f"(d[26]), "+f"(d[27]), "+f"(d[28]), "+f"(d[29]), "+f"(d[30]), "+f"(d[31]), "+f"(d[32]), "+f"(d[33]), "+f"(d[34]), "+f"(d[35]), "+f"(d[36]), "+f"(d[37]), "+f"(d[38]), "+f"(d[39]), "+f"(d[40]), "+f"(d[41]), "+f"(d[42]), "+f"(d[43]), "+f"(d[44]), "+f"(d[45]), "+f"(d[46]), "+f"(d[47]), "+f"(d[48]), "+f"(d[49]), "+f"(d[50]), "+f"(d[51]), "+f"(d[52]), "+f"(d[53]), "+f"(d[54]), "+f"(d[55]), "+f"(d[56]), "+f"(d[57]), "+f"(d[58]), "+f"(d[59]), "+f"(d[60]), "+f"(d[61]), "+f"(d[62]), "+f"(d[63]), "+f"(d[64]), "+f"(d[65]), "+f"(d[66]), "+f"(d[67]), "+f"(d[68]), "+f"(d[69]), "+f"(d[70]), "+f"(d[71]), "+f"(d[72]), "+f"(d[73]), "+f"(d[74]), "+f"(d[75]), "+f"(d[76]), "+f"(d[77]), "+f"(d[78]), "+f"(d[79]), "+f"(d[80]), "+f"(d[81]), "+f"(d[82]), "+f"(d[83]), "+f"(d[84]), "+f"(d[85]), "+f"(d[86]), "+f"(d[87]), "+f"(d[88]), "+f"(d[89]), "+f"(d[90]), "+f"(d[91]), "+f"(d[92]), "+f"(d[93]), "+f"(d[94]), "+f"(d[95]), "+f"(d[96]), "+f"(d[97]), "+f"(d[98]), "+f"(d[99]), "+f"(d[100]), "+f"(d[101]), "+f"(d[102]), "+f"(d[103]), "+f"(d[104]), "+f"(d[105]), "+f"(d[106]), "+f"(d[107]), "+f"(d[108]), "+f"(d[109]), "+f"(d[110]), "+f"(d[111]), "+f"(d[112]), "+f"(d[113]), "+f"(d[114]), "+f"(d[115]), "+f"(d[116]), "+f"(d[117]), "+f"(d[118]), "+f"(d[119]), "+f"(d[120]), "+f"(d[121]), "+f"(d[122]), "+f"(d[123]), "+f"(d[124]), "+f"(d[125]), "+f"(d[126]), "+f"(d[127])
    : "l"(da), "l"(db));
}
__device__ __forceinline__ void wgmma_n256_first(float (&d)[128], uint64_t da, uint64_t db) {
  asm volatile("wgmma.mma_async.sync.aligned.m64n256k16.f32.bf16.bf16 "
    "{%0, %1, %2, %3, %4, %5, %6, %7, %8, %9, %10, %11, %12, %13, %14, %15, %16, %17, %18, %19, %20, %21, %22, %23, %24, %25, %26, %27, %28, %29, %30, %31, %32, %33, %34, %35, %36, %37, %38, %39, %40, %41, %42, %43, %44, %45, %46, %47, %48, %49, %50, %51, %52, %53, %54, %55, %56, %57, %58, %59, %60, %61, %62, %63, %64, %65, %66, %67, %68, %69, %70, %71, %72, %73, %74, %75, %76, %77, %78, %79, %80, %81, %82, %83, %84, %85, %86, %87, %88, %89, %90, %91, %92, %93, %94, %95, %96, %97, %98, %99, %100, %101, %102, %103, %104, %105, %106, %107, %108, %109, %110, %111, %112, %113, %114, %115, %116, %117, %118, %119, %120, %121, %122, %123, %124, %125, %126, %127}, "
    "%128, %129, 0, 1, 1, 0, 1;\n"
    : "=f"(d[0]), "=f"(d[1]), "=f"(d[2]), "=f"(d[3]), "=f"(d[4]), "=f"(d[5]), "=f"(d[6]), "=f"(d[7]), "=f"(d[8]), "=f"(d[9]), "=f"(d[10]), "=f"(d[11]), "=f"(d[12]), "=f"(d[13]), "=f"(d[14]), "=f"(d[15]), "=f"(d[16]), "=f"(d[17]), "=f"(d[18]), "=f"(d[19]), "=f"(d[20]), "=f"(d[21]), "=f"(d[22]), "=f"(d[23]), "=f"(d[24]), "=f"(d[25]), "=f"(d[26]), "=f"(d[27]), "=f"(d[28]), "=f"(d[29]), "=f"(d[30]), "=f"(d[31]), "=f"(d[32]), "=f"(d[33]), "=f"(d[34]), "=f"(d[35]), "=f"(d[36]), "=f"(d[37]), "=f"(d[38]), "=f"(d[39]), "=f"(d[40]), "=f"(d[41]), "=f"(d[42]), "=f"(d[43]), "=f"(d[44]), "=f"(d[45]), "=f"(d[46]), "=f"(d[47]), "=f"(d[48]), "=f"(d[49]), "=f"(d[50]), "=f"(d[51]), "=f"(d[52]), "=f"(d[53]), "=f"(d[54]), "=f"(d[55]), "=f"(d[56]), "=f"(d[57]), "=f"(d[58]), "=f"(d[59]), "=f"(d[60]), "=f"(d[61]), "=f"(d[62]), "=f"(d[63]), "=f"(d[64]), "=f"(d[65]), "=f"(d[66]), "=f"(d[67]), "=f"(d[68]), "=f"(d[69]), "=f"(d[70]), "=f"(d[71]), "=f"(d[72]), "=f"(d[73]), "=f"(d[74]), "=f"(d[75]), "=f"(d[76]), "=f"(d[77]), "=f"(d[78]), "=f"(d[79]), "=f"(d[80]), "=f"(d[81]), "=f"(d[82]), "=f"(d[83]), "=f"(d[84]), "=f"(d[85]), "=f"(d[86]), "=f"(d[87]), "=f"(d[88]), "=f"(d[89]), "=f"(d[90]), "=f"(d[91]), "=f"(d[92]), "=f"(d[93]), "=f"(d[94]), "=f"(d[95]), "=f"(d[96]), "=f"(d[97]), "=f"(d[98]), "=f"(d[99]), "=f"(d[100]), "=f"(d[101]), "=f"(d[102]), "=f"(d[103]), "=f"(d[104]), "=f"(d[105]), "=f"(d[106]), "=f"(d[107]), "=f"(d[108]), "=f"(d[109]), "=f"(d[110]), "=f"(d[111]), "=f"(d[112]), "=f"(d[113]), "=f"(d[114]), "=f"(d[115]), "=f"(d[116]), "=f"(d[117]), "=f"(d[118]), "=f"(d[119]), "=f"(d[120]), "=f"(d[121]), "=f"(d[122]), "=f"(d[123]), "=f"(d[124]), "=f"(d[125]), "=f"(d[126]), "=f"(d[127])
    : "l"(da), "l"(db));
}

template <int N> struct WG;
#define DEF_WG(N) template <> struct WG<N> { \
  static __device__ __forceinline__ void mma(float (&d)[N / 2], uint64_t a, uint64_t b) { wgmma_n##N(d, a, b); } \
  static __device__ __forceinline__ void first(float (&d)[N / 2], uint64_t a, uint64_t b) { wgmma_n##N##_first(d, a, b); } };
DEF_WG(128) DEF_WG(256)

constexpr uint64_t DESC_A = (1ull << 62) | ((uint64_t)(1024 >> 4) << 32) | (1ull << 16);
constexpr uint64_t DESC_B = (1ull << 62) | ((uint64_t)(1024 >> 4) << 32) | ((uint64_t)(8192 >> 4) << 16);

struct Ring { int s; uint32_t ph; int wrap; };
template <int NS> __device__ __forceinline__ void ring_next(Ring& r) { r.s = (r.s + 1 == NS) ? 0 : r.s + 1; if (r.s == r.wrap) r.ph ^= 1; }

__device__ __forceinline__ int own_order(int it, int j) {
  return it < 2 ? 2 * j + it : it < 4 ? 2 * (j ^ 1) + it - 2 : ((j >> 1) * 4 + 2 * it - (it < 10 ? 4 : 15)) & 15;
}

template <int V> struct IC { static constexpr int v = V; };
template <int I, int E, class F> __device__ __forceinline__ void static_for(F&& f) { if constexpr (I < E) { f(IC<I>{}); static_for<I + 1, E>(f); } }

template <int N, int NS, int PRE, int LAG, class Pre, class Mid, class Last>
__device__ __forceinline__ void mainloop(float (&acc)[N / 2], int nkb, bool own, Ring& r, uint32_t sb, int wg, int lane, uint32_t rel_base, Pre pre, Mid mid, Last last, int lag_par = 0) {
  constexpr int SLOT = RING / NS;
  const uint32_t full = sb + MISC + (NS == 4 ? B_FULL4 : B_FULL6);
  const uint32_t rel = rel_base + (NS == 4 ? B_EMPTY4 : B_EMPTY6);
  const uint32_t s0 = (sb & 0x3FFFF) >> 4, a0 = s0 + wg * (HALF >> 4);
  int ps;
  auto issue = [&](int it, bool first) {
    const uint64_t da = DESC_A | (a0 + ((own && it < 2) ? (STG + it * BLK) >> 4 : r.s * (SLOT >> 4))), db = DESC_B | (s0 + r.s * (SLOT >> 4) + (BLK >> 4));
    mbar_wait(full + r.s * 8, r.ph);
    wg_arrive();
    if (first) WG<N>::first(acc, da, db); else WG<N>::mma(acc, da, db);
#pragma unroll
    for (int k = 1; k < 4; k++) WG<N>::mma(acc, da + k * 2, db + k * 128);
    wg_commit();
  };
  auto retire = [&](int it) {
    wg_wait<1>();
    if (lane < 2) mbar_arrive_cl(rel + ps * 8);
    ps = r.s;
    ring_next<NS>(r);
  };
  issue(0, true);
  ps = r.s;
  ring_next<NS>(r);
  static_for<1, PRE + 1>([&](auto ic) { issue(ic.v, false); pre(ic); retire(ic.v); });
#pragma unroll 1
  for (int it = PRE + 1; it < nkb; it++) {
    if (LAG && it == nkb - LAG && wg == 1) mbar_wait(sb + MISC + B_LAG, lag_par);
    issue(it, false); mid(it); retire(it);
  }
  if (LAG && wg == 0 && lane == 0) mbar_arrive(sb + MISC + B_LAG);
  last();
  wg_wait<0>();
#pragma unroll
  for (int i = 0; i < N / 2; i++) asm volatile("" : "+f"(acc[i]) :: "memory");
  if (lane < 2) mbar_arrive_cl(rel + ps * 8);
}

__device__ __forceinline__ uint32_t tag_of(uint32_t ep) { return (ep & 127u) + 1u; }
__device__ __forceinline__ void ln_publish(const float (&v)[64], uint2* st, int j, int row0, int lane, uint32_t ep) {
  float s0 = 0, s1 = 0, s2 = 0, s3 = 0, q0 = 0, q1 = 0, q2 = 0, q3 = 0;
#pragma unroll
  for (int i = 0; i < 16; i++) {
    s0 += v[4 * i]; s1 += v[4 * i + 1]; s2 += v[4 * i + 2]; s3 += v[4 * i + 3];
    q0 = fmaf(v[4 * i], v[4 * i], q0); q1 = fmaf(v[4 * i + 1], v[4 * i + 1], q1); q2 = fmaf(v[4 * i + 2], v[4 * i + 2], q2); q3 = fmaf(v[4 * i + 3], v[4 * i + 3], q3);
  }
  s0 += s1; s2 += s3; q0 += q1; q2 += q3;
  const bool odd = lane & 1;
  float s = (odd ? s2 : s0) + __shfl_xor_sync(~0u, odd ? s0 : s2, 1), q = (odd ? q2 : q0) + __shfl_xor_sync(~0u, odd ? q0 : q2, 1);
  s += __shfl_xor_sync(~0u, s, 2); q += __shfl_xor_sync(~0u, q, 2);
  if ((lane & 3) < 2) st_rlx2(st + j * 128 + row0 + (lane & 1) * 8, __float_as_uint(s), (__float_as_uint(fmaf(s * (-1.f / 128), s, q)) & ~255u) | tag_of(ep));
}
__device__ __forceinline__ void ln_gather(const uint2* st, int row0, int lane, uint32_t ep, float& n0, float& r0, float& n1, float& r1, bool rnd) {
  const uint2* p = st + (lane & 2) * 256 + row0 + (lane & 1) * 8;
  const uint32_t tag = tag_of(ep);
  uint2 a, b, c, d; uint32_t n = 0;
  while (true) {
    a = ld_rlx2(p); b = ld_rlx2(p + 128); c = ld_rlx2(p + 256); d = ld_rlx2(p + 384);
    if ((((a.y ^ tag) | (b.y ^ tag) | (c.y ^ tag) | (d.y ^ tag)) & 255u) == 0) break;
    SPIN_GUARD(n);
  }
  __syncwarp();
  const uint32_t fix = tag ^ 128u;
  float s = (__uint_as_float(a.x) + __uint_as_float(b.x)) + (__uint_as_float(c.x) + __uint_as_float(d.x));
  float q = (__uint_as_float(a.y ^ fix) + __uint_as_float(b.y ^ fix)) + (__uint_as_float(c.y ^ fix) + __uint_as_float(d.y ^ fix));
  q = fmaf(fmaf(__uint_as_float(a.x), __uint_as_float(a.x), __uint_as_float(b.x) * __uint_as_float(b.x)) +
           fmaf(__uint_as_float(c.x), __uint_as_float(c.x), __uint_as_float(d.x) * __uint_as_float(d.x)), 1.f / 128, q);
  s += __shfl_xor_sync(~0u, s, 2); q += __shfl_xor_sync(~0u, q, 2);
  s *= 1.f / 1024;
  const float var = fmaxf(fmaf(-s, s, q * (1.f / 1024)), 0.f);
  float r;
  if (rnd) {
    float sd; asm("sqrt.approx.f32 %0, %1;" : "=f"(sd) : "f"(bf_round(bf_round(var) + 1e-5f)));
    r = rcp(bf_round(sd)); s = bf_round(s);
  } else r = rsqrtf(var + 1e-5f);
  const float nn = -s * r;
  const float ro = __shfl_xor_sync(~0u, r, 1), no = __shfl_xor_sync(~0u, nn, 1);
  const bool odd = lane & 1;
  r0 = odd ? ro : r; n0 = odd ? no : nn; r1 = odd ? r : ro; n1 = odd ? nn : no;
}
__device__ __forceinline__ void load_vec(uint32_t* w, uint32_t sb, int sec, int b, int lane) {
#pragma unroll
  for (int q = 0; q < 2; q++) { uint4 t = lds128(sb + MISC + MODV + sec * 256 + (lane & 3) * 64 + b * 32 + q * 16); w[4 * q] = t.x; w[4 * q + 1] = t.y; w[4 * q + 2] = t.z; w[4 * q + 3] = t.w; }
}
__device__ __forceinline__ void stage_done(uint32_t sb, int wg, int b, int lane) {
  fence_async_smem();
  __syncwarp();
  if (lane == 0) mbar_arrive(sb + MISC + B_RDY + b * 8);
}
__device__ __forceinline__ uint32_t hfma2(uint32_t a, uint32_t b, uint32_t c) { uint32_t r; asm("fma.rn.bf16x2 %0, %1, %2, %3;" : "=r"(r) : "r"(a), "r"(b), "r"(c)); return r; }
__device__ __forceinline__ void ln_apply(const float (&v)[64], const uint2* st, int row0, uint32_t ep, uint32_t sb, int sec_shift, int sec_scale, uint32_t stg_row, int wg, int lane) {
  uint32_t sc[16], sh[16];
#pragma unroll
  for (int b = 0; b < 2; b++) { load_vec(sc + 8 * b, sb, sec_scale, b, lane); load_vec(sh + 8 * b, sb, sec_shift, b, lane); }
  float n0, r0, n1, r1;
  ln_gather(st, row0, lane, ep, n0, r0, n1, r1, sec_shift == 0);
#pragma unroll
  for (int i = 0; i < 16; i += 2) {
    if (i == 8) { const float z = lds32f(sb + MISC + ZERO); n0 += z; n1 += z; }
    uint32_t w[4];
#pragma unroll
    for (int u = 0; u < 2; u++) {
      int q = i + u;
      w[2 * u] = hfma2(pack2(fmaf(v[4 * q], r0, n0), fmaf(v[4 * q + 1], r0, n0)), sc[q], sh[q]);
      w[2 * u + 1] = hfma2(pack2(fmaf(v[4 * q + 2], r1, n1), fmaf(v[4 * q + 3], r1, n1)), sc[q], sh[q]);
    }
    stsm4(stg_row + (i >> 3) * BLK + ((((i & 7) + (lane >> 4)) ^ (lane & 7)) << 4), w[0], w[1], w[2], w[3]);
    if ((i & 7) == 6) { stage_done(sb, wg, i >> 3, lane); }
  }
}
__device__ __forceinline__ uint32_t hmul2(uint32_t a, uint32_t b) { uint32_t r; asm("mul.rn.bf16x2 %0, %1, %2;" : "=r"(r) : "r"(a), "r"(b)); return r; }
__device__ __forceinline__ uint32_t silu_mul2(uint32_t g, uint32_t u) {
  const uint32_t h = hmul2(g, 0x3f003f00u);
  const float h0 = bf_lo(h), h1 = bf_hi(h);
  return hmul2(pack2(fmaf(h0, tanh_fast(h0), h0), fmaf(h1, tanh_fast(h1), h1)), u);
}

__device__ __forceinline__ void gemv_fma(float (&a)[8], uint4 w, float s) {
  a[0] = fmaf(bf_lo(w.x), s, a[0]); a[1] = fmaf(bf_hi(w.x), s, a[1]); a[2] = fmaf(bf_lo(w.y), s, a[2]); a[3] = fmaf(bf_hi(w.y), s, a[3]);
  a[4] = fmaf(bf_lo(w.z), s, a[4]); a[5] = fmaf(bf_hi(w.z), s, a[5]); a[6] = fmaf(bf_lo(w.w), s, a[6]); a[7] = fmaf(bf_hi(w.w), s, a[7]);
}
__device__ __forceinline__ float silu_c(float v) { return bf_round(__fdividef(v, 1.f + __expf(-v))); }
__device__ __forceinline__ float mod_gather(const uint32_t* p, uint32_t ep) {
  const uint32_t tag = tag_of(ep), fix = tag ^ 128u;
  uint32_t a, b, c, d, n = 0;
  while (true) {
    a = ld_rlx1(p); b = ld_rlx1(p + 2048); c = ld_rlx1(p + 4096); d = ld_rlx1(p + 6144);
    if ((((a ^ tag) | (b ^ tag) | (c ^ tag) | (d ^ tag)) & 255u) == 0) break;
    SPIN_GUARD(n);
  }
  return (__uint_as_float(a ^ fix) + __uint_as_float(b ^ fix)) + (__uint_as_float(c ^ fix) + __uint_as_float(d ^ fix));
}
__device__ __forceinline__ void mod_store(uint32_t sb, int sec, int col, float v) {
  v = bf_round(v);
  if (sec == 1) v += 1.f;
  sts16(sb + MISC + MODV + sec * 256 + (((col >> 1) & 3) * 16 + (col >> 3)) * 4 + (col & 1) * 2, __float2bfloat16_rn(v));
}

__global__ void __cluster_dims__(2, 1, 1) __launch_bounds__(384, 1)
fused_kernel(const bf16* __restrict__ cvec, const bf16* __restrict__ wmod, Scratch* gs, int by_sm, const __grid_constant__ Maps maps) {
  extern __shared__ __align__(1024) uint8_t smem_raw[];
  uint32_t sm; asm volatile("mov.u32 %0, %%smid;" : "=r"(sm));
  const uint32_t id = by_sm ? sm : blockIdx.x, xs = by_sm ? 112 + 8 * by_sm : 0, u = id < xs ? id : id - 4;
  const bool extra = id - xs < 4;
  uint4 wv[8];
  uint32_t ep0; uint16_t cv_;
  if (threadIdx.x < 256) {
    const int r0 = ((u >> 5) & 3) * 256 + (threadIdx.x & 224);
    asm volatile("ld.global.nc.u16 %0, [%1];" : "=h"(cv_) : "l"(cvec + r0 + (threadIdx.x & 31)));
    asm volatile("ld.global.u32 %0, [%1];" : "=r"(ep0) : "l"(gs->epoch + (blockIdx.x | (threadIdx.x & by_sm & 4))));
    if (!extra) {
      const bf16* wp = wmod + (r0 + ((threadIdx.x >> 3) & 3)) * 6144 + (u & 31) * 64 + (threadIdx.x & 7) * 8;
#pragma unroll
      for (int i = 0; i < 8; i++) wv[i] = ldg_nc(wp + i * 4 * 6144);
    }
  }
  const uint32_t sb = smem_u32(smem_raw);
  const int warp = __shfl_sync(~0u, threadIdx.x >> 5, 0), lane = threadIdx.x & 31;
  const int rank = blockIdx.x & 1;
  const int t = sm >> 1, v = t < 32 || by_sm == 2 ? t : t < 60 ? t + 1 + (((t - 32) * 37) >> 8) : (t - 58) * 8;
  const int gr = 0x71546320u >> ((v & 7) * 4);
  const int cid = !by_sm ? (blockIdx.x >> 1) - 2 : extra ? (t & 1) - 2 : (gr & 4) * 8 + (v >> 3) * 4 + (gr & 3);
  const int bid = cid * 2 + rank;
  const int m = cid >> 2, j = (cid & 3) * 2 + rank;
  const uint32_t bar = sb + MISC;

  if (warp >= 8) {
    asm volatile("setmaxnreg.dec.sync.aligned.u32 40;");
    if (extra) {
      if (warp == 8) {
        if (lane == 0) { for (int s = 0; s < 6; s++) { mbar_init(bar + B_FULL6 + s * 8, 1); mbar_init(bar + B_EMPTY6 + s * 8, 8); } fence_async_smem(); }
        __syncwarp();
        asm volatile("bar.arrive 2, 288;" ::: "memory");
        __nanosleep(XSLEEP);
#pragma unroll 1
        for (int it = 0, s = 0, par = 1; it < 64; it++) {
          mbar_wait(bar + B_EMPTY6 + s * 8, par);
          expect_e(bar + B_FULL6 + s * 8, 32768); tma_3d_e(sb + s * 32768, &maps.wmod, bar + B_FULL6 + s * 8, 0, (it & 15) * 64, 12 + (it >> 4) * 4 + bid);
          if (++s == 6) { s = 0; par ^= 1; }
        }
      }
    } else if (warp < 10) {
      uint32_t f6 = bar + B_FULL6, d6 = sb + (warp == 8 ? BLK : rank * HALF), p6 = 1;
      auto next6 = [&]() { f6 += 8; d6 += 32768; if (f6 == bar + B_FULL6 + 48) { f6 -= 48; d6 -= RING; p6 ^= 1; } };
      auto drained4 = [&](int q, int late) { if (q < 5) mbar_wait(bar + B_EMPTY4 + (((late ? 0x10332 : 0x32110) >> (4 * q)) & 3) * 8, 1); };
      auto drained6 = [&](int q) { if (q < 3) mbar_wait(bar + B_EMPTY6 + ((0x154 >> (4 * q)) & 7) * 8, q >> 1); };
      auto skip6 = [&]() { mbar_wait(f6 + 48, p6); expect_e(f6, 0); next6(); };
      if (warp == 8) {
        if (lane == 0) {
          if (sb & 1023) bail();
          for (int b = 0; b < 2; b++) mbar_init(bar + B_X + b * 8, 1);
          for (int s = 0; s < 4; s++) { mbar_init(bar + B_FULL4 + s * 8, 2); mbar_init(bar + B_EMPTY4 + s * 8, 16); }
          for (int s = 0; s < 6; s++) { mbar_init(bar + B_FULL6 + s * 8, 2); mbar_init(bar + B_EMPTY6 + s * 8, 16); }
          for (int b = 0; b < 2; b++) { mbar_init(bar + B_RDY + b * 8, 8); mbar_init(bar + B_FREE + b * 8, 1); mbar_init(bar + B_HH + b * 8, 1); mbar_init(bar + B_OUT + b * 8, 2); mbar_init(bar + B_HALO + b * 8, 1); }
          mbar_init(bar + B_MOD, 1); mbar_init(bar + B_LAG, 4); mbar_init(bar + B_ALL, 1); mbar_init(bar + B_HH2, 1);
          asm volatile("st.shared.u32 [%0], 0;" :: "r"(bar + ZERO) : "memory");
          asm volatile("fence.mbarrier_init.release.cluster;" ::: "memory");
          fence_async_smem();
        }
        __syncwarp();
        cl_arrive_relaxed();
        for (int b = 0; b < 2; b++) { expect_e(bar + B_X + b * 8, BLK); tma_3d_e(sb + STG + b * BLK, &maps.x, bar + B_X + b * 8, j * 128 + b * 64, m * 64, 0); }
        mbar_wait(bar + B_X + 8, 0);
#pragma unroll 1
        for (int ph = 0; ph < 2; ph++) {
          const CUtensorMap* const m0 = ph ? &maps.w1 : &maps.wqkv;
#pragma unroll 1
          for (int it = 0; it < (ph ? 48 : 16); it++) {
            const int s = (it + 2 * ph) & 3;
            int a0 = (ph ? it & 48 : 16) + 2 * j, a1 = ph ? a0 : a0 + 16, k0 = (it < 16 ? own_order(it, j) : it & 15) * 64;
            uint32_t full = bar + B_FULL4 + s * 8, d = sb + s * 49152 + BLK;
            if (ph) drained6(it);
            mbar_wait(full + 32, ~(it >> 2) & 1);
            tma_3d_e(d, m0, full, 0, k0, a0);
            if (it < 4) { const uint32_t t0 = clock(); while ((uint32_t)clock() - t0 < GAP) {} }
            tma_3d_e(d + BLK, m0 + ph, full, 0, k0, a1);
            expect_e(full, 2 * BLK);
            if (it < 4) { const uint32_t t0 = clock(); while ((uint32_t)clock() - t0 < GAP) {} }
            if (it >= 44) {
              if (it == 44) { mbar_wait(bar + B_FREE, 0); mbar_wait(bar + B_FREE + 8, 0); expect_e(bar + B_X, 2 * BLK); }
              bulk_ld_e(sb + STG + (it - 44) * HALF, gs->x1 + bid * 2048 + (it - 44) * 512, HALF, bar + B_X);
            }
          }
          const CUtensorMap* const m1 = ph ? &maps.w1s : &maps.wqkv;
          const int a = ph ? 48 + j : 2 * j;
#pragma unroll 1
          for (int k0 = 0; k0 < 1024; k0 += 64) {
            drained4(k0 >> 6, ph);
            mbar_wait(f6 + 48, p6);
            tma_3d_e(d6, m1, f6, 0, k0, a);
            if (ph) tma_3d_e(d6 + HALF, &maps.w3s, f6, 0, k0, a);
            expect_e(f6, BLK);
            next6();
          }
          if (ph) break;
#pragma unroll 1
          for (int it = 0; it < 16; it++) {
            const int k0 = own_order(it, j) * 64;
            mbar_wait(f6 + 48, p6);
            tma_3d_e(d6, &maps.wo, f6, 0, k0, 2 * j);
            expect_e(f6, BLK);
            next6();
          }
          skip6();
        }
#pragma unroll 1
        for (int k0 = 0; k0 < F_; k0 += 64) {
          mbar_wait(f6 + 48, p6);
          tma_3d_e(d6, &maps.w2, f6, 0, k0, 2 * j);
          expect_e(f6, BLK);
          next6();
        }
      } else {
        if (lane < 9) prefetch_map(&maps.x + lane);
        const uint32_t ep = gs->epoch[blockIdx.x] + 1;
        cl_arrive_relaxed(); cl_wait();
        auto run6 = [&](const uint4* src, int n, int sw) {
          src += rank * 512;
#pragma unroll 1
          for (int it = 0; it < n; it++) {
            if (sw >= 0) drained4(it, sw);
            mbar_wait(f6 + 48, p6);
            bulk_ld_mc_e(d6, src, HALF, f6);
            expect_e(f6, BLK);
            next6();
            src += 1024;
          }
        };
        uint32_t ready = 0;
        auto need = [&](int e, uint32_t mask) {
          if (!(ready & mask)) {
            uint32_t n = 0;
            do { ready = __ballot_sync(~0u, ld_acquire(gs->flag + (m * 128 + e * 16 + (lane & 14)) * FS) == ep); SPIN_GUARD(n); } while (!(ready & mask));
            fence_async_global();
          }
        };
        auto fresh = [&](int e, int it, uint32_t full, uint32_t empty, int par, uint32_t slot, uint4* src) {
          mbar_wait(empty, par);
          expect_e(full, it < 2 ? 0 : BLK);
          if (it >= 4) {
            const int kb = own_order(it, j);
            if (it < 10) need(e, 1u << kb); else if (it == 10) mbar_wait(bar + B_ALL, e & 1);
            bulk_ld_mc_e(slot + rank * HALF, src + kb * 1024 + rank * 512, HALF, full);
          } else if (it >= 2) {
            const int b = it > 2;
            const uint32_t to_peer = mapa(sb, rank ^ 1) - sb;
            const bool push = b && e != 1;
            mbar_wait(bar + (push ? B_RDY : B_FREE) + b * 8, e & 1);
            if (push) bulk_push_e(slot + to_peer, sb + STG + BLK, BLK, full + to_peer);
            else { fence_async_global(); bulk_ld_e(slot + to_peer, src + (2 * j + b) * 1024, BLK, full + to_peer); }
          } else ready = 0;
        };
        uint4* const h = gs->h + m * 16384;
#pragma unroll 1
        for (int e = 0; e < 3; e++) {
#pragma unroll 1
          for (int it = 0; it < 16; it++) {
            const int s = (it + e) & 3;
            const uint32_t full = e == 1 ? f6 : bar + B_FULL4 + s * 8;
            if (e == 2) drained6(it);
            fresh(e, it, full, full + (e == 1 ? 48 : 32), e == 1 ? p6 : ~(it >> 2) & 1, e == 1 ? d6 - rank * HALF : sb + s * 49152, e == 1 ? gs->o + m * 16384 : h);
            if (e == 1) next6();
          }
          if (e == 1) { skip6(); continue; }
#pragma unroll 1
          for (int it = 16; it < 16 + 16 * e; it++) {
            const int s = (it + 2) & 3;
            const uint32_t full = bar + B_FULL4 + s * 8;
            mbar_wait(full + 32, ~(it >> 2) & 1);
            bulk_ld_mc_e(sb + s * 49152 + rank * HALF, h + (it & 15) * 1024 + rank * 512, HALF, full);
            expect_e(full, BLK);
          }
          run6(h, 16, e);
        }
#pragma unroll 1
        for (int q = 0; q < 3; q++) {
          mbar_wait(bar + (q == 2 ? B_HH2 : B_HH + q * 8), 0);
          run6(gs->hh + m * 57344 + (64 - (64 >> q)) * 1024, 32 >> q, -1);
        }
      }
    } else {
      const int b = warp - 10;
      const uint32_t ep = gs->epoch[blockIdx.x] + 1;
      const uint32_t stg = sb + STG + b * BLK;
      cl_arrive_relaxed(); cl_wait();
      auto all_there = [&](int u, uint32_t done) {
        const uint32_t* fl = gs->flag + u * FS;
        uint32_t n = 0;
        while (!__all_sync(~0u, ld_acquire(fl) == ep)) { __nanosleep(100); SPIN_GUARD(n); }
        fence_async_global();
        arrive_e(done);
      };
#pragma unroll 1
      for (int e = 0; e < 7 - b; e++) {
        const int kb = (e < 3 ? 2 * j : e < 6 ? 2 * (8 * (e - 3) + j) : 48 + j) + b;
        uint4* const dst = (e == 1 ? gs->o + m * 16384 : e < 3 ? gs->h + m * 16384 : gs->hh + m * 57344) + kb * 1024;
        uint32_t* const fl = gs->flag + (m * 128 + (e < 3 ? e * 16 : U_HH) + kb) * FS;
        if (e < 3 && lane < 8) st_rlx1(fl + lane, 0);
        if (b && e < 3) {
          mbar_wait(bar + B_FREE, e & 1);
          const uint32_t t0 = clock();
          while ((uint32_t)clock() - t0 < (e == 1 ? B1D : B1P)) {}
        }
        mbar_wait(bar + B_RDY + b * 8, e & 1);
        bulk_st_e(dst, stg, e < 3 ? BLK : BLK / NPIECE);
        if (e >= 3) {
#pragma unroll 1
          for (int q = 1; q < NPIECE; q++) { __nanosleep(PSLEEP); bulk_st_e(dst + q * (1024 / NPIECE), stg + q * (BLK / NPIECE), BLK / NPIECE); }
        }
        publish_e(bar + B_FREE + b * 8, fl, ep);
        if (b && (e < 3 || e == 4)) all_there(m * 128 + (e < 3 ? e * 16 + (lane & 15) : U_HH + lane), bar + (e < 3 ? B_ALL : B_HH));
        if (!b && (e == 1 || e == 2)) {
#pragma unroll 1
          for (int sec = e == 1 ? 2 : 5; sec < 4 + e; sec++) {
            const uint4* p = (const uint4*)(gs->modv + (sec - 2) * 1024 + j * 128) + lane;
            uint4 v0, v1; uint32_t n = 0;
            while (true) {
              v0 = ld_rlx4(p); v1 = ld_rlx4(p + 32);
              if (__all_sync(~0u, v0.y == ep && v0.w == ep && v1.y == ep && v1.w == ep)) break;
              SPIN_GUARD(n);
            }
            const uint32_t d = sb + MISC + MODV + sec * 256 + ((lane & 3) * 16 + (lane >> 2)) * 4;
            asm volatile("st.shared.u32 [%0], %1;" :: "r"(d), "r"(__byte_perm(v0.x, v0.z, 0x7632)) : "memory");
            asm volatile("st.shared.u32 [%0], %1;" :: "r"(d + 32), "r"(__byte_perm(v1.x, v1.z, 0x7632)) : "memory");
          }
          __syncwarp();
          if (e == 1) { arrive_e(bar + B_MOD); }
        }
        if (e == 0) {
          uint32_t* const hf = gs->flag + (m * 128 + 48 + 2 * j + b) * FS;
          uint4* const hp = gs->halo + ((m * 8 + j) * 2 + b) * 256;
          if (m < 15 && lane < 8) st_rlx1(hf + 128 * FS + lane, 0);
          mbar_wait(bar + B_OUT + b * 8, 0);
          if (m < 15) {
            for (int w = 0; w < 2; w++) bulk_st_e(hp + 4096 + w * 128, stg + w * HALF, 2048);
            publish_e(bar + B_OUT + b * 8, hf + 128 * FS, ep);
          }
          if (m > 0) {
            uint32_t n = 0;
            while (!__all_sync(~0u, ld_acquire(hf) == ep)) SPIN_GUARD(n);
            fence_async_global();
            for (int w = 0; w < 2; w++) bulk_ld_e(stg + w * HALF, hp + w * 128, 2048, bar + B_HALO + b * 8);
            expect_e(bar + B_HALO + b * 8, 4096);
          } else {
            __syncwarp();
#pragma unroll
            for (int i = 0; i < 8; i++) sts128(stg + (i >> 2) * HALF + (i & 3) * 512 + lane * 16, 0, 0, 0, 0);
            __syncwarp();
            arrive_e(bar + B_HALO + b * 8);
          }
        }
      }
      if (b) {
#pragma unroll 1
        for (int q = 0; q < 2; q++) all_there(m * 128 + U_HH + 32 + q * 16 + (lane & (15 >> q)), bar + (q ? B_HH2 : B_HH + 8));
      }
    }
  } else {
    const int wg = warp >> 2, wq = warp & 3, tid = threadIdx.x;
    const int g = lane >> 2, c = lane & 3;
    if (!extra) cl_arrive_relaxed();
    asm volatile("setmaxnreg.inc.sync.aligned.u32 232;" ::: "memory");
    if (__builtin_expect(extra, 0)) {
      const uint32_t ep = ep0 + 1;
      float sv[4];
#pragma unroll
      for (int p = 0; p < 4; p++) sv[p] = silu_c(__bfloat162float(cvec[64 * (4 * p + (lane >> 3)) + 8 * warp + (lane & 7)]));
      named_bar(2, 288);
      int s = 0, par = 0;
#pragma unroll 1
      for (int sec = 0; sec < 4; sec++) {
        float a[8] = {0, 0, 0, 0, 0, 0, 0, 0};
#pragma unroll 1
        for (int it = 0; it < 16; it++) {
          const float sc = it < 4 ? sv[0] : it < 8 ? sv[1] : it < 12 ? sv[2] : sv[3];
          mbar_wait(bar + B_FULL6 + s * 8, par);
          uint4 w[8];
#pragma unroll
          for (int i = 0; i < 8; i++) w[i] = lds128(sb + s * 32768 + (warp * 8 + i) * 512 + lane * 16);
#pragma unroll
          for (int i = 0; i < 8; i++) gemv_fma(a, w[i], __shfl_sync(~0u, sc, (it & 3) * 8 + i));
          if (lane == 0) mbar_arrive(bar + B_EMPTY6 + s * 8);
          if (++s == 6) { s = 0; par ^= 1; }
        }
        const uint32_t red = sb + STG + sec * 8192;
        sts128(red + warp * 1024 + lane * 32, __float_as_uint(a[0]), __float_as_uint(a[1]), __float_as_uint(a[2]), __float_as_uint(a[3]));
        sts128(red + warp * 1024 + lane * 32 + 16, __float_as_uint(a[4]), __float_as_uint(a[5]), __float_as_uint(a[6]), __float_as_uint(a[7]));
        named_bar(1, 256);
        float t = 0;
#pragma unroll
        for (int q = 0; q < 8; q++) t += lds32f(red + q * 1024 + tid * 4);
        t = bf_round(t);
        if (sec == 2) t = bf_round(t + 1.f);
        st_rlx2(gs->modv + sec * 1024 + (bid + 4) * 256 + tid, __float_as_uint(t), ep);
      }
      if (tid == 0) gs->epoch[blockIdx.x] = ep;
      return;
    }
    const int row0 = wg * 64 + wq * 16 + g;
    if (c < 2) st_rlx2(gs->stat + m * 1024 + j * 128 + row0 + c * 8, 0, 0);
    cl_wait();
    uint32_t ep;
    asm volatile("add.u32 %0, %1, 1;" : "=r"(ep) : "r"(ep0) : "memory");
    const float sc_ = silu_c(__uint_as_float((uint32_t)cv_ << 16));
    const uint32_t rel = mapa(bar, (lane & 1) ^ rank);
    const uint32_t stg_row = sb + STG + (wg * 64 + wq * 16 + (lane & 15)) * 128;
    const uint32_t fre = bar + B_FREE;
    Ring r4{0, 0, 0}, r6{0, 0, 0};
    auto none = [](auto) {};
    uint32_t xk[32];
    {
      float a[8] = {0, 0, 0, 0, 0, 0, 0, 0};
#pragma unroll
      for (int i = 0; i < 8; i++) gemv_fma(a, wv[i], __shfl_sync(~0u, sc_, i * 4 + (lane >> 3)));
#pragma unroll
      for (int i = 0; i < 8; i++) { a[i] += __shfl_xor_sync(~0u, a[i], 8); a[i] += __shfl_xor_sync(~0u, a[i], 16); }
      if (lane < 8) {
        sts128(sb + RED_OFF + warp * 256 + lane * 32, __float_as_uint(a[0]), __float_as_uint(a[1]), __float_as_uint(a[2]), __float_as_uint(a[3]));
        sts128(sb + RED_OFF + warp * 256 + lane * 32 + 16, __float_as_uint(a[4]), __float_as_uint(a[5]), __float_as_uint(a[6]), __float_as_uint(a[7]));
      }
      named_bar(1, 256);
      if (tid < 64) {
        float s = 0;
#pragma unroll
        for (int w = 0; w < 8; w++) s += lds32f(sb + RED_OFF + w * 256 + tid * 4);
        st_rlx1(gs->modp + u * 64 + tid, (__float_as_uint(s) & ~255u) | tag_of(ep));
      }
      float v[64];
      mbar_wait(bar + B_X, 0); mbar_wait(bar + B_X + 8, 0);
#pragma unroll
      for (int i = 0; i < 16; i += 2) {
        uint32_t w0, w1, w2, w3;
        ldsm4(stg_row + (i >> 3) * BLK + ((((i & 7) + (lane >> 4)) ^ (lane & 7)) << 4), w0, w1, w2, w3);
        xk[2 * i] = w0; xk[2 * i + 1] = w1; xk[2 * i + 2] = w2; xk[2 * i + 3] = w3;
        v[4 * i] = bf_lo(w0); v[4 * i + 1] = bf_hi(w0); v[4 * i + 2] = bf_lo(w1); v[4 * i + 3] = bf_hi(w1);
        v[4 * i + 4] = bf_lo(w2); v[4 * i + 5] = bf_hi(w2); v[4 * i + 6] = bf_lo(w3); v[4 * i + 7] = bf_hi(w3);
      }
      ln_publish(v, gs->stat + m * 1024, j, row0, lane, ep);
      mod_store(sb, tid >> 7, tid & 127, mod_gather(gs->modp + (tid >> 7) * 1024 + j * 128 + (tid & 127), ep));
      named_bar(1, 256);
      ln_apply(v, gs->stat + m * 1024, row0, ep, sb, 0, 1, stg_row, wg, lane);
      named_bar(1, 256);
    }
    {
      uint32_t kf[32], vf[32], pv[32];
      const bool first = wq == 0 && m == 0;
      const uint32_t xa = sb + STG + wg * HALF + wq * 2048 + lane * 16;
      {
        float acc[128];
        mainloop<256, 4, 0, 0>(acc, 16, true, r4, sb, wg, lane, rel, none, none, [&] {
          mbar_wait(fre + 8, 0);
          if (c < 2) st_rlx2(gs->stat + (16 + m) * 1024 + j * 128 + row0 + c * 8, 0, 0);
        });
#pragma unroll
        for (int i = 0; i < 32; i++) { kf[i] = pack2(acc[2 * i], acc[2 * i + 1]); vf[i] = pack2(acc[64 + 2 * i], acc[65 + 2 * i]); }
      }
      float acc[64];
      constexpr int QP = 2;
      auto inbox = [&](const int b) {
        if (wq == 0) mbar_wait(bar + B_HALO + b * 8, 0);
#pragma unroll
        for (int i = 4 * b; i < 4 * b + 4; i++) {
          uint4 q = lds128(xa + b * BLK + (i & 3) * 512);
          pv[4 * i] = q.x; pv[4 * i + 1] = q.y; pv[4 * i + 2] = q.z; pv[4 * i + 3] = q.w;
        }
        __syncwarp();
      };
      auto sent = [&](int b) { if (wq == 3) { fence_async_smem(); __syncwarp(); if (lane == 0) mbar_arrive(bar + B_OUT + b * 8); } };
      mainloop<128, 6, 8 / QP, 0>(acc, 16, false, r6, sb, wg, lane, rel, [&](auto ic) {
        constexpr int q = (ic.v - 1) * QP;
        if (q == 4) sent(0);
#pragma unroll
        for (int i = 4 * q; i < 4 * (q + QP); i++) vf[i] = movm(vf[i]);
#pragma unroll
        for (int i = q; i < q + QP; i++) sts128(xa + (wq == 3 ? -6144 : 2048) + (i >> 2) * BLK + (i & 3) * 512, kf[4 * i + 1], kf[4 * i + 3], vf[4 * i + 1], vf[4 * i + 3]);
      }, [&](int it) { if (it == 8 / QP + 1) sent(1); }, [&] {
        named_bar(2 + wg, 128);
        inbox(0);
      });
      int gz = g;
#pragma unroll
      for (int b = 0; b < 2; b++) {
        const bool up0 = 2 * c > gz, up1 = 2 * c + 1 > gz;
        const uint32_t mup = (up0 ? 0xffffu : 0u) | (up1 ? 0xffff0000u : 0u);
        float l[2][4], mx[4];
#pragma unroll
        for (int h = 0; h < 2; h++) {
          uint32_t q[8];
          const int k = 16 * b + 8 * h;
#pragma unroll
          for (int i = 0; i < 8; i++) q[i] = pack2(acc[2 * k + 2 * i], acc[2 * k + 2 * i + 1]);
          float s0[4], s1[4], s2[4];
          mma16z(s0, q[0], q[1], q[2], q[3], pv[k], pv[k + 1]); mma16z(s1, q[0], q[1], q[2], q[3], kf[k], kf[k + 2]); mma16z(s2, q[0], q[1], q[2], q[3], kf[k + 1], kf[k + 3]);
          mma16(s0, q[4], q[5], q[6], q[7], pv[k + 4], pv[k + 5]); mma16(s1, q[4], q[5], q[6], q[7], kf[k + 4], kf[k + 6]); mma16(s2, q[4], q[5], q[6], q[7], kf[k + 5], kf[k + 7]);
          if (first) { s0[0] = -INFINITY; s0[1] = -INFINITY; }
          l[h][0] = up0 ? s0[0] : s1[0]; l[h][1] = up1 ? s0[1] : s1[1]; l[h][2] = up0 ? s1[2] : s2[2]; l[h][3] = up1 ? s1[3] : s2[3];
          mx[2 * h] = fmaxf(l[h][0], l[h][1]); mx[2 * h + 1] = fmaxf(l[h][2], l[h][3]);
        }
#pragma unroll
        for (int o = 1; o < 4; o <<= 1) {
#pragma unroll
          for (int h = 0; h < 4; h++) mx[h] = fmaxf(mx[h], __shfl_xor_sync(~0u, mx[h], o));
        }
#pragma unroll
        for (int h = 0; h < 2; h++) {
          const float n0 = -mx[2 * h] * SCL, n1 = -mx[2 * h + 1] * SCL;
          const uint32_t pa = pack2(ex2(fmaf(l[h][0], SCL, n0)), ex2(fmaf(l[h][1], SCL, n0))), pb = pack2(ex2(fmaf(l[h][2], SCL, n1)), ex2(fmaf(l[h][3], SCL, n1)));
          float sm[4];
          mma8z(sm, pa, pb, 0x3f803f80u);
          const float ia = rcp(sm[0]), ib = rcp(sm[2]);
#pragma unroll
          for (int i = 8 * b + 4 * h; i < 8 * b + 4 * h + 4; i += 2) {
            uint32_t of[4];
#pragma unroll
            for (int d = 0; d < 2; d++) {
              float o[4];
              mma16z(o, pa & ~mup, pb & mup, 0u, pb & ~mup, vf[2 * (i + d)], vf[2 * (i + d) + 1]);
              mma8(o, pa & mup, 0u, pv[2 * i + 2 + d]);
              of[2 * d] = pack2(o[0] * ia, o[1] * ia); of[2 * d + 1] = pack2(o[2] * ib, o[3] * ib);
            }
            stsm4(stg_row + b * BLK + ((((i & 7) + (lane >> 4)) ^ (lane & 7)) << 4), of[0], of[1], of[2], of[3]);
          }
        }
        stage_done(sb, wg, b, lane);
        if (b == 0) inbox(1);
        if (b == 0) gz += __float_as_uint(lds32f(bar + ZERO));
      }
      named_bar(1, 256);
    }
    uint32_t pk[64];
    {
      float acc[64];
      mainloop<128, 6, 0, 0>(acc, 16, true, r6, sb, wg, lane, rel, none, none, [&] {
        mbar_wait(bar + B_MOD, 0); mbar_wait(fre + 8, 1);
        load_vec(pk + 32, sb, 2, 0, lane); load_vec(pk + 40, sb, 2, 1, lane);
#pragma unroll
        for (int i = 0; i < 32; i++) { pk[i] = xk[i]; asm volatile("" : "+r"(pk[i])); }
      });
#pragma unroll
      for (int i = 0; i < 32; i++) {
        acc[2 * i] = fmaf(acc[2 * i], bf_lo(pk[32 + (i >> 1)]), bf_lo(pk[i]));
        acc[2 * i + 1] = fmaf(acc[2 * i + 1], bf_hi(pk[32 + (i >> 1)]), bf_hi(pk[i]));
      }
      ln_publish(acc, gs->stat + (16 + m) * 1024, j, row0, lane, ep);
      mbar_wait(bar + B_FULL6 + 16, 1);
      if (lane < 2) mbar_arrive_cl(rel + B_EMPTY6 + 16);
      ring_next<6>(r6);
#pragma unroll
      for (int i = 0; i < 32; i++) { pk[i] = pack2(acc[2 * i], acc[2 * i + 1]); pk[32 + i] = 0; }
      ln_apply(acc, gs->stat + (16 + m) * 1024, row0, ep, sb, 3, 4, stg_row, wg, lane);
      named_bar(1, 256);
    }
    auto swiglu = [&](int q, int uo, int par) {
      if ((q & 3) == 0 && par >= 0) mbar_wait(fre + 2 * q, par);
      uint32_t w[4];
#pragma unroll
      for (int u = 0; u < 4; u++) w[u] = silu_mul2(pk[4 * q + u], pk[uo + 4 * q + u]);
      stsm4(stg_row + (q >> 2) * BLK + ((((2 * q & 7) + (lane >> 4)) ^ (lane & 7)) << 4), w[0], w[1], w[2], w[3]);
    };
    r4.s = r4.wrap = 2;
#pragma unroll 1
    for (int t = 0; t < 3; t++) {
      float acc[128];
      mainloop<256, 4, 4, 1>(acc, 16, t == 0, r4, sb, wg, lane, rel, [&](auto ic) {
        if (t) {
          if (ic.v == 3) stage_done(sb, wg, 0, lane);
          swiglu(2 * ic.v - 2, 32, ~t & 1); swiglu(2 * ic.v - 1, 32, 0);
        }
      }, [&](int it) {
        if (t && it == 5) stage_done(sb, wg, 1, lane);
        if (t == 0 && it >= 8) {
          uint4* p = gs->x1 + bid * 2048 + ((it >> 2) & 1) * 1024 + warp * 128 + (it & 3) * 32 + lane;
#pragma unroll
          for (int i = 0; i < 8; i++)
            asm volatile("{\n.reg .pred p;\nsetp.eq.u32 p, %5, %6;\n@p st.global.v4.u32 [%0], {%1,%2,%3,%4};\n}" :: "l"(p), "r"(pk[4 * i]), "r"(pk[4 * i + 1]), "r"(pk[4 * i + 2]), "r"(pk[4 * i + 3]), "r"(it), "r"(8 + i) : "memory");
        }
      }, [&] { if (t == 0) fence_async_global(); else if (t == 2) mbar_wait(bar + B_X, 1); }, t & 1);
#pragma unroll
      for (int i = 0; i < 64; i++) pk[i] = pack2(acc[2 * i], acc[2 * i + 1]);
    }
    uint32_t x1[32];
    {
      float acc[64];
      mainloop<128, 6, 10, 1>(acc, 16, false, r6, sb, wg, lane, rel, [&](auto ic) {
        constexpr int b = ic.v > 5, q = ic.v - 5 * b;
        if (q == 1) {
          if (b) stage_done(sb, wg, 0, lane);
#pragma unroll
          for (int i = 4 * b; i < 4 * b + 4; i++) { const uint4 x = lds128(sb + STG + b * BLK + warp * 2048 + (i & 3) * 512 + lane * 16); x1[4 * i] = x.x; x1[4 * i + 1] = x.y; x1[4 * i + 2] = x.z; x1[4 * i + 3] = x.w; }
          __syncwarp();
        } else swiglu(4 * b + q - 2, 32, -1);
      }, [&](int it) { if (it == 11) stage_done(sb, wg, 1, lane); }, [] {}, 1);
#pragma unroll
      for (int i = 0; i < 32; i++) pk[i] = pack2(acc[2 * i], acc[2 * i + 1]);
    }
    {
      float acc[64];
      mainloop<128, 6, 4, TAILLAG>(acc, 56, false, r6, sb, wg, lane, rel, [&](auto ic) { swiglu(ic.v - 1, 16, 1); },
                                   [&](int it) { if (it == 5) stage_done(sb, wg, 0, lane); }, [&] {
        load_vec(pk + 32, sb, 5, 0, lane); load_vec(pk + 40, sb, 5, 1, lane);
        mbar_wait(fre, 0); mbar_wait(fre + 8, 1);
      }, 0);
      __syncwarp();
      cl_arrive_relaxed();
#pragma unroll
      for (int i = 0; i < 16; i += 2) {
        uint32_t w[4];
#pragma unroll
        for (int u = 0; u < 4; u++) {
          const int q = 2 * i + u;
          w[u] = pack2(fmaf(acc[2 * q], bf_lo(pk[32 + (q >> 1)]), bf_lo(x1[q])), fmaf(acc[2 * q + 1], bf_hi(pk[32 + (q >> 1)]), bf_hi(x1[q])));
        }
        stsm4(stg_row + (i >> 3) * BLK + ((((i & 7) + (lane >> 4)) ^ (lane & 7)) << 4), w[0], w[1], w[2], w[3]);
        if ((i & 7) == 6) {
          fence_async_smem();
          named_bar(2 + wg, 128);
          if (wq == 0 && elect()) { tma_store_3d(&maps.out, sb + STG + (i >> 3) * BLK + wg * HALF, j * 128 + (i >> 3) * 64, m * 64, wg); bulk_commit(); }
          if (i < 8) x1[16] |= __float_as_uint(lds32f(bar + ZERO));
        }
      }
      if (wq == 0) bulk_wait_read();
      if (tid == 0) gs->epoch[blockIdx.x] = ep;
      cl_wait();
    }
  }
}

typedef CUresult (*EncodeFn)(CUtensorMap*, CUtensorMapDataType, cuuint32_t, void*, const cuuint64_t*, const cuuint64_t*, const cuuint32_t*, const cuuint32_t*,
                             CUtensorMapInterleave, CUtensorMapSwizzle, CUtensorMapL2promotion, CUtensorMapFloatOOBfill);

void make_map(EncodeFn fn, CUtensorMap* mp, const void* base, uint64_t d0, uint64_t d1, uint64_t d2, uint64_t s1, uint64_t s2, uint32_t b2, uint32_t b0 = 64) {
  cuuint64_t d[3] = {d0, d1, d2}, s[2] = {s1, s2};
  cuuint32_t b[3] = {b0, 64, b2}, e[3] = {1, 1, 1};
  fn(mp, CU_TENSOR_MAP_DATA_TYPE_BFLOAT16, 3, (void*)base, d, s, b, e, CU_TENSOR_MAP_INTERLEAVE_NONE, b0 == 64 ? CU_TENSOR_MAP_SWIZZLE_128B : CU_TENSOR_MAP_SWIZZLE_NONE,
     CU_TENSOR_MAP_L2_PROMOTION_L2_128B, CU_TENSOR_MAP_FLOAT_OOB_FILL_NONE);
}

__global__ void probe_kernel() {}
int max_clusters(int size) {
  cudaLaunchConfig_t cfg = {};
  cudaLaunchAttribute at;
  at.id = cudaLaunchAttributeClusterDimension; at.val.clusterDim.x = size; at.val.clusterDim.y = 1; at.val.clusterDim.z = 1;
  cfg.gridDim = dim3(size * 66); cfg.blockDim = dim3(384); cfg.dynamicSmemBytes = SMEM_BYTES; cfg.attrs = &at; cfg.numAttrs = 1;
  int n = 0;
  if (cudaOccupancyMaxActiveClusters(&n, probe_kernel, &cfg) != cudaSuccess) { cudaGetLastError(); return 0; }
  return n;
}

}

extern "C" void kernel_launch(void* const* d_in, const int* in_sizes, int n_in, void* d_out, int out_size) {
  static EncodeFn fn = nullptr;
  static int by_sm = 0;
  static Scratch* gs = nullptr;
  if (!fn) {
    void* p = nullptr; cudaDriverEntryPointQueryResult q;
    cudaGetDriverEntryPoint("cuTensorMapEncodeTiled", &p, cudaEnableDefault, &q);
    fn = (EncodeFn)p;
    cudaFuncSetAttribute(fused_kernel, cudaFuncAttributeMaxDynamicSharedMemorySize, SMEM_BYTES);
    int dev = 0, sms = 0;
    cudaGetSymbolAddress((void**)&gs, g_scratch);
    cudaGetDevice(&dev);
    cudaDeviceGetAttribute(&sms, cudaDevAttrMultiProcessorCount, dev);
    cudaFuncSetAttribute(probe_kernel, cudaFuncAttributeMaxDynamicSharedMemorySize, SMEM_BYTES);
    if (sms == 132 && max_clusters(2) == 66) {
      const int c4 = max_clusters(4), c6 = max_clusters(6), c8 = max_clusters(8);
      by_sm = c4 == 30 && c6 == 17 && c8 == 15 ? 1 : c8 == 16 ? 2 : 0;
    }
  }
  Maps mp;
  make_map(fn, &mp.x, d_in[0], D_, S_ / 2, 2, 4096, 2048, 2);
  make_map(fn, &mp.out, d_out, D_, S_ / 2, 2, 4096, 2048, 1);
  make_map(fn, &mp.wqkv, d_in[1], 64, D_, 3 * D_ / 64, 3 * D_ * 2, 128, 2);
  make_map(fn, &mp.wo, d_in[2], 64, D_, D_ / 64, D_ * 2, 128, 2);
  make_map(fn, &mp.w1, d_in[4], 64, D_, F_ / 64, F_ * 2, 128, 2);
  make_map(fn, &mp.w3, d_in[5], 64, D_, F_ / 64, F_ * 2, 128, 2);
  make_map(fn, &mp.w1s, d_in[4], 64, D_, F_ / 64, F_ * 2, 128, 1);
  make_map(fn, &mp.w3s, d_in[5], 64, D_, F_ / 64, F_ * 2, 128, 1);
  make_map(fn, &mp.w2, d_in[6], 64, F_, D_ / 64, D_ * 2, 128, 2);
  make_map(fn, &mp.wmod, d_in[8], 256, D_, 24, 6 * D_ * 2, 512, 1, 256);
  fused_kernel<<<132, 384, SMEM_BYTES>>>((const bf16*)d_in[7], (const bf16*)d_in[8], gs, by_sm, mp);
}
```

```cpp
#include <cuda_runtime.h>
#include <cuda_bf16.h>
#include <cuda.h>
#include <stdint.h>

typedef __nv_bfloat16 bf16;

namespace {

constexpr int S_ = 2048, D_ = 1024, F_ = 3584;
constexpr int BLK = 16384;
constexpr int HALF = 8192;
constexpr int RING = 196608;
constexpr int STG = RING;
constexpr int MISC = RING + 2 * BLK;
constexpr int SMEM_BYTES = MISC + 3072;
constexpr int B_FULL4 = 0, B_EMPTY4 = 32, B_FULL6 = 64, B_EMPTY6 = 112, B_RDY = 160, B_FREE = 176, B_LAG = 192, B_X = 208, B_MOD = 224, B_OUT = 240, B_HH = 256, B_ALL = 272, B_HH2 = 288, ZERO = 296, B_HALO = 304;
constexpr int MODV = 512;
constexpr int RED_OFF = 0;
constexpr float SCL = 0.17677669529663687f * 1.4426950408889634f;
constexpr int U_HH = 64;
constexpr int FS = 8;
constexpr int NPIECE = 4, PSLEEP = 300;
constexpr int XSLEEP = 4000;
constexpr uint32_t GAP = 250;
constexpr uint32_t B1P = 3700, B1D = 700;
constexpr int TAILLAG = 5;

struct Maps { CUtensorMap x, out, wqkv, wo, w1, w3, w1s, w3s, w2, wmod; };

struct Scratch {
  uint32_t epoch[256];
  uint32_t flag[16 * 128 * FS];
  uint32_t modp[8 * 2 * 4 * 128];
  uint2 modv[4 * 1024];
  uint2 stat[2 * 16 * 8 * 128];
  uint4 halo[16 * 8 * 2 * 256];
  uint4 x1[128 * 8 * 256];
  uint4 h[16 * 16 * 1024];
  uint4 o[16 * 16 * 1024];
  uint4 hh[16 * 56 * 1024];
};
__device__ __align__(1024) Scratch g_scratch;

__device__ __forceinline__ void bail() { asm volatile("st.global.u32 [%0], %1;" :: "l"(0ull), "r"(0) : "memory"); }
__device__ __forceinline__ uint32_t smem_u32(const void* p) { return (uint32_t)__cvta_generic_to_shared(p); }
__device__ __forceinline__ void mbar_init(uint32_t bar, uint32_t cnt) { asm volatile("mbarrier.init.shared::cta.b64 [%0], %1;" :: "r"(bar), "r"(cnt) : "memory"); }
__device__ __forceinline__ void mbar_arrive(uint32_t bar) { asm volatile("mbarrier.arrive.shared::cta.b64 _, [%0];" :: "r"(bar) : "memory"); }
__device__ __forceinline__ void mbar_arrive_cl(uint32_t cl_addr) { asm volatile("mbarrier.arrive.shared::cluster.b64 _, [%0];" :: "r"(cl_addr) : "memory"); }
__device__ __forceinline__ uint32_t mapa(uint32_t addr, uint32_t cta) { uint32_t r; asm("mapa.shared::cluster.u32 %0, %1, %2;" : "=r"(r) : "r"(addr), "r"(cta)); return r; }
__device__ __forceinline__ void mbar_wait(uint32_t bar, uint32_t parity) {
  asm volatile("{\n.reg .pred p;\n.reg .b32 n;\n.reg .b64 z;\nmov.b32 n, 0;\nmov.b64 z, 0;\n"
               "W: add.u32 n, n, 1;\nsetp.gt.u32 p, n, 0x400000;\n@p st.global.u32 [z], n;\n"
               "mbarrier.try_wait.parity.shared::cta.b64 p, [%0], %1;\n@!p bra W;\n}" :: "r"(bar), "r"(parity) : "memory");
}
__device__ __forceinline__ void tma_store_3d(const CUtensorMap* m, uint32_t src, int c0, int c1, int c2) {
  asm volatile("cp.async.bulk.tensor.3d.global.shared::cta.bulk_group [%0, {%2, %3, %4}], [%1];" :: "l"(m), "r"(src), "r"(c0), "r"(c1), "r"(c2) : "memory");
}
#define ELECT "{\n.reg .pred p;\nelect.sync _|p, 0xffffffff;\n@p "
__device__ __forceinline__ void expect_e(uint32_t bar, uint32_t bytes) { asm volatile(ELECT "mbarrier.arrive.expect_tx.shared::cta.b64 _, [%0], %1;\n}" :: "r"(bar), "r"(bytes) : "memory"); }
__device__ __forceinline__ void tma_3d_e(uint32_t dst, const CUtensorMap* m, uint32_t bar, int c0, int c1, int c2) {
  asm volatile(ELECT "cp.async.bulk.tensor.3d.shared::cluster.global.mbarrier::complete_tx::bytes [%0], [%1, {%3, %4, %5}], [%2];\n}" :: "r"(dst), "l"(m), "r"(bar), "r"(c0), "r"(c1), "r"(c2) : "memory");
}
__device__ __forceinline__ void bulk_ld_e(uint32_t dst, const void* src, uint32_t bytes, uint32_t bar) {
  asm volatile(ELECT "cp.async.bulk.shared::cluster.global.mbarrier::complete_tx::bytes [%0], [%1], %2, [%3];\n}" :: "r"(dst), "l"(src), "r"(bytes), "r"(bar) : "memory");
}
__device__ __forceinline__ void bulk_ld_mc_e(uint32_t dst, const void* src, uint32_t bytes, uint32_t bar) {
  asm volatile(ELECT "cp.async.bulk.shared::cluster.global.mbarrier::complete_tx::bytes.multicast::cluster [%0], [%1], %2, [%3], %4;\n}" :: "r"(dst), "l"(src), "r"(bytes), "r"(bar), "h"((uint16_t)3) : "memory");
}
__device__ __forceinline__ void bulk_push_e(uint32_t dst_cl, uint32_t src, uint32_t bytes, uint32_t bar_cl) {
  asm volatile(ELECT "cp.async.bulk.shared::cluster.shared::cta.mbarrier::complete_tx::bytes [%0], [%1], %2, [%3];\n}" :: "r"(dst_cl), "r"(src), "r"(bytes), "r"(bar_cl) : "memory");
}
__device__ __forceinline__ void arrive_e(uint32_t bar) { asm volatile(ELECT "mbarrier.arrive.shared::cta.b64 _, [%0];\n}" :: "r"(bar) : "memory"); }
__device__ __forceinline__ void bulk_st_e(void* dst, uint32_t src, uint32_t bytes) {
  asm volatile(ELECT "cp.async.bulk.global.shared::cta.bulk_group [%0], [%1], %2;\n}" :: "l"(dst), "r"(src), "r"(bytes) : "memory");
}
__device__ __forceinline__ void publish_e(uint32_t free_bar, uint32_t* flag, uint32_t ep) {
  asm volatile(ELECT "cp.async.bulk.commit_group;\n@p cp.async.bulk.wait_group 0;\n@p mbarrier.arrive.shared::cta.b64 _, [%0];\n@p st.release.gpu.global.u32 [%1], %2;\n}"
               :: "r"(free_bar), "l"(flag), "r"(ep) : "memory");
}
__device__ __forceinline__ void bulk_commit() { asm volatile("cp.async.bulk.commit_group;" ::: "memory"); }
__device__ __forceinline__ void bulk_wait_read() { asm volatile("cp.async.bulk.wait_group.read 0;" ::: "memory"); }
__device__ __forceinline__ void fence_async_global() { asm volatile("fence.proxy.async.global;" ::: "memory"); }
__device__ __forceinline__ void fence_async_smem() { asm volatile("fence.proxy.async.shared::cta;" ::: "memory"); }
__device__ __forceinline__ void wg_arrive() { asm volatile("wgmma.fence.sync.aligned;" ::: "memory"); }
__device__ __forceinline__ void wg_commit() { asm volatile("wgmma.commit_group.sync.aligned;" ::: "memory"); }
template <int N> __device__ __forceinline__ void wg_wait() { asm volatile("wgmma.wait_group.sync.aligned %0;" :: "n"(N) : "memory"); }
__device__ __forceinline__ void cl_arrive_relaxed() { asm volatile("barrier.cluster.arrive.relaxed.aligned;" ::: "memory"); }
__device__ __forceinline__ void cl_wait() { asm volatile("barrier.cluster.wait.acquire.aligned;" ::: "memory"); }
__device__ __forceinline__ bool elect() { uint32_t p; asm volatile("{\n.reg .pred p;\nelect.sync _|p, 0xffffffff;\nselp.u32 %0, 1, 0, p;\n}" : "=r"(p)); return p; }
__device__ __forceinline__ void named_bar(int id, int n) { asm volatile("bar.sync %0, %1;" :: "r"(id), "r"(n) : "memory"); }
__device__ __forceinline__ uint32_t pack2(float lo, float hi) { uint32_t r; asm("cvt.rn.bf16x2.f32 %0, %1, %2;" : "=r"(r) : "f"(hi), "f"(lo)); return r; }
__device__ __forceinline__ float bf_lo(uint32_t w) { return __uint_as_float(w << 16); }
__device__ __forceinline__ float bf_hi(uint32_t w) { return __uint_as_float(w & 0xffff0000u); }
__device__ __forceinline__ float bf_round(float v) { return __bfloat162float(__float2bfloat16_rn(v)); }
__device__ __forceinline__ void stsm4(uint32_t addr, uint32_t a, uint32_t b, uint32_t c, uint32_t d) {
  asm volatile("stmatrix.sync.aligned.m8n8.x4.shared.b16 [%0], {%1, %2, %3, %4};" :: "r"(addr), "r"(a), "r"(b), "r"(c), "r"(d) : "memory");
}
__device__ __forceinline__ void ldsm4(uint32_t addr, uint32_t& a, uint32_t& b, uint32_t& c, uint32_t& d) {
  asm volatile("ldmatrix.sync.aligned.m8n8.x4.shared.b16 {%0, %1, %2, %3}, [%4];" : "=r"(a), "=r"(b), "=r"(c), "=r"(d) : "r"(addr) : "memory");
}
__device__ __forceinline__ uint32_t movm(uint32_t a) { uint32_t r; asm volatile("movmatrix.sync.aligned.m8n8.trans.b16 %0, %1;" : "=r"(r) : "r"(a)); return r; }
__device__ __forceinline__ void mma16(float (&d)[4], uint32_t a0, uint32_t a1, uint32_t a2, uint32_t a3, uint32_t b0, uint32_t b1) {
  asm("mma.sync.aligned.m16n8k16.row.col.f32.bf16.bf16.f32 {%0,%1,%2,%3}, {%4,%5,%6,%7}, {%8,%9}, {%0,%1,%2,%3};"
               : "+f"(d[0]), "+f"(d[1]), "+f"(d[2]), "+f"(d[3]) : "r"(a0), "r"(a1), "r"(a2), "r"(a3), "r"(b0), "r"(b1));
}
__device__ __forceinline__ void mma16z(float (&d)[4], uint32_t a0, uint32_t a1, uint32_t a2, uint32_t a3, uint32_t b0, uint32_t b1) {
  asm("mma.sync.aligned.m16n8k16.row.col.f32.bf16.bf16.f32 {%0,%1,%2,%3}, {%4,%5,%6,%7}, {%8,%9}, {%10,%10,%10,%10};"
      : "=f"(d[0]), "=f"(d[1]), "=f"(d[2]), "=f"(d[3]) : "r"(a0), "r"(a1), "r"(a2), "r"(a3), "r"(b0), "r"(b1), "f"(0.f));
}
__device__ __forceinline__ void mma8z(float (&d)[4], uint32_t a0, uint32_t a1, uint32_t b0) {
  asm("mma.sync.aligned.m16n8k8.row.col.f32.bf16.bf16.f32 {%0,%1,%2,%3}, {%4,%5}, {%6}, {%7,%7,%7,%7};"
      : "=f"(d[0]), "=f"(d[1]), "=f"(d[2]), "=f"(d[3]) : "r"(a0), "r"(a1), "r"(b0), "f"(0.f));
}
__device__ __forceinline__ void mma8(float (&d)[4], uint32_t a0, uint32_t a1, uint32_t b0) {
  asm("mma.sync.aligned.m16n8k8.row.col.f32.bf16.bf16.f32 {%0,%1,%2,%3}, {%4,%5}, {%6}, {%0,%1,%2,%3};"
               : "+f"(d[0]), "+f"(d[1]), "+f"(d[2]), "+f"(d[3]) : "r"(a0), "r"(a1), "r"(b0));
}
__device__ __forceinline__ uint4 lds128(uint32_t a) { uint4 v; asm volatile("ld.shared.v4.u32 {%0,%1,%2,%3}, [%4];" : "=r"(v.x), "=r"(v.y), "=r"(v.z), "=r"(v.w) : "r"(a) : "memory"); return v; }
__device__ __forceinline__ void sts128(uint32_t a, uint32_t x, uint32_t y, uint32_t z, uint32_t w) { asm volatile("st.shared.v4.u32 [%0], {%1,%2,%3,%4};" :: "r"(a), "r"(x), "r"(y), "r"(z), "r"(w) : "memory"); }
__device__ __forceinline__ float lds32f(uint32_t a) { float v; asm volatile("ld.shared.f32 %0, [%1];" : "=f"(v) : "r"(a) : "memory"); return v; }
__device__ __forceinline__ void sts16(uint32_t a, bf16 v) { asm volatile("st.shared.b16 [%0], %1;" :: "r"(a), "h"(__bfloat16_as_ushort(v)) : "memory"); }
__device__ __forceinline__ uint4 ldg_nc(const void* p) { uint4 v; asm volatile("ld.global.nc.L1::no_allocate.v4.u32 {%0,%1,%2,%3}, [%4];" : "=r"(v.x), "=r"(v.y), "=r"(v.z), "=r"(v.w) : "l"(p)); return v; }
__device__ __forceinline__ uint4 ld_rlx4(const uint4* p) {
  unsigned long long a, b; asm volatile("ld.relaxed.gpu.global.v2.b64 {%0,%1}, [%2];" : "=l"(a), "=l"(b) : "l"(p) : "memory");
  return make_uint4((uint32_t)a, (uint32_t)(a >> 32), (uint32_t)b, (uint32_t)(b >> 32));
}
__device__ __forceinline__ uint2 ld_rlx2(const uint2* p) { unsigned long long a; asm volatile("ld.relaxed.gpu.global.b64 %0, [%1];" : "=l"(a) : "l"(p) : "memory"); return make_uint2((uint32_t)a, (uint32_t)(a >> 32)); }
__device__ __forceinline__ void st_rlx2(uint2* p, uint32_t x, uint32_t y) { asm volatile("st.relaxed.gpu.global.b64 [%0], %1;" :: "l"(p), "l"((unsigned long long)x | ((unsigned long long)y << 32)) : "memory"); }
__device__ __forceinline__ void st_rlx1(uint32_t* p, uint32_t v) { asm volatile("st.relaxed.gpu.global.u32 [%0], %1;" :: "l"(p), "r"(v) : "memory"); }
__device__ __forceinline__ uint32_t ld_rlx1(const uint32_t* p) { uint32_t v; asm volatile("ld.relaxed.gpu.global.u32 %0, [%1];" : "=r"(v) : "l"(p) : "memory"); return v; }
__device__ __forceinline__ uint32_t ld_acquire(const uint32_t* p) { uint32_t v; asm volatile("ld.acquire.gpu.global.u32 %0, [%1];" : "=r"(v) : "l"(p) : "memory"); return v; }
__device__ __forceinline__ void prefetch_map(const CUtensorMap* m) { asm volatile("prefetch.tensormap [%0];" :: "l"(m) : "memory"); }
__device__ __forceinline__ float rcp(float x) { float r; asm("rcp.approx.ftz.f32 %0, %1;" : "=f"(r) : "f"(x)); return r; }
__device__ __forceinline__ float ex2(float x) { float r; asm("ex2.approx.ftz.f32 %0, %1;" : "=f"(r) : "f"(x)); return r; }
__device__ __forceinline__ float tanh_fast(float x) { float r; asm("tanh.approx.f32 %0, %1;" : "=f"(r) : "f"(x)); return r; }
#define SPIN_GUARD(n) if (++(n) > (1u << 24)) bail()

__device__ __forceinline__ void wgmma_n128(float (&d)[64], uint64_t da, uint64_t db) {
  asm volatile("wgmma.mma_async.sync.aligned.m64n128k16.f32.bf16.bf16 "
    "{%0, %1, %2, %3, %4, %5, %6, %7, %8, %9, %10, %11, %12, %13, %14, %15, %16, %17, %18, %19, %20, %21, %22, %23, %24, %25, %26, %27, %28, %29, %30, %31, %32, %33, %34, %35, %36, %37, %38, %39, %40, %41, %42, %43, %44, %45, %46, %47, %48, %49, %50, %51, %52, %53, %54, %55, %56, %57, %58, %59, %60, %61, %62, %63}, "
    "%64, %65, 1, 1, 1, 0, 1;\n"
    : "+f"(d[0]), "+f"(d[1]), "+f"(d[2]), "+f"(d[3]), "+f"(d[4]), "+f"(d[5]), "+f"(d[6]), "+f"(d[7]), "+f"(d[8]), "+f"(d[9]), "+f"(d[10]), "+f"(d[11]), "+f"(d[12]), "+f"(d[13]), "+f"(d[14]), "+f"(d[15]), "+f"(d[16]), "+f"(d[17]), "+f"(d[18]), "+f"(d[19]), "+f"(d[20]), "+f"(d[21]), "+f"(d[22]), "+f"(d[23]), "+f"(d[24]), "+f"(d[25]), "+f"(d[26]), "+f"(d[27]), "+f"(d[28]), "+f"(d[29]), "+f"(d[30]), "+f"(d[31]), "+f"(d[32]), "+f"(d[33]), "+f"(d[34]), "+f"(d[35]), "+f"(d[36]), "+f"(d[37]), "+f"(d[38]), "+f"(d[39]), "+f"(d[40]), "+f"(d[41]), "+f"(d[42]), "+f"(d[43]), "+f"(d[44]), "+f"(d[45]), "+f"(d[46]), "+f"(d[47]), "+f"(d[48]), "+f"(d[49]), "+f"(d[50]), "+f"(d[51]), "+f"(d[52]), "+f"(d[53]), "+f"(d[54]), "+f"(d[55]), "+f"(d[56]), "+f"(d[57]), "+f"(d[58]), "+f"(d[59]), "+f"(d[60]), "+f"(d[61]), "+f"(d[62]), "+f"(d[63])
    : "l"(da), "l"(db));
}
__device__ __forceinline__ void wgmma_n128_first(float (&d)[64], uint64_t da, uint64_t db) {
  asm volatile("wgmma.mma_async.sync.aligned.m64n128k16.f32.bf16.bf16 "
    "{%0, %1, %2, %3, %4, %5, %6, %7, %8, %9, %10, %11, %12, %13, %14, %15, %16, %17, %18, %19, %20, %21, %22, %23, %24, %25, %26, %27, %28, %29, %30, %31, %32, %33, %34, %35, %36, %37, %38, %39, %40, %41, %42, %43, %44, %45, %46, %47, %48, %49, %50, %51, %52, %53, %54, %55, %56, %57, %58, %59, %60, %61, %62, %63}, "
    "%64, %65, 0, 1, 1, 0, 1;\n"
    : "=f"(d[0]), "=f"(d[1]), "=f"(d[2]), "=f"(d[3]), "=f"(d[4]), "=f"(d[5]), "=f"(d[6]), "=f"(d[7]), "=f"(d[8]), "=f"(d[9]), "=f"(d[10]), "=f"(d[11]), "=f"(d[12]), "=f"(d[13]), "=f"(d[14]), "=f"(d[15]), "=f"(d[16]), "=f"(d[17]), "=f"(d[18]), "=f"(d[19]), "=f"(d[20]), "=f"(d[21]), "=f"(d[22]), "=f"(d[23]), "=f"(d[24]), "=f"(d[25]), "=f"(d[26]), "=f"(d[27]), "=f"(d[28]), "=f"(d[29]), "=f"(d[30]), "=f"(d[31]), "=f"(d[32]), "=f"(d[33]), "=f"(d[34]), "=f"(d[35]), "=f"(d[36]), "=f"(d[37]), "=f"(d[38]), "=f"(d[39]), "=f"(d[40]), "=f"(d[41]), "=f"(d[42]), "=f"(d[43]), "=f"(d[44]), "=f"(d[45]), "=f"(d[46]), "=f"(d[47]), "=f"(d[48]), "=f"(d[49]), "=f"(d[50]), "=f"(d[51]), "=f"(d[52]), "=f"(d[53]), "=f"(d[54]), "=f"(d[55]), "=f"(d[56]), "=f"(d[57]), "=f"(d[58]), "=f"(d[59]), "=f"(d[60]), "=f"(d[61]), "=f"(d[62]), "=f"(d[63])
    : "l"(da), "l"(db));
}
__device__ __forceinline__ void wgmma_n256(float (&d)[128], uint64_t da, uint64_t db) {
  asm volatile("wgmma.mma_async.sync.aligned.m64n256k16.f32.bf16.bf16 "
    "{%0, %1, %2, %3, %4, %5, %6, %7, %8, %9, %10, %11, %12, %13, %14, %15, %16, %17, %18, %19, %20, %21, %22, %23, %24, %25, %26, %27, %28, %29, %30, %31, %32, %33, %34, %35, %36, %37, %38, %39, %40, %41, %42, %43, %44, %45, %46, %47, %48, %49, %50, %51, %52, %53, %54, %55, %56, %57, %58, %59, %60, %61, %62, %63, %64, %65, %66, %67, %68, %69, %70, %71, %72, %73, %74, %75, %76, %77, %78, %79, %80, %81, %82, %83, %84, %85, %86, %87, %88, %89, %90, %91, %92, %93, %94, %95, %96, %97, %98, %99, %100, %101, %102, %103, %104, %105, %106, %107, %108, %109, %110, %111, %112, %113, %114, %115, %116, %117, %118, %119, %120, %121, %122, %123, %124, %125, %126, %127}, "
    "%128, %129, 1, 1, 1, 0, 1;\n"
    : "+f"(d[0]), "+f"(d[1]), "+f"(d[2]), "+f"(d[3]), "+f"(d[4]), "+f"(d[5]), "+f"(d[6]), "+f"(d[7]), "+f"(d[8]), "+f"(d[9]), "+f"(d[10]), "+f"(d[11]), "+f"(d[12]), "+f"(d[13]), "+f"(d[14]), "+f"(d[15]), "+f"(d[16]), "+f"(d[17]), "+f"(d[18]), "+f"(d[19]), "+f"(d[20]), "+f"(d[21]), "+f"(d[22]), "+f"(d[23]), "+f"(d[24]), "+f"(d[25]), "+f"(d[26]), "+f"(d[27]), "+f"(d[28]), "+f"(d[29]), "+f"(d[30]), "+f"(d[31]), "+f"(d[32]), "+f"(d[33]), "+f"(d[34]), "+f"(d[35]), "+f"(d[36]), "+f"(d[37]), "+f"(d[38]), "+f"(d[39]), "+f"(d[40]), "+f"(d[41]), "+f"(d[42]), "+f"(d[43]), "+f"(d[44]), "+f"(d[45]), "+f"(d[46]), "+f"(d[47]), "+f"(d[48]), "+f"(d[49]), "+f"(d[50]), "+f"(d[51]), "+f"(d[52]), "+f"(d[53]), "+f"(d[54]), "+f"(d[55]), "+f"(d[56]), "+f"(d[57]), "+f"(d[58]), "+f"(d[59]), "+f"(d[60]), "+f"(d[61]), "+f"(d[62]), "+f"(d[63]), "+f"(d[64]), "+f"(d[65]), "+f"(d[66]), "+f"(d[67]), "+f"(d[68]), "+f"(d[69]), "+f"(d[70]), "+f"(d[71]), "+f"(d[72]), "+f"(d[73]), "+f"(d[74]), "+f"(d[75]), "+f"(d[76]), "+f"(d[77]), "+f"(d[78]), "+f"(d[79]), "+f"(d[80]), "+f"(d[81]), "+f"(d[82]), "+f"(d[83]), "+f"(d[84]), "+f"(d[85]), "+f"(d[86]), "+f"(d[87]), "+f"(d[88]), "+f"(d[89]), "+f"(d[90]), "+f"(d[91]), "+f"(d[92]), "+f"(d[93]), "+f"(d[94]), "+f"(d[95]), "+f"(d[96]), "+f"(d[97]), "+f"(d[98]), "+f"(d[99]), "+f"(d[100]), "+f"(d[101]), "+f"(d[102]), "+f"(d[103]), "+f"(d[104]), "+f"(d[105]), "+f"(d[106]), "+f"(d[107]), "+f"(d[108]), "+f"(d[109]), "+f"(d[110]), "+f"(d[111]), "+f"(d[112]), "+f"(d[113]), "+f"(d[114]), "+f"(d[115]), "+f"(d[116]), "+f"(d[117]), "+f"(d[118]), "+f"(d[119]), "+f"(d[120]), "+f"(d[121]), "+f"(d[122]), "+f"(d[123]), "+f"(d[124]), "+f"(d[125]), "+f"(d[126]), "+f"(d[127])
    : "l"(da), "l"(db));
}
__device__ __forceinline__ void wgmma_n256_first(float (&d)[128], uint64_t da, uint64_t db) {
  asm volatile("wgmma.mma_async.sync.aligned.m64n256k16.f32.bf16.bf16 "
    "{%0, %1, %2, %3, %4, %5, %6, %7, %8, %9, %10, %11, %12, %13, %14, %15, %16, %17, %18, %19, %20, %21, %22, %23, %24, %25, %26, %27, %28, %29, %30, %31, %32, %33, %34, %35, %36, %37, %38, %39, %40, %41, %42, %43, %44, %45, %46, %47, %48, %49, %50, %51, %52, %53, %54, %55, %56, %57, %58, %59, %60, %61, %62, %63, %64, %65, %66, %67, %68, %69, %70, %71, %72, %73, %74, %75, %76, %77, %78, %79, %80, %81, %82, %83, %84, %85, %86, %87, %88, %89, %90, %91, %92, %93, %94, %95, %96, %97, %98, %99, %100, %101, %102, %103, %104, %105, %106, %107, %108, %109, %110, %111, %112, %113, %114, %115, %116, %117, %118, %119, %120, %121, %122, %123, %124, %125, %126, %127}, "
    "%128, %129, 0, 1, 1, 0, 1;\n"
    : "=f"(d[0]), "=f"(d[1]), "=f"(d[2]), "=f"(d[3]), "=f"(d[4]), "=f"(d[5]), "=f"(d[6]), "=f"(d[7]), "=f"(d[8]), "=f"(d[9]), "=f"(d[10]), "=f"(d[11]), "=f"(d[12]), "=f"(d[13]), "=f"(d[14]), "=f"(d[15]), "=f"(d[16]), "=f"(d[17]), "=f"(d[18]), "=f"(d[19]), "=f"(d[20]), "=f"(d[21]), "=f"(d[22]), "=f"(d[23]), "=f"(d[24]), "=f"(d[25]), "=f"(d[26]), "=f"(d[27]), "=f"(d[28]), "=f"(d[29]), "=f"(d[30]), "=f"(d[31]), "=f"(d[32]), "=f"(d[33]), "=f"(d[34]), "=f"(d[35]), "=f"(d[36]), "=f"(d[37]), "=f"(d[38]), "=f"(d[39]), "=f"(d[40]), "=f"(d[41]), "=f"(d[42]), "=f"(d[43]), "=f"(d[44]), "=f"(d[45]), "=f"(d[46]), "=f"(d[47]), "=f"(d[48]), "=f"(d[49]), "=f"(d[50]), "=f"(d[51]), "=f"(d[52]), "=f"(d[53]), "=f"(d[54]), "=f"(d[55]), "=f"(d[56]), "=f"(d[57]), "=f"(d[58]), "=f"(d[59]), "=f"(d[60]), "=f"(d[61]), "=f"(d[62]), "=f"(d[63]), "=f"(d[64]), "=f"(d[65]), "=f"(d[66]), "=f"(d[67]), "=f"(d[68]), "=f"(d[69]), "=f"(d[70]), "=f"(d[71]), "=f"(d[72]), "=f"(d[73]), "=f"(d[74]), "=f"(d[75]), "=f"(d[76]), "=f"(d[77]), "=f"(d[78]), "=f"(d[79]), "=f"(d[80]), "=f"(d[81]), "=f"(d[82]), "=f"(d[83]), "=f"(d[84]), "=f"(d[85]), "=f"(d[86]), "=f"(d[87]), "=f"(d[88]), "=f"(d[89]), "=f"(d[90]), "=f"(d[91]), "=f"(d[92]), "=f"(d[93]), "=f"(d[94]), "=f"(d[95]), "=f"(d[96]), "=f"(d[97]), "=f"(d[98]), "=f"(d[99]), "=f"(d[100]), "=f"(d[101]), "=f"(d[102]), "=f"(d[103]), "=f"(d[104]), "=f"(d[105]), "=f"(d[106]), "=f"(d[107]), "=f"(d[108]), "=f"(d[109]), "=f"(d[110]), "=f"(d[111]), "=f"(d[112]), "=f"(d[113]), "=f"(d[114]), "=f"(d[115]), "=f"(d[116]), "=f"(d[117]), "=f"(d[118]), "=f"(d[119]), "=f"(d[120]), "=f"(d[121]), "=f"(d[122]), "=f"(d[123]), "=f"(d[124]), "=f"(d[125]), "=f"(d[126]), "=f"(d[127])
    : "l"(da), "l"(db));
}

template <int N> struct WG;
#define DEF_WG(N) template <> struct WG<N> { \
  static __device__ __forceinline__ void mma(float (&d)[N / 2], uint64_t a, uint64_t b) { wgmma_n##N(d, a, b); } \
  static __device__ __forceinline__ void first(float (&d)[N / 2], uint64_t a, uint64_t b) { wgmma_n##N##_first(d, a, b); } };
DEF_WG(128) DEF_WG(256)

constexpr uint64_t DESC_A = (1ull << 62) | ((uint64_t)(1024 >> 4) << 32) | (1ull << 16);
constexpr uint64_t DESC_B = (1ull << 62) | ((uint64_t)(1024 >> 4) << 32) | ((uint64_t)(8192 >> 4) << 16);

struct Ring { int s; uint32_t ph; int wrap; };
template <int NS> __device__ __forceinline__ void ring_next(Ring& r) { r.s = (r.s + 1 == NS) ? 0 : r.s + 1; if (r.s == r.wrap) r.ph ^= 1; }

__device__ __forceinline__ int own_order(int it, int j) {
  return it < 2 ? 2 * j + it : it < 4 ? 2 * (j ^ 1) + it - 2 : ((j >> 1) * 4 + 2 * it - (it < 10 ? 4 : 15)) & 15;
}

template <int V> struct IC { static constexpr int v = V; };
template <int I, int E, class F> __device__ __forceinline__ void static_for(F&& f) { if constexpr (I < E) { f(IC<I>{}); static_for<I + 1, E>(f); } }

template <int N, int NS, int PRE, int LAG, class Pre, class Mid, class Last>
__device__ __forceinline__ void mainloop(float (&acc)[N / 2], int nkb, bool own, Ring& r, uint32_t sb, int wg, int lane, uint32_t rel_base, Pre pre, Mid mid, Last last, int lag_par = 0) {
  constexpr int SLOT = RING / NS;
  const uint32_t full = sb + MISC + (NS == 4 ? B_FULL4 : B_FULL6);
  const uint32_t rel = rel_base + (NS == 4 ? B_EMPTY4 : B_EMPTY6);
  const uint32_t s0 = (sb & 0x3FFFF) >> 4, a0 = s0 + wg * (HALF >> 4);
  int ps;
  auto issue = [&](int it, bool first) {
    const uint64_t da = DESC_A | (a0 + ((own && it < 2) ? (STG + it * BLK) >> 4 : r.s * (SLOT >> 4))), db = DESC_B | (s0 + r.s * (SLOT >> 4) + (BLK >> 4));
    mbar_wait(full + r.s * 8, r.ph);
    wg_arrive();
    if (first) WG<N>::first(acc, da, db); else WG<N>::mma(acc, da, db);
#pragma unroll
    for (int k = 1; k < 4; k++) WG<N>::mma(acc, da + k * 2, db + k * 128);
    wg_commit();
  };
  auto retire = [&](int it) {
    wg_wait<1>();
    if (lane < 2) mbar_arrive_cl(rel + ps * 8);
    ps = r.s;
    ring_next<NS>(r);
  };
  issue(0, true);
  ps = r.s;
  ring_next<NS>(r);
  static_for<1, PRE + 1>([&](auto ic) { issue(ic.v, false); pre(ic); retire(ic.v); });
#pragma unroll 1
  for (int it = PRE + 1; it < nkb; it++) {
    if (LAG && it == nkb - LAG && wg == 1) mbar_wait(sb + MISC + B_LAG, lag_par);
    issue(it, false); mid(it);
    if (LAG > 1 && it > nkb - NS) ring_next<NS>(r); else retire(it);
  }
  if (LAG && wg == 0 && lane == 0) mbar_arrive(sb + MISC + B_LAG);
  last();
  wg_wait<0>();
#pragma unroll
  for (int i = 0; i < N / 2; i++) asm volatile("" : "+f"(acc[i]) :: "memory");
  if (LAG <= 1 && lane < 2) mbar_arrive_cl(rel + ps * 8);
}

__device__ __forceinline__ uint32_t tag_of(uint32_t ep) { return (ep & 127u) + 1u; }
__device__ __forceinline__ void ln_publish(const float (&v)[64], uint2* st, int j, int row0, int lane, uint32_t ep) {
  float s0 = 0, s1 = 0, s2 = 0, s3 = 0, q0 = 0, q1 = 0, q2 = 0, q3 = 0;
#pragma unroll
  for (int i = 0; i < 16; i++) {
    s0 += v[4 * i]; s1 += v[4 * i + 1]; s2 += v[4 * i + 2]; s3 += v[4 * i + 3];
    q0 = fmaf(v[4 * i], v[4 * i], q0); q1 = fmaf(v[4 * i + 1], v[4 * i + 1], q1); q2 = fmaf(v[4 * i + 2], v[4 * i + 2], q2); q3 = fmaf(v[4 * i + 3], v[4 * i + 3], q3);
  }
  s0 += s1; s2 += s3; q0 += q1; q2 += q3;
  const bool odd = lane & 1;
  float s = (odd ? s2 : s0) + __shfl_xor_sync(~0u, odd ? s0 : s2, 1), q = (odd ? q2 : q0) + __shfl_xor_sync(~0u, odd ? q0 : q2, 1);
  s += __shfl_xor_sync(~0u, s, 2); q += __shfl_xor_sync(~0u, q, 2);
  if ((lane & 3) < 2) st_rlx2(st + j * 128 + row0 + (lane & 1) * 8, __float_as_uint(s), (__float_as_uint(fmaf(s * (-1.f / 128), s, q)) & ~255u) | tag_of(ep));
}
__device__ __forceinline__ void ln_gather(const uint2* st, int row0, int lane, uint32_t ep, float& n0, float& r0, float& n1, float& r1, bool rnd) {
  const uint2* p = st + (lane & 2) * 256 + row0 + (lane & 1) * 8;
  const uint32_t tag = tag_of(ep);
  uint2 a, b, c, d; uint32_t n = 0;
  while (true) {
    a = ld_rlx2(p); b = ld_rlx2(p + 128); c = ld_rlx2(p + 256); d = ld_rlx2(p + 384);
    if ((((a.y ^ tag) | (b.y ^ tag) | (c.y ^ tag) | (d.y ^ tag)) & 255u) == 0) break;
    SPIN_GUARD(n);
  }
  __syncwarp();
  const uint32_t fix = tag ^ 128u;
  float s = (__uint_as_float(a.x) + __uint_as_float(b.x)) + (__uint_as_float(c.x) + __uint_as_float(d.x));
  float q = (__uint_as_float(a.y ^ fix) + __uint_as_float(b.y ^ fix)) + (__uint_as_float(c.y ^ fix) + __uint_as_float(d.y ^ fix));
  q = fmaf(fmaf(__uint_as_float(a.x), __uint_as_float(a.x), __uint_as_float(b.x) * __uint_as_float(b.x)) +
           fmaf(__uint_as_float(c.x), __uint_as_float(c.x), __uint_as_float(d.x) * __uint_as_float(d.x)), 1.f / 128, q);
  s += __shfl_xor_sync(~0u, s, 2); q += __shfl_xor_sync(~0u, q, 2);
  s *= 1.f / 1024;
  const float var = fmaxf(fmaf(-s, s, q * (1.f / 1024)), 0.f);
  float r;
  if (rnd) {
    float sd; asm("sqrt.approx.f32 %0, %1;" : "=f"(sd) : "f"(bf_round(bf_round(var) + 1e-5f)));
    r = rcp(bf_round(sd)); s = bf_round(s);
  } else r = rsqrtf(var + 1e-5f);
  const float nn = -s * r;
  const float ro = __shfl_xor_sync(~0u, r, 1), no = __shfl_xor_sync(~0u, nn, 1);
  const bool odd = lane & 1;
  r0 = odd ? ro : r; n0 = odd ? no : nn; r1 = odd ? r : ro; n1 = odd ? nn : no;
}
__device__ __forceinline__ void load_vec(uint32_t* w, uint32_t sb, int sec, int b, int lane) {
#pragma unroll
  for (int q = 0; q < 2; q++) { uint4 t = lds128(sb + MISC + MODV + sec * 256 + (lane & 3) * 64 + b * 32 + q * 16); w[4 * q] = t.x; w[4 * q + 1] = t.y; w[4 * q + 2] = t.z; w[4 * q + 3] = t.w; }
}
__device__ __forceinline__ void stage_done(uint32_t sb, int wg, int b, int lane) {
  fence_async_smem();
  __syncwarp();
  if (lane == 0) mbar_arrive(sb + MISC + B_RDY + b * 8);
}
__device__ __forceinline__ uint32_t hfma2(uint32_t a, uint32_t b, uint32_t c) { uint32_t r; asm("fma.rn.bf16x2 %0, %1, %2, %3;" : "=r"(r) : "r"(a), "r"(b), "r"(c)); return r; }
__device__ __forceinline__ void ln_apply(const float (&v)[64], const uint2* st, int row0, uint32_t ep, uint32_t sb, int sec_shift, int sec_scale, uint32_t stg_row, int wg, int lane) {
  uint32_t sc[16], sh[16];
#pragma unroll
  for (int b = 0; b < 2; b++) { load_vec(sc + 8 * b, sb, sec_scale, b, lane); load_vec(sh + 8 * b, sb, sec_shift, b, lane); }
  float n0, r0, n1, r1;
  ln_gather(st, row0, lane, ep, n0, r0, n1, r1, sec_shift == 0);
#pragma unroll
  for (int i = 0; i < 16; i += 2) {
    if (i == 8) { const float z = lds32f(sb + MISC + ZERO); n0 += z; n1 += z; }
    uint32_t w[4];
#pragma unroll
    for (int u = 0; u < 2; u++) {
      int q = i + u;
      w[2 * u] = hfma2(pack2(fmaf(v[4 * q], r0, n0), fmaf(v[4 * q + 1], r0, n0)), sc[q], sh[q]);
      w[2 * u + 1] = hfma2(pack2(fmaf(v[4 * q + 2], r1, n1), fmaf(v[4 * q + 3], r1, n1)), sc[q], sh[q]);
    }
    stsm4(stg_row + (i >> 3) * BLK + ((((i & 7) + (lane >> 4)) ^ (lane & 7)) << 4), w[0], w[1], w[2], w[3]);
    if ((i & 7) == 6) { stage_done(sb, wg, i >> 3, lane); }
  }
}
__device__ __forceinline__ uint32_t hmul2(uint32_t a, uint32_t b) { uint32_t r; asm("mul.rn.bf16x2 %0, %1, %2;" : "=r"(r) : "r"(a), "r"(b)); return r; }
__device__ __forceinline__ uint32_t silu_mul2(uint32_t g, uint32_t u) {
  const uint32_t h = hmul2(g, 0x3f003f00u);
  const float h0 = bf_lo(h), h1 = bf_hi(h);
  return hmul2(pack2(fmaf(h0, tanh_fast(h0), h0), fmaf(h1, tanh_fast(h1), h1)), u);
}

__device__ __forceinline__ void gemv_fma(float (&a)[8], uint4 w, float s) {
  a[0] = fmaf(bf_lo(w.x), s, a[0]); a[1] = fmaf(bf_hi(w.x), s, a[1]); a[2] = fmaf(bf_lo(w.y), s, a[2]); a[3] = fmaf(bf_hi(w.y), s, a[3]);
  a[4] = fmaf(bf_lo(w.z), s, a[4]); a[5] = fmaf(bf_hi(w.z), s, a[5]); a[6] = fmaf(bf_lo(w.w), s, a[6]); a[7] = fmaf(bf_hi(w.w), s, a[7]);
}
__device__ __forceinline__ float silu_c(float v) { return bf_round(__fdividef(v, 1.f + __expf(-v))); }
__device__ __forceinline__ float mod_gather(const uint32_t* p, uint32_t ep) {
  const uint32_t tag = tag_of(ep), fix = tag ^ 128u;
  uint32_t a, b, c, d, n = 0;
  while (true) {
    a = ld_rlx1(p); b = ld_rlx1(p + 2048); c = ld_rlx1(p + 4096); d = ld_rlx1(p + 6144);
    if ((((a ^ tag) | (b ^ tag) | (c ^ tag) | (d ^ tag)) & 255u) == 0) break;
    SPIN_GUARD(n);
  }
  return (__uint_as_float(a ^ fix) + __uint_as_float(b ^ fix)) + (__uint_as_float(c ^ fix) + __uint_as_float(d ^ fix));
}
__device__ __forceinline__ void mod_store(uint32_t sb, int sec, int col, float v) {
  v = bf_round(v);
  if (sec == 1) v += 1.f;
  sts16(sb + MISC + MODV + sec * 256 + (((col >> 1) & 3) * 16 + (col >> 3)) * 4 + (col & 1) * 2, __float2bfloat16_rn(v));
}

__global__ void __cluster_dims__(2, 1, 1) __launch_bounds__(384, 1)
fused_kernel(const bf16* __restrict__ cvec, const bf16* __restrict__ wmod, Scratch* gs, int by_sm, const __grid_constant__ Maps maps) {
  extern __shared__ __align__(1024) uint8_t smem_raw[];
  uint32_t sm; asm volatile("mov.u32 %0, %%smid;" : "=r"(sm));
  const uint32_t id = by_sm ? sm : blockIdx.x, xs = by_sm ? 112 + 8 * by_sm : 0, u = id < xs ? id : id - 4;
  const bool extra = id - xs < 4;
  uint4 wv[8];
  uint32_t ep0; uint16_t cv_;
  if (threadIdx.x < 256) {
    const int r0 = ((u >> 5) & 3) * 256 + (threadIdx.x & 224);
    asm volatile("ld.global.nc.u16 %0, [%1];" : "=h"(cv_) : "l"(cvec + r0 + (threadIdx.x & 31)));
    asm volatile("ld.global.u32 %0, [%1];" : "=r"(ep0) : "l"(gs->epoch + (blockIdx.x | (threadIdx.x & by_sm & 4))));
    if (!extra) {
      const bf16* wp = wmod + (r0 + ((threadIdx.x >> 3) & 3)) * 6144 + (u & 31) * 64 + (threadIdx.x & 7) * 8;
#pragma unroll
      for (int i = 0; i < 8; i++) wv[i] = ldg_nc(wp + i * 4 * 6144);
    }
  }
  const uint32_t sb = smem_u32(smem_raw);
  const int warp = __shfl_sync(~0u, threadIdx.x >> 5, 0), lane = threadIdx.x & 31;
  const int rank = blockIdx.x & 1;
  const int t = sm >> 1, v = t < 32 || by_sm == 2 ? t : t < 60 ? t + 1 + (((t - 32) * 37) >> 8) : (t - 58) * 8;
  const int gr = 0x71546320u >> ((v & 7) * 4);
  const int cid = !by_sm ? (blockIdx.x >> 1) - 2 : extra ? (t & 1) - 2 : (gr & 4) * 8 + (v >> 3) * 4 + (gr & 3);
  const int bid = cid * 2 + rank;
  const int m = cid >> 2, j = (cid & 3) * 2 + rank;
  const uint32_t bar = sb + MISC;

  if (warp >= 8) {
    asm volatile("setmaxnreg.dec.sync.aligned.u32 40;");
    if (extra) {
      if (warp == 8) {
        if (lane == 0) { for (int s = 0; s < 6; s++) { mbar_init(bar + B_FULL6 + s * 8, 1); mbar_init(bar + B_EMPTY6 + s * 8, 8); } fence_async_smem(); }
        __syncwarp();
        asm volatile("bar.arrive 2, 288;" ::: "memory");
        __nanosleep(XSLEEP);
#pragma unroll 1
        for (int it = 0, s = 0, par = 1; it < 64; it++) {
          mbar_wait(bar + B_EMPTY6 + s * 8, par);
          expect_e(bar + B_FULL6 + s * 8, 32768); tma_3d_e(sb + s * 32768, &maps.wmod, bar + B_FULL6 + s * 8, 0, (it & 15) * 64, 12 + (it >> 4) * 4 + bid);
          if (++s == 6) { s = 0; par ^= 1; }
        }
      }
    } else if (warp < 10) {
      uint32_t f6 = bar + B_FULL6, d6 = sb + (warp == 8 ? BLK : rank * HALF), p6 = 1;
      auto next6 = [&]() { f6 += 8; d6 += 32768; if (f6 == bar + B_FULL6 + 48) { f6 -= 48; d6 -= RING; p6 ^= 1; } };
      auto drained4 = [&](int q, int late) { if (q < 5) mbar_wait(bar + B_EMPTY4 + (((late ? 0x10332 : 0x32110) >> (4 * q)) & 3) * 8, 1); };
      auto drained6 = [&](int q) { if (q < 3) mbar_wait(bar + B_EMPTY6 + ((0x154 >> (4 * q)) & 7) * 8, q >> 1); };
      auto skip6 = [&]() { mbar_wait(f6 + 48, p6); expect_e(f6, 0); next6(); };
      if (warp == 8) {
        if (lane == 0) {
          if (sb & 1023) bail();
          for (int b = 0; b < 2; b++) mbar_init(bar + B_X + b * 8, 1);
          for (int s = 0; s < 4; s++) { mbar_init(bar + B_FULL4 + s * 8, 2); mbar_init(bar + B_EMPTY4 + s * 8, 16); }
          for (int s = 0; s < 6; s++) { mbar_init(bar + B_FULL6 + s * 8, 2); mbar_init(bar + B_EMPTY6 + s * 8, 16); }
          for (int b = 0; b < 2; b++) { mbar_init(bar + B_RDY + b * 8, 8); mbar_init(bar + B_FREE + b * 8, 1); mbar_init(bar + B_HH + b * 8, 1); mbar_init(bar + B_OUT + b * 8, 2); mbar_init(bar + B_HALO + b * 8, 1); }
          mbar_init(bar + B_MOD, 1); mbar_init(bar + B_LAG, 4); mbar_init(bar + B_ALL, 1); mbar_init(bar + B_HH2, 1);
          asm volatile("st.shared.u32 [%0], 0;" :: "r"(bar + ZERO) : "memory");
          asm volatile("fence.mbarrier_init.release.cluster;" ::: "memory");
          fence_async_smem();
        }
        __syncwarp();
        cl_arrive_relaxed();
        for (int b = 0; b < 2; b++) { expect_e(bar + B_X + b * 8, BLK); tma_3d_e(sb + STG + b * BLK, &maps.x, bar + B_X + b * 8, j * 128 + b * 64, m * 64, 0); }
        mbar_wait(bar + B_X + 8, 0);
#pragma unroll 1
        for (int ph = 0; ph < 2; ph++) {
          const CUtensorMap* const m0 = ph ? &maps.w1 : &maps.wqkv;
#pragma unroll 1
          for (int it = 0; it < (ph ? 48 : 16); it++) {
            const int s = (it + 2 * ph) & 3;
            int a0 = (ph ? it & 48 : 16) + 2 * j, a1 = ph ? a0 : a0 + 16, k0 = (it < 16 ? own_order(it, j) : it & 15) * 64;
            uint32_t full = bar + B_FULL4 + s * 8, d = sb + s * 49152 + BLK;
            if (ph) drained6(it);
            mbar_wait(full + 32, ~(it >> 2) & 1);
            tma_3d_e(d, m0, full, 0, k0, a0);
            if (it < 4) { const uint32_t t0 = clock(); while ((uint32_t)clock() - t0 < GAP) {} }
            tma_3d_e(d + BLK, m0 + ph, full, 0, k0, a1);
            expect_e(full, 2 * BLK);
            if (it < 4) { const uint32_t t0 = clock(); while ((uint32_t)clock() - t0 < GAP) {} }
            if (it >= 44) {
              if (it == 44) { mbar_wait(bar + B_FREE, 0); mbar_wait(bar + B_FREE + 8, 0); expect_e(bar + B_X, 2 * BLK); }
              bulk_ld_e(sb + STG + (it - 44) * HALF, gs->x1 + bid * 2048 + (it - 44) * 512, HALF, bar + B_X);
            }
          }
          const CUtensorMap* const m1 = ph ? &maps.w1s : &maps.wqkv;
          const int a = ph ? 48 + j : 2 * j;
#pragma unroll 1
          for (int k0 = 0; k0 < 1024; k0 += 64) {
            drained4(k0 >> 6, ph);
            mbar_wait(f6 + 48, p6);
            tma_3d_e(d6, m1, f6, 0, k0, a);
            if (ph) tma_3d_e(d6 + HALF, &maps.w3s, f6, 0, k0, a);
            expect_e(f6, BLK);
            next6();
          }
          if (ph) break;
#pragma unroll 1
          for (int it = 0; it < 16; it++) {
            const int k0 = own_order(it, j) * 64;
            mbar_wait(f6 + 48, p6);
            tma_3d_e(d6, &maps.wo, f6, 0, k0, 2 * j);
            expect_e(f6, BLK);
            next6();
          }
          skip6();
        }
#pragma unroll 1
        for (int k0 = 0; k0 < F_; k0 += 64) {
          mbar_wait(f6 + 48, p6);
          tma_3d_e(d6, &maps.w2, f6, 0, k0, 2 * j);
          expect_e(f6, BLK);
          next6();
        }
      } else {
        if (lane < 9) prefetch_map(&maps.x + lane);
        const uint32_t ep = gs->epoch[blockIdx.x] + 1;
        cl_arrive_relaxed(); cl_wait();
        auto run6 = [&](const uint4* src, int n, int sw) {
          src += rank * 512;
#pragma unroll 1
          for (int it = 0; it < n; it++) {
            if (sw >= 0) drained4(it, sw);
            mbar_wait(f6 + 48, p6);
            bulk_ld_mc_e(d6, src, HALF, f6);
            expect_e(f6, BLK);
            next6();
            src += 1024;
          }
        };
        uint32_t ready = 0;
        auto need = [&](int e, uint32_t mask) {
          if (!(ready & mask)) {
            uint32_t n = 0;
            do { ready = __ballot_sync(~0u, ld_acquire(gs->flag + (m * 128 + e * 16 + (lane & 14)) * FS) == ep); SPIN_GUARD(n); } while (!(ready & mask));
            fence_async_global();
          }
        };
        auto fresh = [&](int e, int it, uint32_t full, uint32_t empty, int par, uint32_t slot, uint4* src) {
          mbar_wait(empty, par);
          expect_e(full, it < 2 ? 0 : BLK);
          if (it >= 4) {
            const int kb = own_order(it, j);
            if (it < 10) need(e, 1u << kb); else if (it == 10) mbar_wait(bar + B_ALL, e & 1);
            bulk_ld_mc_e(slot + rank * HALF, src + kb * 1024 + rank * 512, HALF, full);
          } else if (it >= 2) {
            const int b = it > 2;
            const uint32_t to_peer = mapa(sb, rank ^ 1) - sb;
            const bool push = b && e != 1;
            mbar_wait(bar + (push ? B_RDY : B_FREE) + b * 8, e & 1);
            if (push) bulk_push_e(slot + to_peer, sb + STG + BLK, BLK, full + to_peer);
            else { fence_async_global(); bulk_ld_e(slot + to_peer, src + (2 * j + b) * 1024, BLK, full + to_peer); }
          } else ready = 0;
        };
        uint4* const h = gs->h + m * 16384;
#pragma unroll 1
        for (int e = 0; e < 3; e++) {
#pragma unroll 1
          for (int it = 0; it < 16; it++) {
            const int s = (it + e) & 3;
            const uint32_t full = e == 1 ? f6 : bar + B_FULL4 + s * 8;
            if (e == 2) drained6(it);
            fresh(e, it, full, full + (e == 1 ? 48 : 32), e == 1 ? p6 : ~(it >> 2) & 1, e == 1 ? d6 - rank * HALF : sb + s * 49152, e == 1 ? gs->o + m * 16384 : h);
            if (e == 1) next6();
          }
          if (e == 1) { skip6(); continue; }
#pragma unroll 1
          for (int it = 16; it < 16 + 16 * e; it++) {
            const int s = (it + 2) & 3;
            const uint32_t full = bar + B_FULL4 + s * 8;
            mbar_wait(full + 32, ~(it >> 2) & 1);
            bulk_ld_mc_e(sb + s * 49152 + rank * HALF, h + (it & 15) * 1024 + rank * 512, HALF, full);
            expect_e(full, BLK);
          }
          run6(h, 16, e);
        }
#pragma unroll 1
        for (int q = 0; q < 3; q++) {
          mbar_wait(bar + (q == 2 ? B_HH2 : B_HH + q * 8), 0);
          run6(gs->hh + m * 57344 + (64 - (64 >> q)) * 1024, 32 >> q, -1);
        }
      }
    } else {
      const int b = warp - 10;
      const uint32_t ep = gs->epoch[blockIdx.x] + 1;
      const uint32_t stg = sb + STG + b * BLK;
      cl_arrive_relaxed(); cl_wait();
      auto all_there = [&](int u, uint32_t done) {
        const uint32_t* fl = gs->flag + u * FS;
        uint32_t n = 0;
        while (!__all_sync(~0u, ld_acquire(fl) == ep)) { __nanosleep(100); SPIN_GUARD(n); }
        fence_async_global();
        arrive_e(done);
      };
#pragma unroll 1
      for (int e = 0; e < 7 - b; e++) {
        const int kb = (e < 3 ? 2 * j : e < 6 ? 2 * (8 * (e - 3) + j) : 48 + j) + b;
        uint4* const dst = (e == 1 ? gs->o + m * 16384 : e < 3 ? gs->h + m * 16384 : gs->hh + m * 57344) + kb * 1024;
        uint32_t* const fl = gs->flag + (m * 128 + (e < 3 ? e * 16 : U_HH) + kb) * FS;
        if (e < 3 && lane < 8) st_rlx1(fl + lane, 0);
        if (b && e < 3) {
          mbar_wait(bar + B_FREE, e & 1);
          const uint32_t t0 = clock();
          while ((uint32_t)clock() - t0 < (e == 1 ? B1D : B1P)) {}
        }
        mbar_wait(bar + B_RDY + b * 8, e & 1);
        bulk_st_e(dst, stg, e < 3 ? BLK : BLK / NPIECE);
        if (e >= 3) {
#pragma unroll 1
          for (int q = 1; q < NPIECE; q++) { __nanosleep(PSLEEP); bulk_st_e(dst + q * (1024 / NPIECE), stg + q * (BLK / NPIECE), BLK / NPIECE); }
        }
        publish_e(bar + B_FREE + b * 8, fl, ep);
        if (b && (e < 3 || e == 4)) all_there(m * 128 + (e < 3 ? e * 16 + (lane & 15) : U_HH + lane), bar + (e < 3 ? B_ALL : B_HH));
        if (!b && (e == 1 || e == 2)) {
#pragma unroll 1
          for (int sec = e == 1 ? 2 : 5; sec < 4 + e; sec++) {
            const uint4* p = (const uint4*)(gs->modv + (sec - 2) * 1024 + j * 128) + lane;
            uint4 v0, v1; uint32_t n = 0;
            while (true) {
              v0 = ld_rlx4(p); v1 = ld_rlx4(p + 32);
              if (__all_sync(~0u, v0.y == ep && v0.w == ep && v1.y == ep && v1.w == ep)) break;
              SPIN_GUARD(n);
            }
            const uint32_t d = sb + MISC + MODV + sec * 256 + ((lane & 3) * 16 + (lane >> 2)) * 4;
            asm volatile("st.shared.u32 [%0], %1;" :: "r"(d), "r"(__byte_perm(v0.x, v0.z, 0x7632)) : "memory");
            asm volatile("st.shared.u32 [%0], %1;" :: "r"(d + 32), "r"(__byte_perm(v1.x, v1.z, 0x7632)) : "memory");
          }
          __syncwarp();
          if (e == 1) { arrive_e(bar + B_MOD); }
        }
        if (e == 0) {
          uint32_t* const hf = gs->flag + (m * 128 + 48 + 2 * j + b) * FS;
          uint4* const hp = gs->halo + ((m * 8 + j) * 2 + b) * 256;
          if (m < 15 && lane < 8) st_rlx1(hf + 128 * FS + lane, 0);
          mbar_wait(bar + B_OUT + b * 8, 0);
          if (m < 15) {
            for (int w = 0; w < 2; w++) bulk_st_e(hp + 4096 + w * 128, stg + w * HALF, 2048);
            publish_e(bar + B_OUT + b * 8, hf + 128 * FS, ep);
          }
          if (m > 0) {
            uint32_t n = 0;
            while (!__all_sync(~0u, ld_acquire(hf) == ep)) SPIN_GUARD(n);
            fence_async_global();
            for (int w = 0; w < 2; w++) bulk_ld_e(stg + w * HALF, hp + w * 128, 2048, bar + B_HALO + b * 8);
            expect_e(bar + B_HALO + b * 8, 4096);
          } else {
            __syncwarp();
#pragma unroll
            for (int i = 0; i < 8; i++) sts128(stg + (i >> 2) * HALF + (i & 3) * 512 + lane * 16, 0, 0, 0, 0);
            __syncwarp();
            arrive_e(bar + B_HALO + b * 8);
          }
        }
      }
      if (b) {
#pragma unroll 1
        for (int q = 0; q < 2; q++) all_there(m * 128 + U_HH + 32 + q * 16 + (lane & (15 >> q)), bar + (q ? B_HH2 : B_HH + 8));
      }
    }
  } else {
    const int wg = warp >> 2, wq = warp & 3, tid = threadIdx.x;
    const int g = lane >> 2, c = lane & 3;
    if (!extra) cl_arrive_relaxed();
    asm volatile("setmaxnreg.inc.sync.aligned.u32 232;" ::: "memory");
    if (__builtin_expect(extra, 0)) {
      const uint32_t ep = ep0 + 1;
      float sv[4];
#pragma unroll
      for (int p = 0; p < 4; p++) sv[p] = silu_c(__bfloat162float(cvec[64 * (4 * p + (lane >> 3)) + 8 * warp + (lane & 7)]));
      named_bar(2, 288);
      int s = 0, par = 0;
#pragma unroll 1
      for (int sec = 0; sec < 4; sec++) {
        float a[8] = {0, 0, 0, 0, 0, 0, 0, 0};
#pragma unroll 1
        for (int it = 0; it < 16; it++) {
          const float sc = it < 4 ? sv[0] : it < 8 ? sv[1] : it < 12 ? sv[2] : sv[3];
          mbar_wait(bar + B_FULL6 + s * 8, par);
          uint4 w[8];
#pragma unroll
          for (int i = 0; i < 8; i++) w[i] = lds128(sb + s * 32768 + (warp * 8 + i) * 512 + lane * 16);
#pragma unroll
          for (int i = 0; i < 8; i++) gemv_fma(a, w[i], __shfl_sync(~0u, sc, (it & 3) * 8 + i));
          if (lane == 0) mbar_arrive(bar + B_EMPTY6 + s * 8);
          if (++s == 6) { s = 0; par ^= 1; }
        }
        const uint32_t red = sb + STG + sec * 8192;
        sts128(red + warp * 1024 + lane * 32, __float_as_uint(a[0]), __float_as_uint(a[1]), __float_as_uint(a[2]), __float_as_uint(a[3]));
        sts128(red + warp * 1024 + lane * 32 + 16, __float_as_uint(a[4]), __float_as_uint(a[5]), __float_as_uint(a[6]), __float_as_uint(a[7]));
        named_bar(1, 256);
        float t = 0;
#pragma unroll
        for (int q = 0; q < 8; q++) t += lds32f(red + q * 1024 + tid * 4);
        t = bf_round(t);
        if (sec == 2) t = bf_round(t + 1.f);
        st_rlx2(gs->modv + sec * 1024 + (bid + 4) * 256 + tid, __float_as_uint(t), ep);
      }
      if (tid == 0) gs->epoch[blockIdx.x] = ep;
      return;
    }
    const int row0 = wg * 64 + wq * 16 + g;
    if (c < 2) st_rlx2(gs->stat + m * 1024 + j * 128 + row0 + c * 8, 0, 0);
    cl_wait();
    uint32_t ep;
    asm volatile("add.u32 %0, %1, 1;" : "=r"(ep) : "r"(ep0) : "memory");
    const float sc_ = silu_c(__uint_as_float((uint32_t)cv_ << 16));
    const uint32_t rel = mapa(bar, (lane & 1) ^ rank);
    const uint32_t stg_row = sb + STG + (wg * 64 + wq * 16 + (lane & 15)) * 128;
    const uint32_t fre = bar + B_FREE;
    Ring r4{0, 0, 0}, r6{0, 0, 0};
    auto none = [](auto) {};
    uint32_t xk[32];
    {
      float a[8] = {0, 0, 0, 0, 0, 0, 0, 0};
#pragma unroll
      for (int i = 0; i < 8; i++) gemv_fma(a, wv[i], __shfl_sync(~0u, sc_, i * 4 + (lane >> 3)));
#pragma unroll
      for (int i = 0; i < 8; i++) { a[i] += __shfl_xor_sync(~0u, a[i], 8); a[i] += __shfl_xor_sync(~0u, a[i], 16); }
      if (lane < 8) {
        sts128(sb + RED_OFF + warp * 256 + lane * 32, __float_as_uint(a[0]), __float_as_uint(a[1]), __float_as_uint(a[2]), __float_as_uint(a[3]));
        sts128(sb + RED_OFF + warp * 256 + lane * 32 + 16, __float_as_uint(a[4]), __float_as_uint(a[5]), __float_as_uint(a[6]), __float_as_uint(a[7]));
      }
      named_bar(1, 256);
      if (tid < 64) {
        float s = 0;
#pragma unroll
        for (int w = 0; w < 8; w++) s += lds32f(sb + RED_OFF + w * 256 + tid * 4);
        st_rlx1(gs->modp + u * 64 + tid, (__float_as_uint(s) & ~255u) | tag_of(ep));
      }
      float v[64];
      mbar_wait(bar + B_X, 0); mbar_wait(bar + B_X + 8, 0);
#pragma unroll
      for (int i = 0; i < 16; i += 2) {
        uint32_t w0, w1, w2, w3;
        ldsm4(stg_row + (i >> 3) * BLK + ((((i & 7) + (lane >> 4)) ^ (lane & 7)) << 4), w0, w1, w2, w3);
        xk[2 * i] = w0; xk[2 * i + 1] = w1; xk[2 * i + 2] = w2; xk[2 * i + 3] = w3;
        v[4 * i] = bf_lo(w0); v[4 * i + 1] = bf_hi(w0); v[4 * i + 2] = bf_lo(w1); v[4 * i + 3] = bf_hi(w1);
        v[4 * i + 4] = bf_lo(w2); v[4 * i + 5] = bf_hi(w2); v[4 * i + 6] = bf_lo(w3); v[4 * i + 7] = bf_hi(w3);
      }
      ln_publish(v, gs->stat + m * 1024, j, row0, lane, ep);
      mod_store(sb, tid >> 7, tid & 127, mod_gather(gs->modp + (tid >> 7) * 1024 + j * 128 + (tid & 127), ep));
      named_bar(1, 256);
      ln_apply(v, gs->stat + m * 1024, row0, ep, sb, 0, 1, stg_row, wg, lane);
      named_bar(1, 256);
    }
    {
      uint32_t kf[32], vf[32], pv[32];
      const bool first = wq == 0 && m == 0;
      const uint32_t xa = sb + STG + wg * HALF + wq * 2048 + lane * 16;
      {
        float acc[128];
        mainloop<256, 4, 0, 0>(acc, 16, true, r4, sb, wg, lane, rel, none, none, [&] {
          mbar_wait(fre + 8, 0);
          if (c < 2) st_rlx2(gs->stat + (16 + m) * 1024 + j * 128 + row0 + c * 8, 0, 0);
        });
#pragma unroll
        for (int i = 0; i < 32; i++) { kf[i] = pack2(acc[2 * i], acc[2 * i + 1]); vf[i] = pack2(acc[64 + 2 * i], acc[65 + 2 * i]); }
      }
      float acc[64];
      constexpr int QP = 2;
      auto inbox = [&](const int b) {
        if (wq == 0) mbar_wait(bar + B_HALO + b * 8, 0);
#pragma unroll
        for (int i = 4 * b; i < 4 * b + 4; i++) {
          uint4 q = lds128(xa + b * BLK + (i & 3) * 512);
          pv[4 * i] = q.x; pv[4 * i + 1] = q.y; pv[4 * i + 2] = q.z; pv[4 * i + 3] = q.w;
        }
        __syncwarp();
      };
      auto sent = [&](int b) { if (wq == 3) { fence_async_smem(); __syncwarp(); if (lane == 0) mbar_arrive(bar + B_OUT + b * 8); } };
      mainloop<128, 6, 8 / QP, 0>(acc, 16, false, r6, sb, wg, lane, rel, [&](auto ic) {
        constexpr int q = (ic.v - 1) * QP;
        if (q == 4) sent(0);
#pragma unroll
        for (int i = 4 * q; i < 4 * (q + QP); i++) vf[i] = movm(vf[i]);
#pragma unroll
        for (int i = q; i < q + QP; i++) sts128(xa + (wq == 3 ? -6144 : 2048) + (i >> 2) * BLK + (i & 3) * 512, kf[4 * i + 1], kf[4 * i + 3], vf[4 * i + 1], vf[4 * i + 3]);
      }, [&](int it) { if (it == 8 / QP + 1) sent(1); }, [&] {
        named_bar(2 + wg, 128);
        inbox(0);
      });
      int gz = g;
#pragma unroll
      for (int b = 0; b < 2; b++) {
        const bool up0 = 2 * c > gz, up1 = 2 * c + 1 > gz;
        const uint32_t mup = (up0 ? 0xffffu : 0u) | (up1 ? 0xffff0000u : 0u);
        float l[2][4], mx[4];
#pragma unroll
        for (int h = 0; h < 2; h++) {
          uint32_t q[8];
          const int k = 16 * b + 8 * h;
#pragma unroll
          for (int i = 0; i < 8; i++) q[i] = pack2(acc[2 * k + 2 * i], acc[2 * k + 2 * i + 1]);
          float s0[4], s1[4], s2[4];
          mma16z(s0, q[0], q[1], q[2], q[3], pv[k], pv[k + 1]); mma16z(s1, q[0], q[1], q[2], q[3], kf[k], kf[k + 2]); mma16z(s2, q[0], q[1], q[2], q[3], kf[k + 1], kf[k + 3]);
          mma16(s0, q[4], q[5], q[6], q[7], pv[k + 4], pv[k + 5]); mma16(s1, q[4], q[5], q[6], q[7], kf[k + 4], kf[k + 6]); mma16(s2, q[4], q[5], q[6], q[7], kf[k + 5], kf[k + 7]);
          if (first) { s0[0] = -INFINITY; s0[1] = -INFINITY; }
          l[h][0] = up0 ? s0[0] : s1[0]; l[h][1] = up1 ? s0[1] : s1[1]; l[h][2] = up0 ? s1[2] : s2[2]; l[h][3] = up1 ? s1[3] : s2[3];
          mx[2 * h] = fmaxf(l[h][0], l[h][1]); mx[2 * h + 1] = fmaxf(l[h][2], l[h][3]);
        }
#pragma unroll
        for (int o = 1; o < 4; o <<= 1) {
#pragma unroll
          for (int h = 0; h < 4; h++) mx[h] = fmaxf(mx[h], __shfl_xor_sync(~0u, mx[h], o));
        }
#pragma unroll
        for (int h = 0; h < 2; h++) {
          const float n0 = -mx[2 * h] * SCL, n1 = -mx[2 * h + 1] * SCL;
          const uint32_t pa = pack2(ex2(fmaf(l[h][0], SCL, n0)), ex2(fmaf(l[h][1], SCL, n0))), pb = pack2(ex2(fmaf(l[h][2], SCL, n1)), ex2(fmaf(l[h][3], SCL, n1)));
          float sm[4];
          mma8z(sm, pa, pb, 0x3f803f80u);
          const float ia = rcp(sm[0]), ib = rcp(sm[2]);
#pragma unroll
          for (int i = 8 * b + 4 * h; i < 8 * b + 4 * h + 4; i += 2) {
            uint32_t of[4];
#pragma unroll
            for (int d = 0; d < 2; d++) {
              float o[4];
              mma16z(o, pa & ~mup, pb & mup, 0u, pb & ~mup, vf[2 * (i + d)], vf[2 * (i + d) + 1]);
              mma8(o, pa & mup, 0u, pv[2 * i + 2 + d]);
              of[2 * d] = pack2(o[0] * ia, o[1] * ia); of[2 * d + 1] = pack2(o[2] * ib, o[3] * ib);
            }
            stsm4(stg_row + b * BLK + ((((i & 7) + (lane >> 4)) ^ (lane & 7)) << 4), of[0], of[1], of[2], of[3]);
          }
        }
        stage_done(sb, wg, b, lane);
        if (b == 0) inbox(1);
        if (b == 0) gz += __float_as_uint(lds32f(bar + ZERO));
      }
      named_bar(1, 256);
    }
    uint32_t pk[64];
    {
      float acc[64];
      mainloop<128, 6, 0, 0>(acc, 16, true, r6, sb, wg, lane, rel, none, none, [&] {
        mbar_wait(bar + B_MOD, 0); mbar_wait(fre + 8, 1);
        load_vec(pk + 32, sb, 2, 0, lane); load_vec(pk + 40, sb, 2, 1, lane);
#pragma unroll
        for (int i = 0; i < 32; i++) { pk[i] = xk[i]; asm volatile("" : "+r"(pk[i])); }
      });
#pragma unroll
      for (int i = 0; i < 32; i++) {
        acc[2 * i] = fmaf(acc[2 * i], bf_lo(pk[32 + (i >> 1)]), bf_lo(pk[i]));
        acc[2 * i + 1] = fmaf(acc[2 * i + 1], bf_hi(pk[32 + (i >> 1)]), bf_hi(pk[i]));
      }
      ln_publish(acc, gs->stat + (16 + m) * 1024, j, row0, lane, ep);
      mbar_wait(bar + B_FULL6 + 16, 1);
      if (lane < 2) mbar_arrive_cl(rel + B_EMPTY6 + 16);
      ring_next<6>(r6);
#pragma unroll
      for (int i = 0; i < 32; i++) { pk[i] = pack2(acc[2 * i], acc[2 * i + 1]); pk[32 + i] = 0; }
      ln_apply(acc, gs->stat + (16 + m) * 1024, row0, ep, sb, 3, 4, stg_row, wg, lane);
      named_bar(1, 256);
    }
    auto swiglu = [&](int q, int uo, int par) {
      if ((q & 3) == 0 && par >= 0) mbar_wait(fre + 2 * q, par);
      uint32_t w[4];
#pragma unroll
      for (int u = 0; u < 4; u++) w[u] = silu_mul2(pk[4 * q + u], pk[uo + 4 * q + u]);
      stsm4(stg_row + (q >> 2) * BLK + ((((2 * q & 7) + (lane >> 4)) ^ (lane & 7)) << 4), w[0], w[1], w[2], w[3]);
    };
    r4.s = r4.wrap = 2;
#pragma unroll 1
    for (int t = 0; t < 3; t++) {
      float acc[128];
      mainloop<256, 4, 4, 1>(acc, 16, t == 0, r4, sb, wg, lane, rel, [&](auto ic) {
        if (t) {
          if (ic.v == 3) stage_done(sb, wg, 0, lane);
          swiglu(2 * ic.v - 2, 32, ~t & 1); swiglu(2 * ic.v - 1, 32, 0);
        }
      }, [&](int it) {
        if (t && it == 5) stage_done(sb, wg, 1, lane);
        if (t == 0 && it >= 8) {
          uint4* p = gs->x1 + bid * 2048 + ((it >> 2) & 1) * 1024 + warp * 128 + (it & 3) * 32 + lane;
#pragma unroll
          for (int i = 0; i < 8; i++)
            asm volatile("{\n.reg .pred p;\nsetp.eq.u32 p, %5, %6;\n@p st.global.v4.u32 [%0], {%1,%2,%3,%4};\n}" :: "l"(p), "r"(pk[4 * i]), "r"(pk[4 * i + 1]), "r"(pk[4 * i + 2]), "r"(pk[4 * i + 3]), "r"(it), "r"(8 + i) : "memory");
        }
      }, [&] { if (t == 0) fence_async_global(); else if (t == 2) mbar_wait(bar + B_X, 1); }, t & 1);
#pragma unroll
      for (int i = 0; i < 64; i++) pk[i] = pack2(acc[2 * i], acc[2 * i + 1]);
    }
    uint32_t x1[32];
    {
      float acc[64];
      mainloop<128, 6, 10, 1>(acc, 16, false, r6, sb, wg, lane, rel, [&](auto ic) {
        constexpr int b = ic.v > 5, q = ic.v - 5 * b;
        if (q == 1) {
          if (b) stage_done(sb, wg, 0, lane);
#pragma unroll
          for (int i = 4 * b; i < 4 * b + 4; i++) { const uint4 x = lds128(sb + STG + b * BLK + warp * 2048 + (i & 3) * 512 + lane * 16); x1[4 * i] = x.x; x1[4 * i + 1] = x.y; x1[4 * i + 2] = x.z; x1[4 * i + 3] = x.w; }
          __syncwarp();
        } else swiglu(4 * b + q - 2, 32, -1);
      }, [&](int it) { if (it == 11) stage_done(sb, wg, 1, lane); }, [] {}, 1);
#pragma unroll
      for (int i = 0; i < 32; i++) pk[i] = pack2(acc[2 * i], acc[2 * i + 1]);
    }
    {
      float acc[64];
      mainloop<128, 6, 4, TAILLAG>(acc, 56, false, r6, sb, wg, lane, rel, [&](auto ic) { swiglu(ic.v - 1, 16, 1); },
                                   [&](int it) { if (it == 5) stage_done(sb, wg, 0, lane); }, [&] {
        load_vec(pk + 32, sb, 5, 0, lane); load_vec(pk + 40, sb, 5, 1, lane);
        mbar_wait(fre, 0); mbar_wait(fre + 8, 1);
      }, 0);
      __syncwarp();
      cl_arrive_relaxed();
#pragma unroll
      for (int i = 0; i < 16; i += 2) {
        uint32_t w[4];
#pragma unroll
        for (int u = 0; u < 4; u++) {
          const int q = 2 * i + u;
          w[u] = hfma2(pack2(acc[2 * q], acc[2 * q + 1]), pk[32 + (q >> 1)], x1[q]);
        }
        stsm4(stg_row + (i >> 3) * BLK + ((((i & 7) + (lane >> 4)) ^ (lane & 7)) << 4), w[0], w[1], w[2], w[3]);
        if ((i & 7) == 6) {
          fence_async_smem();
          __syncwarp();
          if (elect()) { tma_store_3d(&maps.out, sb + STG + (i >> 3) * BLK + warp * 2048, j * 128 + (i >> 3) * 64, m * 64 + wq * 16, wg); if (i > 8) bulk_commit(); }
        }
      }
      bulk_wait_read();
      if (tid == 0) gs->epoch[blockIdx.x] = ep;
      cl_wait();
    }
  }
}

typedef CUresult (*EncodeFn)(CUtensorMap*, CUtensorMapDataType, cuuint32_t, void*, const cuuint64_t*, const cuuint64_t*, const cuuint32_t*, const cuuint32_t*,
                             CUtensorMapInterleave, CUtensorMapSwizzle, CUtensorMapL2promotion, CUtensorMapFloatOOBfill);

void make_map(EncodeFn fn, CUtensorMap* mp, const void* base, uint64_t d0, uint64_t d1, uint64_t d2, uint64_t s1, uint64_t s2, uint32_t b2, uint32_t b0 = 64, uint32_t b1 = 64) {
  cuuint64_t d[3] = {d0, d1, d2}, s[2] = {s1, s2};
  cuuint32_t b[3] = {b0, b1, b2}, e[3] = {1, 1, 1};
  fn(mp, CU_TENSOR_MAP_DATA_TYPE_BFLOAT16, 3, (void*)base, d, s, b, e, CU_TENSOR_MAP_INTERLEAVE_NONE, b0 == 64 ? CU_TENSOR_MAP_SWIZZLE_128B : CU_TENSOR_MAP_SWIZZLE_NONE,
     CU_TENSOR_MAP_L2_PROMOTION_L2_128B, CU_TENSOR_MAP_FLOAT_OOB_FILL_NONE);
}

__global__ void probe_kernel() {}
int max_clusters(int size) {
  cudaLaunchConfig_t cfg = {};
  cudaLaunchAttribute at;
  at.id = cudaLaunchAttributeClusterDimension; at.val.clusterDim.x = size; at.val.clusterDim.y = 1; at.val.clusterDim.z = 1;
  cfg.gridDim = dim3(size * 66); cfg.blockDim = dim3(384); cfg.dynamicSmemBytes = SMEM_BYTES; cfg.attrs = &at; cfg.numAttrs = 1;
  int n = 0;
  if (cudaOccupancyMaxActiveClusters(&n, probe_kernel, &cfg) != cudaSuccess) { cudaGetLastError(); return 0; }
  return n;
}

}

extern "C" void kernel_launch(void* const* d_in, const int* in_sizes, int n_in, void* d_out, int out_size) {
  static EncodeFn fn = nullptr;
  static int by_sm = 0;
  static Scratch* gs = nullptr;
  if (!fn) {
    void* p = nullptr; cudaDriverEntryPointQueryResult q;
    cudaGetDriverEntryPoint("cuTensorMapEncodeTiled", &p, cudaEnableDefault, &q);
    fn = (EncodeFn)p;
    cudaFuncSetAttribute(fused_kernel, cudaFuncAttributeMaxDynamicSharedMemorySize, SMEM_BYTES);
    int dev = 0, sms = 0;
    cudaGetSymbolAddress((void**)&gs, g_scratch);
    cudaGetDevice(&dev);
    cudaDeviceGetAttribute(&sms, cudaDevAttrMultiProcessorCount, dev);
    cudaFuncSetAttribute(probe_kernel, cudaFuncAttributeMaxDynamicSharedMemorySize, SMEM_BYTES);
    if (sms == 132 && max_clusters(2) == 66) {
      const int c4 = max_clusters(4), c6 = max_clusters(6), c8 = max_clusters(8);
      by_sm = c4 == 30 && c6 == 17 && c8 == 15 ? 1 : c8 == 16 ? 2 : 0;
    }
  }
  Maps mp;
  make_map(fn, &mp.x, d_in[0], D_, S_ / 2, 2, 4096, 2048, 2);
  make_map(fn, &mp.out, d_out, D_, S_ / 2, 2, 4096, 2048, 1, 64, 16);
  make_map(fn, &mp.wqkv, d_in[1], 64, D_, 3 * D_ / 64, 3 * D_ * 2, 128, 2);
  make_map(fn, &mp.wo, d_in[2], 64, D_, D_ / 64, D_ * 2, 128, 2);
  make_map(fn, &mp.w1, d_in[4], 64, D_, F_ / 64, F_ * 2, 128, 2);
  make_map(fn, &mp.w3, d_in[5], 64, D_, F_ / 64, F_ * 2, 128, 2);
  make_map(fn, &mp.w1s, d_in[4], 64, D_, F_ / 64, F_ * 2, 128, 1);
  make_map(fn, &mp.w3s, d_in[5], 64, D_, F_ / 64, F_ * 2, 128, 1);
  make_map(fn, &mp.w2, d_in[6], 64, F_, D_ / 64, D_ * 2, 128, 2);
  make_map(fn, &mp.wmod, d_in[8], 256, D_, 24, 6 * D_ * 2, 512, 1, 256);
  fused_kernel<<<132, 384, SMEM_BYTES>>>((const bf16*)d_in[7], (const bf16*)d_in[8], gs, by_sm, mp);
}
```

```cpp
#include <cuda_runtime.h>
#include <cuda_bf16.h>
#include <cuda.h>
#include <stdint.h>

typedef __nv_bfloat16 bf16;

namespace {

constexpr int S_ = 2048, D_ = 1024, F_ = 3584;
constexpr int BLK = 16384;
constexpr int HALF = 8192;
constexpr int RING = 196608;
constexpr int STG = RING;
constexpr int MISC = RING + 2 * BLK;
constexpr int SMEM_BYTES = MISC + 3072;
constexpr int B_FULL4 = 0, B_EMPTY4 = 32, B_FULL6 = 64, B_EMPTY6 = 112, B_RDY = 160, B_FREE = 176, B_LAG = 192, B_X = 208, B_MOD = 224, B_OUT = 240, B_HH = 256, B_ALL = 272, B_HH2 = 288, ZERO = 296, B_HALO = 304;
constexpr int MODV = 512;
constexpr int RED_OFF = 0;
constexpr float SCL = 0.17677669529663687f * 1.4426950408889634f;
constexpr int U_HH = 64;
constexpr int FS = 8;
constexpr int NPIECE = 4, PSLEEP = 300;
constexpr int XSLEEP = 4000;
constexpr uint32_t GAP = 250;
constexpr uint32_t B1P = 3700, B1D = 700;
constexpr int TAILLAG = 5;

struct Maps { CUtensorMap x, out, wqkv, wo, w1, w3, w1s, w3s, w2, wmod; };

struct Scratch {
  uint32_t epoch[256];
  uint32_t flag[16 * 128 * FS];
  uint32_t modp[8 * 2 * 4 * 128];
  uint2 modv[4 * 1024];
  uint2 stat[2 * 16 * 8 * 128];
  uint4 halo[16 * 8 * 2 * 256];
  uint4 x1[128 * 8 * 256];
  uint4 h[16 * 16 * 1024];
  uint4 o[16 * 16 * 1024];
  uint4 hh[16 * 56 * 1024];
};
__device__ __align__(1024) Scratch g_scratch;

__device__ __forceinline__ void bail() { asm volatile("st.global.u32 [%0], %1;" :: "l"(0ull), "r"(0) : "memory"); }
__device__ __forceinline__ uint32_t smem_u32(const void* p) { return (uint32_t)__cvta_generic_to_shared(p); }
__device__ __forceinline__ void mbar_init(uint32_t bar, uint32_t cnt) { asm volatile("mbarrier.init.shared::cta.b64 [%0], %1;" :: "r"(bar), "r"(cnt) : "memory"); }
__device__ __forceinline__ void mbar_arrive(uint32_t bar) { asm volatile("mbarrier.arrive.shared::cta.b64 _, [%0];" :: "r"(bar) : "memory"); }
__device__ __forceinline__ void mbar_arrive_cl(uint32_t cl_addr) { asm volatile("mbarrier.arrive.shared::cluster.b64 _, [%0];" :: "r"(cl_addr) : "memory"); }
__device__ __forceinline__ uint32_t mapa(uint32_t addr, uint32_t cta) { uint32_t r; asm("mapa.shared::cluster.u32 %0, %1, %2;" : "=r"(r) : "r"(addr), "r"(cta)); return r; }
__device__ __forceinline__ void mbar_wait(uint32_t bar, uint32_t parity) {
  asm volatile("{\n.reg .pred p;\n.reg .b32 n;\n.reg .b64 z;\nmov.b32 n, 0;\nmov.b64 z, 0;\n"
               "W: add.u32 n, n, 1;\nsetp.gt.u32 p, n, 0x400000;\n@p st.global.u32 [z], n;\n"
               "mbarrier.try_wait.parity.shared::cta.b64 p, [%0], %1;\n@!p bra W;\n}" :: "r"(bar), "r"(parity) : "memory");
}
__device__ __forceinline__ void tma_store_3d(const CUtensorMap* m, uint32_t src, int c0, int c1, int c2) {
  asm volatile("cp.async.bulk.tensor.3d.global.shared::cta.bulk_group [%0, {%2, %3, %4}], [%1];" :: "l"(m), "r"(src), "r"(c0), "r"(c1), "r"(c2) : "memory");
}
#define ELECT "{\n.reg .pred p;\nelect.sync _|p, 0xffffffff;\n@p "
__device__ __forceinline__ void expect_e(uint32_t bar, uint32_t bytes) { asm volatile(ELECT "mbarrier.arrive.expect_tx.shared::cta.b64 _, [%0], %1;\n}" :: "r"(bar), "r"(bytes) : "memory"); }
__device__ __forceinline__ void tma_3d_e(uint32_t dst, const CUtensorMap* m, uint32_t bar, int c0, int c1, int c2) {
  asm volatile(ELECT "cp.async.bulk.tensor.3d.shared::cluster.global.mbarrier::complete_tx::bytes [%0], [%1, {%3, %4, %5}], [%2];\n}" :: "r"(dst), "l"(m), "r"(bar), "r"(c0), "r"(c1), "r"(c2) : "memory");
}
__device__ __forceinline__ void bulk_ld_e(uint32_t dst, const void* src, uint32_t bytes, uint32_t bar) {
  asm volatile(ELECT "cp.async.bulk.shared::cluster.global.mbarrier::complete_tx::bytes [%0], [%1], %2, [%3];\n}" :: "r"(dst), "l"(src), "r"(bytes), "r"(bar) : "memory");
}
__device__ __forceinline__ void bulk_ld_mc_e(uint32_t dst, const void* src, uint32_t bytes, uint32_t bar) {
  asm volatile(ELECT "cp.async.bulk.shared::cluster.global.mbarrier::complete_tx::bytes.multicast::cluster [%0], [%1], %2, [%3], %4;\n}" :: "r"(dst), "l"(src), "r"(bytes), "r"(bar), "h"((uint16_t)3) : "memory");
}
__device__ __forceinline__ void bulk_push_e(uint32_t dst_cl, uint32_t src, uint32_t bytes, uint32_t bar_cl) {
  asm volatile(ELECT "cp.async.bulk.shared::cluster.shared::cta.mbarrier::complete_tx::bytes [%0], [%1], %2, [%3];\n}" :: "r"(dst_cl), "r"(src), "r"(bytes), "r"(bar_cl) : "memory");
}
__device__ __forceinline__ void arrive_e(uint32_t bar) { asm volatile(ELECT "mbarrier.arrive.shared::cta.b64 _, [%0];\n}" :: "r"(bar) : "memory"); }
__device__ __forceinline__ void bulk_st_e(void* dst, uint32_t src, uint32_t bytes) {
  asm volatile(ELECT "cp.async.bulk.global.shared::cta.bulk_group [%0], [%1], %2;\n}" :: "l"(dst), "r"(src), "r"(bytes) : "memory");
}
__device__ __forceinline__ void publish_e(uint32_t free_bar, uint32_t* flag, uint32_t ep) {
  asm volatile(ELECT "cp.async.bulk.commit_group;\n@p cp.async.bulk.wait_group 0;\n@p mbarrier.arrive.shared::cta.b64 _, [%0];\n@p st.release.gpu.global.u32 [%1], %2;\n}"
               :: "r"(free_bar), "l"(flag), "r"(ep) : "memory");
}
__device__ __forceinline__ void bulk_commit() { asm volatile("cp.async.bulk.commit_group;" ::: "memory"); }
__device__ __forceinline__ void bulk_wait_read() { asm volatile("cp.async.bulk.wait_group.read 0;" ::: "memory"); }
__device__ __forceinline__ void fence_async_global() { asm volatile("fence.proxy.async.global;" ::: "memory"); }
__device__ __forceinline__ void fence_async_smem() { asm volatile("fence.proxy.async.shared::cta;" ::: "memory"); }
__device__ __forceinline__ void wg_arrive() { asm volatile("wgmma.fence.sync.aligned;" ::: "memory"); }
__device__ __forceinline__ void wg_commit() { asm volatile("wgmma.commit_group.sync.aligned;" ::: "memory"); }
template <int N> __device__ __forceinline__ void wg_wait() { asm volatile("wgmma.wait_group.sync.aligned %0;" :: "n"(N) : "memory"); }
__device__ __forceinline__ void cl_arrive_relaxed() { asm volatile("barrier.cluster.arrive.relaxed.aligned;" ::: "memory"); }
__device__ __forceinline__ void cl_wait() { asm volatile("barrier.cluster.wait.acquire.aligned;" ::: "memory"); }
__device__ __forceinline__ bool elect() { uint32_t p; asm volatile("{\n.reg .pred p;\nelect.sync _|p, 0xffffffff;\nselp.u32 %0, 1, 0, p;\n}" : "=r"(p)); return p; }
__device__ __forceinline__ void named_bar(int id, int n) { asm volatile("bar.sync %0, %1;" :: "r"(id), "r"(n) : "memory"); }
__device__ __forceinline__ uint32_t pack2(float lo, float hi) { uint32_t r; asm("cvt.rn.bf16x2.f32 %0, %1, %2;" : "=r"(r) : "f"(hi), "f"(lo)); return r; }
__device__ __forceinline__ float bf_lo(uint32_t w) { return __uint_as_float(w << 16); }
__device__ __forceinline__ float bf_hi(uint32_t w) { return __uint_as_float(w & 0xffff0000u); }
__device__ __forceinline__ float bf_round(float v) { return __bfloat162float(__float2bfloat16_rn(v)); }
__device__ __forceinline__ void stsm4(uint32_t addr, uint32_t a, uint32_t b, uint32_t c, uint32_t d) {
  asm volatile("stmatrix.sync.aligned.m8n8.x4.shared.b16 [%0], {%1, %2, %3, %4};" :: "r"(addr), "r"(a), "r"(b), "r"(c), "r"(d) : "memory");
}
__device__ __forceinline__ void ldsm4(uint32_t addr, uint32_t& a, uint32_t& b, uint32_t& c, uint32_t& d) {
  asm volatile("ldmatrix.sync.aligned.m8n8.x4.shared.b16 {%0, %1, %2, %3}, [%4];" : "=r"(a), "=r"(b), "=r"(c), "=r"(d) : "r"(addr) : "memory");
}
__device__ __forceinline__ uint32_t movm(uint32_t a) { uint32_t r; asm volatile("movmatrix.sync.aligned.m8n8.trans.b16 %0, %1;" : "=r"(r) : "r"(a)); return r; }
__device__ __forceinline__ void mma16(float (&d)[4], uint32_t a0, uint32_t a1, uint32_t a2, uint32_t a3, uint32_t b0, uint32_t b1) {
  asm("mma.sync.aligned.m16n8k16.row.col.f32.bf16.bf16.f32 {%0,%1,%2,%3}, {%4,%5,%6,%7}, {%8,%9}, {%0,%1,%2,%3};"
               : "+f"(d[0]), "+f"(d[1]), "+f"(d[2]), "+f"(d[3]) : "r"(a0), "r"(a1), "r"(a2), "r"(a3), "r"(b0), "r"(b1));
}
__device__ __forceinline__ void mma16z(float (&d)[4], uint32_t a0, uint32_t a1, uint32_t a2, uint32_t a3, uint32_t b0, uint32_t b1) {
  asm("mma.sync.aligned.m16n8k16.row.col.f32.bf16.bf16.f32 {%0,%1,%2,%3}, {%4,%5,%6,%7}, {%8,%9}, {%10,%10,%10,%10};"
      : "=f"(d[0]), "=f"(d[1]), "=f"(d[2]), "=f"(d[3]) : "r"(a0), "r"(a1), "r"(a2), "r"(a3), "r"(b0), "r"(b1), "f"(0.f));
}
__device__ __forceinline__ void mma8z(float (&d)[4], uint32_t a0, uint32_t a1, uint32_t b0) {
  asm("mma.sync.aligned.m16n8k8.row.col.f32.bf16.bf16.f32 {%0,%1,%2,%3}, {%4,%5}, {%6}, {%7,%7,%7,%7};"
      : "=f"(d[0]), "=f"(d[1]), "=f"(d[2]), "=f"(d[3]) : "r"(a0), "r"(a1), "r"(b0), "f"(0.f));
}
__device__ __forceinline__ void mma8(float (&d)[4], uint32_t a0, uint32_t a1, uint32_t b0) {
  asm("mma.sync.aligned.m16n8k8.row.col.f32.bf16.bf16.f32 {%0,%1,%2,%3}, {%4,%5}, {%6}, {%0,%1,%2,%3};"
               : "+f"(d[0]), "+f"(d[1]), "+f"(d[2]), "+f"(d[3]) : "r"(a0), "r"(a1), "r"(b0));
}
__device__ __forceinline__ uint4 lds128(uint32_t a) { uint4 v; asm volatile("ld.shared.v4.u32 {%0,%1,%2,%3}, [%4];" : "=r"(v.x), "=r"(v.y), "=r"(v.z), "=r"(v.w) : "r"(a) : "memory"); return v; }
__device__ __forceinline__ void sts128(uint32_t a, uint32_t x, uint32_t y, uint32_t z, uint32_t w) { asm volatile("st.shared.v4.u32 [%0], {%1,%2,%3,%4};" :: "r"(a), "r"(x), "r"(y), "r"(z), "r"(w) : "memory"); }
__device__ __forceinline__ float lds32f(uint32_t a) { float v; asm volatile("ld.shared.f32 %0, [%1];" : "=f"(v) : "r"(a) : "memory"); return v; }
__device__ __forceinline__ void sts16(uint32_t a, bf16 v) { asm volatile("st.shared.b16 [%0], %1;" :: "r"(a), "h"(__bfloat16_as_ushort(v)) : "memory"); }
__device__ __forceinline__ uint4 ldg_nc(const void* p) { uint4 v; asm volatile("ld.global.nc.L1::no_allocate.v4.u32 {%0,%1,%2,%3}, [%4];" : "=r"(v.x), "=r"(v.y), "=r"(v.z), "=r"(v.w) : "l"(p)); return v; }
__device__ __forceinline__ uint4 ld_rlx4(const uint4* p) {
  unsigned long long a, b; asm volatile("ld.relaxed.gpu.global.v2.b64 {%0,%1}, [%2];" : "=l"(a), "=l"(b) : "l"(p) : "memory");
  return make_uint4((uint32_t)a, (uint32_t)(a >> 32), (uint32_t)b, (uint32_t)(b >> 32));
}
__device__ __forceinline__ uint2 ld_rlx2(const uint2* p) { unsigned long long a; asm volatile("ld.relaxed.gpu.global.b64 %0, [%1];" : "=l"(a) : "l"(p) : "memory"); return make_uint2((uint32_t)a, (uint32_t)(a >> 32)); }
__device__ __forceinline__ void st_rlx2(uint2* p, uint32_t x, uint32_t y) { asm volatile("st.relaxed.gpu.global.b64 [%0], %1;" :: "l"(p), "l"((unsigned long long)x | ((unsigned long long)y << 32)) : "memory"); }
__device__ __forceinline__ void st_rlx1(uint32_t* p, uint32_t v) { asm volatile("st.relaxed.gpu.global.u32 [%0], %1;" :: "l"(p), "r"(v) : "memory"); }
__device__ __forceinline__ uint32_t ld_rlx1(const uint32_t* p) { uint32_t v; asm volatile("ld.relaxed.gpu.global.u32 %0, [%1];" : "=r"(v) : "l"(p) : "memory"); return v; }
__device__ __forceinline__ uint32_t ld_acquire(const uint32_t* p) { uint32_t v; asm volatile("ld.acquire.gpu.global.u32 %0, [%1];" : "=r"(v) : "l"(p) : "memory"); return v; }
__device__ __forceinline__ void prefetch_map(const CUtensorMap* m) { asm volatile("prefetch.tensormap [%0];" :: "l"(m) : "memory"); }
__device__ __forceinline__ float rcp(float x) { float r; asm("rcp.approx.ftz.f32 %0, %1;" : "=f"(r) : "f"(x)); return r; }
__device__ __forceinline__ float ex2(float x) { float r; asm("ex2.approx.ftz.f32 %0, %1;" : "=f"(r) : "f"(x)); return r; }
__device__ __forceinline__ float tanh_fast(float x) { float r; asm("tanh.approx.f32 %0, %1;" : "=f"(r) : "f"(x)); return r; }
#define SPIN_GUARD(n) if (++(n) > (1u << 24)) bail()

__device__ __forceinline__ void wgmma_n128(float (&d)[64], uint64_t da, uint64_t db) {
  asm volatile("wgmma.mma_async.sync.aligned.m64n128k16.f32.bf16.bf16 "
    "{%0, %1, %2, %3, %4, %5, %6, %7, %8, %9, %10, %11, %12, %13, %14, %15, %16, %17, %18, %19, %20, %21, %22, %23, %24, %25, %26, %27, %28, %29, %30, %31, %32, %33, %34, %35, %36, %37, %38, %39, %40, %41, %42, %43, %44, %45, %46, %47, %48, %49, %50, %51, %52, %53, %54, %55, %56, %57, %58, %59, %60, %61, %62, %63}, "
    "%64, %65, 1, 1, 1, 0, 1;\n"
    : "+f"(d[0]), "+f"(d[1]), "+f"(d[2]), "+f"(d[3]), "+f"(d[4]), "+f"(d[5]), "+f"(d[6]), "+f"(d[7]), "+f"(d[8]), "+f"(d[9]), "+f"(d[10]), "+f"(d[11]), "+f"(d[12]), "+f"(d[13]), "+f"(d[14]), "+f"(d[15]), "+f"(d[16]), "+f"(d[17]), "+f"(d[18]), "+f"(d[19]), "+f"(d[20]), "+f"(d[21]), "+f"(d[22]), "+f"(d[23]), "+f"(d[24]), "+f"(d[25]), "+f"(d[26]), "+f"(d[27]), "+f"(d[28]), "+f"(d[29]), "+f"(d[30]), "+f"(d[31]), "+f"(d[32]), "+f"(d[33]), "+f"(d[34]), "+f"(d[35]), "+f"(d[36]), "+f"(d[37]), "+f"(d[38]), "+f"(d[39]), "+f"(d[40]), "+f"(d[41]), "+f"(d[42]), "+f"(d[43]), "+f"(d[44]), "+f"(d[45]), "+f"(d[46]), "+f"(d[47]), "+f"(d[48]), "+f"(d[49]), "+f"(d[50]), "+f"(d[51]), "+f"(d[52]), "+f"(d[53]), "+f"(d[54]), "+f"(d[55]), "+f"(d[56]), "+f"(d[57]), "+f"(d[58]), "+f"(d[59]), "+f"(d[60]), "+f"(d[61]), "+f"(d[62]), "+f"(d[63])
    : "l"(da), "l"(db));
}
__device__ __forceinline__ void wgmma_n128_first(float (&d)[64], uint64_t da, uint64_t db) {
  asm volatile("wgmma.mma_async.sync.aligned.m64n128k16.f32.bf16.bf16 "
    "{%0, %1, %2, %3, %4, %5, %6, %7, %8, %9, %10, %11, %12, %13, %14, %15, %16, %17, %18, %19, %20, %21, %22, %23, %24, %25, %26, %27, %28, %29, %30, %31, %32, %33, %34, %35, %36, %37, %38, %39, %40, %41, %42, %43, %44, %45, %46, %47, %48, %49, %50, %51, %52, %53, %54, %55, %56, %57, %58, %59, %60, %61, %62, %63}, "
    "%64, %65, 0, 1, 1, 0, 1;\n"
    : "=f"(d[0]), "=f"(d[1]), "=f"(d[2]), "=f"(d[3]), "=f"(d[4]), "=f"(d[5]), "=f"(d[6]), "=f"(d[7]), "=f"(d[8]), "=f"(d[9]), "=f"(d[10]), "=f"(d[11]), "=f"(d[12]), "=f"(d[13]), "=f"(d[14]), "=f"(d[15]), "=f"(d[16]), "=f"(d[17]), "=f"(d[18]), "=f"(d[19]), "=f"(d[20]), "=f"(d[21]), "=f"(d[22]), "=f"(d[23]), "=f"(d[24]), "=f"(d[25]), "=f"(d[26]), "=f"(d[27]), "=f"(d[28]), "=f"(d[29]), "=f"(d[30]), "=f"(d[31]), "=f"(d[32]), "=f"(d[33]), "=f"(d[34]), "=f"(d[35]), "=f"(d[36]), "=f"(d[37]), "=f"(d[38]), "=f"(d[39]), "=f"(d[40]), "=f"(d[41]), "=f"(d[42]), "=f"(d[43]), "=f"(d[44]), "=f"(d[45]), "=f"(d[46]), "=f"(d[47]), "=f"(d[48]), "=f"(d[49]), "=f"(d[50]), "=f"(d[51]), "=f"(d[52]), "=f"(d[53]), "=f"(d[54]), "=f"(d[55]), "=f"(d[56]), "=f"(d[57]), "=f"(d[58]), "=f"(d[59]), "=f"(d[60]), "=f"(d[61]), "=f"(d[62]), "=f"(d[63])
    : "l"(da), "l"(db));
}
__device__ __forceinline__ void wgmma_n256(float (&d)[128], uint64_t da, uint64_t db) {
  asm volatile("wgmma.mma_async.sync.aligned.m64n256k16.f32.bf16.bf16 "
    "{%0, %1, %2, %3, %4, %5, %6, %7, %8, %9, %10, %11, %12, %13, %14, %15, %16, %17, %18, %19, %20, %21, %22, %23, %24, %25, %26, %27, %28, %29, %30, %31, %32, %33, %34, %35, %36, %37, %38, %39, %40, %41, %42, %43, %44, %45, %46, %47, %48, %49, %50, %51, %52, %53, %54, %55, %56, %57, %58, %59, %60, %61, %62, %63, %64, %65, %66, %67, %68, %69, %70, %71, %72, %73, %74, %75, %76, %77, %78, %79, %80, %81, %82, %83, %84, %85, %86, %87, %88, %89, %90, %91, %92, %93, %94, %95, %96, %97, %98, %99, %100, %101, %102, %103, %104, %105, %106, %107, %108, %109, %110, %111, %112, %113, %114, %115, %116, %117, %118, %119, %120, %121, %122, %123, %124, %125, %126, %127}, "
    "%128, %129, 1, 1, 1, 0, 1;\n"
    : "+f"(d[0]), "+f"(d[1]), "+f"(d[2]), "+f"(d[3]), "+f"(d[4]), "+f"(d[5]), "+f"(d[6]), "+f"(d[7]), "+f"(d[8]), "+f"(d[9]), "+f"(d[10]), "+f"(d[11]), "+f"(d[12]), "+f"(d[13]), "+f"(d[14]), "+f"(d[15]), "+f"(d[16]), "+f"(d[17]), "+f"(d[18]), "+f"(d[19]), "+f"(d[20]), "+f"(d[21]), "+f"(d[22]), "+f"(d[23]), "+f"(d[24]), "+f"(d[25]), "+f"(d[26]), "+f"(d[27]), "+f"(d[28]), "+f"(d[29]), "+f"(d[30]), "+f"(d[31]), "+f"(d[32]), "+f"(d[33]), "+f"(d[34]), "+f"(d[35]), "+f"(d[36]), "+f"(d[37]), "+f"(d[38]), "+f"(d[39]), "+f"(d[40]), "+f"(d[41]), "+f"(d[42]), "+f"(d[43]), "+f"(d[44]), "+f"(d[45]), "+f"(d[46]), "+f"(d[47]), "+f"(d[48]), "+f"(d[49]), "+f"(d[50]), "+f"(d[51]), "+f"(d[52]), "+f"(d[53]), "+f"(d[54]), "+f"(d[55]), "+f"(d[56]), "+f"(d[57]), "+f"(d[58]), "+f"(d[59]), "+f"(d[60]), "+f"(d[61]), "+f"(d[62]), "+f"(d[63]), "+f"(d[64]), "+f"(d[65]), "+f"(d[66]), "+f"(d[67]), "+f"(d[68]), "+f"(d[69]), "+f"(d[70]), "+f"(d[71]), "+f"(d[72]), "+f"(d[73]), "+f"(d[74]), "+f"(d[75]), "+f"(d[76]), "+f"(d[77]), "+f"(d[78]), "+f"(d[79]), "+f"(d[80]), "+f"(d[81]), "+f"(d[82]), "+f"(d[83]), "+f"(d[84]), "+f"(d[85]), "+f"(d[86]), "+f"(d[87]), "+f"(d[88]), "+f"(d[89]), "+f"(d[90]), "+f"(d[91]), "+f"(d[92]), "+f"(d[93]), "+f"(d[94]), "+f"(d[95]), "+f"(d[96]), "+f"(d[97]), "+f"(d[98]), "+f"(d[99]), "+f"(d[100]), "+f"(d[101]), "+f"(d[102]), "+f"(d[103]), "+f"(d[104]), "+f"(d[105]), "+f"(d[106]), "+f"(d[107]), "+f"(d[108]), "+f"(d[109]), "+f"(d[110]), "+f"(d[111]), "+f"(d[112]), "+f"(d[113]), "+f"(d[114]), "+f"(d[115]), "+f"(d[116]), "+f"(d[117]), "+f"(d[118]), "+f"(d[119]), "+f"(d[120]), "+f"(d[121]), "+f"(d[122]), "+f"(d[123]), "+f"(d[124]), "+f"(d[125]), "+f"(d[126]), "+f"(d[127])
    : "l"(da), "l"(db));
}
__device__ __forceinline__ void wgmma_n256_first(float (&d)[128], uint64_t da, uint64_t db) {
  asm volatile("wgmma.mma_async.sync.aligned.m64n256k16.f32.bf16.bf16 "
    "{%0, %1, %2, %3, %4, %5, %6, %7, %8, %9, %10, %11, %12, %13, %14, %15, %16, %17, %18, %19, %20, %21, %22, %23, %24, %25, %26, %27, %28, %29, %30, %31, %32, %33, %34, %35, %36, %37, %38, %39, %40, %41, %42, %43, %44, %45, %46, %47, %48, %49, %50, %51, %52, %53, %54, %55, %56, %57, %58, %59, %60, %61, %62, %63, %64, %65, %66, %67, %68, %69, %70, %71, %72, %73, %74, %75, %76, %77, %78, %79, %80, %81, %82, %83, %84, %85, %86, %87, %88, %89, %90, %91, %92, %93, %94, %95, %96, %97, %98, %99, %100, %101, %102, %103, %104, %105, %106, %107, %108, %109, %110, %111, %112, %113, %114, %115, %116, %117, %118, %119, %120, %121, %122, %123, %124, %125, %126, %127}, "
    "%128, %129, 0, 1, 1, 0, 1;\n"
    : "=f"(d[0]), "=f"(d[1]), "=f"(d[2]), "=f"(d[3]), "=f"(d[4]), "=f"(d[5]), "=f"(d[6]), "=f"(d[7]), "=f"(d[8]), "=f"(d[9]), "=f"(d[10]), "=f"(d[11]), "=f"(d[12]), "=f"(d[13]), "=f"(d[14]), "=f"(d[15]), "=f"(d[16]), "=f"(d[17]), "=f"(d[18]), "=f"(d[19]), "=f"(d[20]), "=f"(d[21]), "=f"(d[22]), "=f"(d[23]), "=f"(d[24]), "=f"(d[25]), "=f"(d[26]), "=f"(d[27]), "=f"(d[28]), "=f"(d[29]), "=f"(d[30]), "=f"(d[31]), "=f"(d[32]), "=f"(d[33]), "=f"(d[34]), "=f"(d[35]), "=f"(d[36]), "=f"(d[37]), "=f"(d[38]), "=f"(d[39]), "=f"(d[40]), "=f"(d[41]), "=f"(d[42]), "=f"(d[43]), "=f"(d[44]), "=f"(d[45]), "=f"(d[46]), "=f"(d[47]), "=f"(d[48]), "=f"(d[49]), "=f"(d[50]), "=f"(d[51]), "=f"(d[52]), "=f"(d[53]), "=f"(d[54]), "=f"(d[55]), "=f"(d[56]), "=f"(d[57]), "=f"(d[58]), "=f"(d[59]), "=f"(d[60]), "=f"(d[61]), "=f"(d[62]), "=f"(d[63]), "=f"(d[64]), "=f"(d[65]), "=f"(d[66]), "=f"(d[67]), "=f"(d[68]), "=f"(d[69]), "=f"(d[70]), "=f"(d[71]), "=f"(d[72]), "=f"(d[73]), "=f"(d[74]), "=f"(d[75]), "=f"(d[76]), "=f"(d[77]), "=f"(d[78]), "=f"(d[79]), "=f"(d[80]), "=f"(d[81]), "=f"(d[82]), "=f"(d[83]), "=f"(d[84]), "=f"(d[85]), "=f"(d[86]), "=f"(d[87]), "=f"(d[88]), "=f"(d[89]), "=f"(d[90]), "=f"(d[91]), "=f"(d[92]), "=f"(d[93]), "=f"(d[94]), "=f"(d[95]), "=f"(d[96]), "=f"(d[97]), "=f"(d[98]), "=f"(d[99]), "=f"(d[100]), "=f"(d[101]), "=f"(d[102]), "=f"(d[103]), "=f"(d[104]), "=f"(d[105]), "=f"(d[106]), "=f"(d[107]), "=f"(d[108]), "=f"(d[109]), "=f"(d[110]), "=f"(d[111]), "=f"(d[112]), "=f"(d[113]), "=f"(d[114]), "=f"(d[115]), "=f"(d[116]), "=f"(d[117]), "=f"(d[118]), "=f"(d[119]), "=f"(d[120]), "=f"(d[121]), "=f"(d[122]), "=f"(d[123]), "=f"(d[124]), "=f"(d[125]), "=f"(d[126]), "=f"(d[127])
    : "l"(da), "l"(db));
}

template <int N> struct WG;
#define DEF_WG(N) template <> struct WG<N> { \
  static __device__ __forceinline__ void mma(float (&d)[N / 2], uint64_t a, uint64_t b) { wgmma_n##N(d, a, b); } \
  static __device__ __forceinline__ void first(float (&d)[N / 2], uint64_t a, uint64_t b) { wgmma_n##N##_first(d, a, b); } };
DEF_WG(128) DEF_WG(256)

constexpr uint64_t DESC_A = (1ull << 62) | ((uint64_t)(1024 >> 4) << 32) | (1ull << 16);
constexpr uint64_t DESC_B = (1ull << 62) | ((uint64_t)(1024 >> 4) << 32) | ((uint64_t)(8192 >> 4) << 16);

struct Ring { int s; uint32_t ph; int wrap; };
template <int NS> __device__ __forceinline__ void ring_next(Ring& r) { r.s = (r.s + 1 == NS) ? 0 : r.s + 1; if (r.s == r.wrap) r.ph ^= 1; }

__device__ __forceinline__ int own_order(int it, int j) {
  return it < 2 ? 2 * j + it : it < 4 ? 2 * (j ^ 1) + it - 2 : ((j >> 1) * 4 + 2 * it - (it < 10 ? 4 : 15)) & 15;
}

template <int V> struct IC { static constexpr int v = V; };
template <int I, int E, class F> __device__ __forceinline__ void static_for(F&& f) { if constexpr (I < E) { f(IC<I>{}); static_for<I + 1, E>(f); } }

template <int N, int NS, int PRE, int LAG, class Pre, class Mid, class Last>
__device__ __forceinline__ void mainloop(float (&acc)[N / 2], int nkb, bool own, Ring& r, uint32_t sb, int wg, int lane, uint32_t rel_base, Pre pre, Mid mid, Last last, int lag_par = 0) {
  constexpr int SLOT = RING / NS;
  const uint32_t full = sb + MISC + (NS == 4 ? B_FULL4 : B_FULL6);
  const uint32_t rel = rel_base + (NS == 4 ? B_EMPTY4 : B_EMPTY6);
  const uint32_t s0 = (sb & 0x3FFFF) >> 4, a0 = s0 + wg * (HALF >> 4);
  int ps;
  auto issue = [&](int it, bool first) {
    const uint64_t da = DESC_A | (a0 + ((own && it < 2) ? (STG + it * BLK) >> 4 : r.s * (SLOT >> 4))), db = DESC_B | (s0 + r.s * (SLOT >> 4) + (BLK >> 4));
    mbar_wait(full + r.s * 8, r.ph);
    wg_arrive();
    if (first) WG<N>::first(acc, da, db); else WG<N>::mma(acc, da, db);
#pragma unroll
    for (int k = 1; k < 4; k++) WG<N>::mma(acc, da + k * 2, db + k * 128);
    wg_commit();
  };
  auto retire = [&](int it) {
    wg_wait<1>();
    if (lane < 2) mbar_arrive_cl(rel + ps * 8);
    ps = r.s;
    ring_next<NS>(r);
  };
  issue(0, true);
  ps = r.s;
  ring_next<NS>(r);
  static_for<1, PRE + 1>([&](auto ic) { issue(ic.v, false); pre(ic); retire(ic.v); });
#pragma unroll 1
  for (int it = PRE + 1; it < nkb; it++) {
    if (LAG && it == nkb - LAG && wg == 1) mbar_wait(sb + MISC + B_LAG, lag_par);
    issue(it, false); mid(it); retire(it);
  }
  if (LAG && wg == 0 && lane == 0) mbar_arrive(sb + MISC + B_LAG);
  last();
  wg_wait<0>();
#pragma unroll
  for (int i = 0; i < N / 2; i++) asm volatile("" : "+f"(acc[i]) :: "memory");
  if (lane < 2) mbar_arrive_cl(rel + ps * 8);
}

__device__ __forceinline__ uint32_t tag_of(uint32_t ep) { return (ep & 127u) + 1u; }
__device__ __forceinline__ void ln_publish(const float (&v)[64], uint2* st, int j, int row0, int lane, uint32_t ep) {
  float s0 = 0, s1 = 0, s2 = 0, s3 = 0, q0 = 0, q1 = 0, q2 = 0, q3 = 0;
#pragma unroll
  for (int i = 0; i < 16; i++) {
    s0 += v[4 * i]; s1 += v[4 * i + 1]; s2 += v[4 * i + 2]; s3 += v[4 * i + 3];
    q0 = fmaf(v[4 * i], v[4 * i], q0); q1 = fmaf(v[4 * i + 1], v[4 * i + 1], q1); q2 = fmaf(v[4 * i + 2], v[4 * i + 2], q2); q3 = fmaf(v[4 * i + 3], v[4 * i + 3], q3);
  }
  s0 += s1; s2 += s3; q0 += q1; q2 += q3;
  const bool odd = lane & 1;
  float s = (odd ? s2 : s0) + __shfl_xor_sync(~0u, odd ? s0 : s2, 1), q = (odd ? q2 : q0) + __shfl_xor_sync(~0u, odd ? q0 : q2, 1);
  s += __shfl_xor_sync(~0u, s, 2); q += __shfl_xor_sync(~0u, q, 2);
  if ((lane & 3) < 2) st_rlx2(st + j * 128 + row0 + (lane & 1) * 8, __float_as_uint(s), (__float_as_uint(fmaf(s * (-1.f / 128), s, q)) & ~255u) | tag_of(ep));
}
__device__ __forceinline__ void ln_gather(const uint2* st, int row0, int lane, uint32_t ep, float& n0, float& r0, float& n1, float& r1, bool rnd) {
  const uint2* p = st + (lane & 2) * 256 + row0 + (lane & 1) * 8;
  const uint32_t tag = tag_of(ep);
  uint2 a, b, c, d; uint32_t n = 0;
  while (true) {
    a = ld_rlx2(p); b = ld_rlx2(p + 128); c = ld_rlx2(p + 256); d = ld_rlx2(p + 384);
    if ((((a.y ^ tag) | (b.y ^ tag) | (c.y ^ tag) | (d.y ^ tag)) & 255u) == 0) break;
    SPIN_GUARD(n);
  }
  __syncwarp();
  const uint32_t fix = tag ^ 128u;
  float s = (__uint_as_float(a.x) + __uint_as_float(b.x)) + (__uint_as_float(c.x) + __uint_as_float(d.x));
  float q = (__uint_as_float(a.y ^ fix) + __uint_as_float(b.y ^ fix)) + (__uint_as_float(c.y ^ fix) + __uint_as_float(d.y ^ fix));
  q = fmaf(fmaf(__uint_as_float(a.x), __uint_as_float(a.x), __uint_as_float(b.x) * __uint_as_float(b.x)) +
           fmaf(__uint_as_float(c.x), __uint_as_float(c.x), __uint_as_float(d.x) * __uint_as_float(d.x)), 1.f / 128, q);
  s += __shfl_xor_sync(~0u, s, 2); q += __shfl_xor_sync(~0u, q, 2);
  s *= 1.f / 1024;
  const float var = fmaxf(fmaf(-s, s, q * (1.f / 1024)), 0.f);
  float r;
  if (rnd) {
    float sd; asm("sqrt.approx.f32 %0, %1;" : "=f"(sd) : "f"(bf_round(bf_round(var) + 1e-5f)));
    r = rcp(bf_round(sd)); s = bf_round(s);
  } else r = rsqrtf(var + 1e-5f);
  const float nn = -s * r;
  const float ro = __shfl_xor_sync(~0u, r, 1), no = __shfl_xor_sync(~0u, nn, 1);
  const bool odd = lane & 1;
  r0 = odd ? ro : r; n0 = odd ? no : nn; r1 = odd ? r : ro; n1 = odd ? nn : no;
}
__device__ __forceinline__ void load_vec(uint32_t* w, uint32_t sb, int sec, int b, int lane) {
#pragma unroll
  for (int q = 0; q < 2; q++) { uint4 t = lds128(sb + MISC + MODV + sec * 256 + (lane & 3) * 64 + b * 32 + q * 16); w[4 * q] = t.x; w[4 * q + 1] = t.y; w[4 * q + 2] = t.z; w[4 * q + 3] = t.w; }
}
__device__ __forceinline__ void stage_done(uint32_t sb, int wg, int b, int lane) {
  fence_async_smem();
  __syncwarp();
  if (lane == 0) mbar_arrive(sb + MISC + B_RDY + b * 8);
}
__device__ __forceinline__ uint32_t hfma2(uint32_t a, uint32_t b, uint32_t c) { uint32_t r; asm("fma.rn.bf16x2 %0, %1, %2, %3;" : "=r"(r) : "r"(a), "r"(b), "r"(c)); return r; }
__device__ __forceinline__ void ln_apply(const float (&v)[64], const uint2* st, int row0, uint32_t ep, uint32_t sb, int sec_shift, int sec_scale, uint32_t stg_row, int wg, int lane) {
  uint32_t sc[16], sh[16];
#pragma unroll
  for (int b = 0; b < 2; b++) { load_vec(sc + 8 * b, sb, sec_scale, b, lane); load_vec(sh + 8 * b, sb, sec_shift, b, lane); }
  float n0, r0, n1, r1;
  ln_gather(st, row0, lane, ep, n0, r0, n1, r1, sec_shift == 0);
#pragma unroll
  for (int i = 0; i < 16; i += 2) {
    if (i == 8) { const float z = lds32f(sb + MISC + ZERO); n0 += z; n1 += z; }
    uint32_t w[4];
#pragma unroll
    for (int u = 0; u < 2; u++) {
      int q = i + u;
      w[2 * u] = hfma2(pack2(fmaf(v[4 * q], r0, n0), fmaf(v[4 * q + 1], r0, n0)), sc[q], sh[q]);
      w[2 * u + 1] = hfma2(pack2(fmaf(v[4 * q + 2], r1, n1), fmaf(v[4 * q + 3], r1, n1)), sc[q], sh[q]);
    }
    stsm4(stg_row + (i >> 3) * BLK + ((((i & 7) + (lane >> 4)) ^ (lane & 7)) << 4), w[0], w[1], w[2], w[3]);
    if ((i & 7) == 6) { stage_done(sb, wg, i >> 3, lane); }
  }
}
__device__ __forceinline__ uint32_t hmul2(uint32_t a, uint32_t b) { uint32_t r; asm("mul.rn.bf16x2 %0, %1, %2;" : "=r"(r) : "r"(a), "r"(b)); return r; }
__device__ __forceinline__ uint32_t silu_mul2(uint32_t g, uint32_t u) {
  const uint32_t h = hmul2(g, 0x3f003f00u);
  const float h0 = bf_lo(h), h1 = bf_hi(h);
  return hmul2(pack2(fmaf(h0, tanh_fast(h0), h0), fmaf(h1, tanh_fast(h1), h1)), u);
}

__device__ __forceinline__ void gemv_fma(float (&a)[8], uint4 w, float s) {
  a[0] = fmaf(bf_lo(w.x), s, a[0]); a[1] = fmaf(bf_hi(w.x), s, a[1]); a[2] = fmaf(bf_lo(w.y), s, a[2]); a[3] = fmaf(bf_hi(w.y), s, a[3]);
  a[4] = fmaf(bf_lo(w.z), s, a[4]); a[5] = fmaf(bf_hi(w.z), s, a[5]); a[6] = fmaf(bf_lo(w.w), s, a[6]); a[7] = fmaf(bf_hi(w.w), s, a[7]);
}
__device__ __forceinline__ float silu_c(float v) { return bf_round(__fdividef(v, 1.f + __expf(-v))); }
__device__ __forceinline__ float mod_gather(const uint32_t* p, uint32_t ep) {
  const uint32_t tag = tag_of(ep), fix = tag ^ 128u;
  uint32_t a, b, c, d, n = 0;
  while (true) {
    a = ld_rlx1(p); b = ld_rlx1(p + 2048); c = ld_rlx1(p + 4096); d = ld_rlx1(p + 6144);
    if ((((a ^ tag) | (b ^ tag) | (c ^ tag) | (d ^ tag)) & 255u) == 0) break;
    SPIN_GUARD(n);
  }
  return (__uint_as_float(a ^ fix) + __uint_as_float(b ^ fix)) + (__uint_as_float(c ^ fix) + __uint_as_float(d ^ fix));
}
__device__ __forceinline__ void mod_store(uint32_t sb, int sec, int col, float v) {
  v = bf_round(v);
  if (sec == 1) v += 1.f;
  sts16(sb + MISC + MODV + sec * 256 + (((col >> 1) & 3) * 16 + (col >> 3)) * 4 + (col & 1) * 2, __float2bfloat16_rn(v));
}

__global__ void __cluster_dims__(2, 1, 1) __launch_bounds__(384, 1)
fused_kernel(const bf16* __restrict__ cvec, const bf16* __restrict__ wmod, Scratch* gs, int by_sm, const __grid_constant__ Maps maps) {
  extern __shared__ __align__(1024) uint8_t smem_raw[];
  uint32_t sm; asm volatile("mov.u32 %0, %%smid;" : "=r"(sm));
  const uint32_t id = by_sm ? sm : blockIdx.x, xs = by_sm ? 112 + 8 * by_sm : 0, u = id < xs ? id : id - 4;
  const bool extra = id - xs < 4;
  uint4 wv[8];
  uint32_t ep0; uint16_t cv_;
  if (threadIdx.x < 256) {
    const int r0 = ((u >> 5) & 3) * 256 + (threadIdx.x & 224);
    asm volatile("ld.global.nc.u16 %0, [%1];" : "=h"(cv_) : "l"(cvec + r0 + (threadIdx.x & 31)));
    asm volatile("ld.global.u32 %0, [%1];" : "=r"(ep0) : "l"(gs->epoch + (blockIdx.x | (threadIdx.x & by_sm & 4))));
    if (!extra) {
      const bf16* wp = wmod + (r0 + ((threadIdx.x >> 3) & 3)) * 6144 + (u & 31) * 64 + (threadIdx.x & 7) * 8;
#pragma unroll
      for (int i = 0; i < 8; i++) wv[i] = ldg_nc(wp + i * 4 * 6144);
    }
  }
  const uint32_t sb = smem_u32(smem_raw);
  const int warp = __shfl_sync(~0u, threadIdx.x >> 5, 0), lane = threadIdx.x & 31;
  const int rank = blockIdx.x & 1;
  const int t = sm >> 1, v = t < 32 || by_sm == 2 ? t : t < 60 ? t + 1 + (((t - 32) * 37) >> 8) : (t - 58) * 8;
  const int gr = 0x71546320u >> ((v & 7) * 4);
  const int cid = !by_sm ? (blockIdx.x >> 1) - 2 : extra ? (t & 1) - 2 : (gr & 4) * 8 + (v >> 3) * 4 + (gr & 3);
  const int bid = cid * 2 + rank;
  const int m = cid >> 2, j = (cid & 3) * 2 + rank;
  const uint32_t bar = sb + MISC;

  if (warp >= 8) {
    asm volatile("setmaxnreg.dec.sync.aligned.u32 40;");
    if (extra) {
      if (warp == 8) {
        if (lane == 0) { for (int s = 0; s < 6; s++) { mbar_init(bar + B_FULL6 + s * 8, 1); mbar_init(bar + B_EMPTY6 + s * 8, 8); } fence_async_smem(); }
        __syncwarp();
        asm volatile("bar.arrive 2, 288;" ::: "memory");
        __nanosleep(XSLEEP);
#pragma unroll 1
        for (int it = 0, s = 0, par = 1; it < 64; it++) {
          mbar_wait(bar + B_EMPTY6 + s * 8, par);
          expect_e(bar + B_FULL6 + s * 8, 32768); tma_3d_e(sb + s * 32768, &maps.wmod, bar + B_FULL6 + s * 8, 0, (it & 15) * 64, 12 + (it >> 4) * 4 + bid);
          if (++s == 6) { s = 0; par ^= 1; }
        }
      }
    } else if (warp < 10) {
      uint32_t f6 = bar + B_FULL6, d6 = sb + (warp == 8 ? BLK : rank * HALF), p6 = 1;
      auto next6 = [&]() { f6 += 8; d6 += 32768; if (f6 == bar + B_FULL6 + 48) { f6 -= 48; d6 -= RING; p6 ^= 1; } };
      auto drained4 = [&](int q, int late) { if (q < 5) mbar_wait(bar + B_EMPTY4 + (((late ? 0x10332 : 0x32110) >> (4 * q)) & 3) * 8, 1); };
      auto drained6 = [&](int q) { if (q < 3) mbar_wait(bar + B_EMPTY6 + ((0x154 >> (4 * q)) & 7) * 8, q >> 1); };
      auto skip6 = [&]() { mbar_wait(f6 + 48, p6); expect_e(f6, 0); next6(); };
      if (warp == 8) {
        if (lane == 0) {
          if (sb & 1023) bail();
          for (int b = 0; b < 2; b++) mbar_init(bar + B_X + b * 8, 1);
          for (int s = 0; s < 4; s++) { mbar_init(bar + B_FULL4 + s * 8, 2); mbar_init(bar + B_EMPTY4 + s * 8, 16); }
          for (int s = 0; s < 6; s++) { mbar_init(bar + B_FULL6 + s * 8, 2); mbar_init(bar + B_EMPTY6 + s * 8, 16); }
          for (int b = 0; b < 2; b++) { mbar_init(bar + B_RDY + b * 8, 8); mbar_init(bar + B_FREE + b * 8, 1); mbar_init(bar + B_HH + b * 8, 1); mbar_init(bar + B_OUT + b * 8, 2); mbar_init(bar + B_HALO + b * 8, 1); }
          mbar_init(bar + B_MOD, 1); mbar_init(bar + B_LAG, 4); mbar_init(bar + B_ALL, 1); mbar_init(bar + B_HH2, 1);
          asm volatile("st.shared.u32 [%0], 0;" :: "r"(bar + ZERO) : "memory");
          asm volatile("fence.mbarrier_init.release.cluster;" ::: "memory");
          fence_async_smem();
        }
        __syncwarp();
        cl_arrive_relaxed();
        for (int b = 0; b < 2; b++) { expect_e(bar + B_X + b * 8, BLK); tma_3d_e(sb + STG + b * BLK, &maps.x, bar + B_X + b * 8, j * 128 + b * 64, m * 64, 0); }
        mbar_wait(bar + B_X + 8, 0);
#pragma unroll 1
        for (int ph = 0; ph < 2; ph++) {
          const CUtensorMap* const m0 = ph ? &maps.w1 : &maps.wqkv;
#pragma unroll 1
          for (int it = 0; it < (ph ? 48 : 16); it++) {
            const int s = (it + 2 * ph) & 3;
            int a0 = (ph ? it & 48 : 16) + 2 * j, a1 = ph ? a0 : a0 + 16, k0 = (it < 16 ? own_order(it, j) : it & 15) * 64;
            uint32_t full = bar + B_FULL4 + s * 8, d = sb + s * 49152 + BLK;
            if (ph) drained6(it);
            mbar_wait(full + 32, ~(it >> 2) & 1);
            tma_3d_e(d, m0, full, 0, k0, a0);
            if (it < 4) { const uint32_t t0 = clock(); while ((uint32_t)clock() - t0 < GAP) {} }
            tma_3d_e(d + BLK, m0 + ph, full, 0, k0, a1);
            expect_e(full, 2 * BLK);
            if (it < 4) { const uint32_t t0 = clock(); while ((uint32_t)clock() - t0 < GAP) {} }
            if (it >= 44) {
              if (it == 44) { mbar_wait(bar + B_FREE, 0); mbar_wait(bar + B_FREE + 8, 0); expect_e(bar + B_X, 2 * BLK); }
              bulk_ld_e(sb + STG + (it - 44) * HALF, gs->x1 + bid * 2048 + (it - 44) * 512, HALF, bar + B_X);
            }
          }
          const CUtensorMap* const m1 = ph ? &maps.w1s : &maps.wqkv;
          const int a = ph ? 48 + j : 2 * j;
#pragma unroll 1
          for (int k0 = 0; k0 < 1024; k0 += 64) {
            drained4(k0 >> 6, ph);
            mbar_wait(f6 + 48, p6);
            tma_3d_e(d6, m1, f6, 0, k0, a);
            if (ph) tma_3d_e(d6 + HALF, &maps.w3s, f6, 0, k0, a);
            expect_e(f6, BLK);
            next6();
          }
          if (ph) break;
#pragma unroll 1
          for (int it = 0; it < 16; it++) {
            const int k0 = own_order(it, j) * 64;
            mbar_wait(f6 + 48, p6);
            tma_3d_e(d6, &maps.wo, f6, 0, k0, 2 * j);
            expect_e(f6, BLK);
            next6();
          }
          skip6();
        }
#pragma unroll 1
        for (int k0 = 0; k0 < F_; k0 += 64) {
          mbar_wait(f6 + 48, p6);
          tma_3d_e(d6, &maps.w2, f6, 0, k0, 2 * j);
          expect_e(f6, BLK);
          next6();
        }
      } else {
        if (lane < 9) prefetch_map(&maps.x + lane);
        const uint32_t ep = gs->epoch[blockIdx.x] + 1;
        cl_arrive_relaxed(); cl_wait();
        auto run6 = [&](const uint4* src, int n, int sw) {
          src += rank * 512;
#pragma unroll 1
          for (int it = 0; it < n; it++) {
            if (sw >= 0) drained4(it, sw);
            mbar_wait(f6 + 48, p6);
            bulk_ld_mc_e(d6, src, HALF, f6);
            expect_e(f6, BLK);
            next6();
            src += 1024;
          }
        };
        uint32_t ready = 0;
        auto need = [&](int e, uint32_t mask) {
          if (!(ready & mask)) {
            uint32_t n = 0;
            do { ready = __ballot_sync(~0u, ld_acquire(gs->flag + (m * 128 + e * 16 + (lane & 14)) * FS) == ep); SPIN_GUARD(n); } while (!(ready & mask));
            fence_async_global();
          }
        };
        auto fresh = [&](int e, int it, uint32_t full, uint32_t empty, int par, uint32_t slot, uint4* src) {
          mbar_wait(empty, par);
          expect_e(full, it < 2 ? 0 : BLK);
          if (it >= 4) {
            const int kb = own_order(it, j);
            if (it < 10) need(e, 1u << kb); else if (it == 10) mbar_wait(bar + B_ALL, e & 1);
            bulk_ld_mc_e(slot + rank * HALF, src + kb * 1024 + rank * 512, HALF, full);
          } else if (it >= 2) {
            const int b = it > 2;
            const uint32_t to_peer = mapa(sb, rank ^ 1) - sb;
            const bool push = b && e != 1;
            mbar_wait(bar + (push ? B_RDY : B_FREE) + b * 8, e & 1);
            if (push) bulk_push_e(slot + to_peer, sb + STG + BLK, BLK, full + to_peer);
            else { fence_async_global(); bulk_ld_e(slot + to_peer, src + (2 * j + b) * 1024, BLK, full + to_peer); }
          } else ready = 0;
        };
        uint4* const h = gs->h + m * 16384;
#pragma unroll 1
        for (int e = 0; e < 3; e++) {
#pragma unroll 1
          for (int it = 0; it < 16; it++) {
            const int s = (it + e) & 3;
            const uint32_t full = e == 1 ? f6 : bar + B_FULL4 + s * 8;
            if (e == 2) drained6(it);
            fresh(e, it, full, full + (e == 1 ? 48 : 32), e == 1 ? p6 : ~(it >> 2) & 1, e == 1 ? d6 - rank * HALF : sb + s * 49152, e == 1 ? gs->o + m * 16384 : h);
            if (e == 1) next6();
          }
          if (e == 1) { skip6(); continue; }
#pragma unroll 1
          for (int it = 16; it < 16 + 16 * e; it++) {
            const int s = (it + 2) & 3;
            const uint32_t full = bar + B_FULL4 + s * 8;
            mbar_wait(full + 32, ~(it >> 2) & 1);
            bulk_ld_mc_e(sb + s * 49152 + rank * HALF, h + (it & 15) * 1024 + rank * 512, HALF, full);
            expect_e(full, BLK);
          }
          run6(h, 16, e);
        }
#pragma unroll 1
        for (int q = 0; q < 3; q++) {
          mbar_wait(bar + (q == 2 ? B_HH2 : B_HH + q * 8), 0);
          run6(gs->hh + m * 57344 + (64 - (64 >> q)) * 1024, 32 >> q, -1);
        }
      }
    } else {
      const int b = warp - 10;
      const uint32_t ep = gs->epoch[blockIdx.x] + 1;
      const uint32_t stg = sb + STG + b * BLK;
      cl_arrive_relaxed(); cl_wait();
      auto all_there = [&](int u, uint32_t done) {
        const uint32_t* fl = gs->flag + u * FS;
        uint32_t n = 0;
        while (!__all_sync(~0u, ld_acquire(fl) == ep)) { __nanosleep(100); SPIN_GUARD(n); }
        fence_async_global();
        arrive_e(done);
      };
#pragma unroll 1
      for (int e = 0; e < 7 - b; e++) {
        const int kb = (e < 3 ? 2 * j : e < 6 ? 2 * (8 * (e - 3) + j) : 48 + j) + b;
        uint4* const dst = (e == 1 ? gs->o + m * 16384 : e < 3 ? gs->h + m * 16384 : gs->hh + m * 57344) + kb * 1024;
        uint32_t* const fl = gs->flag + (m * 128 + (e < 3 ? e * 16 : U_HH) + kb) * FS;
        if (e < 3 && lane < 8) st_rlx1(fl + lane, 0);
        if (b && e < 3) {
          mbar_wait(bar + B_FREE, e & 1);
          const uint32_t t0 = clock();
          while ((uint32_t)clock() - t0 < (e == 1 ? B1D : B1P)) {}
        }
        mbar_wait(bar + B_RDY + b * 8, e & 1);
        bulk_st_e(dst, stg, e < 3 ? BLK : BLK / NPIECE);
        if (e >= 3) {
#pragma unroll 1
          for (int q = 1; q < NPIECE; q++) { __nanosleep(PSLEEP); bulk_st_e(dst + q * (1024 / NPIECE), stg + q * (BLK / NPIECE), BLK / NPIECE); }
        }
        publish_e(bar + B_FREE + b * 8, fl, ep);
        if (b && (e < 3 || e == 4)) all_there(m * 128 + (e < 3 ? e * 16 + (lane & 15) : U_HH + lane), bar + (e < 3 ? B_ALL : B_HH));
        if (!b && (e == 1 || e == 2)) {
#pragma unroll 1
          for (int sec = e == 1 ? 2 : 5; sec < 4 + e; sec++) {
            const uint4* p = (const uint4*)(gs->modv + (sec - 2) * 1024 + j * 128) + lane;
            uint4 v0, v1; uint32_t n = 0;
            while (true) {
              v0 = ld_rlx4(p); v1 = ld_rlx4(p + 32);
              if (__all_sync(~0u, v0.y == ep && v0.w == ep && v1.y == ep && v1.w == ep)) break;
              SPIN_GUARD(n);
            }
            const uint32_t d = sb + MISC + MODV + sec * 256 + ((lane & 3) * 16 + (lane >> 2)) * 4;
            asm volatile("st.shared.u32 [%0], %1;" :: "r"(d), "r"(__byte_perm(v0.x, v0.z, 0x7632)) : "memory");
            asm volatile("st.shared.u32 [%0], %1;" :: "r"(d + 32), "r"(__byte_perm(v1.x, v1.z, 0x7632)) : "memory");
          }
          __syncwarp();
          if (e == 1) { arrive_e(bar + B_MOD); }
        }
        if (e == 0) {
          uint32_t* const hf = gs->flag + (m * 128 + 48 + 2 * j + b) * FS;
          uint4* const hp = gs->halo + ((m * 8 + j) * 2 + b) * 256;
          if (m < 15 && lane < 8) st_rlx1(hf + 128 * FS + lane, 0);
          mbar_wait(bar + B_OUT + b * 8, 0);
          if (m < 15) {
            for (int w = 0; w < 2; w++) bulk_st_e(hp + 4096 + w * 128, stg + w * HALF, 2048);
            publish_e(bar + B_OUT + b * 8, hf + 128 * FS, ep);
          }
          if (m > 0) {
            uint32_t n = 0;
            while (!__all_sync(~0u, ld_acquire(hf) == ep)) SPIN_GUARD(n);
            fence_async_global();
            for (int w = 0; w < 2; w++) bulk_ld_e(stg + w * HALF, hp + w * 128, 2048, bar + B_HALO + b * 8);
            expect_e(bar + B_HALO + b * 8, 4096);
          } else {
            __syncwarp();
#pragma unroll
            for (int i = 0; i < 8; i++) sts128(stg + (i >> 2) * HALF + (i & 3) * 512 + lane * 16, 0, 0, 0, 0);
            __syncwarp();
            arrive_e(bar + B_HALO + b * 8);
          }
        }
      }
      if (b) {
#pragma unroll 1
        for (int q = 0; q < 2; q++) all_there(m * 128 + U_HH + 32 + q * 16 + (lane & (15 >> q)), bar + (q ? B_HH2 : B_HH + 8));
      }
    }
  } else {
    const int wg = warp >> 2, wq = warp & 3, tid = threadIdx.x;
    const int g = lane >> 2, c = lane & 3;
    if (!extra) cl_arrive_relaxed();
    asm volatile("setmaxnreg.inc.sync.aligned.u32 232;" ::: "memory");
    if (__builtin_expect(extra, 0)) {
      const uint32_t ep = ep0 + 1;
      float sv[4];
#pragma unroll
      for (int p = 0; p < 4; p++) sv[p] = silu_c(__bfloat162float(cvec[64 * (4 * p + (lane >> 3)) + 8 * warp + (lane & 7)]));
      named_bar(2, 288);
      int s = 0, par = 0;
#pragma unroll 1
      for (int sec = 0; sec < 4; sec++) {
        float a[8] = {0, 0, 0, 0, 0, 0, 0, 0};
#pragma unroll 1
        for (int it = 0; it < 16; it++) {
          const float sc = it < 4 ? sv[0] : it < 8 ? sv[1] : it < 12 ? sv[2] : sv[3];
          mbar_wait(bar + B_FULL6 + s * 8, par);
          uint4 w[8];
#pragma unroll
          for (int i = 0; i < 8; i++) w[i] = lds128(sb + s * 32768 + (warp * 8 + i) * 512 + lane * 16);
#pragma unroll
          for (int i = 0; i < 8; i++) gemv_fma(a, w[i], __shfl_sync(~0u, sc, (it & 3) * 8 + i));
          if (lane == 0) mbar_arrive(bar + B_EMPTY6 + s * 8);
          if (++s == 6) { s = 0; par ^= 1; }
        }
        const uint32_t red = sb + STG + sec * 8192;
        sts128(red + warp * 1024 + lane * 32, __float_as_uint(a[0]), __float_as_uint(a[1]), __float_as_uint(a[2]), __float_as_uint(a[3]));
        sts128(red + warp * 1024 + lane * 32 + 16, __float_as_uint(a[4]), __float_as_uint(a[5]), __float_as_uint(a[6]), __float_as_uint(a[7]));
        named_bar(1, 256);
        float t = 0;
#pragma unroll
        for (int q = 0; q < 8; q++) t += lds32f(red + q * 1024 + tid * 4);
        t = bf_round(t);
        if (sec == 2) t = bf_round(t + 1.f);
        st_rlx2(gs->modv + sec * 1024 + (bid + 4) * 256 + tid, __float_as_uint(t), ep);
      }
      if (tid == 0) gs->epoch[blockIdx.x] = ep;
      return;
    }
    const int row0 = wg * 64 + wq * 16 + g;
    if (c < 2) st_rlx2(gs->stat + m * 1024 + j * 128 + row0 + c * 8, 0, 0);
    cl_wait();
    uint32_t ep;
    asm volatile("add.u32 %0, %1, 1;" : "=r"(ep) : "r"(ep0) : "memory");
    const float sc_ = silu_c(__uint_as_float((uint32_t)cv_ << 16));
    const uint32_t rel = mapa(bar, (lane & 1) ^ rank);
    const uint32_t stg_row = sb + STG + (wg * 64 + wq * 16 + (lane & 15)) * 128;
    const uint32_t fre = bar + B_FREE;
    Ring r4{0, 0, 0}, r6{0, 0, 0};
    auto none = [](auto) {};
    uint32_t xk[32];
    {
      float a[8] = {0, 0, 0, 0, 0, 0, 0, 0};
#pragma unroll
      for (int i = 0; i < 8; i++) gemv_fma(a, wv[i], __shfl_sync(~0u, sc_, i * 4 + (lane >> 3)));
#pragma unroll
      for (int i = 0; i < 8; i++) { a[i] += __shfl_xor_sync(~0u, a[i], 8); a[i] += __shfl_xor_sync(~0u, a[i], 16); }
      if (lane < 8) {
        sts128(sb + RED_OFF + warp * 256 + lane * 32, __float_as_uint(a[0]), __float_as_uint(a[1]), __float_as_uint(a[2]), __float_as_uint(a[3]));
        sts128(sb + RED_OFF + warp * 256 + lane * 32 + 16, __float_as_uint(a[4]), __float_as_uint(a[5]), __float_as_uint(a[6]), __float_as_uint(a[7]));
      }
      named_bar(1, 256);
      if (tid < 64) {
        float s = 0;
#pragma unroll
        for (int w = 0; w < 8; w++) s += lds32f(sb + RED_OFF + w * 256 + tid * 4);
        st_rlx1(gs->modp + u * 64 + tid, (__float_as_uint(s) & ~255u) | tag_of(ep));
      }
      float v[64];
      mbar_wait(bar + B_X, 0); mbar_wait(bar + B_X + 8, 0);
#pragma unroll
      for (int i = 0; i < 16; i += 2) {
        uint32_t w0, w1, w2, w3;
        ldsm4(stg_row + (i >> 3) * BLK + ((((i & 7) + (lane >> 4)) ^ (lane & 7)) << 4), w0, w1, w2, w3);
        xk[2 * i] = w0; xk[2 * i + 1] = w1; xk[2 * i + 2] = w2; xk[2 * i + 3] = w3;
        v[4 * i] = bf_lo(w0); v[4 * i + 1] = bf_hi(w0); v[4 * i + 2] = bf_lo(w1); v[4 * i + 3] = bf_hi(w1);
        v[4 * i + 4] = bf_lo(w2); v[4 * i + 5] = bf_hi(w2); v[4 * i + 6] = bf_lo(w3); v[4 * i + 7] = bf_hi(w3);
      }
      ln_publish(v, gs->stat + m * 1024, j, row0, lane, ep);
      mod_store(sb, tid >> 7, tid & 127, mod_gather(gs->modp + (tid >> 7) * 1024 + j * 128 + (tid & 127), ep));
      named_bar(1, 256);
      ln_apply(v, gs->stat + m * 1024, row0, ep, sb, 0, 1, stg_row, wg, lane);
      named_bar(1, 256);
    }
    {
      uint32_t kf[32], vf[32], pv[32];
      const bool first = wq == 0 && m == 0;
      const uint32_t xa = sb + STG + wg * HALF + wq * 2048 + lane * 16;
      {
        float acc[128];
        mainloop<256, 4, 0, 0>(acc, 16, true, r4, sb, wg, lane, rel, none, none, [&] {
          mbar_wait(fre + 8, 0);
          if (c < 2) st_rlx2(gs->stat + (16 + m) * 1024 + j * 128 + row0 + c * 8, 0, 0);
        });
#pragma unroll
        for (int i = 0; i < 32; i++) { kf[i] = pack2(acc[2 * i], acc[2 * i + 1]); vf[i] = pack2(acc[64 + 2 * i], acc[65 + 2 * i]); }
      }
      float acc[64];
      constexpr int QP = 2;
      auto inbox = [&](const int b) {
        if (wq == 0) mbar_wait(bar + B_HALO + b * 8, 0);
#pragma unroll
        for (int i = 4 * b; i < 4 * b + 4; i++) {
          uint4 q = lds128(xa + b * BLK + (i & 3) * 512);
          pv[4 * i] = q.x; pv[4 * i + 1] = q.y; pv[4 * i + 2] = q.z; pv[4 * i + 3] = q.w;
        }
        __syncwarp();
      };
      auto sent = [&](int b) { if (wq == 3) { fence_async_smem(); __syncwarp(); if (lane == 0) mbar_arrive(bar + B_OUT + b * 8); } };
      mainloop<128, 6, 8 / QP, 0>(acc, 16, false, r6, sb, wg, lane, rel, [&](auto ic) {
        constexpr int q = (ic.v - 1) * QP;
        if (q == 4) sent(0);
#pragma unroll
        for (int i = 4 * q; i < 4 * (q + QP); i++) vf[i] = movm(vf[i]);
#pragma unroll
        for (int i = q; i < q + QP; i++) sts128(xa + (wq == 3 ? -6144 : 2048) + (i >> 2) * BLK + (i & 3) * 512, kf[4 * i + 1], kf[4 * i + 3], vf[4 * i + 1], vf[4 * i + 3]);
      }, [&](int it) { if (it == 8 / QP + 1) sent(1); }, [&] {
        named_bar(2 + wg, 128);
        inbox(0);
      });
      int gz = g;
#pragma unroll
      for (int b = 0; b < 2; b++) {
        const bool up0 = 2 * c > gz, up1 = 2 * c + 1 > gz;
        const uint32_t mup = (up0 ? 0xffffu : 0u) | (up1 ? 0xffff0000u : 0u);
        float l[2][4], mx[4];
#pragma unroll
        for (int h = 0; h < 2; h++) {
          uint32_t q[8];
          const int k = 16 * b + 8 * h;
#pragma unroll
          for (int i = 0; i < 8; i++) q[i] = pack2(acc[2 * k + 2 * i], acc[2 * k + 2 * i + 1]);
          float s0[4], s1[4], s2[4];
          mma16z(s0, q[0], q[1], q[2], q[3], pv[k], pv[k + 1]); mma16z(s1, q[0], q[1], q[2], q[3], kf[k], kf[k + 2]); mma16z(s2, q[0], q[1], q[2], q[3], kf[k + 1], kf[k + 3]);
          mma16(s0, q[4], q[5], q[6], q[7], pv[k + 4], pv[k + 5]); mma16(s1, q[4], q[5], q[6], q[7], kf[k + 4], kf[k + 6]); mma16(s2, q[4], q[5], q[6], q[7], kf[k + 5], kf[k + 7]);
          if (first) { s0[0] = -INFINITY; s0[1] = -INFINITY; }
          l[h][0] = up0 ? s0[0] : s1[0]; l[h][1] = up1 ? s0[1] : s1[1]; l[h][2] = up0 ? s1[2] : s2[2]; l[h][3] = up1 ? s1[3] : s2[3];
          mx[2 * h] = fmaxf(l[h][0], l[h][1]); mx[2 * h + 1] = fmaxf(l[h][2], l[h][3]);
        }
#pragma unroll
        for (int o = 1; o < 4; o <<= 1) {
#pragma unroll
          for (int h = 0; h < 4; h++) mx[h] = fmaxf(mx[h], __shfl_xor_sync(~0u, mx[h], o));
        }
#pragma unroll
        for (int h = 0; h < 2; h++) {
          const float n0 = -mx[2 * h] * SCL, n1 = -mx[2 * h + 1] * SCL;
          const uint32_t pa = pack2(ex2(fmaf(l[h][0], SCL, n0)), ex2(fmaf(l[h][1], SCL, n0))), pb = pack2(ex2(fmaf(l[h][2], SCL, n1)), ex2(fmaf(l[h][3], SCL, n1)));
          float sm[4];
          mma8z(sm, pa, pb, 0x3f803f80u);
          const float ia = rcp(sm[0]), ib = rcp(sm[2]);
#pragma unroll
          for (int i = 8 * b + 4 * h; i < 8 * b + 4 * h + 4; i += 2) {
            uint32_t of[4];
#pragma unroll
            for (int d = 0; d < 2; d++) {
              float o[4];
              mma16z(o, pa & ~mup, pb & mup, 0u, pb & ~mup, vf[2 * (i + d)], vf[2 * (i + d) + 1]);
              mma8(o, pa & mup, 0u, pv[2 * i + 2 + d]);
              of[2 * d] = pack2(o[0] * ia, o[1] * ia); of[2 * d + 1] = pack2(o[2] * ib, o[3] * ib);
            }
            stsm4(stg_row + b * BLK + ((((i & 7) + (lane >> 4)) ^ (lane & 7)) << 4), of[0], of[1], of[2], of[3]);
          }
        }
        stage_done(sb, wg, b, lane);
        if (b == 0) inbox(1);
        if (b == 0) gz += __float_as_uint(lds32f(bar + ZERO));
      }
      named_bar(1, 256);
    }
    uint32_t pk[64];
    {
      float acc[64];
      mainloop<128, 6, 0, 0>(acc, 16, true, r6, sb, wg, lane, rel, none, none, [&] {
        mbar_wait(bar + B_MOD, 0); mbar_wait(fre + 8, 1);
        load_vec(pk + 32, sb, 2, 0, lane); load_vec(pk + 40, sb, 2, 1, lane);
#pragma unroll
        for (int i = 0; i < 32; i++) { pk[i] = xk[i]; asm volatile("" : "+r"(pk[i])); }
      });
#pragma unroll
      for (int i = 0; i < 32; i++) {
        acc[2 * i] = fmaf(acc[2 * i], bf_lo(pk[32 + (i >> 1)]), bf_lo(pk[i]));
        acc[2 * i + 1] = fmaf(acc[2 * i + 1], bf_hi(pk[32 + (i >> 1)]), bf_hi(pk[i]));
      }
      ln_publish(acc, gs->stat + (16 + m) * 1024, j, row0, lane, ep);
      mbar_wait(bar + B_FULL6 + 16, 1);
      if (lane < 2) mbar_arrive_cl(rel + B_EMPTY6 + 16);
      ring_next<6>(r6);
#pragma unroll
      for (int i = 0; i < 32; i++) { pk[i] = pack2(acc[2 * i], acc[2 * i + 1]); pk[32 + i] = 0; }
      ln_apply(acc, gs->stat + (16 + m) * 1024, row0, ep, sb, 3, 4, stg_row, wg, lane);
      named_bar(1, 256);
    }
    auto swiglu = [&](int q, int uo, int par) {
      if ((q & 3) == 0 && par >= 0) mbar_wait(fre + 2 * q, par);
      uint32_t w[4];
#pragma unroll
      for (int u = 0; u < 4; u++) w[u] = silu_mul2(pk[4 * q + u], pk[uo + 4 * q + u]);
      stsm4(stg_row + (q >> 2) * BLK + ((((2 * q & 7) + (lane >> 4)) ^ (lane & 7)) << 4), w[0], w[1], w[2], w[3]);
    };
    r4.s = r4.wrap = 2;
#pragma unroll 1
    for (int t = 0; t < 3; t++) {
      float acc[128];
      mainloop<256, 4, 4, 1>(acc, 16, t == 0, r4, sb, wg, lane, rel, [&](auto ic) {
        if (t) {
          if (ic.v == 3) stage_done(sb, wg, 0, lane);
          swiglu(2 * ic.v - 2, 32, ~t & 1); swiglu(2 * ic.v - 1, 32, 0);
        }
      }, [&](int it) {
        if (t && it == 5) stage_done(sb, wg, 1, lane);
        if (t == 0 && it >= 8) {
          uint4* p = gs->x1 + bid * 2048 + ((it >> 2) & 1) * 1024 + warp * 128 + (it & 3) * 32 + lane;
#pragma unroll
          for (int i = 0; i < 8; i++)
            asm volatile("{\n.reg .pred p;\nsetp.eq.u32 p, %5, %6;\n@p st.global.v4.u32 [%0], {%1,%2,%3,%4};\n}" :: "l"(p), "r"(pk[4 * i]), "r"(pk[4 * i + 1]), "r"(pk[4 * i + 2]), "r"(pk[4 * i + 3]), "r"(it), "r"(8 + i) : "memory");
        }
      }, [&] { if (t == 0) fence_async_global(); else if (t == 2) mbar_wait(bar + B_X, 1); }, t & 1);
#pragma unroll
      for (int i = 0; i < 64; i++) pk[i] = pack2(acc[2 * i], acc[2 * i + 1]);
    }
    uint32_t x1[32];
    {
      float acc[64];
      mainloop<128, 6, 10, 1>(acc, 16, false, r6, sb, wg, lane, rel, [&](auto ic) {
        constexpr int b = ic.v > 5, q = ic.v - 5 * b;
        if (q == 1) {
          if (b) stage_done(sb, wg, 0, lane);
#pragma unroll
          for (int i = 4 * b; i < 4 * b + 4; i++) { const uint4 x = lds128(sb + STG + b * BLK + warp * 2048 + (i & 3) * 512 + lane * 16); x1[4 * i] = x.x; x1[4 * i + 1] = x.y; x1[4 * i + 2] = x.z; x1[4 * i + 3] = x.w; }
          __syncwarp();
        } else swiglu(4 * b + q - 2, 32, -1);
      }, [&](int it) { if (it == 11) stage_done(sb, wg, 1, lane); }, [] {}, 1);
#pragma unroll
      for (int i = 0; i < 32; i++) pk[i] = pack2(acc[2 * i], acc[2 * i + 1]);
    }
    {
      float acc[64];
      mainloop<128, 6, 4, TAILLAG>(acc, 56, false, r6, sb, wg, lane, rel, [&](auto ic) { swiglu(ic.v - 1, 16, 1); },
                                   [&](int it) { if (it == 5) stage_done(sb, wg, 0, lane); }, [&] {
        load_vec(pk + 32, sb, 5, 0, lane); load_vec(pk + 40, sb, 5, 1, lane);
        mbar_wait(fre, 0); mbar_wait(fre + 8, 1);
      }, 0);
      __syncwarp();
      cl_arrive_relaxed();
#pragma unroll
      for (int i = 0; i < 16; i += 2) {
        uint32_t w[4];
#pragma unroll
        for (int u = 0; u < 4; u++) {
          const int q = 2 * i + u;
          w[u] = hfma2(pack2(acc[2 * q], acc[2 * q + 1]), pk[32 + (q >> 1)], x1[q]);
        }
        stsm4(stg_row + (i >> 3) * BLK + ((((i & 7) + (lane >> 4)) ^ (lane & 7)) << 4), w[0], w[1], w[2], w[3]);
        if ((i & 7) == 6) {
          fence_async_smem();
          named_bar(2 + wg, 128);
          if (wq == 0 && elect()) { tma_store_3d(&maps.out, sb + STG + (i >> 3) * BLK + wg * HALF, j * 128 + (i >> 3) * 64, m * 64, wg); bulk_commit(); }
          if (i < 8) x1[16] |= __float_as_uint(lds32f(bar + ZERO));
        }
      }
      if (wq == 0) bulk_wait_read();
      if (tid == 0) gs->epoch[blockIdx.x] = ep;
      cl_wait();
    }
  }
}

typedef CUresult (*EncodeFn)(CUtensorMap*, CUtensorMapDataType, cuuint32_t, void*, const cuuint64_t*, const cuuint64_t*, const cuuint32_t*, const cuuint32_t*,
                             CUtensorMapInterleave, CUtensorMapSwizzle, CUtensorMapL2promotion, CUtensorMapFloatOOBfill);

void make_map(EncodeFn fn, CUtensorMap* mp, const void* base, uint64_t d0, uint64_t d1, uint64_t d2, uint64_t s1, uint64_t s2, uint32_t b2, uint32_t b0 = 64) {
  cuuint64_t d[3] = {d0, d1, d2}, s[2] = {s1, s2};
  cuuint32_t b[3] = {b0, 64, b2}, e[3] = {1, 1, 1};
  fn(mp, CU_TENSOR_MAP_DATA_TYPE_BFLOAT16, 3, (void*)base, d, s, b, e, CU_TENSOR_MAP_INTERLEAVE_NONE, b0 == 64 ? CU_TENSOR_MAP_SWIZZLE_128B : CU_TENSOR_MAP_SWIZZLE_NONE,
     CU_TENSOR_MAP_L2_PROMOTION_L2_128B, CU_TENSOR_MAP_FLOAT_OOB_FILL_NONE);
}

__global__ void probe_kernel() {}
int max_clusters(int size) {
  cudaLaunchConfig_t cfg = {};
  cudaLaunchAttribute at;
  at.id = cudaLaunchAttributeClusterDimension; at.val.clusterDim.x = size; at.val.clusterDim.y = 1; at.val.clusterDim.z = 1;
  cfg.gridDim = dim3(size * 66); cfg.blockDim = dim3(384); cfg.dynamicSmemBytes = SMEM_BYTES; cfg.attrs = &at; cfg.numAttrs = 1;
  int n = 0;
  if (cudaOccupancyMaxActiveClusters(&n, probe_kernel, &cfg) != cudaSuccess) { cudaGetLastError(); return 0; }
  return n;
}

}

extern "C" void kernel_launch(void* const* d_in, const int* in_sizes, int n_in, void* d_out, int out_size) {
  static EncodeFn fn = nullptr;
  static int by_sm = 0;
  static Scratch* gs = nullptr;
  if (!fn) {
    void* p = nullptr; cudaDriverEntryPointQueryResult q;
    cudaGetDriverEntryPoint("cuTensorMapEncodeTiled", &p, cudaEnableDefault, &q);
    fn = (EncodeFn)p;
    cudaFuncSetAttribute(fused_kernel, cudaFuncAttributeMaxDynamicSharedMemorySize, SMEM_BYTES);
    int dev = 0, sms = 0;
    cudaGetSymbolAddress((void**)&gs, g_scratch);
    cudaGetDevice(&dev);
    cudaDeviceGetAttribute(&sms, cudaDevAttrMultiProcessorCount, dev);
    cudaFuncSetAttribute(probe_kernel, cudaFuncAttributeMaxDynamicSharedMemorySize, SMEM_BYTES);
    if (sms == 132 && max_clusters(2) == 66) {
      const int c4 = max_clusters(4), c6 = max_clusters(6), c8 = max_clusters(8);
      by_sm = c4 == 30 && c6 == 17 && c8 == 15 ? 1 : c8 == 16 ? 2 : 0;
    }
  }
  Maps mp;
  make_map(fn, &mp.x, d_in[0], D_, S_ / 2, 2, 4096, 2048, 2);
  make_map(fn, &mp.out, d_out, D_, S_ / 2, 2, 4096, 2048, 1);
  make_map(fn, &mp.wqkv, d_in[1], 64, D_, 3 * D_ / 64, 3 * D_ * 2, 128, 2);
  make_map(fn, &mp.wo, d_in[2], 64, D_, D_ / 64, D_ * 2, 128, 2);
  make_map(fn, &mp.w1, d_in[4], 64, D_, F_ / 64, F_ * 2, 128, 2);
  make_map(fn, &mp.w3, d_in[5], 64, D_, F_ / 64, F_ * 2, 128, 2);
  make_map(fn, &mp.w1s, d_in[4], 64, D_, F_ / 64, F_ * 2, 128, 1);
  make_map(fn, &mp.w3s, d_in[5], 64, D_, F_ / 64, F_ * 2, 128, 1);
  make_map(fn, &mp.w2, d_in[6], 64, F_, D_ / 64, D_ * 2, 128, 2);
  make_map(fn, &mp.wmod, d_in[8], 256, D_, 24, 6 * D_ * 2, 512, 1, 256);
  fused_kernel<<<132, 384, SMEM_BYTES>>>((const bf16*)d_in[7], (const bf16*)d_in[8], gs, by_sm, mp);
}
```

```cpp
#include <cuda_runtime.h>
#include <cuda_bf16.h>
#include <cuda.h>
#include <stdint.h>

typedef __nv_bfloat16 bf16;

namespace {

constexpr int S_ = 2048, D_ = 1024, F_ = 3584;
constexpr int BLK = 16384;
constexpr int HALF = 8192;
constexpr int RING = 196608;
constexpr int STG = RING;
constexpr int MISC = RING + 2 * BLK;
constexpr int SMEM_BYTES = MISC + 3072;
constexpr int B_FULL4 = 0, B_EMPTY4 = 32, B_FULL6 = 64, B_EMPTY6 = 112, B_RDY = 160, B_FREE = 176, B_LAG = 192, B_X = 208, B_MOD = 224, B_OUT = 240, B_HH = 256, B_ALL = 272, B_HH2 = 288, ZERO = 296, B_HALO = 304;
constexpr int MODV = 512;
constexpr int RED_OFF = 0;
constexpr float SCL = 0.17677669529663687f * 1.4426950408889634f;
constexpr int U_HH = 64;
constexpr int FS = 8;
constexpr int NPIECE = 4, PSLEEP = 300;
constexpr int XSLEEP = 4000;
constexpr uint32_t GAP = 250;
constexpr uint32_t B1P = 3700, B1D = 700;
constexpr int TAILLAG = 5;

struct Maps { CUtensorMap x, out, wqkv, wo, w1, w3, w1s, w3s, w2, wmod; };

struct Scratch {
  uint32_t epoch[256];
  uint32_t flag[16 * 128 * FS];
  uint32_t modp[8 * 2 * 4 * 128];
  uint2 modv[4 * 1024];
  uint2 stat[2 * 16 * 8 * 128];
  uint4 halo[16 * 8 * 2 * 256];
  uint4 x1[128 * 8 * 256];
  uint4 h[16 * 16 * 1024];
  uint4 o[16 * 16 * 1024];
  uint4 hh[16 * 56 * 1024];
};
__device__ __align__(1024) Scratch g_scratch;

__device__ __forceinline__ void bail() { asm volatile("st.global.u32 [%0], %1;" :: "l"(0ull), "r"(0) : "memory"); }
__device__ __forceinline__ uint32_t smem_u32(const void* p) { return (uint32_t)__cvta_generic_to_shared(p); }
__device__ __forceinline__ void mbar_init(uint32_t bar, uint32_t cnt) { asm volatile("mbarrier.init.shared::cta.b64 [%0], %1;" :: "r"(bar), "r"(cnt) : "memory"); }
__device__ __forceinline__ void mbar_arrive(uint32_t bar) { asm volatile("mbarrier.arrive.shared::cta.b64 _, [%0];" :: "r"(bar) : "memory"); }
__device__ __forceinline__ void mbar_arrive_cl(uint32_t cl_addr) { asm volatile("mbarrier.arrive.shared::cluster.b64 _, [%0];" :: "r"(cl_addr) : "memory"); }
__device__ __forceinline__ uint32_t mapa(uint32_t addr, uint32_t cta) { uint32_t r; asm("mapa.shared::cluster.u32 %0, %1, %2;" : "=r"(r) : "r"(addr), "r"(cta)); return r; }
__device__ __forceinline__ void mbar_wait(uint32_t bar, uint32_t parity) {
  asm volatile("{\n.reg .pred p;\n.reg .b32 n;\n.reg .b64 z;\nmov.b32 n, 0;\nmov.b64 z, 0;\n"
               "W: add.u32 n, n, 1;\nsetp.gt.u32 p, n, 0x400000;\n@p st.global.u32 [z], n;\n"
               "mbarrier.try_wait.parity.shared::cta.b64 p, [%0], %1;\n@!p bra W;\n}" :: "r"(bar), "r"(parity) : "memory");
}
__device__ __forceinline__ void tma_store_3d(const CUtensorMap* m, uint32_t src, int c0, int c1, int c2) {
  asm volatile("cp.async.bulk.tensor.3d.global.shared::cta.bulk_group [%0, {%2, %3, %4}], [%1];" :: "l"(m), "r"(src), "r"(c0), "r"(c1), "r"(c2) : "memory");
}
#define ELECT "{\n.reg .pred p;\nelect.sync _|p, 0xffffffff;\n@p "
__device__ __forceinline__ void expect_e(uint32_t bar, uint32_t bytes) { asm volatile(ELECT "mbarrier.arrive.expect_tx.shared::cta.b64 _, [%0], %1;\n}" :: "r"(bar), "r"(bytes) : "memory"); }
__device__ __forceinline__ void tma_3d_e(uint32_t dst, const CUtensorMap* m, uint32_t bar, int c0, int c1, int c2) {
  asm volatile(ELECT "cp.async.bulk.tensor.3d.shared::cluster.global.mbarrier::complete_tx::bytes [%0], [%1, {%3, %4, %5}], [%2];\n}" :: "r"(dst), "l"(m), "r"(bar), "r"(c0), "r"(c1), "r"(c2) : "memory");
}
__device__ __forceinline__ void bulk_ld_e(uint32_t dst, const void* src, uint32_t bytes, uint32_t bar) {
  asm volatile(ELECT "cp.async.bulk.shared::cluster.global.mbarrier::complete_tx::bytes [%0], [%1], %2, [%3];\n}" :: "r"(dst), "l"(src), "r"(bytes), "r"(bar) : "memory");
}
__device__ __forceinline__ void bulk_ld_mc_e(uint32_t dst, const void* src, uint32_t bytes, uint32_t bar) {
  asm volatile(ELECT "cp.async.bulk.shared::cluster.global.mbarrier::complete_tx::bytes.multicast::cluster [%0], [%1], %2, [%3], %4;\n}" :: "r"(dst), "l"(src), "r"(bytes), "r"(bar), "h"((uint16_t)3) : "memory");
}
__device__ __forceinline__ void bulk_push_e(uint32_t dst_cl, uint32_t src, uint32_t bytes, uint32_t bar_cl) {
  asm volatile(ELECT "cp.async.bulk.shared::cluster.shared::cta.mbarrier::complete_tx::bytes [%0], [%1], %2, [%3];\n}" :: "r"(dst_cl), "r"(src), "r"(bytes), "r"(bar_cl) : "memory");
}
__device__ __forceinline__ void arrive_e(uint32_t bar) { asm volatile(ELECT "mbarrier.arrive.shared::cta.b64 _, [%0];\n}" :: "r"(bar) : "memory"); }
__device__ __forceinline__ void bulk_st_e(void* dst, uint32_t src, uint32_t bytes) {
  asm volatile(ELECT "cp.async.bulk.global.shared::cta.bulk_group [%0], [%1], %2;\n}" :: "l"(dst), "r"(src), "r"(bytes) : "memory");
}
__device__ __forceinline__ void publish_e(uint32_t free_bar, uint32_t* flag, uint32_t ep) {
  asm volatile(ELECT "cp.async.bulk.commit_group;\n@p cp.async.bulk.wait_group 0;\n@p mbarrier.arrive.shared::cta.b64 _, [%0];\n@p st.release.gpu.global.u32 [%1], %2;\n}"
               :: "r"(free_bar), "l"(flag), "r"(ep) : "memory");
}
__device__ __forceinline__ void bulk_commit() { asm volatile("cp.async.bulk.commit_group;" ::: "memory"); }
__device__ __forceinline__ void bulk_wait_read() { asm volatile("cp.async.bulk.wait_group.read 0;" ::: "memory"); }
__device__ __forceinline__ void fence_async_global() { asm volatile("fence.proxy.async.global;" ::: "memory"); }
__device__ __forceinline__ void fence_async_smem() { asm volatile("fence.proxy.async.shared::cta;" ::: "memory"); }
__device__ __forceinline__ void wg_arrive() { asm volatile("wgmma.fence.sync.aligned;" ::: "memory"); }
__device__ __forceinline__ void wg_commit() { asm volatile("wgmma.commit_group.sync.aligned;" ::: "memory"); }
template <int N> __device__ __forceinline__ void wg_wait() { asm volatile("wgmma.wait_group.sync.aligned %0;" :: "n"(N) : "memory"); }
__device__ __forceinline__ void cl_arrive_relaxed() { asm volatile("barrier.cluster.arrive.relaxed.aligned;" ::: "memory"); }
__device__ __forceinline__ void cl_wait() { asm volatile("barrier.cluster.wait.acquire.aligned;" ::: "memory"); }
__device__ __forceinline__ bool elect() { uint32_t p; asm volatile("{\n.reg .pred p;\nelect.sync _|p, 0xffffffff;\nselp.u32 %0, 1, 0, p;\n}" : "=r"(p)); return p; }
__device__ __forceinline__ void named_bar(int id, int n) { asm volatile("bar.sync %0, %1;" :: "r"(id), "r"(n) : "memory"); }
__device__ __forceinline__ uint32_t pack2(float lo, float hi) { uint32_t r; asm("cvt.rn.bf16x2.f32 %0, %1, %2;" : "=r"(r) : "f"(hi), "f"(lo)); return r; }
__device__ __forceinline__ float bf_lo(uint32_t w) { return __uint_as_float(w << 16); }
__device__ __forceinline__ float bf_hi(uint32_t w) { return __uint_as_float(w & 0xffff0000u); }
__device__ __forceinline__ float bf_round(float v) { return __bfloat162float(__float2bfloat16_rn(v)); }
__device__ __forceinline__ void stsm4(uint32_t addr, uint32_t a, uint32_t b, uint32_t c, uint32_t d) {
  asm volatile("stmatrix.sync.aligned.m8n8.x4.shared.b16 [%0], {%1, %2, %3, %4};" :: "r"(addr), "r"(a), "r"(b), "r"(c), "r"(d) : "memory");
}
__device__ __forceinline__ void ldsm4(uint32_t addr, uint32_t& a, uint32_t& b, uint32_t& c, uint32_t& d) {
  asm volatile("ldmatrix.sync.aligned.m8n8.x4.shared.b16 {%0, %1, %2, %3}, [%4];" : "=r"(a), "=r"(b), "=r"(c), "=r"(d) : "r"(addr) : "memory");
}
__device__ __forceinline__ uint32_t movm(uint32_t a) { uint32_t r; asm volatile("movmatrix.sync.aligned.m8n8.trans.b16 %0, %1;" : "=r"(r) : "r"(a)); return r; }
__device__ __forceinline__ void mma16(float (&d)[4], uint32_t a0, uint32_t a1, uint32_t a2, uint32_t a3, uint32_t b0, uint32_t b1) {
  asm("mma.sync.aligned.m16n8k16.row.col.f32.bf16.bf16.f32 {%0,%1,%2,%3}, {%4,%5,%6,%7}, {%8,%9}, {%0,%1,%2,%3};"
               : "+f"(d[0]), "+f"(d[1]), "+f"(d[2]), "+f"(d[3]) : "r"(a0), "r"(a1), "r"(a2), "r"(a3), "r"(b0), "r"(b1));
}
__device__ __forceinline__ void mma16z(float (&d)[4], uint32_t a0, uint32_t a1, uint32_t a2, uint32_t a3, uint32_t b0, uint32_t b1) {
  asm("mma.sync.aligned.m16n8k16.row.col.f32.bf16.bf16.f32 {%0,%1,%2,%3}, {%4,%5,%6,%7}, {%8,%9}, {%10,%10,%10,%10};"
      : "=f"(d[0]), "=f"(d[1]), "=f"(d[2]), "=f"(d[3]) : "r"(a0), "r"(a1), "r"(a2), "r"(a3), "r"(b0), "r"(b1), "f"(0.f));
}
__device__ __forceinline__ void mma8z(float (&d)[4], uint32_t a0, uint32_t a1, uint32_t b0) {
  asm("mma.sync.aligned.m16n8k8.row.col.f32.bf16.bf16.f32 {%0,%1,%2,%3}, {%4,%5}, {%6}, {%7,%7,%7,%7};"
      : "=f"(d[0]), "=f"(d[1]), "=f"(d[2]), "=f"(d[3]) : "r"(a0), "r"(a1), "r"(b0), "f"(0.f));
}
__device__ __forceinline__ void mma8(float (&d)[4], uint32_t a0, uint32_t a1, uint32_t b0) {
  asm("mma.sync.aligned.m16n8k8.row.col.f32.bf16.bf16.f32 {%0,%1,%2,%3}, {%4,%5}, {%6}, {%0,%1,%2,%3};"
               : "+f"(d[0]), "+f"(d[1]), "+f"(d[2]), "+f"(d[3]) : "r"(a0), "r"(a1), "r"(b0));
}
__device__ __forceinline__ uint4 lds128(uint32_t a) { uint4 v; asm volatile("ld.shared.v4.u32 {%0,%1,%2,%3}, [%4];" : "=r"(v.x), "=r"(v.y), "=r"(v.z), "=r"(v.w) : "r"(a) : "memory"); return v; }
__device__ __forceinline__ void sts128(uint32_t a, uint32_t x, uint32_t y, uint32_t z, uint32_t w) { asm volatile("st.shared.v4.u32 [%0], {%1,%2,%3,%4};" :: "r"(a), "r"(x), "r"(y), "r"(z), "r"(w) : "memory"); }
__device__ __forceinline__ float lds32f(uint32_t a) { float v; asm volatile("ld.shared.f32 %0, [%1];" : "=f"(v) : "r"(a) : "memory"); return v; }
__device__ __forceinline__ void sts16(uint32_t a, bf16 v) { asm volatile("st.shared.b16 [%0], %1;" :: "r"(a), "h"(__bfloat16_as_ushort(v)) : "memory"); }
__device__ __forceinline__ uint4 ldg_nc(const void* p) { uint4 v; asm volatile("ld.global.nc.L1::no_allocate.v4.u32 {%0,%1,%2,%3}, [%4];" : "=r"(v.x), "=r"(v.y), "=r"(v.z), "=r"(v.w) : "l"(p)); return v; }
__device__ __forceinline__ uint4 ld_rlx4(const uint4* p) {
  unsigned long long a, b; asm volatile("ld.relaxed.gpu.global.v2.b64 {%0,%1}, [%2];" : "=l"(a), "=l"(b) : "l"(p) : "memory");
  return make_uint4((uint32_t)a, (uint32_t)(a >> 32), (uint32_t)b, (uint32_t)(b >> 32));
}
__device__ __forceinline__ uint2 ld_rlx2(const uint2* p) { unsigned long long a; asm volatile("ld.relaxed.gpu.global.b64 %0, [%1];" : "=l"(a) : "l"(p) : "memory"); return make_uint2((uint32_t)a, (uint32_t)(a >> 32)); }
__device__ __forceinline__ void st_rlx2(uint2* p, uint32_t x, uint32_t y) { asm volatile("st.relaxed.gpu.global.b64 [%0], %1;" :: "l"(p), "l"((unsigned long long)x | ((unsigned long long)y << 32)) : "memory"); }
__device__ __forceinline__ void st_rlx1(uint32_t* p, uint32_t v) { asm volatile("st.relaxed.gpu.global.u32 [%0], %1;" :: "l"(p), "r"(v) : "memory"); }
__device__ __forceinline__ uint32_t ld_rlx1(const uint32_t* p) { uint32_t v; asm volatile("ld.relaxed.gpu.global.u32 %0, [%1];" : "=r"(v) : "l"(p) : "memory"); return v; }
__device__ __forceinline__ uint32_t ld_acquire(const uint32_t* p) { uint32_t v; asm volatile("ld.acquire.gpu.global.u32 %0, [%1];" : "=r"(v) : "l"(p) : "memory"); return v; }
__device__ __forceinline__ void prefetch_map(const CUtensorMap* m) { asm volatile("prefetch.tensormap [%0];" :: "l"(m) : "memory"); }
__device__ __forceinline__ float rcp(float x) { float r; asm("rcp.approx.ftz.f32 %0, %1;" : "=f"(r) : "f"(x)); return r; }
__device__ __forceinline__ float ex2(float x) { float r; asm("ex2.approx.ftz.f32 %0, %1;" : "=f"(r) : "f"(x)); return r; }
__device__ __forceinline__ float tanh_fast(float x) { float r; asm("tanh.approx.f32 %0, %1;" : "=f"(r) : "f"(x)); return r; }
#define SPIN_GUARD(n) if (++(n) > (1u << 24)) bail()

__device__ __forceinline__ void wgmma_n128(float (&d)[64], uint64_t da, uint64_t db) {
  asm volatile("wgmma.mma_async.sync.aligned.m64n128k16.f32.bf16.bf16 "
    "{%0, %1, %2, %3, %4, %5, %6, %7, %8, %9, %10, %11, %12, %13, %14, %15, %16, %17, %18, %19, %20, %21, %22, %23, %24, %25, %26, %27, %28, %29, %30, %31, %32, %33, %34, %35, %36, %37, %38, %39, %40, %41, %42, %43, %44, %45, %46, %47, %48, %49, %50, %51, %52, %53, %54, %55, %56, %57, %58, %59, %60, %61, %62, %63}, "
    "%64, %65, 1, 1, 1, 0, 1;\n"
    : "+f"(d[0]), "+f"(d[1]), "+f"(d[2]), "+f"(d[3]), "+f"(d[4]), "+f"(d[5]), "+f"(d[6]), "+f"(d[7]), "+f"(d[8]), "+f"(d[9]), "+f"(d[10]), "+f"(d[11]), "+f"(d[12]), "+f"(d[13]), "+f"(d[14]), "+f"(d[15]), "+f"(d[16]), "+f"(d[17]), "+f"(d[18]), "+f"(d[19]), "+f"(d[20]), "+f"(d[21]), "+f"(d[22]), "+f"(d[23]), "+f"(d[24]), "+f"(d[25]), "+f"(d[26]), "+f"(d[27]), "+f"(d[28]), "+f"(d[29]), "+f"(d[30]), "+f"(d[31]), "+f"(d[32]), "+f"(d[33]), "+f"(d[34]), "+f"(d[35]), "+f"(d[36]), "+f"(d[37]), "+f"(d[38]), "+f"(d[39]), "+f"(d[40]), "+f"(d[41]), "+f"(d[42]), "+f"(d[43]), "+f"(d[44]), "+f"(d[45]), "+f"(d[46]), "+f"(d[47]), "+f"(d[48]), "+f"(d[49]), "+f"(d[50]), "+f"(d[51]), "+f"(d[52]), "+f"(d[53]), "+f"(d[54]), "+f"(d[55]), "+f"(d[56]), "+f"(d[57]), "+f"(d[58]), "+f"(d[59]), "+f"(d[60]), "+f"(d[61]), "+f"(d[62]), "+f"(d[63])
    : "l"(da), "l"(db));
}
__device__ __forceinline__ void wgmma_n128_first(float (&d)[64], uint64_t da, uint64_t db) {
  asm volatile("wgmma.mma_async.sync.aligned.m64n128k16.f32.bf16.bf16 "
    "{%0, %1, %2, %3, %4, %5, %6, %7, %8, %9, %10, %11, %12, %13, %14, %15, %16, %17, %18, %19, %20, %21, %22, %23, %24, %25, %26, %27, %28, %29, %30, %31, %32, %33, %34, %35, %36, %37, %38, %39, %40, %41, %42, %43, %44, %45, %46, %47, %48, %49, %50, %51, %52, %53, %54, %55, %56, %57, %58, %59, %60, %61, %62, %63}, "
    "%64, %65, 0, 1, 1, 0, 1;\n"
    : "=f"(d[0]), "=f"(d[1]), "=f"(d[2]), "=f"(d[3]), "=f"(d[4]), "=f"(d[5]), "=f"(d[6]), "=f"(d[7]), "=f"(d[8]), "=f"(d[9]), "=f"(d[10]), "=f"(d[11]), "=f"(d[12]), "=f"(d[13]), "=f"(d[14]), "=f"(d[15]), "=f"(d[16]), "=f"(d[17]), "=f"(d[18]), "=f"(d[19]), "=f"(d[20]), "=f"(d[21]), "=f"(d[22]), "=f"(d[23]), "=f"(d[24]), "=f"(d[25]), "=f"(d[26]), "=f"(d[27]), "=f"(d[28]), "=f"(d[29]), "=f"(d[30]), "=f"(d[31]), "=f"(d[32]), "=f"(d[33]), "=f"(d[34]), "=f"(d[35]), "=f"(d[36]), "=f"(d[37]), "=f"(d[38]), "=f"(d[39]), "=f"(d[40]), "=f"(d[41]), "=f"(d[42]), "=f"(d[43]), "=f"(d[44]), "=f"(d[45]), "=f"(d[46]), "=f"(d[47]), "=f"(d[48]), "=f"(d[49]), "=f"(d[50]), "=f"(d[51]), "=f"(d[52]), "=f"(d[53]), "=f"(d[54]), "=f"(d[55]), "=f"(d[56]), "=f"(d[57]), "=f"(d[58]), "=f"(d[59]), "=f"(d[60]), "=f"(d[61]), "=f"(d[62]), "=f"(d[63])
    : "l"(da), "l"(db));
}
__device__ __forceinline__ void wgmma_n256(float (&d)[128], uint64_t da, uint64_t db) {
  asm volatile("wgmma.mma_async.sync.aligned.m64n256k16.f32.bf16.bf16 "
    "{%0, %1, %2, %3, %4, %5, %6, %7, %8, %9, %10, %11, %12, %13, %14, %15, %16, %17, %18, %19, %20, %21, %22, %23, %24, %25, %26, %27, %28, %29, %30, %31, %32, %33, %34, %35, %36, %37, %38, %39, %40, %41, %42, %43, %44, %45, %46, %47, %48, %49, %50, %51, %52, %53, %54, %55, %56, %57, %58, %59, %60, %61, %62, %63, %64, %65, %66, %67, %68, %69, %70, %71, %72, %73, %74, %75, %76, %77, %78, %79, %80, %81, %82, %83, %84, %85, %86, %87, %88, %89, %90, %91, %92, %93, %94, %95, %96, %97, %98, %99, %100, %101, %102, %103, %104, %105, %106, %107, %108, %109, %110, %111, %112, %113, %114, %115, %116, %117, %118, %119, %120, %121, %122, %123, %124, %125, %126, %127}, "
    "%128, %129, 1, 1, 1, 0, 1;\n"
    : "+f"(d[0]), "+f"(d[1]), "+f"(d[2]), "+f"(d[3]), "+f"(d[4]), "+f"(d[5]), "+f"(d[6]), "+f"(d[7]), "+f"(d[8]), "+f"(d[9]), "+f"(d[10]), "+f"(d[11]), "+f"(d[12]), "+f"(d[13]), "+f"(d[14]), "+f"(d[15]), "+f"(d[16]), "+f"(d[17]), "+f"(d[18]), "+f"(d[19]), "+f"(d[20]), "+f"(d[21]), "+f"(d[22]), "+f"(d[23]), "+f"(d[24]), "+f"(d[25]), "+f"(d[26]), "+f"(d[27]), "+f"(d[28]), "+f"(d[29]), "+f"(d[30]), "+f"(d[31]), "+f"(d[32]), "+f"(d[33]), "+f"(d[34]), "+f"(d[35]), "+f"(d[36]), "+f"(d[37]), "+f"(d[38]), "+f"(d[39]), "+f"(d[40]), "+f"(d[41]), "+f"(d[42]), "+f"(d[43]), "+f"(d[44]), "+f"(d[45]), "+f"(d[46]), "+f"(d[47]), "+f"(d[48]), "+f"(d[49]), "+f"(d[50]), "+f"(d[51]), "+f"(d[52]), "+f"(d[53]), "+f"(d[54]), "+f"(d[55]), "+f"(d[56]), "+f"(d[57]), "+f"(d[58]), "+f"(d[59]), "+f"(d[60]), "+f"(d[61]), "+f"(d[62]), "+f"(d[63]), "+f"(d[64]), "+f"(d[65]), "+f"(d[66]), "+f"(d[67]), "+f"(d[68]), "+f"(d[69]), "+f"(d[70]), "+f"(d[71]), "+f"(d[72]), "+f"(d[73]), "+f"(d[74]), "+f"(d[75]), "+f"(d[76]), "+f"(d[77]), "+f"(d[78]), "+f"(d[79]), "+f"(d[80]), "+f"(d[81]), "+f"(d[82]), "+f"(d[83]), "+f"(d[84]), "+f"(d[85]), "+f"(d[86]), "+f"(d[87]), "+f"(d[88]), "+f"(d[89]), "+f"(d[90]), "+f"(d[91]), "+f"(d[92]), "+f"(d[93]), "+f"(d[94]), "+f"(d[95]), "+f"(d[96]), "+f"(d[97]), "+f"(d[98]), "+f"(d[99]), "+f"(d[100]), "+f"(d[101]), "+f"(d[102]), "+f"(d[103]), "+f"(d[104]), "+f"(d[105]), "+f"(d[106]), "+f"(d[107]), "+f"(d[108]), "+f"(d[109]), "+f"(d[110]), "+f"(d[111]), "+f"(d[112]), "+f"(d[113]), "+f"(d[114]), "+f"(d[115]), "+f"(d[116]), "+f"(d[117]), "+f"(d[118]), "+f"(d[119]), "+f"(d[120]), "+f"(d[121]), "+f"(d[122]), "+f"(d[123]), "+f"(d[124]), "+f"(d[125]), "+f"(d[126]), "+f"(d[127])
    : "l"(da), "l"(db));
}
__device__ __forceinline__ void wgmma_n256_first(float (&d)[128], uint64_t da, uint64_t db) {
  asm volatile("wgmma.mma_async.sync.aligned.m64n256k16.f32.bf16.bf16 "
    "{%0, %1, %2, %3, %4, %5, %6, %7, %8, %9, %10, %11, %12, %13, %14, %15, %16, %17, %18, %19, %20, %21, %22, %23, %24, %25, %26, %27, %28, %29, %30, %31, %32, %33, %34, %35, %36, %37, %38, %39, %40, %41, %42, %43, %44, %45, %46, %47, %48, %49, %50, %51, %52, %53, %54, %55, %56, %57, %58, %59, %60, %61, %62, %63, %64, %65, %66, %67, %68, %69, %70, %71, %72, %73, %74, %75, %76, %77, %78, %79, %80, %81, %82, %83, %84, %85, %86, %87, %88, %89, %90, %91, %92, %93, %94, %95, %96, %97, %98, %99, %100, %101, %102, %103, %104, %105, %106, %107, %108, %109, %110, %111, %112, %113, %114, %115, %116, %117, %118, %119, %120, %121, %122, %123, %124, %125, %126, %127}, "
    "%128, %129, 0, 1, 1, 0, 1;\n"
    : "=f"(d[0]), "=f"(d[1]), "=f"(d[2]), "=f"(d[3]), "=f"(d[4]), "=f"(d[5]), "=f"(d[6]), "=f"(d[7]), "=f"(d[8]), "=f"(d[9]), "=f"(d[10]), "=f"(d[11]), "=f"(d[12]), "=f"(d[13]), "=f"(d[14]), "=f"(d[15]), "=f"(d[16]), "=f"(d[17]), "=f"(d[18]), "=f"(d[19]), "=f"(d[20]), "=f"(d[21]), "=f"(d[22]), "=f"(d[23]), "=f"(d[24]), "=f"(d[25]), "=f"(d[26]), "=f"(d[27]), "=f"(d[28]), "=f"(d[29]), "=f"(d[30]), "=f"(d[31]), "=f"(d[32]), "=f"(d[33]), "=f"(d[34]), "=f"(d[35]), "=f"(d[36]), "=f"(d[37]), "=f"(d[38]), "=f"(d[39]), "=f"(d[40]), "=f"(d[41]), "=f"(d[42]), "=f"(d[43]), "=f"(d[44]), "=f"(d[45]), "=f"(d[46]), "=f"(d[47]), "=f"(d[48]), "=f"(d[49]), "=f"(d[50]), "=f"(d[51]), "=f"(d[52]), "=f"(d[53]), "=f"(d[54]), "=f"(d[55]), "=f"(d[56]), "=f"(d[57]), "=f"(d[58]), "=f"(d[59]), "=f"(d[60]), "=f"(d[61]), "=f"(d[62]), "=f"(d[63]), "=f"(d[64]), "=f"(d[65]), "=f"(d[66]), "=f"(d[67]), "=f"(d[68]), "=f"(d[69]), "=f"(d[70]), "=f"(d[71]), "=f"(d[72]), "=f"(d[73]), "=f"(d[74]), "=f"(d[75]), "=f"(d[76]), "=f"(d[77]), "=f"(d[78]), "=f"(d[79]), "=f"(d[80]), "=f"(d[81]), "=f"(d[82]), "=f"(d[83]), "=f"(d[84]), "=f"(d[85]), "=f"(d[86]), "=f"(d[87]), "=f"(d[88]), "=f"(d[89]), "=f"(d[90]), "=f"(d[91]), "=f"(d[92]), "=f"(d[93]), "=f"(d[94]), "=f"(d[95]), "=f"(d[96]), "=f"(d[97]), "=f"(d[98]), "=f"(d[99]), "=f"(d[100]), "=f"(d[101]), "=f"(d[102]), "=f"(d[103]), "=f"(d[104]), "=f"(d[105]), "=f"(d[106]), "=f"(d[107]), "=f"(d[108]), "=f"(d[109]), "=f"(d[110]), "=f"(d[111]), "=f"(d[112]), "=f"(d[113]), "=f"(d[114]), "=f"(d[115]), "=f"(d[116]), "=f"(d[117]), "=f"(d[118]), "=f"(d[119]), "=f"(d[120]), "=f"(d[121]), "=f"(d[122]), "=f"(d[123]), "=f"(d[124]), "=f"(d[125]), "=f"(d[126]), "=f"(d[127])
    : "l"(da), "l"(db));
}

template <int N> struct WG;
#define DEF_WG(N) template <> struct WG<N> { \
  static __device__ __forceinline__ void mma(float (&d)[N / 2], uint64_t a, uint64_t b) { wgmma_n##N(d, a, b); } \
  static __device__ __forceinline__ void first(float (&d)[N / 2], uint64_t a, uint64_t b) { wgmma_n##N##_first(d, a, b); } };
DEF_WG(128) DEF_WG(256)

constexpr uint64_t DESC_A = (1ull << 62) | ((uint64_t)(1024 >> 4) << 32) | (1ull << 16);
constexpr uint64_t DESC_B = (1ull << 62) | ((uint64_t)(1024 >> 4) << 32) | ((uint64_t)(8192 >> 4) << 16);

struct Ring { int s; uint32_t ph; int wrap; };
template <int NS> __device__ __forceinline__ void ring_next(Ring& r) { r.s = (r.s + 1 == NS) ? 0 : r.s + 1; if (r.s == r.wrap) r.ph ^= 1; }

__device__ __forceinline__ int own_order(int it, int j) {
  return it < 2 ? 2 * j + it : it < 4 ? 2 * (j ^ 1) + it - 2 : ((j >> 1) * 4 + 2 * it - (it < 10 ? 4 : 15)) & 15;
}

template <int V> struct IC { static constexpr int v = V; };
template <int I, int E, class F> __device__ __forceinline__ void static_for(F&& f) { if constexpr (I < E) { f(IC<I>{}); static_for<I + 1, E>(f); } }

template <int N, int NS, int PRE, int LAG, class Pre, class Mid, class Last>
__device__ __forceinline__ void mainloop(float (&acc)[N / 2], int nkb, bool own, Ring& r, uint32_t sb, int wg, int lane, uint32_t rel_base, Pre pre, Mid mid, Last last, int lag_par = 0) {
  constexpr int SLOT = RING / NS;
  const uint32_t full = sb + MISC + (NS == 4 ? B_FULL4 : B_FULL6);
  const uint32_t rel = rel_base + (NS == 4 ? B_EMPTY4 : B_EMPTY6);
  const uint32_t s0 = (sb & 0x3FFFF) >> 4, a0 = s0 + wg * (HALF >> 4);
  int ps;
  auto issue = [&](int it, bool first) {
    const uint64_t da = DESC_A | (a0 + ((own && it < 2) ? (STG + it * BLK) >> 4 : r.s * (SLOT >> 4))), db = DESC_B | (s0 + r.s * (SLOT >> 4) + (BLK >> 4));
    mbar_wait(full + r.s * 8, r.ph);
    wg_arrive();
    if (first) WG<N>::first(acc, da, db); else WG<N>::mma(acc, da, db);
#pragma unroll
    for (int k = 1; k < 4; k++) WG<N>::mma(acc, da + k * 2, db + k * 128);
    wg_commit();
  };
  auto retire = [&](int it) {
    wg_wait<1>();
    if (lane < 2) mbar_arrive_cl(rel + ps * 8);
    ps = r.s;
    ring_next<NS>(r);
  };
  issue(0, true);
  ps = r.s;
  ring_next<NS>(r);
  static_for<1, PRE + 1>([&](auto ic) { issue(ic.v, false); pre(ic); retire(ic.v); });
#pragma unroll 1
  for (int it = PRE + 1; it < nkb; it++) {
    if (LAG && it == nkb - LAG && wg == 1) mbar_wait(sb + MISC + B_LAG, lag_par);
    issue(it, false); mid(it); retire(it);
  }
  if (LAG && wg == 0 && lane == 0) mbar_arrive(sb + MISC + B_LAG);
  last();
  wg_wait<0>();
#pragma unroll
  for (int i = 0; i < N / 2; i++) asm volatile("" : "+f"(acc[i]) :: "memory");
  if (lane < 2) mbar_arrive_cl(rel + ps * 8);
}

__device__ __forceinline__ uint32_t tag_of(uint32_t ep) { return (ep & 127u) + 1u; }
__device__ __forceinline__ void ln_publish(const float (&v)[64], uint2* st, int j, int row0, int lane, uint32_t ep) {
  float s0 = 0, s1 = 0, s2 = 0, s3 = 0, q0 = 0, q1 = 0, q2 = 0, q3 = 0;
#pragma unroll
  for (int i = 0; i < 16; i++) {
    s0 += v[4 * i]; s1 += v[4 * i + 1]; s2 += v[4 * i + 2]; s3 += v[4 * i + 3];
    q0 = fmaf(v[4 * i], v[4 * i], q0); q1 = fmaf(v[4 * i + 1], v[4 * i + 1], q1); q2 = fmaf(v[4 * i + 2], v[4 * i + 2], q2); q3 = fmaf(v[4 * i + 3], v[4 * i + 3], q3);
  }
  s0 += s1; s2 += s3; q0 += q1; q2 += q3;
  const bool odd = lane & 1;
  float s = (odd ? s2 : s0) + __shfl_xor_sync(~0u, odd ? s0 : s2, 1), q = (odd ? q2 : q0) + __shfl_xor_sync(~0u, odd ? q0 : q2, 1);
  s += __shfl_xor_sync(~0u, s, 2); q += __shfl_xor_sync(~0u, q, 2);
  if ((lane & 3) < 2) st_rlx2(st + j * 128 + row0 + (lane & 1) * 8, __float_as_uint(s), (__float_as_uint(fmaf(s * (-1.f / 128), s, q)) & ~255u) | tag_of(ep));
}
__device__ __forceinline__ void ln_gather(const uint2* st, int row0, int lane, uint32_t ep, float& n0, float& r0, float& n1, float& r1, bool rnd) {
  const uint2* p = st + (lane & 2) * 256 + row0 + (lane & 1) * 8;
  const uint32_t tag = tag_of(ep);
  uint2 a, b, c, d; uint32_t n = 0;
  while (true) {
    a = ld_rlx2(p); b = ld_rlx2(p + 128); c = ld_rlx2(p + 256); d = ld_rlx2(p + 384);
    if ((((a.y ^ tag) | (b.y ^ tag) | (c.y ^ tag) | (d.y ^ tag)) & 255u) == 0) break;
    SPIN_GUARD(n);
  }
  __syncwarp();
  const uint32_t fix = tag ^ 128u;
  float s = (__uint_as_float(a.x) + __uint_as_float(b.x)) + (__uint_as_float(c.x) + __uint_as_float(d.x));
  float q = (__uint_as_float(a.y ^ fix) + __uint_as_float(b.y ^ fix)) + (__uint_as_float(c.y ^ fix) + __uint_as_float(d.y ^ fix));
  q = fmaf(fmaf(__uint_as_float(a.x), __uint_as_float(a.x), __uint_as_float(b.x) * __uint_as_float(b.x)) +
           fmaf(__uint_as_float(c.x), __uint_as_float(c.x), __uint_as_float(d.x) * __uint_as_float(d.x)), 1.f / 128, q);
  s += __shfl_xor_sync(~0u, s, 2); q += __shfl_xor_sync(~0u, q, 2);
  s *= 1.f / 1024;
  const float var = fmaxf(fmaf(-s, s, q * (1.f / 1024)), 0.f);
  float r;
  if (rnd) {
    float sd; asm("sqrt.approx.f32 %0, %1;" : "=f"(sd) : "f"(bf_round(bf_round(var) + 1e-5f)));
    r = rcp(bf_round(sd)); s = bf_round(s);
  } else r = rsqrtf(var + 1e-5f);
  const float nn = -s * r;
  const float ro = __shfl_xor_sync(~0u, r, 1), no = __shfl_xor_sync(~0u, nn, 1);
  const bool odd = lane & 1;
  r0 = odd ? ro : r; n0 = odd ? no : nn; r1 = odd ? r : ro; n1 = odd ? nn : no;
}
__device__ __forceinline__ void load_vec(uint32_t* w, uint32_t sb, int sec, int b, int lane) {
#pragma unroll
  for (int q = 0; q < 2; q++) { uint4 t = lds128(sb + MISC + MODV + sec * 256 + (lane & 3) * 64 + b * 32 + q * 16); w[4 * q] = t.x; w[4 * q + 1] = t.y; w[4 * q + 2] = t.z; w[4 * q + 3] = t.w; }
}
__device__ __forceinline__ void stage_done(uint32_t sb, int wg, int b, int lane) {
  fence_async_smem();
  __syncwarp();
  if (lane == 0) mbar_arrive(sb + MISC + B_RDY + b * 8);
}
__device__ __forceinline__ uint32_t hfma2(uint32_t a, uint32_t b, uint32_t c) { uint32_t r; asm("fma.rn.bf16x2 %0, %1, %2, %3;" : "=r"(r) : "r"(a), "r"(b), "r"(c)); return r; }
__device__ __forceinline__ void ln_apply(const float (&v)[64], const uint2* st, int row0, uint32_t ep, uint32_t sb, int sec_shift, int sec_scale, uint32_t stg_row, int wg, int lane) {
  uint32_t sc[16], sh[16];
#pragma unroll
  for (int b = 0; b < 2; b++) { load_vec(sc + 8 * b, sb, sec_scale, b, lane); load_vec(sh + 8 * b, sb, sec_shift, b, lane); }
  float n0, r0, n1, r1;
  ln_gather(st, row0, lane, ep, n0, r0, n1, r1, sec_shift == 0);
#pragma unroll
  for (int i = 0; i < 16; i += 2) {
    if (i == 8) { const float z = lds32f(sb + MISC + ZERO); n0 += z; n1 += z; }
    uint32_t w[4];
#pragma unroll
    for (int u = 0; u < 2; u++) {
      int q = i + u;
      w[2 * u] = hfma2(pack2(fmaf(v[4 * q], r0, n0), fmaf(v[4 * q + 1], r0, n0)), sc[q], sh[q]);
      w[2 * u + 1] = hfma2(pack2(fmaf(v[4 * q + 2], r1, n1), fmaf(v[4 * q + 3], r1, n1)), sc[q], sh[q]);
    }
    stsm4(stg_row + (i >> 3) * BLK + ((((i & 7) + (lane >> 4)) ^ (lane & 7)) << 4), w[0], w[1], w[2], w[3]);
    if ((i & 7) == 6) { stage_done(sb, wg, i >> 3, lane); }
  }
}
__device__ __forceinline__ uint32_t hmul2(uint32_t a, uint32_t b) { uint32_t r; asm("mul.rn.bf16x2 %0, %1, %2;" : "=r"(r) : "r"(a), "r"(b)); return r; }
__device__ __forceinline__ uint32_t silu_mul2(uint32_t g, uint32_t u) {
  const uint32_t h = hmul2(g, 0x3f003f00u);
  const float h0 = bf_lo(h), h1 = bf_hi(h);
  return hmul2(pack2(fmaf(h0, tanh_fast(h0), h0), fmaf(h1, tanh_fast(h1), h1)), u);
}

__device__ __forceinline__ void gemv_fma(float (&a)[8], uint4 w, float s) {
  a[0] = fmaf(bf_lo(w.x), s, a[0]); a[1] = fmaf(bf_hi(w.x), s, a[1]); a[2] = fmaf(bf_lo(w.y), s, a[2]); a[3] = fmaf(bf_hi(w.y), s, a[3]);
  a[4] = fmaf(bf_lo(w.z), s, a[4]); a[5] = fmaf(bf_hi(w.z), s, a[5]); a[6] = fmaf(bf_lo(w.w), s, a[6]); a[7] = fmaf(bf_hi(w.w), s, a[7]);
}
__device__ __forceinline__ float silu_c(float v) { return bf_round(__fdividef(v, 1.f + __expf(-v))); }
__device__ __forceinline__ float mod_gather(const uint32_t* p, uint32_t ep) {
  const uint32_t tag = tag_of(ep), fix = tag ^ 128u;
  uint32_t a, b, c, d, n = 0;
  while (true) {
    a = ld_rlx1(p); b = ld_rlx1(p + 2048); c = ld_rlx1(p + 4096); d = ld_rlx1(p + 6144);
    if ((((a ^ tag) | (b ^ tag) | (c ^ tag) | (d ^ tag)) & 255u) == 0) break;
    SPIN_GUARD(n);
  }
  return (__uint_as_float(a ^ fix) + __uint_as_float(b ^ fix)) + (__uint_as_float(c ^ fix) + __uint_as_float(d ^ fix));
}
__device__ __forceinline__ void mod_store(uint32_t sb, int sec, int col, float v) {
  v = bf_round(v);
  if (sec == 1) v += 1.f;
  sts16(sb + MISC + MODV + sec * 256 + (((col >> 1) & 3) * 16 + (col >> 3)) * 4 + (col & 1) * 2, __float2bfloat16_rn(v));
}

__global__ void __cluster_dims__(2, 1, 1) __launch_bounds__(384, 1)
fused_kernel(const bf16* __restrict__ cvec, const bf16* __restrict__ wmod, Scratch* gs, int by_sm, const __grid_constant__ Maps maps) {
  extern __shared__ __align__(1024) uint8_t smem_raw[];
  uint32_t sm; asm volatile("mov.u32 %0, %%smid;" : "=r"(sm));
  const uint32_t id = by_sm ? sm : blockIdx.x, xs = by_sm ? 112 + 8 * by_sm : 0, u = id < xs ? id : id - 4;
  const bool extra = id - xs < 4;
  uint4 wv[8];
  uint32_t ep0; uint16_t cv_;
  if (threadIdx.x < 256) {
    const int r0 = ((u >> 5) & 3) * 256 + (threadIdx.x & 224);
    asm volatile("ld.global.nc.u16 %0, [%1];" : "=h"(cv_) : "l"(cvec + r0 + (threadIdx.x & 31)));
    asm volatile("ld.global.u32 %0, [%1];" : "=r"(ep0) : "l"(gs->epoch + (blockIdx.x | (threadIdx.x & by_sm & 4))));
    if (!extra) {
      const bf16* wp = wmod + (r0 + ((threadIdx.x >> 3) & 3)) * 6144 + (u & 31) * 64 + (threadIdx.x & 7) * 8;
#pragma unroll
      for (int i = 0; i < 8; i++) wv[i] = ldg_nc(wp + i * 4 * 6144);
    }
  }
  const uint32_t sb = smem_u32(smem_raw);
  const int warp = __shfl_sync(~0u, threadIdx.x >> 5, 0), lane = threadIdx.x & 31;
  const int rank = blockIdx.x & 1;
  const int t = sm >> 1, v = t < 32 || by_sm == 2 ? t : t < 60 ? t + 1 + (((t - 32) * 37) >> 8) : (t - 58) * 8;
  const int gr = 0x71546320u >> ((v & 7) * 4);
  const int cid = !by_sm ? (blockIdx.x >> 1) - 2 : extra ? (t & 1) - 2 : (gr & 4) * 8 + (v >> 3) * 4 + (gr & 3);
  const int bid = cid * 2 + rank;
  const int m = cid >> 2, j = (cid & 3) * 2 + rank;
  const uint32_t bar = sb + MISC;

  if (warp >= 8) {
    asm volatile("setmaxnreg.dec.sync.aligned.u32 40;");
    if (extra) {
      if (warp == 8) {
        if (lane == 0) { for (int s = 0; s < 6; s++) { mbar_init(bar + B_FULL6 + s * 8, 1); mbar_init(bar + B_EMPTY6 + s * 8, 8); } fence_async_smem(); }
        __syncwarp();
        asm volatile("bar.arrive 2, 288;" ::: "memory");
        __nanosleep(XSLEEP);
#pragma unroll 1
        for (int it = 0, s = 0, par = 1; it < 64; it++) {
          mbar_wait(bar + B_EMPTY6 + s * 8, par);
          expect_e(bar + B_FULL6 + s * 8, 32768); tma_3d_e(sb + s * 32768, &maps.wmod, bar + B_FULL6 + s * 8, 0, (it & 15) * 64, 12 + (it >> 4) * 4 + bid);
          if (++s == 6) { s = 0; par ^= 1; }
        }
      }
    } else if (warp < 10) {
      uint32_t f6 = bar + B_FULL6, d6 = sb + (warp == 8 ? BLK : rank * HALF), p6 = 1;
      auto next6 = [&]() { f6 += 8; d6 += 32768; if (f6 == bar + B_FULL6 + 48) { f6 -= 48; d6 -= RING; p6 ^= 1; } };
      auto drained4 = [&](int q, int late) { if (q < 5) mbar_wait(bar + B_EMPTY4 + (((late ? 0x10332 : 0x32110) >> (4 * q)) & 3) * 8, 1); };
      auto drained6 = [&](int q) { if (q < 3) mbar_wait(bar + B_EMPTY6 + ((0x154 >> (4 * q)) & 7) * 8, q >> 1); };
      auto skip6 = [&]() { mbar_wait(f6 + 48, p6); expect_e(f6, 0); next6(); };
      if (warp == 8) {
        if (lane == 0) {
          if (sb & 1023) bail();
          for (int b = 0; b < 2; b++) mbar_init(bar + B_X + b * 8, 1);
          for (int s = 0; s < 4; s++) { mbar_init(bar + B_FULL4 + s * 8, 2); mbar_init(bar + B_EMPTY4 + s * 8, 16); }
          for (int s = 0; s < 6; s++) { mbar_init(bar + B_FULL6 + s * 8, 2); mbar_init(bar + B_EMPTY6 + s * 8, 16); }
          for (int b = 0; b < 2; b++) { mbar_init(bar + B_RDY + b * 8, 8); mbar_init(bar + B_FREE + b * 8, 1); mbar_init(bar + B_HH + b * 8, 1); mbar_init(bar + B_OUT + b * 8, 2); mbar_init(bar + B_HALO + b * 8, 1); }
          mbar_init(bar + B_MOD, 1); mbar_init(bar + B_LAG, 4); mbar_init(bar + B_ALL, 1); mbar_init(bar + B_HH2, 1);
          asm volatile("st.shared.u32 [%0], 0;" :: "r"(bar + ZERO) : "memory");
          asm volatile("fence.mbarrier_init.release.cluster;" ::: "memory");
          fence_async_smem();
        }
        __syncwarp();
        cl_arrive_relaxed();
        for (int b = 0; b < 2; b++) { expect_e(bar + B_X + b * 8, BLK); tma_3d_e(sb + STG + b * BLK, &maps.x, bar + B_X + b * 8, j * 128 + b * 64, m * 64, 0); }
        mbar_wait(bar + B_X + 8, 0);
#pragma unroll 1
        for (int ph = 0; ph < 2; ph++) {
          const CUtensorMap* const m0 = ph ? &maps.w1 : &maps.wqkv;
#pragma unroll 1
          for (int it = 0; it < (ph ? 48 : 16); it++) {
            const int s = (it + 2 * ph) & 3;
            int a0 = (ph ? it & 48 : 16) + 2 * j, a1 = ph ? a0 : a0 + 16, k0 = (it < 16 ? own_order(it, j) : it & 15) * 64;
            uint32_t full = bar + B_FULL4 + s * 8, d = sb + s * 49152 + BLK;
            if (ph) drained6(it);
            mbar_wait(full + 32, ~(it >> 2) & 1);
            tma_3d_e(d, m0, full, 0, k0, a0);
            if (it < 4) { const uint32_t t0 = clock(); while ((uint32_t)clock() - t0 < GAP) {} }
            tma_3d_e(d + BLK, m0 + ph, full, 0, k0, a1);
            expect_e(full, 2 * BLK);
            if (it < 4) { const uint32_t t0 = clock(); while ((uint32_t)clock() - t0 < GAP) {} }
            if (it >= 44) {
              if (it == 44) { mbar_wait(bar + B_FREE, 0); mbar_wait(bar + B_FREE + 8, 0); expect_e(bar + B_X, 2 * BLK); }
              bulk_ld_e(sb + STG + (it - 44) * HALF, gs->x1 + bid * 2048 + (it - 44) * 512, HALF, bar + B_X);
            }
          }
          const CUtensorMap* const m1 = ph ? &maps.w1s : &maps.wqkv;
          const int a = ph ? 48 + j : 2 * j;
#pragma unroll 1
          for (int k0 = 0; k0 < 1024; k0 += 64) {
            drained4(k0 >> 6, ph);
            mbar_wait(f6 + 48, p6);
            tma_3d_e(d6, m1, f6, 0, k0, a);
            if (ph) tma_3d_e(d6 + HALF, &maps.w3s, f6, 0, k0, a);
            expect_e(f6, BLK);
            next6();
          }
          if (ph) break;
#pragma unroll 1
          for (int it = 0; it < 16; it++) {
            const int k0 = own_order(it, j) * 64;
            mbar_wait(f6 + 48, p6);
            tma_3d_e(d6, &maps.wo, f6, 0, k0, 2 * j);
            expect_e(f6, BLK);
            next6();
          }
          skip6();
        }
#pragma unroll 1
        for (int k0 = 0; k0 < F_; k0 += 64) {
          mbar_wait(f6 + 48, p6);
          tma_3d_e(d6, &maps.w2, f6, 0, k0, 2 * j);
          expect_e(f6, BLK);
          next6();
        }
      } else {
        if (lane < 9) prefetch_map(&maps.x + lane);
        const uint32_t ep = gs->epoch[blockIdx.x] + 1;
        cl_arrive_relaxed(); cl_wait();
        auto run6 = [&](const uint4* src, int n, int sw) {
          src += rank * 512;
#pragma unroll 1
          for (int it = 0; it < n; it++) {
            if (sw >= 0) drained4(it, sw);
            mbar_wait(f6 + 48, p6);
            bulk_ld_mc_e(d6, src, HALF, f6);
            expect_e(f6, BLK);
            next6();
            src += 1024;
          }
        };
        uint32_t ready = 0;
        auto need = [&](int e, uint32_t mask) {
          if (!(ready & mask)) {
            uint32_t n = 0;
            do { ready = __ballot_sync(~0u, ld_acquire(gs->flag + (m * 128 + e * 16 + (lane & 14)) * FS) == ep); SPIN_GUARD(n); } while (!(ready & mask));
            fence_async_global();
          }
        };
        auto fresh = [&](int e, int it, uint32_t full, uint32_t empty, int par, uint32_t slot, uint4* src) {
          mbar_wait(empty, par);
          expect_e(full, it < 2 ? 0 : BLK);
          if (it >= 4) {
            const int kb = own_order(it, j);
            if (it < 10) need(e, 1u << kb); else if (it == 10) mbar_wait(bar + B_ALL, e & 1);
            bulk_ld_mc_e(slot + rank * HALF, src + kb * 1024 + rank * 512, HALF, full);
          } else if (it >= 2) {
            const int b = it > 2;
            const uint32_t to_peer = mapa(sb, rank ^ 1) - sb;
            const bool push = b && e != 1;
            mbar_wait(bar + (push ? B_RDY : B_FREE) + b * 8, e & 1);
            if (push) bulk_push_e(slot + to_peer, sb + STG + BLK, BLK, full + to_peer);
            else { fence_async_global(); bulk_ld_e(slot + to_peer, src + (2 * j + b) * 1024, BLK, full + to_peer); }
          } else ready = 0;
        };
        uint4* const h = gs->h + m * 16384;
#pragma unroll 1
        for (int e = 0; e < 3; e++) {
#pragma unroll 1
          for (int it = 0; it < 16; it++) {
            const int s = (it + e) & 3;
            const uint32_t full = e == 1 ? f6 : bar + B_FULL4 + s * 8;
            if (e == 2) drained6(it);
            fresh(e, it, full, full + (e == 1 ? 48 : 32), e == 1 ? p6 : ~(it >> 2) & 1, e == 1 ? d6 - rank * HALF : sb + s * 49152, e == 1 ? gs->o + m * 16384 : h);
            if (e == 1) next6();
          }
          if (e == 1) { skip6(); continue; }
#pragma unroll 1
          for (int it = 16; it < 16 + 16 * e; it++) {
            const int s = (it + 2) & 3;
            const uint32_t full = bar + B_FULL4 + s * 8;
            mbar_wait(full + 32, ~(it >> 2) & 1);
            bulk_ld_mc_e(sb + s * 49152 + rank * HALF, h + (it & 15) * 1024 + rank * 512, HALF, full);
            expect_e(full, BLK);
          }
          run6(h, 16, e);
        }
#pragma unroll 1
        for (int q = 0; q < 3; q++) {
          mbar_wait(bar + (q == 2 ? B_HH2 : B_HH + q * 8), 0);
          run6(gs->hh + m * 57344 + (64 - (64 >> q)) * 1024, 32 >> q, -1);
        }
      }
    } else {
      const int b = warp - 10;
      const uint32_t ep = gs->epoch[blockIdx.x] + 1;
      const uint32_t stg = sb + STG + b * BLK;
      cl_arrive_relaxed(); cl_wait();
      auto all_there = [&](int u, uint32_t done) {
        const uint32_t* fl = gs->flag + u * FS;
        uint32_t n = 0;
        while (!__all_sync(~0u, ld_acquire(fl) == ep)) { __nanosleep(100); SPIN_GUARD(n); }
        fence_async_global();
        arrive_e(done);
      };
#pragma unroll 1
      for (int e = 0; e < 7 - b; e++) {
        const int kb = (e < 3 ? 2 * j : e < 6 ? 2 * (8 * (e - 3) + j) : 48 + j) + b;
        uint4* const dst = (e == 1 ? gs->o + m * 16384 : e < 3 ? gs->h + m * 16384 : gs->hh + m * 57344) + kb * 1024;
        uint32_t* const fl = gs->flag + (m * 128 + (e < 3 ? e * 16 : U_HH) + kb) * FS;
        if (e < 3 && lane < 8) st_rlx1(fl + lane, 0);
        if (b && e < 3) {
          mbar_wait(bar + B_FREE, e & 1);
          const uint32_t t0 = clock();
          while ((uint32_t)clock() - t0 < (e == 1 ? B1D : B1P)) {}
        }
        mbar_wait(bar + B_RDY + b * 8, e & 1);
        bulk_st_e(dst, stg, e < 3 ? BLK : BLK / NPIECE);
        if (e >= 3) {
#pragma unroll 1
          for (int q = 1; q < NPIECE; q++) { __nanosleep(PSLEEP); bulk_st_e(dst + q * (1024 / NPIECE), stg + q * (BLK / NPIECE), BLK / NPIECE); }
        }
        publish_e(bar + B_FREE + b * 8, fl, ep);
        if (b && (e < 3 || e == 4)) all_there(m * 128 + (e < 3 ? e * 16 + (lane & 15) : U_HH + lane), bar + (e < 3 ? B_ALL : B_HH));
        if (!b && (e == 1 || e == 2)) {
#pragma unroll 1
          for (int sec = e == 1 ? 2 : 5; sec < 4 + e; sec++) {
            const uint4* p = (const uint4*)(gs->modv + (sec - 2) * 1024 + j * 128) + lane;
            uint4 v0, v1; uint32_t n = 0;
            while (true) {
              v0 = ld_rlx4(p); v1 = ld_rlx4(p + 32);
              if (__all_sync(~0u, v0.y == ep && v0.w == ep && v1.y == ep && v1.w == ep)) break;
              SPIN_GUARD(n);
            }
            const uint32_t d = sb + MISC + MODV + sec * 256 + ((lane & 3) * 16 + (lane >> 2)) * 4;
            asm volatile("st.shared.u32 [%0], %1;" :: "r"(d), "r"(__byte_perm(v0.x, v0.z, 0x7632)) : "memory");
            asm volatile("st.shared.u32 [%0], %1;" :: "r"(d + 32), "r"(__byte_perm(v1.x, v1.z, 0x7632)) : "memory");
          }
          __syncwarp();
          if (e == 1) { arrive_e(bar + B_MOD); }
        }
        if (e == 0) {
          uint32_t* const hf = gs->flag + (m * 128 + 48 + 2 * j + b) * FS;
          uint4* const hp = gs->halo + ((m * 8 + j) * 2 + b) * 256;
          if (m < 15 && lane < 8) st_rlx1(hf + 128 * FS + lane, 0);
          mbar_wait(bar + B_OUT + b * 8, 0);
          if (m < 15) {
            for (int w = 0; w < 2; w++) bulk_st_e(hp + 4096 + w * 128, stg + w * HALF, 2048);
            publish_e(bar + B_OUT + b * 8, hf + 128 * FS, ep);
          }
          if (m > 0) {
            uint32_t n = 0;
            while (!__all_sync(~0u, ld_acquire(hf) == ep)) SPIN_GUARD(n);
            fence_async_global();
            for (int w = 0; w < 2; w++) bulk_ld_e(stg + w * HALF, hp + w * 128, 2048, bar + B_HALO + b * 8);
            expect_e(bar + B_HALO + b * 8, 4096);
          } else {
            __syncwarp();
#pragma unroll
            for (int i = 0; i < 8; i++) sts128(stg + (i >> 2) * HALF + (i & 3) * 512 + lane * 16, 0, 0, 0, 0);
            __syncwarp();
            arrive_e(bar + B_HALO + b * 8);
          }
        }
      }
      if (b) {
#pragma unroll 1
        for (int q = 0; q < 2; q++) all_there(m * 128 + U_HH + 32 + q * 16 + (lane & (15 >> q)), bar + (q ? B_HH2 : B_HH + 8));
      }
    }
  } else {
    const int wg = warp >> 2, wq = warp & 3, tid = threadIdx.x;
    const int g = lane >> 2, c = lane & 3;
    if (!extra) cl_arrive_relaxed();
    asm volatile("setmaxnreg.inc.sync.aligned.u32 232;" ::: "memory");
    if (__builtin_expect(extra, 0)) {
      const uint32_t ep = ep0 + 1;
      float sv[4];
#pragma unroll
      for (int p = 0; p < 4; p++) sv[p] = silu_c(__bfloat162float(cvec[64 * (4 * p + (lane >> 3)) + 8 * warp + (lane & 7)]));
      named_bar(2, 288);
      int s = 0, par = 0;
#pragma unroll 1
      for (int sec = 0; sec < 4; sec++) {
        float a[8] = {0, 0, 0, 0, 0, 0, 0, 0};
#pragma unroll 1
        for (int it = 0; it < 16; it++) {
          const float sc = it < 4 ? sv[0] : it < 8 ? sv[1] : it < 12 ? sv[2] : sv[3];
          mbar_wait(bar + B_FULL6 + s * 8, par);
          uint4 w[8];
#pragma unroll
          for (int i = 0; i < 8; i++) w[i] = lds128(sb + s * 32768 + (warp * 8 + i) * 512 + lane * 16);
#pragma unroll
          for (int i = 0; i < 8; i++) gemv_fma(a, w[i], __shfl_sync(~0u, sc, (it & 3) * 8 + i));
          if (lane == 0) mbar_arrive(bar + B_EMPTY6 + s * 8);
          if (++s == 6) { s = 0; par ^= 1; }
        }
        const uint32_t red = sb + STG + sec * 8192;
        sts128(red + warp * 1024 + lane * 32, __float_as_uint(a[0]), __float_as_uint(a[1]), __float_as_uint(a[2]), __float_as_uint(a[3]));
        sts128(red + warp * 1024 + lane * 32 + 16, __float_as_uint(a[4]), __float_as_uint(a[5]), __float_as_uint(a[6]), __float_as_uint(a[7]));
        named_bar(1, 256);
        float t = 0;
#pragma unroll
        for (int q = 0; q < 8; q++) t += lds32f(red + q * 1024 + tid * 4);
        t = bf_round(t);
        if (sec == 2) t = bf_round(t + 1.f);
        st_rlx2(gs->modv + sec * 1024 + (bid + 4) * 256 + tid, __float_as_uint(t), ep);
      }
      if (tid == 0) gs->epoch[blockIdx.x] = ep;
      return;
    }
    const int row0 = wg * 64 + wq * 16 + g;
    if (c < 2) st_rlx2(gs->stat + m * 1024 + j * 128 + row0 + c * 8, 0, 0);
    cl_wait();
    uint32_t ep;
    asm volatile("add.u32 %0, %1, 1;" : "=r"(ep) : "r"(ep0) : "memory");
    const float sc_ = silu_c(__uint_as_float((uint32_t)cv_ << 16));
    const uint32_t rel = mapa(bar, (lane & 1) ^ rank);
    const uint32_t stg_row = sb + STG + (wg * 64 + wq * 16 + (lane & 15)) * 128;
    const uint32_t fre = bar + B_FREE;
    Ring r4{0, 0, 0}, r6{0, 0, 0};
    auto none = [](auto) {};
    uint32_t xk[32];
    {
      float a[8] = {0, 0, 0, 0, 0, 0, 0, 0};
#pragma unroll
      for (int i = 0; i < 8; i++) gemv_fma(a, wv[i], __shfl_sync(~0u, sc_, i * 4 + (lane >> 3)));
#pragma unroll
      for (int i = 0; i < 8; i++) { a[i] += __shfl_xor_sync(~0u, a[i], 8); a[i] += __shfl_xor_sync(~0u, a[i], 16); }
      if (lane < 8) {
        sts128(sb + RED_OFF + warp * 256 + lane * 32, __float_as_uint(a[0]), __float_as_uint(a[1]), __float_as_uint(a[2]), __float_as_uint(a[3]));
        sts128(sb + RED_OFF + warp * 256 + lane * 32 + 16, __float_as_uint(a[4]), __float_as_uint(a[5]), __float_as_uint(a[6]), __float_as_uint(a[7]));
      }
      named_bar(1, 256);
      if (tid < 64) {
        float s = 0;
#pragma unroll
        for (int w = 0; w < 8; w++) s += lds32f(sb + RED_OFF + w * 256 + tid * 4);
        st_rlx1(gs->modp + u * 64 + tid, (__float_as_uint(s) & ~255u) | tag_of(ep));
      }
      float v[64];
      mbar_wait(bar + B_X, 0); mbar_wait(bar + B_X + 8, 0);
#pragma unroll
      for (int i = 0; i < 16; i += 2) {
        uint32_t w0, w1, w2, w3;
        ldsm4(stg_row + (i >> 3) * BLK + ((((i & 7) + (lane >> 4)) ^ (lane & 7)) << 4), w0, w1, w2, w3);
        xk[2 * i] = w0; xk[2 * i + 1] = w1; xk[2 * i + 2] = w2; xk[2 * i + 3] = w3;
        v[4 * i] = bf_lo(w0); v[4 * i + 1] = bf_hi(w0); v[4 * i + 2] = bf_lo(w1); v[4 * i + 3] = bf_hi(w1);
        v[4 * i + 4] = bf_lo(w2); v[4 * i + 5] = bf_hi(w2); v[4 * i + 6] = bf_lo(w3); v[4 * i + 7] = bf_hi(w3);
      }
      ln_publish(v, gs->stat + m * 1024, j, row0, lane, ep);
      mod_store(sb, tid >> 7, tid & 127, mod_gather(gs->modp + (tid >> 7) * 1024 + j * 128 + (tid & 127), ep));
      named_bar(1, 256);
      ln_apply(v, gs->stat + m * 1024, row0, ep, sb, 0, 1, stg_row, wg, lane);
      named_bar(1, 256);
    }
    {
      uint32_t kf[32], vf[32], pv[32];
      const bool first = wq == 0 && m == 0;
      const uint32_t xa = sb + STG + wg * HALF + wq * 2048 + lane * 16;
      {
        float acc[128];
        mainloop<256, 4, 0, 0>(acc, 16, true, r4, sb, wg, lane, rel, none, none, [&] {
          mbar_wait(fre + 8, 0);
          if (c < 2) st_rlx2(gs->stat + (16 + m) * 1024 + j * 128 + row0 + c * 8, 0, 0);
        });
#pragma unroll
        for (int i = 0; i < 32; i++) { kf[i] = pack2(acc[2 * i], acc[2 * i + 1]); vf[i] = pack2(acc[64 + 2 * i], acc[65 + 2 * i]); }
      }
      float acc[64];
      constexpr int QP = 2;
      auto inbox = [&](const int b) {
        if (wq == 0) mbar_wait(bar + B_HALO + b * 8, 0);
#pragma unroll
        for (int i = 4 * b; i < 4 * b + 4; i++) {
          uint4 q = lds128(xa + b * BLK + (i & 3) * 512);
          pv[4 * i] = q.x; pv[4 * i + 1] = q.y; pv[4 * i + 2] = q.z; pv[4 * i + 3] = q.w;
        }
        __syncwarp();
      };
      auto sent = [&](int b) { if (wq == 3) { fence_async_smem(); __syncwarp(); if (lane == 0) mbar_arrive(bar + B_OUT + b * 8); } };
      mainloop<128, 6, 8 / QP, 0>(acc, 16, false, r6, sb, wg, lane, rel, [&](auto ic) {
        constexpr int q = (ic.v - 1) * QP;
        if (q == 4) sent(0);
#pragma unroll
        for (int i = 4 * q; i < 4 * (q + QP); i++) vf[i] = movm(vf[i]);
#pragma unroll
        for (int i = q; i < q + QP; i++) sts128(xa + (wq == 3 ? -6144 : 2048) + (i >> 2) * BLK + (i & 3) * 512, kf[4 * i + 1], kf[4 * i + 3], vf[4 * i + 1], vf[4 * i + 3]);
      }, [&](int it) { if (it == 8 / QP + 1) sent(1); }, [&] {
        named_bar(2 + wg, 128);
        inbox(0);
      });
      int gz = g;
#pragma unroll
      for (int b = 0; b < 2; b++) {
        const bool up0 = 2 * c > gz, up1 = 2 * c + 1 > gz;
        const uint32_t mup = (up0 ? 0xffffu : 0u) | (up1 ? 0xffff0000u : 0u);
        float l[2][4], mx[4];
#pragma unroll
        for (int h = 0; h < 2; h++) {
          uint32_t q[8];
          const int k = 16 * b + 8 * h;
#pragma unroll
          for (int i = 0; i < 8; i++) q[i] = pack2(acc[2 * k + 2 * i], acc[2 * k + 2 * i + 1]);
          float s0[4], s1[4], s2[4];
          mma16z(s0, q[0], q[1], q[2], q[3], pv[k], pv[k + 1]); mma16z(s1, q[0], q[1], q[2], q[3], kf[k], kf[k + 2]); mma16z(s2, q[0], q[1], q[2], q[3], kf[k + 1], kf[k + 3]);
          mma16(s0, q[4], q[5], q[6], q[7], pv[k + 4], pv[k + 5]); mma16(s1, q[4], q[5], q[6], q[7], kf[k + 4], kf[k + 6]); mma16(s2, q[4], q[5], q[6], q[7], kf[k + 5], kf[k + 7]);
          if (first) { s0[0] = -INFINITY; s0[1] = -INFINITY; }
          l[h][0] = up0 ? s0[0] : s1[0]; l[h][1] = up1 ? s0[1] : s1[1]; l[h][2] = up0 ? s1[2] : s2[2]; l[h][3] = up1 ? s1[3] : s2[3];
          mx[2 * h] = fmaxf(l[h][0], l[h][1]); mx[2 * h + 1] = fmaxf(l[h][2], l[h][3]);
        }
#pragma unroll
        for (int o = 1; o < 4; o <<= 1) {
#pragma unroll
          for (int h = 0; h < 4; h++) mx[h] = fmaxf(mx[h], __shfl_xor_sync(~0u, mx[h], o));
        }
#pragma unroll
        for (int h = 0; h < 2; h++) {
          const float n0 = -mx[2 * h] * SCL, n1 = -mx[2 * h + 1] * SCL;
          const uint32_t pa = pack2(ex2(fmaf(l[h][0], SCL, n0)), ex2(fmaf(l[h][1], SCL, n0))), pb = pack2(ex2(fmaf(l[h][2], SCL, n1)), ex2(fmaf(l[h][3], SCL, n1)));
          float sm[4];
          mma8z(sm, pa, pb, 0x3f803f80u);
          const float ia = rcp(sm[0]), ib = rcp(sm[2]);
#pragma unroll
          for (int i = 8 * b + 4 * h; i < 8 * b + 4 * h + 4; i += 2) {
            uint32_t of[4];
#pragma unroll
            for (int d = 0; d < 2; d++) {
              float o[4];
              mma16z(o, pa & ~mup, pb & mup, 0u, pb & ~mup, vf[2 * (i + d)], vf[2 * (i + d) + 1]);
              mma8(o, pa & mup, 0u, pv[2 * i + 2 + d]);
              of[2 * d] = pack2(o[0] * ia, o[1] * ia); of[2 * d + 1] = pack2(o[2] * ib, o[3] * ib);
            }
            stsm4(stg_row + b * BLK + ((((i & 7) + (lane >> 4)) ^ (lane & 7)) << 4), of[0], of[1], of[2], of[3]);
          }
        }
        stage_done(sb, wg, b, lane);
        if (b == 0) inbox(1);
        if (b == 0) gz += __float_as_uint(lds32f(bar + ZERO));
      }
      named_bar(1, 256);
    }
    uint32_t pk[64];
    {
      float acc[64];
      mainloop<128, 6, 0, 0>(acc, 16, true, r6, sb, wg, lane, rel, none, none, [&] {
        mbar_wait(bar + B_MOD, 0); mbar_wait(fre + 8, 1);
        load_vec(pk + 32, sb, 2, 0, lane); load_vec(pk + 40, sb, 2, 1, lane);
#pragma unroll
        for (int i = 0; i < 32; i++) { pk[i] = xk[i]; asm volatile("" : "+r"(pk[i])); }
      });
#pragma unroll
      for (int i = 0; i < 32; i++) {
        acc[2 * i] = fmaf(acc[2 * i], bf_lo(pk[32 + (i >> 1)]), bf_lo(pk[i]));
        acc[2 * i + 1] = fmaf(acc[2 * i + 1], bf_hi(pk[32 + (i >> 1)]), bf_hi(pk[i]));
      }
      ln_publish(acc, gs->stat + (16 + m) * 1024, j, row0, lane, ep);
      mbar_wait(bar + B_FULL6 + 16, 1);
      if (lane < 2) mbar_arrive_cl(rel + B_EMPTY6 + 16);
      ring_next<6>(r6);
#pragma unroll
      for (int i = 0; i < 32; i++) { pk[i] = pack2(acc[2 * i], acc[2 * i + 1]); pk[32 + i] = 0; }
      ln_apply(acc, gs->stat + (16 + m) * 1024, row0, ep, sb, 3, 4, stg_row, wg, lane);
      named_bar(1, 256);
    }
    auto swiglu = [&](int q, int uo, int par) {
      if ((q & 3) == 0 && par >= 0) mbar_wait(fre + 2 * q, par);
      uint32_t w[4];
#pragma unroll
      for (int u = 0; u < 4; u++) w[u] = silu_mul2(pk[4 * q + u], pk[uo + 4 * q + u]);
      stsm4(stg_row + (q >> 2) * BLK + ((((2 * q & 7) + (lane >> 4)) ^ (lane & 7)) << 4), w[0], w[1], w[2], w[3]);
    };
    r4.s = r4.wrap = 2;
#pragma unroll 1
    for (int t = 0; t < 3; t++) {
      float acc[128];
      mainloop<256, 4, 4, 1>(acc, 16, t == 0, r4, sb, wg, lane, rel, [&](auto ic) {
        if (t) {
          if (ic.v == 3) stage_done(sb, wg, 0, lane);
          swiglu(2 * ic.v - 2, 32, ~t & 1); swiglu(2 * ic.v - 1, 32, 0);
        }
      }, [&](int it) {
        if (t && it == 5) stage_done(sb, wg, 1, lane);
        if (t == 0 && it >= 8) {
          uint4* p = gs->x1 + bid * 2048 + ((it >> 2) & 1) * 1024 + warp * 128 + (it & 3) * 32 + lane;
#pragma unroll
          for (int i = 0; i < 8; i++)
            asm volatile("{\n.reg .pred p;\nsetp.eq.u32 p, %5, %6;\n@p st.global.v4.u32 [%0], {%1,%2,%3,%4};\n}" :: "l"(p), "r"(pk[4 * i]), "r"(pk[4 * i + 1]), "r"(pk[4 * i + 2]), "r"(pk[4 * i + 3]), "r"(it), "r"(8 + i) : "memory");
        }
      }, [&] { if (t == 0) fence_async_global(); else if (t == 2) mbar_wait(bar + B_X, 1); }, t & 1);
#pragma unroll
      for (int i = 0; i < 64; i++) pk[i] = pack2(acc[2 * i], acc[2 * i + 1]);
    }
    uint32_t x1[32];
    {
      float acc[64];
      mainloop<128, 6, 10, 1>(acc, 16, false, r6, sb, wg, lane, rel, [&](auto ic) {
        constexpr int b = ic.v > 5, q = ic.v - 5 * b;
        if (q == 1) {
          if (b) stage_done(sb, wg, 0, lane);
#pragma unroll
          for (int i = 4 * b; i < 4 * b + 4; i++) { const uint4 x = lds128(sb + STG + b * BLK + warp * 2048 + (i & 3) * 512 + lane * 16); x1[4 * i] = x.x; x1[4 * i + 1] = x.y; x1[4 * i + 2] = x.z; x1[4 * i + 3] = x.w; }
          __syncwarp();
        } else swiglu(4 * b + q - 2, 32, -1);
      }, [&](int it) { if (it == 11) stage_done(sb, wg, 1, lane); }, [] {}, 1);
#pragma unroll
      for (int i = 0; i < 32; i++) pk[i] = pack2(acc[2 * i], acc[2 * i + 1]);
    }
    {
      float acc[64];
      mainloop<128, 6, 4, TAILLAG>(acc, 56, false, r6, sb, wg, lane, rel, [&](auto ic) { swiglu(ic.v - 1, 16, 1); },
                                   [&](int it) { if (it == 5) stage_done(sb, wg, 0, lane); }, [&] {
        load_vec(pk + 32, sb, 5, 0, lane); load_vec(pk + 40, sb, 5, 1, lane);
        mbar_wait(fre, 0); mbar_wait(fre + 8, 1);
      }, 0);
      __syncwarp();
      cl_arrive_relaxed();
#pragma unroll
      for (int i = 0; i < 16; i += 2) {
        uint32_t w[4];
#pragma unroll
        for (int u = 0; u < 4; u++) {
          const int q = 2 * i + u;
          w[u] = hfma2(pack2(acc[2 * q], acc[2 * q + 1]), pk[32 + (q >> 1)], x1[q]);
        }
        stsm4(stg_row + (i >> 3) * BLK + ((((i & 7) + (lane >> 4)) ^ (lane & 7)) << 4), w[0], w[1], w[2], w[3]);
        if ((i & 7) == 6) {
          fence_async_smem();
          __syncwarp();
          if (elect()) { tma_store_3d(&maps.out, sb + STG + (i >> 3) * BLK + warp * 2048, j * 128 + (i >> 3) * 64, m * 64 + wq * 16, wg); if (i > 8) bulk_commit(); }
        }
      }
      bulk_wait_read();
      if (tid == 0) gs->epoch[blockIdx.x] = ep;
      cl_wait();
    }
  }
}

typedef CUresult (*EncodeFn)(CUtensorMap*, CUtensorMapDataType, cuuint32_t, void*, const cuuint64_t*, const cuuint64_t*, const cuuint32_t*, const cuuint32_t*,
                             CUtensorMapInterleave, CUtensorMapSwizzle, CUtensorMapL2promotion, CUtensorMapFloatOOBfill);

void make_map(EncodeFn fn, CUtensorMap* mp, const void* base, uint64_t d0, uint64_t d1, uint64_t d2, uint64_t s1, uint64_t s2, uint32_t b2, uint32_t b0 = 64, uint32_t b1 = 64) {
  cuuint64_t d[3] = {d0, d1, d2}, s[2] = {s1, s2};
  cuuint32_t b[3] = {b0, b1, b2}, e[3] = {1, 1, 1};
  fn(mp, CU_TENSOR_MAP_DATA_TYPE_BFLOAT16, 3, (void*)base, d, s, b, e, CU_TENSOR_MAP_INTERLEAVE_NONE, b0 == 64 ? CU_TENSOR_MAP_SWIZZLE_128B : CU_TENSOR_MAP_SWIZZLE_NONE,
     CU_TENSOR_MAP_L2_PROMOTION_L2_128B, CU_TENSOR_MAP_FLOAT_OOB_FILL_NONE);
}

__global__ void probe_kernel() {}
int max_clusters(int size) {
  cudaLaunchConfig_t cfg = {};
  cudaLaunchAttribute at;
  at.id = cudaLaunchAttributeClusterDimension; at.val.clusterDim.x = size; at.val.clusterDim.y = 1; at.val.clusterDim.z = 1;
  cfg.gridDim = dim3(size * 66); cfg.blockDim = dim3(384); cfg.dynamicSmemBytes = SMEM_BYTES; cfg.attrs = &at; cfg.numAttrs = 1;
  int n = 0;
  if (cudaOccupancyMaxActiveClusters(&n, probe_kernel, &cfg) != cudaSuccess) { cudaGetLastError(); return 0; }
  return n;
}

}

extern "C" void kernel_launch(void* const* d_in, const int* in_sizes, int n_in, void* d_out, int out_size) {
  static EncodeFn fn = nullptr;
  static int by_sm = 0;
  static Scratch* gs = nullptr;
  if (!fn) {
    void* p = nullptr; cudaDriverEntryPointQueryResult q;
    cudaGetDriverEntryPoint("cuTensorMapEncodeTiled", &p, cudaEnableDefault, &q);
    fn = (EncodeFn)p;
    cudaFuncSetAttribute(fused_kernel, cudaFuncAttributeMaxDynamicSharedMemorySize, SMEM_BYTES);
    int dev = 0, sms = 0;
    cudaGetSymbolAddress((void**)&gs, g_scratch);
    cudaGetDevice(&dev);
    cudaDeviceGetAttribute(&sms, cudaDevAttrMultiProcessorCount, dev);
    cudaFuncSetAttribute(probe_kernel, cudaFuncAttributeMaxDynamicSharedMemorySize, SMEM_BYTES);
    if (sms == 132 && max_clusters(2) == 66) {
      const int c4 = max_clusters(4), c6 = max_clusters(6), c8 = max_clusters(8);
      by_sm = c4 == 30 && c6 == 17 && c8 == 15 ? 1 : c8 == 16 ? 2 : 0;
    }
  }
  Maps mp;
  make_map(fn, &mp.x, d_in[0], D_, S_ / 2, 2, 4096, 2048, 2);
  make_map(fn, &mp.out, d_out, D_, S_ / 2, 2, 4096, 2048, 1, 64, 16);
  make_map(fn, &mp.wqkv, d_in[1], 64, D_, 3 * D_ / 64, 3 * D_ * 2, 128, 2);
  make_map(fn, &mp.wo, d_in[2], 64, D_, D_ / 64, D_ * 2, 128, 2);
  make_map(fn, &mp.w1, d_in[4], 64, D_, F_ / 64, F_ * 2, 128, 2);
  make_map(fn, &mp.w3, d_in[5], 64, D_, F_ / 64, F_ * 2, 128, 2);
  make_map(fn, &mp.w1s, d_in[4], 64, D_, F_ / 64, F_ * 2, 128, 1);
  make_map(fn, &mp.w3s, d_in[5], 64, D_, F_ / 64, F_ * 2, 128, 1);
  make_map(fn, &mp.w2, d_in[6], 64, F_, D_ / 64, D_ * 2, 128, 2);
  make_map(fn, &mp.wmod, d_in[8], 256, D_, 24, 6 * D_ * 2, 512, 1, 256);
  fused_kernel<<<132, 384, SMEM_BYTES>>>((const bf16*)d_in[7], (const bf16*)d_in[8], gs, by_sm, mp);
}
```

```cpp
#include <cuda_runtime.h>
#include <cuda_bf16.h>
#include <cuda.h>
#include <stdint.h>

typedef __nv_bfloat16 bf16;

namespace {

constexpr int S_ = 2048, D_ = 1024, F_ = 3584;
constexpr int BLK = 16384;
constexpr int HALF = 8192;
constexpr int RING = 196608;
constexpr int STG = RING;
constexpr int MISC = RING + 2 * BLK;
constexpr int SMEM_BYTES = MISC + 3072;
constexpr int B_FULL4 = 0, B_EMPTY4 = 32, B_FULL6 = 64, B_EMPTY6 = 112, B_RDY = 160, B_FREE = 176, B_LAG = 192, B_X = 208, B_MOD = 224, B_OUT = 240, B_HH = 256, B_ALL = 272, B_HH2 = 288, ZERO = 296, B_HALO = 304;
constexpr int MODV = 512;
constexpr int RED_OFF = 0;
constexpr float SCL = 0.17677669529663687f * 1.4426950408889634f;
constexpr int U_HH = 64;
constexpr int FS = 8;
constexpr int NPIECE = 4, PSLEEP = 300;
constexpr int XSLEEP = 4000;
constexpr uint32_t GAP = 250;
constexpr uint32_t B1P = 3700, B1D = 700;
constexpr int TAILLAG = 5;

struct Maps { CUtensorMap x, out, wqkv, wo, w1, w3, w1s, w3s, w2, wmod; };

struct Scratch {
  uint32_t epoch[256];
  uint32_t flag[16 * 128 * FS];
  uint32_t modp[8 * 2 * 4 * 128];
  uint2 modv[4 * 1024];
  uint2 stat[2 * 16 * 8 * 128];
  uint4 halo[16 * 8 * 2 * 256];
  uint4 x1[128 * 8 * 256];
  uint4 h[16 * 16 * 1024];
  uint4 o[16 * 16 * 1024];
  uint4 hh[16 * 56 * 1024];
};
__device__ __align__(1024) Scratch g_scratch;

__device__ __forceinline__ void bail() { asm volatile("st.global.u32 [%0], %1;" :: "l"(0ull), "r"(0) : "memory"); }
__device__ __forceinline__ uint32_t smem_u32(const void* p) { return (uint32_t)__cvta_generic_to_shared(p); }
__device__ __forceinline__ void mbar_init(uint32_t bar, uint32_t cnt) { asm volatile("mbarrier.init.shared::cta.b64 [%0], %1;" :: "r"(bar), "r"(cnt) : "memory"); }
__device__ __forceinline__ void mbar_arrive(uint32_t bar) { asm volatile("mbarrier.arrive.shared::cta.b64 _, [%0];" :: "r"(bar) : "memory"); }
__device__ __forceinline__ void mbar_arrive_cl(uint32_t cl_addr) { asm volatile("mbarrier.arrive.shared::cluster.b64 _, [%0];" :: "r"(cl_addr) : "memory"); }
__device__ __forceinline__ uint32_t mapa(uint32_t addr, uint32_t cta) { uint32_t r; asm("mapa.shared::cluster.u32 %0, %1, %2;" : "=r"(r) : "r"(addr), "r"(cta)); return r; }
__device__ __forceinline__ void mbar_wait(uint32_t bar, uint32_t parity) {
  asm volatile("{\n.reg .pred p;\n.reg .b32 n;\n.reg .b64 z;\nmov.b32 n, 0;\nmov.b64 z, 0;\n"
               "W: add.u32 n, n, 1;\nsetp.gt.u32 p, n, 0x400000;\n@p st.global.u32 [z], n;\n"
               "mbarrier.try_wait.parity.shared::cta.b64 p, [%0], %1;\n@!p bra W;\n}" :: "r"(bar), "r"(parity) : "memory");
}
__device__ __forceinline__ void tma_store_3d(const CUtensorMap* m, uint32_t src, int c0, int c1, int c2) {
  asm volatile("cp.async.bulk.tensor.3d.global.shared::cta.bulk_group [%0, {%2, %3, %4}], [%1];" :: "l"(m), "r"(src), "r"(c0), "r"(c1), "r"(c2) : "memory");
}
#define ELECT "{\n.reg .pred p;\nelect.sync _|p, 0xffffffff;\n@p "
__device__ __forceinline__ void expect_e(uint32_t bar, uint32_t bytes) { asm volatile(ELECT "mbarrier.arrive.expect_tx.shared::cta.b64 _, [%0], %1;\n}" :: "r"(bar), "r"(bytes) : "memory"); }
__device__ __forceinline__ void tma_3d_e(uint32_t dst, const CUtensorMap* m, uint32_t bar, int c0, int c1, int c2) {
  asm volatile(ELECT "cp.async.bulk.tensor.3d.shared::cluster.global.mbarrier::complete_tx::bytes [%0], [%1, {%3, %4, %5}], [%2];\n}" :: "r"(dst), "l"(m), "r"(bar), "r"(c0), "r"(c1), "r"(c2) : "memory");
}
__device__ __forceinline__ void bulk_ld_e(uint32_t dst, const void* src, uint32_t bytes, uint32_t bar) {
  asm volatile(ELECT "cp.async.bulk.shared::cluster.global.mbarrier::complete_tx::bytes [%0], [%1], %2, [%3];\n}" :: "r"(dst), "l"(src), "r"(bytes), "r"(bar) : "memory");
}
__device__ __forceinline__ void bulk_ld_mc_e(uint32_t dst, const void* src, uint32_t bytes, uint32_t bar) {
  asm volatile(ELECT "cp.async.bulk.shared::cluster.global.mbarrier::complete_tx::bytes.multicast::cluster [%0], [%1], %2, [%3], %4;\n}" :: "r"(dst), "l"(src), "r"(bytes), "r"(bar), "h"((uint16_t)3) : "memory");
}
__device__ __forceinline__ void bulk_push_e(uint32_t dst_cl, uint32_t src, uint32_t bytes, uint32_t bar_cl) {
  asm volatile(ELECT "cp.async.bulk.shared::cluster.shared::cta.mbarrier::complete_tx::bytes [%0], [%1], %2, [%3];\n}" :: "r"(dst_cl), "r"(src), "r"(bytes), "r"(bar_cl) : "memory");
}
__device__ __forceinline__ void arrive_e(uint32_t bar) { asm volatile(ELECT "mbarrier.arrive.shared::cta.b64 _, [%0];\n}" :: "r"(bar) : "memory"); }
__device__ __forceinline__ void bulk_st_e(void* dst, uint32_t src, uint32_t bytes) {
  asm volatile(ELECT "cp.async.bulk.global.shared::cta.bulk_group [%0], [%1], %2;\n}" :: "l"(dst), "r"(src), "r"(bytes) : "memory");
}
__device__ __forceinline__ void publish_e(uint32_t free_bar, uint32_t* flag, uint32_t ep) {
  asm volatile(ELECT "cp.async.bulk.commit_group;\n@p cp.async.bulk.wait_group 0;\n@p mbarrier.arrive.shared::cta.b64 _, [%0];\n@p st.release.gpu.global.u32 [%1], %2;\n}"
               :: "r"(free_bar), "l"(flag), "r"(ep) : "memory");
}
__device__ __forceinline__ void bulk_commit() { asm volatile("cp.async.bulk.commit_group;" ::: "memory"); }
__device__ __forceinline__ void bulk_wait_read() { asm volatile("cp.async.bulk.wait_group.read 0;" ::: "memory"); }
__device__ __forceinline__ void fence_async_global() { asm volatile("fence.proxy.async.global;" ::: "memory"); }
__device__ __forceinline__ void fence_async_smem() { asm volatile("fence.proxy.async.shared::cta;" ::: "memory"); }
__device__ __forceinline__ void wg_arrive() { asm volatile("wgmma.fence.sync.aligned;" ::: "memory"); }
__device__ __forceinline__ void wg_commit() { asm volatile("wgmma.commit_group.sync.aligned;" ::: "memory"); }
template <int N> __device__ __forceinline__ void wg_wait() { asm volatile("wgmma.wait_group.sync.aligned %0;" :: "n"(N) : "memory"); }
__device__ __forceinline__ void cl_arrive_relaxed() { asm volatile("barrier.cluster.arrive.relaxed.aligned;" ::: "memory"); }
__device__ __forceinline__ void cl_wait() { asm volatile("barrier.cluster.wait.acquire.aligned;" ::: "memory"); }
__device__ __forceinline__ bool elect() { uint32_t p; asm volatile("{\n.reg .pred p;\nelect.sync _|p, 0xffffffff;\nselp.u32 %0, 1, 0, p;\n}" : "=r"(p)); return p; }
__device__ __forceinline__ void named_bar(int id, int n) { asm volatile("bar.sync %0, %1;" :: "r"(id), "r"(n) : "memory"); }
__device__ __forceinline__ uint32_t pack2(float lo, float hi) { uint32_t r; asm("cvt.rn.bf16x2.f32 %0, %1, %2;" : "=r"(r) : "f"(hi), "f"(lo)); return r; }
__device__ __forceinline__ float bf_lo(uint32_t w) { return __uint_as_float(w << 16); }
__device__ __forceinline__ float bf_hi(uint32_t w) { return __uint_as_float(w & 0xffff0000u); }
__device__ __forceinline__ float bf_round(float v) { return __bfloat162float(__float2bfloat16_rn(v)); }
__device__ __forceinline__ void stsm4(uint32_t addr, uint32_t a, uint32_t b, uint32_t c, uint32_t d) {
  asm volatile("stmatrix.sync.aligned.m8n8.x4.shared.b16 [%0], {%1, %2, %3, %4};" :: "r"(addr), "r"(a), "r"(b), "r"(c), "r"(d) : "memory");
}
__device__ __forceinline__ void ldsm4(uint32_t addr, uint32_t& a, uint32_t& b, uint32_t& c, uint32_t& d) {
  asm volatile("ldmatrix.sync.aligned.m8n8.x4.shared.b16 {%0, %1, %2, %3}, [%4];" : "=r"(a), "=r"(b), "=r"(c), "=r"(d) : "r"(addr) : "memory");
}
__device__ __forceinline__ uint32_t movm(uint32_t a) { uint32_t r; asm volatile("movmatrix.sync.aligned.m8n8.trans.b16 %0, %1;" : "=r"(r) : "r"(a)); return r; }
__device__ __forceinline__ void mma16(float (&d)[4], uint32_t a0, uint32_t a1, uint32_t a2, uint32_t a3, uint32_t b0, uint32_t b1) {
  asm("mma.sync.aligned.m16n8k16.row.col.f32.bf16.bf16.f32 {%0,%1,%2,%3}, {%4,%5,%6,%7}, {%8,%9}, {%0,%1,%2,%3};"
               : "+f"(d[0]), "+f"(d[1]), "+f"(d[2]), "+f"(d[3]) : "r"(a0), "r"(a1), "r"(a2), "r"(a3), "r"(b0), "r"(b1));
}
__device__ __forceinline__ void mma16z(float (&d)[4], uint32_t a0, uint32_t a1, uint32_t a2, uint32_t a3, uint32_t b0, uint32_t b1) {
  asm("mma.sync.aligned.m16n8k16.row.col.f32.bf16.bf16.f32 {%0,%1,%2,%3}, {%4,%5,%6,%7}, {%8,%9}, {%10,%10,%10,%10};"
      : "=f"(d[0]), "=f"(d[1]), "=f"(d[2]), "=f"(d[3]) : "r"(a0), "r"(a1), "r"(a2), "r"(a3), "r"(b0), "r"(b1), "f"(0.f));
}
__device__ __forceinline__ void mma8z(float (&d)[4], uint32_t a0, uint32_t a1, uint32_t b0) {
  asm("mma.sync.aligned.m16n8k8.row.col.f32.bf16.bf16.f32 {%0,%1,%2,%3}, {%4,%5}, {%6}, {%7,%7,%7,%7};"
      : "=f"(d[0]), "=f"(d[1]), "=f"(d[2]), "=f"(d[3]) : "r"(a0), "r"(a1), "r"(b0), "f"(0.f));
}
__device__ __forceinline__ void mma8(float (&d)[4], uint32_t a0, uint32_t a1, uint32_t b0) {
  asm("mma.sync.aligned.m16n8k8.row.col.f32.bf16.bf16.f32 {%0,%1,%2,%3}, {%4,%5}, {%6}, {%0,%1,%2,%3};"
               : "+f"(d[0]), "+f"(d[1]), "+f"(d[2]), "+f"(d[3]) : "r"(a0), "r"(a1), "r"(b0));
}
__device__ __forceinline__ uint4 lds128(uint32_t a) { uint4 v; asm volatile("ld.shared.v4.u32 {%0,%1,%2,%3}, [%4];" : "=r"(v.x), "=r"(v.y), "=r"(v.z), "=r"(v.w) : "r"(a) : "memory"); return v; }
__device__ __forceinline__ void sts128(uint32_t a, uint32_t x, uint32_t y, uint32_t z, uint32_t w) { asm volatile("st.shared.v4.u32 [%0], {%1,%2,%3,%4};" :: "r"(a), "r"(x), "r"(y), "r"(z), "r"(w) : "memory"); }
__device__ __forceinline__ float lds32f(uint32_t a) { float v; asm volatile("ld.shared.f32 %0, [%1];" : "=f"(v) : "r"(a) : "memory"); return v; }
__device__ __forceinline__ void sts16(uint32_t a, bf16 v) { asm volatile("st.shared.b16 [%0], %1;" :: "r"(a), "h"(__bfloat16_as_ushort(v)) : "memory"); }
__device__ __forceinline__ uint4 ldg_nc(const void* p) { uint4 v; asm volatile("ld.global.nc.L1::no_allocate.v4.u32 {%0,%1,%2,%3}, [%4];" : "=r"(v.x), "=r"(v.y), "=r"(v.z), "=r"(v.w) : "l"(p)); return v; }
__device__ __forceinline__ uint4 ld_rlx4(const uint4* p) {
  unsigned long long a, b; asm volatile("ld.relaxed.gpu.global.v2.b64 {%0,%1}, [%2];" : "=l"(a), "=l"(b) : "l"(p) : "memory");
  return make_uint4((uint32_t)a, (uint32_t)(a >> 32), (uint32_t)b, (uint32_t)(b >> 32));
}
__device__ __forceinline__ uint2 ld_rlx2(const uint2* p) { unsigned long long a; asm volatile("ld.relaxed.gpu.global.b64 %0, [%1];" : "=l"(a) : "l"(p) : "memory"); return make_uint2((uint32_t)a, (uint32_t)(a >> 32)); }
__device__ __forceinline__ void st_rlx2(uint2* p, uint32_t x, uint32_t y) { asm volatile("st.relaxed.gpu.global.b64 [%0], %1;" :: "l"(p), "l"((unsigned long long)x | ((unsigned long long)y << 32)) : "memory"); }
__device__ __forceinline__ void st_rlx1(uint32_t* p, uint32_t v) { asm volatile("st.relaxed.gpu.global.u32 [%0], %1;" :: "l"(p), "r"(v) : "memory"); }
__device__ __forceinline__ uint32_t ld_rlx1(const uint32_t* p) { uint32_t v; asm volatile("ld.relaxed.gpu.global.u32 %0, [%1];" : "=r"(v) : "l"(p) : "memory"); return v; }
__device__ __forceinline__ uint32_t ld_acquire(const uint32_t* p) { uint32_t v; asm volatile("ld.acquire.gpu.global.u32 %0, [%1];" : "=r"(v) : "l"(p) : "memory"); return v; }
__device__ __forceinline__ void prefetch_map(const CUtensorMap* m) { asm volatile("prefetch.tensormap [%0];" :: "l"(m) : "memory"); }
__device__ __forceinline__ float rcp(float x) { float r; asm("rcp.approx.ftz.f32 %0, %1;" : "=f"(r) : "f"(x)); return r; }
__device__ __forceinline__ float ex2(float x) { float r; asm("ex2.approx.ftz.f32 %0, %1;" : "=f"(r) : "f"(x)); return r; }
__device__ __forceinline__ float tanh_fast(float x) { float r; asm("tanh.approx.f32 %0, %1;" : "=f"(r) : "f"(x)); return r; }
#define SPIN_GUARD(n) if (++(n) > (1u << 24)) bail()

__device__ __forceinline__ void wgmma_n128(float (&d)[64], uint64_t da, uint64_t db) {
  asm volatile("wgmma.mma_async.sync.aligned.m64n128k16.f32.bf16.bf16 "
    "{%0, %1, %2, %3, %4, %5, %6, %7, %8, %9, %10, %11, %12, %13, %14, %15, %16, %17, %18, %19, %20, %21, %22, %23, %24, %25, %26, %27, %28, %29, %30, %31, %32, %33, %34, %35, %36, %37, %38, %39, %40, %41, %42, %43, %44, %45, %46, %47, %48, %49, %50, %51, %52, %53, %54, %55, %56, %57, %58, %59, %60, %61, %62, %63}, "
    "%64, %65, 1, 1, 1, 0, 1;\n"
    : "+f"(d[0]), "+f"(d[1]), "+f"(d[2]), "+f"(d[3]), "+f"(d[4]), "+f"(d[5]), "+f"(d[6]), "+f"(d[7]), "+f"(d[8]), "+f"(d[9]), "+f"(d[10]), "+f"(d[11]), "+f"(d[12]), "+f"(d[13]), "+f"(d[14]), "+f"(d[15]), "+f"(d[16]), "+f"(d[17]), "+f"(d[18]), "+f"(d[19]), "+f"(d[20]), "+f"(d[21]), "+f"(d[22]), "+f"(d[23]), "+f"(d[24]), "+f"(d[25]), "+f"(d[26]), "+f"(d[27]), "+f"(d[28]), "+f"(d[29]), "+f"(d[30]), "+f"(d[31]), "+f"(d[32]), "+f"(d[33]), "+f"(d[34]), "+f"(d[35]), "+f"(d[36]), "+f"(d[37]), "+f"(d[38]), "+f"(d[39]), "+f"(d[40]), "+f"(d[41]), "+f"(d[42]), "+f"(d[43]), "+f"(d[44]), "+f"(d[45]), "+f"(d[46]), "+f"(d[47]), "+f"(d[48]), "+f"(d[49]), "+f"(d[50]), "+f"(d[51]), "+f"(d[52]), "+f"(d[53]), "+f"(d[54]), "+f"(d[55]), "+f"(d[56]), "+f"(d[57]), "+f"(d[58]), "+f"(d[59]), "+f"(d[60]), "+f"(d[61]), "+f"(d[62]), "+f"(d[63])
    : "l"(da), "l"(db));
}
__device__ __forceinline__ void wgmma_n128_first(float (&d)[64], uint64_t da, uint64_t db) {
  asm volatile("wgmma.mma_async.sync.aligned.m64n128k16.f32.bf16.bf16 "
    "{%0, %1, %2, %3, %4, %5, %6, %7, %8, %9, %10, %11, %12, %13, %14, %15, %16, %17, %18, %19, %20, %21, %22, %23, %24, %25, %26, %27, %28, %29, %30, %31, %32, %33, %34, %35, %36, %37, %38, %39, %40, %41, %42, %43, %44, %45, %46, %47, %48, %49, %50, %51, %52, %53, %54, %55, %56, %57, %58, %59, %60, %61, %62, %63}, "
    "%64, %65, 0, 1, 1, 0, 1;\n"
    : "=f"(d[0]), "=f"(d[1]), "=f"(d[2]), "=f"(d[3]), "=f"(d[4]), "=f"(d[5]), "=f"(d[6]), "=f"(d[7]), "=f"(d[8]), "=f"(d[9]), "=f"(d[10]), "=f"(d[11]), "=f"(d[12]), "=f"(d[13]), "=f"(d[14]), "=f"(d[15]), "=f"(d[16]), "=f"(d[17]), "=f"(d[18]), "=f"(d[19]), "=f"(d[20]), "=f"(d[21]), "=f"(d[22]), "=f"(d[23]), "=f"(d[24]), "=f"(d[25]), "=f"(d[26]), "=f"(d[27]), "=f"(d[28]), "=f"(d[29]), "=f"(d[30]), "=f"(d[31]), "=f"(d[32]), "=f"(d[33]), "=f"(d[34]), "=f"(d[35]), "=f"(d[36]), "=f"(d[37]), "=f"(d[38]), "=f"(d[39]), "=f"(d[40]), "=f"(d[41]), "=f"(d[42]), "=f"(d[43]), "=f"(d[44]), "=f"(d[45]), "=f"(d[46]), "=f"(d[47]), "=f"(d[48]), "=f"(d[49]), "=f"(d[50]), "=f"(d[51]), "=f"(d[52]), "=f"(d[53]), "=f"(d[54]), "=f"(d[55]), "=f"(d[56]), "=f"(d[57]), "=f"(d[58]), "=f"(d[59]), "=f"(d[60]), "=f"(d[61]), "=f"(d[62]), "=f"(d[63])
    : "l"(da), "l"(db));
}
__device__ __forceinline__ void wgmma_n256(float (&d)[128], uint64_t da, uint64_t db) {
  asm volatile("wgmma.mma_async.sync.aligned.m64n256k16.f32.bf16.bf16 "
    "{%0, %1, %2, %3, %4, %5, %6, %7, %8, %9, %10, %11, %12, %13, %14, %15, %16, %17, %18, %19, %20, %21, %22, %23, %24, %25, %26, %27, %28, %29, %30, %31, %32, %33, %34, %35, %36, %37, %38, %39, %40, %41, %42, %43, %44, %45, %46, %47, %48, %49, %50, %51, %52, %53, %54, %55, %56, %57, %58, %59, %60, %61, %62, %63, %64, %65, %66, %67, %68, %69, %70, %71, %72, %73, %74, %75, %76, %77, %78, %79, %80, %81, %82, %83, %84, %85, %86, %87, %88, %89, %90, %91, %92, %93, %94, %95, %96, %97, %98, %99, %100, %101, %102, %103, %104, %105, %106, %107, %108, %109, %110, %111, %112, %113, %114, %115, %116, %117, %118, %119, %120, %121, %122, %123, %124, %125, %126, %127}, "
    "%128, %129, 1, 1, 1, 0, 1;\n"
    : "+f"(d[0]), "+f"(d[1]), "+f"(d[2]), "+f"(d[3]), "+f"(d[4]), "+f"(d[5]), "+f"(d[6]), "+f"(d[7]), "+f"(d[8]), "+f"(d[9]), "+f"(d[10]), "+f"(d[11]), "+f"(d[12]), "+f"(d[13]), "+f"(d[14]), "+f"(d[15]), "+f"(d[16]), "+f"(d[17]), "+f"(d[18]), "+f"(d[19]), "+f"(d[20]), "+f"(d[21]), "+f"(d[22]), "+f"(d[23]), "+f"(d[24]), "+f"(d[25]), "+f"(d[26]), "+f"(d[27]), "+f"(d[28]), "+f"(d[29]), "+f"(d[30]), "+f"(d[31]), "+f"(d[32]), "+f"(d[33]), "+f"(d[34]), "+f"(d[35]), "+f"(d[36]), "+f"(d[37]), "+f"(d[38]), "+f"(d[39]), "+f"(d[40]), "+f"(d[41]), "+f"(d[42]), "+f"(d[43]), "+f"(d[44]), "+f"(d[45]), "+f"(d[46]), "+f"(d[47]), "+f"(d[48]), "+f"(d[49]), "+f"(d[50]), "+f"(d[51]), "+f"(d[52]), "+f"(d[53]), "+f"(d[54]), "+f"(d[55]), "+f"(d[56]), "+f"(d[57]), "+f"(d[58]), "+f"(d[59]), "+f"(d[60]), "+f"(d[61]), "+f"(d[62]), "+f"(d[63]), "+f"(d[64]), "+f"(d[65]), "+f"(d[66]), "+f"(d[67]), "+f"(d[68]), "+f"(d[69]), "+f"(d[70]), "+f"(d[71]), "+f"(d[72]), "+f"(d[73]), "+f"(d[74]), "+f"(d[75]), "+f"(d[76]), "+f"(d[77]), "+f"(d[78]), "+f"(d[79]), "+f"(d[80]), "+f"(d[81]), "+f"(d[82]), "+f"(d[83]), "+f"(d[84]), "+f"(d[85]), "+f"(d[86]), "+f"(d[87]), "+f"(d[88]), "+f"(d[89]), "+f"(d[90]), "+f"(d[91]), "+f"(d[92]), "+f"(d[93]), "+f"(d[94]), "+f"(d[95]), "+f"(d[96]), "+f"(d[97]), "+f"(d[98]), "+f"(d[99]), "+f"(d[100]), "+f"(d[101]), "+f"(d[102]), "+f"(d[103]), "+f"(d[104]), "+f"(d[105]), "+f"(d[106]), "+f"(d[107]), "+f"(d[108]), "+f"(d[109]), "+f"(d[110]), "+f"(d[111]), "+f"(d[112]), "+f"(d[113]), "+f"(d[114]), "+f"(d[115]), "+f"(d[116]), "+f"(d[117]), "+f"(d[118]), "+f"(d[119]), "+f"(d[120]), "+f"(d[121]), "+f"(d[122]), "+f"(d[123]), "+f"(d[124]), "+f"(d[125]), "+f"(d[126]), "+f"(d[127])
    : "l"(da), "l"(db));
}
__device__ __forceinline__ void wgmma_n256_first(float (&d)[128], uint64_t da, uint64_t db) {
  asm volatile("wgmma.mma_async.sync.aligned.m64n256k16.f32.bf16.bf16 "
    "{%0, %1, %2, %3, %4, %5, %6, %7, %8, %9, %10, %11, %12, %13, %14, %15, %16, %17, %18, %19, %20, %21, %22, %23, %24, %25, %26, %27, %28, %29, %30, %31, %32, %33, %34, %35, %36, %37, %38, %39, %40, %41, %42, %43, %44, %45, %46, %47, %48, %49, %50, %51, %52, %53, %54, %55, %56, %57, %58, %59, %60, %61, %62, %63, %64, %65, %66, %67, %68, %69, %70, %71, %72, %73, %74, %75, %76, %77, %78, %79, %80, %81, %82, %83, %84, %85, %86, %87, %88, %89, %90, %91, %92, %93, %94, %95, %96, %97, %98, %99, %100, %101, %102, %103, %104, %105, %106, %107, %108, %109, %110, %111, %112, %113, %114, %115, %116, %117, %118, %119, %120, %121, %122, %123, %124, %125, %126, %127}, "
    "%128, %129, 0, 1, 1, 0, 1;\n"
    : "=f"(d[0]), "=f"(d[1]), "=f"(d[2]), "=f"(d[3]), "=f"(d[4]), "=f"(d[5]), "=f"(d[6]), "=f"(d[7]), "=f"(d[8]), "=f"(d[9]), "=f"(d[10]), "=f"(d[11]), "=f"(d[12]), "=f"(d[13]), "=f"(d[14]), "=f"(d[15]), "=f"(d[16]), "=f"(d[17]), "=f"(d[18]), "=f"(d[19]), "=f"(d[20]), "=f"(d[21]), "=f"(d[22]), "=f"(d[23]), "=f"(d[24]), "=f"(d[25]), "=f"(d[26]), "=f"(d[27]), "=f"(d[28]), "=f"(d[29]), "=f"(d[30]), "=f"(d[31]), "=f"(d[32]), "=f"(d[33]), "=f"(d[34]), "=f"(d[35]), "=f"(d[36]), "=f"(d[37]), "=f"(d[38]), "=f"(d[39]), "=f"(d[40]), "=f"(d[41]), "=f"(d[42]), "=f"(d[43]), "=f"(d[44]), "=f"(d[45]), "=f"(d[46]), "=f"(d[47]), "=f"(d[48]), "=f"(d[49]), "=f"(d[50]), "=f"(d[51]), "=f"(d[52]), "=f"(d[53]), "=f"(d[54]), "=f"(d[55]), "=f"(d[56]), "=f"(d[57]), "=f"(d[58]), "=f"(d[59]), "=f"(d[60]), "=f"(d[61]), "=f"(d[62]), "=f"(d[63]), "=f"(d[64]), "=f"(d[65]), "=f"(d[66]), "=f"(d[67]), "=f"(d[68]), "=f"(d[69]), "=f"(d[70]), "=f"(d[71]), "=f"(d[72]), "=f"(d[73]), "=f"(d[74]), "=f"(d[75]), "=f"(d[76]), "=f"(d[77]), "=f"(d[78]), "=f"(d[79]), "=f"(d[80]), "=f"(d[81]), "=f"(d[82]), "=f"(d[83]), "=f"(d[84]), "=f"(d[85]), "=f"(d[86]), "=f"(d[87]), "=f"(d[88]), "=f"(d[89]), "=f"(d[90]), "=f"(d[91]), "=f"(d[92]), "=f"(d[93]), "=f"(d[94]), "=f"(d[95]), "=f"(d[96]), "=f"(d[97]), "=f"(d[98]), "=f"(d[99]), "=f"(d[100]), "=f"(d[101]), "=f"(d[102]), "=f"(d[103]), "=f"(d[104]), "=f"(d[105]), "=f"(d[106]), "=f"(d[107]), "=f"(d[108]), "=f"(d[109]), "=f"(d[110]), "=f"(d[111]), "=f"(d[112]), "=f"(d[113]), "=f"(d[114]), "=f"(d[115]), "=f"(d[116]), "=f"(d[117]), "=f"(d[118]), "=f"(d[119]), "=f"(d[120]), "=f"(d[121]), "=f"(d[122]), "=f"(d[123]), "=f"(d[124]), "=f"(d[125]), "=f"(d[126]), "=f"(d[127])
    : "l"(da), "l"(db));
}

template <int N> struct WG;
#define DEF_WG(N) template <> struct WG<N> { \
  static __device__ __forceinline__ void mma(float (&d)[N / 2], uint64_t a, uint64_t b) { wgmma_n##N(d, a, b); } \
  static __device__ __forceinline__ void first(float (&d)[N / 2], uint64_t a, uint64_t b) { wgmma_n##N##_first(d, a, b); } };
DEF_WG(128) DEF_WG(256)

constexpr uint64_t DESC_A = (1ull << 62) | ((uint64_t)(1024 >> 4) << 32) | (1ull << 16);
constexpr uint64_t DESC_B = (1ull << 62) | ((uint64_t)(1024 >> 4) << 32) | ((uint64_t)(8192 >> 4) << 16);

struct Ring { int s; uint32_t ph; int wrap; };
template <int NS> __device__ __forceinline__ void ring_next(Ring& r) { r.s = (r.s + 1 == NS) ? 0 : r.s + 1; if (r.s == r.wrap) r.ph ^= 1; }

__device__ __forceinline__ int own_order(int it, int j) {
  return it < 2 ? 2 * j + it : it < 4 ? 2 * (j ^ 1) + it - 2 : ((j >> 1) * 4 + 2 * it - (it < 10 ? 4 : 15)) & 15;
}

template <int V> struct IC { static constexpr int v = V; };
template <int I, int E, class F> __device__ __forceinline__ void static_for(F&& f) { if constexpr (I < E) { f(IC<I>{}); static_for<I + 1, E>(f); } }

template <int N, int NS, int PRE, int LAG, class Pre, class Mid, class Last>
__device__ __forceinline__ void mainloop(float (&acc)[N / 2], int nkb, bool own, Ring& r, uint32_t sb, int wg, int lane, uint32_t rel_base, Pre pre, Mid mid, Last last, int lag_par = 0) {
  constexpr int SLOT = RING / NS;
  const uint32_t full = sb + MISC + (NS == 4 ? B_FULL4 : B_FULL6);
  const uint32_t rel = rel_base + (NS == 4 ? B_EMPTY4 : B_EMPTY6);
  const uint32_t s0 = (sb & 0x3FFFF) >> 4, a0 = s0 + wg * (HALF >> 4);
  int ps;
  auto issue = [&](int it, bool first) {
    const uint64_t da = DESC_A | (a0 + ((own && it < 2) ? (STG + it * BLK) >> 4 : r.s * (SLOT >> 4))), db = DESC_B | (s0 + r.s * (SLOT >> 4) + (BLK >> 4));
    mbar_wait(full + r.s * 8, r.ph);
    wg_arrive();
    if (first) WG<N>::first(acc, da, db); else WG<N>::mma(acc, da, db);
#pragma unroll
    for (int k = 1; k < 4; k++) WG<N>::mma(acc, da + k * 2, db + k * 128);
    wg_commit();
  };
  auto retire = [&](int it) {
    wg_wait<1>();
    if (lane < 2) mbar_arrive_cl(rel + ps * 8);
    ps = r.s;
    ring_next<NS>(r);
  };
  issue(0, true);
  ps = r.s;
  ring_next<NS>(r);
  static_for<1, PRE + 1>([&](auto ic) { issue(ic.v, false); pre(ic); retire(ic.v); });
#pragma unroll 1
  for (int it = PRE + 1; it < nkb; it++) {
    if (LAG && it == nkb - LAG && wg == 1) mbar_wait(sb + MISC + B_LAG, lag_par);
    issue(it, false); mid(it);
    if (LAG > 1 && it > nkb - NS) ring_next<NS>(r); else retire(it);
  }
  if (LAG && wg == 0 && lane == 0) mbar_arrive(sb + MISC + B_LAG);
  last();
  wg_wait<0>();
#pragma unroll
  for (int i = 0; i < N / 2; i++) asm volatile("" : "+f"(acc[i]) :: "memory");
  if (LAG <= 1 && lane < 2) mbar_arrive_cl(rel + ps * 8);
}

__device__ __forceinline__ uint32_t tag_of(uint32_t ep) { return (ep & 127u) + 1u; }
__device__ __forceinline__ void ln_publish(const float (&v)[64], uint2* st, int j, int row0, int lane, uint32_t ep) {
  float s0 = 0, s1 = 0, s2 = 0, s3 = 0, q0 = 0, q1 = 0, q2 = 0, q3 = 0;
#pragma unroll
  for (int i = 0; i < 16; i++) {
    s0 += v[4 * i]; s1 += v[4 * i + 1]; s2 += v[4 * i + 2]; s3 += v[4 * i + 3];
    q0 = fmaf(v[4 * i], v[4 * i], q0); q1 = fmaf(v[4 * i + 1], v[4 * i + 1], q1); q2 = fmaf(v[4 * i + 2], v[4 * i + 2], q2); q3 = fmaf(v[4 * i + 3], v[4 * i + 3], q3);
  }
  s0 += s1; s2 += s3; q0 += q1; q2 += q3;
  const bool odd = lane & 1;
  float s = (odd ? s2 : s0) + __shfl_xor_sync(~0u, odd ? s0 : s2, 1), q = (odd ? q2 : q0) + __shfl_xor_sync(~0u, odd ? q0 : q2, 1);
  s += __shfl_xor_sync(~0u, s, 2); q += __shfl_xor_sync(~0u, q, 2);
  if ((lane & 3) < 2) st_rlx2(st + j * 128 + row0 + (lane & 1) * 8, __float_as_uint(s), (__float_as_uint(fmaf(s * (-1.f / 128), s, q)) & ~255u) | tag_of(ep));
}
__device__ __forceinline__ void ln_gather(const uint2* st, int row0, int lane, uint32_t ep, float& n0, float& r0, float& n1, float& r1, bool rnd) {
  const uint2* p = st + (lane & 2) * 256 + row0 + (lane & 1) * 8;
  const uint32_t tag = tag_of(ep);
  uint2 a, b, c, d; uint32_t n = 0;
  while (true) {
    a = ld_rlx2(p); b = ld_rlx2(p + 128); c = ld_rlx2(p + 256); d = ld_rlx2(p + 384);
    if ((((a.y ^ tag) | (b.y ^ tag) | (c.y ^ tag) | (d.y ^ tag)) & 255u) == 0) break;
    SPIN_GUARD(n);
  }
  __syncwarp();
  const uint32_t fix = tag ^ 128u;
  float s = (__uint_as_float(a.x) + __uint_as_float(b.x)) + (__uint_as_float(c.x) + __uint_as_float(d.x));
  float q = (__uint_as_float(a.y ^ fix) + __uint_as_float(b.y ^ fix)) + (__uint_as_float(c.y ^ fix) + __uint_as_float(d.y ^ fix));
  q = fmaf(fmaf(__uint_as_float(a.x), __uint_as_float(a.x), __uint_as_float(b.x) * __uint_as_float(b.x)) +
           fmaf(__uint_as_float(c.x), __uint_as_float(c.x), __uint_as_float(d.x) * __uint_as_float(d.x)), 1.f / 128, q);
  s += __shfl_xor_sync(~0u, s, 2); q += __shfl_xor_sync(~0u, q, 2);
  s *= 1.f / 1024;
  const float var = fmaxf(fmaf(-s, s, q * (1.f / 1024)), 0.f);
  float r;
  if (rnd) {
    float sd; asm("sqrt.approx.f32 %0, %1;" : "=f"(sd) : "f"(bf_round(bf_round(var) + 1e-5f)));
    r = rcp(bf_round(sd)); s = bf_round(s);
  } else r = rsqrtf(var + 1e-5f);
  const float nn = -s * r;
  const float ro = __shfl_xor_sync(~0u, r, 1), no = __shfl_xor_sync(~0u, nn, 1);
  const bool odd = lane & 1;
  r0 = odd ? ro : r; n0 = odd ? no : nn; r1 = odd ? r : ro; n1 = odd ? nn : no;
}
__device__ __forceinline__ void load_vec(uint32_t* w, uint32_t sb, int sec, int b, int lane) {
#pragma unroll
  for (int q = 0; q < 2; q++) { uint4 t = lds128(sb + MISC + MODV + sec * 256 + (lane & 3) * 64 + b * 32 + q * 16); w[4 * q] = t.x; w[4 * q + 1] = t.y; w[4 * q + 2] = t.z; w[4 * q + 3] = t.w; }
}
__device__ __forceinline__ void stage_done(uint32_t sb, int wg, int b, int lane) {
  fence_async_smem();
  __syncwarp();
  if (lane == 0) mbar_arrive(sb + MISC + B_RDY + b * 8);
}
__device__ __forceinline__ uint32_t hfma2(uint32_t a, uint32_t b, uint32_t c) { uint32_t r; asm("fma.rn.bf16x2 %0, %1, %2, %3;" : "=r"(r) : "r"(a), "r"(b), "r"(c)); return r; }
__device__ __forceinline__ void ln_apply(const float (&v)[64], const uint2* st, int row0, uint32_t ep, uint32_t sb, int sec_shift, int sec_scale, uint32_t stg_row, int wg, int lane) {
  uint32_t sc[16], sh[16];
#pragma unroll
  for (int b = 0; b < 2; b++) { load_vec(sc + 8 * b, sb, sec_scale, b, lane); load_vec(sh + 8 * b, sb, sec_shift, b, lane); }
  float n0, r0, n1, r1;
  ln_gather(st, row0, lane, ep, n0, r0, n1, r1, sec_shift == 0);
#pragma unroll
  for (int i = 0; i < 16; i += 2) {
    if (i == 8) { const float z = lds32f(sb + MISC + ZERO); n0 += z; n1 += z; }
    uint32_t w[4];
#pragma unroll
    for (int u = 0; u < 2; u++) {
      int q = i + u;
      w[2 * u] = hfma2(pack2(fmaf(v[4 * q], r0, n0), fmaf(v[4 * q + 1], r0, n0)), sc[q], sh[q]);
      w[2 * u + 1] = hfma2(pack2(fmaf(v[4 * q + 2], r1, n1), fmaf(v[4 * q + 3], r1, n1)), sc[q], sh[q]);
    }
    stsm4(stg_row + (i >> 3) * BLK + ((((i & 7) + (lane >> 4)) ^ (lane & 7)) << 4), w[0], w[1], w[2], w[3]);
    if ((i & 7) == 6) { stage_done(sb, wg, i >> 3, lane); }
  }
}
__device__ __forceinline__ uint32_t hmul2(uint32_t a, uint32_t b) { uint32_t r; asm("mul.rn.bf16x2 %0, %1, %2;" : "=r"(r) : "r"(a), "r"(b)); return r; }
__device__ __forceinline__ uint32_t silu_mul2(uint32_t g, uint32_t u) {
  const uint32_t h = hmul2(g, 0x3f003f00u);
  const float h0 = bf_lo(h), h1 = bf_hi(h);
  return hmul2(pack2(fmaf(h0, tanh_fast(h0), h0), fmaf(h1, tanh_fast(h1), h1)), u);
}

__device__ __forceinline__ void gemv_fma(float (&a)[8], uint4 w, float s) {
  a[0] = fmaf(bf_lo(w.x), s, a[0]); a[1] = fmaf(bf_hi(w.x), s, a[1]); a[2] = fmaf(bf_lo(w.y), s, a[2]); a[3] = fmaf(bf_hi(w.y), s, a[3]);
  a[4] = fmaf(bf_lo(w.z), s, a[4]); a[5] = fmaf(bf_hi(w.z), s, a[5]); a[6] = fmaf(bf_lo(w.w), s, a[6]); a[7] = fmaf(bf_hi(w.w), s, a[7]);
}
__device__ __forceinline__ float silu_c(float v) { return bf_round(__fdividef(v, 1.f + __expf(-v))); }
__device__ __forceinline__ float mod_gather(const uint32_t* p, uint32_t ep) {
  const uint32_t tag = tag_of(ep), fix = tag ^ 128u;
  uint32_t a, b, c, d, n = 0;
  while (true) {
    a = ld_rlx1(p); b = ld_rlx1(p + 2048); c = ld_rlx1(p + 4096); d = ld_rlx1(p + 6144);
    if ((((a ^ tag) | (b ^ tag) | (c ^ tag) | (d ^ tag)) & 255u) == 0) break;
    SPIN_GUARD(n);
  }
  return (__uint_as_float(a ^ fix) + __uint_as_float(b ^ fix)) + (__uint_as_float(c ^ fix) + __uint_as_float(d ^ fix));
}
__device__ __forceinline__ void mod_store(uint32_t sb, int sec, int col, float v) {
  v = bf_round(v);
  if (sec == 1) v += 1.f;
  sts16(sb + MISC + MODV + sec * 256 + (((col >> 1) & 3) * 16 + (col >> 3)) * 4 + (col & 1) * 2, __float2bfloat16_rn(v));
}

__global__ void __cluster_dims__(2, 1, 1) __launch_bounds__(384, 1)
fused_kernel(const bf16* __restrict__ cvec, const bf16* __restrict__ wmod, Scratch* gs, int by_sm, const __grid_constant__ Maps maps) {
  extern __shared__ __align__(1024) uint8_t smem_raw[];
  uint32_t sm; asm volatile("mov.u32 %0, %%smid;" : "=r"(sm));
  const uint32_t id = by_sm ? sm : blockIdx.x, xs = by_sm ? 112 + 8 * by_sm : 0, u = id < xs ? id : id - 4;
  const bool extra = id - xs < 4;
  uint4 wv[8];
  uint32_t ep0; uint16_t cv_;
  if (threadIdx.x < 256) {
    const int r0 = ((u >> 5) & 3) * 256 + (threadIdx.x & 224);
    asm volatile("ld.global.nc.u16 %0, [%1];" : "=h"(cv_) : "l"(cvec + r0 + (threadIdx.x & 31)));
    asm volatile("ld.global.u32 %0, [%1];" : "=r"(ep0) : "l"(gs->epoch + (blockIdx.x | (threadIdx.x & by_sm & 4))));
    if (!extra) {
      const bf16* wp = wmod + (r0 + ((threadIdx.x >> 3) & 3)) * 6144 + (u & 31) * 64 + (threadIdx.x & 7) * 8;
#pragma unroll
      for (int i = 0; i < 8; i++) wv[i] = ldg_nc(wp + i * 4 * 6144);
    }
  }
  const uint32_t sb = smem_u32(smem_raw);
  const int warp = __shfl_sync(~0u, threadIdx.x >> 5, 0), lane = threadIdx.x & 31;
  const int rank = blockIdx.x & 1;
  const int t = sm >> 1, v = t < 32 || by_sm == 2 ? t : t < 60 ? t + 1 + (((t - 32) * 37) >> 8) : (t - 58) * 8;
  const int gr = 0x71546320u >> ((v & 7) * 4);
  const int cid = !by_sm ? (blockIdx.x >> 1) - 2 : extra ? (t & 1) - 2 : (gr & 4) * 8 + (v >> 3) * 4 + (gr & 3);
  const int bid = cid * 2 + rank;
  const int m = cid >> 2, j = (cid & 3) * 2 + rank;
  const uint32_t bar = sb + MISC;

  if (warp >= 8) {
    asm volatile("setmaxnreg.dec.sync.aligned.u32 40;");
    if (extra) {
      if (warp == 8) {
        if (lane == 0) { for (int s = 0; s < 6; s++) { mbar_init(bar + B_FULL6 + s * 8, 1); mbar_init(bar + B_EMPTY6 + s * 8, 8); } fence_async_smem(); }
        __syncwarp();
        asm volatile("bar.arrive 2, 288;" ::: "memory");
        __nanosleep(XSLEEP);
#pragma unroll 1
        for (int it = 0, s = 0, par = 1; it < 64; it++) {
          mbar_wait(bar + B_EMPTY6 + s * 8, par);
          expect_e(bar + B_FULL6 + s * 8, 32768); tma_3d_e(sb + s * 32768, &maps.wmod, bar + B_FULL6 + s * 8, 0, (it & 15) * 64, 12 + (it >> 4) * 4 + bid);
          if (++s == 6) { s = 0; par ^= 1; }
        }
      }
    } else if (warp < 10) {
      uint32_t f6 = bar + B_FULL6, d6 = sb + (warp == 8 ? BLK : rank * HALF), p6 = 1;
      auto next6 = [&]() { f6 += 8; d6 += 32768; if (f6 == bar + B_FULL6 + 48) { f6 -= 48; d6 -= RING; p6 ^= 1; } };
      auto drained4 = [&](int q, int late) { if (q < 5) mbar_wait(bar + B_EMPTY4 + (((late ? 0x10332 : 0x32110) >> (4 * q)) & 3) * 8, 1); };
      auto drained6 = [&](int q) { if (q < 3) mbar_wait(bar + B_EMPTY6 + ((0x154 >> (4 * q)) & 7) * 8, q >> 1); };
      auto skip6 = [&]() { mbar_wait(f6 + 48, p6); expect_e(f6, 0); next6(); };
      if (warp == 8) {
        if (lane == 0) {
          if (sb & 1023) bail();
          for (int b = 0; b < 2; b++) mbar_init(bar + B_X + b * 8, 1);
          for (int s = 0; s < 4; s++) { mbar_init(bar + B_FULL4 + s * 8, 2); mbar_init(bar + B_EMPTY4 + s * 8, 16); }
          for (int s = 0; s < 6; s++) { mbar_init(bar + B_FULL6 + s * 8, 2); mbar_init(bar + B_EMPTY6 + s * 8, 16); }
          for (int b = 0; b < 2; b++) { mbar_init(bar + B_RDY + b * 8, 8); mbar_init(bar + B_FREE + b * 8, 1); mbar_init(bar + B_HH + b * 8, 1); mbar_init(bar + B_OUT + b * 8, 2); mbar_init(bar + B_HALO + b * 8, 1); }
          mbar_init(bar + B_MOD, 1); mbar_init(bar + B_LAG, 4); mbar_init(bar + B_ALL, 1); mbar_init(bar + B_HH2, 1);
          asm volatile("st.shared.u32 [%0], 0;" :: "r"(bar + ZERO) : "memory");
          asm volatile("fence.mbarrier_init.release.cluster;" ::: "memory");
          fence_async_smem();
        }
        __syncwarp();
        cl_arrive_relaxed();
        for (int b = 0; b < 2; b++) { expect_e(bar + B_X + b * 8, BLK); tma_3d_e(sb + STG + b * BLK, &maps.x, bar + B_X + b * 8, j * 128 + b * 64, m * 64, 0); }
        mbar_wait(bar + B_X + 8, 0);
#pragma unroll 1
        for (int ph = 0; ph < 2; ph++) {
          const CUtensorMap* const m0 = ph ? &maps.w1 : &maps.wqkv;
#pragma unroll 1
          for (int it = 0; it < (ph ? 48 : 16); it++) {
            const int s = (it + 2 * ph) & 3;
            int a0 = (ph ? it & 48 : 16) + 2 * j, a1 = ph ? a0 : a0 + 16, k0 = (it < 16 ? own_order(it, j) : it & 15) * 64;
            uint32_t full = bar + B_FULL4 + s * 8, d = sb + s * 49152 + BLK;
            if (ph) drained6(it);
            mbar_wait(full + 32, ~(it >> 2) & 1);
            tma_3d_e(d, m0, full, 0, k0, a0);
            if (it < 4) { const uint32_t t0 = clock(); while ((uint32_t)clock() - t0 < GAP) {} }
            tma_3d_e(d + BLK, m0 + ph, full, 0, k0, a1);
            expect_e(full, 2 * BLK);
            if (it < 4) { const uint32_t t0 = clock(); while ((uint32_t)clock() - t0 < GAP) {} }
            if (it >= 44) {
              if (it == 44) { mbar_wait(bar + B_FREE, 0); mbar_wait(bar + B_FREE + 8, 0); expect_e(bar + B_X, 2 * BLK); }
              bulk_ld_e(sb + STG + (it - 44) * HALF, gs->x1 + bid * 2048 + (it - 44) * 512, HALF, bar + B_X);
            }
          }
          const CUtensorMap* const m1 = ph ? &maps.w1s : &maps.wqkv;
          const int a = ph ? 48 + j : 2 * j;
#pragma unroll 1
          for (int k0 = 0; k0 < 1024; k0 += 64) {
            drained4(k0 >> 6, ph);
            mbar_wait(f6 + 48, p6);
            tma_3d_e(d6, m1, f6, 0, k0, a);
            if (ph) tma_3d_e(d6 + HALF, &maps.w3s, f6, 0, k0, a);
            expect_e(f6, BLK);
            next6();
          }
          if (ph) break;
#pragma unroll 1
          for (int it = 0; it < 16; it++) {
            const int k0 = own_order(it, j) * 64;
            mbar_wait(f6 + 48, p6);
            tma_3d_e(d6, &maps.wo, f6, 0, k0, 2 * j);
            expect_e(f6, BLK);
            next6();
          }
          skip6();
        }
#pragma unroll 1
        for (int k0 = 0; k0 < F_; k0 += 64) {
          mbar_wait(f6 + 48, p6);
          tma_3d_e(d6, &maps.w2, f6, 0, k0, 2 * j);
          expect_e(f6, BLK);
          next6();
        }
      } else {
        if (lane < 9) prefetch_map(&maps.x + lane);
        const uint32_t ep = gs->epoch[blockIdx.x] + 1;
        cl_arrive_relaxed(); cl_wait();
        auto run6 = [&](const uint4* src, int n, int sw) {
          src += rank * 512;
#pragma unroll 1
          for (int it = 0; it < n; it++) {
            if (sw >= 0) drained4(it, sw);
            mbar_wait(f6 + 48, p6);
            bulk_ld_mc_e(d6, src, HALF, f6);
            expect_e(f6, BLK);
            next6();
            src += 1024;
          }
        };
        uint32_t ready = 0;
        auto need = [&](int e, uint32_t mask) {
          if (!(ready & mask)) {
            uint32_t n = 0;
            do { ready = __ballot_sync(~0u, ld_acquire(gs->flag + (m * 128 + e * 16 + (lane & 14)) * FS) == ep); SPIN_GUARD(n); } while (!(ready & mask));
            fence_async_global();
          }
        };
        auto fresh = [&](int e, int it, uint32_t full, uint32_t empty, int par, uint32_t slot, uint4* src) {
          mbar_wait(empty, par);
          expect_e(full, it < 2 ? 0 : BLK);
          if (it >= 4) {
            const int kb = own_order(it, j);
            if (it < 10) need(e, 1u << kb); else if (it == 10) mbar_wait(bar + B_ALL, e & 1);
            bulk_ld_mc_e(slot + rank * HALF, src + kb * 1024 + rank * 512, HALF, full);
          } else if (it >= 2) {
            const int b = it > 2;
            const uint32_t to_peer = mapa(sb, rank ^ 1) - sb;
            const bool push = b && e != 1;
            mbar_wait(bar + (push ? B_RDY : B_FREE) + b * 8, e & 1);
            if (push) bulk_push_e(slot + to_peer, sb + STG + BLK, BLK, full + to_peer);
            else { fence_async_global(); bulk_ld_e(slot + to_peer, src + (2 * j + b) * 1024, BLK, full + to_peer); }
          } else ready = 0;
        };
        uint4* const h = gs->h + m * 16384;
#pragma unroll 1
        for (int e = 0; e < 3; e++) {
#pragma unroll 1
          for (int it = 0; it < 16; it++) {
            const int s = (it + e) & 3;
            const uint32_t full = e == 1 ? f6 : bar + B_FULL4 + s * 8;
            if (e == 2) drained6(it);
            fresh(e, it, full, full + (e == 1 ? 48 : 32), e == 1 ? p6 : ~(it >> 2) & 1, e == 1 ? d6 - rank * HALF : sb + s * 49152, e == 1 ? gs->o + m * 16384 : h);
            if (e == 1) next6();
          }
          if (e == 1) { skip6(); continue; }
#pragma unroll 1
          for (int it = 16; it < 16 + 16 * e; it++) {
            const int s = (it + 2) & 3;
            const uint32_t full = bar + B_FULL4 + s * 8;
            mbar_wait(full + 32, ~(it >> 2) & 1);
            bulk_ld_mc_e(sb + s * 49152 + rank * HALF, h + (it & 15) * 1024 + rank * 512, HALF, full);
            expect_e(full, BLK);
          }
          run6(h, 16, e);
        }
#pragma unroll 1
        for (int q = 0; q < 3; q++) {
          mbar_wait(bar + (q == 2 ? B_HH2 : B_HH + q * 8), 0);
          run6(gs->hh + m * 57344 + (64 - (64 >> q)) * 1024, 32 >> q, -1);
        }
      }
    } else {
      const int b = warp - 10;
      const uint32_t ep = gs->epoch[blockIdx.x] + 1;
      const uint32_t stg = sb + STG + b * BLK;
      cl_arrive_relaxed(); cl_wait();
      auto all_there = [&](int u, uint32_t done) {
        const uint32_t* fl = gs->flag + u * FS;
        uint32_t n = 0;
        while (!__all_sync(~0u, ld_acquire(fl) == ep)) { __nanosleep(100); SPIN_GUARD(n); }
        fence_async_global();
        arrive_e(done);
      };
#pragma unroll 1
      for (int e = 0; e < 7 - b; e++) {
        const int kb = (e < 3 ? 2 * j : e < 6 ? 2 * (8 * (e - 3) + j) : 48 + j) + b;
        uint4* const dst = (e == 1 ? gs->o + m * 16384 : e < 3 ? gs->h + m * 16384 : gs->hh + m * 57344) + kb * 1024;
        uint32_t* const fl = gs->flag + (m * 128 + (e < 3 ? e * 16 : U_HH) + kb) * FS;
        if (e < 3 && lane < 8) st_rlx1(fl + lane, 0);
        if (b && e < 3) {
          mbar_wait(bar + B_FREE, e & 1);
          const uint32_t t0 = clock();
          while ((uint32_t)clock() - t0 < (e == 1 ? B1D : B1P)) {}
        }
        mbar_wait(bar + B_RDY + b * 8, e & 1);
        bulk_st_e(dst, stg, e < 3 ? BLK : BLK / NPIECE);
        if (e >= 3) {
#pragma unroll 1
          for (int q = 1; q < NPIECE; q++) { __nanosleep(PSLEEP); bulk_st_e(dst + q * (1024 / NPIECE), stg + q * (BLK / NPIECE), BLK / NPIECE); }
        }
        publish_e(bar + B_FREE + b * 8, fl, ep);
        if (b && (e < 3 || e == 4)) all_there(m * 128 + (e < 3 ? e * 16 + (lane & 15) : U_HH + lane), bar + (e < 3 ? B_ALL : B_HH));
        if (!b && (e == 1 || e == 2)) {
#pragma unroll 1
          for (int sec = e == 1 ? 2 : 5; sec < 4 + e; sec++) {
            const uint4* p = (const uint4*)(gs->modv + (sec - 2) * 1024 + j * 128) + lane;
            uint4 v0, v1; uint32_t n = 0;
            while (true) {
              v0 = ld_rlx4(p); v1 = ld_rlx4(p + 32);
              if (__all_sync(~0u, v0.y == ep && v0.w == ep && v1.y == ep && v1.w == ep)) break;
              SPIN_GUARD(n);
            }
            const uint32_t d = sb + MISC + MODV + sec * 256 + ((lane & 3) * 16 + (lane >> 2)) * 4;
            asm volatile("st.shared.u32 [%0], %1;" :: "r"(d), "r"(__byte_perm(v0.x, v0.z, 0x7632)) : "memory");
            asm volatile("st.shared.u32 [%0], %1;" :: "r"(d + 32), "r"(__byte_perm(v1.x, v1.z, 0x7632)) : "memory");
          }
          __syncwarp();
          if (e == 1) { arrive_e(bar + B_MOD); }
        }
        if (e == 0) {
          uint32_t* const hf = gs->flag + (m * 128 + 48 + 2 * j + b) * FS;
          uint4* const hp = gs->halo + ((m * 8 + j) * 2 + b) * 256;
          if (m < 15 && lane < 8) st_rlx1(hf + 128 * FS + lane, 0);
          mbar_wait(bar + B_OUT + b * 8, 0);
          if (m < 15) {
            for (int w = 0; w < 2; w++) bulk_st_e(hp + 4096 + w * 128, stg + w * HALF, 2048);
            publish_e(bar + B_OUT + b * 8, hf + 128 * FS, ep);
          }
          if (m > 0) {
            uint32_t n = 0;
            while (!__all_sync(~0u, ld_acquire(hf) == ep)) SPIN_GUARD(n);
            fence_async_global();
            for (int w = 0; w < 2; w++) bulk_ld_e(stg + w * HALF, hp + w * 128, 2048, bar + B_HALO + b * 8);
            expect_e(bar + B_HALO + b * 8, 4096);
          } else {
            __syncwarp();
#pragma unroll
            for (int i = 0; i < 8; i++) sts128(stg + (i >> 2) * HALF + (i & 3) * 512 + lane * 16, 0, 0, 0, 0);
            __syncwarp();
            arrive_e(bar + B_HALO + b * 8);
          }
        }
      }
      if (b) {
#pragma unroll 1
        for (int q = 0; q < 2; q++) all_there(m * 128 + U_HH + 32 + q * 16 + (lane & (15 >> q)), bar + (q ? B_HH2 : B_HH + 8));
      }
    }
  } else {
    const int wg = warp >> 2, wq = warp & 3, tid = threadIdx.x;
    const int g = lane >> 2, c = lane & 3;
    if (!extra) cl_arrive_relaxed();
    asm volatile("setmaxnreg.inc.sync.aligned.u32 232;" ::: "memory");
    if (__builtin_expect(extra, 0)) {
      const uint32_t ep = ep0 + 1;
      float sv[4];
#pragma unroll
      for (int p = 0; p < 4; p++) sv[p] = silu_c(__bfloat162float(cvec[64 * (4 * p + (lane >> 3)) + 8 * warp + (lane & 7)]));
      named_bar(2, 288);
      int s = 0, par = 0;
#pragma unroll 1
      for (int sec = 0; sec < 4; sec++) {
        float a[8] = {0, 0, 0, 0, 0, 0, 0, 0};
#pragma unroll 1
        for (int it = 0; it < 16; it++) {
          const float sc = it < 4 ? sv[0] : it < 8 ? sv[1] : it < 12 ? sv[2] : sv[3];
          mbar_wait(bar + B_FULL6 + s * 8, par);
          uint4 w[8];
#pragma unroll
          for (int i = 0; i < 8; i++) w[i] = lds128(sb + s * 32768 + (warp * 8 + i) * 512 + lane * 16);
#pragma unroll
          for (int i = 0; i < 8; i++) gemv_fma(a, w[i], __shfl_sync(~0u, sc, (it & 3) * 8 + i));
          if (lane == 0) mbar_arrive(bar + B_EMPTY6 + s * 8);
          if (++s == 6) { s = 0; par ^= 1; }
        }
        const uint32_t red = sb + STG + sec * 8192;
        sts128(red + warp * 1024 + lane * 32, __float_as_uint(a[0]), __float_as_uint(a[1]), __float_as_uint(a[2]), __float_as_uint(a[3]));
        sts128(red + warp * 1024 + lane * 32 + 16, __float_as_uint(a[4]), __float_as_uint(a[5]), __float_as_uint(a[6]), __float_as_uint(a[7]));
        named_bar(1, 256);
        float t = 0;
#pragma unroll
        for (int q = 0; q < 8; q++) t += lds32f(red + q * 1024 + tid * 4);
        t = bf_round(t);
        if (sec == 2) t = bf_round(t + 1.f);
        st_rlx2(gs->modv + sec * 1024 + (bid + 4) * 256 + tid, __float_as_uint(t), ep);
      }
      if (tid == 0) gs->epoch[blockIdx.x] = ep;
      return;
    }
    const int row0 = wg * 64 + wq * 16 + g;
    if (c < 2) st_rlx2(gs->stat + m * 1024 + j * 128 + row0 + c * 8, 0, 0);
    cl_wait();
    uint32_t ep;
    asm volatile("add.u32 %0, %1, 1;" : "=r"(ep) : "r"(ep0) : "memory");
    const float sc_ = silu_c(__uint_as_float((uint32_t)cv_ << 16));
    const uint32_t rel = mapa(bar, (lane & 1) ^ rank);
    const uint32_t stg_row = sb + STG + (wg * 64 + wq * 16 + (lane & 15)) * 128;
    const uint32_t fre = bar + B_FREE;
    Ring r4{0, 0, 0}, r6{0, 0, 0};
    auto none = [](auto) {};
    uint32_t xk[32];
    {
      float a[8] = {0, 0, 0, 0, 0, 0, 0, 0};
#pragma unroll
      for (int i = 0; i < 8; i++) gemv_fma(a, wv[i], __shfl_sync(~0u, sc_, i * 4 + (lane >> 3)));
#pragma unroll
      for (int i = 0; i < 8; i++) { a[i] += __shfl_xor_sync(~0u, a[i], 8); a[i] += __shfl_xor_sync(~0u, a[i], 16); }
      if (lane < 8) {
        sts128(sb + RED_OFF + warp * 256 + lane * 32, __float_as_uint(a[0]), __float_as_uint(a[1]), __float_as_uint(a[2]), __float_as_uint(a[3]));
        sts128(sb + RED_OFF + warp * 256 + lane * 32 + 16, __float_as_uint(a[4]), __float_as_uint(a[5]), __float_as_uint(a[6]), __float_as_uint(a[7]));
      }
      named_bar(1, 256);
      if (tid < 64) {
        float s = 0;
#pragma unroll
        for (int w = 0; w < 8; w++) s += lds32f(sb + RED_OFF + w * 256 + tid * 4);
        st_rlx1(gs->modp + u * 64 + tid, (__float_as_uint(s) & ~255u) | tag_of(ep));
      }
      float v[64];
      mbar_wait(bar + B_X, 0); mbar_wait(bar + B_X + 8, 0);
#pragma unroll
      for (int i = 0; i < 16; i += 2) {
        uint32_t w0, w1, w2, w3;
        ldsm4(stg_row + (i >> 3) * BLK + ((((i & 7) + (lane >> 4)) ^ (lane & 7)) << 4), w0, w1, w2, w3);
        xk[2 * i] = w0; xk[2 * i + 1] = w1; xk[2 * i + 2] = w2; xk[2 * i + 3] = w3;
        v[4 * i] = bf_lo(w0); v[4 * i + 1] = bf_hi(w0); v[4 * i + 2] = bf_lo(w1); v[4 * i + 3] = bf_hi(w1);
        v[4 * i + 4] = bf_lo(w2); v[4 * i + 5] = bf_hi(w2); v[4 * i + 6] = bf_lo(w3); v[4 * i + 7] = bf_hi(w3);
      }
      ln_publish(v, gs->stat + m * 1024, j, row0, lane, ep);
      mod_store(sb, tid >> 7, tid & 127, mod_gather(gs->modp + (tid >> 7) * 1024 + j * 128 + (tid & 127), ep));
      named_bar(1, 256);
      ln_apply(v, gs->stat + m * 1024, row0, ep, sb, 0, 1, stg_row, wg, lane);
      named_bar(1, 256);
    }
    {
      uint32_t kf[32], vf[32], pv[32];
      const bool first = wq == 0 && m == 0;
      const uint32_t xa = sb + STG + wg * HALF + wq * 2048 + lane * 16;
      {
        float acc[128];
        mainloop<256, 4, 0, 0>(acc, 16, true, r4, sb, wg, lane, rel, none, none, [&] {
          mbar_wait(fre + 8, 0);
          if (c < 2) st_rlx2(gs->stat + (16 + m) * 1024 + j * 128 + row0 + c * 8, 0, 0);
        });
#pragma unroll
        for (int i = 0; i < 32; i++) { kf[i] = pack2(acc[2 * i], acc[2 * i + 1]); vf[i] = pack2(acc[64 + 2 * i], acc[65 + 2 * i]); }
      }
      float acc[64];
      constexpr int QP = 2;
      auto inbox = [&](const int b) {
        if (wq == 0) mbar_wait(bar + B_HALO + b * 8, 0);
#pragma unroll
        for (int i = 4 * b; i < 4 * b + 4; i++) {
          uint4 q = lds128(xa + b * BLK + (i & 3) * 512);
          pv[4 * i] = q.x; pv[4 * i + 1] = q.y; pv[4 * i + 2] = q.z; pv[4 * i + 3] = q.w;
        }
        __syncwarp();
      };
      auto sent = [&](int b) { if (wq == 3) { fence_async_smem(); __syncwarp(); if (lane == 0) mbar_arrive(bar + B_OUT + b * 8); } };
      mainloop<128, 6, 8 / QP, 0>(acc, 16, false, r6, sb, wg, lane, rel, [&](auto ic) {
        constexpr int q = (ic.v - 1) * QP;
        if (q == 4) sent(0);
#pragma unroll
        for (int i = 4 * q; i < 4 * (q + QP); i++) vf[i] = movm(vf[i]);
#pragma unroll
        for (int i = q; i < q + QP; i++) sts128(xa + (wq == 3 ? -6144 : 2048) + (i >> 2) * BLK + (i & 3) * 512, kf[4 * i + 1], kf[4 * i + 3], vf[4 * i + 1], vf[4 * i + 3]);
      }, [&](int it) { if (it == 8 / QP + 1) sent(1); }, [&] {
        named_bar(2 + wg, 128);
        inbox(0);
      });
      const bool up0 = 2 * c > g, up1 = 2 * c + 1 > g;
      const uint32_t mup = (up0 ? 0xffffu : 0u) | (up1 ? 0xffff0000u : 0u);
#pragma unroll
      for (int b = 0; b < 2; b++) {
        float l[2][4], mx[4];
#pragma unroll
        for (int h = 0; h < 2; h++) {
          uint32_t q[8];
          const int k = 16 * b + 8 * h;
#pragma unroll
          for (int i = 0; i < 8; i++) q[i] = pack2(acc[2 * k + 2 * i], acc[2 * k + 2 * i + 1]);
          float s0[4], s1[4], s2[4];
          mma16z(s0, q[0], q[1], q[2], q[3], pv[k], pv[k + 1]); mma16z(s1, q[0], q[1], q[2], q[3], kf[k], kf[k + 2]); mma16z(s2, q[0], q[1], q[2], q[3], kf[k + 1], kf[k + 3]);
          mma16(s0, q[4], q[5], q[6], q[7], pv[k + 4], pv[k + 5]); mma16(s1, q[4], q[5], q[6], q[7], kf[k + 4], kf[k + 6]); mma16(s2, q[4], q[5], q[6], q[7], kf[k + 5], kf[k + 7]);
          if (first) { s0[0] = -INFINITY; s0[1] = -INFINITY; }
          l[h][0] = up0 ? s0[0] : s1[0]; l[h][1] = up1 ? s0[1] : s1[1]; l[h][2] = up0 ? s1[2] : s2[2]; l[h][3] = up1 ? s1[3] : s2[3];
          mx[2 * h] = fmaxf(l[h][0], l[h][1]); mx[2 * h + 1] = fmaxf(l[h][2], l[h][3]);
        }
#pragma unroll
        for (int o = 1; o < 4; o <<= 1) {
#pragma unroll
          for (int h = 0; h < 4; h++) mx[h] = fmaxf(mx[h], __shfl_xor_sync(~0u, mx[h], o));
        }
#pragma unroll
        for (int h = 0; h < 2; h++) {
          const float m0 = mx[2 * h], m1 = mx[2 * h + 1];
          const uint32_t pa = pack2(ex2((l[h][0] - m0) * SCL), ex2((l[h][1] - m0) * SCL)), pb = pack2(ex2((l[h][2] - m1) * SCL), ex2((l[h][3] - m1) * SCL));
          float sm[4];
          mma8z(sm, pa, pb, 0x3f803f80u);
          const float ia = rcp(sm[0]), ib = rcp(sm[2]);
#pragma unroll
          for (int i = 8 * b + 4 * h; i < 8 * b + 4 * h + 4; i += 2) {
            uint32_t of[4];
#pragma unroll
            for (int d = 0; d < 2; d++) {
              float o[4];
              mma16z(o, pa & ~mup, pb & mup, 0u, pb & ~mup, vf[2 * (i + d)], vf[2 * (i + d) + 1]);
              mma8(o, pa & mup, 0u, pv[2 * i + 2 + d]);
              of[2 * d] = pack2(o[0] * ia, o[1] * ia); of[2 * d + 1] = pack2(o[2] * ib, o[3] * ib);
            }
            stsm4(stg_row + b * BLK + ((((i & 7) + (lane >> 4)) ^ (lane & 7)) << 4), of[0], of[1], of[2], of[3]);
          }
        }
        stage_done(sb, wg, b, lane);
        if (b == 0) inbox(1);
      }
      named_bar(1, 256);
    }
    uint32_t pk[64];
    {
      float acc[64];
      mainloop<128, 6, 0, 0>(acc, 16, true, r6, sb, wg, lane, rel, none, none, [&] {
        mbar_wait(bar + B_MOD, 0); mbar_wait(fre + 8, 1);
        load_vec(pk + 32, sb, 2, 0, lane); load_vec(pk + 40, sb, 2, 1, lane);
#pragma unroll
        for (int i = 0; i < 32; i++) { pk[i] = xk[i]; asm volatile("" : "+r"(pk[i])); }
      });
#pragma unroll
      for (int i = 0; i < 32; i++) {
        acc[2 * i] = fmaf(acc[2 * i], bf_lo(pk[32 + (i >> 1)]), bf_lo(pk[i]));
        acc[2 * i + 1] = fmaf(acc[2 * i + 1], bf_hi(pk[32 + (i >> 1)]), bf_hi(pk[i]));
      }
      ln_publish(acc, gs->stat + (16 + m) * 1024, j, row0, lane, ep);
      mbar_wait(bar + B_FULL6 + 16, 1);
      if (lane < 2) mbar_arrive_cl(rel + B_EMPTY6 + 16);
      ring_next<6>(r6);
#pragma unroll
      for (int i = 0; i < 32; i++) { pk[i] = pack2(acc[2 * i], acc[2 * i + 1]); pk[32 + i] = 0; }
      ln_apply(acc, gs->stat + (16 + m) * 1024, row0, ep, sb, 3, 4, stg_row, wg, lane);
      named_bar(1, 256);
    }
    auto swiglu = [&](int q, int uo, int par) {
      if ((q & 3) == 0 && par >= 0) mbar_wait(fre + 2 * q, par);
      uint32_t w[4];
#pragma unroll
      for (int u = 0; u < 4; u++) w[u] = silu_mul2(pk[4 * q + u], pk[uo + 4 * q + u]);
      stsm4(stg_row + (q >> 2) * BLK + ((((2 * q & 7) + (lane >> 4)) ^ (lane & 7)) << 4), w[0], w[1], w[2], w[3]);
    };
    r4.s = r4.wrap = 2;
#pragma unroll 1
    for (int t = 0; t < 3; t++) {
      float acc[128];
      mainloop<256, 4, 4, 1>(acc, 16, t == 0, r4, sb, wg, lane, rel, [&](auto ic) {
        if (t) {
          if (ic.v == 3) stage_done(sb, wg, 0, lane);
          swiglu(2 * ic.v - 2, 32, ~t & 1); swiglu(2 * ic.v - 1, 32, 0);
        }
      }, [&](int it) {
        if (t && it == 5) stage_done(sb, wg, 1, lane);
        if (t == 0 && it >= 8) {
          uint4* p = gs->x1 + bid * 2048 + ((it >> 2) & 1) * 1024 + warp * 128 + (it & 3) * 32 + lane;
#pragma unroll
          for (int i = 0; i < 8; i++)
            asm volatile("{\n.reg .pred p;\nsetp.eq.u32 p, %5, %6;\n@p st.global.v4.u32 [%0], {%1,%2,%3,%4};\n}" :: "l"(p), "r"(pk[4 * i]), "r"(pk[4 * i + 1]), "r"(pk[4 * i + 2]), "r"(pk[4 * i + 3]), "r"(it), "r"(8 + i) : "memory");
        }
      }, [&] { if (t == 0) fence_async_global(); else if (t == 2) mbar_wait(bar + B_X, 1); }, t & 1);
#pragma unroll
      for (int i = 0; i < 64; i++) pk[i] = pack2(acc[2 * i], acc[2 * i + 1]);
    }
    uint32_t x1[32];
    {
      float acc[64];
      mainloop<128, 6, 10, 1>(acc, 16, false, r6, sb, wg, lane, rel, [&](auto ic) {
        constexpr int b = ic.v > 5, q = ic.v - 5 * b;
        if (q == 1) {
          if (b) stage_done(sb, wg, 0, lane);
#pragma unroll
          for (int i = 4 * b; i < 4 * b + 4; i++) { const uint4 x = lds128(sb + STG + b * BLK + warp * 2048 + (i & 3) * 512 + lane * 16); x1[4 * i] = x.x; x1[4 * i + 1] = x.y; x1[4 * i + 2] = x.z; x1[4 * i + 3] = x.w; }
          __syncwarp();
        } else swiglu(4 * b + q - 2, 32, -1);
      }, [&](int it) { if (it == 11) stage_done(sb, wg, 1, lane); }, [] {}, 1);
#pragma unroll
      for (int i = 0; i < 32; i++) pk[i] = pack2(acc[2 * i], acc[2 * i + 1]);
    }
    {
      float acc[64];
      mainloop<128, 6, 4, TAILLAG>(acc, 56, false, r6, sb, wg, lane, rel, [&](auto ic) { swiglu(ic.v - 1, 16, 1); },
                                   [&](int it) { if (it == 5) stage_done(sb, wg, 0, lane); }, [&] {
        load_vec(pk + 32, sb, 5, 0, lane); load_vec(pk + 40, sb, 5, 1, lane);
        mbar_wait(fre, 0); mbar_wait(fre + 8, 1);
      }, 0);
      __syncwarp();
      cl_arrive_relaxed();
#pragma unroll
      for (int i = 0; i < 16; i += 2) {
        uint32_t w[4];
#pragma unroll
        for (int u = 0; u < 4; u++) {
          const int q = 2 * i + u;
          w[u] = hfma2(pack2(acc[2 * q], acc[2 * q + 1]), pk[32 + (q >> 1)], x1[q]);
        }
        stsm4(stg_row + (i >> 3) * BLK + ((((i & 7) + (lane >> 4)) ^ (lane & 7)) << 4), w[0], w[1], w[2], w[3]);
        if ((i & 7) == 6) {
          fence_async_smem();
          __syncwarp();
          if (elect()) { tma_store_3d(&maps.out, sb + STG + (i >> 3) * BLK + warp * 2048, j * 128 + (i >> 3) * 64, m * 64 + wq * 16, wg); if (i > 8) bulk_commit(); }
        }
      }
      bulk_wait_read();
      if (tid == 0) gs->epoch[blockIdx.x] = ep;
      cl_wait();
    }
  }
}

typedef CUresult (*EncodeFn)(CUtensorMap*, CUtensorMapDataType, cuuint32_t, void*, const cuuint64_t*, const cuuint64_t*, const cuuint32_t*, const cuuint32_t*,
                             CUtensorMapInterleave, CUtensorMapSwizzle, CUtensorMapL2promotion, CUtensorMapFloatOOBfill);

void make_map(EncodeFn fn, CUtensorMap* mp, const void* base, uint64_t d0, uint64_t d1, uint64_t d2, uint64_t s1, uint64_t s2, uint32_t b2, uint32_t b0 = 64, uint32_t b1 = 64) {
  cuuint64_t d[3] = {d0, d1, d2}, s[2] = {s1, s2};
  cuuint32_t b[3] = {b0, b1, b2}, e[3] = {1, 1, 1};
  fn(mp, CU_TENSOR_MAP_DATA_TYPE_BFLOAT16, 3, (void*)base, d, s, b, e, CU_TENSOR_MAP_INTERLEAVE_NONE, b0 == 64 ? CU_TENSOR_MAP_SWIZZLE_128B : CU_TENSOR_MAP_SWIZZLE_NONE,
     CU_TENSOR_MAP_L2_PROMOTION_L2_128B, CU_TENSOR_MAP_FLOAT_OOB_FILL_NONE);
}

__global__ void probe_kernel() {}
int max_clusters(int size) {
  cudaLaunchConfig_t cfg = {};
  cudaLaunchAttribute at;
  at.id = cudaLaunchAttributeClusterDimension; at.val.clusterDim.x = size; at.val.clusterDim.y = 1; at.val.clusterDim.z = 1;
  cfg.gridDim = dim3(size * 66); cfg.blockDim = dim3(384); cfg.dynamicSmemBytes = SMEM_BYTES; cfg.attrs = &at; cfg.numAttrs = 1;
  int n = 0;
  if (cudaOccupancyMaxActiveClusters(&n, probe_kernel, &cfg) != cudaSuccess) { cudaGetLastError(); return 0; }
  return n;
}

}

extern "C" void kernel_launch(void* const* d_in, const int* in_sizes, int n_in, void* d_out, int out_size) {
  static EncodeFn fn = nullptr;
  static int by_sm = 0;
  static Scratch* gs = nullptr;
  if (!fn) {
    void* p = nullptr; cudaDriverEntryPointQueryResult q;
    cudaGetDriverEntryPoint("cuTensorMapEncodeTiled", &p, cudaEnableDefault, &q);
    fn = (EncodeFn)p;
    cudaFuncSetAttribute(fused_kernel, cudaFuncAttributeMaxDynamicSharedMemorySize, SMEM_BYTES);
    int dev = 0, sms = 0;
    cudaGetSymbolAddress((void**)&gs, g_scratch);
    cudaGetDevice(&dev);
    cudaDeviceGetAttribute(&sms, cudaDevAttrMultiProcessorCount, dev);
    cudaFuncSetAttribute(probe_kernel, cudaFuncAttributeMaxDynamicSharedMemorySize, SMEM_BYTES);
    if (sms == 132 && max_clusters(2) == 66) {
      const int c4 = max_clusters(4), c6 = max_clusters(6), c8 = max_clusters(8);
      by_sm = c4 == 30 && c6 == 17 && c8 == 15 ? 1 : c8 == 16 ? 2 : 0;
    }
  }
  Maps mp;
  make_map(fn, &mp.x, d_in[0], D_, S_ / 2, 2, 4096, 2048, 2);
  make_map(fn, &mp.out, d_out, D_, S_ / 2, 2, 4096, 2048, 1, 64, 16);
  make_map(fn, &mp.wqkv, d_in[1], 64, D_, 3 * D_ / 64, 3 * D_ * 2, 128, 2);
  make_map(fn, &mp.wo, d_in[2], 64, D_, D_ / 64, D_ * 2, 128, 2);
  make_map(fn, &mp.w1, d_in[4], 64, D_, F_ / 64, F_ * 2, 128, 2);
  make_map(fn, &mp.w3, d_in[5], 64, D_, F_ / 64, F_ * 2, 128, 2);
  make_map(fn, &mp.w1s, d_in[4], 64, D_, F_ / 64, F_ * 2, 128, 1);
  make_map(fn, &mp.w3s, d_in[5], 64, D_, F_ / 64, F_ * 2, 128, 1);
  make_map(fn, &mp.w2, d_in[6], 64, F_, D_ / 64, D_ * 2, 128, 2);
  make_map(fn, &mp.wmod, d_in[8], 256, D_, 24, 6 * D_ * 2, 512, 1, 256);
  fused_kernel<<<132, 384, SMEM_BYTES>>>((const bf16*)d_in[7], (const bf16*)d_in[8], gs, by_sm, mp);
}
```
